```python
import torch

def _softmax(x, axis=-1):
    return torch.softmax(x, dim=axis)
def _gelu(x):
    return torch.nn.functional.gelu(x, approximate="tanh")
def _silu(x):
    return torch.nn.functional.silu(x)
def _sigmoid(x):
    return torch.sigmoid(x)
def _layernorm(x, axis=-1, eps=1e-5):
    m = x.mean(dim=axis, keepdim=True)
    v = x.var(dim=axis, keepdim=True, unbiased=False)
    return (x - m) / torch.sqrt(v + eps)
def _scatter_add(tgt, idx, src, axis=0):
    return tgt.clone().index_add_(axis, idx, src)
def _segment_sum(src, seg, n):
    out = torch.zeros((n,) + src.shape[1:], dtype=src.dtype)
    return out.index_add_(0, seg, src)
def _pad(x, pw):
    flat = tuple(v for pair in reversed(pw) for v in pair)
    return torch.nn.functional.pad(x, flat)

kernel_name = 'sequential_preLN__ssm_conv_s4__glu_gated_bilinear__prompt'

def setup_inputs():

    _w = (lambda a: (lambda t: t.to(torch.bfloat16) if t.is_floating_point() else t)(torch.as_tensor(a)))
    def _A_setup():
        B, L, D, N = 1, 2048, 448, 256
        A_re = -(lambda _x: torch.exp(torch.as_tensor(_x)))((lambda *s: torch.randn(*s, dtype=torch.bfloat16) * 3.2)(D, N))
        A_im = torch.pi * (lambda *s: torch.randn(*s, dtype=torch.bfloat16) * 0.05)(D, N)
        B_re = (lambda *s: torch.randn(*s, dtype=torch.bfloat16) * 0.05)(D, N)
        B_im = (lambda *s: torch.randn(*s, dtype=torch.bfloat16) * 0.05)(D, N)
        C_re = (lambda *s: torch.randn(*s, dtype=torch.bfloat16) * 0.05)(D, N)
        C_im = (lambda *s: torch.randn(*s, dtype=torch.bfloat16) * 0.05)(D, N)
        log_dt = (lambda *s: torch.randn(*s, dtype=torch.bfloat16) * 0.05)(D) * 0.5 - 4.0
        Dskip = (lambda *s: torch.randn(*s, dtype=torch.bfloat16) * 0.05)(D)
        return {
            "u": _w((lambda *s: torch.randn(*s, dtype=torch.bfloat16) * 0.05)(B, L, D)),
            "A_re": _w(A_re),
            "A_im": _w(A_im),
            "B_re": _w(B_re),
            "B_im": _w(B_im),
            "C_re": _w(C_re),
            "C_im": _w(C_im),
            "log_dt": _w(log_dt),
            "Dskip": _w(Dskip),
        }
    _A_in = _A_setup()

    def _B_setup():
        B, S, D, F = 1, 2048, 448, 1792
        return {
            "x": _w((lambda *s: torch.randn(*s, dtype=torch.bfloat16) * 0.05)(B, S, D)),
            "w_gate": _w((lambda *s: torch.randn(*s, dtype=torch.bfloat16) * 0.4)(D, F) * (D ** -0.5)),
            "w_up": _w((lambda *s: torch.randn(*s, dtype=torch.bfloat16) * 0.4)(D, F) * (D ** -0.5)),
            "w_down": _w((lambda *s: torch.randn(*s, dtype=torch.bfloat16) * 0.4)(F, D) * (F ** -0.5)),
        }
    _B_in = _B_setup()

    return {
        "A_u": _A_in["u"],
        "A_A_re": _A_in["A_re"],
        "A_A_im": _A_in["A_im"],
        "A_B_re": _A_in["B_re"],
        "A_B_im": _A_in["B_im"],
        "A_C_re": _A_in["C_re"],
        "A_C_im": _A_in["C_im"],
        "A_log_dt": _A_in["log_dt"],
        "A_Dskip": _A_in["Dskip"],
        "B_x": _B_in["x"],
        "B_w_gate": _B_in["w_gate"],
        "B_w_up": _B_in["w_up"],
        "B_w_down": _B_in["w_down"],
    }

def reference(A_u, A_A_re, A_A_im, A_B_re, A_B_im, A_C_re, A_C_im, A_log_dt, A_Dskip, B_x, B_w_gate, B_w_up, B_w_down):
    def _A_ref(u, A_re, A_im, B_re, B_im, C_re, C_im, log_dt, Dskip):
        Bsz, L, D = u.shape
        dt = torch.exp(log_dt)[:, None]
        A = A_re + 1j * A_im
        Bc = B_re + 1j * B_im
        Cc = C_re + 1j * C_im
        logdA = dt * A
        dB = dt * Bc
        l = (lambda x, dt: x.to(dt))(torch.arange(L), A_re.dtype)
        P = torch.exp(logdA[:, :, None] * l[None, None, :])
        K = torch.einsum("dn,dnl,dn->dl", Cc, P, dB).real
        L2 = 2 * L
        Kp = _pad(K, ((0, 0), (0, L)))
        up = (lambda x, *d: x.permute(*d))(u, 0, 2, 1)
        up = _pad(up, ((0, 0), (0, 0), (0, L)))
        Kf = (lambda x, axes=(-2,-1): torch.fft.rfft2(x.float(), dim=axes))(Kp[:, None, :], axes=(-2, -1))
        Uf = (lambda x, axes=(-2,-1): torch.fft.rfft2(x.float(), dim=axes))(up[:, :, None, :], axes=(-2, -1))
        Yf = Uf * Kf[None, :, :, :]
        y = (lambda x, s, axes=(-2,-1): torch.fft.irfft2(x, s=s, dim=axes).to(torch.bfloat16))(Yf, (1, L2), axes=(-2, -1))[:, :, 0, :L]
        y = (lambda x, *d: x.permute(*d))(y, 0, 2, 1) + u * Dskip[None, None, :]
        return y

    def _B_ref(x, w_gate, w_up, w_down):
        g = torch.einsum("bsd,df->bsf", x, w_gate)
        u = torch.einsum("bsd,df->bsf", x, w_up)
        h = g * u
        return torch.einsum("bsf,fd->bsd", h, w_down)

    x = A_u
    h = x + _A_ref(_layernorm(x, axis=-1), A_A_re, A_A_im, A_B_re, A_B_im, A_C_re, A_C_im, A_log_dt, A_Dskip)
    h2 = h + _B_ref(_layernorm(h, axis=-1), B_w_gate, B_w_up, B_w_down)
    return h2
```

```cpp
#include <cuda_runtime.h>
#include <cuda_bf16.h>
#include <cuda.h>
#include <stdint.h>

constexpr int LSEQ = 2048, DM = 448, FF = 1792, NST = 256;

__device__ uint4    g_himg[16 * 114688 / 16];
__device__ float    g_colsum[2 * FF];
__device__ uint4    g_part[16 * 8 * 8 * 14336 / 16];
__device__ unsigned g_flags[16 * 8 * 8 * 2];
__device__ __nv_bfloat16 g_u[LSEQ * DM];
__device__ float    g_kd[DM * 2064];

__device__ __forceinline__ uint32_t s2u(const void* p) { return (uint32_t)__cvta_generic_to_shared(p); }
__device__ __forceinline__ void mbar_init(uint32_t b, int c) { asm volatile("mbarrier.init.shared::cta.b64 [%0], %1;" ::"r"(b), "r"(c)); }
__device__ __forceinline__ void mbar_expect(uint32_t b, int bytes) { asm volatile("mbarrier.arrive.expect_tx.shared::cta.b64 _, [%0], %1;" ::"r"(b), "r"(bytes) : "memory"); }
__device__ __forceinline__ void mbar_arrive(uint32_t b) { asm volatile("mbarrier.arrive.shared::cta.b64 _, [%0];" ::"r"(b) : "memory"); }
__device__ __forceinline__ void mbar_wait(uint32_t b, int ph) {
  asm volatile("{\n.reg .pred p;\nLW:\nmbarrier.try_wait.parity.shared::cta.b64 p, [%0], %1;\n@p bra LD;\nbra LW;\nLD:\n}" ::"r"(b), "r"(ph) : "memory");
}
__device__ __forceinline__ uint64_t mkdesc(uint32_t addr, uint32_t lbo, uint32_t sbo, uint32_t sw) {
  return (uint64_t)((addr & 0x3FFFF) >> 4) | ((uint64_t)((lbo >> 4) & 0x3FFF) << 16) | ((uint64_t)((sbo >> 4) & 0x3FFF) << 32) | ((uint64_t)sw << 62);
}
__device__ __forceinline__ void wg_fence() { asm volatile("wgmma.fence.sync.aligned;" ::: "memory"); }
__device__ __forceinline__ void wg_commit() { asm volatile("wgmma.commit_group.sync.aligned;" ::: "memory"); }
template <int N> __device__ __forceinline__ void wg_wait() { asm volatile("wgmma.wait_group.sync.aligned %0;" ::"n"(N) : "memory"); }
template <int N> __device__ __forceinline__ void reg_fence(float (&a)[N]) {
#pragma unroll
  for (int i = 0; i < N; i++) asm volatile("" : "+f"(a[i])::"memory");
}
__device__ __forceinline__ uint32_t pack_bf16(float lo, float hi) {
  uint32_t r; asm("cvt.rn.bf16x2.f32 %0, %1, %2;" : "=r"(r) : "f"(hi), "f"(lo)); return r;
}
__device__ __forceinline__ float bf_lo(uint32_t v) { return __uint_as_float(v << 16); }
__device__ __forceinline__ float bf_hi(uint32_t v) { return __uint_as_float(v & 0xFFFF0000u); }
__device__ __forceinline__ float rbf(float x) { return __bfloat162float(__float2bfloat16_rn(x)); }
__device__ __forceinline__ uint32_t hmul2_bf(uint32_t a, uint32_t b) { uint32_t r; asm("mul.rn.bf16x2 %0, %1, %2;" : "=r"(r) : "r"(a), "r"(b)); return r; }
__device__ __forceinline__ uint32_t hadd2_bf(uint32_t a, uint32_t b) { uint32_t r; asm("add.rn.bf16x2 %0, %1, %2;" : "=r"(r) : "r"(a), "r"(b)); return r; }
__device__ __forceinline__ void tma3d(uint32_t dst, const CUtensorMap* m, int c0, int c1, int c2, uint32_t bar) {
  asm volatile("cp.async.bulk.tensor.3d.shared::cluster.global.mbarrier::complete_tx::bytes [%0], [%1, {%3, %4, %5}], [%2];"
               ::"r"(dst), "l"(m), "r"(bar), "r"(c0), "r"(c1), "r"(c2) : "memory");
}
__device__ __forceinline__ void tma2d(uint32_t dst, const CUtensorMap* m, int c0, int c1, uint32_t bar) {
  asm volatile("cp.async.bulk.tensor.2d.shared::cluster.global.mbarrier::complete_tx::bytes [%0], [%1, {%3, %4}], [%2];"
               ::"r"(dst), "l"(m), "r"(bar), "r"(c0), "r"(c1) : "memory");
}
__device__ __forceinline__ void bulk_ld(uint32_t dst, const void* src, int bytes, uint32_t bar) {
  asm volatile("cp.async.bulk.shared::cluster.global.mbarrier::complete_tx::bytes [%0], [%1], %2, [%3];"
               ::"r"(dst), "l"(src), "r"(bytes), "r"(bar) : "memory");
}

__device__ __forceinline__ void wgmma_ss256(float (&d)[128], uint64_t a, uint64_t b, int acc) {
  asm volatile("{\n.reg .pred p;\nsetp.ne.b32 p, %130, 0;\n"
    "wgmma.mma_async.sync.aligned.m64n256k16.f32.bf16.bf16 {%0,%1,%2,%3,%4,%5,%6,%7,%8,%9,%10,%11,%12,%13,%14,%15,%16,%17,%18,%19,%20,%21,%22,%23,%24,%25,%26,%27,%28,%29,%30,%31,%32,%33,%34,%35,%36,%37,%38,%39,%40,%41,%42,%43,%44,%45,%46,%47,%48,%49,%50,%51,%52,%53,%54,%55,%56,%57,%58,%59,%60,%61,%62,%63,%64,%65,%66,%67,%68,%69,%70,%71,%72,%73,%74,%75,%76,%77,%78,%79,%80,%81,%82,%83,%84,%85,%86,%87,%88,%89,%90,%91,%92,%93,%94,%95,%96,%97,%98,%99,%100,%101,%102,%103,%104,%105,%106,%107,%108,%109,%110,%111,%112,%113,%114,%115,%116,%117,%118,%119,%120,%121,%122,%123,%124,%125,%126,%127}, %128, %129, p, 1, 1, 1, 1;\n}\n"
    : "+f"(d[0]),"+f"(d[1]),"+f"(d[2]),"+f"(d[3]),"+f"(d[4]),"+f"(d[5]),"+f"(d[6]),"+f"(d[7]),"+f"(d[8]),"+f"(d[9]),"+f"(d[10]),"+f"(d[11]),"+f"(d[12]),"+f"(d[13]),"+f"(d[14]),"+f"(d[15]),"+f"(d[16]),"+f"(d[17]),"+f"(d[18]),"+f"(d[19]),"+f"(d[20]),"+f"(d[21]),"+f"(d[22]),"+f"(d[23]),"+f"(d[24]),"+f"(d[25]),"+f"(d[26]),"+f"(d[27]),"+f"(d[28]),"+f"(d[29]),"+f"(d[30]),"+f"(d[31]),"+f"(d[32]),"+f"(d[33]),"+f"(d[34]),"+f"(d[35]),"+f"(d[36]),"+f"(d[37]),"+f"(d[38]),"+f"(d[39]),"+f"(d[40]),"+f"(d[41]),"+f"(d[42]),"+f"(d[43]),"+f"(d[44]),"+f"(d[45]),"+f"(d[46]),"+f"(d[47]),"+f"(d[48]),"+f"(d[49]),"+f"(d[50]),"+f"(d[51]),"+f"(d[52]),"+f"(d[53]),"+f"(d[54]),"+f"(d[55]),"+f"(d[56]),"+f"(d[57]),"+f"(d[58]),"+f"(d[59]),"+f"(d[60]),"+f"(d[61]),"+f"(d[62]),"+f"(d[63]),"+f"(d[64]),"+f"(d[65]),"+f"(d[66]),"+f"(d[67]),"+f"(d[68]),"+f"(d[69]),"+f"(d[70]),"+f"(d[71]),"+f"(d[72]),"+f"(d[73]),"+f"(d[74]),"+f"(d[75]),"+f"(d[76]),"+f"(d[77]),"+f"(d[78]),"+f"(d[79]),"+f"(d[80]),"+f"(d[81]),"+f"(d[82]),"+f"(d[83]),"+f"(d[84]),"+f"(d[85]),"+f"(d[86]),"+f"(d[87]),"+f"(d[88]),"+f"(d[89]),"+f"(d[90]),"+f"(d[91]),"+f"(d[92]),"+f"(d[93]),"+f"(d[94]),"+f"(d[95]),"+f"(d[96]),"+f"(d[97]),"+f"(d[98]),"+f"(d[99]),"+f"(d[100]),"+f"(d[101]),"+f"(d[102]),"+f"(d[103]),"+f"(d[104]),"+f"(d[105]),"+f"(d[106]),"+f"(d[107]),"+f"(d[108]),"+f"(d[109]),"+f"(d[110]),"+f"(d[111]),"+f"(d[112]),"+f"(d[113]),"+f"(d[114]),"+f"(d[115]),"+f"(d[116]),"+f"(d[117]),"+f"(d[118]),"+f"(d[119]),"+f"(d[120]),"+f"(d[121]),"+f"(d[122]),"+f"(d[123]),"+f"(d[124]),"+f"(d[125]),"+f"(d[126]),"+f"(d[127])
    : "l"(a), "l"(b), "r"(acc));
}
__device__ __forceinline__ void wgmma_ss192(float (&d)[96], uint64_t a, uint64_t b, int acc) {
  asm volatile("{\n.reg .pred p;\nsetp.ne.b32 p, %98, 0;\n"
    "wgmma.mma_async.sync.aligned.m64n192k16.f32.bf16.bf16 {%0,%1,%2,%3,%4,%5,%6,%7,%8,%9,%10,%11,%12,%13,%14,%15,%16,%17,%18,%19,%20,%21,%22,%23,%24,%25,%26,%27,%28,%29,%30,%31,%32,%33,%34,%35,%36,%37,%38,%39,%40,%41,%42,%43,%44,%45,%46,%47,%48,%49,%50,%51,%52,%53,%54,%55,%56,%57,%58,%59,%60,%61,%62,%63,%64,%65,%66,%67,%68,%69,%70,%71,%72,%73,%74,%75,%76,%77,%78,%79,%80,%81,%82,%83,%84,%85,%86,%87,%88,%89,%90,%91,%92,%93,%94,%95}, %96, %97, p, 1, 1, 1, 1;\n}\n"
    : "+f"(d[0]),"+f"(d[1]),"+f"(d[2]),"+f"(d[3]),"+f"(d[4]),"+f"(d[5]),"+f"(d[6]),"+f"(d[7]),"+f"(d[8]),"+f"(d[9]),"+f"(d[10]),"+f"(d[11]),"+f"(d[12]),"+f"(d[13]),"+f"(d[14]),"+f"(d[15]),"+f"(d[16]),"+f"(d[17]),"+f"(d[18]),"+f"(d[19]),"+f"(d[20]),"+f"(d[21]),"+f"(d[22]),"+f"(d[23]),"+f"(d[24]),"+f"(d[25]),"+f"(d[26]),"+f"(d[27]),"+f"(d[28]),"+f"(d[29]),"+f"(d[30]),"+f"(d[31]),"+f"(d[32]),"+f"(d[33]),"+f"(d[34]),"+f"(d[35]),"+f"(d[36]),"+f"(d[37]),"+f"(d[38]),"+f"(d[39]),"+f"(d[40]),"+f"(d[41]),"+f"(d[42]),"+f"(d[43]),"+f"(d[44]),"+f"(d[45]),"+f"(d[46]),"+f"(d[47]),"+f"(d[48]),"+f"(d[49]),"+f"(d[50]),"+f"(d[51]),"+f"(d[52]),"+f"(d[53]),"+f"(d[54]),"+f"(d[55]),"+f"(d[56]),"+f"(d[57]),"+f"(d[58]),"+f"(d[59]),"+f"(d[60]),"+f"(d[61]),"+f"(d[62]),"+f"(d[63]),"+f"(d[64]),"+f"(d[65]),"+f"(d[66]),"+f"(d[67]),"+f"(d[68]),"+f"(d[69]),"+f"(d[70]),"+f"(d[71]),"+f"(d[72]),"+f"(d[73]),"+f"(d[74]),"+f"(d[75]),"+f"(d[76]),"+f"(d[77]),"+f"(d[78]),"+f"(d[79]),"+f"(d[80]),"+f"(d[81]),"+f"(d[82]),"+f"(d[83]),"+f"(d[84]),"+f"(d[85]),"+f"(d[86]),"+f"(d[87]),"+f"(d[88]),"+f"(d[89]),"+f"(d[90]),"+f"(d[91]),"+f"(d[92]),"+f"(d[93]),"+f"(d[94]),"+f"(d[95])
    : "l"(a), "l"(b), "r"(acc));
}
__device__ __forceinline__ void wgmma_rs56(float (&d)[28], uint32_t a0, uint32_t a1, uint32_t a2, uint32_t a3, uint64_t b, int acc) {
  asm volatile("{\n.reg .pred p;\nsetp.ne.b32 p, %33, 0;\n"
    "wgmma.mma_async.sync.aligned.m64n56k16.f32.bf16.bf16 {%0,%1,%2,%3,%4,%5,%6,%7,%8,%9,%10,%11,%12,%13,%14,%15,%16,%17,%18,%19,%20,%21,%22,%23,%24,%25,%26,%27}, {%28,%29,%30,%31}, %32, p, 1, 1, 1;\n}\n"
    : "+f"(d[0]),"+f"(d[1]),"+f"(d[2]),"+f"(d[3]),"+f"(d[4]),"+f"(d[5]),"+f"(d[6]),"+f"(d[7]),"+f"(d[8]),"+f"(d[9]),"+f"(d[10]),"+f"(d[11]),"+f"(d[12]),"+f"(d[13]),"+f"(d[14]),"+f"(d[15]),"+f"(d[16]),"+f"(d[17]),"+f"(d[18]),"+f"(d[19]),"+f"(d[20]),"+f"(d[21]),"+f"(d[22]),"+f"(d[23]),"+f"(d[24]),"+f"(d[25]),"+f"(d[26]),"+f"(d[27])
    : "r"(a0), "r"(a1), "r"(a2), "r"(a3), "l"(b), "r"(acc));
}

__global__ void k_ln1(const __nv_bfloat16* __restrict__ x) {
  int row = blockIdx.x * 8 + threadIdx.x / 32, lane = threadIdx.x & 31;
  float v[14]; float s = 0;
  for (int i = 0; i < 14; i++) { v[i] = __bfloat162float(x[row * DM + lane + 32 * i]); s += v[i]; }
  for (int o = 16; o; o >>= 1) s += __shfl_xor_sync(~0u, s, o);
  float mean = s / DM, q = 0;
  for (int i = 0; i < 14; i++) q += (v[i] - mean) * (v[i] - mean);
  for (int o = 16; o; o >>= 1) q += __shfl_xor_sync(~0u, q, o);
  float m = rbf(mean), sd = rbf(sqrtf(rbf(rbf(q / DM) + 1e-5f)));
  for (int i = 0; i < 14; i++) g_u[row * DM + lane + 32 * i] = __float2bfloat16_rn(rbf(v[i] - m) / sd);
  if (blockIdx.x == 0) for (int i = threadIdx.x; i < 2048; i += 256) g_flags[i] = 0;
}
__global__ void k_kgen(const __nv_bfloat16* are, const __nv_bfloat16* aim, const __nv_bfloat16* bre, const __nv_bfloat16* bim,
                       const __nv_bfloat16* cre, const __nv_bfloat16* cim, const __nv_bfloat16* logdt) {
  int d = blockIdx.x;
  float dt = rbf(expf(__bfloat162float(logdt[d])));
  for (int l = threadIdx.x; l < 2048; l += blockDim.x) {
    float lf = rbf((float)l), acc = 0;
    for (int n = 0; n < NST; n++) {
      int i = d * NST + n;
      float lr = dt * __bfloat162float(are[i]), li = dt * __bfloat162float(aim[i]);
      float br = dt * __bfloat162float(bre[i]), bi = dt * __bfloat162float(bim[i]);
      float cr = __bfloat162float(cre[i]), ci = __bfloat162float(cim[i]);
      float wr = cr * br - ci * bi, wi = cr * bi + ci * br;
      float e = expf(lr * lf), sn, cs; sincosf(li * lf, &sn, &cs);
      acc += e * (wr * cs - wi * sn);
    }
    g_kd[d * 2064 + l] = acc;
  }
}
__global__ void k_conv(const __nv_bfloat16* __restrict__ x, const __nv_bfloat16* dskip) {
  __shared__ float sk[2048], su[2048];
  int d = blockIdx.x;
  for (int i = threadIdx.x; i < 2048; i += blockDim.x) { sk[i] = g_kd[d * 2064 + i]; su[i] = __bfloat162float(g_u[i * DM + d]); }
  __syncthreads();
  float ds = __bfloat162float(dskip[d]);
  for (int t = threadIdx.x; t < 2048; t += blockDim.x) {
    float acc = 0;
    for (int l = 0; l <= t; l++) acc += sk[l] * su[t - l];
    float yb = rbf(rbf(acc) + rbf(su[t] * ds));
    float h = rbf(__bfloat162float(x[t * DM + d]) + yb);
    int tau = t >> 3, rt = tau >> 4, mh = (tau >> 3) & 1, c = tau & 7, r = d & 7;
    size_t off = (size_t)rt * 114688 + (d >> 3) * 2048 + mh * 1024 + r * 128 + ((c ^ r) * 16) + (t & 7) * 2;
    *(__nv_bfloat16*)((char*)g_himg + off) = __float2bfloat16_rn(h);
  }
}
__global__ void k_colsum(const __nv_bfloat16* wg, const __nv_bfloat16* wu) {
  int f = blockIdx.x * blockDim.x + threadIdx.x;
  const __nv_bfloat16* w = f < FF ? wg : wu; int ff = f < FF ? f : f - FF;
  float s = 0; for (int d = 0; d < DM; d++) s += __bfloat162float(w[d * FF + ff]);
  g_colsum[f] = s;
}

constexpr int B_SA = 0, B_RING = 114688, B_SLOT = 16384, B_NSLOT = 6;
constexpr int B_STAT = B_RING + B_NSLOT * B_SLOT;
constexpr int B_CS = B_STAT + 1024;
constexpr int B_RED = B_CS + 1792;
constexpr int B_BAR = B_RED + 6144;
constexpr int B_SMEM = B_BAR + 512;

__global__ void __launch_bounds__(384, 1)
k_ffn(const __grid_constant__ CUtensorMap mg4, const __grid_constant__ CUtensorMap mu4,
      const __grid_constant__ CUtensorMap mg3, const __grid_constant__ CUtensorMap mu3,
      const __grid_constant__ CUtensorMap mdn, __nv_bfloat16* __restrict__ out) {
  extern __shared__ __align__(1024) unsigned char sm[];
  const uint32_t sb = s2u(sm);
  const int tid = threadIdx.x, wg = tid >> 7, warp = tid >> 5, lane = tid & 31;
  const int j = blockIdx.x >> 4, rt = blockIdx.x & 15;
  const uint32_t bar_full = sb + B_BAR, bar_empty = bar_full + 48, bar_h = bar_full + 96, bar_stat = bar_full + 152, bar_pub = bar_full + 160;
  if (tid == 0) {
    for (int i = 0; i < B_NSLOT; i++) { mbar_init(bar_full + 8 * i, 1); mbar_init(bar_empty + 8 * i, 2); }
    for (int i = 0; i < 7; i++) mbar_init(bar_h + 8 * i, 1);
    mbar_init(bar_stat, 96);
    for (int i = 0; i < 14; i++) mbar_init(bar_pub + 8 * i, 128);
    asm volatile("fence.mbarrier_init.release.cluster;" ::: "memory");
  }
  __syncthreads();

  if (wg == 2) {
    asm volatile("setmaxnreg.dec.sync.aligned.u32 88;");
    if (warp == 8) {
      if (lane == 0) {
        for (int s = 0; s < 44; s++) {
          int slot = s % B_NSLOT, ph = (s / B_NSLOT) & 1;
          if (s == B_NSLOT) {
            asm volatile("griddepcontrol.wait;" ::: "memory");
            for (int p = 0; p < 7; p++) {
              mbar_expect(bar_h + 8 * p, 16384);
              bulk_ld(sb + B_SA + p * 16384, (const char*)g_himg + (size_t)rt * 114688 + p * 16384, 16384, bar_h + 8 * p);
            }
          }
          if (s >= B_NSLOT) mbar_wait(bar_empty + 8 * slot, ph ^ 1);
          uint32_t dst = sb + B_RING + slot * B_SLOT, fb = bar_full + 8 * slot;
          if (s < 14) {
            mbar_expect(fb, 16384);
            tma3d(dst, &mg4, 0, 32 * s, 7 * j, fb);
            tma3d(dst + 8192, &mu4, 0, 32 * s, 7 * j, fb);
          } else if (s < 28) {
            mbar_expect(fb, 12288);
            tma3d(dst, &mg3, 0, 32 * (s - 14), 7 * j + 4, fb);
            tma3d(dst + 6144, &mu3, 0, 32 * (s - 14), 7 * j + 4, fb);
          } else {
            int cc = (s - 28) >> 1, hf = (s - 28) & 1, c = (j + 1 + cc) & 7;
            mbar_expect(fb, 14336);
            tma2d(dst, &mdn, 56 * c, 224 * j + 112 * hf, fb);
          }
        }
      }
    } else {
      const int t96 = tid - 288;
      asm volatile("griddepcontrol.wait;" ::: "memory");
      float* cs = (float*)(sm + B_CS);
      for (int i = t96; i < 448; i += 96) cs[i] = __ldcg(&g_colsum[(i >= 224 ? FF - 224 : 0) + 224 * j + i]);
      const int c16 = t96 & 15, dg = t96 >> 4, mh = c16 >> 3, c = c16 & 7;
      float x0[8], s1[8], s2[8];
      mbar_wait(bar_h, 0);
      {
        uint4 v = *(const uint4*)(sm + B_SA + mh * 1024 + c * 16);
        x0[0] = bf_lo(v.x); x0[1] = bf_hi(v.x); x0[2] = bf_lo(v.y); x0[3] = bf_hi(v.y);
        x0[4] = bf_lo(v.z); x0[5] = bf_hi(v.z); x0[6] = bf_lo(v.w); x0[7] = bf_hi(v.w);
      }
#pragma unroll
      for (int i = 0; i < 8; i++) { s1[i] = 0.f; s2[i] = 0.f; }
      int k = dg;
      for (int p = 0; p < 7; p++) {
        mbar_wait(bar_h + 8 * p, 0);
        for (; k < 64 * (p + 1); k += 6) {
          int r = k & 7;
          uint4 v = *(const uint4*)(sm + B_SA + (k >> 3) * 2048 + mh * 1024 + r * 128 + ((c ^ r) << 4));
          float e[8] = {bf_lo(v.x), bf_hi(v.x), bf_lo(v.y), bf_hi(v.y), bf_lo(v.z), bf_hi(v.z), bf_lo(v.w), bf_hi(v.w)};
#pragma unroll
          for (int i = 0; i < 8; i++) { float dlt = e[i] - x0[i]; s1[i] += dlt; s2[i] = fmaf(dlt, dlt, s2[i]); }
        }
      }
      float2* red = (float2*)(sm + B_RED);
#pragma unroll
      for (int i = 0; i < 8; i++) red[dg * 128 + c16 * 8 + i] = make_float2(s1[i], s2[i]);
      asm volatile("bar.sync 1, 96;" ::: "memory");
      for (int l = t96; l < 128; l += 96) {
        float a = 0.f, b = 0.f;
#pragma unroll
        for (int g = 0; g < 6; g++) { float2 v = red[g * 128 + l]; a += v.x; b += v.y; }
        float xx = __bfloat162float(*(const __nv_bfloat16*)(sm + B_SA + (l >> 6) * 1024 + (l & 63) * 2));
        float dm = a * (1.f / DM);
        float var = fmaxf(b * (1.f / DM) - dm * dm, 0.f);
        float m = rbf(xx + dm), sd = rbf(sqrtf(rbf(rbf(var) + 1e-5f)));
        ((float2*)(sm + B_STAT))[l] = make_float2(m, 1.f / sd);
      }
      mbar_arrive(bar_stat);
      if (warp <= 10 && lane == 0) {
        const int w = warp - 9;
        for (int cc = 0; cc < 7; cc++) {
          mbar_wait(bar_pub + 8 * (w * 7 + cc), 0);
          asm volatile("fence.acq_rel.gpu;" ::: "memory");
          int c2 = (j + 1 + cc) & 7;
          asm volatile("st.relaxed.gpu.global.u32 [%0], %1;" ::"l"(&g_flags[((rt * 8 + c2) * 8 + j) * 2 + w]), "r"(1u) : "memory");
        }
      }
    }
  } else {
    asm volatile("setmaxnreg.inc.sync.aligned.u32 208;");
    const int g = lane >> 2, t = lane & 3, wq = warp & 3;
    uint32_t hh[56];
    const float* cs = (const float*)(sm + B_CS);
    float m0, r0, m1, r1;
    int s = 0;
    {
      float acc[128];
      for (int st = 0; st < 14; st++, s++) {
        int slot = s % B_NSLOT, ph = (s / B_NSLOT) & 1;
        if (!(st & 1)) mbar_wait(bar_h + 8 * (st >> 1), 0);
        mbar_wait(bar_full + 8 * slot, ph);
        wg_fence();
#pragma unroll
        for (int kk = 0; kk < 2; kk++)
          wgmma_ss256(acc, mkdesc(sb + B_SA + (2 * st + kk) * 4096 + wg * 1024, 0, 2048, 1),
                      mkdesc(sb + B_RING + slot * B_SLOT + kk * 1024, 2048, 512, 2), (st | kk) != 0);
        wg_commit();
        if (st > 0) { wg_wait<1>(); if ((tid & 127) == 0) mbar_arrive(bar_empty + 8 * ((s - 1) % B_NSLOT)); }
      }
      mbar_wait(bar_stat, 0);
      {
        float2 a = ((const float2*)(sm + B_STAT))[wg * 64 + wq * 16 + g], b = ((const float2*)(sm + B_STAT))[wg * 64 + wq * 16 + g + 8];
        m0 = -a.x; r0 = a.y; m1 = -b.x; r1 = b.y;
      }
      wg_wait<0>();
      reg_fence(acc);
      if ((tid & 127) == 0) mbar_arrive(bar_empty + 8 * ((s - 1) % B_NSLOT));
#pragma unroll
      for (int i = 0; i < 16; i++) {
        float2 cg = *(const float2*)(cs + 8 * i + 2 * t), cu = *(const float2*)(cs + 224 + 8 * i + 2 * t);
        uint32_t g0 = pack_bf16(fmaf(m0, cg.x, acc[4 * i]) * r0, fmaf(m0, cg.y, acc[4 * i + 1]) * r0);
        uint32_t g1 = pack_bf16(fmaf(m1, cg.x, acc[4 * i + 2]) * r1, fmaf(m1, cg.y, acc[4 * i + 3]) * r1);
        uint32_t u0 = pack_bf16(fmaf(m0, cu.x, acc[64 + 4 * i]) * r0, fmaf(m0, cu.y, acc[64 + 4 * i + 1]) * r0);
        uint32_t u1 = pack_bf16(fmaf(m1, cu.x, acc[64 + 4 * i + 2]) * r1, fmaf(m1, cu.y, acc[64 + 4 * i + 3]) * r1);
        hh[2 * i] = hmul2_bf(g0, u0); hh[2 * i + 1] = hmul2_bf(g1, u1);
      }
    }
    {
      float acc[96];
      for (int st = 0; st < 14; st++, s++) {
        int slot = s % B_NSLOT, ph = (s / B_NSLOT) & 1;
        mbar_wait(bar_full + 8 * slot, ph);
        wg_fence();
#pragma unroll
        for (int kk = 0; kk < 2; kk++)
          wgmma_ss192(acc, mkdesc(sb + B_SA + (2 * st + kk) * 4096 + wg * 1024, 0, 2048, 1),
                      mkdesc(sb + B_RING + slot * B_SLOT + kk * 1024, 2048, 512, 2), (st | kk) != 0);
        wg_commit();
        if (st > 0) { wg_wait<1>(); if ((tid & 127) == 0) mbar_arrive(bar_empty + 8 * ((s - 1) % B_NSLOT)); }
      }
      wg_wait<0>();
      reg_fence(acc);
      if ((tid & 127) == 0) mbar_arrive(bar_empty + 8 * ((s - 1) % B_NSLOT));
#pragma unroll
      for (int i = 0; i < 12; i++) {
        float2 cg = *(const float2*)(cs + 128 + 8 * i + 2 * t), cu = *(const float2*)(cs + 224 + 128 + 8 * i + 2 * t);
        uint32_t g0 = pack_bf16(fmaf(m0, cg.x, acc[4 * i]) * r0, fmaf(m0, cg.y, acc[4 * i + 1]) * r0);
        uint32_t g1 = pack_bf16(fmaf(m1, cg.x, acc[4 * i + 2]) * r1, fmaf(m1, cg.y, acc[4 * i + 3]) * r1);
        uint32_t u0 = pack_bf16(fmaf(m0, cu.x, acc[48 + 4 * i]) * r0, fmaf(m0, cu.y, acc[48 + 4 * i + 1]) * r0);
        uint32_t u1 = pack_bf16(fmaf(m1, cu.x, acc[48 + 4 * i + 2]) * r1, fmaf(m1, cu.y, acc[48 + 4 * i + 3]) * r1);
        hh[32 + 2 * i] = hmul2_bf(g0, u0); hh[32 + 2 * i + 1] = hmul2_bf(g1, u1);
      }
    }
    float accA[28], accB[28];
    auto issue = [&](float (&acc)[28]) {
#pragma unroll
      for (int hf = 0; hf < 2; hf++, s++) {
        int slot = s % B_NSLOT, ph = (s / B_NSLOT) & 1;
        mbar_wait(bar_full + 8 * slot, ph);
        wg_fence();
#pragma unroll
        for (int kk = 0; kk < 7; kk++) {
          const int ks = hf * 7 + kk;
          wgmma_rs56(acc, hh[4 * ks], hh[4 * ks + 1], hh[4 * ks + 2], hh[4 * ks + 3],
                     mkdesc(sb + B_RING + slot * B_SLOT + kk * 2048, 0, 1024, 1), ks != 0);
        }
      }
      wg_commit();
    };
    auto send = [&](float (&acc)[28], int cc) {
      reg_fence(acc);
      if ((tid & 127) == 0) { int s0 = 28 + 2 * cc; mbar_arrive(bar_empty + 8 * (s0 % B_NSLOT)); mbar_arrive(bar_empty + 8 * ((s0 + 1) % B_NSLOT)); }
      int c2 = (j + 1 + cc) & 7;
      uint4* dst = g_part + (size_t)((rt * 8 + c2) * 8 + j) * 896 + wg * 448;
      uint32_t p[14];
#pragma unroll
      for (int i = 0; i < 14; i++) p[i] = pack_bf16(acc[2 * i], acc[2 * i + 1]);
#pragma unroll
      for (int q = 0; q < 3; q++) __stcg(dst + q * 128 + (tid & 127), make_uint4(p[4 * q], p[4 * q + 1], p[4 * q + 2], p[4 * q + 3]));
      __stcg((uint2*)(dst + 384) + (tid & 127), make_uint2(p[12], p[13]));
      mbar_arrive(bar_pub + 8 * (wg * 7 + cc));
    };
    issue(accA);
#pragma unroll
    for (int cp = 0; cp < 3; cp++) {
      issue(accB); wg_wait<1>(); send(accA, 2 * cp);
      issue(accA); wg_wait<1>(); send(accB, 2 * cp + 1);
    }
    issue(accB); wg_wait<1>(); send(accA, 6);
    {
      const unsigned* fl = &g_flags[((rt * 8 + j) * 8 + (lane & 7)) * 2 + wg];
      bool need = (lane < 8) && (lane != j);
      int it = 0;
      while (true) {
        unsigned v = 1;
        if (need) asm volatile("ld.acquire.gpu.global.u32 %0, [%1];" : "=r"(v) : "l"(fl) : "memory");
        if (__all_sync(~0u, v != 0) || ++it > 2000000) break;
      }
    }
#pragma unroll
    for (int i = 0; i < 28; i++) accA[i] = 0.f;
#pragma unroll
    for (int q = 1; q < 8; q++) {
      int src = (j + q) & 7;
      const uint4* p = g_part + (size_t)((rt * 8 + j) * 8 + src) * 896 + wg * 448;
      uint4 a = __ldcg(p + (tid & 127)), b = __ldcg(p + 128 + (tid & 127)), c = __ldcg(p + 256 + (tid & 127));
      uint2 d = __ldcg((const uint2*)(p + 384) + (tid & 127));
      uint32_t v[14] = {a.x, a.y, a.z, a.w, b.x, b.y, b.z, b.w, c.x, c.y, c.z, c.w, d.x, d.y};
#pragma unroll
      for (int i = 0; i < 14; i++) { accA[2 * i] += bf_lo(v[i]); accA[2 * i + 1] += bf_hi(v[i]); }
    }
    uint32_t hres[16];
#pragma unroll
    for (int i = 0; i < 4; i++) {
      int q = lane >> 3, r = lane & 7, kg = 7 * j + 2 * i + (q >> 1), c = 2 * wq + (q & 1);
      if (kg > 55) kg = 55;
      uint32_t addr = sb + B_SA + kg * 2048 + wg * 1024 + r * 128 + ((c ^ r) << 4);
      asm volatile("ldmatrix.sync.aligned.m8n8.x4.trans.shared.b16 {%0,%1,%2,%3}, [%4];"
                   : "=r"(hres[4 * i]), "=r"(hres[4 * i + 1]), "=r"(hres[4 * i + 2]), "=r"(hres[4 * i + 3]) : "r"(addr));
    }
    wg_wait<0>();
    reg_fence(accB);
    const int row = rt * 128 + wg * 64 + wq * 16 + g;
    uint32_t* o0 = (uint32_t*)(out + (size_t)row * DM + 56 * j + 2 * t);
    uint32_t* o1 = o0 + 8 * DM / 2;
#pragma unroll
    for (int i = 0; i < 7; i++) {
      o0[4 * i] = hadd2_bf(hres[2 * i], pack_bf16(accA[4 * i] + accB[4 * i], accA[4 * i + 1] + accB[4 * i + 1]));
      o1[4 * i] = hadd2_bf(hres[2 * i + 1], pack_bf16(accA[4 * i + 2] + accB[4 * i + 2], accA[4 * i + 3] + accB[4 * i + 3]));
    }
  }
}

typedef CUresult (*EncFn)(CUtensorMap*, CUtensorMapDataType, cuuint32_t, void*, const cuuint64_t*, const cuuint64_t*,
                          const cuuint32_t*, const cuuint32_t*, CUtensorMapInterleave, CUtensorMapSwizzle,
                          CUtensorMapL2promotion, CUtensorMapFloatOOBfill);

extern "C" void kernel_launch(void* const* d_in, const int* in_sizes, int n_in, void* d_out, int out_size) {
  const __nv_bfloat16* x = (const __nv_bfloat16*)d_in[0];
  const __nv_bfloat16 *are = (const __nv_bfloat16*)d_in[1], *aim = (const __nv_bfloat16*)d_in[2], *bre = (const __nv_bfloat16*)d_in[3],
                      *bim = (const __nv_bfloat16*)d_in[4], *cre = (const __nv_bfloat16*)d_in[5], *cim = (const __nv_bfloat16*)d_in[6],
                      *logdt = (const __nv_bfloat16*)d_in[7], *dskip = (const __nv_bfloat16*)d_in[8];
  const __nv_bfloat16 *wg = (const __nv_bfloat16*)d_in[10], *wu = (const __nv_bfloat16*)d_in[11], *wd = (const __nv_bfloat16*)d_in[12];

  static EncFn enc = nullptr;
  if (!enc) {
    void* fn = nullptr; cudaDriverEntryPointQueryResult qr;
    cudaGetDriverEntryPoint("cuTensorMapEncodeTiled", &fn, cudaEnableDefault, &qr);
    enc = (EncFn)fn;
    cudaFuncSetAttribute(k_ffn, cudaFuncAttributeMaxDynamicSharedMemorySize, B_SMEM);
  }
  CUtensorMap mg4, mu4, mg3, mu3, mdn;
  {
    cuuint64_t dims[3] = {32, DM, FF / 32}; cuuint64_t str[2] = {FF * 2, 64}; cuuint32_t es[3] = {1, 1, 1};
    cuuint32_t b4[3] = {32, 32, 4}, b3[3] = {32, 32, 3};
    enc(&mg4, CU_TENSOR_MAP_DATA_TYPE_BFLOAT16, 3, (void*)wg, dims, str, b4, es, CU_TENSOR_MAP_INTERLEAVE_NONE, CU_TENSOR_MAP_SWIZZLE_64B, CU_TENSOR_MAP_L2_PROMOTION_L2_256B, CU_TENSOR_MAP_FLOAT_OOB_FILL_NONE);
    enc(&mu4, CU_TENSOR_MAP_DATA_TYPE_BFLOAT16, 3, (void*)wu, dims, str, b4, es, CU_TENSOR_MAP_INTERLEAVE_NONE, CU_TENSOR_MAP_SWIZZLE_64B, CU_TENSOR_MAP_L2_PROMOTION_L2_256B, CU_TENSOR_MAP_FLOAT_OOB_FILL_NONE);
    enc(&mg3, CU_TENSOR_MAP_DATA_TYPE_BFLOAT16, 3, (void*)wg, dims, str, b3, es, CU_TENSOR_MAP_INTERLEAVE_NONE, CU_TENSOR_MAP_SWIZZLE_64B, CU_TENSOR_MAP_L2_PROMOTION_L2_256B, CU_TENSOR_MAP_FLOAT_OOB_FILL_NONE);
    enc(&mu3, CU_TENSOR_MAP_DATA_TYPE_BFLOAT16, 3, (void*)wu, dims, str, b3, es, CU_TENSOR_MAP_INTERLEAVE_NONE, CU_TENSOR_MAP_SWIZZLE_64B, CU_TENSOR_MAP_L2_PROMOTION_L2_256B, CU_TENSOR_MAP_FLOAT_OOB_FILL_NONE);
    cuuint64_t dd[2] = {DM, FF}; cuuint64_t sd[1] = {DM * 2}; cuuint32_t bd[2] = {64, 112};
    enc(&mdn, CU_TENSOR_MAP_DATA_TYPE_BFLOAT16, 2, (void*)wd, dd, sd, bd, es, CU_TENSOR_MAP_INTERLEAVE_NONE, CU_TENSOR_MAP_SWIZZLE_128B, CU_TENSOR_MAP_L2_PROMOTION_L2_256B, CU_TENSOR_MAP_FLOAT_OOB_FILL_NONE);
  }
  cudaStream_t st = cudaStreamPerThread;
  k_ln1<<<256, 256, 0, st>>>(x);
  k_kgen<<<DM, 512, 0, st>>>(are, aim, bre, bim, cre, cim, logdt);
  k_conv<<<DM, 512, 0, st>>>(x, dskip);
  k_colsum<<<2 * FF / 128, 128, 0, st>>>(wg, wu);
  k_ffn<<<128, 384, B_SMEM, st>>>(mg4, mu4, mg3, mu3, mdn, (__nv_bfloat16*)d_out);
}
```

```cpp
#include <cuda_runtime.h>
#include <cuda_bf16.h>
#include <stdint.h>

constexpr int LSEQ = 2048, DM = 448, FF = 1792, NST = 256;

__device__ uint4    g_himg[16 * 114688 / 16];
__device__ float    g_colsum[2 * FF];
__device__ uint4    g_part[16 * 8 * 8 * 1024];
__device__ uint4    g_wimg[8 * 602112 / 16];
__device__ unsigned g_epoch;
__device__ __nv_bfloat16 g_u[LSEQ * DM];
__device__ float    g_kd[DM * 2064];

#define TR(k, i) do {} while (0)
__device__ __forceinline__ uint32_t s2u(const void* p) { return (uint32_t)__cvta_generic_to_shared(p); }
__device__ __forceinline__ void mbar_init(uint32_t b, int c) { asm volatile("mbarrier.init.shared::cta.b64 [%0], %1;" ::"r"(b), "r"(c)); }
__device__ __forceinline__ void mbar_expect(uint32_t b, int bytes) { asm volatile("mbarrier.arrive.expect_tx.shared::cta.b64 _, [%0], %1;" ::"r"(b), "r"(bytes) : "memory"); }
__device__ __forceinline__ void mbar_arrive(uint32_t b) { asm volatile("mbarrier.arrive.shared::cta.b64 _, [%0];" ::"r"(b) : "memory"); }
__device__ __forceinline__ void mbar_wait(uint32_t b, int ph) {
  asm volatile("{\n.reg .pred p;\nLW:\nmbarrier.try_wait.parity.shared::cta.b64 p, [%0], %1;\n@p bra LD;\nbra LW;\nLD:\n}" ::"r"(b), "r"(ph) : "memory");
}
__device__ __forceinline__ uint64_t mkdesc(uint32_t addr, uint32_t lbo, uint32_t sbo, uint32_t sw) {
  return (uint64_t)((addr & 0x3FFFF) >> 4) | ((uint64_t)((lbo >> 4) & 0x3FFF) << 16) | ((uint64_t)((sbo >> 4) & 0x3FFF) << 32) | ((uint64_t)sw << 62);
}
__device__ __forceinline__ void wg_fence() { asm volatile("wgmma.fence.sync.aligned;" ::: "memory"); }
__device__ __forceinline__ void wg_commit() { asm volatile("wgmma.commit_group.sync.aligned;" ::: "memory"); }
template <int N> __device__ __forceinline__ void wg_wait() { asm volatile("wgmma.wait_group.sync.aligned %0;" ::"n"(N) : "memory"); }
template <int N> __device__ __forceinline__ void reg_fence(float (&a)[N]) {
#pragma unroll
  for (int i = 0; i < N; i++) asm volatile("" : "+f"(a[i])::"memory");
}
__device__ __forceinline__ uint32_t pack_bf16(float lo, float hi) {
  uint32_t r; asm("cvt.rn.bf16x2.f32 %0, %1, %2;" : "=r"(r) : "f"(hi), "f"(lo)); return r;
}
__device__ __forceinline__ float bf_lo(uint32_t v) { return __uint_as_float(v << 16); }
__device__ __forceinline__ float bf_hi(uint32_t v) { return __uint_as_float(v & 0xFFFF0000u); }
__device__ __forceinline__ float rbf(float x) { return __bfloat162float(__float2bfloat16_rn(x)); }
__device__ __forceinline__ uint32_t hmul2_bf(uint32_t a, uint32_t b) { uint32_t r; asm("mul.rn.bf16x2 %0, %1, %2;" : "=r"(r) : "r"(a), "r"(b)); return r; }
__device__ __forceinline__ uint32_t hadd2_bf(uint32_t a, uint32_t b) { uint32_t r; asm("add.rn.bf16x2 %0, %1, %2;" : "=r"(r) : "r"(a), "r"(b)); return r; }
__device__ __forceinline__ void bulk_ld(uint32_t dst, const void* src, int bytes, uint32_t bar) {
  asm volatile("cp.async.bulk.shared::cluster.global.mbarrier::complete_tx::bytes [%0], [%1], %2, [%3];"
               ::"r"(dst), "l"(src), "r"(bytes), "r"(bar) : "memory");
}

__device__ __forceinline__ void wgmma_ss224(float (&d)[112], uint64_t a, uint64_t b, int acc) {
  asm volatile("{\n.reg .pred p;\nsetp.ne.b32 p, %114, 0;\n"
    "wgmma.mma_async.sync.aligned.m64n224k16.f32.bf16.bf16 {%0,%1,%2,%3,%4,%5,%6,%7,%8,%9,%10,%11,%12,%13,%14,%15,%16,%17,%18,%19,%20,%21,%22,%23,%24,%25,%26,%27,%28,%29,%30,%31,%32,%33,%34,%35,%36,%37,%38,%39,%40,%41,%42,%43,%44,%45,%46,%47,%48,%49,%50,%51,%52,%53,%54,%55,%56,%57,%58,%59,%60,%61,%62,%63,%64,%65,%66,%67,%68,%69,%70,%71,%72,%73,%74,%75,%76,%77,%78,%79,%80,%81,%82,%83,%84,%85,%86,%87,%88,%89,%90,%91,%92,%93,%94,%95,%96,%97,%98,%99,%100,%101,%102,%103,%104,%105,%106,%107,%108,%109,%110,%111}, %112, %113, p, 1, 1, 1, 1;\n}\n"
    : "+f"(d[0]),"+f"(d[1]),"+f"(d[2]),"+f"(d[3]),"+f"(d[4]),"+f"(d[5]),"+f"(d[6]),"+f"(d[7]),"+f"(d[8]),"+f"(d[9]),"+f"(d[10]),"+f"(d[11]),"+f"(d[12]),"+f"(d[13]),"+f"(d[14]),"+f"(d[15]),"+f"(d[16]),"+f"(d[17]),"+f"(d[18]),"+f"(d[19]),"+f"(d[20]),"+f"(d[21]),"+f"(d[22]),"+f"(d[23]),"+f"(d[24]),"+f"(d[25]),"+f"(d[26]),"+f"(d[27]),"+f"(d[28]),"+f"(d[29]),"+f"(d[30]),"+f"(d[31]),"+f"(d[32]),"+f"(d[33]),"+f"(d[34]),"+f"(d[35]),"+f"(d[36]),"+f"(d[37]),"+f"(d[38]),"+f"(d[39]),"+f"(d[40]),"+f"(d[41]),"+f"(d[42]),"+f"(d[43]),"+f"(d[44]),"+f"(d[45]),"+f"(d[46]),"+f"(d[47]),"+f"(d[48]),"+f"(d[49]),"+f"(d[50]),"+f"(d[51]),"+f"(d[52]),"+f"(d[53]),"+f"(d[54]),"+f"(d[55]),"+f"(d[56]),"+f"(d[57]),"+f"(d[58]),"+f"(d[59]),"+f"(d[60]),"+f"(d[61]),"+f"(d[62]),"+f"(d[63]),"+f"(d[64]),"+f"(d[65]),"+f"(d[66]),"+f"(d[67]),"+f"(d[68]),"+f"(d[69]),"+f"(d[70]),"+f"(d[71]),"+f"(d[72]),"+f"(d[73]),"+f"(d[74]),"+f"(d[75]),"+f"(d[76]),"+f"(d[77]),"+f"(d[78]),"+f"(d[79]),"+f"(d[80]),"+f"(d[81]),"+f"(d[82]),"+f"(d[83]),"+f"(d[84]),"+f"(d[85]),"+f"(d[86]),"+f"(d[87]),"+f"(d[88]),"+f"(d[89]),"+f"(d[90]),"+f"(d[91]),"+f"(d[92]),"+f"(d[93]),"+f"(d[94]),"+f"(d[95]),"+f"(d[96]),"+f"(d[97]),"+f"(d[98]),"+f"(d[99]),"+f"(d[100]),"+f"(d[101]),"+f"(d[102]),"+f"(d[103]),"+f"(d[104]),"+f"(d[105]),"+f"(d[106]),"+f"(d[107]),"+f"(d[108]),"+f"(d[109]),"+f"(d[110]),"+f"(d[111])
    : "l"(a), "l"(b), "r"(acc));
}
__device__ __forceinline__ void wgmma_rs56(float (&d)[28], uint32_t a0, uint32_t a1, uint32_t a2, uint32_t a3, uint64_t b, int acc) {
  asm volatile("{\n.reg .pred p;\nsetp.ne.b32 p, %33, 0;\n"
    "wgmma.mma_async.sync.aligned.m64n56k16.f32.bf16.bf16 {%0,%1,%2,%3,%4,%5,%6,%7,%8,%9,%10,%11,%12,%13,%14,%15,%16,%17,%18,%19,%20,%21,%22,%23,%24,%25,%26,%27}, {%28,%29,%30,%31}, %32, p, 1, 1, 1;\n}\n"
    : "+f"(d[0]),"+f"(d[1]),"+f"(d[2]),"+f"(d[3]),"+f"(d[4]),"+f"(d[5]),"+f"(d[6]),"+f"(d[7]),"+f"(d[8]),"+f"(d[9]),"+f"(d[10]),"+f"(d[11]),"+f"(d[12]),"+f"(d[13]),"+f"(d[14]),"+f"(d[15]),"+f"(d[16]),"+f"(d[17]),"+f"(d[18]),"+f"(d[19]),"+f"(d[20]),"+f"(d[21]),"+f"(d[22]),"+f"(d[23]),"+f"(d[24]),"+f"(d[25]),"+f"(d[26]),"+f"(d[27])
    : "r"(a0), "r"(a1), "r"(a2), "r"(a3), "l"(b), "r"(acc));
}

__global__ void k_ln1(const __nv_bfloat16* __restrict__ x) {
  int row = blockIdx.x * 8 + threadIdx.x / 32, lane = threadIdx.x & 31;
  float v[14]; float s = 0;
  for (int i = 0; i < 14; i++) { v[i] = __bfloat162float(x[row * DM + lane + 32 * i]); s += v[i]; }
  for (int o = 16; o; o >>= 1) s += __shfl_xor_sync(~0u, s, o);
  float mean = s / DM, q = 0;
  for (int i = 0; i < 14; i++) q += (v[i] - mean) * (v[i] - mean);
  for (int o = 16; o; o >>= 1) q += __shfl_xor_sync(~0u, q, o);
  float m = rbf(mean), sd = rbf(sqrtf(rbf(rbf(q / DM) + 1e-5f)));
  for (int i = 0; i < 14; i++) g_u[row * DM + lane + 32 * i] = __float2bfloat16_rn(rbf(v[i] - m) / sd);
  if (blockIdx.x == 0 && threadIdx.x == 0) g_epoch = g_epoch + 1;
}
__global__ void k_kgen(const __nv_bfloat16* are, const __nv_bfloat16* aim, const __nv_bfloat16* bre, const __nv_bfloat16* bim,
                       const __nv_bfloat16* cre, const __nv_bfloat16* cim, const __nv_bfloat16* logdt) {
  int d = blockIdx.x;
  float dt = rbf(expf(__bfloat162float(logdt[d])));
  for (int l = threadIdx.x; l < 2048; l += blockDim.x) {
    float lf = rbf((float)l), acc = 0;
    for (int n = 0; n < NST; n++) {
      int i = d * NST + n;
      float lr = dt * __bfloat162float(are[i]), li = dt * __bfloat162float(aim[i]);
      float br = dt * __bfloat162float(bre[i]), bi = dt * __bfloat162float(bim[i]);
      float cr = __bfloat162float(cre[i]), ci = __bfloat162float(cim[i]);
      float wr = cr * br - ci * bi, wi = cr * bi + ci * br;
      float e = expf(lr * lf), sn, cs; sincosf(li * lf, &sn, &cs);
      acc += e * (wr * cs - wi * sn);
    }
    g_kd[d * 2064 + l] = acc;
  }
}
__global__ void k_conv(const __nv_bfloat16* __restrict__ x, const __nv_bfloat16* dskip) {
  __shared__ float sk[2048], su[2048];
  int d = blockIdx.x;
  for (int i = threadIdx.x; i < 2048; i += blockDim.x) { sk[i] = g_kd[d * 2064 + i]; su[i] = __bfloat162float(g_u[i * DM + d]); }
  __syncthreads();
  float ds = __bfloat162float(dskip[d]);
  for (int t = threadIdx.x; t < 2048; t += blockDim.x) {
    float acc = 0;
    for (int l = 0; l <= t; l++) acc += sk[l] * su[t - l];
    float yb = rbf(rbf(acc) + rbf(su[t] * ds));
    float h = rbf(__bfloat162float(x[t * DM + d]) + yb);
    int tau = t >> 3, rt = tau >> 4, mh = (tau >> 3) & 1, c = tau & 7, r = d & 7;
    size_t off = (size_t)rt * 114688 + (d >> 3) * 2048 + mh * 1024 + r * 128 + ((c ^ r) * 16) + (t & 7) * 2;
    *(__nv_bfloat16*)((char*)g_himg + off) = __float2bfloat16_rn(h);
  }
}
__global__ void k_colsum(const __nv_bfloat16* wg, const __nv_bfloat16* wu) {
  int f = blockIdx.x * blockDim.x + threadIdx.x;
  const __nv_bfloat16* w = f < FF ? wg : wu; int ff = f < FF ? f : f - FF;
  float s = 0; for (int d = 0; d < DM; d++) s += __bfloat162float(w[d * FF + ff]);
  g_colsum[f] = s;
}

__global__ void k_pack(const uint4* __restrict__ wg, const uint4* __restrict__ wu, const uint4* __restrict__ wd) {
  int i = blockIdx.x * blockDim.x + threadIdx.x;
  int mat = i / 100352, e = i % 100352;
  if (mat < 2) {
    int d = e / 224, ngg = e % 224;
    int j = ngg / 28, q = (ngg % 28) / 14, ng = ngg % 14 + 14 * mat;
    g_wimg[(size_t)j * 37632 + (q * 14 + (d >> 5)) * 896 + ng * 32 + (d & 31)] = (mat ? wu : wg)[e];
  } else {
    int f = e / 56, ngg = e % 56;
    int j = f / 224, hf = (f % 224) / 112, k = f % 112, c = ngg / 7, ng = ngg % 7;
    g_wimg[(size_t)j * 37632 + 25088 + (c * 2 + hf) * 784 + ng * 112 + k] = wd[e];
  }
}

constexpr int B_SA = 0, B_RING = 114688, B_SLOT = 14336, B_NSLOT = 7;
constexpr int B_STAT = B_RING + B_NSLOT * B_SLOT;
constexpr int B_CS = B_STAT + 1024;
constexpr int B_RED = B_CS + 1792;
constexpr int B_BAR = B_RED + 4096;
constexpr int B_SMEM = B_BAR + 512;

__device__ __forceinline__ void st128(uint4* p, uint32_t a, uint32_t b, uint32_t c, uint32_t d) {
  asm volatile("{\n.reg .b128 v;\n.reg .b64 lo, hi;\nmov.b64 lo, {%1, %2};\nmov.b64 hi, {%3, %4};\nmov.b128 v, {lo, hi};\n"
               "st.relaxed.gpu.global.b128 [%0], v;\n}" ::"l"(p), "r"(a), "r"(b), "r"(c), "r"(d) : "memory");
}
__device__ __forceinline__ void ld128(const uint4* p, uint32_t* r) {
  asm volatile("{\n.reg .b128 v;\n.reg .b64 lo, hi;\nld.relaxed.gpu.global.b128 v, [%4];\nmov.b128 {lo, hi}, v;\n"
               "mov.b64 {%0, %1}, lo;\nmov.b64 {%2, %3}, hi;\n}" : "=r"(r[0]), "=r"(r[1]), "=r"(r[2]), "=r"(r[3]) : "l"(p) : "memory");
}

__global__ void __launch_bounds__(384, 1) k_ffn(__nv_bfloat16* __restrict__ out) {
  extern __shared__ __align__(1024) unsigned char sm[];
  const uint32_t sb = s2u(sm);
  const int tid = threadIdx.x, wg = tid >> 7, warp = tid >> 5, lane = tid & 31;
  const int j = blockIdx.x >> 4, rt = blockIdx.x & 15;
  const uint32_t bar_full = sb + B_BAR, bar_empty = bar_full + 64, bar_h = bar_full + 128, bar_cs = bar_full + 192;
  if (tid == 0) {
    TR(1, 0);
    for (int i = 0; i < B_NSLOT; i++) { mbar_init(bar_full + 8 * i, 1); mbar_init(bar_empty + 8 * i, 2); }
    for (int i = 0; i < 7; i++) mbar_init(bar_h + 8 * i, 1);
    mbar_init(bar_cs, 1);
    asm volatile("fence.mbarrier_init.release.cluster;" ::: "memory");
  }
  __syncthreads();

  if (wg == 2) {
    asm volatile("setmaxnreg.dec.sync.aligned.u32 40;");
    if (warp == 8 && lane == 0) {
      const char* wsrc = (const char*)g_wimg + (size_t)j * 602112;
      asm volatile("griddepcontrol.wait;" ::: "memory");
      TR(1, 1);
      int slot = 0, ph = 0;
      for (int s = 0; s < 44; s++) {
        if (s >= B_NSLOT) mbar_wait(bar_empty + 8 * slot, ph ^ 1);
        uint32_t dst = sb + B_RING + slot * B_SLOT, fb = bar_full + 8 * slot;
        if (s < 28) {
          mbar_expect(fb, 14336);
          bulk_ld(dst, wsrc + s * 14336, 14336, fb);
        } else {
          int c = (j + 1 + ((s - 28) >> 1)) & 7;
          mbar_expect(fb, 12544);
          bulk_ld(dst, wsrc + 401408 + (c * 2 + (s & 1)) * 12544, 12544, fb);
        }
        if (++slot == B_NSLOT) { slot = 0; ph ^= 1; }
      }
    } else if (warp == 9 && lane == 0) {
      asm volatile("griddepcontrol.wait;" ::: "memory");
      for (int p = 0; p < 7; p++) {
        mbar_expect(bar_h + 8 * p, 16384);
        bulk_ld(sb + B_SA + p * 16384, (const char*)g_himg + (size_t)rt * 114688 + p * 16384, 16384, bar_h + 8 * p);
      }
      mbar_expect(bar_cs, 1792);
      bulk_ld(sb + B_CS, g_colsum + 224 * j, 896, bar_cs);
      bulk_ld(sb + B_CS + 896, g_colsum + FF + 224 * j, 896, bar_cs);
    }
  } else {
    asm volatile("setmaxnreg.inc.sync.aligned.u32 232;");
    const int g = lane >> 2, t = lane & 3, wq = warp & 3, t128 = tid & 127;
    uint32_t hh[56];
    const float* cs = (const float*)(sm + B_CS);
    float m0, r0, m1, r1;
    int slot = 0, ph = 0, pslot = 0;
    asm volatile("griddepcontrol.wait;" ::: "memory");
    const uint32_t tag = (__ldcg(&g_epoch) & 0xFFFFu) << 16;
#pragma unroll
    for (int q = 0; q < 2; q++) {
      float acc[112];
      float s1[8], s2[8];
      const unsigned char* sp = sm + B_SA + wg * 1024 + (t128 >> 6) * 2048 + ((t128 >> 3) & 7) * 128 + (((t128 ^ (t128 >> 3)) & 7) << 4);
      if (q == 0) {
#pragma unroll
        for (int i = 0; i < 8; i++) { s1[i] = 0.f; s2[i] = 0.f; }
      }
#pragma unroll 1
      for (int st = 0; st < 14; st++) {
        if (q == 0 && !(st & 1)) mbar_wait(bar_h + 8 * (st >> 1), 0);
        mbar_wait(bar_full + 8 * slot, ph);
        wg_fence();
#pragma unroll
        for (int kk = 0; kk < 2; kk++)
          wgmma_ss224(acc, mkdesc(sb + B_SA + (2 * st + kk) * 4096 + wg * 1024, 0, 2048, 1),
                      mkdesc(sb + B_RING + slot * B_SLOT + kk * 256, 128, 512, 0), (st | kk) != 0);
        wg_commit();
        if (q == 0 && st == 0 && tid == 0) TR(1, 3);
        if (q == 0) {
          if (st >= 1 && st <= 7) {
            mbar_wait(bar_h + 8 * (st - 1), 0);
#pragma unroll
            for (int i = 0; i < 4; i++) {
              uint4 v = *(const uint4*)(sp + (st - 1) * 16384 + i * 4096);
              float e[8] = {bf_lo(v.x), bf_hi(v.x), bf_lo(v.y), bf_hi(v.y), bf_lo(v.z), bf_hi(v.z), bf_lo(v.w), bf_hi(v.w)};
#pragma unroll
              for (int k = 0; k < 8; k++) { s1[k] += e[k]; s2[k] = fmaf(e[k], e[k], s2[k]); }
            }
          } else if (st == 8) {
#pragma unroll
            for (int k = 0; k < 8; k++) {
              s1[k] += __shfl_xor_sync(~0u, s1[k], 8); s2[k] += __shfl_xor_sync(~0u, s2[k], 8);
              s1[k] += __shfl_xor_sync(~0u, s1[k], 16); s2[k] += __shfl_xor_sync(~0u, s2[k], 16);
            }
            if (lane < 8) {
              float4* red = (float4*)(sm + B_RED + wg * 2048 + wq * 512 + lane * 64);
#pragma unroll
              for (int k = 0; k < 4; k++) red[k] = make_float4(s1[2 * k], s2[2 * k], s1[2 * k + 1], s2[2 * k + 1]);
            }
          } else if (st == 9) {
            asm volatile("bar.sync %0, 128;" ::"r"(1 + wg) : "memory");
            if (t128 < 64) {
              float a = 0.f, b = 0.f;
#pragma unroll
              for (int w = 0; w < 4; w++) { float2 v = *(const float2*)(sm + B_RED + wg * 2048 + w * 512 + t128 * 8); a += v.x; b += v.y; }
              float mean = a * (1.f / DM);
              float var = fmaxf(fmaf(-mean, mean, b * (1.f / DM)), 0.f);
              float sd = rbf(sqrtf(rbf(rbf(var) + 1e-5f)));
              ((float2*)(sm + B_STAT))[wg * 64 + t128] = make_float2(rbf(mean), 1.f / sd);
            }
          } else if (st == 10) {
            asm volatile("bar.sync %0, 128;" ::"r"(1 + wg) : "memory");
            mbar_wait(bar_cs, 0);
          }
        }
        if (st > 0) { wg_wait<1>(); if (t128 == 0) mbar_arrive(bar_empty + 8 * pslot); }
        pslot = slot;
        if (++slot == B_NSLOT) { slot = 0; ph ^= 1; }
      }
      if (q == 0) {
        float2 a = ((const float2*)(sm + B_STAT))[wg * 64 + wq * 16 + g], b = ((const float2*)(sm + B_STAT))[wg * 64 + wq * 16 + g + 8];
        m0 = -a.x; r0 = a.y; m1 = -b.x; r1 = b.y;
        if (tid == 0) TR(1, 4);
      }
      wg_wait<0>();
      reg_fence(acc);
      if (t128 == 0) mbar_arrive(bar_empty + 8 * pslot);
#pragma unroll
      for (int i = 0; i < 14; i++) {
        float2 cg = *(const float2*)(cs + 112 * q + 8 * i + 2 * t), cu = *(const float2*)(cs + 224 + 112 * q + 8 * i + 2 * t);
        uint32_t g0 = pack_bf16(fmaf(m0, cg.x, acc[4 * i]) * r0, fmaf(m0, cg.y, acc[4 * i + 1]) * r0);
        uint32_t g1 = pack_bf16(fmaf(m1, cg.x, acc[4 * i + 2]) * r1, fmaf(m1, cg.y, acc[4 * i + 3]) * r1);
        uint32_t u0 = pack_bf16(fmaf(m0, cu.x, acc[56 + 4 * i]) * r0, fmaf(m0, cu.y, acc[56 + 4 * i + 1]) * r0);
        uint32_t u1 = pack_bf16(fmaf(m1, cu.x, acc[56 + 4 * i + 2]) * r1, fmaf(m1, cu.y, acc[56 + 4 * i + 3]) * r1);
        hh[28 * q + 2 * i] = hmul2_bf(g0, u0); hh[28 * q + 2 * i + 1] = hmul2_bf(g1, u1);
      }
      if (tid == 0) TR(1, 5 + q);
    }
    float accA[28], accB[28], sum[28];
    uint32_t inA[16], inB[16];
    unsigned pend = 0;
#pragma unroll
    for (int i = 0; i < 28; i++) sum[i] = 0.f;
    auto issue = [&](float (&acc)[28], int cc) {
#pragma unroll
      for (int hf = 0; hf < 2; hf++) {
        const int s = 28 + 2 * cc + hf, sl = s % B_NSLOT;
        mbar_wait(bar_full + 8 * sl, (s / B_NSLOT) & 1);
        wg_fence();
#pragma unroll
        for (int kk = 0; kk < 7; kk++) {
          const int ks = hf * 7 + kk;
          wgmma_rs56(acc, hh[4 * ks], hh[4 * ks + 1], hh[4 * ks + 2], hh[4 * ks + 3],
                     mkdesc(sb + B_RING + sl * B_SLOT + kk * 256, 128, 1792, 0), ks != 0);
        }
      }
      wg_commit();
    };
    auto send = [&](float (&acc)[28], int cc) {
      reg_fence(acc);
      if (t128 == 0) { const int s0 = 28 + 2 * cc; mbar_arrive(bar_empty + 8 * (s0 % B_NSLOT)); mbar_arrive(bar_empty + 8 * ((s0 + 1) % B_NSLOT)); }
      uint4* dst = g_part + (size_t)((rt * 8 + ((j + 1 + cc) & 7)) * 8 + j) * 1024 + wg * 512 + t128;
#pragma unroll
      for (int q = 0; q < 4; q++)
        st128(dst + q * 128, pack_bf16(acc[7 * q], acc[7 * q + 1]), pack_bf16(acc[7 * q + 2], acc[7 * q + 3]),
              pack_bf16(acc[7 * q + 4], acc[7 * q + 5]), (pack_bf16(acc[7 * q + 6], 0.f) & 0xFFFFu) | tag);
    };
    auto fetch = [&](uint32_t (&in)[16], int q) {
      const uint4* p = g_part + (size_t)((rt * 8 + j) * 8 + ((j + 7 - q) & 7)) * 1024 + wg * 512 + t128;
#pragma unroll
      for (int i = 0; i < 4; i++) ld128(p + i * 128, in + 4 * i);
    };
    auto valid = [&](uint32_t (&in)[16]) {
      bool ok = (((in[3] ^ tag) | (in[7] ^ tag) | (in[11] ^ tag) | (in[15] ^ tag)) & 0xFFFF0000u) == 0;
      return __all_sync(~0u, ok) != 0;
    };
    auto accum = [&](uint32_t (&in)[16]) {
#pragma unroll
      for (int q = 0; q < 4; q++) {
        sum[7 * q] += bf_lo(in[4 * q]); sum[7 * q + 1] += bf_hi(in[4 * q]);
        sum[7 * q + 2] += bf_lo(in[4 * q + 1]); sum[7 * q + 3] += bf_hi(in[4 * q + 1]);
        sum[7 * q + 4] += bf_lo(in[4 * q + 2]); sum[7 * q + 5] += bf_hi(in[4 * q + 2]);
        sum[7 * q + 6] += bf_lo(in[4 * q + 3]);
      }
    };
    auto consume = [&](uint32_t (&in)[16], int q) { if (valid(in)) accum(in); else pend |= 1u << q; };
    issue(accA, 0);
    issue(accB, 1); wg_wait<1>(); send(accA, 0);
    issue(accA, 2); wg_wait<1>(); send(accB, 1); fetch(inA, 0);
    issue(accB, 3); wg_wait<1>(); send(accA, 2); fetch(inB, 1); consume(inA, 0);
    issue(accA, 4); wg_wait<1>(); send(accB, 3); fetch(inA, 2); consume(inB, 1);
    issue(accB, 5); wg_wait<1>(); send(accA, 4); fetch(inB, 3); consume(inA, 2);
    issue(accA, 6); wg_wait<1>(); send(accB, 5); fetch(inA, 4); consume(inB, 3);
    issue(accB, 7); wg_wait<1>(); send(accA, 6); fetch(inB, 5); consume(inA, 4);
    if (tid == 0) TR(1, 7);
    uint32_t hres[16];
#pragma unroll
    for (int i = 0; i < 4; i++) {
      int q = lane >> 3, r = lane & 7, kg = 7 * j + 2 * i + (q >> 1), c = 2 * wq + (q & 1);
      if (kg > 55) kg = 55;
      uint32_t addr = sb + B_SA + kg * 2048 + wg * 1024 + r * 128 + ((c ^ r) << 4);
      asm volatile("ldmatrix.sync.aligned.m8n8.x4.trans.shared.b16 {%0,%1,%2,%3}, [%4];"
                   : "=r"(hres[4 * i]), "=r"(hres[4 * i + 1]), "=r"(hres[4 * i + 2]), "=r"(hres[4 * i + 3]) : "r"(addr));
    }
    consume(inB, 5);
    pend |= 64u;
    if (tid == 0) TR(1, 8);
#pragma unroll 1
    for (int q = 0; q < 7; q++) {
      if ((pend >> q) & 1) {
        int it = 0;
        do { fetch(inA, q); } while (!valid(inA) && ++it < 200000);
        accum(inA);
      }
    }
    wg_wait<0>();
    reg_fence(accB);
    if (tid == 0) TR(1, 9);
    const int row = rt * 128 + wg * 64 + wq * 16 + g;
    uint32_t* o0 = (uint32_t*)(out + (size_t)row * DM + 56 * j + 2 * t);
    uint32_t* o1 = o0 + 8 * DM / 2;
#pragma unroll
    for (int i = 0; i < 7; i++) {
      o0[4 * i] = hadd2_bf(hres[2 * i], pack_bf16(sum[4 * i] + accB[4 * i], sum[4 * i + 1] + accB[4 * i + 1]));
      o1[4 * i] = hadd2_bf(hres[2 * i + 1], pack_bf16(sum[4 * i + 2] + accB[4 * i + 2], sum[4 * i + 3] + accB[4 * i + 3]));
    }
    if (tid == 0) TR(1, 10);
  }
}

extern "C" void kernel_launch(void* const* d_in, const int* in_sizes, int n_in, void* d_out, int out_size) {
  const __nv_bfloat16* x = (const __nv_bfloat16*)d_in[0];
  const __nv_bfloat16 *are = (const __nv_bfloat16*)d_in[1], *aim = (const __nv_bfloat16*)d_in[2], *bre = (const __nv_bfloat16*)d_in[3],
                      *bim = (const __nv_bfloat16*)d_in[4], *cre = (const __nv_bfloat16*)d_in[5], *cim = (const __nv_bfloat16*)d_in[6],
                      *logdt = (const __nv_bfloat16*)d_in[7], *dskip = (const __nv_bfloat16*)d_in[8];
  const __nv_bfloat16 *wg = (const __nv_bfloat16*)d_in[10], *wu = (const __nv_bfloat16*)d_in[11], *wd = (const __nv_bfloat16*)d_in[12];

  static bool init = false;
  if (!init) {
    init = true;
    cudaFuncSetAttribute(k_ffn, cudaFuncAttributeMaxDynamicSharedMemorySize, B_SMEM);
  }
  cudaStream_t st = cudaStreamPerThread;
  k_ln1<<<256, 256, 0, st>>>(x);
  k_kgen<<<DM, 512, 0, st>>>(are, aim, bre, bim, cre, cim, logdt);
  k_conv<<<DM, 512, 0, st>>>(x, dskip);
  k_colsum<<<2 * FF / 128, 128, 0, st>>>(wg, wu);
  k_pack<<<3 * 100352 / 256, 256, 0, st>>>((const uint4*)wg, (const uint4*)wu, (const uint4*)wd);
  k_ffn<<<128, 384, B_SMEM, st>>>((__nv_bfloat16*)d_out);
}
```

```cpp
#include <cuda_runtime.h>
#include <cuda_bf16.h>
#include <stdint.h>

constexpr int LSEQ = 2048, DM = 448, FF = 1792, NST = 256;

__device__ uint4    g_himg[16 * 114688 / 16];
__device__ float    g_colsum[2 * FF];
__device__ uint4    g_part[128 * 3 * 1024];
__device__ uint4    g_wimg[8 * 602112 / 16];
__device__ unsigned g_epoch;
__device__ __nv_bfloat16 g_u[LSEQ * DM];
__device__ float    g_kd[DM * 2064];

#define TR(k, i) do {} while (0)
__device__ __forceinline__ uint32_t s2u(const void* p) { return (uint32_t)__cvta_generic_to_shared(p); }
__device__ __forceinline__ void mbar_init(uint32_t b, int c) { asm volatile("mbarrier.init.shared::cta.b64 [%0], %1;" ::"r"(b), "r"(c)); }
__device__ __forceinline__ void mbar_expect(uint32_t b, int bytes) { asm volatile("mbarrier.arrive.expect_tx.shared::cta.b64 _, [%0], %1;" ::"r"(b), "r"(bytes) : "memory"); }
__device__ __forceinline__ void mbar_arrive(uint32_t b) { asm volatile("mbarrier.arrive.shared::cta.b64 _, [%0];" ::"r"(b) : "memory"); }
__device__ __forceinline__ void mbar_wait(uint32_t b, int ph) {
  asm volatile("{\n.reg .pred p;\nLW:\nmbarrier.try_wait.parity.shared::cta.b64 p, [%0], %1;\n@p bra LD;\nbra LW;\nLD:\n}" ::"r"(b), "r"(ph) : "memory");
}
__device__ __forceinline__ uint64_t mkdesc(uint32_t addr, uint32_t lbo, uint32_t sbo, uint32_t sw) {
  return (uint64_t)((addr & 0x3FFFF) >> 4) | ((uint64_t)((lbo >> 4) & 0x3FFF) << 16) | ((uint64_t)((sbo >> 4) & 0x3FFF) << 32) | ((uint64_t)sw << 62);
}
__device__ __forceinline__ void wg_fence() { asm volatile("wgmma.fence.sync.aligned;" ::: "memory"); }
__device__ __forceinline__ void wg_commit() { asm volatile("wgmma.commit_group.sync.aligned;" ::: "memory"); }
template <int N> __device__ __forceinline__ void wg_wait() { asm volatile("wgmma.wait_group.sync.aligned %0;" ::"n"(N) : "memory"); }
template <int N> __device__ __forceinline__ void reg_fence(float (&a)[N]) {
#pragma unroll
  for (int i = 0; i < N; i++) asm volatile("" : "+f"(a[i])::"memory");
}
__device__ __forceinline__ uint32_t pack_bf16(float lo, float hi) {
  uint32_t r; asm("cvt.rn.bf16x2.f32 %0, %1, %2;" : "=r"(r) : "f"(hi), "f"(lo)); return r;
}
__device__ __forceinline__ float bf_lo(uint32_t v) { return __uint_as_float(v << 16); }
__device__ __forceinline__ float bf_hi(uint32_t v) { return __uint_as_float(v & 0xFFFF0000u); }
__device__ __forceinline__ float rbf(float x) { return __bfloat162float(__float2bfloat16_rn(x)); }
__device__ __forceinline__ uint32_t hmul2_bf(uint32_t a, uint32_t b) { uint32_t r; asm("mul.rn.bf16x2 %0, %1, %2;" : "=r"(r) : "r"(a), "r"(b)); return r; }
__device__ __forceinline__ uint32_t hadd2_bf(uint32_t a, uint32_t b) { uint32_t r; asm("add.rn.bf16x2 %0, %1, %2;" : "=r"(r) : "r"(a), "r"(b)); return r; }
__device__ __forceinline__ void bulk_ld(uint32_t dst, const void* src, int bytes, uint32_t bar) {
  asm volatile("cp.async.bulk.shared::cluster.global.mbarrier::complete_tx::bytes [%0], [%1], %2, [%3];"
               ::"r"(dst), "l"(src), "r"(bytes), "r"(bar) : "memory");
}

__device__ __forceinline__ void wgmma_ss224(float (&d)[112], uint64_t a, uint64_t b, int acc) {
  asm volatile("{\n.reg .pred p;\nsetp.ne.b32 p, %114, 0;\n"
    "wgmma.mma_async.sync.aligned.m64n224k16.f32.bf16.bf16 {%0,%1,%2,%3,%4,%5,%6,%7,%8,%9,%10,%11,%12,%13,%14,%15,%16,%17,%18,%19,%20,%21,%22,%23,%24,%25,%26,%27,%28,%29,%30,%31,%32,%33,%34,%35,%36,%37,%38,%39,%40,%41,%42,%43,%44,%45,%46,%47,%48,%49,%50,%51,%52,%53,%54,%55,%56,%57,%58,%59,%60,%61,%62,%63,%64,%65,%66,%67,%68,%69,%70,%71,%72,%73,%74,%75,%76,%77,%78,%79,%80,%81,%82,%83,%84,%85,%86,%87,%88,%89,%90,%91,%92,%93,%94,%95,%96,%97,%98,%99,%100,%101,%102,%103,%104,%105,%106,%107,%108,%109,%110,%111}, %112, %113, p, 1, 1, 1, 1;\n}\n"
    : "+f"(d[0]),"+f"(d[1]),"+f"(d[2]),"+f"(d[3]),"+f"(d[4]),"+f"(d[5]),"+f"(d[6]),"+f"(d[7]),"+f"(d[8]),"+f"(d[9]),"+f"(d[10]),"+f"(d[11]),"+f"(d[12]),"+f"(d[13]),"+f"(d[14]),"+f"(d[15]),"+f"(d[16]),"+f"(d[17]),"+f"(d[18]),"+f"(d[19]),"+f"(d[20]),"+f"(d[21]),"+f"(d[22]),"+f"(d[23]),"+f"(d[24]),"+f"(d[25]),"+f"(d[26]),"+f"(d[27]),"+f"(d[28]),"+f"(d[29]),"+f"(d[30]),"+f"(d[31]),"+f"(d[32]),"+f"(d[33]),"+f"(d[34]),"+f"(d[35]),"+f"(d[36]),"+f"(d[37]),"+f"(d[38]),"+f"(d[39]),"+f"(d[40]),"+f"(d[41]),"+f"(d[42]),"+f"(d[43]),"+f"(d[44]),"+f"(d[45]),"+f"(d[46]),"+f"(d[47]),"+f"(d[48]),"+f"(d[49]),"+f"(d[50]),"+f"(d[51]),"+f"(d[52]),"+f"(d[53]),"+f"(d[54]),"+f"(d[55]),"+f"(d[56]),"+f"(d[57]),"+f"(d[58]),"+f"(d[59]),"+f"(d[60]),"+f"(d[61]),"+f"(d[62]),"+f"(d[63]),"+f"(d[64]),"+f"(d[65]),"+f"(d[66]),"+f"(d[67]),"+f"(d[68]),"+f"(d[69]),"+f"(d[70]),"+f"(d[71]),"+f"(d[72]),"+f"(d[73]),"+f"(d[74]),"+f"(d[75]),"+f"(d[76]),"+f"(d[77]),"+f"(d[78]),"+f"(d[79]),"+f"(d[80]),"+f"(d[81]),"+f"(d[82]),"+f"(d[83]),"+f"(d[84]),"+f"(d[85]),"+f"(d[86]),"+f"(d[87]),"+f"(d[88]),"+f"(d[89]),"+f"(d[90]),"+f"(d[91]),"+f"(d[92]),"+f"(d[93]),"+f"(d[94]),"+f"(d[95]),"+f"(d[96]),"+f"(d[97]),"+f"(d[98]),"+f"(d[99]),"+f"(d[100]),"+f"(d[101]),"+f"(d[102]),"+f"(d[103]),"+f"(d[104]),"+f"(d[105]),"+f"(d[106]),"+f"(d[107]),"+f"(d[108]),"+f"(d[109]),"+f"(d[110]),"+f"(d[111])
    : "l"(a), "l"(b), "r"(acc));
}
template <int OFF, uint32_t BHI, int ACC>
__device__ __forceinline__ void wgmma_rs56(float (&d)[28], uint32_t a0, uint32_t a1, uint32_t a2, uint32_t a3, uint32_t blo) {
  asm volatile("{\n.reg .pred p;\n.reg .b32 l;\n.reg .b64 bd;\nsetp.ne.b32 p, %35, 0;\nadd.u32 l, %32, %33;\nmov.b64 bd, {l, %34};\n"
    "wgmma.mma_async.sync.aligned.m64n56k16.f32.bf16.bf16 {%0,%1,%2,%3,%4,%5,%6,%7,%8,%9,%10,%11,%12,%13,%14,%15,%16,%17,%18,%19,%20,%21,%22,%23,%24,%25,%26,%27}, {%28,%29,%30,%31}, bd, p, 1, 1, 1;\n}\n"
    : "+f"(d[0]),"+f"(d[1]),"+f"(d[2]),"+f"(d[3]),"+f"(d[4]),"+f"(d[5]),"+f"(d[6]),"+f"(d[7]),"+f"(d[8]),"+f"(d[9]),"+f"(d[10]),"+f"(d[11]),"+f"(d[12]),"+f"(d[13]),"+f"(d[14]),"+f"(d[15]),"+f"(d[16]),"+f"(d[17]),"+f"(d[18]),"+f"(d[19]),"+f"(d[20]),"+f"(d[21]),"+f"(d[22]),"+f"(d[23]),"+f"(d[24]),"+f"(d[25]),"+f"(d[26]),"+f"(d[27])
    : "r"(a0), "r"(a1), "r"(a2), "r"(a3), "r"(blo), "n"(OFF), "n"(BHI), "n"(ACC));
}

__global__ void k_ln1(const __nv_bfloat16* __restrict__ x) {
  int row = blockIdx.x * 8 + threadIdx.x / 32, lane = threadIdx.x & 31;
  float v[14]; float s = 0;
  for (int i = 0; i < 14; i++) { v[i] = __bfloat162float(x[row * DM + lane + 32 * i]); s += v[i]; }
  for (int o = 16; o; o >>= 1) s += __shfl_xor_sync(~0u, s, o);
  float mean = s / DM, q = 0;
  for (int i = 0; i < 14; i++) q += (v[i] - mean) * (v[i] - mean);
  for (int o = 16; o; o >>= 1) q += __shfl_xor_sync(~0u, q, o);
  float m = rbf(mean), sd = rbf(sqrtf(rbf(rbf(q / DM) + 1e-5f)));
  for (int i = 0; i < 14; i++) g_u[row * DM + lane + 32 * i] = __float2bfloat16_rn(rbf(v[i] - m) / sd);
  if (blockIdx.x == 0 && threadIdx.x == 0) g_epoch = g_epoch + 1;
}
__global__ void k_kgen(const __nv_bfloat16* are, const __nv_bfloat16* aim, const __nv_bfloat16* bre, const __nv_bfloat16* bim,
                       const __nv_bfloat16* cre, const __nv_bfloat16* cim, const __nv_bfloat16* logdt) {
  int d = blockIdx.x;
  float dt = rbf(expf(__bfloat162float(logdt[d])));
  for (int l = threadIdx.x; l < 2048; l += blockDim.x) {
    float lf = rbf((float)l), acc = 0;
    for (int n = 0; n < NST; n++) {
      int i = d * NST + n;
      float lr = dt * __bfloat162float(are[i]), li = dt * __bfloat162float(aim[i]);
      float br = dt * __bfloat162float(bre[i]), bi = dt * __bfloat162float(bim[i]);
      float cr = __bfloat162float(cre[i]), ci = __bfloat162float(cim[i]);
      float wr = cr * br - ci * bi, wi = cr * bi + ci * br;
      float e = expf(lr * lf), sn, cs; sincosf(li * lf, &sn, &cs);
      acc += e * (wr * cs - wi * sn);
    }
    g_kd[d * 2064 + l] = acc;
  }
}
__global__ void k_conv(const __nv_bfloat16* __restrict__ x, const __nv_bfloat16* dskip) {
  __shared__ float sk[2048], su[2048];
  int d = blockIdx.x;
  for (int i = threadIdx.x; i < 2048; i += blockDim.x) { sk[i] = g_kd[d * 2064 + i]; su[i] = __bfloat162float(g_u[i * DM + d]); }
  __syncthreads();
  float ds = __bfloat162float(dskip[d]);
  for (int t = threadIdx.x; t < 2048; t += blockDim.x) {
    float acc = 0;
    for (int l = 0; l <= t; l++) acc += sk[l] * su[t - l];
    float yb = rbf(rbf(acc) + rbf(su[t] * ds));
    float h = rbf(__bfloat162float(x[t * DM + d]) + yb);
    int tau = t >> 3, rt = tau >> 4, mh = (tau >> 3) & 1, c = tau & 7, r = d & 7;
    size_t off = (size_t)rt * 114688 + (d >> 3) * 2048 + mh * 1024 + r * 128 + ((c ^ r) * 16) + (t & 7) * 2;
    *(__nv_bfloat16*)((char*)g_himg + off) = __float2bfloat16_rn(h);
  }
}
__global__ void k_colsum(const __nv_bfloat16* wg, const __nv_bfloat16* wu) {
  int f = blockIdx.x * blockDim.x + threadIdx.x;
  const __nv_bfloat16* w = f < FF ? wg : wu; int ff = f < FF ? f : f - FF;
  float s = 0; for (int d = 0; d < DM; d++) s += __bfloat162float(w[d * FF + ff]);
  g_colsum[f] = s;
}

__global__ void k_pack(const uint4* __restrict__ wg, const uint4* __restrict__ wu, const uint4* __restrict__ wd) {
  int i = blockIdx.x * blockDim.x + threadIdx.x;
  int mat = i / 100352, e = i % 100352;
  if (mat < 2) {
    int d = e / 224, ngg = e % 224;
    int j = ngg / 28, q = (ngg % 28) / 14, ng = ngg % 14 + 14 * mat;
    g_wimg[(size_t)j * 37632 + (q * 14 + (d >> 5)) * 896 + ng * 32 + (d & 31)] = (mat ? wu : wg)[e];
  } else {
    int f = e / 56, ngg = e % 56;
    int j = f / 224, hf = (f % 224) / 112, k = f % 112, c = ngg / 7, ng = ngg % 7;
    g_wimg[(size_t)j * 37632 + 25088 + (c * 2 + hf) * 784 + ng * 112 + k] = wd[e];
  }
}

constexpr int B_SA = 0, B_RING = 114688, B_SLOT = 14336, B_NSLOT = 7;
constexpr int B_STAT = B_RING + B_NSLOT * B_SLOT;
constexpr int B_CS = B_STAT + 1024;
constexpr int B_RED = B_CS + 1792;
constexpr int B_BAR = B_RED + 4096;
constexpr int B_SMEM = B_BAR + 512;

__device__ __forceinline__ void st128(uint4* p, uint32_t a, uint32_t b, uint32_t c, uint32_t d) {
  asm volatile("{\n.reg .b128 v;\n.reg .b64 lo, hi;\nmov.b64 lo, {%1, %2};\nmov.b64 hi, {%3, %4};\nmov.b128 v, {lo, hi};\n"
               "st.relaxed.gpu.global.b128 [%0], v;\n}" ::"l"(p), "r"(a), "r"(b), "r"(c), "r"(d) : "memory");
}
__device__ __forceinline__ void ld128(const uint4* p, uint32_t* r) {
  asm volatile("{\n.reg .b128 v;\n.reg .b64 lo, hi;\nld.relaxed.gpu.global.b128 v, [%4];\nmov.b128 {lo, hi}, v;\n"
               "mov.b64 {%0, %1}, lo;\nmov.b64 {%2, %3}, hi;\n}" : "=r"(r[0]), "=r"(r[1]), "=r"(r[2]), "=r"(r[3]) : "l"(p) : "memory");
}

__device__ __forceinline__ uint32_t mapa(uint32_t a, uint32_t r) { uint32_t o; asm("mapa.shared::cluster.u32 %0, %1, %2;" : "=r"(o) : "r"(a), "r"(r)); return o; }

__global__ void __cluster_dims__(2, 1, 1) __launch_bounds__(384, 1) k_ffn(__nv_bfloat16* __restrict__ out) {
  extern __shared__ __align__(1024) unsigned char sm[];
  const uint32_t sb = s2u(sm);
  const int tid = threadIdx.x, wg = tid >> 7, warp = tid >> 5, lane = tid & 31;
  const int rank = blockIdx.x & 1, p = (blockIdx.x >> 1) & 3, rt = blockIdx.x >> 3, j = 2 * p + rank;
  const uint32_t bar_full = sb + B_BAR, bar_empty = bar_full + 64, bar_h = bar_full + 128, bar_cs = bar_full + 240,
                 bar_afree = bar_full + 248, bar_hh = bar_full + 256;
  if (tid == 0) {
    TR(1, 0);
    for (int i = 0; i < B_NSLOT; i++) { mbar_init(bar_full + 8 * i, 1); mbar_init(bar_empty + 8 * i, 2); }
    for (int i = 0; i < 14; i++) mbar_init(bar_h + 8 * i, 1);
    mbar_init(bar_cs, 1);
    mbar_init(bar_afree, 2);
    for (int i = 0; i < 4; i++) { mbar_init(bar_hh + 8 * i, 1); mbar_expect(bar_hh + 8 * i, 14336); }
    asm volatile("fence.mbarrier_init.release.cluster;" ::: "memory");
  }
  __syncthreads();
  asm volatile("barrier.cluster.arrive.release.aligned;" ::: "memory");

  if (wg == 2) {
    asm volatile("setmaxnreg.dec.sync.aligned.u32 40;");
    if (warp == 8 && lane == 0) {
      const char* wsrc = (const char*)g_wimg + (size_t)j * 602112;
      const char* hsrc = (const char*)g_himg + (size_t)rt * 114688;
      asm volatile("griddepcontrol.wait;" ::: "memory");
      TR(1, 1);
      int slot = 0, ph = 0;
      for (int s = 0; s < 44; s++) {
        if (s < B_NSLOT) {
          mbar_expect(bar_h + 8 * s, 8192);
          bulk_ld(sb + B_SA + s * 8192, hsrc + s * 8192, 8192, bar_h + 8 * s);
        } else {
          if (s == B_NSLOT) {
            for (int i = 7; i < 14; i++) {
              mbar_expect(bar_h + 8 * i, 8192);
              bulk_ld(sb + B_SA + i * 8192, hsrc + i * 8192, 8192, bar_h + 8 * i);
            }
            mbar_expect(bar_cs, 1792);
            bulk_ld(sb + B_CS, g_colsum + 224 * j, 896, bar_cs);
            bulk_ld(sb + B_CS + 896, g_colsum + FF + 224 * j, 896, bar_cs);
          }
          mbar_wait(bar_empty + 8 * slot, ph ^ 1);
        }
        uint32_t dst = sb + B_RING + slot * B_SLOT, fb = bar_full + 8 * slot;
        if (s < 28) {
          mbar_expect(fb, 14336);
          bulk_ld(dst, wsrc + s * 14336, 14336, fb);
        } else {
          const int i = s - 28;
          const int ci = i < 3 ? 0 : i < 6 ? 1 : i < 8 ? i - 6 : i < 12 ? 2 : 3;
          const int kp = i < 3 ? i : i < 6 ? i - 3 : i < 8 ? 3 : (i & 3);
          const int cg = 4 * rank + ((p + 1 + ci) & 3);
          mbar_expect(fb, 12544);
          bulk_ld(dst, (const char*)g_wimg + (size_t)(j ^ (kp >> 1)) * 602112 + 401408 + (cg * 2 + (kp & 1)) * 12544, 12544, fb);
        }
        if (++slot == B_NSLOT) { slot = 0; ph ^= 1; }
      }
    }
    asm volatile("barrier.cluster.wait.acquire.aligned;" ::: "memory");
  } else {
    asm volatile("setmaxnreg.inc.sync.aligned.u32 232;");
    const int g = lane >> 2, t = lane & 3, wq = warp & 3, t128 = tid & 127;
    uint32_t hh[56], hres[16];
    const float* cs = (const float*)(sm + B_CS);
    float m0, r0, m1, r1;
    int slot = 0, ph = 0, pslot = 0;
    asm volatile("barrier.cluster.wait.acquire.aligned;" ::: "memory");
    asm volatile("griddepcontrol.wait;" ::: "memory");
    const uint32_t tag = (__ldcg(&g_epoch) & 0xFFFFu) << 16;
    const uint32_t peer_hh = mapa(sb + B_SA + wg * 14336 + t128 * 16, rank ^ 1);
    const uint32_t peer_bar = mapa(bar_hh + 8 * wg, rank ^ 1);
    auto send_hh = [&](int q) {
#pragma unroll
      for (int i = 0; i < 7; i++)
        asm volatile("st.async.weak.shared::cluster.mbarrier::complete_tx::bytes.v4.b32 [%0], {%1, %2, %3, %4}, [%5];"
                     ::"r"(peer_hh + q * 28672 + i * 2048), "r"(hh[28 * q + 4 * i]), "r"(hh[28 * q + 4 * i + 1]),
                       "r"(hh[28 * q + 4 * i + 2]), "r"(hh[28 * q + 4 * i + 3]), "r"(peer_bar + q * 16) : "memory");
    };
    if (wg == 1) asm volatile("bar.sync 3, 256;" ::: "memory");
#pragma unroll
    for (int q = 0; q < 2; q++) {
      float acc[112];
      float s1[8], s2[8];
      const unsigned char* sp = sm + B_SA + wg * 1024 + (t128 >> 6) * 2048 + ((t128 >> 3) & 7) * 128 + (((t128 ^ (t128 >> 3)) & 7) << 4);
      if (q == 0) {
#pragma unroll
        for (int i = 0; i < 8; i++) { s1[i] = 0.f; s2[i] = 0.f; }
      }
#pragma unroll 1
      for (int st = 0; st < 14; st++) {
        if (q == 0) mbar_wait(bar_h + 8 * st, 0);
        mbar_wait(bar_full + 8 * slot, ph);
        wg_fence();
#pragma unroll
        for (int kk = 0; kk < 2; kk++)
          wgmma_ss224(acc, mkdesc(sb + B_SA + (2 * st + kk) * 4096 + wg * 1024, 0, 2048, 1),
                      mkdesc(sb + B_RING + slot * B_SLOT + kk * 256, 128, 512, 0), (st | kk) != 0);
        wg_commit();
        if (q == 0 && st == 0 && tid == 0) TR(1, 3);
        if (q == 0 && st == 4 && tid == 0) TR(1, 21);
        if (q == 0 && st == 8 && tid == 0) TR(1, 22);
        if (q == 0 && st == 11 && tid == 0) TR(1, 23);
        if (q == 0) {
          if (st == 1 && wg == 0) asm volatile("bar.arrive 3, 256;" ::: "memory");
          if (st <= 10) {
            const int np = st < 8 ? 1 : 2, p0 = st < 8 ? st : 2 * st - 8;
            for (int pp = p0; pp < p0 + np; pp++) {
              mbar_wait(bar_h + 8 * pp, 0);
#pragma unroll
              for (int i = 0; i < 2; i++) {
                uint4 v = *(const uint4*)(sp + pp * 8192 + i * 4096);
                float e[8] = {bf_lo(v.x), bf_hi(v.x), bf_lo(v.y), bf_hi(v.y), bf_lo(v.z), bf_hi(v.z), bf_lo(v.w), bf_hi(v.w)};
#pragma unroll
                for (int k = 0; k < 8; k++) { s1[k] += e[k]; s2[k] = fmaf(e[k], e[k], s2[k]); }
              }
            }
          } else if (st == 11) {
#pragma unroll
            for (int k = 0; k < 8; k++) {
              s1[k] += __shfl_xor_sync(~0u, s1[k], 8); s2[k] += __shfl_xor_sync(~0u, s2[k], 8);
              s1[k] += __shfl_xor_sync(~0u, s1[k], 16); s2[k] += __shfl_xor_sync(~0u, s2[k], 16);
            }
            if (lane < 8) {
              float4* red = (float4*)(sm + B_RED + wg * 2048 + wq * 512 + lane * 64);
#pragma unroll
              for (int k = 0; k < 4; k++) red[k] = make_float4(s1[2 * k], s2[2 * k], s1[2 * k + 1], s2[2 * k + 1]);
            }
          } else if (st == 12) {
            asm volatile("bar.sync %0, 128;" ::"r"(1 + wg) : "memory");
            if (t128 < 64) {
              float a = 0.f, b = 0.f;
#pragma unroll
              for (int w = 0; w < 4; w++) { float2 v = *(const float2*)(sm + B_RED + wg * 2048 + w * 512 + t128 * 8); a += v.x; b += v.y; }
              float mean = a * (1.f / DM);
              float var = fmaxf(fmaf(-mean, mean, b * (1.f / DM)), 0.f);
              float sd = rbf(sqrtf(rbf(rbf(var) + 1e-5f)));
              ((float2*)(sm + B_STAT))[wg * 64 + t128] = make_float2(rbf(mean), 1.f / sd);
            }
          } else {
            asm volatile("bar.sync %0, 128;" ::"r"(1 + wg) : "memory");
            mbar_wait(bar_cs, 0);
          }
        } else {
          if (st == 0) {
#pragma unroll
            for (int i = 0; i < 4; i++) {
              int qq = lane >> 3, r = lane & 7, kg = 7 * (4 * rank + p) + 2 * i + (qq >> 1), c = 2 * wq + (qq & 1);
              if (kg > 55) kg = 55;
              uint32_t addr = sb + B_SA + kg * 2048 + wg * 1024 + r * 128 + ((c ^ r) << 4);
              asm volatile("ldmatrix.sync.aligned.m8n8.x4.trans.shared.b16 {%0,%1,%2,%3}, [%4];"
                           : "=r"(hres[4 * i]), "=r"(hres[4 * i + 1]), "=r"(hres[4 * i + 2]), "=r"(hres[4 * i + 3]) : "r"(addr) : "memory");
            }
          } else if (st == 11) {
            mbar_wait(bar_afree, 0);
            send_hh(0);
          }
        }
        if (st > 0) {
          wg_wait<1>();
          if (t128 == 0) {
            mbar_arrive(bar_empty + 8 * pslot);
            if (q == 1 && st == 8) asm volatile("mbarrier.arrive.shared::cluster.b64 _, [%0];" ::"r"(mapa(bar_afree, rank ^ 1)) : "memory");
          }
        }
        pslot = slot;
        if (++slot == B_NSLOT) { slot = 0; ph ^= 1; }
      }
      if (q == 0) {
        float2 a = ((const float2*)(sm + B_STAT))[wg * 64 + wq * 16 + g], b = ((const float2*)(sm + B_STAT))[wg * 64 + wq * 16 + g + 8];
        m0 = -a.x; r0 = a.y; m1 = -b.x; r1 = b.y;
        if (tid == 0) TR(1, 4);
      }
      wg_wait<0>();
      reg_fence(acc);
      if (t128 == 0) mbar_arrive(bar_empty + 8 * pslot);
#pragma unroll
      for (int i = 0; i < 14; i++) {
        float2 cg = *(const float2*)(cs + 112 * q + 8 * i + 2 * t), cu = *(const float2*)(cs + 224 + 112 * q + 8 * i + 2 * t);
        uint32_t g0 = pack_bf16(fmaf(m0, cg.x, acc[4 * i]) * r0, fmaf(m0, cg.y, acc[4 * i + 1]) * r0);
        uint32_t g1 = pack_bf16(fmaf(m1, cg.x, acc[4 * i + 2]) * r1, fmaf(m1, cg.y, acc[4 * i + 3]) * r1);
        uint32_t u0 = pack_bf16(fmaf(m0, cu.x, acc[56 + 4 * i]) * r0, fmaf(m0, cu.y, acc[56 + 4 * i + 1]) * r0);
        uint32_t u1 = pack_bf16(fmaf(m1, cu.x, acc[56 + 4 * i + 2]) * r1, fmaf(m1, cu.y, acc[56 + 4 * i + 3]) * r1);
        hh[28 * q + 2 * i] = hmul2_bf(g0, u0); hh[28 * q + 2 * i + 1] = hmul2_bf(g1, u1);
      }
      if (tid == 0) TR(1, 5 + q);
    }
    float accA[28], accB[28], accC[28];
    uint32_t ph0[28], ph1[28];
    const uint32_t blo = (((sb + B_RING) & 0x3FFFF) >> 4) | (8u << 16);
#define ISSUE(acc, I, a, FIRST) do { \
      constexpr int s_ = 28 + (I), sl_ = s_ % B_NSLOT; \
      mbar_wait(bar_full + 8 * sl_, (s_ / B_NSLOT) & 1); \
      wg_fence(); \
      wgmma_rs56<(sl_ * B_SLOT + 0 * 256) / 16, 112, !(FIRST)>(acc, (a)[0], (a)[1], (a)[2], (a)[3], blo); \
      wgmma_rs56<(sl_ * B_SLOT + 1 * 256) / 16, 112, 1>(acc, (a)[4], (a)[5], (a)[6], (a)[7], blo); \
      wgmma_rs56<(sl_ * B_SLOT + 2 * 256) / 16, 112, 1>(acc, (a)[8], (a)[9], (a)[10], (a)[11], blo); \
      wgmma_rs56<(sl_ * B_SLOT + 3 * 256) / 16, 112, 1>(acc, (a)[12], (a)[13], (a)[14], (a)[15], blo); \
      wgmma_rs56<(sl_ * B_SLOT + 4 * 256) / 16, 112, 1>(acc, (a)[16], (a)[17], (a)[18], (a)[19], blo); \
      wgmma_rs56<(sl_ * B_SLOT + 5 * 256) / 16, 112, 1>(acc, (a)[20], (a)[21], (a)[22], (a)[23], blo); \
      wgmma_rs56<(sl_ * B_SLOT + 6 * 256) / 16, 112, 1>(acc, (a)[24], (a)[25], (a)[26], (a)[27], blo); \
      wg_commit(); } while (0)
    auto rel = [&](int i) { if (t128 == 0) mbar_arrive(bar_empty + 8 * ((28 + i) % B_NSLOT)); };
    auto load_hh = [&](uint32_t (&d)[28], int q) {
      mbar_wait(bar_hh + 16 * q + 8 * wg, 0);
#pragma unroll
      for (int i = 0; i < 7; i++) {
        uint4 v = *(const uint4*)(sm + B_SA + q * 28672 + wg * 14336 + i * 2048 + t128 * 16);
        d[4 * i] = v.x; d[4 * i + 1] = v.y; d[4 * i + 2] = v.z; d[4 * i + 3] = v.w;
      }
    };
    auto send = [&](float (&acc)[28], int ci) {
      reg_fence(acc);
      uint4* dst = g_part + (size_t)((rt * 8 + ((p + 1 + ci) & 3) * 2 + rank) * 3 + ci) * 1024 + wg * 512 + t128;
#pragma unroll
      for (int q = 0; q < 4; q++)
        st128(dst + q * 128, pack_bf16(acc[7 * q], acc[7 * q + 1]), pack_bf16(acc[7 * q + 2], acc[7 * q + 3]),
              pack_bf16(acc[7 * q + 4], acc[7 * q + 5]), (pack_bf16(acc[7 * q + 6], 0.f) & 0xFFFFu) | tag);
    };
    auto fetch = [&](uint32_t (&in)[16], int ci) {
      const uint4* src = g_part + (size_t)(blockIdx.x * 3 + ci) * 1024 + wg * 512 + t128;
#pragma unroll
      for (int i = 0; i < 4; i++) ld128(src + i * 128, in + 4 * i);
    };
    auto valid = [&](uint32_t (&in)[16]) {
      bool ok = (((in[3] ^ tag) | (in[7] ^ tag) | (in[11] ^ tag) | (in[15] ^ tag)) & 0xFFFF0000u) == 0;
      return __all_sync(~0u, ok) != 0;
    };
    auto accum = [&](float (&sum)[28], uint32_t (&in)[16], int ci) {
      int it = 0;
      while (!valid(in) && ++it < 200000) fetch(in, ci);
#pragma unroll
      for (int q = 0; q < 4; q++) {
        sum[7 * q] += bf_lo(in[4 * q]); sum[7 * q + 1] += bf_hi(in[4 * q]);
        sum[7 * q + 2] += bf_lo(in[4 * q + 1]); sum[7 * q + 3] += bf_hi(in[4 * q + 1]);
        sum[7 * q + 4] += bf_lo(in[4 * q + 2]); sum[7 * q + 5] += bf_hi(in[4 * q + 2]);
        sum[7 * q + 6] += bf_lo(in[4 * q + 3]);
      }
    };
    ISSUE(accA, 0, hh, true);
    send_hh(1);
    ISSUE(accA, 1, hh + 28, false);
    load_hh(ph0, 0);
    wg_wait<1>(); rel(0);
    ISSUE(accA, 2, ph0, false);      wg_wait<1>(); rel(1);
    ISSUE(accB, 3, hh, true);        wg_wait<1>(); rel(2);
    ISSUE(accB, 4, hh + 28, false);  wg_wait<1>(); rel(3);
    ISSUE(accB, 5, ph0, false);
    if (tid == 0) TR(1, 11);
    load_hh(ph1, 1);
    if (tid == 0) TR(1, 12);
    wg_wait<1>(); rel(4);
    ISSUE(accA, 6, ph1, false);      wg_wait<1>(); rel(5);
    ISSUE(accB, 7, ph1, false);      wg_wait<1>(); rel(6);
    ISSUE(accC, 8, hh, true);        send(accA, 0); wg_wait<1>(); rel(7);
    ISSUE(accC, 9, hh + 28, false);  send(accB, 1); wg_wait<1>(); rel(8);
    if (tid == 0) TR(1, 13);
    ISSUE(accC, 10, ph0, false);
    ISSUE(accC, 11, ph1, false);
    ISSUE(accA, 12, hh, true);
    ISSUE(accA, 13, hh + 28, false);
    wg_wait<2>();
    send(accC, 2);
    if (tid == 0) TR(1, 14);
    ISSUE(accA, 14, ph0, false);
    ISSUE(accA, 15, ph1, false);
    uint32_t in0[16], in1[16], in2[16];
    fetch(in0, 0); fetch(in1, 1);
    if (tid == 0) TR(1, 7);
#pragma unroll
    for (int i = 0; i < 28; i++) accB[i] = 0.f;
    accum(accB, in0, 0); accum(accB, in1, 1);
    wg_wait<1>();
    if (tid == 0) TR(1, 8);
    fetch(in2, 2);
    accum(accB, in2, 2);
    wg_wait<0>();
    reg_fence(accA);
    if (tid == 0) TR(1, 9);
    const int row = rt * 128 + wg * 64 + wq * 16 + g;
    uint32_t* o0 = (uint32_t*)(out + (size_t)row * DM + 56 * (4 * rank + p) + 2 * t);
    uint32_t* o1 = o0 + 8 * DM / 2;
#pragma unroll
    for (int i = 0; i < 7; i++) {
      o0[4 * i] = hadd2_bf(hres[2 * i], pack_bf16(accA[4 * i] + accB[4 * i], accA[4 * i + 1] + accB[4 * i + 1]));
      o1[4 * i] = hadd2_bf(hres[2 * i + 1], pack_bf16(accA[4 * i + 2] + accB[4 * i + 2], accA[4 * i + 3] + accB[4 * i + 3]));
    }
    if (tid == 0) TR(1, 10);
    if (tid == 128) TR(1, 15);
  }
}

extern "C" void kernel_launch(void* const* d_in, const int* in_sizes, int n_in, void* d_out, int out_size) {
  const __nv_bfloat16* x = (const __nv_bfloat16*)d_in[0];
  const __nv_bfloat16 *are = (const __nv_bfloat16*)d_in[1], *aim = (const __nv_bfloat16*)d_in[2], *bre = (const __nv_bfloat16*)d_in[3],
                      *bim = (const __nv_bfloat16*)d_in[4], *cre = (const __nv_bfloat16*)d_in[5], *cim = (const __nv_bfloat16*)d_in[6],
                      *logdt = (const __nv_bfloat16*)d_in[7], *dskip = (const __nv_bfloat16*)d_in[8];
  const __nv_bfloat16 *wg = (const __nv_bfloat16*)d_in[10], *wu = (const __nv_bfloat16*)d_in[11], *wd = (const __nv_bfloat16*)d_in[12];

  static bool init = false;
  if (!init) {
    init = true;
    cudaFuncSetAttribute(k_ffn, cudaFuncAttributeMaxDynamicSharedMemorySize, B_SMEM);
  }
  cudaStream_t st = cudaStreamPerThread;
  k_ln1<<<256, 256, 0, st>>>(x);
  k_kgen<<<DM, 512, 0, st>>>(are, aim, bre, bim, cre, cim, logdt);
  k_conv<<<DM, 512, 0, st>>>(x, dskip);
  k_colsum<<<2 * FF / 128, 128, 0, st>>>(wg, wu);
  k_pack<<<3 * 100352 / 256, 256, 0, st>>>((const uint4*)wg, (const uint4*)wu, (const uint4*)wd);
  k_ffn<<<128, 384, B_SMEM, st>>>((__nv_bfloat16*)d_out);
}
```

```cpp
#include <cuda_runtime.h>
#include <cuda_bf16.h>
#include <stdint.h>

constexpr int LSEQ = 2048, DM = 448, FF = 1792, NST = 256;

__device__ uint4    g_himg[16 * 114688 / 16];
__device__ float    g_colsum[2 * FF];
__device__ uint4    g_part[128 * 3 * 1024];
__device__ uint4    g_wimg[8 * 602112 / 16];
__device__ unsigned g_epoch;
__device__ __nv_bfloat16 g_u[LSEQ * DM];
__device__ float    g_kd[DM * 2064];

#define TR(k, i) do {} while (0)
__device__ __forceinline__ uint32_t s2u(const void* p) { return (uint32_t)__cvta_generic_to_shared(p); }
__device__ __forceinline__ void mbar_init(uint32_t b, int c) { asm volatile("mbarrier.init.shared::cta.b64 [%0], %1;" ::"r"(b), "r"(c)); }
__device__ __forceinline__ void mbar_expect(uint32_t b, int bytes) { asm volatile("mbarrier.arrive.expect_tx.shared::cta.b64 _, [%0], %1;" ::"r"(b), "r"(bytes) : "memory"); }
__device__ __forceinline__ void mbar_arrive(uint32_t b) { asm volatile("mbarrier.arrive.shared::cta.b64 _, [%0];" ::"r"(b) : "memory"); }
__device__ __forceinline__ void mbar_wait(uint32_t b, int ph) {
  asm volatile("{\n.reg .pred p;\nLW:\nmbarrier.try_wait.parity.shared::cta.b64 p, [%0], %1;\n@p bra LD;\nbra LW;\nLD:\n}" ::"r"(b), "r"(ph) : "memory");
}
__device__ __forceinline__ uint64_t mkdesc(uint32_t addr, uint32_t lbo, uint32_t sbo, uint32_t sw) {
  return (uint64_t)((addr & 0x3FFFF) >> 4) | ((uint64_t)((lbo >> 4) & 0x3FFF) << 16) | ((uint64_t)((sbo >> 4) & 0x3FFF) << 32) | ((uint64_t)sw << 62);
}
__device__ __forceinline__ void wg_fence() { asm volatile("wgmma.fence.sync.aligned;" ::: "memory"); }
__device__ __forceinline__ void wg_commit() { asm volatile("wgmma.commit_group.sync.aligned;" ::: "memory"); }
template <int N> __device__ __forceinline__ void wg_wait() { asm volatile("wgmma.wait_group.sync.aligned %0;" ::"n"(N) : "memory"); }
template <int N> __device__ __forceinline__ void reg_fence(float (&a)[N]) {
#pragma unroll
  for (int i = 0; i < N; i++) asm volatile("" : "+f"(a[i])::"memory");
}
__device__ __forceinline__ uint32_t pack_bf16(float lo, float hi) {
  uint32_t r; asm("cvt.rn.bf16x2.f32 %0, %1, %2;" : "=r"(r) : "f"(hi), "f"(lo)); return r;
}
__device__ __forceinline__ float bf_lo(uint32_t v) { return __uint_as_float(v << 16); }
__device__ __forceinline__ float bf_hi(uint32_t v) { return __uint_as_float(v & 0xFFFF0000u); }
__device__ __forceinline__ float rbf(float x) { return __bfloat162float(__float2bfloat16_rn(x)); }
__device__ __forceinline__ uint32_t hmul2_bf(uint32_t a, uint32_t b) { uint32_t r; asm("mul.rn.bf16x2 %0, %1, %2;" : "=r"(r) : "r"(a), "r"(b)); return r; }
__device__ __forceinline__ uint32_t hadd2_bf(uint32_t a, uint32_t b) { uint32_t r; asm("add.rn.bf16x2 %0, %1, %2;" : "=r"(r) : "r"(a), "r"(b)); return r; }
__device__ __forceinline__ void bulk_ld(uint32_t dst, const void* src, int bytes, uint32_t bar) {
  asm volatile("cp.async.bulk.shared::cluster.global.mbarrier::complete_tx::bytes [%0], [%1], %2, [%3];"
               ::"r"(dst), "l"(src), "r"(bytes), "r"(bar) : "memory");
}

__device__ __forceinline__ void wgmma_ss224(float (&d)[112], uint64_t a, uint64_t b, int acc) {
  asm volatile("{\n.reg .pred p;\nsetp.ne.b32 p, %114, 0;\n"
    "wgmma.mma_async.sync.aligned.m64n224k16.f32.bf16.bf16 {%0,%1,%2,%3,%4,%5,%6,%7,%8,%9,%10,%11,%12,%13,%14,%15,%16,%17,%18,%19,%20,%21,%22,%23,%24,%25,%26,%27,%28,%29,%30,%31,%32,%33,%34,%35,%36,%37,%38,%39,%40,%41,%42,%43,%44,%45,%46,%47,%48,%49,%50,%51,%52,%53,%54,%55,%56,%57,%58,%59,%60,%61,%62,%63,%64,%65,%66,%67,%68,%69,%70,%71,%72,%73,%74,%75,%76,%77,%78,%79,%80,%81,%82,%83,%84,%85,%86,%87,%88,%89,%90,%91,%92,%93,%94,%95,%96,%97,%98,%99,%100,%101,%102,%103,%104,%105,%106,%107,%108,%109,%110,%111}, %112, %113, p, 1, 1, 1, 1;\n}\n"
    : "+f"(d[0]),"+f"(d[1]),"+f"(d[2]),"+f"(d[3]),"+f"(d[4]),"+f"(d[5]),"+f"(d[6]),"+f"(d[7]),"+f"(d[8]),"+f"(d[9]),"+f"(d[10]),"+f"(d[11]),"+f"(d[12]),"+f"(d[13]),"+f"(d[14]),"+f"(d[15]),"+f"(d[16]),"+f"(d[17]),"+f"(d[18]),"+f"(d[19]),"+f"(d[20]),"+f"(d[21]),"+f"(d[22]),"+f"(d[23]),"+f"(d[24]),"+f"(d[25]),"+f"(d[26]),"+f"(d[27]),"+f"(d[28]),"+f"(d[29]),"+f"(d[30]),"+f"(d[31]),"+f"(d[32]),"+f"(d[33]),"+f"(d[34]),"+f"(d[35]),"+f"(d[36]),"+f"(d[37]),"+f"(d[38]),"+f"(d[39]),"+f"(d[40]),"+f"(d[41]),"+f"(d[42]),"+f"(d[43]),"+f"(d[44]),"+f"(d[45]),"+f"(d[46]),"+f"(d[47]),"+f"(d[48]),"+f"(d[49]),"+f"(d[50]),"+f"(d[51]),"+f"(d[52]),"+f"(d[53]),"+f"(d[54]),"+f"(d[55]),"+f"(d[56]),"+f"(d[57]),"+f"(d[58]),"+f"(d[59]),"+f"(d[60]),"+f"(d[61]),"+f"(d[62]),"+f"(d[63]),"+f"(d[64]),"+f"(d[65]),"+f"(d[66]),"+f"(d[67]),"+f"(d[68]),"+f"(d[69]),"+f"(d[70]),"+f"(d[71]),"+f"(d[72]),"+f"(d[73]),"+f"(d[74]),"+f"(d[75]),"+f"(d[76]),"+f"(d[77]),"+f"(d[78]),"+f"(d[79]),"+f"(d[80]),"+f"(d[81]),"+f"(d[82]),"+f"(d[83]),"+f"(d[84]),"+f"(d[85]),"+f"(d[86]),"+f"(d[87]),"+f"(d[88]),"+f"(d[89]),"+f"(d[90]),"+f"(d[91]),"+f"(d[92]),"+f"(d[93]),"+f"(d[94]),"+f"(d[95]),"+f"(d[96]),"+f"(d[97]),"+f"(d[98]),"+f"(d[99]),"+f"(d[100]),"+f"(d[101]),"+f"(d[102]),"+f"(d[103]),"+f"(d[104]),"+f"(d[105]),"+f"(d[106]),"+f"(d[107]),"+f"(d[108]),"+f"(d[109]),"+f"(d[110]),"+f"(d[111])
    : "l"(a), "l"(b), "r"(acc));
}
template <int OFF, uint32_t BHI, int ACC>
__device__ __forceinline__ void wgmma_rs56(float (&d)[28], uint32_t a0, uint32_t a1, uint32_t a2, uint32_t a3, uint32_t blo) {
  asm volatile("{\n.reg .pred p;\n.reg .b32 l;\n.reg .b64 bd;\nsetp.ne.b32 p, %35, 0;\nadd.u32 l, %32, %33;\nmov.b64 bd, {l, %34};\n"
    "wgmma.mma_async.sync.aligned.m64n56k16.f32.bf16.bf16 {%0,%1,%2,%3,%4,%5,%6,%7,%8,%9,%10,%11,%12,%13,%14,%15,%16,%17,%18,%19,%20,%21,%22,%23,%24,%25,%26,%27}, {%28,%29,%30,%31}, bd, p, 1, 1, 1;\n}\n"
    : "+f"(d[0]),"+f"(d[1]),"+f"(d[2]),"+f"(d[3]),"+f"(d[4]),"+f"(d[5]),"+f"(d[6]),"+f"(d[7]),"+f"(d[8]),"+f"(d[9]),"+f"(d[10]),"+f"(d[11]),"+f"(d[12]),"+f"(d[13]),"+f"(d[14]),"+f"(d[15]),"+f"(d[16]),"+f"(d[17]),"+f"(d[18]),"+f"(d[19]),"+f"(d[20]),"+f"(d[21]),"+f"(d[22]),"+f"(d[23]),"+f"(d[24]),"+f"(d[25]),"+f"(d[26]),"+f"(d[27])
    : "r"(a0), "r"(a1), "r"(a2), "r"(a3), "r"(blo), "n"(OFF), "n"(BHI), "n"(ACC));
}

__global__ void k_ln1(const __nv_bfloat16* __restrict__ x) {
  int row = blockIdx.x * 8 + threadIdx.x / 32, lane = threadIdx.x & 31;
  float v[14]; float s = 0;
  for (int i = 0; i < 14; i++) { v[i] = __bfloat162float(x[row * DM + lane + 32 * i]); s += v[i]; }
  for (int o = 16; o; o >>= 1) s += __shfl_xor_sync(~0u, s, o);
  float mean = s / DM, q = 0;
  for (int i = 0; i < 14; i++) q += (v[i] - mean) * (v[i] - mean);
  for (int o = 16; o; o >>= 1) q += __shfl_xor_sync(~0u, q, o);
  float m = rbf(mean), sd = rbf(sqrtf(rbf(rbf(q / DM) + 1e-5f)));
  for (int i = 0; i < 14; i++) g_u[row * DM + lane + 32 * i] = __float2bfloat16_rn(rbf(v[i] - m) / sd);
  if (blockIdx.x == 0 && threadIdx.x == 0) g_epoch = g_epoch + 1;
}
__global__ void k_kgen(const __nv_bfloat16* are, const __nv_bfloat16* aim, const __nv_bfloat16* bre, const __nv_bfloat16* bim,
                       const __nv_bfloat16* cre, const __nv_bfloat16* cim, const __nv_bfloat16* logdt) {
  int d = blockIdx.x;
  float dt = rbf(expf(__bfloat162float(logdt[d])));
  for (int l = threadIdx.x; l < 2048; l += blockDim.x) {
    float lf = rbf((float)l), acc = 0;
    for (int n = 0; n < NST; n++) {
      int i = d * NST + n;
      float lr = dt * __bfloat162float(are[i]), li = dt * __bfloat162float(aim[i]);
      float br = dt * __bfloat162float(bre[i]), bi = dt * __bfloat162float(bim[i]);
      float cr = __bfloat162float(cre[i]), ci = __bfloat162float(cim[i]);
      float wr = cr * br - ci * bi, wi = cr * bi + ci * br;
      float e = expf(lr * lf), sn, cs; sincosf(li * lf, &sn, &cs);
      acc += e * (wr * cs - wi * sn);
    }
    g_kd[d * 2064 + l] = acc;
  }
}
__global__ void k_conv(const __nv_bfloat16* __restrict__ x, const __nv_bfloat16* dskip) {
  __shared__ float sk[2048], su[2048];
  int d = blockIdx.x;
  for (int i = threadIdx.x; i < 2048; i += blockDim.x) { sk[i] = g_kd[d * 2064 + i]; su[i] = __bfloat162float(g_u[i * DM + d]); }
  __syncthreads();
  float ds = __bfloat162float(dskip[d]);
  for (int t = threadIdx.x; t < 2048; t += blockDim.x) {
    float acc = 0;
    for (int l = 0; l <= t; l++) acc += sk[l] * su[t - l];
    float yb = rbf(rbf(acc) + rbf(su[t] * ds));
    float h = rbf(__bfloat162float(x[t * DM + d]) + yb);
    int tau = t >> 3, rt = tau >> 4, mh = (tau >> 3) & 1, c = tau & 7, r = d & 7;
    size_t off = (size_t)rt * 114688 + (d >> 3) * 2048 + mh * 1024 + r * 128 + ((c ^ r) * 16) + (t & 7) * 2;
    *(__nv_bfloat16*)((char*)g_himg + off) = __float2bfloat16_rn(h);
  }
}
__global__ void k_colsum(const __nv_bfloat16* wg, const __nv_bfloat16* wu) {
  int f = blockIdx.x * blockDim.x + threadIdx.x;
  const __nv_bfloat16* w = f < FF ? wg : wu; int ff = f < FF ? f : f - FF;
  float s = 0; for (int d = 0; d < DM; d++) s += __bfloat162float(w[d * FF + ff]);
  g_colsum[f] = s;
}

__global__ void k_pack(const uint4* __restrict__ wg, const uint4* __restrict__ wu, const uint4* __restrict__ wd) {
  int i = blockIdx.x * blockDim.x + threadIdx.x;
  int mat = i / 100352, e = i % 100352;
  if (mat < 2) {
    int d = e / 224, ngg = e % 224;
    int j = ngg / 28, q = (ngg % 28) / 14, ng = ngg % 14 + 14 * mat;
    g_wimg[(size_t)j * 37632 + (q * 14 + (d >> 5)) * 896 + ng * 32 + (d & 31)] = (mat ? wu : wg)[e];
  } else {
    int f = e / 56, ngg = e % 56;
    int j = f / 224, hf = (f % 224) / 112, k = f % 112, c = ngg / 7, ng = ngg % 7;
    g_wimg[(size_t)j * 37632 + 25088 + (c * 2 + hf) * 784 + ng * 112 + k] = wd[e];
  }
}

constexpr int B_SA = 0, B_RING = 114688, B_SLOT = 14336, B_NSLOT = 7;
constexpr int B_STAT = B_RING + B_NSLOT * B_SLOT;
constexpr int B_CS = B_STAT + 1024;
constexpr int B_RED = B_CS + 1792;
constexpr int B_BAR = B_RED + 4096;
constexpr int B_SMEM = B_BAR + 512;

__device__ __forceinline__ void st128(uint4* p, uint32_t a, uint32_t b, uint32_t c, uint32_t d) {
  asm volatile("{\n.reg .b128 v;\n.reg .b64 lo, hi;\nmov.b64 lo, {%1, %2};\nmov.b64 hi, {%3, %4};\nmov.b128 v, {lo, hi};\n"
               "st.relaxed.gpu.global.b128 [%0], v;\n}" ::"l"(p), "r"(a), "r"(b), "r"(c), "r"(d) : "memory");
}
__device__ __forceinline__ void ld128(const uint4* p, uint32_t* r) {
  asm volatile("{\n.reg .b128 v;\n.reg .b64 lo, hi;\nld.relaxed.gpu.global.b128 v, [%4];\nmov.b128 {lo, hi}, v;\n"
               "mov.b64 {%0, %1}, lo;\nmov.b64 {%2, %3}, hi;\n}" : "=r"(r[0]), "=r"(r[1]), "=r"(r[2]), "=r"(r[3]) : "l"(p) : "memory");
}

__device__ __forceinline__ uint32_t mapa(uint32_t a, uint32_t r) { uint32_t o; asm("mapa.shared::cluster.u32 %0, %1, %2;" : "=r"(o) : "r"(a), "r"(r)); return o; }

__global__ void __cluster_dims__(2, 1, 1) __launch_bounds__(384, 1) k_ffn(__nv_bfloat16* __restrict__ out) {
  extern __shared__ __align__(1024) unsigned char sm[];
  const uint32_t sb = s2u(sm);
  const int tid = threadIdx.x, wg = tid >> 7, warp = tid >> 5, lane = tid & 31;
  const int rank = blockIdx.x & 1, p = (blockIdx.x >> 1) & 3, rt = blockIdx.x >> 3, j = 2 * p + rank;
  const uint32_t bar_full = sb + B_BAR, bar_empty = bar_full + 64, bar_h = bar_full + 128, bar_cs = bar_full + 240,
                 bar_afree = bar_full + 248, bar_hh = bar_full + 256;
  if (tid == 0) {
    TR(1, 0);
    for (int i = 0; i < B_NSLOT; i++) { mbar_init(bar_full + 8 * i, 1); mbar_init(bar_empty + 8 * i, 2); }
    for (int i = 0; i < 14; i++) mbar_init(bar_h + 8 * i, 1);
    mbar_init(bar_cs, 1);
    mbar_init(bar_afree, 2);
    for (int i = 0; i < 4; i++) { mbar_init(bar_hh + 8 * i, 1); mbar_expect(bar_hh + 8 * i, 14336); }
    asm volatile("fence.mbarrier_init.release.cluster;" ::: "memory");
  }
  __syncthreads();
  asm volatile("barrier.cluster.arrive.release.aligned;" ::: "memory");

  if (wg == 2) {
    asm volatile("setmaxnreg.dec.sync.aligned.u32 40;");
    if (warp == 8 && lane == 0) {
      const char* wsrc = (const char*)g_wimg + (size_t)j * 602112;
      const char* hsrc = (const char*)g_himg + (size_t)rt * 114688;
      asm volatile("griddepcontrol.wait;" ::: "memory");
      TR(1, 1);
      int slot = 0, ph = 0;
      for (int s = 0; s < 44; s++) {
        if (s < B_NSLOT) {
          mbar_expect(bar_h + 8 * s, 8192);
          bulk_ld(sb + B_SA + s * 8192, hsrc + s * 8192, 8192, bar_h + 8 * s);
        } else {
          if (s == B_NSLOT) {
            for (int i = 7; i < 14; i++) {
              mbar_expect(bar_h + 8 * i, 8192);
              bulk_ld(sb + B_SA + i * 8192, hsrc + i * 8192, 8192, bar_h + 8 * i);
            }
            mbar_expect(bar_cs, 1792);
            bulk_ld(sb + B_CS, g_colsum + 224 * j, 896, bar_cs);
            bulk_ld(sb + B_CS + 896, g_colsum + FF + 224 * j, 896, bar_cs);
          }
          mbar_wait(bar_empty + 8 * slot, ph ^ 1);
        }
        uint32_t dst = sb + B_RING + slot * B_SLOT, fb = bar_full + 8 * slot;
        if (s < 28) {
          mbar_expect(fb, 14336);
          bulk_ld(dst, wsrc + s * 14336, 14336, fb);
        } else {
          const int i = s - 28;
          const int ci = i < 3 ? 0 : i < 6 ? 1 : i < 8 ? i - 6 : i < 12 ? 2 : 3;
          const int kp = i < 3 ? i : i < 6 ? i - 3 : i < 8 ? 3 : (i & 3);
          const int cg = 4 * rank + ((p + 1 + ci) & 3);
          mbar_expect(fb, 12544);
          bulk_ld(dst, (const char*)g_wimg + (size_t)(j ^ (kp >> 1)) * 602112 + 401408 + (cg * 2 + (kp & 1)) * 12544, 12544, fb);
        }
        if (++slot == B_NSLOT) { slot = 0; ph ^= 1; }
      }
    }
    asm volatile("barrier.cluster.wait.acquire.aligned;" ::: "memory");
  } else {
    asm volatile("setmaxnreg.inc.sync.aligned.u32 232;");
    const int g = lane >> 2, t = lane & 3, wq = warp & 3, t128 = tid & 127;
    uint32_t hh[56], hres[16];
    float m0, r0, m1, r1;
    int slot = 0, ph = 0, pslot = 0;
    asm volatile("barrier.cluster.wait.acquire.aligned;" ::: "memory");
    asm volatile("griddepcontrol.wait;" ::: "memory");
    const uint32_t tag = (__ldcg(&g_epoch) & 0xFFFFu) << 16;
    const uint32_t peer_hh = mapa(sb + B_SA + wg * 14336 + t128 * 16, rank ^ 1);
    const uint32_t peer_bar = mapa(bar_hh + 8 * wg, rank ^ 1);
    auto send_hh = [&](int q) {
#pragma unroll
      for (int i = 0; i < 7; i++)
        asm volatile("st.async.weak.shared::cluster.mbarrier::complete_tx::bytes.v4.b32 [%0], {%1, %2, %3, %4}, [%5];"
                     ::"r"(peer_hh + q * 28672 + i * 2048), "r"(hh[28 * q + 4 * i]), "r"(hh[28 * q + 4 * i + 1]),
                       "r"(hh[28 * q + 4 * i + 2]), "r"(hh[28 * q + 4 * i + 3]), "r"(peer_bar + q * 16) : "memory");
    };
    if (wg == 1) asm volatile("bar.sync 3, 256;" ::: "memory");
#pragma unroll
    for (int q = 0; q < 2; q++) {
      float acc[112];
      float s1[8], s2[8];
      const unsigned char* sp = sm + B_SA + wg * 1024 + (t128 >> 6) * 2048 + ((t128 >> 3) & 7) * 128 + (((t128 ^ (t128 >> 3)) & 7) << 4);
      if (q == 0) {
#pragma unroll
        for (int i = 0; i < 8; i++) { s1[i] = 0.f; s2[i] = 0.f; }
      }
#pragma unroll 1
      for (int st = 0; st < 14; st++) {
        if (q == 0) mbar_wait(bar_h + 8 * st, 0);
        mbar_wait(bar_full + 8 * slot, ph);
        uint4 v[4];
        if (q == 0) {
          if (st < 2) {
            v[0] = *(const uint4*)(sp + st * 8192); v[1] = *(const uint4*)(sp + st * 8192 + 4096);
            v[2] = make_uint4(0, 0, 0, 0); v[3] = v[2];
          } else if (st < 8) {
            mbar_wait(bar_h + 8 * (2 * st - 2), 0); mbar_wait(bar_h + 8 * (2 * st - 1), 0);
#pragma unroll
            for (int i = 0; i < 4; i++) v[i] = *(const uint4*)(sp + (2 * st - 2) * 8192 + i * 4096);
          } else if (st < 10) {
            const int o = st == 8 ? 8 : 16;
            v[0].x = __shfl_xor_sync(~0u, __float_as_uint(s1[0]), o); v[0].y = __shfl_xor_sync(~0u, __float_as_uint(s1[1]), o);
            v[0].z = __shfl_xor_sync(~0u, __float_as_uint(s1[2]), o); v[0].w = __shfl_xor_sync(~0u, __float_as_uint(s1[3]), o);
            v[1].x = __shfl_xor_sync(~0u, __float_as_uint(s1[4]), o); v[1].y = __shfl_xor_sync(~0u, __float_as_uint(s1[5]), o);
            v[1].z = __shfl_xor_sync(~0u, __float_as_uint(s1[6]), o); v[1].w = __shfl_xor_sync(~0u, __float_as_uint(s1[7]), o);
            v[2].x = __shfl_xor_sync(~0u, __float_as_uint(s2[0]), o); v[2].y = __shfl_xor_sync(~0u, __float_as_uint(s2[1]), o);
            v[2].z = __shfl_xor_sync(~0u, __float_as_uint(s2[2]), o); v[2].w = __shfl_xor_sync(~0u, __float_as_uint(s2[3]), o);
            v[3].x = __shfl_xor_sync(~0u, __float_as_uint(s2[4]), o); v[3].y = __shfl_xor_sync(~0u, __float_as_uint(s2[5]), o);
            v[3].z = __shfl_xor_sync(~0u, __float_as_uint(s2[6]), o); v[3].w = __shfl_xor_sync(~0u, __float_as_uint(s2[7]), o);
          } else if (st == 10) {
            if (lane < 8) {
              float4* red = (float4*)(sm + B_RED + wg * 2048 + wq * 512 + lane * 64);
#pragma unroll
              for (int k = 0; k < 4; k++) red[k] = make_float4(s1[2 * k], s2[2 * k], s1[2 * k + 1], s2[2 * k + 1]);
            }
          } else if (st == 11) {
            asm volatile("bar.sync %0, 128;" ::"r"(1 + wg) : "memory");
#pragma unroll
            for (int w = 0; w < 4; w++) {
              float2 a = *(const float2*)(sm + B_RED + wg * 2048 + w * 512 + (wq * 16 + g) * 8);
              float2 b = *(const float2*)(sm + B_RED + wg * 2048 + w * 512 + (wq * 16 + g + 8) * 8);
              v[w] = make_uint4(__float_as_uint(a.x), __float_as_uint(a.y), __float_as_uint(b.x), __float_as_uint(b.y));
            }
          } else if (st == 12) {
            mbar_wait(bar_cs, 0);
          }
        } else {
          if (st == 0) {
#pragma unroll
            for (int i = 0; i < 4; i++) {
              int qq = lane >> 3, r = lane & 7, kg = 7 * (4 * rank + p) + 2 * i + (qq >> 1), c = 2 * wq + (qq & 1);
              if (kg > 55) kg = 55;
              uint32_t addr = sb + B_SA + kg * 2048 + wg * 1024 + r * 128 + ((c ^ r) << 4);
              asm volatile("ldmatrix.sync.aligned.m8n8.x4.trans.shared.b16 {%0,%1,%2,%3}, [%4];"
                           : "=r"(hres[4 * i]), "=r"(hres[4 * i + 1]), "=r"(hres[4 * i + 2]), "=r"(hres[4 * i + 3]) : "r"(addr) : "memory");
            }
          } else if (st == 11) {
            mbar_wait(bar_afree, 0);
            send_hh(0);
          }
        }
        wg_fence();
#pragma unroll
        for (int kk = 0; kk < 2; kk++)
          wgmma_ss224(acc, mkdesc(sb + B_SA + (2 * st + kk) * 4096 + wg * 1024, 0, 2048, 1),
                      mkdesc(sb + B_RING + slot * B_SLOT + kk * 256, 128, 512, 0), (st | kk) != 0);
        wg_commit();
        if (q == 0 && st == 0 && tid == 0) TR(1, 3);
        if (q == 0 && st == 4 && tid == 0) TR(1, 21);
        if (q == 0 && st == 8 && tid == 0) TR(1, 22);
        if (q == 0 && st == 11 && tid == 0) TR(1, 23);
        if (q == 0) {
          if (st == 1 && wg == 0) asm volatile("bar.arrive 3, 256;" ::: "memory");
          if (st < 8) {
#pragma unroll
            for (int i = 0; i < 4; i++) {
              float e[8] = {bf_lo(v[i].x), bf_hi(v[i].x), bf_lo(v[i].y), bf_hi(v[i].y), bf_lo(v[i].z), bf_hi(v[i].z), bf_lo(v[i].w), bf_hi(v[i].w)};
#pragma unroll
              for (int k = 0; k < 8; k++) { s1[k] += e[k]; s2[k] = fmaf(e[k], e[k], s2[k]); }
            }
          } else if (st < 10) {
            s1[0] += __uint_as_float(v[0].x); s1[1] += __uint_as_float(v[0].y); s1[2] += __uint_as_float(v[0].z); s1[3] += __uint_as_float(v[0].w);
            s1[4] += __uint_as_float(v[1].x); s1[5] += __uint_as_float(v[1].y); s1[6] += __uint_as_float(v[1].z); s1[7] += __uint_as_float(v[1].w);
            s2[0] += __uint_as_float(v[2].x); s2[1] += __uint_as_float(v[2].y); s2[2] += __uint_as_float(v[2].z); s2[3] += __uint_as_float(v[2].w);
            s2[4] += __uint_as_float(v[3].x); s2[5] += __uint_as_float(v[3].y); s2[6] += __uint_as_float(v[3].z); s2[7] += __uint_as_float(v[3].w);
          } else if (st == 11) {
            float a0 = 0.f, b0 = 0.f, a1 = 0.f, b1 = 0.f;
#pragma unroll
            for (int w = 0; w < 4; w++) { a0 += __uint_as_float(v[w].x); b0 += __uint_as_float(v[w].y); a1 += __uint_as_float(v[w].z); b1 += __uint_as_float(v[w].w); }
            a0 *= 1.f / DM; a1 *= 1.f / DM;
            b0 = fmaxf(fmaf(-a0, a0, b0 * (1.f / DM)), 0.f); b1 = fmaxf(fmaf(-a1, a1, b1 * (1.f / DM)), 0.f);
            s1[0] = -rbf(a0); s1[1] = 1.f / rbf(sqrtf(rbf(rbf(b0) + 1e-5f)));
            s1[2] = -rbf(a1); s1[3] = 1.f / rbf(sqrtf(rbf(rbf(b1) + 1e-5f)));
          }
        }
        if (st > 0) {
          wg_wait<1>();
          if (t128 == 0) {
            mbar_arrive(bar_empty + 8 * pslot);
            if (q == 1 && st == 8) asm volatile("mbarrier.arrive.shared::cluster.b64 _, [%0];" ::"r"(mapa(bar_afree, rank ^ 1)) : "memory");
          }
        }
        pslot = slot;
        if (++slot == B_NSLOT) { slot = 0; ph ^= 1; }
      }
      if (q == 0) {
        m0 = s1[0]; r0 = s1[1]; m1 = s1[2]; r1 = s1[3];
        if (tid == 0) TR(1, 4);
      }
      float2 cg[14], cu[14];
#pragma unroll
      for (int i = 0; i < 14; i++) {
        asm volatile("ld.shared.v2.f32 {%0, %1}, [%2];" : "=f"(cg[i].x), "=f"(cg[i].y) : "r"(sb + B_CS + (112 * q + 8 * i + 2 * t) * 4) : "memory");
        asm volatile("ld.shared.v2.f32 {%0, %1}, [%2];" : "=f"(cu[i].x), "=f"(cu[i].y) : "r"(sb + B_CS + (224 + 112 * q + 8 * i + 2 * t) * 4) : "memory");
      }
      wg_wait<0>();
      reg_fence(acc);
      if (t128 == 0) mbar_arrive(bar_empty + 8 * pslot);
#pragma unroll
      for (int i = 0; i < 14; i++) {
        uint32_t g0 = pack_bf16(fmaf(m0, cg[i].x, acc[4 * i]) * r0, fmaf(m0, cg[i].y, acc[4 * i + 1]) * r0);
        uint32_t g1 = pack_bf16(fmaf(m1, cg[i].x, acc[4 * i + 2]) * r1, fmaf(m1, cg[i].y, acc[4 * i + 3]) * r1);
        uint32_t u0 = pack_bf16(fmaf(m0, cu[i].x, acc[56 + 4 * i]) * r0, fmaf(m0, cu[i].y, acc[56 + 4 * i + 1]) * r0);
        uint32_t u1 = pack_bf16(fmaf(m1, cu[i].x, acc[56 + 4 * i + 2]) * r1, fmaf(m1, cu[i].y, acc[56 + 4 * i + 3]) * r1);
        hh[28 * q + 2 * i] = hmul2_bf(g0, u0); hh[28 * q + 2 * i + 1] = hmul2_bf(g1, u1);
      }
      if (tid == 0) TR(1, 5 + q);
    }
    float accA[28], accB[28], accC[28];
    uint32_t ph0[28], ph1[28];
    const uint32_t blo = (((sb + B_RING) & 0x3FFFF) >> 4) | (8u << 16);
#define ISSUE(acc, I, a, FIRST) do { \
      constexpr int s_ = 28 + (I), sl_ = s_ % B_NSLOT; \
      mbar_wait(bar_full + 8 * sl_, (s_ / B_NSLOT) & 1); \
      wg_fence(); \
      wgmma_rs56<(sl_ * B_SLOT + 0 * 256) / 16, 112, !(FIRST)>(acc, (a)[0], (a)[1], (a)[2], (a)[3], blo); \
      wgmma_rs56<(sl_ * B_SLOT + 1 * 256) / 16, 112, 1>(acc, (a)[4], (a)[5], (a)[6], (a)[7], blo); \
      wgmma_rs56<(sl_ * B_SLOT + 2 * 256) / 16, 112, 1>(acc, (a)[8], (a)[9], (a)[10], (a)[11], blo); \
      wgmma_rs56<(sl_ * B_SLOT + 3 * 256) / 16, 112, 1>(acc, (a)[12], (a)[13], (a)[14], (a)[15], blo); \
      wgmma_rs56<(sl_ * B_SLOT + 4 * 256) / 16, 112, 1>(acc, (a)[16], (a)[17], (a)[18], (a)[19], blo); \
      wgmma_rs56<(sl_ * B_SLOT + 5 * 256) / 16, 112, 1>(acc, (a)[20], (a)[21], (a)[22], (a)[23], blo); \
      wgmma_rs56<(sl_ * B_SLOT + 6 * 256) / 16, 112, 1>(acc, (a)[24], (a)[25], (a)[26], (a)[27], blo); \
      wg_commit(); } while (0)
    auto rel = [&](int i) { if (t128 == 0) mbar_arrive(bar_empty + 8 * ((28 + i) % B_NSLOT)); };
    auto load_hh = [&](uint32_t (&d)[28], int q) {
      mbar_wait(bar_hh + 16 * q + 8 * wg, 0);
#pragma unroll
      for (int i = 0; i < 7; i++) {
        uint4 v = *(const uint4*)(sm + B_SA + q * 28672 + wg * 14336 + i * 2048 + t128 * 16);
        d[4 * i] = v.x; d[4 * i + 1] = v.y; d[4 * i + 2] = v.z; d[4 * i + 3] = v.w;
      }
    };
    auto send = [&](float (&acc)[28], int ci) {
      reg_fence(acc);
      uint4* dst = g_part + (size_t)((rt * 8 + ((p + 1 + ci) & 3) * 2 + rank) * 3 + ci) * 1024 + wg * 512 + t128;
#pragma unroll
      for (int q = 0; q < 4; q++)
        st128(dst + q * 128, pack_bf16(acc[7 * q], acc[7 * q + 1]), pack_bf16(acc[7 * q + 2], acc[7 * q + 3]),
              pack_bf16(acc[7 * q + 4], acc[7 * q + 5]), (pack_bf16(acc[7 * q + 6], 0.f) & 0xFFFFu) | tag);
    };
    auto fetch = [&](uint32_t (&in)[16], int ci) {
      const uint4* src = g_part + (size_t)(blockIdx.x * 3 + ci) * 1024 + wg * 512 + t128;
#pragma unroll
      for (int i = 0; i < 4; i++) ld128(src + i * 128, in + 4 * i);
    };
    auto valid = [&](uint32_t (&in)[16]) {
      bool ok = (((in[3] ^ tag) | (in[7] ^ tag) | (in[11] ^ tag) | (in[15] ^ tag)) & 0xFFFF0000u) == 0;
      return __all_sync(~0u, ok) != 0;
    };
    auto accum = [&](float (&sum)[28], uint32_t (&in)[16], int ci) {
      int it = 0;
      while (!valid(in) && ++it < 200000) fetch(in, ci);
#pragma unroll
      for (int q = 0; q < 4; q++) {
        sum[7 * q] += bf_lo(in[4 * q]); sum[7 * q + 1] += bf_hi(in[4 * q]);
        sum[7 * q + 2] += bf_lo(in[4 * q + 1]); sum[7 * q + 3] += bf_hi(in[4 * q + 1]);
        sum[7 * q + 4] += bf_lo(in[4 * q + 2]); sum[7 * q + 5] += bf_hi(in[4 * q + 2]);
        sum[7 * q + 6] += bf_lo(in[4 * q + 3]);
      }
    };
    ISSUE(accA, 0, hh, true);
    send_hh(1);
    ISSUE(accA, 1, hh + 28, false);
    load_hh(ph0, 0);
    wg_wait<1>(); rel(0);
    ISSUE(accA, 2, ph0, false);      wg_wait<1>(); rel(1);
    ISSUE(accB, 3, hh, true);        wg_wait<1>(); rel(2);
    ISSUE(accB, 4, hh + 28, false);  wg_wait<1>(); rel(3);
    ISSUE(accB, 5, ph0, false);
    if (tid == 0) TR(1, 11);
    load_hh(ph1, 1);
    if (tid == 0) TR(1, 12);
    wg_wait<1>(); rel(4);
    ISSUE(accA, 6, ph1, false);      wg_wait<1>(); rel(5);
    ISSUE(accB, 7, ph1, false);      wg_wait<1>(); rel(6);
    ISSUE(accC, 8, hh, true);        send(accA, 0); wg_wait<1>(); rel(7);
    ISSUE(accC, 9, hh + 28, false);  send(accB, 1); wg_wait<1>(); rel(8);
    if (tid == 0) TR(1, 13);
    ISSUE(accC, 10, ph0, false);
    ISSUE(accC, 11, ph1, false);
    ISSUE(accA, 12, hh, true);
    ISSUE(accA, 13, hh + 28, false);
    wg_wait<2>();
    send(accC, 2);
    if (tid == 0) TR(1, 14);
    ISSUE(accA, 14, ph0, false);
    ISSUE(accA, 15, ph1, false);
    uint32_t in0[16], in1[16], in2[16];
    fetch(in0, 0); fetch(in1, 1);
    if (tid == 0) TR(1, 7);
#pragma unroll
    for (int i = 0; i < 28; i++) accB[i] = 0.f;
    accum(accB, in0, 0); accum(accB, in1, 1);
    wg_wait<1>();
    if (tid == 0) TR(1, 8);
    fetch(in2, 2);
    accum(accB, in2, 2);
    wg_wait<0>();
    reg_fence(accA);
    if (tid == 0) TR(1, 9);
    const int row = rt * 128 + wg * 64 + wq * 16 + g;
    uint32_t* o0 = (uint32_t*)(out + (size_t)row * DM + 56 * (4 * rank + p) + 2 * t);
    uint32_t* o1 = o0 + 8 * DM / 2;
#pragma unroll
    for (int i = 0; i < 7; i++) {
      o0[4 * i] = hadd2_bf(hres[2 * i], pack_bf16(accA[4 * i] + accB[4 * i], accA[4 * i + 1] + accB[4 * i + 1]));
      o1[4 * i] = hadd2_bf(hres[2 * i + 1], pack_bf16(accA[4 * i + 2] + accB[4 * i + 2], accA[4 * i + 3] + accB[4 * i + 3]));
    }
    if (tid == 0) TR(1, 10);
    if (tid == 128) TR(1, 15);
  }
}

extern "C" void kernel_launch(void* const* d_in, const int* in_sizes, int n_in, void* d_out, int out_size) {
  const __nv_bfloat16* x = (const __nv_bfloat16*)d_in[0];
  const __nv_bfloat16 *are = (const __nv_bfloat16*)d_in[1], *aim = (const __nv_bfloat16*)d_in[2], *bre = (const __nv_bfloat16*)d_in[3],
                      *bim = (const __nv_bfloat16*)d_in[4], *cre = (const __nv_bfloat16*)d_in[5], *cim = (const __nv_bfloat16*)d_in[6],
                      *logdt = (const __nv_bfloat16*)d_in[7], *dskip = (const __nv_bfloat16*)d_in[8];
  const __nv_bfloat16 *wg = (const __nv_bfloat16*)d_in[10], *wu = (const __nv_bfloat16*)d_in[11], *wd = (const __nv_bfloat16*)d_in[12];

  static bool init = false;
  if (!init) {
    init = true;
    cudaFuncSetAttribute(k_ffn, cudaFuncAttributeMaxDynamicSharedMemorySize, B_SMEM);
  }
  cudaStream_t st = cudaStreamPerThread;
  k_ln1<<<256, 256, 0, st>>>(x);
  k_kgen<<<DM, 512, 0, st>>>(are, aim, bre, bim, cre, cim, logdt);
  k_conv<<<DM, 512, 0, st>>>(x, dskip);
  k_colsum<<<2 * FF / 128, 128, 0, st>>>(wg, wu);
  k_pack<<<3 * 100352 / 256, 256, 0, st>>>((const uint4*)wg, (const uint4*)wu, (const uint4*)wd);
  k_ffn<<<128, 384, B_SMEM, st>>>((__nv_bfloat16*)d_out);
}
```

```cpp
#include <cuda_runtime.h>
#include <cuda_bf16.h>
#include <stdint.h>

constexpr int LSEQ = 2048, DM = 448, FF = 1792, NST = 256;

__device__ uint4    g_himg[16 * 114688 / 16];
__device__ float    g_colsum[2 * FF];
__device__ uint4    g_part[128 * 7 * 896];
__device__ uint4    g_wimg[8 * 602112 / 16];
__device__ unsigned g_epoch;
__device__ __nv_bfloat16 g_u[LSEQ * DM];
__device__ float    g_kd[DM * 2064];

#define TR(k, i) do {} while (0)
__device__ __forceinline__ uint32_t s2u(const void* p) { return (uint32_t)__cvta_generic_to_shared(p); }
__device__ __forceinline__ void mbar_init(uint32_t b, int c) { asm volatile("mbarrier.init.shared::cta.b64 [%0], %1;" ::"r"(b), "r"(c)); }
__device__ __forceinline__ void mbar_expect(uint32_t b, int bytes) { asm volatile("mbarrier.arrive.expect_tx.shared::cta.b64 _, [%0], %1;" ::"r"(b), "r"(bytes) : "memory"); }
__device__ __forceinline__ void mbar_arrive(uint32_t b) { asm volatile("mbarrier.arrive.shared::cta.b64 _, [%0];" ::"r"(b) : "memory"); }
__device__ __forceinline__ void mbar_wait(uint32_t b, int ph) {
  asm volatile("{\n.reg .pred p;\nLW:\nmbarrier.try_wait.parity.shared::cta.b64 p, [%0], %1;\n@p bra LD;\nbra LW;\nLD:\n}" ::"r"(b), "r"(ph) : "memory");
}
__device__ __forceinline__ uint64_t mkdesc(uint32_t addr, uint32_t lbo, uint32_t sbo, uint32_t sw) {
  return (uint64_t)((addr & 0x3FFFF) >> 4) | ((uint64_t)((lbo >> 4) & 0x3FFF) << 16) | ((uint64_t)((sbo >> 4) & 0x3FFF) << 32) | ((uint64_t)sw << 62);
}
__device__ __forceinline__ void wg_fence() { asm volatile("wgmma.fence.sync.aligned;" ::: "memory"); }
__device__ __forceinline__ void wg_commit() { asm volatile("wgmma.commit_group.sync.aligned;" ::: "memory"); }
template <int N> __device__ __forceinline__ void wg_wait() { asm volatile("wgmma.wait_group.sync.aligned %0;" ::"n"(N) : "memory"); }
template <int N> __device__ __forceinline__ void reg_fence(float (&a)[N]) {
#pragma unroll
  for (int i = 0; i < N; i++) asm volatile("" : "+f"(a[i])::"memory");
}
__device__ __forceinline__ uint32_t pack_bf16(float lo, float hi) {
  uint32_t r; asm("cvt.rn.bf16x2.f32 %0, %1, %2;" : "=r"(r) : "f"(hi), "f"(lo)); return r;
}
__device__ __forceinline__ float bf_lo(uint32_t v) { return __uint_as_float(v << 16); }
__device__ __forceinline__ float bf_hi(uint32_t v) { return __uint_as_float(v & 0xFFFF0000u); }
__device__ __forceinline__ float rbf(float x) { return __bfloat162float(__float2bfloat16_rn(x)); }
__device__ __forceinline__ uint32_t hmul2_bf(uint32_t a, uint32_t b) { uint32_t r; asm("mul.rn.bf16x2 %0, %1, %2;" : "=r"(r) : "r"(a), "r"(b)); return r; }
__device__ __forceinline__ uint32_t hadd2_bf(uint32_t a, uint32_t b) { uint32_t r; asm("add.rn.bf16x2 %0, %1, %2;" : "=r"(r) : "r"(a), "r"(b)); return r; }
__device__ __forceinline__ void bulk_ld(uint32_t dst, const void* src, int bytes, uint32_t bar) {
  asm volatile("cp.async.bulk.shared::cluster.global.mbarrier::complete_tx::bytes [%0], [%1], %2, [%3];"
               ::"r"(dst), "l"(src), "r"(bytes), "r"(bar) : "memory");
}

__device__ __forceinline__ void bulk_ld_mc(uint32_t dst, const void* src, int bytes, uint32_t bar) {
  asm volatile("cp.async.bulk.shared::cluster.global.mbarrier::complete_tx::bytes.multicast::cluster [%0], [%1], %2, [%3], %4;"
               ::"r"(dst), "l"(src), "r"(bytes), "r"(bar), "h"((uint16_t)3) : "memory");
}
__device__ __forceinline__ void wgmma_ss224(float (&d)[112], uint64_t a, uint64_t b, int acc) {
  asm volatile("{\n.reg .pred p;\nsetp.ne.b32 p, %114, 0;\n"
    "wgmma.mma_async.sync.aligned.m64n224k16.f32.bf16.bf16 {%0,%1,%2,%3,%4,%5,%6,%7,%8,%9,%10,%11,%12,%13,%14,%15,%16,%17,%18,%19,%20,%21,%22,%23,%24,%25,%26,%27,%28,%29,%30,%31,%32,%33,%34,%35,%36,%37,%38,%39,%40,%41,%42,%43,%44,%45,%46,%47,%48,%49,%50,%51,%52,%53,%54,%55,%56,%57,%58,%59,%60,%61,%62,%63,%64,%65,%66,%67,%68,%69,%70,%71,%72,%73,%74,%75,%76,%77,%78,%79,%80,%81,%82,%83,%84,%85,%86,%87,%88,%89,%90,%91,%92,%93,%94,%95,%96,%97,%98,%99,%100,%101,%102,%103,%104,%105,%106,%107,%108,%109,%110,%111}, %112, %113, p, 1, 1, 1, 1;\n}\n"
    : "+f"(d[0]),"+f"(d[1]),"+f"(d[2]),"+f"(d[3]),"+f"(d[4]),"+f"(d[5]),"+f"(d[6]),"+f"(d[7]),"+f"(d[8]),"+f"(d[9]),"+f"(d[10]),"+f"(d[11]),"+f"(d[12]),"+f"(d[13]),"+f"(d[14]),"+f"(d[15]),"+f"(d[16]),"+f"(d[17]),"+f"(d[18]),"+f"(d[19]),"+f"(d[20]),"+f"(d[21]),"+f"(d[22]),"+f"(d[23]),"+f"(d[24]),"+f"(d[25]),"+f"(d[26]),"+f"(d[27]),"+f"(d[28]),"+f"(d[29]),"+f"(d[30]),"+f"(d[31]),"+f"(d[32]),"+f"(d[33]),"+f"(d[34]),"+f"(d[35]),"+f"(d[36]),"+f"(d[37]),"+f"(d[38]),"+f"(d[39]),"+f"(d[40]),"+f"(d[41]),"+f"(d[42]),"+f"(d[43]),"+f"(d[44]),"+f"(d[45]),"+f"(d[46]),"+f"(d[47]),"+f"(d[48]),"+f"(d[49]),"+f"(d[50]),"+f"(d[51]),"+f"(d[52]),"+f"(d[53]),"+f"(d[54]),"+f"(d[55]),"+f"(d[56]),"+f"(d[57]),"+f"(d[58]),"+f"(d[59]),"+f"(d[60]),"+f"(d[61]),"+f"(d[62]),"+f"(d[63]),"+f"(d[64]),"+f"(d[65]),"+f"(d[66]),"+f"(d[67]),"+f"(d[68]),"+f"(d[69]),"+f"(d[70]),"+f"(d[71]),"+f"(d[72]),"+f"(d[73]),"+f"(d[74]),"+f"(d[75]),"+f"(d[76]),"+f"(d[77]),"+f"(d[78]),"+f"(d[79]),"+f"(d[80]),"+f"(d[81]),"+f"(d[82]),"+f"(d[83]),"+f"(d[84]),"+f"(d[85]),"+f"(d[86]),"+f"(d[87]),"+f"(d[88]),"+f"(d[89]),"+f"(d[90]),"+f"(d[91]),"+f"(d[92]),"+f"(d[93]),"+f"(d[94]),"+f"(d[95]),"+f"(d[96]),"+f"(d[97]),"+f"(d[98]),"+f"(d[99]),"+f"(d[100]),"+f"(d[101]),"+f"(d[102]),"+f"(d[103]),"+f"(d[104]),"+f"(d[105]),"+f"(d[106]),"+f"(d[107]),"+f"(d[108]),"+f"(d[109]),"+f"(d[110]),"+f"(d[111])
    : "l"(a), "l"(b), "r"(acc));
}
template <int OFF, uint32_t BHI, int ACC>
__device__ __forceinline__ void wgmma_rs56(float (&d)[28], uint32_t a0, uint32_t a1, uint32_t a2, uint32_t a3, uint32_t blo) {
  asm volatile("{\n.reg .pred p;\n.reg .b32 l;\n.reg .b64 bd;\nsetp.ne.b32 p, %35, 0;\nadd.u32 l, %32, %33;\nmov.b64 bd, {l, %34};\n"
    "wgmma.mma_async.sync.aligned.m64n56k16.f32.bf16.bf16 {%0,%1,%2,%3,%4,%5,%6,%7,%8,%9,%10,%11,%12,%13,%14,%15,%16,%17,%18,%19,%20,%21,%22,%23,%24,%25,%26,%27}, {%28,%29,%30,%31}, bd, p, 1, 1, 1;\n}\n"
    : "+f"(d[0]),"+f"(d[1]),"+f"(d[2]),"+f"(d[3]),"+f"(d[4]),"+f"(d[5]),"+f"(d[6]),"+f"(d[7]),"+f"(d[8]),"+f"(d[9]),"+f"(d[10]),"+f"(d[11]),"+f"(d[12]),"+f"(d[13]),"+f"(d[14]),"+f"(d[15]),"+f"(d[16]),"+f"(d[17]),"+f"(d[18]),"+f"(d[19]),"+f"(d[20]),"+f"(d[21]),"+f"(d[22]),"+f"(d[23]),"+f"(d[24]),"+f"(d[25]),"+f"(d[26]),"+f"(d[27])
    : "r"(a0), "r"(a1), "r"(a2), "r"(a3), "r"(blo), "n"(OFF), "n"(BHI), "n"(ACC));
}

__global__ void k_ln1(const __nv_bfloat16* __restrict__ x) {
  int row = blockIdx.x * 8 + threadIdx.x / 32, lane = threadIdx.x & 31;
  float v[14]; float s = 0;
  for (int i = 0; i < 14; i++) { v[i] = __bfloat162float(x[row * DM + lane + 32 * i]); s += v[i]; }
  for (int o = 16; o; o >>= 1) s += __shfl_xor_sync(~0u, s, o);
  float mean = s / DM, q = 0;
  for (int i = 0; i < 14; i++) q += (v[i] - mean) * (v[i] - mean);
  for (int o = 16; o; o >>= 1) q += __shfl_xor_sync(~0u, q, o);
  float m = rbf(mean), sd = rbf(sqrtf(rbf(rbf(q / DM) + 1e-5f)));
  for (int i = 0; i < 14; i++) g_u[row * DM + lane + 32 * i] = __float2bfloat16_rn(rbf(v[i] - m) / sd);
  if (blockIdx.x == 0 && threadIdx.x == 0) g_epoch = g_epoch + 1;
}
__global__ void k_kgen(const __nv_bfloat16* are, const __nv_bfloat16* aim, const __nv_bfloat16* bre, const __nv_bfloat16* bim,
                       const __nv_bfloat16* cre, const __nv_bfloat16* cim, const __nv_bfloat16* logdt) {
  int d = blockIdx.x;
  float dt = rbf(expf(__bfloat162float(logdt[d])));
  for (int l = threadIdx.x; l < 2048; l += blockDim.x) {
    float lf = rbf((float)l), acc = 0;
    for (int n = 0; n < NST; n++) {
      int i = d * NST + n;
      float lr = dt * __bfloat162float(are[i]), li = dt * __bfloat162float(aim[i]);
      float br = dt * __bfloat162float(bre[i]), bi = dt * __bfloat162float(bim[i]);
      float cr = __bfloat162float(cre[i]), ci = __bfloat162float(cim[i]);
      float wr = cr * br - ci * bi, wi = cr * bi + ci * br;
      float e = expf(lr * lf), sn, cs; sincosf(li * lf, &sn, &cs);
      acc += e * (wr * cs - wi * sn);
    }
    g_kd[d * 2064 + l] = acc;
  }
}
__global__ void k_conv(const __nv_bfloat16* __restrict__ x, const __nv_bfloat16* dskip) {
  __shared__ float sk[2048], su[2048];
  int d = blockIdx.x;
  for (int i = threadIdx.x; i < 2048; i += blockDim.x) { sk[i] = g_kd[d * 2064 + i]; su[i] = __bfloat162float(g_u[i * DM + d]); }
  __syncthreads();
  float ds = __bfloat162float(dskip[d]);
  for (int t = threadIdx.x; t < 2048; t += blockDim.x) {
    float acc = 0;
    for (int l = 0; l <= t; l++) acc += sk[l] * su[t - l];
    float yb = rbf(rbf(acc) + rbf(su[t] * ds));
    float h = rbf(__bfloat162float(x[t * DM + d]) + yb);
    int tau = t >> 3, rt = tau >> 4, mh = (tau >> 3) & 1, c = tau & 7, r = d & 7;
    size_t off = (size_t)rt * 114688 + (d >> 3) * 2048 + mh * 1024 + r * 128 + ((c ^ r) * 16) + (t & 7) * 2;
    *(__nv_bfloat16*)((char*)g_himg + off) = __float2bfloat16_rn(h);
  }
}
__global__ void k_colsum(const __nv_bfloat16* wg, const __nv_bfloat16* wu) {
  int f = blockIdx.x * blockDim.x + threadIdx.x;
  const __nv_bfloat16* w = f < FF ? wg : wu; int ff = f < FF ? f : f - FF;
  float s = 0; for (int d = 0; d < DM; d++) s += __bfloat162float(w[d * FF + ff]);
  g_colsum[f] = s;
}

__global__ void k_pack(const uint4* __restrict__ wg, const uint4* __restrict__ wu, const uint4* __restrict__ wd) {
  int i = blockIdx.x * blockDim.x + threadIdx.x;
  int mat = i / 100352, e = i % 100352;
  if (mat < 2) {
    int d = e / 224, ngg = e % 224;
    int j = ngg / 28, q = (ngg % 28) / 14, ng = ngg % 14 + 14 * mat;
    g_wimg[(size_t)j * 37632 + (q * 14 + (d >> 5)) * 896 + ng * 32 + (d & 31)] = (mat ? wu : wg)[e];
  } else {
    int f = e / 56, ngg = e % 56;
    int j = f / 224, hf = (f % 224) / 112, k = f % 112, c = ngg / 7, ng = ngg % 7;
    g_wimg[(size_t)j * 37632 + 25088 + (c * 2 + hf) * 784 + ng * 112 + k] = wd[e];
  }
}

constexpr int B_SA = 0, B_RING = 114688, B_SLOT = 14336, B_NSLOT = 7;
constexpr int B_STAT = B_RING + B_NSLOT * B_SLOT;
constexpr int B_CS = B_STAT + 1024;
constexpr int B_RED = B_CS + 1792;
constexpr int B_BAR = B_RED + 4096;
constexpr int B_SMEM = B_BAR + 512;

__device__ __forceinline__ void st128(uint4* p, uint32_t a, uint32_t b, uint32_t c, uint32_t d) {
  asm volatile("{\n.reg .b128 v;\n.reg .b64 lo, hi;\nmov.b64 lo, {%1, %2};\nmov.b64 hi, {%3, %4};\nmov.b128 v, {lo, hi};\n"
               "st.relaxed.gpu.global.b128 [%0], v;\n}" ::"l"(p), "r"(a), "r"(b), "r"(c), "r"(d) : "memory");
}
__device__ __forceinline__ void ld128(const uint4* p, uint32_t* r) {
  asm volatile("{\n.reg .b128 v;\n.reg .b64 lo, hi;\nld.relaxed.gpu.global.b128 v, [%4];\nmov.b128 {lo, hi}, v;\n"
               "mov.b64 {%0, %1}, lo;\nmov.b64 {%2, %3}, hi;\n}" : "=r"(r[0]), "=r"(r[1]), "=r"(r[2]), "=r"(r[3]) : "l"(p) : "memory");
}

__device__ __forceinline__ uint32_t mapa(uint32_t a, uint32_t r) { uint32_t o; asm("mapa.shared::cluster.u32 %0, %1, %2;" : "=r"(o) : "r"(a), "r"(r)); return o; }

__global__ void __cluster_dims__(2, 1, 1) __launch_bounds__(384, 1) k_ffn(__nv_bfloat16* __restrict__ out) {
  extern __shared__ __align__(1024) unsigned char sm[];
  const uint32_t sb = s2u(sm);
  const int tid = threadIdx.x, wg = tid >> 7, warp = tid >> 5, lane = tid & 31;
  const int rank = blockIdx.x & 1, rt = blockIdx.x & 15, j = blockIdx.x >> 4;
  const uint32_t bar_full = sb + B_BAR, bar_empty = bar_full + 64, bar_h = bar_full + 128, bar_cs = bar_full + 240;
  if (tid == 0) {
    TR(1, 0);
    for (int i = 0; i < B_NSLOT; i++) { mbar_init(bar_full + 8 * i, 1); mbar_init(bar_empty + 8 * i, 4); }
    for (int i = 0; i < 14; i++) mbar_init(bar_h + 8 * i, 1);
    mbar_init(bar_cs, 1);
    asm volatile("fence.mbarrier_init.release.cluster;" ::: "memory");
  }
  __syncthreads();
  asm volatile("barrier.cluster.arrive.release.aligned;" ::: "memory");

  if (wg == 2) {
    asm volatile("setmaxnreg.dec.sync.aligned.u32 40;");
    asm volatile("barrier.cluster.wait.acquire.aligned;" ::: "memory");
    if (warp == 8 && lane == 0) {
      const char* wsrc = (const char*)g_wimg + (size_t)j * 602112;
      asm volatile("griddepcontrol.wait;" ::: "memory");
      TR(1, 1);
      int slot = 0, ph = 0;
      for (int s = 0; s < 44; s++) {
        if (s >= B_NSLOT) mbar_wait(bar_empty + 8 * slot, ph ^ 1);
        uint32_t dst = sb + B_RING + slot * B_SLOT, fb = bar_full + 8 * slot;
        if (s < 28) {
          mbar_expect(fb, 14336);
          bulk_ld_mc(dst + rank * 7168, wsrc + s * 14336 + rank * 7168, 7168, fb);
        } else {
          const int c = (j + 1 + ((s - 28) >> 1)) & 7;
          mbar_expect(fb, 12544);
          bulk_ld_mc(dst + rank * 6272, wsrc + 401408 + (c * 2 + (s & 1)) * 12544 + rank * 6272, 6272, fb);
        }
        if (++slot == B_NSLOT) { slot = 0; ph ^= 1; }
      }
    } else if (warp == 9 && lane == 0) {
      const char* hsrc = (const char*)g_himg + (size_t)rt * 114688;
      asm volatile("griddepcontrol.wait;" ::: "memory");
      for (int i = 0; i < 14; i++) {
        mbar_expect(bar_h + 8 * i, 8192);
        bulk_ld(sb + B_SA + i * 8192, hsrc + i * 8192, 8192, bar_h + 8 * i);
      }
      mbar_expect(bar_cs, 1792);
      bulk_ld(sb + B_CS, g_colsum + 224 * j, 896, bar_cs);
      bulk_ld(sb + B_CS + 896, g_colsum + FF + 224 * j, 896, bar_cs);
    }
  } else {
    asm volatile("setmaxnreg.inc.sync.aligned.u32 232;");
    const int g = lane >> 2, t = lane & 3, wq = warp & 3, t128 = tid & 127;
    uint32_t hh[56], hres[16];
    float m0, r0, m1, r1;
    int slot = 0, ph = 0, pslot = 0;
    asm volatile("barrier.cluster.wait.acquire.aligned;" ::: "memory");
    asm volatile("griddepcontrol.wait;" ::: "memory");
    const uint32_t tag = (__ldcg(&g_epoch) & 1u) << 16;
    const uint32_t rel_bar = mapa(bar_empty, t128 & 1);
    auto release = [&](int sl) { if (t128 < 2) asm volatile("mbarrier.arrive.shared::cluster.b64 _, [%0];" ::"r"(rel_bar + 8 * sl) : "memory"); };
    if (wg == 1) asm volatile("bar.sync 3, 256;" ::: "memory");
#pragma unroll
    for (int q = 0; q < 2; q++) {
      float acc[112];
      float s1[8], s2[8];
      const unsigned char* sp = sm + B_SA + wg * 1024 + (t128 >> 6) * 2048 + ((t128 >> 3) & 7) * 128 + (((t128 ^ (t128 >> 3)) & 7) << 4);
      if (q == 0) {
#pragma unroll
        for (int i = 0; i < 8; i++) { s1[i] = 0.f; s2[i] = 0.f; }
      }
#pragma unroll 1
      for (int st = 0; st < 14; st++) {
        if (q == 0) mbar_wait(bar_h + 8 * st, 0);
        mbar_wait(bar_full + 8 * slot, ph);
        uint4 v[4];
        if (q == 0) {
          if (st < 2) {
            v[0] = *(const uint4*)(sp + st * 8192); v[1] = *(const uint4*)(sp + st * 8192 + 4096);
            v[2] = make_uint4(0, 0, 0, 0); v[3] = v[2];
          } else if (st < 8) {
            mbar_wait(bar_h + 8 * (2 * st - 2), 0); mbar_wait(bar_h + 8 * (2 * st - 1), 0);
#pragma unroll
            for (int i = 0; i < 4; i++) v[i] = *(const uint4*)(sp + (2 * st - 2) * 8192 + i * 4096);
          } else if (st < 10) {
            const int o = st == 8 ? 8 : 16;
            v[0].x = __shfl_xor_sync(~0u, __float_as_uint(s1[0]), o); v[0].y = __shfl_xor_sync(~0u, __float_as_uint(s1[1]), o);
            v[0].z = __shfl_xor_sync(~0u, __float_as_uint(s1[2]), o); v[0].w = __shfl_xor_sync(~0u, __float_as_uint(s1[3]), o);
            v[1].x = __shfl_xor_sync(~0u, __float_as_uint(s1[4]), o); v[1].y = __shfl_xor_sync(~0u, __float_as_uint(s1[5]), o);
            v[1].z = __shfl_xor_sync(~0u, __float_as_uint(s1[6]), o); v[1].w = __shfl_xor_sync(~0u, __float_as_uint(s1[7]), o);
            v[2].x = __shfl_xor_sync(~0u, __float_as_uint(s2[0]), o); v[2].y = __shfl_xor_sync(~0u, __float_as_uint(s2[1]), o);
            v[2].z = __shfl_xor_sync(~0u, __float_as_uint(s2[2]), o); v[2].w = __shfl_xor_sync(~0u, __float_as_uint(s2[3]), o);
            v[3].x = __shfl_xor_sync(~0u, __float_as_uint(s2[4]), o); v[3].y = __shfl_xor_sync(~0u, __float_as_uint(s2[5]), o);
            v[3].z = __shfl_xor_sync(~0u, __float_as_uint(s2[6]), o); v[3].w = __shfl_xor_sync(~0u, __float_as_uint(s2[7]), o);
          } else if (st == 10) {
            if (lane < 8) {
              float4* red = (float4*)(sm + B_RED + wg * 2048 + wq * 512 + lane * 64);
#pragma unroll
              for (int k = 0; k < 4; k++) red[k] = make_float4(s1[2 * k], s2[2 * k], s1[2 * k + 1], s2[2 * k + 1]);
            }
          } else if (st == 11) {
            asm volatile("bar.sync %0, 128;" ::"r"(1 + wg) : "memory");
#pragma unroll
            for (int w = 0; w < 4; w++) {
              float2 a = *(const float2*)(sm + B_RED + wg * 2048 + w * 512 + (wq * 16 + g) * 8);
              float2 b = *(const float2*)(sm + B_RED + wg * 2048 + w * 512 + (wq * 16 + g + 8) * 8);
              v[w] = make_uint4(__float_as_uint(a.x), __float_as_uint(a.y), __float_as_uint(b.x), __float_as_uint(b.y));
            }
          } else if (st == 12) {
            mbar_wait(bar_cs, 0);
          }
        }
        wg_fence();
#pragma unroll
        for (int kk = 0; kk < 2; kk++)
          wgmma_ss224(acc, mkdesc(sb + B_SA + (2 * st + kk) * 4096 + wg * 1024, 0, 2048, 1),
                      mkdesc(sb + B_RING + slot * B_SLOT + kk * 256, 128, 512, 0), (st | kk) != 0);
        wg_commit();
        if (q == 0 && st == 0 && tid == 0) TR(1, 3);
        if (q == 0 && st == 4 && tid == 0) TR(1, 21);
        if (q == 0 && st == 8 && tid == 0) TR(1, 22);
        if (q == 0 && st == 11 && tid == 0) TR(1, 23);
        if (q == 0) {
          if (st == 1 && wg == 0) asm volatile("bar.arrive 3, 256;" ::: "memory");
          if (st < 8) {
#pragma unroll
            for (int i = 0; i < 4; i++) {
              float e[8] = {bf_lo(v[i].x), bf_hi(v[i].x), bf_lo(v[i].y), bf_hi(v[i].y), bf_lo(v[i].z), bf_hi(v[i].z), bf_lo(v[i].w), bf_hi(v[i].w)};
#pragma unroll
              for (int k = 0; k < 8; k++) { s1[k] += e[k]; s2[k] = fmaf(e[k], e[k], s2[k]); }
            }
          } else if (st < 10) {
            s1[0] += __uint_as_float(v[0].x); s1[1] += __uint_as_float(v[0].y); s1[2] += __uint_as_float(v[0].z); s1[3] += __uint_as_float(v[0].w);
            s1[4] += __uint_as_float(v[1].x); s1[5] += __uint_as_float(v[1].y); s1[6] += __uint_as_float(v[1].z); s1[7] += __uint_as_float(v[1].w);
            s2[0] += __uint_as_float(v[2].x); s2[1] += __uint_as_float(v[2].y); s2[2] += __uint_as_float(v[2].z); s2[3] += __uint_as_float(v[2].w);
            s2[4] += __uint_as_float(v[3].x); s2[5] += __uint_as_float(v[3].y); s2[6] += __uint_as_float(v[3].z); s2[7] += __uint_as_float(v[3].w);
          } else if (st == 11) {
            float a0 = 0.f, b0 = 0.f, a1 = 0.f, b1 = 0.f;
#pragma unroll
            for (int w = 0; w < 4; w++) { a0 += __uint_as_float(v[w].x); b0 += __uint_as_float(v[w].y); a1 += __uint_as_float(v[w].z); b1 += __uint_as_float(v[w].w); }
            a0 *= 1.f / DM; a1 *= 1.f / DM;
            b0 = fmaxf(fmaf(-a0, a0, b0 * (1.f / DM)), 0.f); b1 = fmaxf(fmaf(-a1, a1, b1 * (1.f / DM)), 0.f);
            s1[0] = -rbf(a0); s1[1] = 1.f / rbf(sqrtf(rbf(rbf(b0) + 1e-5f)));
            s1[2] = -rbf(a1); s1[3] = 1.f / rbf(sqrtf(rbf(rbf(b1) + 1e-5f)));
          }
        }
        if (st > 0) { wg_wait<1>(); release(pslot); }
        pslot = slot;
        if (++slot == B_NSLOT) { slot = 0; ph ^= 1; }
      }
      if (q == 0) {
        m0 = s1[0]; r0 = s1[1]; m1 = s1[2]; r1 = s1[3];
        if (tid == 0) TR(1, 4);
      }
      float2 cg[14], cu[14];
#pragma unroll
      for (int i = 0; i < 14; i++) {
        asm volatile("ld.shared.v2.f32 {%0, %1}, [%2];" : "=f"(cg[i].x), "=f"(cg[i].y) : "r"(sb + B_CS + (112 * q + 8 * i + 2 * t) * 4) : "memory");
        asm volatile("ld.shared.v2.f32 {%0, %1}, [%2];" : "=f"(cu[i].x), "=f"(cu[i].y) : "r"(sb + B_CS + (224 + 112 * q + 8 * i + 2 * t) * 4) : "memory");
      }
      wg_wait<0>();
      reg_fence(acc);
      release(pslot);
#pragma unroll
      for (int i = 0; i < 14; i++) {
        uint32_t g0 = pack_bf16(fmaf(m0, cg[i].x, acc[4 * i]) * r0, fmaf(m0, cg[i].y, acc[4 * i + 1]) * r0);
        uint32_t g1 = pack_bf16(fmaf(m1, cg[i].x, acc[4 * i + 2]) * r1, fmaf(m1, cg[i].y, acc[4 * i + 3]) * r1);
        uint32_t u0 = pack_bf16(fmaf(m0, cu[i].x, acc[56 + 4 * i]) * r0, fmaf(m0, cu[i].y, acc[56 + 4 * i + 1]) * r0);
        uint32_t u1 = pack_bf16(fmaf(m1, cu[i].x, acc[56 + 4 * i + 2]) * r1, fmaf(m1, cu[i].y, acc[56 + 4 * i + 3]) * r1);
        hh[28 * q + 2 * i] = hmul2_bf(g0, u0); hh[28 * q + 2 * i + 1] = hmul2_bf(g1, u1);
      }
      if (tid == 0) TR(1, 5 + q);
    }
    float accA[28], accB[28], sum[28];
    uint32_t inA[14], inB[14];
    unsigned pend = 0;
#pragma unroll
    for (int i = 0; i < 28; i++) sum[i] = 0.f;
    const uint32_t blo = (((sb + B_RING) & 0x3FFFF) >> 4) | (8u << 16);
#define ISSUE(acc, I, a, FIRST) do { \
      constexpr int s_ = 28 + (I), sl_ = s_ % B_NSLOT; \
      mbar_wait(bar_full + 8 * sl_, (s_ / B_NSLOT) & 1); \
      wg_fence(); \
      wgmma_rs56<(sl_ * B_SLOT + 0 * 256) / 16, 112, !(FIRST)>(acc, (a)[0], (a)[1], (a)[2], (a)[3], blo); \
      wgmma_rs56<(sl_ * B_SLOT + 1 * 256) / 16, 112, 1>(acc, (a)[4], (a)[5], (a)[6], (a)[7], blo); \
      wgmma_rs56<(sl_ * B_SLOT + 2 * 256) / 16, 112, 1>(acc, (a)[8], (a)[9], (a)[10], (a)[11], blo); \
      wgmma_rs56<(sl_ * B_SLOT + 3 * 256) / 16, 112, 1>(acc, (a)[12], (a)[13], (a)[14], (a)[15], blo); \
      wgmma_rs56<(sl_ * B_SLOT + 4 * 256) / 16, 112, 1>(acc, (a)[16], (a)[17], (a)[18], (a)[19], blo); \
      wgmma_rs56<(sl_ * B_SLOT + 5 * 256) / 16, 112, 1>(acc, (a)[20], (a)[21], (a)[22], (a)[23], blo); \
      wgmma_rs56<(sl_ * B_SLOT + 6 * 256) / 16, 112, 1>(acc, (a)[24], (a)[25], (a)[26], (a)[27], blo); \
      wg_commit(); } while (0)
    auto rel = [&](int i) { if (i < 9) release((28 + i) % B_NSLOT); };
    auto tg = [&](uint32_t v) { return (v & 0xFFFEFFFFu) | tag; };
    auto send_lo = [&](float (&acc)[28], int cc) {
      reg_fence(acc);
      uint4* dst = g_part + (size_t)((rt * 8 + ((j + 1 + cc) & 7)) * 7 + cc) * 896 + wg * 448 + t128;
#pragma unroll
      for (int q = 0; q < 2; q++)
        st128(dst + q * 128, pack_bf16(acc[8 * q], acc[8 * q + 1]), pack_bf16(acc[8 * q + 2], acc[8 * q + 3]),
              pack_bf16(acc[8 * q + 4], acc[8 * q + 5]), tg(pack_bf16(acc[8 * q + 6], acc[8 * q + 7])));
    };
    auto send_hi = [&](float (&acc)[28], int cc) {
      uint4* dst = g_part + (size_t)((rt * 8 + ((j + 1 + cc) & 7)) * 7 + cc) * 896 + wg * 448;
      st128(dst + 256 + t128, pack_bf16(acc[16], acc[17]), pack_bf16(acc[18], acc[19]), pack_bf16(acc[20], acc[21]), tg(pack_bf16(acc[22], acc[23])));
      asm volatile("{\n.reg .b64 v;\nmov.b64 v, {%1, %2};\nst.relaxed.gpu.global.b64 [%0], v;\n}"
                   ::"l"((uint2*)(dst + 384) + t128), "r"(pack_bf16(acc[24], acc[25])), "r"(tg(pack_bf16(acc[26], acc[27]))) : "memory");
    };
    auto fetch = [&](uint32_t (&in)[14], int q) {
      const uint4* src = g_part + (size_t)((rt * 8 + j) * 7 + q) * 896 + wg * 448;
#pragma unroll
      for (int i = 0; i < 3; i++) ld128(src + i * 128 + t128, in + 4 * i);
      asm volatile("{\n.reg .b64 v;\nld.relaxed.gpu.global.b64 v, [%2];\nmov.b64 {%0, %1}, v;\n}"
                   : "=r"(in[12]), "=r"(in[13]) : "l"((const uint2*)(src + 384) + t128) : "memory");
    };
    auto valid = [&](uint32_t (&in)[14]) {
      bool ok = (((in[3] ^ tag) | (in[7] ^ tag) | (in[11] ^ tag) | (in[13] ^ tag)) & 0x10000u) == 0;
      return __all_sync(~0u, ok) != 0;
    };
    auto accum = [&](uint32_t (&in)[14]) {
#pragma unroll
      for (int i = 0; i < 14; i++) { sum[2 * i] += bf_lo(in[i]); sum[2 * i + 1] += bf_hi(in[i]); }
    };
    auto consume = [&](uint32_t (&in)[14], int q) { if (valid(in)) accum(in); else pend |= 1u << q; };
#define CHUNK(cur, prev, CC, EXTRA) do { \
      ISSUE(cur, 2 * (CC), hh, true); wg_wait<1>(); rel(2 * (CC) - 1); send_lo(prev, (CC) - 1); \
      ISSUE(cur, 2 * (CC) + 1, hh + 28, false); send_hi(prev, (CC) - 1); EXTRA; wg_wait<1>(); rel(2 * (CC)); } while (0)
    ISSUE(accA, 0, hh, true);
    ISSUE(accA, 1, hh + 28, false); wg_wait<1>(); rel(0);
    CHUNK(accB, accA, 1, );
    if (tid == 0) TR(1, 11);
    CHUNK(accA, accB, 2, );
    if (tid == 0) TR(1, 12);
    CHUNK(accB, accA, 3, fetch(inA, 0));
    if (tid == 0) TR(1, 13);
    CHUNK(accA, accB, 4, (fetch(inB, 1), consume(inA, 0)));
    if (tid == 0) TR(1, 14);
    CHUNK(accB, accA, 5, (fetch(inA, 2), consume(inB, 1)));
    if (tid == 0) TR(1, 16);
    CHUNK(accA, accB, 6, (fetch(inB, 3), consume(inA, 2)));
    if (tid == 0) TR(1, 17);
    CHUNK(accB, accA, 7, (fetch(inA, 4), consume(inB, 3)));
    if (tid == 0) TR(1, 7);
    fetch(inB, 5);
#pragma unroll
    for (int i = 0; i < 4; i++) {
      int qq = lane >> 3, r = lane & 7, kg = 7 * j + 2 * i + (qq >> 1), c = 2 * wq + (qq & 1);
      if (kg > 55) kg = 55;
      uint32_t addr = sb + B_SA + kg * 2048 + wg * 1024 + r * 128 + ((c ^ r) << 4);
      asm volatile("ldmatrix.sync.aligned.m8n8.x4.trans.shared.b16 {%0,%1,%2,%3}, [%4];"
                   : "=r"(hres[4 * i]), "=r"(hres[4 * i + 1]), "=r"(hres[4 * i + 2]), "=r"(hres[4 * i + 3]) : "r"(addr) : "memory");
    }
    consume(inA, 4);
    wg_wait<0>();
    reg_fence(accB);
    fetch(inA, 6);
    consume(inB, 5);
    consume(inA, 6);
    if (tid == 0) TR(1, 8);
#pragma unroll 1
    for (int q = 0; q < 7; q++) {
      if ((pend >> q) & 1) {
        int it = 0;
        do { fetch(inA, q); } while (!valid(inA) && ++it < 200000);
        accum(inA);
      }
    }
    if (tid == 0) TR(1, 9);
    const int row = rt * 128 + wg * 64 + wq * 16 + g;
    uint32_t* o0 = (uint32_t*)(out + (size_t)row * DM + 56 * j + 2 * t);
    uint32_t* o1 = o0 + 8 * DM / 2;
#pragma unroll
    for (int i = 0; i < 7; i++) {
      o0[4 * i] = hadd2_bf(hres[2 * i], pack_bf16(sum[4 * i] + accB[4 * i], sum[4 * i + 1] + accB[4 * i + 1]));
      o1[4 * i] = hadd2_bf(hres[2 * i + 1], pack_bf16(sum[4 * i + 2] + accB[4 * i + 2], sum[4 * i + 3] + accB[4 * i + 3]));
    }
    if (tid == 0) TR(1, 10);
    if (tid == 128) TR(1, 15);
  }
}

extern "C" void kernel_launch(void* const* d_in, const int* in_sizes, int n_in, void* d_out, int out_size) {
  const __nv_bfloat16* x = (const __nv_bfloat16*)d_in[0];
  const __nv_bfloat16 *are = (const __nv_bfloat16*)d_in[1], *aim = (const __nv_bfloat16*)d_in[2], *bre = (const __nv_bfloat16*)d_in[3],
                      *bim = (const __nv_bfloat16*)d_in[4], *cre = (const __nv_bfloat16*)d_in[5], *cim = (const __nv_bfloat16*)d_in[6],
                      *logdt = (const __nv_bfloat16*)d_in[7], *dskip = (const __nv_bfloat16*)d_in[8];
  const __nv_bfloat16 *wg = (const __nv_bfloat16*)d_in[10], *wu = (const __nv_bfloat16*)d_in[11], *wd = (const __nv_bfloat16*)d_in[12];

  static bool init = false;
  if (!init) {
    init = true;
    cudaFuncSetAttribute(k_ffn, cudaFuncAttributeMaxDynamicSharedMemorySize, B_SMEM);
  }
  cudaStream_t st = cudaStreamPerThread;
  k_ln1<<<256, 256, 0, st>>>(x);
  k_kgen<<<DM, 512, 0, st>>>(are, aim, bre, bim, cre, cim, logdt);
  k_conv<<<DM, 512, 0, st>>>(x, dskip);
  k_colsum<<<2 * FF / 128, 128, 0, st>>>(wg, wu);
  k_pack<<<3 * 100352 / 256, 256, 0, st>>>((const uint4*)wg, (const uint4*)wu, (const uint4*)wd);
  k_ffn<<<128, 384, B_SMEM, st>>>((__nv_bfloat16*)d_out);
}
```

```cpp
#include <cuda_runtime.h>
#include <cuda_bf16.h>
#include <stdint.h>

constexpr int LSEQ = 2048, DM = 448, FF = 1792, NST = 256;

__device__ uint4    g_himg[16 * 114688 / 16];
__device__ uint4    g_cimg[8 * 2 * 224];
__device__ uint2    g_stat2[LSEQ];
__device__ uint4    g_part[128 * 7 * 896];
__device__ uint4    g_wimg[8 * 602112 / 16];
__device__ unsigned g_epoch;
__device__ __nv_bfloat16 g_u[LSEQ * DM];
__device__ float    g_kd[DM * 2064];

#define TR(k, i) do {} while (0)
__device__ __forceinline__ uint32_t s2u(const void* p) { return (uint32_t)__cvta_generic_to_shared(p); }
__device__ __forceinline__ void mbar_init(uint32_t b, int c) { asm volatile("mbarrier.init.shared::cta.b64 [%0], %1;" ::"r"(b), "r"(c)); }
__device__ __forceinline__ void mbar_expect(uint32_t b, int bytes) { asm volatile("mbarrier.arrive.expect_tx.shared::cta.b64 _, [%0], %1;" ::"r"(b), "r"(bytes) : "memory"); }
__device__ __forceinline__ void mbar_arrive(uint32_t b) { asm volatile("mbarrier.arrive.shared::cta.b64 _, [%0];" ::"r"(b) : "memory"); }
__device__ __forceinline__ void mbar_wait(uint32_t b, int ph) {
  asm volatile("{\n.reg .pred p;\n.reg .b32 n;\nmov.b32 n, 0;\nLW:\nmbarrier.try_wait.parity.shared::cta.b64 p, [%0], %1;\n@p bra LD;\n"
               "add.u32 n, n, 1;\nsetp.lt.u32 p, n, 4000000;\n@p bra LW;\ntrap;\nLD:\n}" ::"r"(b), "r"(ph) : "memory");
}
__device__ __forceinline__ uint64_t mkdesc(uint32_t addr, uint32_t lbo, uint32_t sbo, uint32_t sw) {
  return (uint64_t)((addr & 0x3FFFF) >> 4) | ((uint64_t)((lbo >> 4) & 0x3FFF) << 16) | ((uint64_t)((sbo >> 4) & 0x3FFF) << 32) | ((uint64_t)sw << 62);
}
__device__ __forceinline__ void wg_fence() { asm volatile("wgmma.fence.sync.aligned;" ::: "memory"); }
__device__ __forceinline__ void wg_commit() { asm volatile("wgmma.commit_group.sync.aligned;" ::: "memory"); }
template <int N> __device__ __forceinline__ void wg_wait() { asm volatile("wgmma.wait_group.sync.aligned %0;" ::"n"(N) : "memory"); }
template <int N> __device__ __forceinline__ void reg_fence(float (&a)[N]) {
#pragma unroll
  for (int i = 0; i < N; i++) asm volatile("" : "+f"(a[i])::"memory");
}
__device__ __forceinline__ uint32_t pack_bf16(float lo, float hi) {
  uint32_t r; asm("cvt.rn.bf16x2.f32 %0, %1, %2;" : "=r"(r) : "f"(hi), "f"(lo)); return r;
}
__device__ __forceinline__ float bf_lo(uint32_t v) { return __uint_as_float(v << 16); }
__device__ __forceinline__ float bf_hi(uint32_t v) { return __uint_as_float(v & 0xFFFF0000u); }
__device__ __forceinline__ float rbf(float x) { return __bfloat162float(__float2bfloat16_rn(x)); }
__device__ __forceinline__ uint32_t hmul2_bf(uint32_t a, uint32_t b) { uint32_t r; asm("mul.rn.bf16x2 %0, %1, %2;" : "=r"(r) : "r"(a), "r"(b)); return r; }
__device__ __forceinline__ uint32_t hadd2_bf(uint32_t a, uint32_t b) { uint32_t r; asm("add.rn.bf16x2 %0, %1, %2;" : "=r"(r) : "r"(a), "r"(b)); return r; }
__device__ __forceinline__ void bulk_ld(uint32_t dst, const void* src, int bytes, uint32_t bar) {
  asm volatile("cp.async.bulk.shared::cluster.global.mbarrier::complete_tx::bytes [%0], [%1], %2, [%3];"
               ::"r"(dst), "l"(src), "r"(bytes), "r"(bar) : "memory");
}

__device__ __forceinline__ void bulk_ld_mc(uint32_t dst, const void* src, int bytes, uint32_t bar) {
  asm volatile("cp.async.bulk.shared::cluster.global.mbarrier::complete_tx::bytes.multicast::cluster [%0], [%1], %2, [%3], %4;"
               ::"r"(dst), "l"(src), "r"(bytes), "r"(bar), "h"((uint16_t)3) : "memory");
}
template <int AOFF, uint32_t AHI, int BOFF, uint32_t BHI, int ACC>
__device__ __forceinline__ void wgmma_ss224(float (&d)[112], uint32_t alo, uint32_t blo) {
  asm volatile("{\n.reg .pred p;\n.reg .b32 la, lb;\n.reg .b64 ad, bd;\nsetp.ne.b32 p, %118, 0;\n"
    "add.u32 la, %112, %114;\nmov.b64 ad, {la, %115};\nadd.u32 lb, %113, %116;\nmov.b64 bd, {lb, %117};\n"
    "wgmma.mma_async.sync.aligned.m64n224k16.f32.bf16.bf16 {%0,%1,%2,%3,%4,%5,%6,%7,%8,%9,%10,%11,%12,%13,%14,%15,%16,%17,%18,%19,%20,%21,%22,%23,%24,%25,%26,%27,%28,%29,%30,%31,%32,%33,%34,%35,%36,%37,%38,%39,%40,%41,%42,%43,%44,%45,%46,%47,%48,%49,%50,%51,%52,%53,%54,%55,%56,%57,%58,%59,%60,%61,%62,%63,%64,%65,%66,%67,%68,%69,%70,%71,%72,%73,%74,%75,%76,%77,%78,%79,%80,%81,%82,%83,%84,%85,%86,%87,%88,%89,%90,%91,%92,%93,%94,%95,%96,%97,%98,%99,%100,%101,%102,%103,%104,%105,%106,%107,%108,%109,%110,%111}, ad, bd, p, 1, 1, 1, 1;\n}\n"
    : "+f"(d[0]),"+f"(d[1]),"+f"(d[2]),"+f"(d[3]),"+f"(d[4]),"+f"(d[5]),"+f"(d[6]),"+f"(d[7]),"+f"(d[8]),"+f"(d[9]),"+f"(d[10]),"+f"(d[11]),"+f"(d[12]),"+f"(d[13]),"+f"(d[14]),"+f"(d[15]),"+f"(d[16]),"+f"(d[17]),"+f"(d[18]),"+f"(d[19]),"+f"(d[20]),"+f"(d[21]),"+f"(d[22]),"+f"(d[23]),"+f"(d[24]),"+f"(d[25]),"+f"(d[26]),"+f"(d[27]),"+f"(d[28]),"+f"(d[29]),"+f"(d[30]),"+f"(d[31]),"+f"(d[32]),"+f"(d[33]),"+f"(d[34]),"+f"(d[35]),"+f"(d[36]),"+f"(d[37]),"+f"(d[38]),"+f"(d[39]),"+f"(d[40]),"+f"(d[41]),"+f"(d[42]),"+f"(d[43]),"+f"(d[44]),"+f"(d[45]),"+f"(d[46]),"+f"(d[47]),"+f"(d[48]),"+f"(d[49]),"+f"(d[50]),"+f"(d[51]),"+f"(d[52]),"+f"(d[53]),"+f"(d[54]),"+f"(d[55]),"+f"(d[56]),"+f"(d[57]),"+f"(d[58]),"+f"(d[59]),"+f"(d[60]),"+f"(d[61]),"+f"(d[62]),"+f"(d[63]),"+f"(d[64]),"+f"(d[65]),"+f"(d[66]),"+f"(d[67]),"+f"(d[68]),"+f"(d[69]),"+f"(d[70]),"+f"(d[71]),"+f"(d[72]),"+f"(d[73]),"+f"(d[74]),"+f"(d[75]),"+f"(d[76]),"+f"(d[77]),"+f"(d[78]),"+f"(d[79]),"+f"(d[80]),"+f"(d[81]),"+f"(d[82]),"+f"(d[83]),"+f"(d[84]),"+f"(d[85]),"+f"(d[86]),"+f"(d[87]),"+f"(d[88]),"+f"(d[89]),"+f"(d[90]),"+f"(d[91]),"+f"(d[92]),"+f"(d[93]),"+f"(d[94]),"+f"(d[95]),"+f"(d[96]),"+f"(d[97]),"+f"(d[98]),"+f"(d[99]),"+f"(d[100]),"+f"(d[101]),"+f"(d[102]),"+f"(d[103]),"+f"(d[104]),"+f"(d[105]),"+f"(d[106]),"+f"(d[107]),"+f"(d[108]),"+f"(d[109]),"+f"(d[110]),"+f"(d[111])
    : "r"(alo), "r"(blo), "n"(AOFF), "n"(AHI), "n"(BOFF), "n"(BHI), "n"(ACC));
}
template <int OFF, uint32_t BHI, int ACC>
__device__ __forceinline__ void wgmma_rs224(float (&d)[112], uint32_t a0, uint32_t a1, uint32_t a2, uint32_t a3, uint32_t blo) {
  asm volatile("{\n.reg .pred p;\n.reg .b32 l;\n.reg .b64 bd;\nsetp.ne.b32 p, %119, 0;\nadd.u32 l, %116, %117;\nmov.b64 bd, {l, %118};\n"
    "wgmma.mma_async.sync.aligned.m64n224k16.f32.bf16.bf16 {%0,%1,%2,%3,%4,%5,%6,%7,%8,%9,%10,%11,%12,%13,%14,%15,%16,%17,%18,%19,%20,%21,%22,%23,%24,%25,%26,%27,%28,%29,%30,%31,%32,%33,%34,%35,%36,%37,%38,%39,%40,%41,%42,%43,%44,%45,%46,%47,%48,%49,%50,%51,%52,%53,%54,%55,%56,%57,%58,%59,%60,%61,%62,%63,%64,%65,%66,%67,%68,%69,%70,%71,%72,%73,%74,%75,%76,%77,%78,%79,%80,%81,%82,%83,%84,%85,%86,%87,%88,%89,%90,%91,%92,%93,%94,%95,%96,%97,%98,%99,%100,%101,%102,%103,%104,%105,%106,%107,%108,%109,%110,%111}, {%112,%113,%114,%115}, bd, p, 1, 1, 1;\n}\n"
    : "+f"(d[0]),"+f"(d[1]),"+f"(d[2]),"+f"(d[3]),"+f"(d[4]),"+f"(d[5]),"+f"(d[6]),"+f"(d[7]),"+f"(d[8]),"+f"(d[9]),"+f"(d[10]),"+f"(d[11]),"+f"(d[12]),"+f"(d[13]),"+f"(d[14]),"+f"(d[15]),"+f"(d[16]),"+f"(d[17]),"+f"(d[18]),"+f"(d[19]),"+f"(d[20]),"+f"(d[21]),"+f"(d[22]),"+f"(d[23]),"+f"(d[24]),"+f"(d[25]),"+f"(d[26]),"+f"(d[27]),"+f"(d[28]),"+f"(d[29]),"+f"(d[30]),"+f"(d[31]),"+f"(d[32]),"+f"(d[33]),"+f"(d[34]),"+f"(d[35]),"+f"(d[36]),"+f"(d[37]),"+f"(d[38]),"+f"(d[39]),"+f"(d[40]),"+f"(d[41]),"+f"(d[42]),"+f"(d[43]),"+f"(d[44]),"+f"(d[45]),"+f"(d[46]),"+f"(d[47]),"+f"(d[48]),"+f"(d[49]),"+f"(d[50]),"+f"(d[51]),"+f"(d[52]),"+f"(d[53]),"+f"(d[54]),"+f"(d[55]),"+f"(d[56]),"+f"(d[57]),"+f"(d[58]),"+f"(d[59]),"+f"(d[60]),"+f"(d[61]),"+f"(d[62]),"+f"(d[63]),"+f"(d[64]),"+f"(d[65]),"+f"(d[66]),"+f"(d[67]),"+f"(d[68]),"+f"(d[69]),"+f"(d[70]),"+f"(d[71]),"+f"(d[72]),"+f"(d[73]),"+f"(d[74]),"+f"(d[75]),"+f"(d[76]),"+f"(d[77]),"+f"(d[78]),"+f"(d[79]),"+f"(d[80]),"+f"(d[81]),"+f"(d[82]),"+f"(d[83]),"+f"(d[84]),"+f"(d[85]),"+f"(d[86]),"+f"(d[87]),"+f"(d[88]),"+f"(d[89]),"+f"(d[90]),"+f"(d[91]),"+f"(d[92]),"+f"(d[93]),"+f"(d[94]),"+f"(d[95]),"+f"(d[96]),"+f"(d[97]),"+f"(d[98]),"+f"(d[99]),"+f"(d[100]),"+f"(d[101]),"+f"(d[102]),"+f"(d[103]),"+f"(d[104]),"+f"(d[105]),"+f"(d[106]),"+f"(d[107]),"+f"(d[108]),"+f"(d[109]),"+f"(d[110]),"+f"(d[111])
    : "r"(a0), "r"(a1), "r"(a2), "r"(a3), "r"(blo), "n"(OFF), "n"(BHI), "n"(ACC));
}
template <int OFF, uint32_t BHI, int ACC>
__device__ __forceinline__ void wgmma_rs56(float (&d)[28], uint32_t a0, uint32_t a1, uint32_t a2, uint32_t a3, uint32_t blo) {
  asm volatile("{\n.reg .pred p;\n.reg .b32 l;\n.reg .b64 bd;\nsetp.ne.b32 p, %35, 0;\nadd.u32 l, %32, %33;\nmov.b64 bd, {l, %34};\n"
    "wgmma.mma_async.sync.aligned.m64n56k16.f32.bf16.bf16 {%0,%1,%2,%3,%4,%5,%6,%7,%8,%9,%10,%11,%12,%13,%14,%15,%16,%17,%18,%19,%20,%21,%22,%23,%24,%25,%26,%27}, {%28,%29,%30,%31}, bd, p, 1, 1, 1;\n}\n"
    : "+f"(d[0]),"+f"(d[1]),"+f"(d[2]),"+f"(d[3]),"+f"(d[4]),"+f"(d[5]),"+f"(d[6]),"+f"(d[7]),"+f"(d[8]),"+f"(d[9]),"+f"(d[10]),"+f"(d[11]),"+f"(d[12]),"+f"(d[13]),"+f"(d[14]),"+f"(d[15]),"+f"(d[16]),"+f"(d[17]),"+f"(d[18]),"+f"(d[19]),"+f"(d[20]),"+f"(d[21]),"+f"(d[22]),"+f"(d[23]),"+f"(d[24]),"+f"(d[25]),"+f"(d[26]),"+f"(d[27])
    : "r"(a0), "r"(a1), "r"(a2), "r"(a3), "r"(blo), "n"(OFF), "n"(BHI), "n"(ACC));
}

__global__ void k_ln1(const __nv_bfloat16* __restrict__ x) {
  int row = blockIdx.x * 8 + threadIdx.x / 32, lane = threadIdx.x & 31;
  float v[14]; float s = 0;
  for (int i = 0; i < 14; i++) { v[i] = __bfloat162float(x[row * DM + lane + 32 * i]); s += v[i]; }
  for (int o = 16; o; o >>= 1) s += __shfl_xor_sync(~0u, s, o);
  float mean = s / DM, q = 0;
  for (int i = 0; i < 14; i++) q += (v[i] - mean) * (v[i] - mean);
  for (int o = 16; o; o >>= 1) q += __shfl_xor_sync(~0u, q, o);
  float m = rbf(mean), sd = rbf(sqrtf(rbf(rbf(q / DM) + 1e-5f)));
  for (int i = 0; i < 14; i++) g_u[row * DM + lane + 32 * i] = __float2bfloat16_rn(rbf(v[i] - m) / sd);
  if (blockIdx.x == 0 && threadIdx.x == 0) g_epoch = g_epoch + 1;
}
__global__ void k_kgen(const __nv_bfloat16* are, const __nv_bfloat16* aim, const __nv_bfloat16* bre, const __nv_bfloat16* bim,
                       const __nv_bfloat16* cre, const __nv_bfloat16* cim, const __nv_bfloat16* logdt) {
  int d = blockIdx.x;
  float dt = rbf(expf(__bfloat162float(logdt[d])));
  for (int l = threadIdx.x; l < 2048; l += blockDim.x) {
    float lf = rbf((float)l), acc = 0;
    for (int n = 0; n < NST; n++) {
      int i = d * NST + n;
      float lr = dt * __bfloat162float(are[i]), li = dt * __bfloat162float(aim[i]);
      float br = dt * __bfloat162float(bre[i]), bi = dt * __bfloat162float(bim[i]);
      float cr = __bfloat162float(cre[i]), ci = __bfloat162float(cim[i]);
      float wr = cr * br - ci * bi, wi = cr * bi + ci * br;
      float e = expf(lr * lf), sn, cs; sincosf(li * lf, &sn, &cs);
      acc += e * (wr * cs - wi * sn);
    }
    g_kd[d * 2064 + l] = acc;
  }
}
__global__ void k_conv(const __nv_bfloat16* __restrict__ x, const __nv_bfloat16* dskip) {
  __shared__ float sk[2048], su[2048];
  int d = blockIdx.x;
  for (int i = threadIdx.x; i < 2048; i += blockDim.x) { sk[i] = g_kd[d * 2064 + i]; su[i] = __bfloat162float(g_u[i * DM + d]); }
  __syncthreads();
  float ds = __bfloat162float(dskip[d]);
  for (int t = threadIdx.x; t < 2048; t += blockDim.x) {
    float acc = 0;
    for (int l = 0; l <= t; l++) acc += sk[l] * su[t - l];
    float yb = rbf(rbf(acc) + rbf(su[t] * ds));
    float h = rbf(__bfloat162float(x[t * DM + d]) + yb);
    int tau = t >> 3, rt = tau >> 4, mh = (tau >> 3) & 1, c = tau & 7, r = d & 7;
    size_t off = (size_t)rt * 114688 + (d >> 3) * 2048 + mh * 1024 + r * 128 + ((c ^ r) * 16) + (t & 7) * 2;
    *(__nv_bfloat16*)((char*)g_himg + off) = __float2bfloat16_rn(h);
  }
}
__global__ void k_colsum(const __nv_bfloat16* wg, const __nv_bfloat16* wu) {
  int f = blockIdx.x * blockDim.x + threadIdx.x;
  const __nv_bfloat16* w = f < FF ? wg : wu; int ff = f < FF ? f : f - FF;
  float s = 0; for (int d = 0; d < DM; d++) s += __bfloat162float(w[d * FF + ff]);
  float hi = rbf(s), mid = rbf(s - hi), lo = rbf(s - hi - mid);
  int j = ff / 224, q = (ff % 224) / 112, n = ff % 112 + (f < FF ? 0 : 112);
  __nv_bfloat16* dst = (__nv_bfloat16*)(g_cimg + (j * 2 + q) * 224 + (n >> 3) * 8) + (n & 7);
  dst[0] = __float2bfloat16_rn(hi); dst[8] = __float2bfloat16_rn(mid); dst[16] = __float2bfloat16_rn(lo);
  for (int k = 3; k < 8; k++) dst[8 * k] = __float2bfloat16_rn(0.f);
}
__global__ void k_pack(const uint4* __restrict__ wg, const uint4* __restrict__ wu, const uint4* __restrict__ wd) {
  int i = blockIdx.x * blockDim.x + threadIdx.x;
  int mat = i / 100352, e = i % 100352;
  if (mat < 2) {
    int d = e / 224, ngg = e % 224;
    int j = ngg / 28, q = (ngg % 28) / 14, ng = ngg % 14 + 14 * mat;
    g_wimg[(size_t)j * 37632 + (q * 14 + (d >> 5)) * 896 + ng * 32 + (d & 31)] = (mat ? wu : wg)[e];
  } else {
    int f = e / 56, ngg = e % 56;
    int j = f / 224, hf = (f % 224) / 112, k = f % 112, c = ngg / 7, ng = ngg % 7;
    g_wimg[(size_t)j * 37632 + 25088 + (c * 2 + hf) * 784 + ng * 112 + k] = wd[e];
  }
}

constexpr int B_SA = 0, B_RING = 114688, B_SLOT = 14336, B_NSLOT = 7;
constexpr int B_CS = B_RING + B_NSLOT * B_SLOT;
constexpr int B_STAT = B_CS + 7168;
constexpr int B_RED = B_STAT + 1024;
constexpr int B_BAR = B_RED + 256;
constexpr int B_SMEM = B_BAR + 512;

__device__ __forceinline__ void st128(uint4* p, uint32_t a, uint32_t b, uint32_t c, uint32_t d) {
  asm volatile("{\n.reg .b128 v;\n.reg .b64 lo, hi;\nmov.b64 lo, {%1, %2};\nmov.b64 hi, {%3, %4};\nmov.b128 v, {lo, hi};\n"
               "st.relaxed.gpu.global.b128 [%0], v;\n}" ::"l"(p), "r"(a), "r"(b), "r"(c), "r"(d) : "memory");
}
__device__ __forceinline__ void ld128(const uint4* p, uint32_t* r) {
  asm volatile("{\n.reg .b128 v;\n.reg .b64 lo, hi;\nld.relaxed.gpu.global.b128 v, [%4];\nmov.b128 {lo, hi}, v;\n"
               "mov.b64 {%0, %1}, lo;\nmov.b64 {%2, %3}, hi;\n}" : "=r"(r[0]), "=r"(r[1]), "=r"(r[2]), "=r"(r[3]) : "l"(p) : "memory");
}

__device__ __forceinline__ uint32_t mapa(uint32_t a, uint32_t r) { uint32_t o; asm("mapa.shared::cluster.u32 %0, %1, %2;" : "=r"(o) : "r"(a), "r"(r)); return o; }

template <int Q, int ST>
__device__ __forceinline__ void g1_stage(float (&acc)[112], uint32_t alo, uint32_t blo, uint32_t bar_full, uint32_t bar_h) {
  constexpr int s = Q * 14 + ST, sl = s % B_NSLOT;
  if (Q == 0) mbar_wait(bar_h + 8 * ST, 0);
  mbar_wait(bar_full + 8 * sl, (s / B_NSLOT) & 1);
  wg_fence();
  wgmma_ss224<(2 * ST) * 256, 0x40000080u, (sl * B_SLOT) / 16, 32, ST != 0>(acc, alo, blo);
  wgmma_ss224<(2 * ST + 1) * 256, 0x40000080u, (sl * B_SLOT + 256) / 16, 32, 1>(acc, alo, blo);
}

__global__ void __cluster_dims__(2, 1, 1) __launch_bounds__(384, 1) k_ffn(__nv_bfloat16* __restrict__ out) {
  extern __shared__ __align__(1024) unsigned char sm[];
  const uint32_t sb = s2u(sm);
  const int tid = threadIdx.x, wg = tid >> 7, warp = tid >> 5, lane = tid & 31;
  const int rank = blockIdx.x & 1, rt = blockIdx.x & 15, j = blockIdx.x >> 4;
  const uint32_t bar_full = sb + B_BAR, bar_empty = bar_full + 64, bar_h = bar_full + 128, bar_cs = bar_full + 240, bar_stat = bar_full + 248;
  if (tid == 0) {
    TR(1, 0);
    for (int i = 0; i < B_NSLOT; i++) { mbar_init(bar_full + 8 * i, 1); mbar_init(bar_empty + 8 * i, 4); }
    for (int i = 0; i < 14; i++) mbar_init(bar_h + 8 * i, 1);
    mbar_init(bar_cs, 1);
    mbar_init(bar_stat, 64);
    asm volatile("fence.mbarrier_init.release.cluster;" ::: "memory");
  }
  __syncthreads();
  asm volatile("barrier.cluster.arrive.release.aligned;" ::: "memory");

  if (wg == 2) {
    asm volatile("setmaxnreg.dec.sync.aligned.u32 88;");
    asm volatile("barrier.cluster.wait.acquire.aligned;" ::: "memory");
    asm volatile("griddepcontrol.wait;" ::: "memory");
    if (warp == 8) {
      if (lane == 0) {
        const char* wsrc = (const char*)g_wimg + (size_t)j * 602112;
        TR(1, 1);
        int slot = 0, ph = 0;
        for (int s = 0; s < 44; s++) {
          if (s >= B_NSLOT) mbar_wait(bar_empty + 8 * slot, ph ^ 1);
          uint32_t dst = sb + B_RING + slot * B_SLOT, fb = bar_full + 8 * slot;
          if (s < 28) {
            mbar_expect(fb, 14336);
            bulk_ld_mc(dst + rank * 7168, wsrc + s * 14336 + rank * 7168, 7168, fb);
          } else {
            const int c = (j + 1 + ((s - 28) >> 1)) & 7;
            mbar_expect(fb, 12544);
            bulk_ld_mc(dst + rank * 6272, wsrc + 401408 + (c * 2 + (s & 1)) * 12544 + rank * 6272, 6272, fb);
          }
          if (++slot == B_NSLOT) { slot = 0; ph ^= 1; }
        }
      }
    } else if (warp == 9) {
      if (lane == 0) {
        const char* hsrc = (const char*)g_himg + (size_t)rt * 114688;
        for (int i = 0; i < 14; i++) {
          mbar_expect(bar_h + 8 * i, 8192);
          bulk_ld(sb + B_SA + i * 8192, hsrc + i * 8192, 8192, bar_h + 8 * i);
        }
        mbar_expect(bar_cs, 7168);
        bulk_ld(sb + B_CS, g_cimg + j * 448, 7168, bar_cs);
      }
    } else {
      const int t64 = tid - 320, c2 = lane & 1, r = (lane >> 1) & 7;
      const uint32_t tag = __ldcg(&g_epoch) & 1u;
      const uint4* src = g_himg + (size_t)rt * 7168 + (t64 >> 4) * 128 + (j >> 2) * 64 + r * 8 + ((((j & 3) * 2 + c2) ^ r));
      uint4 v[14];
#pragma unroll
      for (int i = 0; i < 14; i++) v[i] = __ldcg(src + i * 512);
      float a[16];
#pragma unroll
      for (int k = 0; k < 16; k++) a[k] = 0.f;
#pragma unroll
      for (int i = 0; i < 14; i++) {
        float e[8] = {bf_lo(v[i].x), bf_hi(v[i].x), bf_lo(v[i].y), bf_hi(v[i].y), bf_lo(v[i].z), bf_hi(v[i].z), bf_lo(v[i].w), bf_hi(v[i].w)};
#pragma unroll
        for (int k = 0; k < 8; k++) { a[2 * k] += e[k]; a[2 * k + 1] = fmaf(e[k], e[k], a[2 * k + 1]); }
      }
#pragma unroll
      for (int rd = 0; rd < 4; rd++) {
        const int n = 8 >> rd;
        const bool up = lane & (2 * n);
#pragma unroll
        for (int k = 0; k < 8; k++) {
          if (k < n) {
            float keep = up ? a[k + n] : a[k], give = up ? a[k] : a[k + n];
            a[k] = keep + __shfl_xor_sync(~0u, give, 2 * n);
          }
        }
      }
      float* red = (float*)(sm + B_RED);
      red[(warp & 1) * 32 + c2 * 16 + (lane >> 1)] = a[0];
      asm volatile("bar.sync 1, 64;" ::: "memory");
      if (t64 < 16) {
        float mean = (red[2 * t64] + red[32 + 2 * t64]) * (1.f / DM);
        float var = fmaxf(fmaf(-mean, mean, (red[2 * t64 + 1] + red[33 + 2 * t64]) * (1.f / DM)), 0.f);
        float rs = 1.f / rbf(sqrtf(rbf(rbf(var) + 1e-5f)));
        uint32_t nm = pack_bf16(-mean, -mean), r2 = (__float_as_uint(rs * rs) & ~1u) | tag;
        asm volatile("{\n.reg .b64 v;\nmov.b64 v, {%1, %2};\nst.relaxed.gpu.global.b64 [%0], v;\n}"
                     ::"l"(g_stat2 + rt * 128 + j * 16 + t64), "r"(nm), "r"(r2) : "memory");
      }
      if (t64 == 0) TR(1, 2);
      mbar_wait(bar_h + 8 * 13, 0);
      uint32_t w[4];
      int it = 0;
      do { ld128((const uint4*)(g_stat2 + rt * 128) + t64, w); } while ((((w[1] ^ tag) | (w[3] ^ tag)) & 1u) && ++it < 200000);
      *(uint4*)(sm + B_STAT + t64 * 16) = make_uint4(w[0], w[1], w[2], w[3]);
      mbar_arrive(bar_stat);
      if (t64 == 0) TR(1, 18);
    }
  } else {
    asm volatile("setmaxnreg.inc.sync.aligned.u32 208;");
    const int g = lane >> 2, t = lane & 3, wq = warp & 3, t128 = tid & 127;
    uint32_t hh[56], hres[16];
    asm volatile("barrier.cluster.wait.acquire.aligned;" ::: "memory");
    asm volatile("griddepcontrol.wait;" ::: "memory");
    const uint32_t tag = (__ldcg(&g_epoch) & 1u) << 16;
    const uint32_t rel_bar = mapa(bar_empty, t128 & 1);
    auto release = [&](int sl) { if (t128 < 2) asm volatile("mbarrier.arrive.shared::cluster.b64 _, [%0];" ::"r"(rel_bar + 8 * sl) : "memory"); };
    const uint32_t alo = __shfl_sync(~0u, ((sb + B_SA + wg * 1024) & 0x3FFFF) >> 4, 0);
    const uint32_t blo = (((sb + B_RING) & 0x3FFFF) >> 4) | (8u << 16);
    const uint32_t clo = ((sb + B_CS) & 0x3FFFF) >> 4;
    uint32_t nm0, nm1; float r20, r21;
    if (wg == 1) asm volatile("bar.sync 3, 256;" ::: "memory");
#define G1S(Q, ST) do { g1_stage<Q, ST>(acc, alo, blo, bar_full, bar_h); wg_commit(); \
      if (ST > 0) { wg_wait<1>(); release((Q * 14 + ST - 1) % B_NSLOT); } } while (0)
#define G1EPI(Q) do { \
      g1_stage<Q, 13>(acc, alo, blo, bar_full, bar_h); \
      wgmma_rs224<Q * 224, 8, 1>(acc, nm0, nm1, 0u, 0u, clo); \
      wg_commit(); wg_wait<1>(); release((Q * 14 + 12) % B_NSLOT); \
      wg_wait<0>(); reg_fence(acc); release((Q * 14 + 13) % B_NSLOT); \
      _Pragma("unroll") \
      for (int i = 0; i < 28; i++) hh[28 * Q + i] = pack_bf16(acc[2 * i] * acc[56 + 2 * i], acc[2 * i + 1] * acc[57 + 2 * i]); \
    } while (0)
    {
      float acc[112];
      G1S(0, 0);
      if (tid == 0) TR(1, 3);
      G1S(0, 1);
      if (wg == 0) asm volatile("bar.arrive 3, 256;" ::: "memory");
      G1S(0, 2); G1S(0, 3); G1S(0, 4); G1S(0, 5); G1S(0, 6); G1S(0, 7); G1S(0, 8); G1S(0, 9); G1S(0, 10); G1S(0, 11); G1S(0, 12);
      if (tid == 0) TR(1, 4);
      mbar_wait(bar_stat, 0);
      mbar_wait(bar_cs, 0);
      {
        uint2 a = *(const uint2*)(sm + B_STAT + (wg * 64 + wq * 16 + g) * 8), b = *(const uint2*)(sm + B_STAT + (wg * 64 + wq * 16 + g + 8) * 8);
        const uint32_t msk = t == 0 ? 0xFFFFFFFFu : t == 1 ? 0xFFFFu : 0u;
        nm0 = a.x & msk; nm1 = b.x & msk; r20 = __uint_as_float(a.y); r21 = __uint_as_float(b.y);
      }
      G1EPI(0);
      if (tid == 0) TR(1, 5);
      G1S(1, 0); G1S(1, 1); G1S(1, 2); G1S(1, 3); G1S(1, 4); G1S(1, 5); G1S(1, 6); G1S(1, 7); G1S(1, 8); G1S(1, 9); G1S(1, 10); G1S(1, 11); G1S(1, 12);
      G1EPI(1);
      if (tid == 0) TR(1, 6);
    }
    float accA[28], accB[28], sum[28];
    uint32_t inA[14], inB[14];
    unsigned pend = 0;
#pragma unroll
    for (int i = 0; i < 28; i++) sum[i] = 0.f;
#define ISSUE(acc, I, a, FIRST) do { \
      constexpr int s_ = 28 + (I), sl_ = s_ % B_NSLOT; \
      mbar_wait(bar_full + 8 * sl_, (s_ / B_NSLOT) & 1); \
      wg_fence(); \
      wgmma_rs56<(sl_ * B_SLOT + 0 * 256) / 16, 112, !(FIRST)>(acc, (a)[0], (a)[1], (a)[2], (a)[3], blo); \
      wgmma_rs56<(sl_ * B_SLOT + 1 * 256) / 16, 112, 1>(acc, (a)[4], (a)[5], (a)[6], (a)[7], blo); \
      wgmma_rs56<(sl_ * B_SLOT + 2 * 256) / 16, 112, 1>(acc, (a)[8], (a)[9], (a)[10], (a)[11], blo); \
      wgmma_rs56<(sl_ * B_SLOT + 3 * 256) / 16, 112, 1>(acc, (a)[12], (a)[13], (a)[14], (a)[15], blo); \
      wgmma_rs56<(sl_ * B_SLOT + 4 * 256) / 16, 112, 1>(acc, (a)[16], (a)[17], (a)[18], (a)[19], blo); \
      wgmma_rs56<(sl_ * B_SLOT + 5 * 256) / 16, 112, 1>(acc, (a)[20], (a)[21], (a)[22], (a)[23], blo); \
      wgmma_rs56<(sl_ * B_SLOT + 6 * 256) / 16, 112, 1>(acc, (a)[24], (a)[25], (a)[26], (a)[27], blo); \
      wg_commit(); } while (0)
    auto rel = [&](int i) { if (i < 9) release((28 + i) % B_NSLOT); };
    auto tg = [&](uint32_t v) { return (v & 0xFFFEFFFFu) | tag; };
    auto send_lo = [&](float (&acc)[28], int cc) {
      reg_fence(acc);
      uint4* dst = g_part + (size_t)((rt * 8 + ((j + 1 + cc) & 7)) * 7 + cc) * 896 + wg * 448 + t128;
#pragma unroll
      for (int q = 0; q < 2; q++)
        st128(dst + q * 128, pack_bf16(acc[8 * q], acc[8 * q + 1]), pack_bf16(acc[8 * q + 2], acc[8 * q + 3]),
              pack_bf16(acc[8 * q + 4], acc[8 * q + 5]), tg(pack_bf16(acc[8 * q + 6], acc[8 * q + 7])));
    };
    auto send_hi = [&](float (&acc)[28], int cc) {
      uint4* dst = g_part + (size_t)((rt * 8 + ((j + 1 + cc) & 7)) * 7 + cc) * 896 + wg * 448;
      st128(dst + 256 + t128, pack_bf16(acc[16], acc[17]), pack_bf16(acc[18], acc[19]), pack_bf16(acc[20], acc[21]), tg(pack_bf16(acc[22], acc[23])));
      asm volatile("{\n.reg .b64 v;\nmov.b64 v, {%1, %2};\nst.relaxed.gpu.global.b64 [%0], v;\n}"
                   ::"l"((uint2*)(dst + 384) + t128), "r"(pack_bf16(acc[24], acc[25])), "r"(tg(pack_bf16(acc[26], acc[27]))) : "memory");
    };
    auto fetch = [&](uint32_t (&in)[14], int q) {
      const uint4* src = g_part + (size_t)((rt * 8 + j) * 7 + q) * 896 + wg * 448;
#pragma unroll
      for (int i = 0; i < 3; i++) ld128(src + i * 128 + t128, in + 4 * i);
      asm volatile("{\n.reg .b64 v;\nld.relaxed.gpu.global.b64 v, [%2];\nmov.b64 {%0, %1}, v;\n}"
                   : "=r"(in[12]), "=r"(in[13]) : "l"((const uint2*)(src + 384) + t128) : "memory");
    };
    auto valid = [&](uint32_t (&in)[14]) {
      bool ok = (((in[3] ^ tag) | (in[7] ^ tag) | (in[11] ^ tag) | (in[13] ^ tag)) & 0x10000u) == 0;
      return __all_sync(~0u, ok) != 0;
    };
    auto accum = [&](uint32_t (&in)[14]) {
#pragma unroll
      for (int i = 0; i < 14; i++) { sum[2 * i] += bf_lo(in[i]); sum[2 * i + 1] += bf_hi(in[i]); }
    };
    auto consume = [&](uint32_t (&in)[14], int q) { if (valid(in)) accum(in); else pend |= 1u << q; };
#define CHUNK(cur, prev, CC, EXTRA) do { \
      ISSUE(cur, 2 * (CC), hh, true); wg_wait<1>(); rel(2 * (CC) - 1); send_lo(prev, (CC) - 1); \
      ISSUE(cur, 2 * (CC) + 1, hh + 28, false); send_hi(prev, (CC) - 1); EXTRA; wg_wait<1>(); rel(2 * (CC)); } while (0)
    ISSUE(accA, 0, hh, true);
    ISSUE(accA, 1, hh + 28, false); wg_wait<1>(); rel(0);
    CHUNK(accB, accA, 1, );
    if (tid == 0) TR(1, 11);
    CHUNK(accA, accB, 2, );
    if (tid == 0) TR(1, 12);
    CHUNK(accB, accA, 3, fetch(inA, 0));
    if (tid == 0) TR(1, 13);
    CHUNK(accA, accB, 4, (fetch(inB, 1), consume(inA, 0)));
    if (tid == 0) TR(1, 14);
    CHUNK(accB, accA, 5, (fetch(inA, 2), consume(inB, 1)));
    if (tid == 0) TR(1, 16);
    CHUNK(accA, accB, 6, (fetch(inB, 3), consume(inA, 2)));
    if (tid == 0) TR(1, 17);
    CHUNK(accB, accA, 7, (fetch(inA, 4), consume(inB, 3)));
    if (tid == 0) TR(1, 7);
    fetch(inB, 5);
#pragma unroll
    for (int i = 0; i < 4; i++) {
      int qq = lane >> 3, r = lane & 7, kg = 7 * j + 2 * i + (qq >> 1), c = 2 * wq + (qq & 1);
      if (kg > 55) kg = 55;
      uint32_t addr = sb + B_SA + kg * 2048 + wg * 1024 + r * 128 + ((c ^ r) << 4);
      asm volatile("ldmatrix.sync.aligned.m8n8.x4.trans.shared.b16 {%0,%1,%2,%3}, [%4];"
                   : "=r"(hres[4 * i]), "=r"(hres[4 * i + 1]), "=r"(hres[4 * i + 2]), "=r"(hres[4 * i + 3]) : "r"(addr) : "memory");
    }
    consume(inA, 4);
    wg_wait<0>();
    reg_fence(accB);
    fetch(inA, 6);
    consume(inB, 5);
    consume(inA, 6);
    if (tid == 0) TR(1, 8);
#pragma unroll 1
    for (int q = 0; q < 7; q++) {
      if ((pend >> q) & 1) {
        int it = 0;
        do { fetch(inA, q); } while (!valid(inA) && ++it < 200000);
        accum(inA);
      }
    }
    if (tid == 0) TR(1, 9);
    const int row = rt * 128 + wg * 64 + wq * 16 + g;
    uint32_t* o0 = (uint32_t*)(out + (size_t)row * DM + 56 * j + 2 * t);
    uint32_t* o1 = o0 + 8 * DM / 2;
#pragma unroll
    for (int i = 0; i < 7; i++) {
      o0[4 * i] = hadd2_bf(hres[2 * i], pack_bf16((sum[4 * i] + accB[4 * i]) * r20, (sum[4 * i + 1] + accB[4 * i + 1]) * r20));
      o1[4 * i] = hadd2_bf(hres[2 * i + 1], pack_bf16((sum[4 * i + 2] + accB[4 * i + 2]) * r21, (sum[4 * i + 3] + accB[4 * i + 3]) * r21));
    }
    if (tid == 0) TR(1, 10);
    if (tid == 128) TR(1, 15);
  }
}

extern "C" void kernel_launch(void* const* d_in, const int* in_sizes, int n_in, void* d_out, int out_size) {
  const __nv_bfloat16* x = (const __nv_bfloat16*)d_in[0];
  const __nv_bfloat16 *are = (const __nv_bfloat16*)d_in[1], *aim = (const __nv_bfloat16*)d_in[2], *bre = (const __nv_bfloat16*)d_in[3],
                      *bim = (const __nv_bfloat16*)d_in[4], *cre = (const __nv_bfloat16*)d_in[5], *cim = (const __nv_bfloat16*)d_in[6],
                      *logdt = (const __nv_bfloat16*)d_in[7], *dskip = (const __nv_bfloat16*)d_in[8];
  const __nv_bfloat16 *wg = (const __nv_bfloat16*)d_in[10], *wu = (const __nv_bfloat16*)d_in[11], *wd = (const __nv_bfloat16*)d_in[12];

  static bool init = false;
  if (!init) {
    init = true;
    cudaFuncSetAttribute(k_ffn, cudaFuncAttributeMaxDynamicSharedMemorySize, B_SMEM);
  }
  cudaStream_t st = cudaStreamPerThread;
  k_ln1<<<256, 256, 0, st>>>(x);
  k_kgen<<<DM, 512, 0, st>>>(are, aim, bre, bim, cre, cim, logdt);
  k_conv<<<DM, 512, 0, st>>>(x, dskip);
  k_colsum<<<2 * FF / 128, 128, 0, st>>>(wg, wu);
  k_pack<<<3 * 100352 / 256, 256, 0, st>>>((const uint4*)wg, (const uint4*)wu, (const uint4*)wd);
  k_ffn<<<128, 384, B_SMEM, st>>>((__nv_bfloat16*)d_out);
}
```

```cpp
#include <cuda_runtime.h>
#include <cuda_bf16.h>
#include <stdint.h>

constexpr int LSEQ = 2048, DM = 448, FF = 1792, NST = 256;

__device__ uint4    g_himg[16 * 114688 / 16];
__device__ uint4    g_cimg[8 * 2 * 224];
__device__ uint2    g_stat2[LSEQ];
__device__ uint4    g_part[128 * 7 * 896];
__device__ uint4    g_wimg[8 * 602112 / 16];
__device__ unsigned g_epoch;
__device__ __nv_bfloat16 g_u[LSEQ * DM];
__device__ float    g_kd[DM * 2064];

#define TR(k, i) do {} while (0)
__device__ __forceinline__ uint32_t s2u(const void* p) { return (uint32_t)__cvta_generic_to_shared(p); }
__device__ __forceinline__ void mbar_init(uint32_t b, int c) { asm volatile("mbarrier.init.shared::cta.b64 [%0], %1;" ::"r"(b), "r"(c)); }
__device__ __forceinline__ void mbar_expect(uint32_t b, int bytes) { asm volatile("mbarrier.arrive.expect_tx.shared::cta.b64 _, [%0], %1;" ::"r"(b), "r"(bytes) : "memory"); }
__device__ __forceinline__ void mbar_arrive(uint32_t b) { asm volatile("mbarrier.arrive.shared::cta.b64 _, [%0];" ::"r"(b) : "memory"); }
__device__ __forceinline__ void mbar_wait(uint32_t b, int ph) {
  asm volatile("{\n.reg .pred p;\n.reg .b32 n;\nmov.b32 n, 0;\nLW:\nmbarrier.try_wait.parity.shared::cta.b64 p, [%0], %1;\n@p bra LD;\n"
               "add.u32 n, n, 1;\nsetp.lt.u32 p, n, 4000000;\n@p bra LW;\ntrap;\nLD:\n}" ::"r"(b), "r"(ph) : "memory");
}
__device__ __forceinline__ uint64_t mkdesc(uint32_t addr, uint32_t lbo, uint32_t sbo, uint32_t sw) {
  return (uint64_t)((addr & 0x3FFFF) >> 4) | ((uint64_t)((lbo >> 4) & 0x3FFF) << 16) | ((uint64_t)((sbo >> 4) & 0x3FFF) << 32) | ((uint64_t)sw << 62);
}
__device__ __forceinline__ void wg_fence() { asm volatile("wgmma.fence.sync.aligned;" ::: "memory"); }
__device__ __forceinline__ void wg_commit() { asm volatile("wgmma.commit_group.sync.aligned;" ::: "memory"); }
template <int N> __device__ __forceinline__ void wg_wait() { asm volatile("wgmma.wait_group.sync.aligned %0;" ::"n"(N) : "memory"); }
template <int N> __device__ __forceinline__ void reg_fence(float (&a)[N]) {
#pragma unroll
  for (int i = 0; i < N; i++) asm volatile("" : "+f"(a[i])::"memory");
}
__device__ __forceinline__ uint32_t pack_bf16(float lo, float hi) {
  uint32_t r; asm("cvt.rn.bf16x2.f32 %0, %1, %2;" : "=r"(r) : "f"(hi), "f"(lo)); return r;
}
__device__ __forceinline__ float bf_lo(uint32_t v) { return __uint_as_float(v << 16); }
__device__ __forceinline__ float bf_hi(uint32_t v) { return __uint_as_float(v & 0xFFFF0000u); }
__device__ __forceinline__ float rbf(float x) { return __bfloat162float(__float2bfloat16_rn(x)); }
__device__ __forceinline__ uint32_t hmul2_bf(uint32_t a, uint32_t b) { uint32_t r; asm("mul.rn.bf16x2 %0, %1, %2;" : "=r"(r) : "r"(a), "r"(b)); return r; }
__device__ __forceinline__ uint32_t hadd2_bf(uint32_t a, uint32_t b) { uint32_t r; asm("add.rn.bf16x2 %0, %1, %2;" : "=r"(r) : "r"(a), "r"(b)); return r; }
__device__ __forceinline__ void bulk_ld(uint32_t dst, const void* src, int bytes, uint32_t bar) {
  asm volatile("cp.async.bulk.shared::cluster.global.mbarrier::complete_tx::bytes [%0], [%1], %2, [%3];"
               ::"r"(dst), "l"(src), "r"(bytes), "r"(bar) : "memory");
}

__device__ __forceinline__ void bulk_ld_mc(uint32_t dst, const void* src, int bytes, uint32_t bar) {
  asm volatile("cp.async.bulk.shared::cluster.global.mbarrier::complete_tx::bytes.multicast::cluster [%0], [%1], %2, [%3], %4;"
               ::"r"(dst), "l"(src), "r"(bytes), "r"(bar), "h"((uint16_t)3) : "memory");
}
template <int AOFF, uint32_t AHI, int BOFF, uint32_t BHI, int ACC>
__device__ __forceinline__ void wgmma_ss224(float (&d)[112], uint32_t alo, uint32_t blo) {
  asm volatile("{\n.reg .pred p;\n.reg .b32 la, lb;\n.reg .b64 ad, bd;\nsetp.ne.b32 p, %118, 0;\n"
    "add.u32 la, %112, %114;\nmov.b64 ad, {la, %115};\nadd.u32 lb, %113, %116;\nmov.b64 bd, {lb, %117};\n"
    "wgmma.mma_async.sync.aligned.m64n224k16.f32.bf16.bf16 {%0,%1,%2,%3,%4,%5,%6,%7,%8,%9,%10,%11,%12,%13,%14,%15,%16,%17,%18,%19,%20,%21,%22,%23,%24,%25,%26,%27,%28,%29,%30,%31,%32,%33,%34,%35,%36,%37,%38,%39,%40,%41,%42,%43,%44,%45,%46,%47,%48,%49,%50,%51,%52,%53,%54,%55,%56,%57,%58,%59,%60,%61,%62,%63,%64,%65,%66,%67,%68,%69,%70,%71,%72,%73,%74,%75,%76,%77,%78,%79,%80,%81,%82,%83,%84,%85,%86,%87,%88,%89,%90,%91,%92,%93,%94,%95,%96,%97,%98,%99,%100,%101,%102,%103,%104,%105,%106,%107,%108,%109,%110,%111}, ad, bd, p, 1, 1, 1, 1;\n}\n"
    : "+f"(d[0]),"+f"(d[1]),"+f"(d[2]),"+f"(d[3]),"+f"(d[4]),"+f"(d[5]),"+f"(d[6]),"+f"(d[7]),"+f"(d[8]),"+f"(d[9]),"+f"(d[10]),"+f"(d[11]),"+f"(d[12]),"+f"(d[13]),"+f"(d[14]),"+f"(d[15]),"+f"(d[16]),"+f"(d[17]),"+f"(d[18]),"+f"(d[19]),"+f"(d[20]),"+f"(d[21]),"+f"(d[22]),"+f"(d[23]),"+f"(d[24]),"+f"(d[25]),"+f"(d[26]),"+f"(d[27]),"+f"(d[28]),"+f"(d[29]),"+f"(d[30]),"+f"(d[31]),"+f"(d[32]),"+f"(d[33]),"+f"(d[34]),"+f"(d[35]),"+f"(d[36]),"+f"(d[37]),"+f"(d[38]),"+f"(d[39]),"+f"(d[40]),"+f"(d[41]),"+f"(d[42]),"+f"(d[43]),"+f"(d[44]),"+f"(d[45]),"+f"(d[46]),"+f"(d[47]),"+f"(d[48]),"+f"(d[49]),"+f"(d[50]),"+f"(d[51]),"+f"(d[52]),"+f"(d[53]),"+f"(d[54]),"+f"(d[55]),"+f"(d[56]),"+f"(d[57]),"+f"(d[58]),"+f"(d[59]),"+f"(d[60]),"+f"(d[61]),"+f"(d[62]),"+f"(d[63]),"+f"(d[64]),"+f"(d[65]),"+f"(d[66]),"+f"(d[67]),"+f"(d[68]),"+f"(d[69]),"+f"(d[70]),"+f"(d[71]),"+f"(d[72]),"+f"(d[73]),"+f"(d[74]),"+f"(d[75]),"+f"(d[76]),"+f"(d[77]),"+f"(d[78]),"+f"(d[79]),"+f"(d[80]),"+f"(d[81]),"+f"(d[82]),"+f"(d[83]),"+f"(d[84]),"+f"(d[85]),"+f"(d[86]),"+f"(d[87]),"+f"(d[88]),"+f"(d[89]),"+f"(d[90]),"+f"(d[91]),"+f"(d[92]),"+f"(d[93]),"+f"(d[94]),"+f"(d[95]),"+f"(d[96]),"+f"(d[97]),"+f"(d[98]),"+f"(d[99]),"+f"(d[100]),"+f"(d[101]),"+f"(d[102]),"+f"(d[103]),"+f"(d[104]),"+f"(d[105]),"+f"(d[106]),"+f"(d[107]),"+f"(d[108]),"+f"(d[109]),"+f"(d[110]),"+f"(d[111])
    : "r"(alo), "r"(blo), "n"(AOFF), "n"(AHI), "n"(BOFF), "n"(BHI), "n"(ACC));
}
template <int OFF, uint32_t BHI, int ACC>
__device__ __forceinline__ void wgmma_rs224(float (&d)[112], uint32_t a0, uint32_t a1, uint32_t a2, uint32_t a3, uint32_t blo) {
  asm volatile("{\n.reg .pred p;\n.reg .b32 l;\n.reg .b64 bd;\nsetp.ne.b32 p, %119, 0;\nadd.u32 l, %116, %117;\nmov.b64 bd, {l, %118};\n"
    "wgmma.mma_async.sync.aligned.m64n224k16.f32.bf16.bf16 {%0,%1,%2,%3,%4,%5,%6,%7,%8,%9,%10,%11,%12,%13,%14,%15,%16,%17,%18,%19,%20,%21,%22,%23,%24,%25,%26,%27,%28,%29,%30,%31,%32,%33,%34,%35,%36,%37,%38,%39,%40,%41,%42,%43,%44,%45,%46,%47,%48,%49,%50,%51,%52,%53,%54,%55,%56,%57,%58,%59,%60,%61,%62,%63,%64,%65,%66,%67,%68,%69,%70,%71,%72,%73,%74,%75,%76,%77,%78,%79,%80,%81,%82,%83,%84,%85,%86,%87,%88,%89,%90,%91,%92,%93,%94,%95,%96,%97,%98,%99,%100,%101,%102,%103,%104,%105,%106,%107,%108,%109,%110,%111}, {%112,%113,%114,%115}, bd, p, 1, 1, 1;\n}\n"
    : "+f"(d[0]),"+f"(d[1]),"+f"(d[2]),"+f"(d[3]),"+f"(d[4]),"+f"(d[5]),"+f"(d[6]),"+f"(d[7]),"+f"(d[8]),"+f"(d[9]),"+f"(d[10]),"+f"(d[11]),"+f"(d[12]),"+f"(d[13]),"+f"(d[14]),"+f"(d[15]),"+f"(d[16]),"+f"(d[17]),"+f"(d[18]),"+f"(d[19]),"+f"(d[20]),"+f"(d[21]),"+f"(d[22]),"+f"(d[23]),"+f"(d[24]),"+f"(d[25]),"+f"(d[26]),"+f"(d[27]),"+f"(d[28]),"+f"(d[29]),"+f"(d[30]),"+f"(d[31]),"+f"(d[32]),"+f"(d[33]),"+f"(d[34]),"+f"(d[35]),"+f"(d[36]),"+f"(d[37]),"+f"(d[38]),"+f"(d[39]),"+f"(d[40]),"+f"(d[41]),"+f"(d[42]),"+f"(d[43]),"+f"(d[44]),"+f"(d[45]),"+f"(d[46]),"+f"(d[47]),"+f"(d[48]),"+f"(d[49]),"+f"(d[50]),"+f"(d[51]),"+f"(d[52]),"+f"(d[53]),"+f"(d[54]),"+f"(d[55]),"+f"(d[56]),"+f"(d[57]),"+f"(d[58]),"+f"(d[59]),"+f"(d[60]),"+f"(d[61]),"+f"(d[62]),"+f"(d[63]),"+f"(d[64]),"+f"(d[65]),"+f"(d[66]),"+f"(d[67]),"+f"(d[68]),"+f"(d[69]),"+f"(d[70]),"+f"(d[71]),"+f"(d[72]),"+f"(d[73]),"+f"(d[74]),"+f"(d[75]),"+f"(d[76]),"+f"(d[77]),"+f"(d[78]),"+f"(d[79]),"+f"(d[80]),"+f"(d[81]),"+f"(d[82]),"+f"(d[83]),"+f"(d[84]),"+f"(d[85]),"+f"(d[86]),"+f"(d[87]),"+f"(d[88]),"+f"(d[89]),"+f"(d[90]),"+f"(d[91]),"+f"(d[92]),"+f"(d[93]),"+f"(d[94]),"+f"(d[95]),"+f"(d[96]),"+f"(d[97]),"+f"(d[98]),"+f"(d[99]),"+f"(d[100]),"+f"(d[101]),"+f"(d[102]),"+f"(d[103]),"+f"(d[104]),"+f"(d[105]),"+f"(d[106]),"+f"(d[107]),"+f"(d[108]),"+f"(d[109]),"+f"(d[110]),"+f"(d[111])
    : "r"(a0), "r"(a1), "r"(a2), "r"(a3), "r"(blo), "n"(OFF), "n"(BHI), "n"(ACC));
}
template <int OFF, uint32_t BHI, int ACC>
__device__ __forceinline__ void wgmma_rs56(float (&d)[28], uint32_t a0, uint32_t a1, uint32_t a2, uint32_t a3, uint32_t blo) {
  asm volatile("{\n.reg .pred p;\n.reg .b32 l;\n.reg .b64 bd;\nsetp.ne.b32 p, %35, 0;\nadd.u32 l, %32, %33;\nmov.b64 bd, {l, %34};\n"
    "wgmma.mma_async.sync.aligned.m64n56k16.f32.bf16.bf16 {%0,%1,%2,%3,%4,%5,%6,%7,%8,%9,%10,%11,%12,%13,%14,%15,%16,%17,%18,%19,%20,%21,%22,%23,%24,%25,%26,%27}, {%28,%29,%30,%31}, bd, p, 1, 1, 1;\n}\n"
    : "+f"(d[0]),"+f"(d[1]),"+f"(d[2]),"+f"(d[3]),"+f"(d[4]),"+f"(d[5]),"+f"(d[6]),"+f"(d[7]),"+f"(d[8]),"+f"(d[9]),"+f"(d[10]),"+f"(d[11]),"+f"(d[12]),"+f"(d[13]),"+f"(d[14]),"+f"(d[15]),"+f"(d[16]),"+f"(d[17]),"+f"(d[18]),"+f"(d[19]),"+f"(d[20]),"+f"(d[21]),"+f"(d[22]),"+f"(d[23]),"+f"(d[24]),"+f"(d[25]),"+f"(d[26]),"+f"(d[27])
    : "r"(a0), "r"(a1), "r"(a2), "r"(a3), "r"(blo), "n"(OFF), "n"(BHI), "n"(ACC));
}

__global__ void k_ln1(const __nv_bfloat16* __restrict__ x) {
  int row = blockIdx.x * 8 + threadIdx.x / 32, lane = threadIdx.x & 31;
  float v[14]; float s = 0;
  for (int i = 0; i < 14; i++) { v[i] = __bfloat162float(x[row * DM + lane + 32 * i]); s += v[i]; }
  for (int o = 16; o; o >>= 1) s += __shfl_xor_sync(~0u, s, o);
  float mean = s / DM, q = 0;
  for (int i = 0; i < 14; i++) q += (v[i] - mean) * (v[i] - mean);
  for (int o = 16; o; o >>= 1) q += __shfl_xor_sync(~0u, q, o);
  float m = rbf(mean), sd = rbf(sqrtf(rbf(rbf(q / DM) + 1e-5f)));
  for (int i = 0; i < 14; i++) g_u[row * DM + lane + 32 * i] = __float2bfloat16_rn(rbf(v[i] - m) / sd);
  if (blockIdx.x == 0 && threadIdx.x == 0) g_epoch = g_epoch + 1;
}
__global__ void k_kgen(const __nv_bfloat16* are, const __nv_bfloat16* aim, const __nv_bfloat16* bre, const __nv_bfloat16* bim,
                       const __nv_bfloat16* cre, const __nv_bfloat16* cim, const __nv_bfloat16* logdt) {
  int d = blockIdx.x;
  float dt = rbf(expf(__bfloat162float(logdt[d])));
  for (int l = threadIdx.x; l < 2048; l += blockDim.x) {
    float lf = rbf((float)l), acc = 0;
    for (int n = 0; n < NST; n++) {
      int i = d * NST + n;
      float lr = dt * __bfloat162float(are[i]), li = dt * __bfloat162float(aim[i]);
      float br = dt * __bfloat162float(bre[i]), bi = dt * __bfloat162float(bim[i]);
      float cr = __bfloat162float(cre[i]), ci = __bfloat162float(cim[i]);
      float wr = cr * br - ci * bi, wi = cr * bi + ci * br;
      float e = expf(lr * lf), sn, cs; sincosf(li * lf, &sn, &cs);
      acc += e * (wr * cs - wi * sn);
    }
    g_kd[d * 2064 + l] = acc;
  }
}
__global__ void k_conv(const __nv_bfloat16* __restrict__ x, const __nv_bfloat16* dskip) {
  __shared__ float sk[2048], su[2048];
  int d = blockIdx.x;
  for (int i = threadIdx.x; i < 2048; i += blockDim.x) { sk[i] = g_kd[d * 2064 + i]; su[i] = __bfloat162float(g_u[i * DM + d]); }
  __syncthreads();
  float ds = __bfloat162float(dskip[d]);
  for (int t = threadIdx.x; t < 2048; t += blockDim.x) {
    float acc = 0;
    for (int l = 0; l <= t; l++) acc += sk[l] * su[t - l];
    float yb = rbf(rbf(acc) + rbf(su[t] * ds));
    float h = rbf(__bfloat162float(x[t * DM + d]) + yb);
    int tau = t >> 3, rt = tau >> 4, mh = (tau >> 3) & 1, c = tau & 7, r = d & 7;
    size_t off = (size_t)rt * 114688 + (d >> 3) * 2048 + mh * 1024 + r * 128 + ((c ^ r) * 16) + (t & 7) * 2;
    *(__nv_bfloat16*)((char*)g_himg + off) = __float2bfloat16_rn(h);
  }
}
__global__ void k_colsum(const __nv_bfloat16* wg, const __nv_bfloat16* wu) {
  int f = blockIdx.x * blockDim.x + threadIdx.x;
  const __nv_bfloat16* w = f < FF ? wg : wu; int ff = f < FF ? f : f - FF;
  float s = 0; for (int d = 0; d < DM; d++) s += __bfloat162float(w[d * FF + ff]);
  float hi = rbf(s), mid = rbf(s - hi), lo = rbf(s - hi - mid);
  int j = ff / 224, q = (ff % 224) / 112, n = ff % 112 + (f < FF ? 0 : 112);
  __nv_bfloat16* dst = (__nv_bfloat16*)(g_cimg + (j * 2 + q) * 224 + (n >> 3) * 8) + (n & 7);
  dst[0] = __float2bfloat16_rn(hi); dst[8] = __float2bfloat16_rn(mid); dst[16] = __float2bfloat16_rn(lo);
  for (int k = 3; k < 8; k++) dst[8 * k] = __float2bfloat16_rn(0.f);
}
__global__ void k_pack(const uint4* __restrict__ wg, const uint4* __restrict__ wu, const uint4* __restrict__ wd) {
  int i = blockIdx.x * blockDim.x + threadIdx.x;
  int mat = i / 100352, e = i % 100352;
  if (mat < 2) {
    int d = e / 224, ngg = e % 224;
    int j = ngg / 28, q = (ngg % 28) / 14, ng = ngg % 14 + 14 * mat;
    g_wimg[(size_t)j * 37632 + (q * 14 + (d >> 5)) * 896 + ng * 32 + (d & 31)] = (mat ? wu : wg)[e];
  } else {
    int f = e / 56, ngg = e % 56;
    int j = f / 224, hf = (f % 224) / 112, k = f % 112, c = ngg / 7, ng = ngg % 7;
    g_wimg[(size_t)j * 37632 + 25088 + (c * 2 + hf) * 784 + ng * 112 + k] = wd[e];
  }
}

constexpr int B_SA = 0, B_RING = 114688, B_SLOT = 14336, B_NSLOT = 7;
constexpr int B_CS = B_RING + B_NSLOT * B_SLOT;
constexpr int B_STAT = B_CS + 7168;
constexpr int B_RED = B_STAT + 1024;
constexpr int B_BAR = B_RED + 512;
constexpr int B_SMEM = B_BAR + 512;

__device__ __forceinline__ void st128(uint4* p, uint32_t a, uint32_t b, uint32_t c, uint32_t d) {
  asm volatile("{\n.reg .b128 v;\n.reg .b64 lo, hi;\nmov.b64 lo, {%1, %2};\nmov.b64 hi, {%3, %4};\nmov.b128 v, {lo, hi};\n"
               "st.relaxed.gpu.global.b128 [%0], v;\n}" ::"l"(p), "r"(a), "r"(b), "r"(c), "r"(d) : "memory");
}
__device__ __forceinline__ void ld128(const uint4* p, uint32_t* r) {
  asm volatile("{\n.reg .b128 v;\n.reg .b64 lo, hi;\nld.relaxed.gpu.global.b128 v, [%4];\nmov.b128 {lo, hi}, v;\n"
               "mov.b64 {%0, %1}, lo;\nmov.b64 {%2, %3}, hi;\n}" : "=r"(r[0]), "=r"(r[1]), "=r"(r[2]), "=r"(r[3]) : "l"(p) : "memory");
}

__device__ __forceinline__ uint32_t mapa(uint32_t a, uint32_t r) { uint32_t o; asm("mapa.shared::cluster.u32 %0, %1, %2;" : "=r"(o) : "r"(a), "r"(r)); return o; }

template <int Q, int ST>
__device__ __forceinline__ void g1_stage(float (&acc)[112], uint32_t alo, uint32_t blo, uint32_t bar_full, uint32_t bar_h) {
  constexpr int s = Q * 14 + ST, sl = s % B_NSLOT;
  if (Q == 0) mbar_wait(bar_h + 8 * ST, 0);
  mbar_wait(bar_full + 8 * sl, (s / B_NSLOT) & 1);
  wg_fence();
  wgmma_ss224<(2 * ST) * 256, 0x40000080u, (sl * B_SLOT) / 16, 32, ST != 0>(acc, alo, blo);
  wgmma_ss224<(2 * ST + 1) * 256, 0x40000080u, (sl * B_SLOT + 256) / 16, 32, 1>(acc, alo, blo);
}

__global__ void __cluster_dims__(2, 1, 1) __launch_bounds__(384, 1) k_ffn(__nv_bfloat16* __restrict__ out) {
  extern __shared__ __align__(1024) unsigned char sm[];
  const uint32_t sb = s2u(sm);
  const int tid = threadIdx.x, wg = tid >> 7, warp = tid >> 5, lane = tid & 31;
  const int rank = blockIdx.x & 1, rt = blockIdx.x & 15, j = blockIdx.x >> 4;
  const uint32_t bar_full = sb + B_BAR, bar_empty = bar_full + 64, bar_h = bar_full + 128, bar_cs = bar_full + 240, bar_stat = bar_full + 248,
                 bar_adead = bar_full + 256, bar_in = bar_full + 264;
  if (tid == 0) {
    TR(1, 0);
    for (int i = 0; i < B_NSLOT; i++) { mbar_init(bar_full + 8 * i, 1); mbar_init(bar_empty + 8 * i, 4); }
    for (int i = 0; i < 14; i++) mbar_init(bar_h + 8 * i, 1);
    mbar_init(bar_cs, 1);
    mbar_init(bar_stat, 64);
    mbar_init(bar_adead, 2);
    for (int i = 0; i < 14; i++) mbar_init(bar_in + 8 * i, 32);
    asm volatile("fence.mbarrier_init.release.cluster;" ::: "memory");
  }
  __syncthreads();
  asm volatile("barrier.cluster.arrive.release.aligned;" ::: "memory");

  if (wg == 2) {
    asm volatile("setmaxnreg.dec.sync.aligned.u32 88;");
    asm volatile("barrier.cluster.wait.acquire.aligned;" ::: "memory");
    asm volatile("griddepcontrol.wait;" ::: "memory");
    if (warp == 8) {
      if (lane == 0) {
        const char* wsrc = (const char*)g_wimg + (size_t)j * 602112;
        TR(1, 1);
        int slot = 0, ph = 0;
        for (int s = 0; s < 44; s++) {
          if (s >= B_NSLOT) mbar_wait(bar_empty + 8 * slot, ph ^ 1);
          uint32_t dst = sb + B_RING + slot * B_SLOT, fb = bar_full + 8 * slot;
          if (s < 28) {
            mbar_expect(fb, 14336);
            bulk_ld_mc(dst + rank * 7168, wsrc + s * 14336 + rank * 7168, 7168, fb);
          } else {
            const int c = (j + 1 + ((s - 28) >> 1)) & 7;
            mbar_expect(fb, 12544);
            bulk_ld_mc(dst + rank * 6272, wsrc + 401408 + (c * 2 + (s & 1)) * 12544 + rank * 6272, 6272, fb);
          }
          if (++slot == B_NSLOT) { slot = 0; ph ^= 1; }
        }
      }
    } else if (warp == 9) {
      if (lane == 0) {
        const char* hsrc = (const char*)g_himg + (size_t)rt * 114688;
        for (int i = 0; i < 14; i++) {
          mbar_expect(bar_h + 8 * i, 8192);
          bulk_ld(sb + B_SA + i * 8192, hsrc + i * 8192, 8192, bar_h + 8 * i);
        }
        mbar_expect(bar_cs, 7168);
        bulk_ld(sb + B_CS, g_cimg + j * 448, 7168, bar_cs);
      }
    } else {
      const int t64 = tid - 320, hw = warp & 1;
      const uint32_t tag = __ldcg(&g_epoch) & 1u;
      mbar_wait(bar_h + 8 * 13, 0);
      {
        uint32_t w[4];
        int it = 0;
        do { ld128((const uint4*)(g_stat2 + rt * 128) + t64, w); } while ((((w[1] ^ tag) | (w[3] ^ tag)) & 1u) && ++it < 200000);
        *(uint4*)(sm + B_STAT + t64 * 16) = make_uint4(w[0], w[1], w[2], w[3]);
        mbar_arrive(bar_stat);
      }
      if (t64 == 0) TR(1, 18);
      mbar_wait(bar_adead, 0);
      const uint32_t tag16 = tag << 16;
#pragma unroll 1
      for (int q = 0; q < 7; q++) {
        const uint4* src = g_part + (size_t)((rt * 8 + j) * 7 + q) * 896 + hw * 448 + lane;
        uint32_t v[14][4];
        int it = 0;
        while (true) {
          uint32_t bad = 0;
#pragma unroll
          for (int i = 0; i < 14; i++) ld128(src + i * 32, v[i]);
#pragma unroll
          for (int i = 0; i < 14; i++) bad |= (v[i][3] ^ tag16) | (i >= 12 ? v[i][1] ^ tag16 : 0u);
          if (__all_sync(~0u, (bad & 0x10000u) == 0) || ++it > 100000) break;
        }
        uint4* dst = (uint4*)(sm + B_SA + q * 14336 + hw * 7168) + lane;
#pragma unroll
        for (int i = 0; i < 14; i++) dst[i * 32] = make_uint4(v[i][0], v[i][1], v[i][2], v[i][3]);
        mbar_arrive(bar_in + 8 * (hw * 7 + q));
        if (t64 == 0) TR(1, 24 + q);
      }
    }
  } else {
    asm volatile("setmaxnreg.inc.sync.aligned.u32 208;");
    const int g = lane >> 2, t = lane & 3, wq = warp & 3, t128 = tid & 127;
    uint32_t hh[56], hres[16];
    asm volatile("barrier.cluster.wait.acquire.aligned;" ::: "memory");
    asm volatile("griddepcontrol.wait;" ::: "memory");
    const uint32_t tag = (__ldcg(&g_epoch) & 1u) << 16;
    const uint32_t rel_bar = mapa(bar_empty, t128 & 1);
    auto release = [&](int sl) { if (t128 < 2) asm volatile("mbarrier.arrive.shared::cluster.b64 _, [%0];" ::"r"(rel_bar + 8 * sl) : "memory"); };
    const uint32_t alo = __shfl_sync(~0u, ((sb + B_SA + wg * 1024) & 0x3FFFF) >> 4, 0);
    const uint32_t blo = (((sb + B_RING) & 0x3FFFF) >> 4) | (8u << 16);
    const uint32_t clo = ((sb + B_CS) & 0x3FFFF) >> 4;
    uint32_t nm0, nm1; float r20, r21;
    if (wg == 1) {
      const int c2 = lane & 1, r = (lane >> 1) & 7;
      const uint4* src = g_himg + (size_t)rt * 7168 + (t128 >> 4) * 128 + (j >> 2) * 64 + r * 8 + ((((j & 3) * 2 + c2) ^ r));
      uint4 v[7];
#pragma unroll
      for (int i = 0; i < 7; i++) v[i] = __ldcg(src + i * 1024);
      float a[16];
#pragma unroll
      for (int k = 0; k < 16; k++) a[k] = 0.f;
#pragma unroll
      for (int i = 0; i < 7; i++) {
        float e[8] = {bf_lo(v[i].x), bf_hi(v[i].x), bf_lo(v[i].y), bf_hi(v[i].y), bf_lo(v[i].z), bf_hi(v[i].z), bf_lo(v[i].w), bf_hi(v[i].w)};
#pragma unroll
        for (int k = 0; k < 8; k++) { a[2 * k] += e[k]; a[2 * k + 1] = fmaf(e[k], e[k], a[2 * k + 1]); }
      }
#pragma unroll
      for (int rd = 0; rd < 4; rd++) {
        const int n = 8 >> rd;
        const bool up = lane & (2 * n);
#pragma unroll
        for (int k = 0; k < 8; k++) {
          if (k < n) {
            float keep = up ? a[k + n] : a[k], give = up ? a[k] : a[k + n];
            a[k] = keep + __shfl_xor_sync(~0u, give, 2 * n);
          }
        }
      }
      float* red = (float*)(sm + B_RED);
      red[wq * 32 + c2 * 16 + (lane >> 1)] = a[0];
      asm volatile("bar.sync 1, 128;" ::: "memory");
      if (t128 < 16) {
        float2 p0 = *(float2*)(red + 2 * t128), p1 = *(float2*)(red + 32 + 2 * t128), p2 = *(float2*)(red + 64 + 2 * t128), p3 = *(float2*)(red + 96 + 2 * t128);
        float mean = ((p0.x + p1.x) + (p2.x + p3.x)) * (1.f / DM);
        float var = fmaxf(fmaf(-mean, mean, ((p0.y + p1.y) + (p2.y + p3.y)) * (1.f / DM)), 0.f);
        float rs = 1.f / rbf(sqrtf(rbf(rbf(var) + 1e-5f)));
        uint32_t nm = pack_bf16(-mean, -mean), r2 = (__float_as_uint(rs * rs) & ~1u) | (tag >> 16);
        asm volatile("{\n.reg .b64 v;\nmov.b64 v, {%1, %2};\nst.relaxed.gpu.global.b64 [%0], v;\n}"
                     ::"l"(g_stat2 + rt * 128 + j * 16 + t128), "r"(nm), "r"(r2) : "memory");
      }
      if (t128 == 0) TR(1, 2);
    }
#define G1S(Q, ST) do { g1_stage<Q, ST>(acc, alo, blo, bar_full, bar_h); wg_commit(); \
      if (ST > 0) { wg_wait<1>(); release((Q * 14 + ST - 1) % B_NSLOT); } } while (0)
#define G1EPI(Q) do { \
      g1_stage<Q, 13>(acc, alo, blo, bar_full, bar_h); \
      wgmma_rs224<Q * 224, 8, 1>(acc, nm0, nm1, 0u, 0u, clo); \
      wg_commit(); wg_wait<1>(); release((Q * 14 + 12) % B_NSLOT); \
      wg_wait<0>(); reg_fence(acc); release((Q * 14 + 13) % B_NSLOT); \
      _Pragma("unroll") \
      for (int i = 0; i < 28; i++) hh[28 * Q + i] = pack_bf16(acc[2 * i] * acc[56 + 2 * i], acc[2 * i + 1] * acc[57 + 2 * i]); \
    } while (0)
    {
      float acc[112];
      G1S(0, 0);
      if (tid == 0) TR(1, 3);
      G1S(0, 1);
      G1S(0, 2); G1S(0, 3); G1S(0, 4); G1S(0, 5); G1S(0, 6); G1S(0, 7); G1S(0, 8); G1S(0, 9); G1S(0, 10); G1S(0, 11); G1S(0, 12);
      if (tid == 0) TR(1, 4);
      mbar_wait(bar_stat, 0);
      mbar_wait(bar_cs, 0);
      {
        uint2 a = *(const uint2*)(sm + B_STAT + (wg * 64 + wq * 16 + g) * 8), b = *(const uint2*)(sm + B_STAT + (wg * 64 + wq * 16 + g + 8) * 8);
        const uint32_t msk = t == 0 ? 0xFFFFFFFFu : t == 1 ? 0xFFFFu : 0u;
        nm0 = a.x & msk; nm1 = b.x & msk; r20 = __uint_as_float(a.y); r21 = __uint_as_float(b.y);
      }
      G1EPI(0);
      if (tid == 0) TR(1, 5);
      G1S(1, 0); G1S(1, 1); G1S(1, 2); G1S(1, 3); G1S(1, 4); G1S(1, 5); G1S(1, 6); G1S(1, 7); G1S(1, 8); G1S(1, 9); G1S(1, 10); G1S(1, 11);
#pragma unroll
      for (int i = 0; i < 4; i++) {
        int qq = lane >> 3, r = lane & 7, kg = 7 * j + 2 * i + (qq >> 1), c = 2 * wq + (qq & 1);
        if (kg > 55) kg = 55;
        uint32_t addr = sb + B_SA + kg * 2048 + wg * 1024 + r * 128 + ((c ^ r) << 4);
        asm volatile("ldmatrix.sync.aligned.m8n8.x4.trans.shared.b16 {%0,%1,%2,%3}, [%4];"
                     : "=r"(hres[4 * i]), "=r"(hres[4 * i + 1]), "=r"(hres[4 * i + 2]), "=r"(hres[4 * i + 3]) : "r"(addr) : "memory");
      }
      G1S(1, 12);
      G1EPI(1);
      if (t128 == 0) mbar_arrive(bar_adead);
      if (tid == 0) TR(1, 6);
    }
    float accA[28], accB[28], sum[28];
    int nxt = 0;
#pragma unroll
    for (int i = 0; i < 28; i++) sum[i] = 0.f;
#define ISSUE(acc, I, a, FIRST) do { \
      constexpr int s_ = 28 + (I), sl_ = s_ % B_NSLOT; \
      mbar_wait(bar_full + 8 * sl_, (s_ / B_NSLOT) & 1); \
      wg_fence(); \
      wgmma_rs56<(sl_ * B_SLOT + 0 * 256) / 16, 112, !(FIRST)>(acc, (a)[0], (a)[1], (a)[2], (a)[3], blo); \
      wgmma_rs56<(sl_ * B_SLOT + 1 * 256) / 16, 112, 1>(acc, (a)[4], (a)[5], (a)[6], (a)[7], blo); \
      wgmma_rs56<(sl_ * B_SLOT + 2 * 256) / 16, 112, 1>(acc, (a)[8], (a)[9], (a)[10], (a)[11], blo); \
      wgmma_rs56<(sl_ * B_SLOT + 3 * 256) / 16, 112, 1>(acc, (a)[12], (a)[13], (a)[14], (a)[15], blo); \
      wgmma_rs56<(sl_ * B_SLOT + 4 * 256) / 16, 112, 1>(acc, (a)[16], (a)[17], (a)[18], (a)[19], blo); \
      wgmma_rs56<(sl_ * B_SLOT + 5 * 256) / 16, 112, 1>(acc, (a)[20], (a)[21], (a)[22], (a)[23], blo); \
      wgmma_rs56<(sl_ * B_SLOT + 6 * 256) / 16, 112, 1>(acc, (a)[24], (a)[25], (a)[26], (a)[27], blo); \
      wg_commit(); } while (0)
    auto rel = [&](int i) { if (i < 9) release((28 + i) % B_NSLOT); };
    auto tg = [&](uint32_t v) { return (v & 0xFFFEFFFFu) | tag; };
    auto send_lo = [&](float (&acc)[28], int cc) {
      reg_fence(acc);
      uint4* dst = g_part + (size_t)((rt * 8 + ((j + 1 + cc) & 7)) * 7 + cc) * 896 + wg * 448 + t128;
#pragma unroll
      for (int q = 0; q < 2; q++)
        st128(dst + q * 128, pack_bf16(acc[8 * q], acc[8 * q + 1]), pack_bf16(acc[8 * q + 2], acc[8 * q + 3]),
              pack_bf16(acc[8 * q + 4], acc[8 * q + 5]), tg(pack_bf16(acc[8 * q + 6], acc[8 * q + 7])));
    };
    auto send_hi = [&](float (&acc)[28], int cc) {
      uint4* dst = g_part + (size_t)((rt * 8 + ((j + 1 + cc) & 7)) * 7 + cc) * 896 + wg * 448;
      st128(dst + 256 + t128, pack_bf16(acc[16], acc[17]), pack_bf16(acc[18], acc[19]), pack_bf16(acc[20], acc[21]), tg(pack_bf16(acc[22], acc[23])));
      asm volatile("{\n.reg .b64 v;\nmov.b64 v, {%1, %2};\nst.relaxed.gpu.global.b64 [%0], v;\n}"
                   ::"l"((uint2*)(dst + 384) + t128), "r"(pack_bf16(acc[24], acc[25])), "r"(tg(pack_bf16(acc[26], acc[27]))) : "memory");
    };
    auto accum = [&]() {
      const unsigned char* src = sm + B_SA + nxt * 14336 + wg * 7168;
      uint4 a = *(const uint4*)(src + t128 * 16), b = *(const uint4*)(src + 2048 + t128 * 16), c = *(const uint4*)(src + 4096 + t128 * 16);
      uint2 d = *(const uint2*)(src + 6144 + t128 * 8);
      uint32_t in[14] = {a.x, a.y, a.z, a.w, b.x, b.y, b.z, b.w, c.x, c.y, c.z, c.w, d.x, d.y};
#pragma unroll
      for (int i = 0; i < 14; i++) { sum[2 * i] += bf_lo(in[i]); sum[2 * i + 1] += bf_hi(in[i]); }
      nxt++;
    };
    auto try_accum = [&]() {
      uint32_t ok;
      asm volatile("{\n.reg .pred p;\nmbarrier.test_wait.parity.shared::cta.b64 p, [%1], 0;\nselp.u32 %0, 1, 0, p;\n}"
                   : "=r"(ok) : "r"(bar_in + 8 * (wg * 7 + nxt)) : "memory");
      if (__all_sync(~0u, ok)) accum();
    };
#define CHUNK(cur, prev, CC, EXTRA) do { \
      ISSUE(cur, 2 * (CC), hh, true); wg_wait<1>(); rel(2 * (CC) - 1); send_lo(prev, (CC) - 1); \
      ISSUE(cur, 2 * (CC) + 1, hh + 28, false); send_hi(prev, (CC) - 1); EXTRA; wg_wait<1>(); rel(2 * (CC)); } while (0)
    ISSUE(accA, 0, hh, true);
    ISSUE(accA, 1, hh + 28, false); wg_wait<1>(); rel(0);
    CHUNK(accB, accA, 1, );
    if (tid == 0) TR(1, 11);
    CHUNK(accA, accB, 2, );
    if (tid == 0) TR(1, 12);
    CHUNK(accB, accA, 3, try_accum());
    if (tid == 0) TR(1, 13);
    CHUNK(accA, accB, 4, try_accum());
    if (tid == 0) TR(1, 14);
    CHUNK(accB, accA, 5, try_accum());
    if (tid == 0) TR(1, 16);
    CHUNK(accA, accB, 6, try_accum());
    if (tid == 0) TR(1, 17);
    CHUNK(accB, accA, 7, try_accum());
    if (tid == 0) TR(1, 7);
#pragma unroll 1
    while (nxt < 7) { mbar_wait(bar_in + 8 * (wg * 7 + nxt), 0); accum(); }
    wg_wait<0>();
    reg_fence(accB);
    if (tid == 0) TR(1, 9);
    const int row = rt * 128 + wg * 64 + wq * 16 + g;
    uint32_t* o0 = (uint32_t*)(out + (size_t)row * DM + 56 * j + 2 * t);
    uint32_t* o1 = o0 + 8 * DM / 2;
#pragma unroll
    for (int i = 0; i < 7; i++) {
      o0[4 * i] = hadd2_bf(hres[2 * i], pack_bf16((sum[4 * i] + accB[4 * i]) * r20, (sum[4 * i + 1] + accB[4 * i + 1]) * r20));
      o1[4 * i] = hadd2_bf(hres[2 * i + 1], pack_bf16((sum[4 * i + 2] + accB[4 * i + 2]) * r21, (sum[4 * i + 3] + accB[4 * i + 3]) * r21));
    }
    if (tid == 0) TR(1, 10);
    if (tid == 128) TR(1, 15);

  }
}

extern "C" void kernel_launch(void* const* d_in, const int* in_sizes, int n_in, void* d_out, int out_size) {
  const __nv_bfloat16* x = (const __nv_bfloat16*)d_in[0];
  const __nv_bfloat16 *are = (const __nv_bfloat16*)d_in[1], *aim = (const __nv_bfloat16*)d_in[2], *bre = (const __nv_bfloat16*)d_in[3],
                      *bim = (const __nv_bfloat16*)d_in[4], *cre = (const __nv_bfloat16*)d_in[5], *cim = (const __nv_bfloat16*)d_in[6],
                      *logdt = (const __nv_bfloat16*)d_in[7], *dskip = (const __nv_bfloat16*)d_in[8];
  const __nv_bfloat16 *wg = (const __nv_bfloat16*)d_in[10], *wu = (const __nv_bfloat16*)d_in[11], *wd = (const __nv_bfloat16*)d_in[12];

  static bool init = false;
  if (!init) {
    init = true;
    cudaFuncSetAttribute(k_ffn, cudaFuncAttributeMaxDynamicSharedMemorySize, B_SMEM);
  }
  cudaStream_t st = cudaStreamPerThread;
  k_ln1<<<256, 256, 0, st>>>(x);
  k_kgen<<<DM, 512, 0, st>>>(are, aim, bre, bim, cre, cim, logdt);
  k_conv<<<DM, 512, 0, st>>>(x, dskip);
  k_colsum<<<2 * FF / 128, 128, 0, st>>>(wg, wu);
  k_pack<<<3 * 100352 / 256, 256, 0, st>>>((const uint4*)wg, (const uint4*)wu, (const uint4*)wd);
  k_ffn<<<128, 384, B_SMEM, st>>>((__nv_bfloat16*)d_out);
}
```

```cpp
#include <cuda_runtime.h>
#include <cuda_bf16.h>
#include <stdint.h>

constexpr int LSEQ = 2048, DM = 448, FF = 1792, NST = 256;

__device__ uint4    g_himg[16 * 114688 / 16];
__device__ uint4    g_cimg[8 * 2 * 224];
__device__ uint2    g_stat2[LSEQ];
__device__ uint4    g_part[128 * 7 * 896];
__device__ uint4    g_wimg[8 * 602112 / 16];
__device__ unsigned g_epoch;
__device__ uint4    g_flag[128 * 16];
__device__ __nv_bfloat16 g_u[LSEQ * DM];
__device__ float    g_kd[DM * 2064];

#define TR(k, i) do {} while (0)
__device__ __forceinline__ uint32_t s2u(const void* p) { return (uint32_t)__cvta_generic_to_shared(p); }
__device__ __forceinline__ void mbar_init(uint32_t b, int c) { asm volatile("mbarrier.init.shared::cta.b64 [%0], %1;" ::"r"(b), "r"(c)); }
__device__ __forceinline__ void mbar_expect(uint32_t b, int bytes) { asm volatile("mbarrier.arrive.expect_tx.shared::cta.b64 _, [%0], %1;" ::"r"(b), "r"(bytes) : "memory"); }
__device__ __forceinline__ void mbar_arrive(uint32_t b) { asm volatile("mbarrier.arrive.shared::cta.b64 _, [%0];" ::"r"(b) : "memory"); }
__device__ __forceinline__ void mbar_wait(uint32_t b, int ph) {
  asm volatile("{\n.reg .pred p;\n.reg .b32 n;\nmov.b32 n, 0;\nLW:\nmbarrier.try_wait.parity.shared::cta.b64 p, [%0], %1;\n@p bra LD;\n"
               "add.u32 n, n, 1;\nsetp.lt.u32 p, n, 4000000;\n@p bra LW;\ntrap;\nLD:\n}" ::"r"(b), "r"(ph) : "memory");
}
__device__ __forceinline__ uint64_t mkdesc(uint32_t addr, uint32_t lbo, uint32_t sbo, uint32_t sw) {
  return (uint64_t)((addr & 0x3FFFF) >> 4) | ((uint64_t)((lbo >> 4) & 0x3FFF) << 16) | ((uint64_t)((sbo >> 4) & 0x3FFF) << 32) | ((uint64_t)sw << 62);
}
__device__ __forceinline__ void wg_fence() { asm volatile("wgmma.fence.sync.aligned;" ::: "memory"); }
__device__ __forceinline__ void wg_commit() { asm volatile("wgmma.commit_group.sync.aligned;" ::: "memory"); }
template <int N> __device__ __forceinline__ void wg_wait() { asm volatile("wgmma.wait_group.sync.aligned %0;" ::"n"(N) : "memory"); }
template <int N> __device__ __forceinline__ void reg_fence(float (&a)[N]) {
#pragma unroll
  for (int i = 0; i < N; i++) asm volatile("" : "+f"(a[i])::"memory");
}
__device__ __forceinline__ uint32_t pack_bf16(float lo, float hi) {
  uint32_t r; asm("cvt.rn.bf16x2.f32 %0, %1, %2;" : "=r"(r) : "f"(hi), "f"(lo)); return r;
}
__device__ __forceinline__ float bf_lo(uint32_t v) { return __uint_as_float(v << 16); }
__device__ __forceinline__ float bf_hi(uint32_t v) { return __uint_as_float(v & 0xFFFF0000u); }
__device__ __forceinline__ float rbf(float x) { return __bfloat162float(__float2bfloat16_rn(x)); }
__device__ __forceinline__ uint32_t hmul2_bf(uint32_t a, uint32_t b) { uint32_t r; asm("mul.rn.bf16x2 %0, %1, %2;" : "=r"(r) : "r"(a), "r"(b)); return r; }
__device__ __forceinline__ uint32_t hadd2_bf(uint32_t a, uint32_t b) { uint32_t r; asm("add.rn.bf16x2 %0, %1, %2;" : "=r"(r) : "r"(a), "r"(b)); return r; }
__device__ __forceinline__ void bulk_ld(uint32_t dst, const void* src, int bytes, uint32_t bar) {
  asm volatile("cp.async.bulk.shared::cluster.global.mbarrier::complete_tx::bytes [%0], [%1], %2, [%3];"
               ::"r"(dst), "l"(src), "r"(bytes), "r"(bar) : "memory");
}

__device__ __forceinline__ void bulk_ld_mc(uint32_t dst, const void* src, int bytes, uint32_t bar) {
  asm volatile("cp.async.bulk.shared::cluster.global.mbarrier::complete_tx::bytes.multicast::cluster [%0], [%1], %2, [%3], %4;"
               ::"r"(dst), "l"(src), "r"(bytes), "r"(bar), "h"((uint16_t)3) : "memory");
}
template <int AOFF, uint32_t AHI, int BOFF, uint32_t BHI, int ACC>
__device__ __forceinline__ void wgmma_ss224(float (&d)[112], uint32_t alo, uint32_t blo) {
  asm volatile("{\n.reg .pred p;\n.reg .b32 la, lb;\n.reg .b64 ad, bd;\nsetp.ne.b32 p, %118, 0;\n"
    "add.u32 la, %112, %114;\nmov.b64 ad, {la, %115};\nadd.u32 lb, %113, %116;\nmov.b64 bd, {lb, %117};\n"
    "wgmma.mma_async.sync.aligned.m64n224k16.f32.bf16.bf16 {%0,%1,%2,%3,%4,%5,%6,%7,%8,%9,%10,%11,%12,%13,%14,%15,%16,%17,%18,%19,%20,%21,%22,%23,%24,%25,%26,%27,%28,%29,%30,%31,%32,%33,%34,%35,%36,%37,%38,%39,%40,%41,%42,%43,%44,%45,%46,%47,%48,%49,%50,%51,%52,%53,%54,%55,%56,%57,%58,%59,%60,%61,%62,%63,%64,%65,%66,%67,%68,%69,%70,%71,%72,%73,%74,%75,%76,%77,%78,%79,%80,%81,%82,%83,%84,%85,%86,%87,%88,%89,%90,%91,%92,%93,%94,%95,%96,%97,%98,%99,%100,%101,%102,%103,%104,%105,%106,%107,%108,%109,%110,%111}, ad, bd, p, 1, 1, 1, 1;\n}\n"
    : "+f"(d[0]),"+f"(d[1]),"+f"(d[2]),"+f"(d[3]),"+f"(d[4]),"+f"(d[5]),"+f"(d[6]),"+f"(d[7]),"+f"(d[8]),"+f"(d[9]),"+f"(d[10]),"+f"(d[11]),"+f"(d[12]),"+f"(d[13]),"+f"(d[14]),"+f"(d[15]),"+f"(d[16]),"+f"(d[17]),"+f"(d[18]),"+f"(d[19]),"+f"(d[20]),"+f"(d[21]),"+f"(d[22]),"+f"(d[23]),"+f"(d[24]),"+f"(d[25]),"+f"(d[26]),"+f"(d[27]),"+f"(d[28]),"+f"(d[29]),"+f"(d[30]),"+f"(d[31]),"+f"(d[32]),"+f"(d[33]),"+f"(d[34]),"+f"(d[35]),"+f"(d[36]),"+f"(d[37]),"+f"(d[38]),"+f"(d[39]),"+f"(d[40]),"+f"(d[41]),"+f"(d[42]),"+f"(d[43]),"+f"(d[44]),"+f"(d[45]),"+f"(d[46]),"+f"(d[47]),"+f"(d[48]),"+f"(d[49]),"+f"(d[50]),"+f"(d[51]),"+f"(d[52]),"+f"(d[53]),"+f"(d[54]),"+f"(d[55]),"+f"(d[56]),"+f"(d[57]),"+f"(d[58]),"+f"(d[59]),"+f"(d[60]),"+f"(d[61]),"+f"(d[62]),"+f"(d[63]),"+f"(d[64]),"+f"(d[65]),"+f"(d[66]),"+f"(d[67]),"+f"(d[68]),"+f"(d[69]),"+f"(d[70]),"+f"(d[71]),"+f"(d[72]),"+f"(d[73]),"+f"(d[74]),"+f"(d[75]),"+f"(d[76]),"+f"(d[77]),"+f"(d[78]),"+f"(d[79]),"+f"(d[80]),"+f"(d[81]),"+f"(d[82]),"+f"(d[83]),"+f"(d[84]),"+f"(d[85]),"+f"(d[86]),"+f"(d[87]),"+f"(d[88]),"+f"(d[89]),"+f"(d[90]),"+f"(d[91]),"+f"(d[92]),"+f"(d[93]),"+f"(d[94]),"+f"(d[95]),"+f"(d[96]),"+f"(d[97]),"+f"(d[98]),"+f"(d[99]),"+f"(d[100]),"+f"(d[101]),"+f"(d[102]),"+f"(d[103]),"+f"(d[104]),"+f"(d[105]),"+f"(d[106]),"+f"(d[107]),"+f"(d[108]),"+f"(d[109]),"+f"(d[110]),"+f"(d[111])
    : "r"(alo), "r"(blo), "n"(AOFF), "n"(AHI), "n"(BOFF), "n"(BHI), "n"(ACC));
}
template <int OFF, uint32_t BHI, int ACC>
__device__ __forceinline__ void wgmma_rs224(float (&d)[112], uint32_t a0, uint32_t a1, uint32_t a2, uint32_t a3, uint32_t blo) {
  asm volatile("{\n.reg .pred p;\n.reg .b32 l;\n.reg .b64 bd;\nsetp.ne.b32 p, %119, 0;\nadd.u32 l, %116, %117;\nmov.b64 bd, {l, %118};\n"
    "wgmma.mma_async.sync.aligned.m64n224k16.f32.bf16.bf16 {%0,%1,%2,%3,%4,%5,%6,%7,%8,%9,%10,%11,%12,%13,%14,%15,%16,%17,%18,%19,%20,%21,%22,%23,%24,%25,%26,%27,%28,%29,%30,%31,%32,%33,%34,%35,%36,%37,%38,%39,%40,%41,%42,%43,%44,%45,%46,%47,%48,%49,%50,%51,%52,%53,%54,%55,%56,%57,%58,%59,%60,%61,%62,%63,%64,%65,%66,%67,%68,%69,%70,%71,%72,%73,%74,%75,%76,%77,%78,%79,%80,%81,%82,%83,%84,%85,%86,%87,%88,%89,%90,%91,%92,%93,%94,%95,%96,%97,%98,%99,%100,%101,%102,%103,%104,%105,%106,%107,%108,%109,%110,%111}, {%112,%113,%114,%115}, bd, p, 1, 1, 1;\n}\n"
    : "+f"(d[0]),"+f"(d[1]),"+f"(d[2]),"+f"(d[3]),"+f"(d[4]),"+f"(d[5]),"+f"(d[6]),"+f"(d[7]),"+f"(d[8]),"+f"(d[9]),"+f"(d[10]),"+f"(d[11]),"+f"(d[12]),"+f"(d[13]),"+f"(d[14]),"+f"(d[15]),"+f"(d[16]),"+f"(d[17]),"+f"(d[18]),"+f"(d[19]),"+f"(d[20]),"+f"(d[21]),"+f"(d[22]),"+f"(d[23]),"+f"(d[24]),"+f"(d[25]),"+f"(d[26]),"+f"(d[27]),"+f"(d[28]),"+f"(d[29]),"+f"(d[30]),"+f"(d[31]),"+f"(d[32]),"+f"(d[33]),"+f"(d[34]),"+f"(d[35]),"+f"(d[36]),"+f"(d[37]),"+f"(d[38]),"+f"(d[39]),"+f"(d[40]),"+f"(d[41]),"+f"(d[42]),"+f"(d[43]),"+f"(d[44]),"+f"(d[45]),"+f"(d[46]),"+f"(d[47]),"+f"(d[48]),"+f"(d[49]),"+f"(d[50]),"+f"(d[51]),"+f"(d[52]),"+f"(d[53]),"+f"(d[54]),"+f"(d[55]),"+f"(d[56]),"+f"(d[57]),"+f"(d[58]),"+f"(d[59]),"+f"(d[60]),"+f"(d[61]),"+f"(d[62]),"+f"(d[63]),"+f"(d[64]),"+f"(d[65]),"+f"(d[66]),"+f"(d[67]),"+f"(d[68]),"+f"(d[69]),"+f"(d[70]),"+f"(d[71]),"+f"(d[72]),"+f"(d[73]),"+f"(d[74]),"+f"(d[75]),"+f"(d[76]),"+f"(d[77]),"+f"(d[78]),"+f"(d[79]),"+f"(d[80]),"+f"(d[81]),"+f"(d[82]),"+f"(d[83]),"+f"(d[84]),"+f"(d[85]),"+f"(d[86]),"+f"(d[87]),"+f"(d[88]),"+f"(d[89]),"+f"(d[90]),"+f"(d[91]),"+f"(d[92]),"+f"(d[93]),"+f"(d[94]),"+f"(d[95]),"+f"(d[96]),"+f"(d[97]),"+f"(d[98]),"+f"(d[99]),"+f"(d[100]),"+f"(d[101]),"+f"(d[102]),"+f"(d[103]),"+f"(d[104]),"+f"(d[105]),"+f"(d[106]),"+f"(d[107]),"+f"(d[108]),"+f"(d[109]),"+f"(d[110]),"+f"(d[111])
    : "r"(a0), "r"(a1), "r"(a2), "r"(a3), "r"(blo), "n"(OFF), "n"(BHI), "n"(ACC));
}
template <int OFF, uint32_t BHI, int ACC>
__device__ __forceinline__ void wgmma_rs56(float (&d)[28], uint32_t a0, uint32_t a1, uint32_t a2, uint32_t a3, uint32_t blo) {
  asm volatile("{\n.reg .pred p;\n.reg .b32 l;\n.reg .b64 bd;\nsetp.ne.b32 p, %35, 0;\nadd.u32 l, %32, %33;\nmov.b64 bd, {l, %34};\n"
    "wgmma.mma_async.sync.aligned.m64n56k16.f32.bf16.bf16 {%0,%1,%2,%3,%4,%5,%6,%7,%8,%9,%10,%11,%12,%13,%14,%15,%16,%17,%18,%19,%20,%21,%22,%23,%24,%25,%26,%27}, {%28,%29,%30,%31}, bd, p, 1, 1, 1;\n}\n"
    : "+f"(d[0]),"+f"(d[1]),"+f"(d[2]),"+f"(d[3]),"+f"(d[4]),"+f"(d[5]),"+f"(d[6]),"+f"(d[7]),"+f"(d[8]),"+f"(d[9]),"+f"(d[10]),"+f"(d[11]),"+f"(d[12]),"+f"(d[13]),"+f"(d[14]),"+f"(d[15]),"+f"(d[16]),"+f"(d[17]),"+f"(d[18]),"+f"(d[19]),"+f"(d[20]),"+f"(d[21]),"+f"(d[22]),"+f"(d[23]),"+f"(d[24]),"+f"(d[25]),"+f"(d[26]),"+f"(d[27])
    : "r"(a0), "r"(a1), "r"(a2), "r"(a3), "r"(blo), "n"(OFF), "n"(BHI), "n"(ACC));
}

__global__ void k_ln1(const __nv_bfloat16* __restrict__ x) {
  int row = blockIdx.x * 8 + threadIdx.x / 32, lane = threadIdx.x & 31;
  float v[14]; float s = 0;
  for (int i = 0; i < 14; i++) { v[i] = __bfloat162float(x[row * DM + lane + 32 * i]); s += v[i]; }
  for (int o = 16; o; o >>= 1) s += __shfl_xor_sync(~0u, s, o);
  float mean = s / DM, q = 0;
  for (int i = 0; i < 14; i++) q += (v[i] - mean) * (v[i] - mean);
  for (int o = 16; o; o >>= 1) q += __shfl_xor_sync(~0u, q, o);
  float m = rbf(mean), sd = rbf(sqrtf(rbf(rbf(q / DM) + 1e-5f)));
  for (int i = 0; i < 14; i++) g_u[row * DM + lane + 32 * i] = __float2bfloat16_rn(rbf(v[i] - m) / sd);
  if (blockIdx.x == 0 && threadIdx.x == 0) g_epoch = g_epoch + 1;
}
__global__ void k_kgen(const __nv_bfloat16* are, const __nv_bfloat16* aim, const __nv_bfloat16* bre, const __nv_bfloat16* bim,
                       const __nv_bfloat16* cre, const __nv_bfloat16* cim, const __nv_bfloat16* logdt) {
  int d = blockIdx.x;
  float dt = rbf(expf(__bfloat162float(logdt[d])));
  for (int l = threadIdx.x; l < 2048; l += blockDim.x) {
    float lf = rbf((float)l), acc = 0;
    for (int n = 0; n < NST; n++) {
      int i = d * NST + n;
      float lr = dt * __bfloat162float(are[i]), li = dt * __bfloat162float(aim[i]);
      float br = dt * __bfloat162float(bre[i]), bi = dt * __bfloat162float(bim[i]);
      float cr = __bfloat162float(cre[i]), ci = __bfloat162float(cim[i]);
      float wr = cr * br - ci * bi, wi = cr * bi + ci * br;
      float e = expf(lr * lf), sn, cs; sincosf(li * lf, &sn, &cs);
      acc += e * (wr * cs - wi * sn);
    }
    g_kd[d * 2064 + l] = acc;
  }
}
__global__ void k_conv(const __nv_bfloat16* __restrict__ x, const __nv_bfloat16* dskip) {
  __shared__ float sk[2048], su[2048];
  int d = blockIdx.x;
  for (int i = threadIdx.x; i < 2048; i += blockDim.x) { sk[i] = g_kd[d * 2064 + i]; su[i] = __bfloat162float(g_u[i * DM + d]); }
  __syncthreads();
  float ds = __bfloat162float(dskip[d]);
  for (int t = threadIdx.x; t < 2048; t += blockDim.x) {
    float acc = 0;
    for (int l = 0; l <= t; l++) acc += sk[l] * su[t - l];
    float yb = rbf(rbf(acc) + rbf(su[t] * ds));
    float h = rbf(__bfloat162float(x[t * DM + d]) + yb);
    int tau = t >> 3, rt = tau >> 4, mh = (tau >> 3) & 1, c = tau & 7, r = d & 7;
    size_t off = (size_t)rt * 114688 + (d >> 3) * 2048 + mh * 1024 + r * 128 + ((c ^ r) * 16) + (t & 7) * 2;
    *(__nv_bfloat16*)((char*)g_himg + off) = __float2bfloat16_rn(h);
  }
}
__global__ void k_colsum(const __nv_bfloat16* wg, const __nv_bfloat16* wu) {
  int f = blockIdx.x * blockDim.x + threadIdx.x;
  const __nv_bfloat16* w = f < FF ? wg : wu; int ff = f < FF ? f : f - FF;
  float s = 0; for (int d = 0; d < DM; d++) s += __bfloat162float(w[d * FF + ff]);
  float hi = rbf(s), mid = rbf(s - hi), lo = rbf(s - hi - mid);
  int j = ff / 224, q = (ff % 224) / 112, n = ff % 112 + (f < FF ? 0 : 112);
  __nv_bfloat16* dst = (__nv_bfloat16*)(g_cimg + (j * 2 + q) * 224 + (n >> 3) * 8) + (n & 7);
  dst[0] = __float2bfloat16_rn(hi); dst[8] = __float2bfloat16_rn(mid); dst[16] = __float2bfloat16_rn(lo);
  for (int k = 3; k < 8; k++) dst[8 * k] = __float2bfloat16_rn(0.f);
}
__global__ void k_pack(const uint4* __restrict__ wg, const uint4* __restrict__ wu, const uint4* __restrict__ wd) {
  int i = blockIdx.x * blockDim.x + threadIdx.x;
  int mat = i / 100352, e = i % 100352;
  if (mat < 2) {
    int d = e / 224, ngg = e % 224;
    int j = ngg / 28, q = (ngg % 28) / 14, ng = ngg % 14 + 14 * mat;
    g_wimg[(size_t)j * 37632 + (q * 14 + (d >> 5)) * 896 + ng * 32 + (d & 31)] = (mat ? wu : wg)[e];
  } else {
    int f = e / 56, ngg = e % 56;
    int j = f / 224, hf = (f % 224) / 112, k = f % 112, c = ngg / 7, ng = ngg % 7;
    g_wimg[(size_t)j * 37632 + 25088 + (c * 2 + hf) * 784 + ng * 112 + k] = wd[e];
  }
}

constexpr int B_SA = 0, B_RING = 114688, B_SLOT = 14336, B_NSLOT = 7;
constexpr int B_CS = B_RING + B_NSLOT * B_SLOT;
constexpr int B_STAT = B_CS + 7168;
constexpr int B_RED = B_STAT + 1024;
constexpr int B_BAR = B_RED + 1024;
constexpr int B_SMEM = B_BAR + 512;

__device__ __forceinline__ void st128(uint4* p, uint32_t a, uint32_t b, uint32_t c, uint32_t d) {
  asm volatile("{\n.reg .b128 v;\n.reg .b64 lo, hi;\nmov.b64 lo, {%1, %2};\nmov.b64 hi, {%3, %4};\nmov.b128 v, {lo, hi};\n"
               "st.relaxed.gpu.global.b128 [%0], v;\n}" ::"l"(p), "r"(a), "r"(b), "r"(c), "r"(d) : "memory");
}
__device__ __forceinline__ void ld128(const uint4* p, uint32_t* r) {
  asm volatile("{\n.reg .b128 v;\n.reg .b64 lo, hi;\nld.relaxed.gpu.global.b128 v, [%4];\nmov.b128 {lo, hi}, v;\n"
               "mov.b64 {%0, %1}, lo;\nmov.b64 {%2, %3}, hi;\n}" : "=r"(r[0]), "=r"(r[1]), "=r"(r[2]), "=r"(r[3]) : "l"(p) : "memory");
}

__device__ __forceinline__ uint32_t mapa(uint32_t a, uint32_t r) { uint32_t o; asm("mapa.shared::cluster.u32 %0, %1, %2;" : "=r"(o) : "r"(a), "r"(r)); return o; }

template <int Q, int ST>
__device__ __forceinline__ void g1_stage(float (&acc)[112], uint32_t alo, uint32_t blo, uint32_t bar_full, uint32_t bar_h) {
  constexpr int s = Q * 14 + ST, sl = s % B_NSLOT;
  if (Q == 0) mbar_wait(bar_h + 8 * ST, 0);
  mbar_wait(bar_full + 8 * sl, (s / B_NSLOT) & 1);
  wg_fence();
  wgmma_ss224<(2 * ST) * 256, 0x40000080u, (sl * B_SLOT) / 16, 32, ST != 0>(acc, alo, blo);
  wgmma_ss224<(2 * ST + 1) * 256, 0x40000080u, (sl * B_SLOT + 256) / 16, 32, 1>(acc, alo, blo);
}

__global__ void __cluster_dims__(2, 1, 1) __launch_bounds__(384, 1) k_ffn(__nv_bfloat16* __restrict__ out) {
  extern __shared__ __align__(1024) unsigned char sm[];
  const uint32_t sb = s2u(sm);
  const int tid = threadIdx.x, wg = tid >> 7, warp = tid >> 5, lane = tid & 31;
  const int rank = blockIdx.x & 1, rt = blockIdx.x & 15, j = blockIdx.x >> 4;
  const uint32_t bar_full = sb + B_BAR, bar_empty = bar_full + 64, bar_h = bar_full + 128, bar_cs = bar_full + 240, bar_stat = bar_full + 248,
                 bar_adead = bar_full + 256, bar_in = bar_full + 264, bar_red = bar_full + 376;
  if (tid == 0) {
    TR(1, 0);
    for (int i = 0; i < B_NSLOT; i++) { mbar_init(bar_full + 8 * i, 1); mbar_init(bar_empty + 8 * i, 4); }
    for (int i = 0; i < 14; i++) mbar_init(bar_h + 8 * i, 1);
    mbar_init(bar_cs, 1);
    mbar_init(bar_stat, 64);
    mbar_init(bar_adead, 2);
    for (int i = 0; i < 14; i++) mbar_init(bar_in + 8 * i, 1);
    mbar_init(bar_red, 256);
    asm volatile("fence.mbarrier_init.release.cluster;" ::: "memory");
  }
  __syncthreads();
  asm volatile("barrier.cluster.arrive.release.aligned;" ::: "memory");

  if (wg == 2) {
    asm volatile("setmaxnreg.dec.sync.aligned.u32 88;");
    asm volatile("barrier.cluster.wait.acquire.aligned;" ::: "memory");
    asm volatile("griddepcontrol.wait;" ::: "memory");
    if (warp == 8) {
      if (lane == 0) {
        const char* wsrc = (const char*)g_wimg + (size_t)j * 602112;
        TR(1, 1);
        int slot = 0, ph = 0;
        for (int s = 0; s < 44; s++) {
          if (s >= B_NSLOT) mbar_wait(bar_empty + 8 * slot, ph ^ 1);
          uint32_t dst = sb + B_RING + slot * B_SLOT, fb = bar_full + 8 * slot;
          if (s < 28) {
            mbar_expect(fb, 14336);
            bulk_ld_mc(dst + rank * 7168, wsrc + s * 14336 + rank * 7168, 7168, fb);
          } else {
            const int c = (j + 1 + ((s - 28) >> 1)) & 7;
            mbar_expect(fb, 12544);
            bulk_ld_mc(dst + rank * 6272, wsrc + 401408 + (c * 2 + (s & 1)) * 12544 + rank * 6272, 6272, fb);
          }
          if (++slot == B_NSLOT) { slot = 0; ph ^= 1; }
        }
      }
    } else if (warp == 9) {
      if (lane == 0) {
        const char* hsrc = (const char*)g_himg + (size_t)rt * 114688;
        for (int i = 0; i < 14; i++) {
          mbar_expect(bar_h + 8 * i, 8192);
          bulk_ld(sb + B_SA + i * 8192, hsrc + i * 8192, 8192, bar_h + 8 * i);
        }
        mbar_expect(bar_cs, 7168);
        bulk_ld(sb + B_CS, g_cimg + j * 448, 7168, bar_cs);
      }
    } else {
      const int t64 = tid - 320;
      const uint32_t ep = __ldcg(&g_epoch), tag = ep & 1u;
      if (t64 < 16) {
        mbar_wait(bar_red, 0);
        const float* red = (const float*)(sm + B_RED);
        float a = 0.f, b = 0.f;
#pragma unroll
        for (int w = 0; w < 8; w++) { float2 v = *(const float2*)(red + w * 32 + 2 * t64); a += v.x; b += v.y; }
        float mean = a * (1.f / DM);
        float var = fmaxf(fmaf(-mean, mean, b * (1.f / DM)), 0.f);
        float rs = __frcp_rn(rbf(__fsqrt_rn(rbf(rbf(var) + 1e-5f))));
        uint32_t nm = pack_bf16(-mean, -mean), r2 = (__float_as_uint(rs * rs) & ~1u) | tag;
        asm volatile("{\n.reg .b64 v;\nmov.b64 v, {%1, %2};\nst.relaxed.gpu.global.b64 [%0], v;\n}"
                     ::"l"(g_stat2 + rt * 128 + j * 16 + t64), "r"(nm), "r"(r2) : "memory");
        if (t64 == 0) TR(1, 2);
      }
      __syncwarp();
      mbar_wait(bar_h + 8 * 13, 0);
      {
        uint32_t w[4];
        int it = 0;
        do { ld128((const uint4*)(g_stat2 + rt * 128) + t64, w); } while ((((w[1] ^ tag) | (w[3] ^ tag)) & 1u) && ++it < 200000);
        *(uint4*)(sm + B_STAT + t64 * 16) = make_uint4(w[0], w[1], w[2], w[3]);
        mbar_arrive(bar_stat);
      }
      if (t64 == 0) TR(1, 18);
      if (warp == 11) {
        mbar_wait(bar_adead, 0);
        bool todo = lane < 14;
        int it = 0;
        while (__any_sync(~0u, todo) && ++it < 200000) {
          if (todo) {
            uint32_t w[4];
            ld128(g_flag + (rt * 8 + j) * 16 + lane, w);
            if (w[0] == ep && w[1] == ep && w[2] == ep && w[3] == ep) {
              const uint32_t b = bar_in + 8 * ((lane & 1) * 7 + (lane >> 1));
              asm volatile("fence.proxy.async.global;" ::: "memory");
              mbar_expect(b, 7168);
              bulk_ld(sb + B_SA + lane * 7168, g_part + (size_t)((rt * 8 + j) * 7) * 896 + lane * 448, 7168, b);
              todo = false;
              if (!(lane & 1)) TR(1, 24 + (lane >> 1));
            }
          }
        }
      }
    }
  } else {
    asm volatile("setmaxnreg.inc.sync.aligned.u32 208;");
    const int g = lane >> 2, t = lane & 3, wq = warp & 3, t128 = tid & 127;
    uint32_t hh[56], hres[16];
    asm volatile("barrier.cluster.wait.acquire.aligned;" ::: "memory");
    asm volatile("griddepcontrol.wait;" ::: "memory");
    uint4 sv[4];
    {
      const int r = (lane >> 1) & 7;
      const uint4* src = g_himg + (size_t)rt * 7168 + (tid >> 4) * 128 + (j >> 2) * 64 + r * 8 + ((((j & 3) * 2 + (lane & 1)) ^ r));
#pragma unroll
      for (int i = 0; i < 3; i++) sv[i] = __ldcg(src + i * 2048);
      sv[3] = wg == 0 ? __ldcg(src + 3 * 2048) : make_uint4(0, 0, 0, 0);
    }
    const uint32_t ep = __ldcg(&g_epoch), tag = (ep & 1u) << 16;
    const uint32_t rel_bar = mapa(bar_empty, t128 & 1);
    auto release = [&](int sl) { if (t128 < 2) asm volatile("mbarrier.arrive.shared::cluster.b64 _, [%0];" ::"r"(rel_bar + 8 * sl) : "memory"); };
    const uint32_t alo = __shfl_sync(~0u, ((sb + B_SA + wg * 1024) & 0x3FFFF) >> 4, 0);
    const uint32_t blo = (((sb + B_RING) & 0x3FFFF) >> 4) | (8u << 16);
    const uint32_t clo = ((sb + B_CS) & 0x3FFFF) >> 4;
    uint32_t nm0, nm1; float r20, r21;
    {
      float a[16];
#pragma unroll
      for (int k = 0; k < 16; k++) a[k] = 0.f;
#pragma unroll
      for (int i = 0; i < 4; i++) {
        float e[8] = {bf_lo(sv[i].x), bf_hi(sv[i].x), bf_lo(sv[i].y), bf_hi(sv[i].y), bf_lo(sv[i].z), bf_hi(sv[i].z), bf_lo(sv[i].w), bf_hi(sv[i].w)};
#pragma unroll
        for (int k = 0; k < 8; k++) { a[2 * k] += e[k]; a[2 * k + 1] = fmaf(e[k], e[k], a[2 * k + 1]); }
      }
#pragma unroll
      for (int rd = 0; rd < 4; rd++) {
        const int n = 8 >> rd;
        const bool up = lane & (2 * n);
#pragma unroll
        for (int k = 0; k < 8; k++) {
          if (k < n) {
            float keep = up ? a[k + n] : a[k], give = up ? a[k] : a[k + n];
            a[k] = keep + __shfl_xor_sync(~0u, give, 2 * n);
          }
        }
      }
      ((float*)(sm + B_RED))[warp * 32 + (lane & 1) * 16 + (lane >> 1)] = a[0];
      mbar_arrive(bar_red);
    }
    if (tid == 0) TR(1, 19);
    if (wg == 1) asm volatile("bar.sync 3, 256;" ::: "memory");
#define G1S(Q, ST) do { g1_stage<Q, ST>(acc, alo, blo, bar_full, bar_h); wg_commit(); \
      if (ST > 0) { wg_wait<1>(); release((Q * 14 + ST - 1) % B_NSLOT); } } while (0)
#define G1EPI(Q) do { \
      g1_stage<Q, 13>(acc, alo, blo, bar_full, bar_h); \
      wgmma_rs224<Q * 224, 8, 1>(acc, nm0, nm1, 0u, 0u, clo); \
      wg_commit(); wg_wait<1>(); release((Q * 14 + 12) % B_NSLOT); \
      wg_wait<0>(); reg_fence(acc); release((Q * 14 + 13) % B_NSLOT); \
      _Pragma("unroll") \
      for (int i = 0; i < 28; i++) hh[28 * Q + i] = pack_bf16(acc[2 * i] * acc[56 + 2 * i], acc[2 * i + 1] * acc[57 + 2 * i]); \
    } while (0)
    {
      float acc[112];
      G1S(0, 0);
      if (tid == 0) TR(1, 3);
      G1S(0, 1);
      if (wg == 0) asm volatile("bar.arrive 3, 256;" ::: "memory");
      G1S(0, 2); G1S(0, 3); G1S(0, 4); G1S(0, 5); G1S(0, 6); G1S(0, 7); G1S(0, 8); G1S(0, 9); G1S(0, 10); G1S(0, 11); G1S(0, 12);
      if (tid == 0) TR(1, 4);
      mbar_wait(bar_stat, 0);
      mbar_wait(bar_cs, 0);
      {
        uint2 a = *(const uint2*)(sm + B_STAT + (wg * 64 + wq * 16 + g) * 8), b = *(const uint2*)(sm + B_STAT + (wg * 64 + wq * 16 + g + 8) * 8);
        const uint32_t msk = t == 0 ? 0xFFFFFFFFu : t == 1 ? 0xFFFFu : 0u;
        nm0 = a.x & msk; nm1 = b.x & msk; r20 = __uint_as_float(a.y); r21 = __uint_as_float(b.y);
      }
      G1EPI(0);
      if (tid == 0) TR(1, 5);
      G1S(1, 0); G1S(1, 1); G1S(1, 2); G1S(1, 3); G1S(1, 4); G1S(1, 5); G1S(1, 6); G1S(1, 7); G1S(1, 8); G1S(1, 9); G1S(1, 10); G1S(1, 11);
#pragma unroll
      for (int i = 0; i < 4; i++) {
        int qq = lane >> 3, r = lane & 7, kg = 7 * j + 2 * i + (qq >> 1), c = 2 * wq + (qq & 1);
        if (kg > 55) kg = 55;
        uint32_t addr = sb + B_SA + kg * 2048 + wg * 1024 + r * 128 + ((c ^ r) << 4);
        asm volatile("ldmatrix.sync.aligned.m8n8.x4.trans.shared.b16 {%0,%1,%2,%3}, [%4];"
                     : "=r"(hres[4 * i]), "=r"(hres[4 * i + 1]), "=r"(hres[4 * i + 2]), "=r"(hres[4 * i + 3]) : "r"(addr) : "memory");
      }
      G1S(1, 12);
      G1EPI(1);
      if (t128 == 0) mbar_arrive(bar_adead);
      if (tid == 0) TR(1, 6);
    }
    float accA[28], accB[28], sum[28];
    int nxt = 0;
#pragma unroll
    for (int i = 0; i < 28; i++) sum[i] = 0.f;
#define ISSUE(acc, I, a, FIRST) do { \
      constexpr int s_ = 28 + (I), sl_ = s_ % B_NSLOT; \
      mbar_wait(bar_full + 8 * sl_, (s_ / B_NSLOT) & 1); \
      wg_fence(); \
      wgmma_rs56<(sl_ * B_SLOT + 0 * 256) / 16, 112, !(FIRST)>(acc, (a)[0], (a)[1], (a)[2], (a)[3], blo); \
      wgmma_rs56<(sl_ * B_SLOT + 1 * 256) / 16, 112, 1>(acc, (a)[4], (a)[5], (a)[6], (a)[7], blo); \
      wgmma_rs56<(sl_ * B_SLOT + 2 * 256) / 16, 112, 1>(acc, (a)[8], (a)[9], (a)[10], (a)[11], blo); \
      wgmma_rs56<(sl_ * B_SLOT + 3 * 256) / 16, 112, 1>(acc, (a)[12], (a)[13], (a)[14], (a)[15], blo); \
      wgmma_rs56<(sl_ * B_SLOT + 4 * 256) / 16, 112, 1>(acc, (a)[16], (a)[17], (a)[18], (a)[19], blo); \
      wgmma_rs56<(sl_ * B_SLOT + 5 * 256) / 16, 112, 1>(acc, (a)[20], (a)[21], (a)[22], (a)[23], blo); \
      wgmma_rs56<(sl_ * B_SLOT + 6 * 256) / 16, 112, 1>(acc, (a)[24], (a)[25], (a)[26], (a)[27], blo); \
      wg_commit(); } while (0)
    auto rel = [&](int i) { if (i < 9) release((28 + i) % B_NSLOT); };
    auto tg = [&](uint32_t v) { return (v & 0xFFFEFFFFu) | tag; };
    auto send_lo = [&](float (&acc)[28], int cc) {
      reg_fence(acc);
      uint4* dst = g_part + (size_t)((rt * 8 + ((j + 1 + cc) & 7)) * 7 + cc) * 896 + wg * 448 + t128;
#pragma unroll
      for (int q = 0; q < 2; q++)
        st128(dst + q * 128, pack_bf16(acc[8 * q], acc[8 * q + 1]), pack_bf16(acc[8 * q + 2], acc[8 * q + 3]),
              pack_bf16(acc[8 * q + 4], acc[8 * q + 5]), tg(pack_bf16(acc[8 * q + 6], acc[8 * q + 7])));
    };
    auto send_hi = [&](float (&acc)[28], int cc) {
      uint4* dst = g_part + (size_t)((rt * 8 + ((j + 1 + cc) & 7)) * 7 + cc) * 896 + wg * 448;
      st128(dst + 256 + t128, pack_bf16(acc[16], acc[17]), pack_bf16(acc[18], acc[19]), pack_bf16(acc[20], acc[21]), tg(pack_bf16(acc[22], acc[23])));
      asm volatile("{\n.reg .b64 v;\nmov.b64 v, {%1, %2};\nst.relaxed.gpu.global.b64 [%0], v;\n}"
                   ::"l"((uint2*)(dst + 384) + t128), "r"(pack_bf16(acc[24], acc[25])), "r"(tg(pack_bf16(acc[26], acc[27]))) : "memory");
      if (lane == 0)
        asm volatile("st.relaxed.gpu.global.u32 [%0], %1;" ::"l"((uint32_t*)(g_flag + (rt * 8 + ((j + 1 + cc) & 7)) * 16 + cc * 2 + wg) + wq), "r"(ep) : "memory");
    };
    auto accum = [&]() {
      const unsigned char* src = sm + B_SA + nxt * 14336 + wg * 7168;
      uint4 a = *(const uint4*)(src + t128 * 16), b = *(const uint4*)(src + 2048 + t128 * 16), c = *(const uint4*)(src + 4096 + t128 * 16);
      uint2 d = *(const uint2*)(src + 6144 + t128 * 8);
      uint32_t in[14] = {a.x, a.y, a.z, a.w, b.x, b.y, b.z, b.w, c.x, c.y, c.z, c.w, d.x, d.y};
      int it = 0;
      while ((((in[3] ^ tag) | (in[7] ^ tag) | (in[11] ^ tag) | (in[13] ^ tag)) & 0x10000u) && ++it < 200000) {
        const uint4* gs = g_part + (size_t)((rt * 8 + j) * 7 + nxt) * 896 + wg * 448;
#pragma unroll
        for (int i = 0; i < 3; i++) ld128(gs + i * 128 + t128, in + 4 * i);
        asm volatile("{\n.reg .b64 v;\nld.relaxed.gpu.global.b64 v, [%2];\nmov.b64 {%0, %1}, v;\n}"
                     : "=r"(in[12]), "=r"(in[13]) : "l"((const uint2*)(gs + 384) + t128) : "memory");
      }
#pragma unroll
      for (int i = 0; i < 14; i++) { sum[2 * i] += bf_lo(in[i]); sum[2 * i + 1] += bf_hi(in[i]); }
      nxt++;
    };
    auto try_accum = [&]() {
      uint32_t ok;
      asm volatile("{\n.reg .pred p;\nmbarrier.test_wait.parity.shared::cta.b64 p, [%1], 0;\nselp.u32 %0, 1, 0, p;\n}"
                   : "=r"(ok) : "r"(bar_in + 8 * (wg * 7 + nxt)) : "memory");
      if (__all_sync(~0u, ok)) accum();
    };
#define CHUNK(cur, prev, CC, EXTRA) do { \
      ISSUE(cur, 2 * (CC), hh, true); wg_wait<1>(); rel(2 * (CC) - 1); send_lo(prev, (CC) - 1); \
      ISSUE(cur, 2 * (CC) + 1, hh + 28, false); send_hi(prev, (CC) - 1); EXTRA; wg_wait<1>(); rel(2 * (CC)); } while (0)
    ISSUE(accA, 0, hh, true);
    ISSUE(accA, 1, hh + 28, false); wg_wait<1>(); rel(0);
    CHUNK(accB, accA, 1, );
    if (tid == 0) TR(1, 11);
    CHUNK(accA, accB, 2, );
    if (tid == 0) TR(1, 12);
    CHUNK(accB, accA, 3, try_accum());
    if (tid == 0) TR(1, 13);
    CHUNK(accA, accB, 4, try_accum());
    if (tid == 0) TR(1, 14);
    CHUNK(accB, accA, 5, try_accum());
    if (tid == 0) TR(1, 16);
    CHUNK(accA, accB, 6, try_accum());
    if (tid == 0) TR(1, 17);
    CHUNK(accB, accA, 7, try_accum());
    if (tid == 0) TR(1, 7);
#pragma unroll 1
    while (nxt < 7) { mbar_wait(bar_in + 8 * (wg * 7 + nxt), 0); accum(); }
    wg_wait<0>();
    reg_fence(accB);
    if (tid == 0) TR(1, 9);
    const int row = rt * 128 + wg * 64 + wq * 16 + g;
    uint32_t* o0 = (uint32_t*)(out + (size_t)row * DM + 56 * j + 2 * t);
    uint32_t* o1 = o0 + 8 * DM / 2;
#pragma unroll
    for (int i = 0; i < 7; i++) {
      o0[4 * i] = hadd2_bf(hres[2 * i], pack_bf16((sum[4 * i] + accB[4 * i]) * r20, (sum[4 * i + 1] + accB[4 * i + 1]) * r20));
      o1[4 * i] = hadd2_bf(hres[2 * i + 1], pack_bf16((sum[4 * i + 2] + accB[4 * i + 2]) * r21, (sum[4 * i + 3] + accB[4 * i + 3]) * r21));
    }
    if (tid == 0) TR(1, 10);
    if (tid == 128) TR(1, 15);

  }
}

extern "C" void kernel_launch(void* const* d_in, const int* in_sizes, int n_in, void* d_out, int out_size) {
  const __nv_bfloat16* x = (const __nv_bfloat16*)d_in[0];
  const __nv_bfloat16 *are = (const __nv_bfloat16*)d_in[1], *aim = (const __nv_bfloat16*)d_in[2], *bre = (const __nv_bfloat16*)d_in[3],
                      *bim = (const __nv_bfloat16*)d_in[4], *cre = (const __nv_bfloat16*)d_in[5], *cim = (const __nv_bfloat16*)d_in[6],
                      *logdt = (const __nv_bfloat16*)d_in[7], *dskip = (const __nv_bfloat16*)d_in[8];
  const __nv_bfloat16 *wg = (const __nv_bfloat16*)d_in[10], *wu = (const __nv_bfloat16*)d_in[11], *wd = (const __nv_bfloat16*)d_in[12];

  static bool init = false;
  if (!init) {
    init = true;
    cudaFuncSetAttribute(k_ffn, cudaFuncAttributeMaxDynamicSharedMemorySize, B_SMEM);
  }
  cudaStream_t st = cudaStreamPerThread;
  k_ln1<<<256, 256, 0, st>>>(x);
  k_kgen<<<DM, 512, 0, st>>>(are, aim, bre, bim, cre, cim, logdt);
  k_conv<<<DM, 512, 0, st>>>(x, dskip);
  k_colsum<<<2 * FF / 128, 128, 0, st>>>(wg, wu);
  k_pack<<<3 * 100352 / 256, 256, 0, st>>>((const uint4*)wg, (const uint4*)wu, (const uint4*)wd);
  k_ffn<<<128, 384, B_SMEM, st>>>((__nv_bfloat16*)d_out);
}
```

```cpp
#include <cuda_runtime.h>
#include <cuda_bf16.h>
#include <stdint.h>

constexpr int LSEQ = 2048, DM = 448, FF = 1792, NST = 256;

__device__ uint4    g_himg[16 * 114688 / 16];
__device__ uint4    g_cimg[8 * 2 * 224];
__device__ uint2    g_stat2[LSEQ];
__device__ uint4    g_part[128 * 7 * 896];
__device__ uint4    g_wimg[8 * 602112 / 16];
__device__ unsigned g_epoch;
__device__ uint4    g_flag[128 * 16];
__device__ __nv_bfloat16 g_u[LSEQ * DM];
__device__ float    g_kd[DM * 2064];

#define TR(k, i) do {} while (0)
__device__ __forceinline__ uint32_t s2u(const void* p) { return (uint32_t)__cvta_generic_to_shared(p); }
__device__ __forceinline__ void mbar_init(uint32_t b, int c) { asm volatile("mbarrier.init.shared::cta.b64 [%0], %1;" ::"r"(b), "r"(c)); }
__device__ __forceinline__ void mbar_expect(uint32_t b, int bytes) { asm volatile("mbarrier.arrive.expect_tx.shared::cta.b64 _, [%0], %1;" ::"r"(b), "r"(bytes) : "memory"); }
__device__ __forceinline__ void mbar_arrive(uint32_t b) { asm volatile("mbarrier.arrive.shared::cta.b64 _, [%0];" ::"r"(b) : "memory"); }
__device__ __forceinline__ void mbar_wait(uint32_t b, int ph) {
  asm volatile("{\n.reg .pred p;\n.reg .b32 n;\nmov.b32 n, 0;\nLW:\nmbarrier.try_wait.parity.shared::cta.b64 p, [%0], %1;\n@p bra LD;\n"
               "add.u32 n, n, 1;\nsetp.lt.u32 p, n, 4000000;\n@p bra LW;\ntrap;\nLD:\n}" ::"r"(b), "r"(ph) : "memory");
}
__device__ __forceinline__ uint64_t mkdesc(uint32_t addr, uint32_t lbo, uint32_t sbo, uint32_t sw) {
  return (uint64_t)((addr & 0x3FFFF) >> 4) | ((uint64_t)((lbo >> 4) & 0x3FFF) << 16) | ((uint64_t)((sbo >> 4) & 0x3FFF) << 32) | ((uint64_t)sw << 62);
}
__device__ __forceinline__ void wg_fence() { asm volatile("wgmma.fence.sync.aligned;" ::: "memory"); }
__device__ __forceinline__ void wg_commit() { asm volatile("wgmma.commit_group.sync.aligned;" ::: "memory"); }
template <int N> __device__ __forceinline__ void wg_wait() { asm volatile("wgmma.wait_group.sync.aligned %0;" ::"n"(N) : "memory"); }
template <int N> __device__ __forceinline__ void reg_fence(float (&a)[N]) {
#pragma unroll
  for (int i = 0; i < N; i++) asm volatile("" : "+f"(a[i])::"memory");
}
__device__ __forceinline__ uint32_t pack_bf16(float lo, float hi) {
  uint32_t r; asm("cvt.rn.bf16x2.f32 %0, %1, %2;" : "=r"(r) : "f"(hi), "f"(lo)); return r;
}
__device__ __forceinline__ float bf_lo(uint32_t v) { return __uint_as_float(v << 16); }
__device__ __forceinline__ float bf_hi(uint32_t v) { return __uint_as_float(v & 0xFFFF0000u); }
__device__ __forceinline__ float rbf(float x) { return __bfloat162float(__float2bfloat16_rn(x)); }
__device__ __forceinline__ uint32_t hmul2_bf(uint32_t a, uint32_t b) { uint32_t r; asm("mul.rn.bf16x2 %0, %1, %2;" : "=r"(r) : "r"(a), "r"(b)); return r; }
__device__ __forceinline__ uint32_t hadd2_bf(uint32_t a, uint32_t b) { uint32_t r; asm("add.rn.bf16x2 %0, %1, %2;" : "=r"(r) : "r"(a), "r"(b)); return r; }
__device__ __forceinline__ void bulk_ld(uint32_t dst, const void* src, int bytes, uint32_t bar) {
  asm volatile("cp.async.bulk.shared::cluster.global.mbarrier::complete_tx::bytes [%0], [%1], %2, [%3];"
               ::"r"(dst), "l"(src), "r"(bytes), "r"(bar) : "memory");
}

__device__ __forceinline__ void bulk_ld_mc(uint32_t dst, const void* src, int bytes, uint32_t bar) {
  asm volatile("cp.async.bulk.shared::cluster.global.mbarrier::complete_tx::bytes.multicast::cluster [%0], [%1], %2, [%3], %4;"
               ::"r"(dst), "l"(src), "r"(bytes), "r"(bar), "h"((uint16_t)3) : "memory");
}
template <int AOFF, uint32_t AHI, int BOFF, uint32_t BHI, int ACC>
__device__ __forceinline__ void wgmma_ss224(float (&d)[112], uint32_t alo, uint32_t blo) {
  asm volatile("{\n.reg .pred p;\n.reg .b32 la, lb;\n.reg .b64 ad, bd;\nsetp.ne.b32 p, %118, 0;\n"
    "add.u32 la, %112, %114;\nmov.b64 ad, {la, %115};\nadd.u32 lb, %113, %116;\nmov.b64 bd, {lb, %117};\n"
    "wgmma.mma_async.sync.aligned.m64n224k16.f32.bf16.bf16 {%0,%1,%2,%3,%4,%5,%6,%7,%8,%9,%10,%11,%12,%13,%14,%15,%16,%17,%18,%19,%20,%21,%22,%23,%24,%25,%26,%27,%28,%29,%30,%31,%32,%33,%34,%35,%36,%37,%38,%39,%40,%41,%42,%43,%44,%45,%46,%47,%48,%49,%50,%51,%52,%53,%54,%55,%56,%57,%58,%59,%60,%61,%62,%63,%64,%65,%66,%67,%68,%69,%70,%71,%72,%73,%74,%75,%76,%77,%78,%79,%80,%81,%82,%83,%84,%85,%86,%87,%88,%89,%90,%91,%92,%93,%94,%95,%96,%97,%98,%99,%100,%101,%102,%103,%104,%105,%106,%107,%108,%109,%110,%111}, ad, bd, p, 1, 1, 1, 1;\n}\n"
    : "+f"(d[0]),"+f"(d[1]),"+f"(d[2]),"+f"(d[3]),"+f"(d[4]),"+f"(d[5]),"+f"(d[6]),"+f"(d[7]),"+f"(d[8]),"+f"(d[9]),"+f"(d[10]),"+f"(d[11]),"+f"(d[12]),"+f"(d[13]),"+f"(d[14]),"+f"(d[15]),"+f"(d[16]),"+f"(d[17]),"+f"(d[18]),"+f"(d[19]),"+f"(d[20]),"+f"(d[21]),"+f"(d[22]),"+f"(d[23]),"+f"(d[24]),"+f"(d[25]),"+f"(d[26]),"+f"(d[27]),"+f"(d[28]),"+f"(d[29]),"+f"(d[30]),"+f"(d[31]),"+f"(d[32]),"+f"(d[33]),"+f"(d[34]),"+f"(d[35]),"+f"(d[36]),"+f"(d[37]),"+f"(d[38]),"+f"(d[39]),"+f"(d[40]),"+f"(d[41]),"+f"(d[42]),"+f"(d[43]),"+f"(d[44]),"+f"(d[45]),"+f"(d[46]),"+f"(d[47]),"+f"(d[48]),"+f"(d[49]),"+f"(d[50]),"+f"(d[51]),"+f"(d[52]),"+f"(d[53]),"+f"(d[54]),"+f"(d[55]),"+f"(d[56]),"+f"(d[57]),"+f"(d[58]),"+f"(d[59]),"+f"(d[60]),"+f"(d[61]),"+f"(d[62]),"+f"(d[63]),"+f"(d[64]),"+f"(d[65]),"+f"(d[66]),"+f"(d[67]),"+f"(d[68]),"+f"(d[69]),"+f"(d[70]),"+f"(d[71]),"+f"(d[72]),"+f"(d[73]),"+f"(d[74]),"+f"(d[75]),"+f"(d[76]),"+f"(d[77]),"+f"(d[78]),"+f"(d[79]),"+f"(d[80]),"+f"(d[81]),"+f"(d[82]),"+f"(d[83]),"+f"(d[84]),"+f"(d[85]),"+f"(d[86]),"+f"(d[87]),"+f"(d[88]),"+f"(d[89]),"+f"(d[90]),"+f"(d[91]),"+f"(d[92]),"+f"(d[93]),"+f"(d[94]),"+f"(d[95]),"+f"(d[96]),"+f"(d[97]),"+f"(d[98]),"+f"(d[99]),"+f"(d[100]),"+f"(d[101]),"+f"(d[102]),"+f"(d[103]),"+f"(d[104]),"+f"(d[105]),"+f"(d[106]),"+f"(d[107]),"+f"(d[108]),"+f"(d[109]),"+f"(d[110]),"+f"(d[111])
    : "r"(alo), "r"(blo), "n"(AOFF), "n"(AHI), "n"(BOFF), "n"(BHI), "n"(ACC));
}
template <int OFF, uint32_t BHI, int ACC>
__device__ __forceinline__ void wgmma_rs224(float (&d)[112], uint32_t a0, uint32_t a1, uint32_t a2, uint32_t a3, uint32_t blo) {
  asm volatile("{\n.reg .pred p;\n.reg .b32 l;\n.reg .b64 bd;\nsetp.ne.b32 p, %119, 0;\nadd.u32 l, %116, %117;\nmov.b64 bd, {l, %118};\n"
    "wgmma.mma_async.sync.aligned.m64n224k16.f32.bf16.bf16 {%0,%1,%2,%3,%4,%5,%6,%7,%8,%9,%10,%11,%12,%13,%14,%15,%16,%17,%18,%19,%20,%21,%22,%23,%24,%25,%26,%27,%28,%29,%30,%31,%32,%33,%34,%35,%36,%37,%38,%39,%40,%41,%42,%43,%44,%45,%46,%47,%48,%49,%50,%51,%52,%53,%54,%55,%56,%57,%58,%59,%60,%61,%62,%63,%64,%65,%66,%67,%68,%69,%70,%71,%72,%73,%74,%75,%76,%77,%78,%79,%80,%81,%82,%83,%84,%85,%86,%87,%88,%89,%90,%91,%92,%93,%94,%95,%96,%97,%98,%99,%100,%101,%102,%103,%104,%105,%106,%107,%108,%109,%110,%111}, {%112,%113,%114,%115}, bd, p, 1, 1, 1;\n}\n"
    : "+f"(d[0]),"+f"(d[1]),"+f"(d[2]),"+f"(d[3]),"+f"(d[4]),"+f"(d[5]),"+f"(d[6]),"+f"(d[7]),"+f"(d[8]),"+f"(d[9]),"+f"(d[10]),"+f"(d[11]),"+f"(d[12]),"+f"(d[13]),"+f"(d[14]),"+f"(d[15]),"+f"(d[16]),"+f"(d[17]),"+f"(d[18]),"+f"(d[19]),"+f"(d[20]),"+f"(d[21]),"+f"(d[22]),"+f"(d[23]),"+f"(d[24]),"+f"(d[25]),"+f"(d[26]),"+f"(d[27]),"+f"(d[28]),"+f"(d[29]),"+f"(d[30]),"+f"(d[31]),"+f"(d[32]),"+f"(d[33]),"+f"(d[34]),"+f"(d[35]),"+f"(d[36]),"+f"(d[37]),"+f"(d[38]),"+f"(d[39]),"+f"(d[40]),"+f"(d[41]),"+f"(d[42]),"+f"(d[43]),"+f"(d[44]),"+f"(d[45]),"+f"(d[46]),"+f"(d[47]),"+f"(d[48]),"+f"(d[49]),"+f"(d[50]),"+f"(d[51]),"+f"(d[52]),"+f"(d[53]),"+f"(d[54]),"+f"(d[55]),"+f"(d[56]),"+f"(d[57]),"+f"(d[58]),"+f"(d[59]),"+f"(d[60]),"+f"(d[61]),"+f"(d[62]),"+f"(d[63]),"+f"(d[64]),"+f"(d[65]),"+f"(d[66]),"+f"(d[67]),"+f"(d[68]),"+f"(d[69]),"+f"(d[70]),"+f"(d[71]),"+f"(d[72]),"+f"(d[73]),"+f"(d[74]),"+f"(d[75]),"+f"(d[76]),"+f"(d[77]),"+f"(d[78]),"+f"(d[79]),"+f"(d[80]),"+f"(d[81]),"+f"(d[82]),"+f"(d[83]),"+f"(d[84]),"+f"(d[85]),"+f"(d[86]),"+f"(d[87]),"+f"(d[88]),"+f"(d[89]),"+f"(d[90]),"+f"(d[91]),"+f"(d[92]),"+f"(d[93]),"+f"(d[94]),"+f"(d[95]),"+f"(d[96]),"+f"(d[97]),"+f"(d[98]),"+f"(d[99]),"+f"(d[100]),"+f"(d[101]),"+f"(d[102]),"+f"(d[103]),"+f"(d[104]),"+f"(d[105]),"+f"(d[106]),"+f"(d[107]),"+f"(d[108]),"+f"(d[109]),"+f"(d[110]),"+f"(d[111])
    : "r"(a0), "r"(a1), "r"(a2), "r"(a3), "r"(blo), "n"(OFF), "n"(BHI), "n"(ACC));
}
template <int OFF, uint32_t BHI, int ACC>
__device__ __forceinline__ void wgmma_rs56(float (&d)[28], uint32_t a0, uint32_t a1, uint32_t a2, uint32_t a3, uint32_t blo) {
  asm volatile("{\n.reg .pred p;\n.reg .b32 l;\n.reg .b64 bd;\nsetp.ne.b32 p, %35, 0;\nadd.u32 l, %32, %33;\nmov.b64 bd, {l, %34};\n"
    "wgmma.mma_async.sync.aligned.m64n56k16.f32.bf16.bf16 {%0,%1,%2,%3,%4,%5,%6,%7,%8,%9,%10,%11,%12,%13,%14,%15,%16,%17,%18,%19,%20,%21,%22,%23,%24,%25,%26,%27}, {%28,%29,%30,%31}, bd, p, 1, 1, 1;\n}\n"
    : "+f"(d[0]),"+f"(d[1]),"+f"(d[2]),"+f"(d[3]),"+f"(d[4]),"+f"(d[5]),"+f"(d[6]),"+f"(d[7]),"+f"(d[8]),"+f"(d[9]),"+f"(d[10]),"+f"(d[11]),"+f"(d[12]),"+f"(d[13]),"+f"(d[14]),"+f"(d[15]),"+f"(d[16]),"+f"(d[17]),"+f"(d[18]),"+f"(d[19]),"+f"(d[20]),"+f"(d[21]),"+f"(d[22]),"+f"(d[23]),"+f"(d[24]),"+f"(d[25]),"+f"(d[26]),"+f"(d[27])
    : "r"(a0), "r"(a1), "r"(a2), "r"(a3), "r"(blo), "n"(OFF), "n"(BHI), "n"(ACC));
}

__global__ void k_ln1(const __nv_bfloat16* __restrict__ x) {
  int row = blockIdx.x * 8 + threadIdx.x / 32, lane = threadIdx.x & 31;
  float v[14]; float s = 0;
  for (int i = 0; i < 14; i++) { v[i] = __bfloat162float(x[row * DM + lane + 32 * i]); s += v[i]; }
  for (int o = 16; o; o >>= 1) s += __shfl_xor_sync(~0u, s, o);
  float mean = s / DM, q = 0;
  for (int i = 0; i < 14; i++) q += (v[i] - mean) * (v[i] - mean);
  for (int o = 16; o; o >>= 1) q += __shfl_xor_sync(~0u, q, o);
  float m = rbf(mean), sd = rbf(sqrtf(rbf(rbf(q / DM) + 1e-5f)));
  for (int i = 0; i < 14; i++) g_u[row * DM + lane + 32 * i] = __float2bfloat16_rn(rbf(v[i] - m) / sd);
  if (blockIdx.x == 0 && threadIdx.x == 0) g_epoch = g_epoch + 1;
}
__global__ void k_kgen(const __nv_bfloat16* are, const __nv_bfloat16* aim, const __nv_bfloat16* bre, const __nv_bfloat16* bim,
                       const __nv_bfloat16* cre, const __nv_bfloat16* cim, const __nv_bfloat16* logdt) {
  int d = blockIdx.x;
  float dt = rbf(expf(__bfloat162float(logdt[d])));
  for (int l = threadIdx.x; l < 2048; l += blockDim.x) {
    float lf = rbf((float)l), acc = 0;
    for (int n = 0; n < NST; n++) {
      int i = d * NST + n;
      float lr = dt * __bfloat162float(are[i]), li = dt * __bfloat162float(aim[i]);
      float br = dt * __bfloat162float(bre[i]), bi = dt * __bfloat162float(bim[i]);
      float cr = __bfloat162float(cre[i]), ci = __bfloat162float(cim[i]);
      float wr = cr * br - ci * bi, wi = cr * bi + ci * br;
      float e = expf(lr * lf), sn, cs; sincosf(li * lf, &sn, &cs);
      acc += e * (wr * cs - wi * sn);
    }
    g_kd[d * 2064 + l] = acc;
  }
}
__global__ void k_conv(const __nv_bfloat16* __restrict__ x, const __nv_bfloat16* dskip) {
  __shared__ float sk[2048], su[2048];
  int d = blockIdx.x;
  for (int i = threadIdx.x; i < 2048; i += blockDim.x) { sk[i] = g_kd[d * 2064 + i]; su[i] = __bfloat162float(g_u[i * DM + d]); }
  __syncthreads();
  float ds = __bfloat162float(dskip[d]);
  for (int t = threadIdx.x; t < 2048; t += blockDim.x) {
    float acc = 0;
    for (int l = 0; l <= t; l++) acc += sk[l] * su[t - l];
    float yb = rbf(rbf(acc) + rbf(su[t] * ds));
    float h = rbf(__bfloat162float(x[t * DM + d]) + yb);
    int tau = t >> 3, rt = tau >> 4, mh = (tau >> 3) & 1, c = tau & 7, r = d & 7;
    size_t off = (size_t)rt * 114688 + (d >> 3) * 2048 + mh * 1024 + r * 128 + ((c ^ r) * 16) + (t & 7) * 2;
    *(__nv_bfloat16*)((char*)g_himg + off) = __float2bfloat16_rn(h);
  }
}
__global__ void k_colsum(const __nv_bfloat16* wg, const __nv_bfloat16* wu) {
  int f = blockIdx.x * blockDim.x + threadIdx.x;
  const __nv_bfloat16* w = f < FF ? wg : wu; int ff = f < FF ? f : f - FF;
  float s = 0; for (int d = 0; d < DM; d++) s += __bfloat162float(w[d * FF + ff]);
  float hi = rbf(s), mid = rbf(s - hi), lo = rbf(s - hi - mid);
  int j = ff / 224, q = (ff % 224) / 112, n = ff % 112 + (f < FF ? 0 : 112);
  __nv_bfloat16* dst = (__nv_bfloat16*)(g_cimg + (j * 2 + q) * 224 + (n >> 3) * 8) + (n & 7);
  dst[0] = __float2bfloat16_rn(hi); dst[8] = __float2bfloat16_rn(mid); dst[16] = __float2bfloat16_rn(lo);
  for (int k = 3; k < 8; k++) dst[8 * k] = __float2bfloat16_rn(0.f);
}
__global__ void k_pack(const uint4* __restrict__ wg, const uint4* __restrict__ wu, const uint4* __restrict__ wd) {
  int i = blockIdx.x * blockDim.x + threadIdx.x;
  int mat = i / 100352, e = i % 100352;
  if (mat < 2) {
    int d = e / 224, ngg = e % 224;
    int j = ngg / 28, q = (ngg % 28) / 14, ng = ngg % 14 + 14 * mat;
    g_wimg[(size_t)j * 37632 + (q * 14 + (d >> 5)) * 896 + ng * 32 + (d & 31)] = (mat ? wu : wg)[e];
  } else {
    int f = e / 56, ngg = e % 56;
    int j = f / 224, hf = (f % 224) / 112, k = f % 112, c = ngg / 7, ng = ngg % 7;
    g_wimg[(size_t)j * 37632 + 25088 + (c * 2 + hf) * 784 + ng * 112 + k] = wd[e];
  }
}

constexpr int B_SA = 0, B_RING = 114688, B_SLOT = 14336, B_NSLOT = 7;
constexpr int B_CS = B_RING + B_NSLOT * B_SLOT;
constexpr int B_STAT = B_CS + 7168;
constexpr int B_BAR = B_STAT + 1024;
constexpr int B_SMEM = B_BAR + 512;

__device__ __forceinline__ void st128(uint4* p, uint32_t a, uint32_t b, uint32_t c, uint32_t d) {
  asm volatile("{\n.reg .b128 v;\n.reg .b64 lo, hi;\nmov.b64 lo, {%1, %2};\nmov.b64 hi, {%3, %4};\nmov.b128 v, {lo, hi};\n"
               "st.relaxed.gpu.global.b128 [%0], v;\n}" ::"l"(p), "r"(a), "r"(b), "r"(c), "r"(d) : "memory");
}
__device__ __forceinline__ void ld128(const uint4* p, uint32_t* r) {
  asm volatile("{\n.reg .b128 v;\n.reg .b64 lo, hi;\nld.relaxed.gpu.global.b128 v, [%4];\nmov.b128 {lo, hi}, v;\n"
               "mov.b64 {%0, %1}, lo;\nmov.b64 {%2, %3}, hi;\n}" : "=r"(r[0]), "=r"(r[1]), "=r"(r[2]), "=r"(r[3]) : "l"(p) : "memory");
}

__device__ __forceinline__ uint32_t mapa(uint32_t a, uint32_t r) { uint32_t o; asm("mapa.shared::cluster.u32 %0, %1, %2;" : "=r"(o) : "r"(a), "r"(r)); return o; }

template <int Q, int ST>
__device__ __forceinline__ void g1_stage(float (&acc)[112], uint32_t alo, uint32_t blo, uint32_t bar_full, uint32_t bar_h) {
  constexpr int s = Q * 14 + ST, sl = s % B_NSLOT;
  if (Q == 0) mbar_wait(bar_h + 8 * ST, 0);
  mbar_wait(bar_full + 8 * sl, (s / B_NSLOT) & 1);
  wg_fence();
  wgmma_ss224<(2 * ST) * 256, 0x40000080u, (sl * B_SLOT) / 16, 32, ST != 0>(acc, alo, blo);
  wgmma_ss224<(2 * ST + 1) * 256, 0x40000080u, (sl * B_SLOT + 256) / 16, 32, 1>(acc, alo, blo);
}

__global__ void __cluster_dims__(2, 1, 1) __launch_bounds__(384, 1) k_ffn(__nv_bfloat16* __restrict__ out) {
  extern __shared__ __align__(1024) unsigned char sm[];
  const uint32_t sb = s2u(sm);
  const int tid = threadIdx.x, wg = tid >> 7, warp = tid >> 5, lane = tid & 31;
  const int rank = blockIdx.x & 1, rt = blockIdx.x & 15, j = blockIdx.x >> 4;
  const uint32_t bar_full = sb + B_BAR, bar_empty = bar_full + 64, bar_h = bar_full + 128, bar_cs = bar_full + 240, bar_stat = bar_full + 248,
                 bar_adead = bar_full + 256, bar_in = bar_full + 264;
  if (tid == 0) {
    TR(1, 0);
    for (int i = 0; i < B_NSLOT; i++) { mbar_init(bar_full + 8 * i, 1); mbar_init(bar_empty + 8 * i, 4); }
    for (int i = 0; i < 14; i++) mbar_init(bar_h + 8 * i, 1);
    mbar_init(bar_cs, 1);
    mbar_init(bar_stat, 64);
    mbar_init(bar_adead, 2);
    for (int i = 0; i < 14; i++) mbar_init(bar_in + 8 * i, 1);
    asm volatile("fence.mbarrier_init.release.cluster;" ::: "memory");
  }
  __syncthreads();
  asm volatile("barrier.cluster.arrive.release.aligned;" ::: "memory");

  if (wg == 2) {
    asm volatile("setmaxnreg.dec.sync.aligned.u32 88;");
    asm volatile("barrier.cluster.wait.acquire.aligned;" ::: "memory");
    asm volatile("griddepcontrol.wait;" ::: "memory");
    if (warp == 8) {
      if (lane == 0) {
        const char* wsrc = (const char*)g_wimg + (size_t)j * 602112;
        TR(1, 1);
        int slot = 0, ph = 0;
        for (int s = 0; s < 44; s++) {
          if (s >= B_NSLOT) mbar_wait(bar_empty + 8 * slot, ph ^ 1);
          uint32_t dst = sb + B_RING + slot * B_SLOT, fb = bar_full + 8 * slot;
          if (s < 28) {
            mbar_expect(fb, 14336);
            bulk_ld_mc(dst + rank * 7168, wsrc + s * 14336 + rank * 7168, 7168, fb);
          } else {
            const int c = (j + 1 + ((s - 28) >> 1)) & 7;
            mbar_expect(fb, 12544);
            bulk_ld_mc(dst + rank * 6272, wsrc + 401408 + (c * 2 + (s & 1)) * 12544 + rank * 6272, 6272, fb);
          }
          if (++slot == B_NSLOT) { slot = 0; ph ^= 1; }
        }
      }
    } else if (warp == 9) {
      if (lane == 0) {
        const char* hsrc = (const char*)g_himg + (size_t)rt * 114688;
        for (int i = 0; i < 14; i++) {
          mbar_expect(bar_h + 8 * i, 8192);
          bulk_ld(sb + B_SA + i * 8192, hsrc + i * 8192, 8192, bar_h + 8 * i);
        }
        mbar_expect(bar_cs, 7168);
        bulk_ld(sb + B_CS, g_cimg + j * 448, 7168, bar_cs);
      }
    } else {
      const int t64 = tid - 320;
      const uint32_t ep = __ldcg(&g_epoch), tag = ep & 1u;
      {
        const int r = lane & 7, c = (j & 3) * 2 + (warp & 1);
        const uint32_t addr = sb + B_SA + (lane >> 3) * 2048 + (j >> 2) * 1024 + r * 128 + ((c ^ r) << 4);
        float d[4] = {0.f, 0.f, 0.f, 0.f};
#pragma unroll 2
        for (int i = 0; i < 14; i++) {
          uint32_t x[4];
          mbar_wait(bar_h + 8 * i, 0);
          asm volatile("ldmatrix.sync.aligned.m8n8.x4.trans.shared.b16 {%0,%1,%2,%3}, [%4];"
                       : "=r"(x[0]), "=r"(x[1]), "=r"(x[2]), "=r"(x[3]) : "r"(addr + i * 8192) : "memory");
#pragma unroll
          for (int k = 0; k < 2; k++)
            asm volatile("mma.sync.aligned.m16n8k16.row.col.f32.bf16.bf16.f32 {%0,%1,%2,%3}, {%4,%6,%5,%6}, {%4,%5}, {%0,%1,%2,%3};"
                         : "+f"(d[0]), "+f"(d[1]), "+f"(d[2]), "+f"(d[3]) : "r"(x[2 * k]), "r"(x[2 * k + 1]), "r"(0x3F803F80u));
        }
        const int g = lane >> 2;
        if ((lane & 3) == (g >> 1)) {
          float mean = ((g & 1) ? d[3] : d[2]) * (1.f / DM);
          float var = fmaxf(fmaf(-mean, mean, ((g & 1) ? d[1] : d[0]) * (1.f / DM)), 0.f);
          float rs = __frcp_rn(rbf(__fsqrt_rn(rbf(rbf(var) + 1e-5f))));
          uint32_t nm = pack_bf16(-mean, -mean), r2 = (__float_as_uint(rs * rs) & ~1u) | tag;
          asm volatile("{\n.reg .b64 v;\nmov.b64 v, {%1, %2};\nst.relaxed.gpu.global.b64 [%0], v;\n}"
                       ::"l"(g_stat2 + rt * 128 + j * 16 + (warp & 1) * 8 + g), "r"(nm), "r"(r2) : "memory");
        }
        if (t64 == 0) TR(1, 2);
      }
      __syncwarp();
      {
        uint32_t w[4];
        int it = 0;
        do { ld128((const uint4*)(g_stat2 + rt * 128) + t64, w); } while ((((w[1] ^ tag) | (w[3] ^ tag)) & 1u) && ++it < 200000);
        *(uint4*)(sm + B_STAT + t64 * 16) = make_uint4(w[0], w[1], w[2], w[3]);
        mbar_arrive(bar_stat);
      }
      if (t64 == 0) TR(1, 18);
      if (warp == 11) {
        mbar_wait(bar_adead, 0);
        bool todo = lane < 14;
        int it = 0;
        while (__any_sync(~0u, todo) && ++it < 200000) {
          if (todo) {
            uint32_t w[4];
            ld128(g_flag + (rt * 8 + j) * 16 + lane, w);
            if (w[0] == ep && w[1] == ep && w[2] == ep && w[3] == ep) {
              const uint32_t b = bar_in + 8 * ((lane & 1) * 7 + (lane >> 1));
              asm volatile("fence.proxy.async.global;" ::: "memory");
              mbar_expect(b, 7168);
              bulk_ld(sb + B_SA + lane * 7168, g_part + (size_t)((rt * 8 + j) * 7) * 896 + lane * 448, 7168, b);
              todo = false;
              if (!(lane & 1)) TR(1, 24 + (lane >> 1));
            }
          }
        }
      }
    }
  } else {
    asm volatile("setmaxnreg.inc.sync.aligned.u32 208;");
    const int g = lane >> 2, t = lane & 3, wq = warp & 3, t128 = tid & 127;
    uint32_t hh[56], hres[16];
    asm volatile("barrier.cluster.wait.acquire.aligned;" ::: "memory");
    asm volatile("griddepcontrol.wait;" ::: "memory");
    const uint32_t ep = __ldcg(&g_epoch), tag = (ep & 1u) << 16;
    const uint32_t rel_bar = mapa(bar_empty, t128 & 1);
    auto release = [&](int sl) { if (t128 < 2) asm volatile("mbarrier.arrive.shared::cluster.b64 _, [%0];" ::"r"(rel_bar + 8 * sl) : "memory"); };
    const uint32_t alo = __shfl_sync(~0u, ((sb + B_SA + wg * 1024) & 0x3FFFF) >> 4, 0);
    const uint32_t blo = (((sb + B_RING) & 0x3FFFF) >> 4) | (8u << 16);
    const uint32_t clo = ((sb + B_CS) & 0x3FFFF) >> 4;
    uint32_t nm0, nm1; float r20, r21;
    if (wg == 1) asm volatile("bar.sync 3, 256;" ::: "memory");
#define G1S(Q, ST) do { g1_stage<Q, ST>(acc, alo, blo, bar_full, bar_h); wg_commit(); \
      if (ST > 0) { wg_wait<1>(); release((Q * 14 + ST - 1) % B_NSLOT); } } while (0)
#define G1EPI(Q) do { \
      g1_stage<Q, 13>(acc, alo, blo, bar_full, bar_h); \
      wgmma_rs224<Q * 224, 8, 1>(acc, nm0, nm1, 0u, 0u, clo); \
      wg_commit(); wg_wait<1>(); release((Q * 14 + 12) % B_NSLOT); \
      wg_wait<0>(); reg_fence(acc); release((Q * 14 + 13) % B_NSLOT); \
      _Pragma("unroll") \
      for (int i = 0; i < 28; i++) hh[28 * Q + i] = pack_bf16(acc[2 * i] * acc[56 + 2 * i], acc[2 * i + 1] * acc[57 + 2 * i]); \
    } while (0)
    {
      float acc[112];
      G1S(0, 0);
      if (tid == 0) TR(1, 3);
      G1S(0, 1);
      if (wg == 0) asm volatile("bar.arrive 3, 256;" ::: "memory");
      G1S(0, 2); G1S(0, 3); G1S(0, 4); G1S(0, 5); G1S(0, 6); G1S(0, 7); G1S(0, 8); G1S(0, 9); G1S(0, 10); G1S(0, 11); G1S(0, 12);
      if (tid == 0) TR(1, 4);
      mbar_wait(bar_stat, 0);
      mbar_wait(bar_cs, 0);
      {
        uint2 a = *(const uint2*)(sm + B_STAT + (wg * 64 + wq * 16 + g) * 8), b = *(const uint2*)(sm + B_STAT + (wg * 64 + wq * 16 + g + 8) * 8);
        const uint32_t msk = t == 0 ? 0xFFFFFFFFu : t == 1 ? 0xFFFFu : 0u;
        nm0 = a.x & msk; nm1 = b.x & msk; r20 = __uint_as_float(a.y); r21 = __uint_as_float(b.y);
      }
      G1EPI(0);
      if (tid == 0) TR(1, 5);
      G1S(1, 0); G1S(1, 1); G1S(1, 2); G1S(1, 3); G1S(1, 4); G1S(1, 5); G1S(1, 6); G1S(1, 7); G1S(1, 8); G1S(1, 9); G1S(1, 10); G1S(1, 11);
#pragma unroll
      for (int i = 0; i < 4; i++) {
        int qq = lane >> 3, r = lane & 7, kg = 7 * j + 2 * i + (qq >> 1), c = 2 * wq + (qq & 1);
        if (kg > 55) kg = 55;
        uint32_t addr = sb + B_SA + kg * 2048 + wg * 1024 + r * 128 + ((c ^ r) << 4);
        asm volatile("ldmatrix.sync.aligned.m8n8.x4.trans.shared.b16 {%0,%1,%2,%3}, [%4];"
                     : "=r"(hres[4 * i]), "=r"(hres[4 * i + 1]), "=r"(hres[4 * i + 2]), "=r"(hres[4 * i + 3]) : "r"(addr) : "memory");
      }
      G1S(1, 12);
      G1EPI(1);
      if (t128 == 0) mbar_arrive(bar_adead);
      if (tid == 0) TR(1, 6);
    }
    float accA[28], accB[28], sum[28];
    int nxt = 0;
#pragma unroll
    for (int i = 0; i < 28; i++) sum[i] = 0.f;
#define ISSUE(acc, I, a, FIRST) do { \
      constexpr int s_ = 28 + (I), sl_ = s_ % B_NSLOT; \
      mbar_wait(bar_full + 8 * sl_, (s_ / B_NSLOT) & 1); \
      wg_fence(); \
      wgmma_rs56<(sl_ * B_SLOT + 0 * 256) / 16, 112, !(FIRST)>(acc, (a)[0], (a)[1], (a)[2], (a)[3], blo); \
      wgmma_rs56<(sl_ * B_SLOT + 1 * 256) / 16, 112, 1>(acc, (a)[4], (a)[5], (a)[6], (a)[7], blo); \
      wgmma_rs56<(sl_ * B_SLOT + 2 * 256) / 16, 112, 1>(acc, (a)[8], (a)[9], (a)[10], (a)[11], blo); \
      wgmma_rs56<(sl_ * B_SLOT + 3 * 256) / 16, 112, 1>(acc, (a)[12], (a)[13], (a)[14], (a)[15], blo); \
      wgmma_rs56<(sl_ * B_SLOT + 4 * 256) / 16, 112, 1>(acc, (a)[16], (a)[17], (a)[18], (a)[19], blo); \
      wgmma_rs56<(sl_ * B_SLOT + 5 * 256) / 16, 112, 1>(acc, (a)[20], (a)[21], (a)[22], (a)[23], blo); \
      wgmma_rs56<(sl_ * B_SLOT + 6 * 256) / 16, 112, 1>(acc, (a)[24], (a)[25], (a)[26], (a)[27], blo); \
      wg_commit(); } while (0)
    auto rel = [&](int i) { if (i < 9) release((28 + i) % B_NSLOT); };
    auto tg = [&](uint32_t v) { return (v & 0xFFFEFFFFu) | tag; };
    auto send_lo = [&](float (&acc)[28], int cc) {
      reg_fence(acc);
      uint4* dst = g_part + (size_t)((rt * 8 + ((j + 1 + cc) & 7)) * 7 + cc) * 896 + wg * 448 + t128;
#pragma unroll
      for (int q = 0; q < 2; q++)
        st128(dst + q * 128, pack_bf16(acc[8 * q], acc[8 * q + 1]), pack_bf16(acc[8 * q + 2], acc[8 * q + 3]),
              pack_bf16(acc[8 * q + 4], acc[8 * q + 5]), tg(pack_bf16(acc[8 * q + 6], acc[8 * q + 7])));
    };
    auto send_hi = [&](float (&acc)[28], int cc) {
      uint4* dst = g_part + (size_t)((rt * 8 + ((j + 1 + cc) & 7)) * 7 + cc) * 896 + wg * 448;
      st128(dst + 256 + t128, pack_bf16(acc[16], acc[17]), pack_bf16(acc[18], acc[19]), pack_bf16(acc[20], acc[21]), tg(pack_bf16(acc[22], acc[23])));
      asm volatile("{\n.reg .b64 v;\nmov.b64 v, {%1, %2};\nst.relaxed.gpu.global.b64 [%0], v;\n}"
                   ::"l"((uint2*)(dst + 384) + t128), "r"(pack_bf16(acc[24], acc[25])), "r"(tg(pack_bf16(acc[26], acc[27]))) : "memory");
      if (lane == 0)
        asm volatile("st.relaxed.gpu.global.u32 [%0], %1;" ::"l"((uint32_t*)(g_flag + (rt * 8 + ((j + 1 + cc) & 7)) * 16 + cc * 2 + wg) + wq), "r"(ep) : "memory");
    };
    auto accum = [&]() {
      const unsigned char* src = sm + B_SA + nxt * 14336 + wg * 7168;
      uint4 a = *(const uint4*)(src + t128 * 16), b = *(const uint4*)(src + 2048 + t128 * 16), c = *(const uint4*)(src + 4096 + t128 * 16);
      uint2 d = *(const uint2*)(src + 6144 + t128 * 8);
      uint32_t in[14] = {a.x, a.y, a.z, a.w, b.x, b.y, b.z, b.w, c.x, c.y, c.z, c.w, d.x, d.y};
      int it = 0;
      while ((((in[3] ^ tag) | (in[7] ^ tag) | (in[11] ^ tag) | (in[13] ^ tag)) & 0x10000u) && ++it < 200000) {
        const uint4* gs = g_part + (size_t)((rt * 8 + j) * 7 + nxt) * 896 + wg * 448;
#pragma unroll
        for (int i = 0; i < 3; i++) ld128(gs + i * 128 + t128, in + 4 * i);
        asm volatile("{\n.reg .b64 v;\nld.relaxed.gpu.global.b64 v, [%2];\nmov.b64 {%0, %1}, v;\n}"
                     : "=r"(in[12]), "=r"(in[13]) : "l"((const uint2*)(gs + 384) + t128) : "memory");
      }
#pragma unroll
      for (int i = 0; i < 14; i++) { sum[2 * i] += bf_lo(in[i]); sum[2 * i + 1] += bf_hi(in[i]); }
      nxt++;
    };
    auto try_accum = [&]() {
      uint32_t ok;
      asm volatile("{\n.reg .pred p;\nmbarrier.test_wait.parity.shared::cta.b64 p, [%1], 0;\nselp.u32 %0, 1, 0, p;\n}"
                   : "=r"(ok) : "r"(bar_in + 8 * (wg * 7 + nxt)) : "memory");
      if (__all_sync(~0u, ok)) accum();
    };
#define CHUNK(cur, prev, CC, EXTRA) do { \
      ISSUE(cur, 2 * (CC), hh, true); wg_wait<1>(); rel(2 * (CC) - 1); send_lo(prev, (CC) - 1); \
      ISSUE(cur, 2 * (CC) + 1, hh + 28, false); send_hi(prev, (CC) - 1); EXTRA; wg_wait<1>(); rel(2 * (CC)); } while (0)
    ISSUE(accA, 0, hh, true);
    ISSUE(accA, 1, hh + 28, false); wg_wait<1>(); rel(0);
    CHUNK(accB, accA, 1, );
    if (tid == 0) TR(1, 11);
    CHUNK(accA, accB, 2, );
    if (tid == 0) TR(1, 12);
    CHUNK(accB, accA, 3, try_accum());
    if (tid == 0) TR(1, 13);
    CHUNK(accA, accB, 4, try_accum());
    if (tid == 0) TR(1, 14);
    CHUNK(accB, accA, 5, try_accum());
    if (tid == 0) TR(1, 16);
    CHUNK(accA, accB, 6, try_accum());
    if (tid == 0) TR(1, 17);
    CHUNK(accB, accA, 7, try_accum());
    if (tid == 0) TR(1, 7);
#pragma unroll 1
    while (nxt < 7) { mbar_wait(bar_in + 8 * (wg * 7 + nxt), 0); accum(); }
    wg_wait<0>();
    reg_fence(accB);
    if (tid == 0) TR(1, 9);
    const int row = rt * 128 + wg * 64 + wq * 16 + g;
    uint32_t* o0 = (uint32_t*)(out + (size_t)row * DM + 56 * j + 2 * t);
    uint32_t* o1 = o0 + 8 * DM / 2;
#pragma unroll
    for (int i = 0; i < 7; i++) {
      o0[4 * i] = hadd2_bf(hres[2 * i], pack_bf16((sum[4 * i] + accB[4 * i]) * r20, (sum[4 * i + 1] + accB[4 * i + 1]) * r20));
      o1[4 * i] = hadd2_bf(hres[2 * i + 1], pack_bf16((sum[4 * i + 2] + accB[4 * i + 2]) * r21, (sum[4 * i + 3] + accB[4 * i + 3]) * r21));
    }
    if (tid == 0) TR(1, 10);
    if (tid == 128) TR(1, 15);

  }
}

extern "C" void kernel_launch(void* const* d_in, const int* in_sizes, int n_in, void* d_out, int out_size) {
  const __nv_bfloat16* x = (const __nv_bfloat16*)d_in[0];
  const __nv_bfloat16 *are = (const __nv_bfloat16*)d_in[1], *aim = (const __nv_bfloat16*)d_in[2], *bre = (const __nv_bfloat16*)d_in[3],
                      *bim = (const __nv_bfloat16*)d_in[4], *cre = (const __nv_bfloat16*)d_in[5], *cim = (const __nv_bfloat16*)d_in[6],
                      *logdt = (const __nv_bfloat16*)d_in[7], *dskip = (const __nv_bfloat16*)d_in[8];
  const __nv_bfloat16 *wg = (const __nv_bfloat16*)d_in[10], *wu = (const __nv_bfloat16*)d_in[11], *wd = (const __nv_bfloat16*)d_in[12];

  static bool init = false;
  if (!init) {
    init = true;
    cudaFuncSetAttribute(k_ffn, cudaFuncAttributeMaxDynamicSharedMemorySize, B_SMEM);
  }
  cudaStream_t st = cudaStreamPerThread;
  k_ln1<<<256, 256, 0, st>>>(x);
  k_kgen<<<DM, 512, 0, st>>>(are, aim, bre, bim, cre, cim, logdt);
  k_conv<<<DM, 512, 0, st>>>(x, dskip);
  k_colsum<<<2 * FF / 128, 128, 0, st>>>(wg, wu);
  k_pack<<<3 * 100352 / 256, 256, 0, st>>>((const uint4*)wg, (const uint4*)wu, (const uint4*)wd);
  k_ffn<<<128, 384, B_SMEM, st>>>((__nv_bfloat16*)d_out);
}
```

```cpp
#include <cuda_runtime.h>
#include <cuda_bf16.h>
#include <stdint.h>

constexpr int LSEQ = 2048, DM = 448, FF = 1792, NST = 256;

__device__ uint4    g_himg[16 * 114688 / 16];
__device__ uint4    g_cimg[8 * 2 * 224];
__device__ uint32_t g_stat2[LSEQ];
__device__ uint4    g_part[128 * 7 * 896];
__device__ uint4    g_wimg[8 * 602112 / 16];
__device__ unsigned g_epoch;
__device__ uint4    g_flag[128 * 16];
__device__ __nv_bfloat16 g_u[LSEQ * DM];
__device__ float    g_kd[DM * 2064];

#define TR(k, i) do {} while (0)
__device__ __forceinline__ uint32_t s2u(const void* p) { return (uint32_t)__cvta_generic_to_shared(p); }
__device__ __forceinline__ void mbar_init(uint32_t b, int c) { asm volatile("mbarrier.init.shared::cta.b64 [%0], %1;" ::"r"(b), "r"(c)); }
__device__ __forceinline__ void mbar_expect(uint32_t b, int bytes) { asm volatile("mbarrier.arrive.expect_tx.shared::cta.b64 _, [%0], %1;" ::"r"(b), "r"(bytes) : "memory"); }
__device__ __forceinline__ void mbar_arrive(uint32_t b) { asm volatile("mbarrier.arrive.shared::cta.b64 _, [%0];" ::"r"(b) : "memory"); }
__device__ __forceinline__ void mbar_wait(uint32_t b, int ph) {
  asm volatile("{\n.reg .pred p;\n.reg .b32 n;\nmov.b32 n, 0;\nLW:\nmbarrier.try_wait.parity.shared::cta.b64 p, [%0], %1;\n@p bra LD;\n"
               "add.u32 n, n, 1;\nsetp.lt.u32 p, n, 4000000;\n@p bra LW;\ntrap;\nLD:\n}" ::"r"(b), "r"(ph) : "memory");
}
__device__ __forceinline__ uint64_t mkdesc(uint32_t addr, uint32_t lbo, uint32_t sbo, uint32_t sw) {
  return (uint64_t)((addr & 0x3FFFF) >> 4) | ((uint64_t)((lbo >> 4) & 0x3FFF) << 16) | ((uint64_t)((sbo >> 4) & 0x3FFF) << 32) | ((uint64_t)sw << 62);
}
__device__ __forceinline__ void wg_fence() { asm volatile("wgmma.fence.sync.aligned;" ::: "memory"); }
__device__ __forceinline__ void wg_commit() { asm volatile("wgmma.commit_group.sync.aligned;" ::: "memory"); }
template <int N> __device__ __forceinline__ void wg_wait() { asm volatile("wgmma.wait_group.sync.aligned %0;" ::"n"(N) : "memory"); }
template <int N> __device__ __forceinline__ void reg_fence(float (&a)[N]) {
#pragma unroll
  for (int i = 0; i < N; i++) asm volatile("" : "+f"(a[i])::"memory");
}
__device__ __forceinline__ uint32_t pack_bf16(float lo, float hi) {
  uint32_t r; asm("cvt.rn.bf16x2.f32 %0, %1, %2;" : "=r"(r) : "f"(hi), "f"(lo)); return r;
}
__device__ __forceinline__ float bf_lo(uint32_t v) { return __uint_as_float(v << 16); }
__device__ __forceinline__ float bf_hi(uint32_t v) { return __uint_as_float(v & 0xFFFF0000u); }
__device__ __forceinline__ float rbf(float x) { return __bfloat162float(__float2bfloat16_rn(x)); }
__device__ __forceinline__ uint32_t hmul2_bf(uint32_t a, uint32_t b) { uint32_t r; asm("mul.rn.bf16x2 %0, %1, %2;" : "=r"(r) : "r"(a), "r"(b)); return r; }
__device__ __forceinline__ uint32_t hadd2_bf(uint32_t a, uint32_t b) { uint32_t r; asm("add.rn.bf16x2 %0, %1, %2;" : "=r"(r) : "r"(a), "r"(b)); return r; }
__device__ __forceinline__ void bulk_ld(uint32_t dst, const void* src, int bytes, uint32_t bar) {
  asm volatile("cp.async.bulk.shared::cluster.global.mbarrier::complete_tx::bytes [%0], [%1], %2, [%3];"
               ::"r"(dst), "l"(src), "r"(bytes), "r"(bar) : "memory");
}

__device__ __forceinline__ void bulk_ld_mc(uint32_t dst, const void* src, int bytes, uint32_t bar) {
  asm volatile("cp.async.bulk.shared::cluster.global.mbarrier::complete_tx::bytes.multicast::cluster [%0], [%1], %2, [%3], %4;"
               ::"r"(dst), "l"(src), "r"(bytes), "r"(bar), "h"((uint16_t)3) : "memory");
}
template <int AOFF, uint32_t AHI, int BOFF, uint32_t BHI, int ACC>
__device__ __forceinline__ void wgmma_ss224(float (&d)[112], uint32_t alo, uint32_t blo) {
  asm volatile("{\n.reg .pred p;\n.reg .b32 la, lb;\n.reg .b64 ad, bd;\nsetp.ne.b32 p, %118, 0;\n"
    "add.u32 la, %112, %114;\nmov.b64 ad, {la, %115};\nadd.u32 lb, %113, %116;\nmov.b64 bd, {lb, %117};\n"
    "wgmma.mma_async.sync.aligned.m64n224k16.f32.bf16.bf16 {%0,%1,%2,%3,%4,%5,%6,%7,%8,%9,%10,%11,%12,%13,%14,%15,%16,%17,%18,%19,%20,%21,%22,%23,%24,%25,%26,%27,%28,%29,%30,%31,%32,%33,%34,%35,%36,%37,%38,%39,%40,%41,%42,%43,%44,%45,%46,%47,%48,%49,%50,%51,%52,%53,%54,%55,%56,%57,%58,%59,%60,%61,%62,%63,%64,%65,%66,%67,%68,%69,%70,%71,%72,%73,%74,%75,%76,%77,%78,%79,%80,%81,%82,%83,%84,%85,%86,%87,%88,%89,%90,%91,%92,%93,%94,%95,%96,%97,%98,%99,%100,%101,%102,%103,%104,%105,%106,%107,%108,%109,%110,%111}, ad, bd, p, 1, 1, 1, 1;\n}\n"
    : "+f"(d[0]),"+f"(d[1]),"+f"(d[2]),"+f"(d[3]),"+f"(d[4]),"+f"(d[5]),"+f"(d[6]),"+f"(d[7]),"+f"(d[8]),"+f"(d[9]),"+f"(d[10]),"+f"(d[11]),"+f"(d[12]),"+f"(d[13]),"+f"(d[14]),"+f"(d[15]),"+f"(d[16]),"+f"(d[17]),"+f"(d[18]),"+f"(d[19]),"+f"(d[20]),"+f"(d[21]),"+f"(d[22]),"+f"(d[23]),"+f"(d[24]),"+f"(d[25]),"+f"(d[26]),"+f"(d[27]),"+f"(d[28]),"+f"(d[29]),"+f"(d[30]),"+f"(d[31]),"+f"(d[32]),"+f"(d[33]),"+f"(d[34]),"+f"(d[35]),"+f"(d[36]),"+f"(d[37]),"+f"(d[38]),"+f"(d[39]),"+f"(d[40]),"+f"(d[41]),"+f"(d[42]),"+f"(d[43]),"+f"(d[44]),"+f"(d[45]),"+f"(d[46]),"+f"(d[47]),"+f"(d[48]),"+f"(d[49]),"+f"(d[50]),"+f"(d[51]),"+f"(d[52]),"+f"(d[53]),"+f"(d[54]),"+f"(d[55]),"+f"(d[56]),"+f"(d[57]),"+f"(d[58]),"+f"(d[59]),"+f"(d[60]),"+f"(d[61]),"+f"(d[62]),"+f"(d[63]),"+f"(d[64]),"+f"(d[65]),"+f"(d[66]),"+f"(d[67]),"+f"(d[68]),"+f"(d[69]),"+f"(d[70]),"+f"(d[71]),"+f"(d[72]),"+f"(d[73]),"+f"(d[74]),"+f"(d[75]),"+f"(d[76]),"+f"(d[77]),"+f"(d[78]),"+f"(d[79]),"+f"(d[80]),"+f"(d[81]),"+f"(d[82]),"+f"(d[83]),"+f"(d[84]),"+f"(d[85]),"+f"(d[86]),"+f"(d[87]),"+f"(d[88]),"+f"(d[89]),"+f"(d[90]),"+f"(d[91]),"+f"(d[92]),"+f"(d[93]),"+f"(d[94]),"+f"(d[95]),"+f"(d[96]),"+f"(d[97]),"+f"(d[98]),"+f"(d[99]),"+f"(d[100]),"+f"(d[101]),"+f"(d[102]),"+f"(d[103]),"+f"(d[104]),"+f"(d[105]),"+f"(d[106]),"+f"(d[107]),"+f"(d[108]),"+f"(d[109]),"+f"(d[110]),"+f"(d[111])
    : "r"(alo), "r"(blo), "n"(AOFF), "n"(AHI), "n"(BOFF), "n"(BHI), "n"(ACC));
}
template <int AOFF, uint32_t AHI, int BOFF, uint32_t BHI, int ACC>
__device__ __forceinline__ void wgmma_ss232(float (&d)[116], uint32_t alo, uint32_t blo) {
  asm volatile("{\n.reg .pred p;\n.reg .b32 la, lb;\n.reg .b64 ad, bd;\nsetp.ne.b32 p, %122, 0;\n"
    "add.u32 la, %116, %118;\nmov.b64 ad, {la, %119};\nadd.u32 lb, %117, %120;\nmov.b64 bd, {lb, %121};\n"
    "wgmma.mma_async.sync.aligned.m64n232k16.f32.bf16.bf16 {%0,%1,%2,%3,%4,%5,%6,%7,%8,%9,%10,%11,%12,%13,%14,%15,%16,%17,%18,%19,%20,%21,%22,%23,%24,%25,%26,%27,%28,%29,%30,%31,%32,%33,%34,%35,%36,%37,%38,%39,%40,%41,%42,%43,%44,%45,%46,%47,%48,%49,%50,%51,%52,%53,%54,%55,%56,%57,%58,%59,%60,%61,%62,%63,%64,%65,%66,%67,%68,%69,%70,%71,%72,%73,%74,%75,%76,%77,%78,%79,%80,%81,%82,%83,%84,%85,%86,%87,%88,%89,%90,%91,%92,%93,%94,%95,%96,%97,%98,%99,%100,%101,%102,%103,%104,%105,%106,%107,%108,%109,%110,%111,%112,%113,%114,%115}, ad, bd, p, 1, 1, 1, 1;\n}\n"
    : "+f"(d[0]),"+f"(d[1]),"+f"(d[2]),"+f"(d[3]),"+f"(d[4]),"+f"(d[5]),"+f"(d[6]),"+f"(d[7]),"+f"(d[8]),"+f"(d[9]),"+f"(d[10]),"+f"(d[11]),"+f"(d[12]),"+f"(d[13]),"+f"(d[14]),"+f"(d[15]),"+f"(d[16]),"+f"(d[17]),"+f"(d[18]),"+f"(d[19]),"+f"(d[20]),"+f"(d[21]),"+f"(d[22]),"+f"(d[23]),"+f"(d[24]),"+f"(d[25]),"+f"(d[26]),"+f"(d[27]),"+f"(d[28]),"+f"(d[29]),"+f"(d[30]),"+f"(d[31]),"+f"(d[32]),"+f"(d[33]),"+f"(d[34]),"+f"(d[35]),"+f"(d[36]),"+f"(d[37]),"+f"(d[38]),"+f"(d[39]),"+f"(d[40]),"+f"(d[41]),"+f"(d[42]),"+f"(d[43]),"+f"(d[44]),"+f"(d[45]),"+f"(d[46]),"+f"(d[47]),"+f"(d[48]),"+f"(d[49]),"+f"(d[50]),"+f"(d[51]),"+f"(d[52]),"+f"(d[53]),"+f"(d[54]),"+f"(d[55]),"+f"(d[56]),"+f"(d[57]),"+f"(d[58]),"+f"(d[59]),"+f"(d[60]),"+f"(d[61]),"+f"(d[62]),"+f"(d[63]),"+f"(d[64]),"+f"(d[65]),"+f"(d[66]),"+f"(d[67]),"+f"(d[68]),"+f"(d[69]),"+f"(d[70]),"+f"(d[71]),"+f"(d[72]),"+f"(d[73]),"+f"(d[74]),"+f"(d[75]),"+f"(d[76]),"+f"(d[77]),"+f"(d[78]),"+f"(d[79]),"+f"(d[80]),"+f"(d[81]),"+f"(d[82]),"+f"(d[83]),"+f"(d[84]),"+f"(d[85]),"+f"(d[86]),"+f"(d[87]),"+f"(d[88]),"+f"(d[89]),"+f"(d[90]),"+f"(d[91]),"+f"(d[92]),"+f"(d[93]),"+f"(d[94]),"+f"(d[95]),"+f"(d[96]),"+f"(d[97]),"+f"(d[98]),"+f"(d[99]),"+f"(d[100]),"+f"(d[101]),"+f"(d[102]),"+f"(d[103]),"+f"(d[104]),"+f"(d[105]),"+f"(d[106]),"+f"(d[107]),"+f"(d[108]),"+f"(d[109]),"+f"(d[110]),"+f"(d[111]),"+f"(d[112]),"+f"(d[113]),"+f"(d[114]),"+f"(d[115])
    : "r"(alo), "r"(blo), "n"(AOFF), "n"(AHI), "n"(BOFF), "n"(BHI), "n"(ACC));
}
template <int OFF, uint32_t BHI, int ACC>
__device__ __forceinline__ void wgmma_rs224(float (&d)[112], uint32_t a0, uint32_t a1, uint32_t a2, uint32_t a3, uint32_t blo) {
  asm volatile("{\n.reg .pred p;\n.reg .b32 l;\n.reg .b64 bd;\nsetp.ne.b32 p, %119, 0;\nadd.u32 l, %116, %117;\nmov.b64 bd, {l, %118};\n"
    "wgmma.mma_async.sync.aligned.m64n224k16.f32.bf16.bf16 {%0,%1,%2,%3,%4,%5,%6,%7,%8,%9,%10,%11,%12,%13,%14,%15,%16,%17,%18,%19,%20,%21,%22,%23,%24,%25,%26,%27,%28,%29,%30,%31,%32,%33,%34,%35,%36,%37,%38,%39,%40,%41,%42,%43,%44,%45,%46,%47,%48,%49,%50,%51,%52,%53,%54,%55,%56,%57,%58,%59,%60,%61,%62,%63,%64,%65,%66,%67,%68,%69,%70,%71,%72,%73,%74,%75,%76,%77,%78,%79,%80,%81,%82,%83,%84,%85,%86,%87,%88,%89,%90,%91,%92,%93,%94,%95,%96,%97,%98,%99,%100,%101,%102,%103,%104,%105,%106,%107,%108,%109,%110,%111}, {%112,%113,%114,%115}, bd, p, 1, 1, 1;\n}\n"
    : "+f"(d[0]),"+f"(d[1]),"+f"(d[2]),"+f"(d[3]),"+f"(d[4]),"+f"(d[5]),"+f"(d[6]),"+f"(d[7]),"+f"(d[8]),"+f"(d[9]),"+f"(d[10]),"+f"(d[11]),"+f"(d[12]),"+f"(d[13]),"+f"(d[14]),"+f"(d[15]),"+f"(d[16]),"+f"(d[17]),"+f"(d[18]),"+f"(d[19]),"+f"(d[20]),"+f"(d[21]),"+f"(d[22]),"+f"(d[23]),"+f"(d[24]),"+f"(d[25]),"+f"(d[26]),"+f"(d[27]),"+f"(d[28]),"+f"(d[29]),"+f"(d[30]),"+f"(d[31]),"+f"(d[32]),"+f"(d[33]),"+f"(d[34]),"+f"(d[35]),"+f"(d[36]),"+f"(d[37]),"+f"(d[38]),"+f"(d[39]),"+f"(d[40]),"+f"(d[41]),"+f"(d[42]),"+f"(d[43]),"+f"(d[44]),"+f"(d[45]),"+f"(d[46]),"+f"(d[47]),"+f"(d[48]),"+f"(d[49]),"+f"(d[50]),"+f"(d[51]),"+f"(d[52]),"+f"(d[53]),"+f"(d[54]),"+f"(d[55]),"+f"(d[56]),"+f"(d[57]),"+f"(d[58]),"+f"(d[59]),"+f"(d[60]),"+f"(d[61]),"+f"(d[62]),"+f"(d[63]),"+f"(d[64]),"+f"(d[65]),"+f"(d[66]),"+f"(d[67]),"+f"(d[68]),"+f"(d[69]),"+f"(d[70]),"+f"(d[71]),"+f"(d[72]),"+f"(d[73]),"+f"(d[74]),"+f"(d[75]),"+f"(d[76]),"+f"(d[77]),"+f"(d[78]),"+f"(d[79]),"+f"(d[80]),"+f"(d[81]),"+f"(d[82]),"+f"(d[83]),"+f"(d[84]),"+f"(d[85]),"+f"(d[86]),"+f"(d[87]),"+f"(d[88]),"+f"(d[89]),"+f"(d[90]),"+f"(d[91]),"+f"(d[92]),"+f"(d[93]),"+f"(d[94]),"+f"(d[95]),"+f"(d[96]),"+f"(d[97]),"+f"(d[98]),"+f"(d[99]),"+f"(d[100]),"+f"(d[101]),"+f"(d[102]),"+f"(d[103]),"+f"(d[104]),"+f"(d[105]),"+f"(d[106]),"+f"(d[107]),"+f"(d[108]),"+f"(d[109]),"+f"(d[110]),"+f"(d[111])
    : "r"(a0), "r"(a1), "r"(a2), "r"(a3), "r"(blo), "n"(OFF), "n"(BHI), "n"(ACC));
}
template <int OFF, uint32_t BHI, int ACC>
__device__ __forceinline__ void wgmma_rs56(float (&d)[28], uint32_t a0, uint32_t a1, uint32_t a2, uint32_t a3, uint32_t blo) {
  asm volatile("{\n.reg .pred p;\n.reg .b32 l;\n.reg .b64 bd;\nsetp.ne.b32 p, %35, 0;\nadd.u32 l, %32, %33;\nmov.b64 bd, {l, %34};\n"
    "wgmma.mma_async.sync.aligned.m64n56k16.f32.bf16.bf16 {%0,%1,%2,%3,%4,%5,%6,%7,%8,%9,%10,%11,%12,%13,%14,%15,%16,%17,%18,%19,%20,%21,%22,%23,%24,%25,%26,%27}, {%28,%29,%30,%31}, bd, p, 1, 1, 1;\n}\n"
    : "+f"(d[0]),"+f"(d[1]),"+f"(d[2]),"+f"(d[3]),"+f"(d[4]),"+f"(d[5]),"+f"(d[6]),"+f"(d[7]),"+f"(d[8]),"+f"(d[9]),"+f"(d[10]),"+f"(d[11]),"+f"(d[12]),"+f"(d[13]),"+f"(d[14]),"+f"(d[15]),"+f"(d[16]),"+f"(d[17]),"+f"(d[18]),"+f"(d[19]),"+f"(d[20]),"+f"(d[21]),"+f"(d[22]),"+f"(d[23]),"+f"(d[24]),"+f"(d[25]),"+f"(d[26]),"+f"(d[27])
    : "r"(a0), "r"(a1), "r"(a2), "r"(a3), "r"(blo), "n"(OFF), "n"(BHI), "n"(ACC));
}

__global__ void k_ln1(const __nv_bfloat16* __restrict__ x) {
  int row = blockIdx.x * 8 + threadIdx.x / 32, lane = threadIdx.x & 31;
  float v[14]; float s = 0;
  for (int i = 0; i < 14; i++) { v[i] = __bfloat162float(x[row * DM + lane + 32 * i]); s += v[i]; }
  for (int o = 16; o; o >>= 1) s += __shfl_xor_sync(~0u, s, o);
  float mean = s / DM, q = 0;
  for (int i = 0; i < 14; i++) q += (v[i] - mean) * (v[i] - mean);
  for (int o = 16; o; o >>= 1) q += __shfl_xor_sync(~0u, q, o);
  float m = rbf(mean), sd = rbf(sqrtf(rbf(rbf(q / DM) + 1e-5f)));
  for (int i = 0; i < 14; i++) g_u[row * DM + lane + 32 * i] = __float2bfloat16_rn(rbf(v[i] - m) / sd);
  if (blockIdx.x == 0 && threadIdx.x == 0) g_epoch = g_epoch + 1;
}
__global__ void k_kgen(const __nv_bfloat16* are, const __nv_bfloat16* aim, const __nv_bfloat16* bre, const __nv_bfloat16* bim,
                       const __nv_bfloat16* cre, const __nv_bfloat16* cim, const __nv_bfloat16* logdt) {
  int d = blockIdx.x;
  float dt = rbf(expf(__bfloat162float(logdt[d])));
  for (int l = threadIdx.x; l < 2048; l += blockDim.x) {
    float lf = rbf((float)l), acc = 0;
    for (int n = 0; n < NST; n++) {
      int i = d * NST + n;
      float lr = dt * __bfloat162float(are[i]), li = dt * __bfloat162float(aim[i]);
      float br = dt * __bfloat162float(bre[i]), bi = dt * __bfloat162float(bim[i]);
      float cr = __bfloat162float(cre[i]), ci = __bfloat162float(cim[i]);
      float wr = cr * br - ci * bi, wi = cr * bi + ci * br;
      float e = expf(lr * lf), sn, cs; sincosf(li * lf, &sn, &cs);
      acc += e * (wr * cs - wi * sn);
    }
    g_kd[d * 2064 + l] = acc;
  }
}
__global__ void k_conv(const __nv_bfloat16* __restrict__ x, const __nv_bfloat16* dskip) {
  __shared__ float sk[2048], su[2048];
  int d = blockIdx.x;
  for (int i = threadIdx.x; i < 2048; i += blockDim.x) { sk[i] = g_kd[d * 2064 + i]; su[i] = __bfloat162float(g_u[i * DM + d]); }
  __syncthreads();
  float ds = __bfloat162float(dskip[d]);
  for (int t = threadIdx.x; t < 2048; t += blockDim.x) {
    float acc = 0;
    for (int l = 0; l <= t; l++) acc += sk[l] * su[t - l];
    float yb = rbf(rbf(acc) + rbf(su[t] * ds));
    float h = rbf(__bfloat162float(x[t * DM + d]) + yb);
    int tau = t >> 3, rt = tau >> 4, mh = (tau >> 3) & 1, c = tau & 7, r = d & 7;
    size_t off = (size_t)rt * 114688 + (d >> 3) * 2048 + mh * 1024 + r * 128 + ((c ^ r) * 16) + (t & 7) * 2;
    *(__nv_bfloat16*)((char*)g_himg + off) = __float2bfloat16_rn(h);
  }
}
__global__ void k_colsum(const __nv_bfloat16* wg, const __nv_bfloat16* wu) {
  int f = blockIdx.x * blockDim.x + threadIdx.x;
  const __nv_bfloat16* w = f < FF ? wg : wu; int ff = f < FF ? f : f - FF;
  float s = 0; for (int d = 0; d < DM; d++) s += __bfloat162float(w[d * FF + ff]);
  float hi = rbf(s), mid = rbf(s - hi), lo = rbf(s - hi - mid);
  int j = ff / 224, q = (ff % 224) / 112, n = ff % 112 + (f < FF ? 0 : 112);
  __nv_bfloat16* dst = (__nv_bfloat16*)(g_cimg + (j * 2 + q) * 224 + (n >> 3) * 8) + (n & 7);
  dst[0] = __float2bfloat16_rn(hi); dst[8] = __float2bfloat16_rn(mid); dst[16] = __float2bfloat16_rn(lo);
  for (int k = 3; k < 8; k++) dst[8 * k] = __float2bfloat16_rn(0.f);
}
__global__ void k_pack(const uint4* __restrict__ wg, const uint4* __restrict__ wu, const uint4* __restrict__ wd) {
  int i = blockIdx.x * blockDim.x + threadIdx.x;
  int mat = i / 100352, e = i % 100352;
  if (mat < 2) {
    int d = e / 224, ngg = e % 224;
    int j = ngg / 28, q = (ngg % 28) / 14, ng = ngg % 14 + 14 * mat;
    g_wimg[(size_t)j * 37632 + (q * 14 + (d >> 5)) * 896 + ng * 32 + (d & 31)] = (mat ? wu : wg)[e];
  } else {
    int f = e / 56, ngg = e % 56;
    int j = f / 224, hf = (f % 224) / 112, k = f % 112, c = ngg / 7, ng = ngg % 7;
    g_wimg[(size_t)j * 37632 + 25088 + (c * 2 + hf) * 784 + ng * 112 + k] = wd[e];
  }
}

constexpr int B_SA = 0, B_RING = 114688, B_SLOT = 14848, B_NSLOT = 7;
constexpr int B_CS = B_RING + B_NSLOT * B_SLOT;
constexpr int B_STAT = B_CS + 7168;
constexpr int B_BAR = B_STAT + 512;
constexpr int B_SMEM = B_BAR + 512;

__device__ __forceinline__ void st128(uint4* p, uint32_t a, uint32_t b, uint32_t c, uint32_t d) {
  asm volatile("{\n.reg .b128 v;\n.reg .b64 lo, hi;\nmov.b64 lo, {%1, %2};\nmov.b64 hi, {%3, %4};\nmov.b128 v, {lo, hi};\n"
               "st.relaxed.gpu.global.b128 [%0], v;\n}" ::"l"(p), "r"(a), "r"(b), "r"(c), "r"(d) : "memory");
}
__device__ __forceinline__ void ld128(const uint4* p, uint32_t* r) {
  asm volatile("{\n.reg .b128 v;\n.reg .b64 lo, hi;\nld.relaxed.gpu.global.b128 v, [%4];\nmov.b128 {lo, hi}, v;\n"
               "mov.b64 {%0, %1}, lo;\nmov.b64 {%2, %3}, hi;\n}" : "=r"(r[0]), "=r"(r[1]), "=r"(r[2]), "=r"(r[3]) : "l"(p) : "memory");
}

__device__ __forceinline__ uint32_t mapa(uint32_t a, uint32_t r) { uint32_t o; asm("mapa.shared::cluster.u32 %0, %1, %2;" : "=r"(o) : "r"(a), "r"(r)); return o; }

template <int Q, int ST>
__device__ __forceinline__ void g1_stage(float (&acc)[116], uint32_t alo, uint32_t blo, uint32_t bar_full, uint32_t bar_h) {
  constexpr int s = Q * 14 + ST, sl = s % B_NSLOT;
  if (Q == 0) mbar_wait(bar_h + 8 * ST, 0);
  mbar_wait(bar_full + 8 * sl, (s / B_NSLOT) & 1);
  wg_fence();
  if (Q == 0) {
    wgmma_ss232<(2 * ST) * 256, 0x40000080u, (sl * B_SLOT) / 16, 32, ST != 0>(acc, alo, blo);
    wgmma_ss232<(2 * ST + 1) * 256, 0x40000080u, (sl * B_SLOT + 256) / 16, 32, 1>(acc, alo, blo);
  } else {
    wgmma_ss224<(2 * ST) * 256, 0x40000080u, (sl * B_SLOT) / 16, 32, ST != 0>(*(float(*)[112])acc, alo, blo);
    wgmma_ss224<(2 * ST + 1) * 256, 0x40000080u, (sl * B_SLOT + 256) / 16, 32, 1>(*(float(*)[112])acc, alo, blo);
  }
}

__global__ void __cluster_dims__(2, 1, 1) __launch_bounds__(384, 1) k_ffn(__nv_bfloat16* __restrict__ out) {
  extern __shared__ __align__(1024) unsigned char sm[];
  const uint32_t sb = s2u(sm);
  const int tid = threadIdx.x, wg = tid >> 7, warp = tid >> 5, lane = tid & 31;
  const int rank = blockIdx.x & 1, rt = blockIdx.x & 15, j = blockIdx.x >> 4;
  const uint32_t bar_full = sb + B_BAR, bar_empty = bar_full + 64, bar_h = bar_full + 128, bar_cs = bar_full + 240, bar_stat = bar_full + 248,
                 bar_adead = bar_full + 256, bar_in = bar_full + 264;
  if (tid == 0) {
    TR(1, 0);
    for (int i = 0; i < B_NSLOT; i++) { mbar_init(bar_full + 8 * i, 1); mbar_init(bar_empty + 8 * i, 4); }
    for (int i = 0; i < 14; i++) mbar_init(bar_h + 8 * i, 1);
    mbar_init(bar_cs, 1);
    mbar_init(bar_stat, 32);
    mbar_init(bar_adead, 3);
    for (int i = 0; i < 14; i++) mbar_init(bar_in + 8 * i, 1);
    asm volatile("fence.mbarrier_init.release.cluster;" ::: "memory");
  }
  if (tid >= 128 && tid < 128 + 224) {
    const int i = tid - 128;
    *(uint4*)(sm + B_RING + (i >> 5) * B_SLOT + 14336 + (i & 31) * 16) = make_uint4(0x3F803F80u, 0x3F803F80u, 0x3F803F80u, 0x3F803F80u);
    asm volatile("fence.proxy.async.shared::cta;" ::: "memory");
  }
  __syncthreads();
  asm volatile("barrier.cluster.arrive.release.aligned;" ::: "memory");

  if (wg == 2) {
    asm volatile("setmaxnreg.dec.sync.aligned.u32 88;");
    asm volatile("barrier.cluster.wait.acquire.aligned;" ::: "memory");
    asm volatile("griddepcontrol.wait;" ::: "memory");
    if (warp == 8) {
      if (lane == 0) {
        const char* wsrc = (const char*)g_wimg + (size_t)j * 602112;
        TR(1, 1);
        int slot = 0, ph = 0;
        for (int s = 0; s < 44; s++) {
          if (s >= B_NSLOT) mbar_wait(bar_empty + 8 * slot, ph ^ 1);
          uint32_t dst = sb + B_RING + slot * B_SLOT, fb = bar_full + 8 * slot;
          if (s < 28) {
            mbar_expect(fb, 14336);
            bulk_ld_mc(dst + rank * 7168, wsrc + s * 14336 + rank * 7168, 7168, fb);
          } else {
            const int c = (j + 1 + ((s - 28) >> 1)) & 7;
            mbar_expect(fb, 12544);
            bulk_ld_mc(dst + rank * 6272, wsrc + 401408 + (c * 2 + (s & 1)) * 12544 + rank * 6272, 6272, fb);
          }
          if (++slot == B_NSLOT) { slot = 0; ph ^= 1; }
        }
      }
    } else if (warp == 9) {
      if (lane == 0) {
        const char* hsrc = (const char*)g_himg + (size_t)rt * 114688;
        for (int i = 0; i < 14; i++) {
          mbar_expect(bar_h + 8 * i, 8192);
          bulk_ld(sb + B_SA + i * 8192, hsrc + i * 8192, 8192, bar_h + 8 * i);
        }
        mbar_expect(bar_cs, 7168);
        bulk_ld(sb + B_CS, g_cimg + j * 448, 7168, bar_cs);
      }
    } else {
      const int t64 = tid - 320;
      const uint32_t ep = __ldcg(&g_epoch), tag = ep & 1u;
      {
        const int r = lane & 7, c = (j & 3) * 2 + (warp & 1);
        const uint32_t addr = sb + B_SA + (lane >> 3) * 2048 + (j >> 2) * 1024 + r * 128 + ((c ^ r) << 4);
        float d[2][4] = {{0.f, 0.f, 0.f, 0.f}, {0.f, 0.f, 0.f, 0.f}};
#pragma unroll 2
        for (int i = 0; i < 14; i++) {
          uint32_t x[4];
          mbar_wait(bar_h + 8 * i, 0);
          asm volatile("ldmatrix.sync.aligned.m8n8.x4.trans.shared.b16 {%0,%1,%2,%3}, [%4];"
                       : "=r"(x[0]), "=r"(x[1]), "=r"(x[2]), "=r"(x[3]) : "r"(addr + i * 8192) : "memory");
#pragma unroll
          for (int k = 0; k < 2; k++)
            asm volatile("mma.sync.aligned.m16n8k16.row.col.f32.bf16.bf16.f32 {%0,%1,%2,%3}, {%4,%6,%5,%6}, {%4,%5}, {%0,%1,%2,%3};"
                         : "+f"(d[k][0]), "+f"(d[k][1]), "+f"(d[k][2]), "+f"(d[k][3]) : "r"(x[2 * k]), "r"(x[2 * k + 1]), "r"(0x3F803F80u));
        }
        const int g = lane >> 2;
        if ((lane & 3) == (g >> 1)) {
          float mean = ((g & 1) ? d[0][3] + d[1][3] : d[0][2] + d[1][2]) * (1.f / DM);
          float var = fmaxf(fmaf(-mean, mean, ((g & 1) ? d[0][1] + d[1][1] : d[0][0] + d[1][0]) * (1.f / DM)), 0.f);
          float rs = __frcp_rn(rbf(__fsqrt_rn(rbf(rbf(var) + 1e-5f))));
          asm volatile("st.relaxed.gpu.global.u32 [%0], %1;"
                       ::"l"(g_stat2 + rt * 128 + j * 16 + (warp & 1) * 8 + g), "r"((__float_as_uint(rs * rs) & ~1u) | tag) : "memory");
        }
        if (t64 == 0) TR(1, 2);
      }
      __syncwarp();
      if (warp == 10) {
        if (lane == 0) mbar_arrive(bar_adead);
        mbar_wait(bar_adead, 0);
        uint32_t w[4];
        int it = 0;
        do { ld128((const uint4*)(g_stat2 + rt * 128) + lane, w); } while ((((w[0] ^ tag) | (w[1] ^ tag) | (w[2] ^ tag) | (w[3] ^ tag)) & 1u) && ++it < 200000);
        *(uint4*)(sm + B_STAT + lane * 16) = make_uint4(w[0], w[1], w[2], w[3]);
        mbar_arrive(bar_stat);
      }
      if (t64 == 0) TR(1, 18);
      if (warp == 11) {
        mbar_wait(bar_adead, 0);
        bool todo = lane < 14;
        int it = 0;
        while (__any_sync(~0u, todo) && ++it < 200000) {
          if (todo) {
            uint32_t w[4];
            ld128(g_flag + (rt * 8 + j) * 16 + lane, w);
            if (w[0] == ep && w[1] == ep && w[2] == ep && w[3] == ep) {
              const uint32_t b = bar_in + 8 * ((lane & 1) * 7 + (lane >> 1));
              asm volatile("fence.proxy.async.global;" ::: "memory");
              mbar_expect(b, 7168);
              bulk_ld(sb + B_SA + lane * 7168, g_part + (size_t)((rt * 8 + j) * 7) * 896 + lane * 448, 7168, b);
              todo = false;
              if (!(lane & 1)) TR(1, 24 + (lane >> 1));
            }
          }
        }
      }
    }
  } else {
    asm volatile("setmaxnreg.inc.sync.aligned.u32 208;");
    const int g = lane >> 2, t = lane & 3, wq = warp & 3, t128 = tid & 127;
    uint32_t hh[56], hres[16];
    asm volatile("barrier.cluster.wait.acquire.aligned;" ::: "memory");
    asm volatile("griddepcontrol.wait;" ::: "memory");
    const uint32_t ep = __ldcg(&g_epoch), tag = (ep & 1u) << 16;
    const uint32_t rel_bar = mapa(bar_empty, t128 & 1);
    auto release = [&](int sl) { if (t128 < 2) asm volatile("mbarrier.arrive.shared::cluster.b64 _, [%0];" ::"r"(rel_bar + 8 * sl) : "memory"); };
    const uint32_t alo = __shfl_sync(~0u, ((sb + B_SA + wg * 1024) & 0x3FFFF) >> 4, 0);
    const uint32_t blo = (((sb + B_RING) & 0x3FFFF) >> 4) | (8u << 16);
    const uint32_t clo = ((sb + B_CS) & 0x3FFFF) >> 4;
    uint32_t nm0, nm1;
    if (wg == 1) asm volatile("bar.sync 3, 256;" ::: "memory");
#define G1S(Q, ST) do { g1_stage<Q, ST>(acc, alo, blo, bar_full, bar_h); wg_commit(); \
      if (ST > 0) { wg_wait<1>(); release((Q * 14 + ST - 1) % B_NSLOT); } } while (0)
#define G1HH(Q) do { \
      _Pragma("unroll") \
      for (int i = 0; i < 28; i++) hh[28 * Q + i] = pack_bf16(acc[2 * i] * acc[56 + 2 * i], acc[2 * i + 1] * acc[57 + 2 * i]); \
    } while (0)
    {
      float acc[116];
      G1S(0, 0);
      if (tid == 0) TR(1, 3);
      G1S(0, 1);
      if (wg == 0) asm volatile("bar.arrive 3, 256;" ::: "memory");
      G1S(0, 2); G1S(0, 3); G1S(0, 4); G1S(0, 5); G1S(0, 6); G1S(0, 7); G1S(0, 8); G1S(0, 9); G1S(0, 10); G1S(0, 11); G1S(0, 12);
      G1S(0, 13);
      if (tid == 0) TR(1, 4);
      mbar_wait(bar_cs, 0);
      wg_wait<0>(); reg_fence(acc); release(13 % B_NSLOT);
      {
        const uint32_t msk = t == 0 ? 0xFFFFFFFFu : t == 1 ? 0xFFFFu : 0u;
        const float a = acc[112] * (-1.f / DM), b = acc[114] * (-1.f / DM);
        nm0 = pack_bf16(a, a) & msk; nm1 = pack_bf16(b, b) & msk;
      }
      wg_fence();
      wgmma_rs224<0, 8, 1>(*(float(*)[112])acc, nm0, nm1, 0u, 0u, clo);
      wg_commit(); wg_wait<0>(); reg_fence(acc);
      G1HH(0);
      if (tid == 0) TR(1, 5);
      G1S(1, 0); G1S(1, 1); G1S(1, 2); G1S(1, 3); G1S(1, 4); G1S(1, 5); G1S(1, 6); G1S(1, 7); G1S(1, 8); G1S(1, 9); G1S(1, 10); G1S(1, 11);
#pragma unroll
      for (int i = 0; i < 4; i++) {
        int qq = lane >> 3, r = lane & 7, kg = 7 * j + 2 * i + (qq >> 1), c = 2 * wq + (qq & 1);
        if (kg > 55) kg = 55;
        uint32_t addr = sb + B_SA + kg * 2048 + wg * 1024 + r * 128 + ((c ^ r) << 4);
        asm volatile("ldmatrix.sync.aligned.m8n8.x4.trans.shared.b16 {%0,%1,%2,%3}, [%4];"
                     : "=r"(hres[4 * i]), "=r"(hres[4 * i + 1]), "=r"(hres[4 * i + 2]), "=r"(hres[4 * i + 3]) : "r"(addr) : "memory");
      }
      G1S(1, 12);
      g1_stage<1, 13>(acc, alo, blo, bar_full, bar_h);
      wgmma_rs224<224, 8, 1>(*(float(*)[112])acc, nm0, nm1, 0u, 0u, clo);
      wg_commit(); wg_wait<1>(); release(26 % B_NSLOT);
      wg_wait<0>(); reg_fence(acc); release(27 % B_NSLOT);
      G1HH(1);
      if (t128 == 0) mbar_arrive(bar_adead);
      if (tid == 0) TR(1, 6);
    }
    float accA[28], accB[28], sum[28];
    int nxt = 0;
#pragma unroll
    for (int i = 0; i < 28; i++) sum[i] = 0.f;
#define ISSUE(acc, I, a, FIRST) do { \
      constexpr int s_ = 28 + (I), sl_ = s_ % B_NSLOT; \
      mbar_wait(bar_full + 8 * sl_, (s_ / B_NSLOT) & 1); \
      wg_fence(); \
      wgmma_rs56<(sl_ * B_SLOT + 0 * 256) / 16, 112, !(FIRST)>(acc, (a)[0], (a)[1], (a)[2], (a)[3], blo); \
      wgmma_rs56<(sl_ * B_SLOT + 1 * 256) / 16, 112, 1>(acc, (a)[4], (a)[5], (a)[6], (a)[7], blo); \
      wgmma_rs56<(sl_ * B_SLOT + 2 * 256) / 16, 112, 1>(acc, (a)[8], (a)[9], (a)[10], (a)[11], blo); \
      wgmma_rs56<(sl_ * B_SLOT + 3 * 256) / 16, 112, 1>(acc, (a)[12], (a)[13], (a)[14], (a)[15], blo); \
      wgmma_rs56<(sl_ * B_SLOT + 4 * 256) / 16, 112, 1>(acc, (a)[16], (a)[17], (a)[18], (a)[19], blo); \
      wgmma_rs56<(sl_ * B_SLOT + 5 * 256) / 16, 112, 1>(acc, (a)[20], (a)[21], (a)[22], (a)[23], blo); \
      wgmma_rs56<(sl_ * B_SLOT + 6 * 256) / 16, 112, 1>(acc, (a)[24], (a)[25], (a)[26], (a)[27], blo); \
      wg_commit(); } while (0)
    auto rel = [&](int i) { if (i < 9) release((28 + i) % B_NSLOT); };
    auto tg = [&](uint32_t v) { return (v & 0xFFFEFFFFu) | tag; };
    auto send_lo = [&](float (&acc)[28], int cc) {
      reg_fence(acc);
      uint4* dst = g_part + (size_t)((rt * 8 + ((j + 1 + cc) & 7)) * 7 + cc) * 896 + wg * 448 + t128;
#pragma unroll
      for (int q = 0; q < 2; q++)
        st128(dst + q * 128, pack_bf16(acc[8 * q], acc[8 * q + 1]), pack_bf16(acc[8 * q + 2], acc[8 * q + 3]),
              pack_bf16(acc[8 * q + 4], acc[8 * q + 5]), tg(pack_bf16(acc[8 * q + 6], acc[8 * q + 7])));
    };
    auto send_hi = [&](float (&acc)[28], int cc) {
      uint4* dst = g_part + (size_t)((rt * 8 + ((j + 1 + cc) & 7)) * 7 + cc) * 896 + wg * 448;
      st128(dst + 256 + t128, pack_bf16(acc[16], acc[17]), pack_bf16(acc[18], acc[19]), pack_bf16(acc[20], acc[21]), tg(pack_bf16(acc[22], acc[23])));
      asm volatile("{\n.reg .b64 v;\nmov.b64 v, {%1, %2};\nst.relaxed.gpu.global.b64 [%0], v;\n}"
                   ::"l"((uint2*)(dst + 384) + t128), "r"(pack_bf16(acc[24], acc[25])), "r"(tg(pack_bf16(acc[26], acc[27]))) : "memory");
      if (lane == 0)
        asm volatile("st.relaxed.gpu.global.u32 [%0], %1;" ::"l"((uint32_t*)(g_flag + (rt * 8 + ((j + 1 + cc) & 7)) * 16 + cc * 2 + wg) + wq), "r"(ep) : "memory");
    };
    auto accum = [&]() {
      const unsigned char* src = sm + B_SA + nxt * 14336 + wg * 7168;
      uint4 a = *(const uint4*)(src + t128 * 16), b = *(const uint4*)(src + 2048 + t128 * 16), c = *(const uint4*)(src + 4096 + t128 * 16);
      uint2 d = *(const uint2*)(src + 6144 + t128 * 8);
      uint32_t in[14] = {a.x, a.y, a.z, a.w, b.x, b.y, b.z, b.w, c.x, c.y, c.z, c.w, d.x, d.y};
      int it = 0;
      while ((((in[3] ^ tag) | (in[7] ^ tag) | (in[11] ^ tag) | (in[13] ^ tag)) & 0x10000u) && ++it < 200000) {
        const uint4* gs = g_part + (size_t)((rt * 8 + j) * 7 + nxt) * 896 + wg * 448;
#pragma unroll
        for (int i = 0; i < 3; i++) ld128(gs + i * 128 + t128, in + 4 * i);
        asm volatile("{\n.reg .b64 v;\nld.relaxed.gpu.global.b64 v, [%2];\nmov.b64 {%0, %1}, v;\n}"
                     : "=r"(in[12]), "=r"(in[13]) : "l"((const uint2*)(gs + 384) + t128) : "memory");
      }
#pragma unroll
      for (int i = 0; i < 14; i++) { sum[2 * i] += bf_lo(in[i]); sum[2 * i + 1] += bf_hi(in[i]); }
      nxt++;
    };
    auto try_accum = [&]() {
      uint32_t ok;
      asm volatile("{\n.reg .pred p;\nmbarrier.test_wait.parity.shared::cta.b64 p, [%1], 0;\nselp.u32 %0, 1, 0, p;\n}"
                   : "=r"(ok) : "r"(bar_in + 8 * (wg * 7 + nxt)) : "memory");
      if (__all_sync(~0u, ok)) accum();
    };
#define CHUNK(cur, prev, CC, EXTRA) do { \
      ISSUE(cur, 2 * (CC), hh, true); wg_wait<1>(); rel(2 * (CC) - 1); send_lo(prev, (CC) - 1); \
      ISSUE(cur, 2 * (CC) + 1, hh + 28, false); send_hi(prev, (CC) - 1); EXTRA; wg_wait<1>(); rel(2 * (CC)); } while (0)
    ISSUE(accA, 0, hh, true);
    ISSUE(accA, 1, hh + 28, false); wg_wait<1>(); rel(0);
    CHUNK(accB, accA, 1, );
    if (tid == 0) TR(1, 11);
    CHUNK(accA, accB, 2, );
    if (tid == 0) TR(1, 12);
    CHUNK(accB, accA, 3, try_accum());
    if (tid == 0) TR(1, 13);
    CHUNK(accA, accB, 4, try_accum());
    if (tid == 0) TR(1, 14);
    CHUNK(accB, accA, 5, try_accum());
    if (tid == 0) TR(1, 16);
    CHUNK(accA, accB, 6, try_accum());
    if (tid == 0) TR(1, 17);
    CHUNK(accB, accA, 7, try_accum());
    if (tid == 0) TR(1, 7);
#pragma unroll 1
    while (nxt < 7) { mbar_wait(bar_in + 8 * (wg * 7 + nxt), 0); accum(); }
    wg_wait<0>();
    reg_fence(accB);
    if (tid == 0) TR(1, 9);
    mbar_wait(bar_stat, 0);
    const float r20 = *(const float*)(sm + B_STAT + (wg * 64 + wq * 16 + g) * 4), r21 = *(const float*)(sm + B_STAT + (wg * 64 + wq * 16 + g + 8) * 4);
    const int row = rt * 128 + wg * 64 + wq * 16 + g;
    uint32_t* o0 = (uint32_t*)(out + (size_t)row * DM + 56 * j + 2 * t);
    uint32_t* o1 = o0 + 8 * DM / 2;
#pragma unroll
    for (int i = 0; i < 7; i++) {
      o0[4 * i] = hadd2_bf(hres[2 * i], pack_bf16((sum[4 * i] + accB[4 * i]) * r20, (sum[4 * i + 1] + accB[4 * i + 1]) * r20));
      o1[4 * i] = hadd2_bf(hres[2 * i + 1], pack_bf16((sum[4 * i + 2] + accB[4 * i + 2]) * r21, (sum[4 * i + 3] + accB[4 * i + 3]) * r21));
    }
    if (tid == 0) TR(1, 10);
    if (tid == 128) TR(1, 15);

  }
}

extern "C" void kernel_launch(void* const* d_in, const int* in_sizes, int n_in, void* d_out, int out_size) {
  const __nv_bfloat16* x = (const __nv_bfloat16*)d_in[0];
  const __nv_bfloat16 *are = (const __nv_bfloat16*)d_in[1], *aim = (const __nv_bfloat16*)d_in[2], *bre = (const __nv_bfloat16*)d_in[3],
                      *bim = (const __nv_bfloat16*)d_in[4], *cre = (const __nv_bfloat16*)d_in[5], *cim = (const __nv_bfloat16*)d_in[6],
                      *logdt = (const __nv_bfloat16*)d_in[7], *dskip = (const __nv_bfloat16*)d_in[8];
  const __nv_bfloat16 *wg = (const __nv_bfloat16*)d_in[10], *wu = (const __nv_bfloat16*)d_in[11], *wd = (const __nv_bfloat16*)d_in[12];

  static bool init = false;
  if (!init) {
    init = true;
    cudaFuncSetAttribute(k_ffn, cudaFuncAttributeMaxDynamicSharedMemorySize, B_SMEM);
  }
  cudaStream_t st = cudaStreamPerThread;
  k_ln1<<<256, 256, 0, st>>>(x);
  k_kgen<<<DM, 512, 0, st>>>(are, aim, bre, bim, cre, cim, logdt);
  k_conv<<<DM, 512, 0, st>>>(x, dskip);
  k_colsum<<<2 * FF / 128, 128, 0, st>>>(wg, wu);
  k_pack<<<3 * 100352 / 256, 256, 0, st>>>((const uint4*)wg, (const uint4*)wu, (const uint4*)wd);
  k_ffn<<<128, 384, B_SMEM, st>>>((__nv_bfloat16*)d_out);
}
```

```cpp
#include <cuda_runtime.h>
#include <cuda_bf16.h>
#include <stdint.h>

constexpr int LSEQ = 2048, DM = 448, FF = 1792, NST = 256;

__device__ uint4    g_himg[16 * 114688 / 16];
__device__ uint4    g_cimg[8 * 2 * 224];
__device__ uint32_t g_stat2[LSEQ];
__device__ uint4    g_part[128 * 7 * 896];
__device__ uint4    g_wimg[8 * 602112 / 16];
__device__ unsigned g_epoch;
__device__ uint4    g_flag[128 * 16];
__device__ __nv_bfloat16 g_u[LSEQ * DM];
__device__ float    g_kd[DM * 2064];

#define TR(k, i) do {} while (0)
__device__ __forceinline__ uint32_t s2u(const void* p) { return (uint32_t)__cvta_generic_to_shared(p); }
__device__ __forceinline__ void mbar_init(uint32_t b, int c) { asm volatile("mbarrier.init.shared::cta.b64 [%0], %1;" ::"r"(b), "r"(c)); }
__device__ __forceinline__ void mbar_expect(uint32_t b, int bytes) { asm volatile("mbarrier.arrive.expect_tx.shared::cta.b64 _, [%0], %1;" ::"r"(b), "r"(bytes) : "memory"); }
__device__ __forceinline__ void mbar_arrive(uint32_t b) { asm volatile("mbarrier.arrive.shared::cta.b64 _, [%0];" ::"r"(b) : "memory"); }
__device__ __forceinline__ void mbar_wait(uint32_t b, int ph) {
  asm volatile("{\n.reg .pred p;\n.reg .b32 n;\nmov.b32 n, 0;\nLW:\nmbarrier.try_wait.parity.shared::cta.b64 p, [%0], %1;\n@p bra LD;\n"
               "add.u32 n, n, 1;\nsetp.lt.u32 p, n, 4000000;\n@p bra LW;\ntrap;\nLD:\n}" ::"r"(b), "r"(ph) : "memory");
}
__device__ __forceinline__ uint64_t mkdesc(uint32_t addr, uint32_t lbo, uint32_t sbo, uint32_t sw) {
  return (uint64_t)((addr & 0x3FFFF) >> 4) | ((uint64_t)((lbo >> 4) & 0x3FFF) << 16) | ((uint64_t)((sbo >> 4) & 0x3FFF) << 32) | ((uint64_t)sw << 62);
}
__device__ __forceinline__ void wg_fence() { asm volatile("wgmma.fence.sync.aligned;" ::: "memory"); }
__device__ __forceinline__ void wg_commit() { asm volatile("wgmma.commit_group.sync.aligned;" ::: "memory"); }
template <int N> __device__ __forceinline__ void wg_wait() { asm volatile("wgmma.wait_group.sync.aligned %0;" ::"n"(N) : "memory"); }
template <int N> __device__ __forceinline__ void reg_fence(float (&a)[N]) {
#pragma unroll
  for (int i = 0; i < N; i++) asm volatile("" : "+f"(a[i])::"memory");
}
__device__ __forceinline__ uint32_t pack_bf16(float lo, float hi) {
  uint32_t r; asm("cvt.rn.bf16x2.f32 %0, %1, %2;" : "=r"(r) : "f"(hi), "f"(lo)); return r;
}
__device__ __forceinline__ float bf_lo(uint32_t v) { return __uint_as_float(v << 16); }
__device__ __forceinline__ float bf_hi(uint32_t v) { return __uint_as_float(v & 0xFFFF0000u); }
__device__ __forceinline__ float rbf(float x) { return __bfloat162float(__float2bfloat16_rn(x)); }
__device__ __forceinline__ uint32_t hmul2_bf(uint32_t a, uint32_t b) { uint32_t r; asm("mul.rn.bf16x2 %0, %1, %2;" : "=r"(r) : "r"(a), "r"(b)); return r; }
__device__ __forceinline__ uint32_t hadd2_bf(uint32_t a, uint32_t b) { uint32_t r; asm("add.rn.bf16x2 %0, %1, %2;" : "=r"(r) : "r"(a), "r"(b)); return r; }
__device__ __forceinline__ void bulk_ld(uint32_t dst, const void* src, int bytes, uint32_t bar) {
  asm volatile("cp.async.bulk.shared::cluster.global.mbarrier::complete_tx::bytes [%0], [%1], %2, [%3];"
               ::"r"(dst), "l"(src), "r"(bytes), "r"(bar) : "memory");
}

__device__ __forceinline__ void bulk_ld_mc(uint32_t dst, const void* src, int bytes, uint32_t bar) {
  asm volatile("cp.async.bulk.shared::cluster.global.mbarrier::complete_tx::bytes.multicast::cluster [%0], [%1], %2, [%3], %4;"
               ::"r"(dst), "l"(src), "r"(bytes), "r"(bar), "h"((uint16_t)3) : "memory");
}
template <int AOFF, uint32_t AHI, int BOFF, uint32_t BHI, int ACC>
__device__ __forceinline__ void wgmma_ss224(float (&d)[112], uint32_t alo, uint32_t blo) {
  asm volatile("{\n.reg .pred p;\n.reg .b32 la, lb;\n.reg .b64 ad, bd;\nsetp.ne.b32 p, %118, 0;\n"
    "add.u32 la, %112, %114;\nmov.b64 ad, {la, %115};\nadd.u32 lb, %113, %116;\nmov.b64 bd, {lb, %117};\n"
    "wgmma.mma_async.sync.aligned.m64n224k16.f32.bf16.bf16 {%0,%1,%2,%3,%4,%5,%6,%7,%8,%9,%10,%11,%12,%13,%14,%15,%16,%17,%18,%19,%20,%21,%22,%23,%24,%25,%26,%27,%28,%29,%30,%31,%32,%33,%34,%35,%36,%37,%38,%39,%40,%41,%42,%43,%44,%45,%46,%47,%48,%49,%50,%51,%52,%53,%54,%55,%56,%57,%58,%59,%60,%61,%62,%63,%64,%65,%66,%67,%68,%69,%70,%71,%72,%73,%74,%75,%76,%77,%78,%79,%80,%81,%82,%83,%84,%85,%86,%87,%88,%89,%90,%91,%92,%93,%94,%95,%96,%97,%98,%99,%100,%101,%102,%103,%104,%105,%106,%107,%108,%109,%110,%111}, ad, bd, p, 1, 1, 1, 1;\n}\n"
    : "+f"(d[0]),"+f"(d[1]),"+f"(d[2]),"+f"(d[3]),"+f"(d[4]),"+f"(d[5]),"+f"(d[6]),"+f"(d[7]),"+f"(d[8]),"+f"(d[9]),"+f"(d[10]),"+f"(d[11]),"+f"(d[12]),"+f"(d[13]),"+f"(d[14]),"+f"(d[15]),"+f"(d[16]),"+f"(d[17]),"+f"(d[18]),"+f"(d[19]),"+f"(d[20]),"+f"(d[21]),"+f"(d[22]),"+f"(d[23]),"+f"(d[24]),"+f"(d[25]),"+f"(d[26]),"+f"(d[27]),"+f"(d[28]),"+f"(d[29]),"+f"(d[30]),"+f"(d[31]),"+f"(d[32]),"+f"(d[33]),"+f"(d[34]),"+f"(d[35]),"+f"(d[36]),"+f"(d[37]),"+f"(d[38]),"+f"(d[39]),"+f"(d[40]),"+f"(d[41]),"+f"(d[42]),"+f"(d[43]),"+f"(d[44]),"+f"(d[45]),"+f"(d[46]),"+f"(d[47]),"+f"(d[48]),"+f"(d[49]),"+f"(d[50]),"+f"(d[51]),"+f"(d[52]),"+f"(d[53]),"+f"(d[54]),"+f"(d[55]),"+f"(d[56]),"+f"(d[57]),"+f"(d[58]),"+f"(d[59]),"+f"(d[60]),"+f"(d[61]),"+f"(d[62]),"+f"(d[63]),"+f"(d[64]),"+f"(d[65]),"+f"(d[66]),"+f"(d[67]),"+f"(d[68]),"+f"(d[69]),"+f"(d[70]),"+f"(d[71]),"+f"(d[72]),"+f"(d[73]),"+f"(d[74]),"+f"(d[75]),"+f"(d[76]),"+f"(d[77]),"+f"(d[78]),"+f"(d[79]),"+f"(d[80]),"+f"(d[81]),"+f"(d[82]),"+f"(d[83]),"+f"(d[84]),"+f"(d[85]),"+f"(d[86]),"+f"(d[87]),"+f"(d[88]),"+f"(d[89]),"+f"(d[90]),"+f"(d[91]),"+f"(d[92]),"+f"(d[93]),"+f"(d[94]),"+f"(d[95]),"+f"(d[96]),"+f"(d[97]),"+f"(d[98]),"+f"(d[99]),"+f"(d[100]),"+f"(d[101]),"+f"(d[102]),"+f"(d[103]),"+f"(d[104]),"+f"(d[105]),"+f"(d[106]),"+f"(d[107]),"+f"(d[108]),"+f"(d[109]),"+f"(d[110]),"+f"(d[111])
    : "r"(alo), "r"(blo), "n"(AOFF), "n"(AHI), "n"(BOFF), "n"(BHI), "n"(ACC));
}
template <int AOFF, uint32_t AHI, int BOFF, uint32_t BHI, int ACC>
__device__ __forceinline__ void wgmma_ss232(float (&d)[116], uint32_t alo, uint32_t blo) {
  asm volatile("{\n.reg .pred p;\n.reg .b32 la, lb;\n.reg .b64 ad, bd;\nsetp.ne.b32 p, %122, 0;\n"
    "add.u32 la, %116, %118;\nmov.b64 ad, {la, %119};\nadd.u32 lb, %117, %120;\nmov.b64 bd, {lb, %121};\n"
    "wgmma.mma_async.sync.aligned.m64n232k16.f32.bf16.bf16 {%0,%1,%2,%3,%4,%5,%6,%7,%8,%9,%10,%11,%12,%13,%14,%15,%16,%17,%18,%19,%20,%21,%22,%23,%24,%25,%26,%27,%28,%29,%30,%31,%32,%33,%34,%35,%36,%37,%38,%39,%40,%41,%42,%43,%44,%45,%46,%47,%48,%49,%50,%51,%52,%53,%54,%55,%56,%57,%58,%59,%60,%61,%62,%63,%64,%65,%66,%67,%68,%69,%70,%71,%72,%73,%74,%75,%76,%77,%78,%79,%80,%81,%82,%83,%84,%85,%86,%87,%88,%89,%90,%91,%92,%93,%94,%95,%96,%97,%98,%99,%100,%101,%102,%103,%104,%105,%106,%107,%108,%109,%110,%111,%112,%113,%114,%115}, ad, bd, p, 1, 1, 1, 1;\n}\n"
    : "+f"(d[0]),"+f"(d[1]),"+f"(d[2]),"+f"(d[3]),"+f"(d[4]),"+f"(d[5]),"+f"(d[6]),"+f"(d[7]),"+f"(d[8]),"+f"(d[9]),"+f"(d[10]),"+f"(d[11]),"+f"(d[12]),"+f"(d[13]),"+f"(d[14]),"+f"(d[15]),"+f"(d[16]),"+f"(d[17]),"+f"(d[18]),"+f"(d[19]),"+f"(d[20]),"+f"(d[21]),"+f"(d[22]),"+f"(d[23]),"+f"(d[24]),"+f"(d[25]),"+f"(d[26]),"+f"(d[27]),"+f"(d[28]),"+f"(d[29]),"+f"(d[30]),"+f"(d[31]),"+f"(d[32]),"+f"(d[33]),"+f"(d[34]),"+f"(d[35]),"+f"(d[36]),"+f"(d[37]),"+f"(d[38]),"+f"(d[39]),"+f"(d[40]),"+f"(d[41]),"+f"(d[42]),"+f"(d[43]),"+f"(d[44]),"+f"(d[45]),"+f"(d[46]),"+f"(d[47]),"+f"(d[48]),"+f"(d[49]),"+f"(d[50]),"+f"(d[51]),"+f"(d[52]),"+f"(d[53]),"+f"(d[54]),"+f"(d[55]),"+f"(d[56]),"+f"(d[57]),"+f"(d[58]),"+f"(d[59]),"+f"(d[60]),"+f"(d[61]),"+f"(d[62]),"+f"(d[63]),"+f"(d[64]),"+f"(d[65]),"+f"(d[66]),"+f"(d[67]),"+f"(d[68]),"+f"(d[69]),"+f"(d[70]),"+f"(d[71]),"+f"(d[72]),"+f"(d[73]),"+f"(d[74]),"+f"(d[75]),"+f"(d[76]),"+f"(d[77]),"+f"(d[78]),"+f"(d[79]),"+f"(d[80]),"+f"(d[81]),"+f"(d[82]),"+f"(d[83]),"+f"(d[84]),"+f"(d[85]),"+f"(d[86]),"+f"(d[87]),"+f"(d[88]),"+f"(d[89]),"+f"(d[90]),"+f"(d[91]),"+f"(d[92]),"+f"(d[93]),"+f"(d[94]),"+f"(d[95]),"+f"(d[96]),"+f"(d[97]),"+f"(d[98]),"+f"(d[99]),"+f"(d[100]),"+f"(d[101]),"+f"(d[102]),"+f"(d[103]),"+f"(d[104]),"+f"(d[105]),"+f"(d[106]),"+f"(d[107]),"+f"(d[108]),"+f"(d[109]),"+f"(d[110]),"+f"(d[111]),"+f"(d[112]),"+f"(d[113]),"+f"(d[114]),"+f"(d[115])
    : "r"(alo), "r"(blo), "n"(AOFF), "n"(AHI), "n"(BOFF), "n"(BHI), "n"(ACC));
}
template <int OFF, uint32_t BHI, int ACC>
__device__ __forceinline__ void wgmma_rs224(float (&d)[112], uint32_t a0, uint32_t a1, uint32_t a2, uint32_t a3, uint32_t blo) {
  asm volatile("{\n.reg .pred p;\n.reg .b32 l;\n.reg .b64 bd;\nsetp.ne.b32 p, %119, 0;\nadd.u32 l, %116, %117;\nmov.b64 bd, {l, %118};\n"
    "wgmma.mma_async.sync.aligned.m64n224k16.f32.bf16.bf16 {%0,%1,%2,%3,%4,%5,%6,%7,%8,%9,%10,%11,%12,%13,%14,%15,%16,%17,%18,%19,%20,%21,%22,%23,%24,%25,%26,%27,%28,%29,%30,%31,%32,%33,%34,%35,%36,%37,%38,%39,%40,%41,%42,%43,%44,%45,%46,%47,%48,%49,%50,%51,%52,%53,%54,%55,%56,%57,%58,%59,%60,%61,%62,%63,%64,%65,%66,%67,%68,%69,%70,%71,%72,%73,%74,%75,%76,%77,%78,%79,%80,%81,%82,%83,%84,%85,%86,%87,%88,%89,%90,%91,%92,%93,%94,%95,%96,%97,%98,%99,%100,%101,%102,%103,%104,%105,%106,%107,%108,%109,%110,%111}, {%112,%113,%114,%115}, bd, p, 1, 1, 1;\n}\n"
    : "+f"(d[0]),"+f"(d[1]),"+f"(d[2]),"+f"(d[3]),"+f"(d[4]),"+f"(d[5]),"+f"(d[6]),"+f"(d[7]),"+f"(d[8]),"+f"(d[9]),"+f"(d[10]),"+f"(d[11]),"+f"(d[12]),"+f"(d[13]),"+f"(d[14]),"+f"(d[15]),"+f"(d[16]),"+f"(d[17]),"+f"(d[18]),"+f"(d[19]),"+f"(d[20]),"+f"(d[21]),"+f"(d[22]),"+f"(d[23]),"+f"(d[24]),"+f"(d[25]),"+f"(d[26]),"+f"(d[27]),"+f"(d[28]),"+f"(d[29]),"+f"(d[30]),"+f"(d[31]),"+f"(d[32]),"+f"(d[33]),"+f"(d[34]),"+f"(d[35]),"+f"(d[36]),"+f"(d[37]),"+f"(d[38]),"+f"(d[39]),"+f"(d[40]),"+f"(d[41]),"+f"(d[42]),"+f"(d[43]),"+f"(d[44]),"+f"(d[45]),"+f"(d[46]),"+f"(d[47]),"+f"(d[48]),"+f"(d[49]),"+f"(d[50]),"+f"(d[51]),"+f"(d[52]),"+f"(d[53]),"+f"(d[54]),"+f"(d[55]),"+f"(d[56]),"+f"(d[57]),"+f"(d[58]),"+f"(d[59]),"+f"(d[60]),"+f"(d[61]),"+f"(d[62]),"+f"(d[63]),"+f"(d[64]),"+f"(d[65]),"+f"(d[66]),"+f"(d[67]),"+f"(d[68]),"+f"(d[69]),"+f"(d[70]),"+f"(d[71]),"+f"(d[72]),"+f"(d[73]),"+f"(d[74]),"+f"(d[75]),"+f"(d[76]),"+f"(d[77]),"+f"(d[78]),"+f"(d[79]),"+f"(d[80]),"+f"(d[81]),"+f"(d[82]),"+f"(d[83]),"+f"(d[84]),"+f"(d[85]),"+f"(d[86]),"+f"(d[87]),"+f"(d[88]),"+f"(d[89]),"+f"(d[90]),"+f"(d[91]),"+f"(d[92]),"+f"(d[93]),"+f"(d[94]),"+f"(d[95]),"+f"(d[96]),"+f"(d[97]),"+f"(d[98]),"+f"(d[99]),"+f"(d[100]),"+f"(d[101]),"+f"(d[102]),"+f"(d[103]),"+f"(d[104]),"+f"(d[105]),"+f"(d[106]),"+f"(d[107]),"+f"(d[108]),"+f"(d[109]),"+f"(d[110]),"+f"(d[111])
    : "r"(a0), "r"(a1), "r"(a2), "r"(a3), "r"(blo), "n"(OFF), "n"(BHI), "n"(ACC));
}
template <int OFF, uint32_t BHI, int ACC>
__device__ __forceinline__ void wgmma_rs56(float (&d)[28], uint32_t a0, uint32_t a1, uint32_t a2, uint32_t a3, uint32_t blo) {
  asm volatile("{\n.reg .pred p;\n.reg .b32 l;\n.reg .b64 bd;\nsetp.ne.b32 p, %35, 0;\nadd.u32 l, %32, %33;\nmov.b64 bd, {l, %34};\n"
    "wgmma.mma_async.sync.aligned.m64n56k16.f32.bf16.bf16 {%0,%1,%2,%3,%4,%5,%6,%7,%8,%9,%10,%11,%12,%13,%14,%15,%16,%17,%18,%19,%20,%21,%22,%23,%24,%25,%26,%27}, {%28,%29,%30,%31}, bd, p, 1, 1, 1;\n}\n"
    : "+f"(d[0]),"+f"(d[1]),"+f"(d[2]),"+f"(d[3]),"+f"(d[4]),"+f"(d[5]),"+f"(d[6]),"+f"(d[7]),"+f"(d[8]),"+f"(d[9]),"+f"(d[10]),"+f"(d[11]),"+f"(d[12]),"+f"(d[13]),"+f"(d[14]),"+f"(d[15]),"+f"(d[16]),"+f"(d[17]),"+f"(d[18]),"+f"(d[19]),"+f"(d[20]),"+f"(d[21]),"+f"(d[22]),"+f"(d[23]),"+f"(d[24]),"+f"(d[25]),"+f"(d[26]),"+f"(d[27])
    : "r"(a0), "r"(a1), "r"(a2), "r"(a3), "r"(blo), "n"(OFF), "n"(BHI), "n"(ACC));
}

__global__ void k_ln1(const __nv_bfloat16* __restrict__ x) {
  int row = blockIdx.x * 8 + threadIdx.x / 32, lane = threadIdx.x & 31;
  float v[14]; float s = 0;
  for (int i = 0; i < 14; i++) { v[i] = __bfloat162float(x[row * DM + lane + 32 * i]); s += v[i]; }
  for (int o = 16; o; o >>= 1) s += __shfl_xor_sync(~0u, s, o);
  float mean = s / DM, q = 0;
  for (int i = 0; i < 14; i++) q += (v[i] - mean) * (v[i] - mean);
  for (int o = 16; o; o >>= 1) q += __shfl_xor_sync(~0u, q, o);
  float m = rbf(mean), sd = rbf(sqrtf(rbf(rbf(q / DM) + 1e-5f)));
  for (int i = 0; i < 14; i++) g_u[row * DM + lane + 32 * i] = __float2bfloat16_rn(rbf(v[i] - m) / sd);
  if (blockIdx.x == 0 && threadIdx.x == 0) g_epoch = g_epoch + 1;
}
__global__ void k_kgen(const __nv_bfloat16* are, const __nv_bfloat16* aim, const __nv_bfloat16* bre, const __nv_bfloat16* bim,
                       const __nv_bfloat16* cre, const __nv_bfloat16* cim, const __nv_bfloat16* logdt) {
  int d = blockIdx.x;
  float dt = rbf(expf(__bfloat162float(logdt[d])));
  for (int l = threadIdx.x; l < 2048; l += blockDim.x) {
    float lf = rbf((float)l), acc = 0;
    for (int n = 0; n < NST; n++) {
      int i = d * NST + n;
      float lr = dt * __bfloat162float(are[i]), li = dt * __bfloat162float(aim[i]);
      float br = dt * __bfloat162float(bre[i]), bi = dt * __bfloat162float(bim[i]);
      float cr = __bfloat162float(cre[i]), ci = __bfloat162float(cim[i]);
      float wr = cr * br - ci * bi, wi = cr * bi + ci * br;
      float e = expf(lr * lf), sn, cs; sincosf(li * lf, &sn, &cs);
      acc += e * (wr * cs - wi * sn);
    }
    g_kd[d * 2064 + l] = acc;
  }
}
__global__ void k_conv(const __nv_bfloat16* __restrict__ x, const __nv_bfloat16* dskip) {
  __shared__ float sk[2048], su[2048];
  int d = blockIdx.x;
  for (int i = threadIdx.x; i < 2048; i += blockDim.x) { sk[i] = g_kd[d * 2064 + i]; su[i] = __bfloat162float(g_u[i * DM + d]); }
  __syncthreads();
  float ds = __bfloat162float(dskip[d]);
  for (int t = threadIdx.x; t < 2048; t += blockDim.x) {
    float acc = 0;
    for (int l = 0; l <= t; l++) acc += sk[l] * su[t - l];
    float yb = rbf(rbf(acc) + rbf(su[t] * ds));
    float h = rbf(__bfloat162float(x[t * DM + d]) + yb);
    int tau = t >> 3, rt = tau >> 4, mh = (tau >> 3) & 1, c = tau & 7, r = d & 7;
    size_t off = (size_t)rt * 114688 + (d >> 3) * 2048 + mh * 1024 + r * 128 + ((c ^ r) * 16) + (t & 7) * 2;
    *(__nv_bfloat16*)((char*)g_himg + off) = __float2bfloat16_rn(h);
  }
}
__global__ void k_colsum(const __nv_bfloat16* wg, const __nv_bfloat16* wu) {
  int f = blockIdx.x * blockDim.x + threadIdx.x;
  const __nv_bfloat16* w = f < FF ? wg : wu; int ff = f < FF ? f : f - FF;
  float s = 0; for (int d = 0; d < DM; d++) s += __bfloat162float(w[d * FF + ff]);
  float hi = rbf(s), mid = rbf(s - hi), lo = rbf(s - hi - mid);
  int j = ff / 224, q = (ff % 224) / 112, n = ff % 112 + (f < FF ? 0 : 112);
  __nv_bfloat16* dst = (__nv_bfloat16*)(g_cimg + (j * 2 + q) * 224 + (n >> 3) * 8) + (n & 7);
  dst[0] = __float2bfloat16_rn(hi); dst[8] = __float2bfloat16_rn(mid); dst[16] = __float2bfloat16_rn(lo);
  for (int k = 3; k < 8; k++) dst[8 * k] = __float2bfloat16_rn(0.f);
}
__global__ void k_pack(const uint4* __restrict__ wg, const uint4* __restrict__ wu, const uint4* __restrict__ wd) {
  int i = blockIdx.x * blockDim.x + threadIdx.x;
  int mat = i / 100352, e = i % 100352;
  if (mat < 2) {
    int d = e / 224, ngg = e % 224;
    int j = ngg / 28, q = (ngg % 28) / 14, ng = ngg % 14 + 14 * mat;
    g_wimg[(size_t)j * 37632 + (q * 14 + (d >> 5)) * 896 + ng * 32 + (d & 31)] = (mat ? wu : wg)[e];
  } else {
    int f = e / 56, ngg = e % 56;
    int j = f / 224, hf = (f % 224) / 112, k = f % 112, c = ngg / 7, ng = ngg % 7;
    g_wimg[(size_t)j * 37632 + 25088 + (c * 2 + hf) * 784 + ng * 112 + k] = wd[e];
  }
}

constexpr int B_SA = 0, B_RING = 114688, B_SLOT = 14848, B_NSLOT = 7;
constexpr int B_CS = B_RING + B_NSLOT * B_SLOT;
constexpr int B_STAT = B_CS + 7168;
constexpr int B_BAR = B_STAT + 512;
constexpr int B_SMEM = B_BAR + 512;

__device__ __forceinline__ void st128(uint4* p, uint32_t a, uint32_t b, uint32_t c, uint32_t d) {
  asm volatile("{\n.reg .b128 v;\n.reg .b64 lo, hi;\nmov.b64 lo, {%1, %2};\nmov.b64 hi, {%3, %4};\nmov.b128 v, {lo, hi};\n"
               "st.relaxed.gpu.global.b128 [%0], v;\n}" ::"l"(p), "r"(a), "r"(b), "r"(c), "r"(d) : "memory");
}
__device__ __forceinline__ void ld128(const uint4* p, uint32_t* r) {
  asm volatile("{\n.reg .b128 v;\n.reg .b64 lo, hi;\nld.relaxed.gpu.global.b128 v, [%4];\nmov.b128 {lo, hi}, v;\n"
               "mov.b64 {%0, %1}, lo;\nmov.b64 {%2, %3}, hi;\n}" : "=r"(r[0]), "=r"(r[1]), "=r"(r[2]), "=r"(r[3]) : "l"(p) : "memory");
}

__device__ __forceinline__ uint32_t mapa(uint32_t a, uint32_t r) { uint32_t o; asm("mapa.shared::cluster.u32 %0, %1, %2;" : "=r"(o) : "r"(a), "r"(r)); return o; }

template <int Q, int ST>
__device__ __forceinline__ void g1_stage(float (&acc)[116], uint32_t alo, uint32_t blo, uint32_t bar_full, uint32_t bar_h) {
  constexpr int s = Q * 14 + ST, sl = s % B_NSLOT;
  if (Q == 0) mbar_wait(bar_h + 8 * ST, 0);
  mbar_wait(bar_full + 8 * sl, (s / B_NSLOT) & 1);
  wg_fence();
  if (Q == 0) {
    wgmma_ss232<(2 * ST) * 256, 0x40000080u, (sl * B_SLOT) / 16, 32, ST != 0>(acc, alo, blo);
    wgmma_ss232<(2 * ST + 1) * 256, 0x40000080u, (sl * B_SLOT + 256) / 16, 32, 1>(acc, alo, blo);
  } else {
    wgmma_ss224<(2 * ST) * 256, 0x40000080u, (sl * B_SLOT) / 16, 32, ST != 0>(*(float(*)[112])acc, alo, blo);
    wgmma_ss224<(2 * ST + 1) * 256, 0x40000080u, (sl * B_SLOT + 256) / 16, 32, 1>(*(float(*)[112])acc, alo, blo);
  }
}

__global__ void __cluster_dims__(2, 1, 1) __launch_bounds__(384, 1) k_ffn(__nv_bfloat16* __restrict__ out) {
  extern __shared__ __align__(1024) unsigned char sm[];
  const uint32_t sb = s2u(sm);
  const int tid = threadIdx.x, wg = tid >> 7, warp = tid >> 5, lane = tid & 31;
  const int rank = blockIdx.x & 1, rt = blockIdx.x & 15, j = blockIdx.x >> 4;
  const uint32_t bar_full = sb + B_BAR, bar_empty = bar_full + 64, bar_h = bar_full + 128, bar_cs = bar_full + 240, bar_stat = bar_full + 248,
                 bar_adead = bar_full + 256, bar_in = bar_full + 264;
  if (tid == 0) {
    TR(1, 0);
    for (int i = 0; i < B_NSLOT; i++) { mbar_init(bar_full + 8 * i, 1); mbar_init(bar_empty + 8 * i, 4); }
    for (int i = 0; i < 14; i++) mbar_init(bar_h + 8 * i, 1);
    mbar_init(bar_cs, 1);
    mbar_init(bar_stat, 32);
    mbar_init(bar_adead, 2);
    for (int i = 0; i < 14; i++) mbar_init(bar_in + 8 * i, 1);
    asm volatile("fence.mbarrier_init.release.cluster;" ::: "memory");
  }
  if (tid >= 128 && tid < 128 + 224) {
    const int i = tid - 128;
    *(uint4*)(sm + B_RING + (i >> 5) * B_SLOT + 14336 + (i & 31) * 16) = make_uint4(0x3F803F80u, 0x3F803F80u, 0x3F803F80u, 0x3F803F80u);
    asm volatile("fence.proxy.async.shared::cta;" ::: "memory");
  }
  __syncthreads();
  asm volatile("barrier.cluster.arrive.release.aligned;" ::: "memory");

  if (wg == 2) {
    asm volatile("setmaxnreg.dec.sync.aligned.u32 88;");
    asm volatile("barrier.cluster.wait.acquire.aligned;" ::: "memory");
    asm volatile("griddepcontrol.wait;" ::: "memory");
    if (warp == 8) {
      if (lane == 0) {
        const char* wsrc = (const char*)g_wimg + (size_t)j * 602112;
        TR(1, 1);
        int slot = 0, ph = 0;
        for (int s = 0; s < 44; s++) {
          if (s >= B_NSLOT) mbar_wait(bar_empty + 8 * slot, ph ^ 1);
          uint32_t dst = sb + B_RING + slot * B_SLOT, fb = bar_full + 8 * slot;
          if (s < 28) {
            mbar_expect(fb, 14336);
            bulk_ld_mc(dst + rank * 7168, wsrc + s * 14336 + rank * 7168, 7168, fb);
          } else {
            const int c = (j + 1 + ((s - 28) >> 1)) & 7;
            mbar_expect(fb, 12544);
            bulk_ld_mc(dst + rank * 6272, wsrc + 401408 + (c * 2 + (s & 1)) * 12544 + rank * 6272, 6272, fb);
          }
          if (++slot == B_NSLOT) { slot = 0; ph ^= 1; }
        }
      }
    } else if (warp == 9) {
      if (lane == 0) {
        const char* hsrc = (const char*)g_himg + (size_t)rt * 114688;
        for (int i = 0; i < 14; i++) {
          mbar_expect(bar_h + 8 * i, 8192);
          bulk_ld(sb + B_SA + i * 8192, hsrc + i * 8192, 8192, bar_h + 8 * i);
        }
        mbar_expect(bar_cs, 7168);
        bulk_ld(sb + B_CS, g_cimg + j * 448, 7168, bar_cs);
      }
    } else {
      const int t64 = tid - 320;
      const uint32_t ep = __ldcg(&g_epoch), tag = ep & 1u;
      {
        const int r = (lane >> 1) & 7, c = (j & 3) * 2 + (lane & 1);
        const unsigned char* src = sm + B_SA + (t64 >> 4) * 2048 + (j >> 2) * 1024 + r * 128 + ((c ^ r) << 4);
        float a[16];
#pragma unroll
        for (int k = 0; k < 16; k++) a[k] = 0.f;
#pragma unroll 1
        for (int i = 0; i < 14; i++) {
          mbar_wait(bar_h + 8 * i, 0);
          uint4 v = *(const uint4*)(src + i * 8192);
          float e[8] = {bf_lo(v.x), bf_hi(v.x), bf_lo(v.y), bf_hi(v.y), bf_lo(v.z), bf_hi(v.z), bf_lo(v.w), bf_hi(v.w)};
#pragma unroll
          for (int k = 0; k < 8; k++) { a[2 * k] += e[k]; a[2 * k + 1] = fmaf(e[k], e[k], a[2 * k + 1]); }
          __nanosleep(160);
        }
#pragma unroll
        for (int rd = 0; rd < 4; rd++) {
          const int n = 8 >> rd;
          const bool up = lane & (2 * n);
#pragma unroll
          for (int k = 0; k < 8; k++) {
            if (k < n) {
              float keep = up ? a[k + n] : a[k], give = up ? a[k] : a[k + n];
              a[k] = keep + __shfl_xor_sync(~0u, give, 2 * n);
            }
          }
        }
        float* red = (float*)(sm + B_STAT);
        red[(warp & 1) * 32 + (lane & 1) * 16 + (lane >> 1)] = a[0];
        asm volatile("bar.sync 1, 64;" ::: "memory");
        if (t64 < 16) {
          float mean = (red[2 * t64] + red[32 + 2 * t64]) * (1.f / DM);
          float var = fmaxf(fmaf(-mean, mean, (red[2 * t64 + 1] + red[33 + 2 * t64]) * (1.f / DM)), 0.f);
          float rs = __frcp_rn(rbf(__fsqrt_rn(rbf(rbf(var) + 1e-5f))));
          asm volatile("st.relaxed.gpu.global.u32 [%0], %1;"
                       ::"l"(g_stat2 + rt * 128 + j * 16 + t64), "r"((__float_as_uint(rs * rs) & ~1u) | tag) : "memory");
        }
        if (t64 == 0) TR(1, 2);
      }
      __syncwarp();
      if (warp == 10) {
        mbar_wait(bar_adead, 0);
        uint32_t w[4];
        int it = 0;
        do { ld128((const uint4*)(g_stat2 + rt * 128) + lane, w); } while ((((w[0] ^ tag) | (w[1] ^ tag) | (w[2] ^ tag) | (w[3] ^ tag)) & 1u) && ++it < 200000);
        *(uint4*)(sm + B_STAT + lane * 16) = make_uint4(w[0], w[1], w[2], w[3]);
        mbar_arrive(bar_stat);
      }
      if (t64 == 0) TR(1, 18);
      if (warp == 11) {
        mbar_wait(bar_adead, 0);
        bool todo = lane < 14;
        int it = 0;
        while (__any_sync(~0u, todo) && ++it < 200000) {
          if (todo) {
            uint32_t w[4];
            ld128(g_flag + (rt * 8 + j) * 16 + lane, w);
            if (w[0] == ep && w[1] == ep && w[2] == ep && w[3] == ep) {
              const uint32_t b = bar_in + 8 * ((lane & 1) * 7 + (lane >> 1));
              asm volatile("fence.proxy.async.global;" ::: "memory");
              mbar_expect(b, 7168);
              bulk_ld(sb + B_SA + lane * 7168, g_part + (size_t)((rt * 8 + j) * 7) * 896 + lane * 448, 7168, b);
              todo = false;
              if (!(lane & 1)) TR(1, 24 + (lane >> 1));
            }
          }
        }
      }
    }
  } else {
    asm volatile("setmaxnreg.inc.sync.aligned.u32 208;");
    const int g = lane >> 2, t = lane & 3, wq = warp & 3, t128 = tid & 127;
    uint32_t hh[56], hres[16];
    asm volatile("barrier.cluster.wait.acquire.aligned;" ::: "memory");
    asm volatile("griddepcontrol.wait;" ::: "memory");
    const uint32_t ep = __ldcg(&g_epoch), tag = (ep & 1u) << 16;
    const uint32_t rel_bar = mapa(bar_empty, t128 & 1);
    auto release = [&](int sl) { if (t128 < 2) asm volatile("mbarrier.arrive.shared::cluster.b64 _, [%0];" ::"r"(rel_bar + 8 * sl) : "memory"); };
    const uint32_t alo = __shfl_sync(~0u, ((sb + B_SA + wg * 1024) & 0x3FFFF) >> 4, 0);
    const uint32_t blo = (((sb + B_RING) & 0x3FFFF) >> 4) | (8u << 16);
    const uint32_t clo = ((sb + B_CS) & 0x3FFFF) >> 4;
    uint32_t nm0, nm1;
    if (wg == 1) asm volatile("bar.sync 3, 256;" ::: "memory");
#define G1S(Q, ST) do { g1_stage<Q, ST>(acc, alo, blo, bar_full, bar_h); wg_commit(); \
      if (ST > 0) { wg_wait<1>(); release((Q * 14 + ST - 1) % B_NSLOT); } } while (0)
#define G1HH(Q) do { \
      _Pragma("unroll") \
      for (int i = 0; i < 28; i++) hh[28 * Q + i] = pack_bf16(acc[2 * i] * acc[56 + 2 * i], acc[2 * i + 1] * acc[57 + 2 * i]); \
    } while (0)
    {
      float acc[116];
      G1S(0, 0);
      if (tid == 0) TR(1, 3);
      G1S(0, 1);
      if (wg == 0) asm volatile("bar.arrive 3, 256;" ::: "memory");
      G1S(0, 2); G1S(0, 3); G1S(0, 4); G1S(0, 5); G1S(0, 6); G1S(0, 7); G1S(0, 8); G1S(0, 9); G1S(0, 10); G1S(0, 11); G1S(0, 12);
      G1S(0, 13);
      if (tid == 0) TR(1, 4);
      mbar_wait(bar_cs, 0);
      wg_wait<0>(); reg_fence(acc); release(13 % B_NSLOT);
      {
        const uint32_t msk = t == 0 ? 0xFFFFFFFFu : t == 1 ? 0xFFFFu : 0u;
        const float a = acc[112] * (-1.f / DM), b = acc[114] * (-1.f / DM);
        nm0 = pack_bf16(a, a) & msk; nm1 = pack_bf16(b, b) & msk;
      }
      wg_fence();
      wgmma_rs224<0, 8, 1>(*(float(*)[112])acc, nm0, nm1, 0u, 0u, clo);
      wg_commit(); wg_wait<0>(); reg_fence(acc);
      G1HH(0);
      if (tid == 0) TR(1, 5);
      G1S(1, 0); G1S(1, 1); G1S(1, 2); G1S(1, 3); G1S(1, 4); G1S(1, 5); G1S(1, 6); G1S(1, 7); G1S(1, 8); G1S(1, 9); G1S(1, 10); G1S(1, 11);
#pragma unroll
      for (int i = 0; i < 4; i++) {
        int qq = lane >> 3, r = lane & 7, kg = 7 * j + 2 * i + (qq >> 1), c = 2 * wq + (qq & 1);
        if (kg > 55) kg = 55;
        uint32_t addr = sb + B_SA + kg * 2048 + wg * 1024 + r * 128 + ((c ^ r) << 4);
        asm volatile("ldmatrix.sync.aligned.m8n8.x4.trans.shared.b16 {%0,%1,%2,%3}, [%4];"
                     : "=r"(hres[4 * i]), "=r"(hres[4 * i + 1]), "=r"(hres[4 * i + 2]), "=r"(hres[4 * i + 3]) : "r"(addr) : "memory");
      }
      G1S(1, 12);
      g1_stage<1, 13>(acc, alo, blo, bar_full, bar_h);
      wgmma_rs224<224, 8, 1>(*(float(*)[112])acc, nm0, nm1, 0u, 0u, clo);
      wg_commit(); wg_wait<1>(); release(26 % B_NSLOT);
      wg_wait<0>(); reg_fence(acc); release(27 % B_NSLOT);
      G1HH(1);
      if (t128 == 0) mbar_arrive(bar_adead);
      if (tid == 0) TR(1, 6);
    }
    float accA[28], accB[28], sum[28];
    int nxt = 0;
#pragma unroll
    for (int i = 0; i < 28; i++) sum[i] = 0.f;
#define ISSUE(acc, I, a, FIRST) do { \
      constexpr int s_ = 28 + (I), sl_ = s_ % B_NSLOT; \
      mbar_wait(bar_full + 8 * sl_, (s_ / B_NSLOT) & 1); \
      wg_fence(); \
      wgmma_rs56<(sl_ * B_SLOT + 0 * 256) / 16, 112, !(FIRST)>(acc, (a)[0], (a)[1], (a)[2], (a)[3], blo); \
      wgmma_rs56<(sl_ * B_SLOT + 1 * 256) / 16, 112, 1>(acc, (a)[4], (a)[5], (a)[6], (a)[7], blo); \
      wgmma_rs56<(sl_ * B_SLOT + 2 * 256) / 16, 112, 1>(acc, (a)[8], (a)[9], (a)[10], (a)[11], blo); \
      wgmma_rs56<(sl_ * B_SLOT + 3 * 256) / 16, 112, 1>(acc, (a)[12], (a)[13], (a)[14], (a)[15], blo); \
      wgmma_rs56<(sl_ * B_SLOT + 4 * 256) / 16, 112, 1>(acc, (a)[16], (a)[17], (a)[18], (a)[19], blo); \
      wgmma_rs56<(sl_ * B_SLOT + 5 * 256) / 16, 112, 1>(acc, (a)[20], (a)[21], (a)[22], (a)[23], blo); \
      wgmma_rs56<(sl_ * B_SLOT + 6 * 256) / 16, 112, 1>(acc, (a)[24], (a)[25], (a)[26], (a)[27], blo); \
      wg_commit(); } while (0)
    auto rel = [&](int i) { if (i < 9) release((28 + i) % B_NSLOT); };
    auto tg = [&](uint32_t v) { return (v & 0xFFFEFFFFu) | tag; };
    auto send_lo = [&](float (&acc)[28], int cc) {
      reg_fence(acc);
      uint4* dst = g_part + (size_t)((rt * 8 + ((j + 1 + cc) & 7)) * 7 + cc) * 896 + wg * 448 + t128;
#pragma unroll
      for (int q = 0; q < 2; q++)
        st128(dst + q * 128, pack_bf16(acc[8 * q], acc[8 * q + 1]), pack_bf16(acc[8 * q + 2], acc[8 * q + 3]),
              pack_bf16(acc[8 * q + 4], acc[8 * q + 5]), tg(pack_bf16(acc[8 * q + 6], acc[8 * q + 7])));
    };
    auto send_hi = [&](float (&acc)[28], int cc) {
      uint4* dst = g_part + (size_t)((rt * 8 + ((j + 1 + cc) & 7)) * 7 + cc) * 896 + wg * 448;
      st128(dst + 256 + t128, pack_bf16(acc[16], acc[17]), pack_bf16(acc[18], acc[19]), pack_bf16(acc[20], acc[21]), tg(pack_bf16(acc[22], acc[23])));
      asm volatile("{\n.reg .b64 v;\nmov.b64 v, {%1, %2};\nst.relaxed.gpu.global.b64 [%0], v;\n}"
                   ::"l"((uint2*)(dst + 384) + t128), "r"(pack_bf16(acc[24], acc[25])), "r"(tg(pack_bf16(acc[26], acc[27]))) : "memory");
      if (lane == 0)
        asm volatile("st.relaxed.gpu.global.u32 [%0], %1;" ::"l"((uint32_t*)(g_flag + (rt * 8 + ((j + 1 + cc) & 7)) * 16 + cc * 2 + wg) + wq), "r"(ep) : "memory");
    };
    auto accum = [&]() {
      const unsigned char* src = sm + B_SA + nxt * 14336 + wg * 7168;
      uint4 a = *(const uint4*)(src + t128 * 16), b = *(const uint4*)(src + 2048 + t128 * 16), c = *(const uint4*)(src + 4096 + t128 * 16);
      uint2 d = *(const uint2*)(src + 6144 + t128 * 8);
      uint32_t in[14] = {a.x, a.y, a.z, a.w, b.x, b.y, b.z, b.w, c.x, c.y, c.z, c.w, d.x, d.y};
      int it = 0;
      while ((((in[3] ^ tag) | (in[7] ^ tag) | (in[11] ^ tag) | (in[13] ^ tag)) & 0x10000u) && ++it < 200000) {
        const uint4* gs = g_part + (size_t)((rt * 8 + j) * 7 + nxt) * 896 + wg * 448;
#pragma unroll
        for (int i = 0; i < 3; i++) ld128(gs + i * 128 + t128, in + 4 * i);
        asm volatile("{\n.reg .b64 v;\nld.relaxed.gpu.global.b64 v, [%2];\nmov.b64 {%0, %1}, v;\n}"
                     : "=r"(in[12]), "=r"(in[13]) : "l"((const uint2*)(gs + 384) + t128) : "memory");
      }
#pragma unroll
      for (int i = 0; i < 14; i++) { sum[2 * i] += bf_lo(in[i]); sum[2 * i + 1] += bf_hi(in[i]); }
      nxt++;
    };
    auto try_accum = [&]() {
      uint32_t ok;
      asm volatile("{\n.reg .pred p;\nmbarrier.test_wait.parity.shared::cta.b64 p, [%1], 0;\nselp.u32 %0, 1, 0, p;\n}"
                   : "=r"(ok) : "r"(bar_in + 8 * (wg * 7 + nxt)) : "memory");
      if (__all_sync(~0u, ok)) accum();
    };
#define CHUNK(cur, prev, CC, EXTRA) do { \
      ISSUE(cur, 2 * (CC), hh, true); wg_wait<1>(); rel(2 * (CC) - 1); send_lo(prev, (CC) - 1); \
      ISSUE(cur, 2 * (CC) + 1, hh + 28, false); send_hi(prev, (CC) - 1); EXTRA; wg_wait<1>(); rel(2 * (CC)); } while (0)
    ISSUE(accA, 0, hh, true);
    ISSUE(accA, 1, hh + 28, false); wg_wait<1>(); rel(0);
    CHUNK(accB, accA, 1, );
    if (tid == 0) TR(1, 11);
    CHUNK(accA, accB, 2, );
    if (tid == 0) TR(1, 12);
    CHUNK(accB, accA, 3, try_accum());
    if (tid == 0) TR(1, 13);
    CHUNK(accA, accB, 4, try_accum());
    if (tid == 0) TR(1, 14);
    CHUNK(accB, accA, 5, try_accum());
    if (tid == 0) TR(1, 16);
    CHUNK(accA, accB, 6, try_accum());
    if (tid == 0) TR(1, 17);
    CHUNK(accB, accA, 7, try_accum());
    if (tid == 0) TR(1, 7);
#pragma unroll 1
    while (nxt < 7) { mbar_wait(bar_in + 8 * (wg * 7 + nxt), 0); accum(); }
    wg_wait<0>();
    reg_fence(accB);
    if (tid == 0) TR(1, 9);
    mbar_wait(bar_stat, 0);
    const float r20 = *(const float*)(sm + B_STAT + (wg * 64 + wq * 16 + g) * 4), r21 = *(const float*)(sm + B_STAT + (wg * 64 + wq * 16 + g + 8) * 4);
    const int row = rt * 128 + wg * 64 + wq * 16 + g;
    uint32_t* o0 = (uint32_t*)(out + (size_t)row * DM + 56 * j + 2 * t);
    uint32_t* o1 = o0 + 8 * DM / 2;
#pragma unroll
    for (int i = 0; i < 7; i++) {
      o0[4 * i] = hadd2_bf(hres[2 * i], pack_bf16((sum[4 * i] + accB[4 * i]) * r20, (sum[4 * i + 1] + accB[4 * i + 1]) * r20));
      o1[4 * i] = hadd2_bf(hres[2 * i + 1], pack_bf16((sum[4 * i + 2] + accB[4 * i + 2]) * r21, (sum[4 * i + 3] + accB[4 * i + 3]) * r21));
    }
    if (tid == 0) TR(1, 10);
    if (tid == 128) TR(1, 15);

  }
}

extern "C" void kernel_launch(void* const* d_in, const int* in_sizes, int n_in, void* d_out, int out_size) {
  const __nv_bfloat16* x = (const __nv_bfloat16*)d_in[0];
  const __nv_bfloat16 *are = (const __nv_bfloat16*)d_in[1], *aim = (const __nv_bfloat16*)d_in[2], *bre = (const __nv_bfloat16*)d_in[3],
                      *bim = (const __nv_bfloat16*)d_in[4], *cre = (const __nv_bfloat16*)d_in[5], *cim = (const __nv_bfloat16*)d_in[6],
                      *logdt = (const __nv_bfloat16*)d_in[7], *dskip = (const __nv_bfloat16*)d_in[8];
  const __nv_bfloat16 *wg = (const __nv_bfloat16*)d_in[10], *wu = (const __nv_bfloat16*)d_in[11], *wd = (const __nv_bfloat16*)d_in[12];

  static bool init = false;
  if (!init) {
    init = true;
    cudaFuncSetAttribute(k_ffn, cudaFuncAttributeMaxDynamicSharedMemorySize, B_SMEM);
  }
  cudaStream_t st = cudaStreamPerThread;
  k_ln1<<<256, 256, 0, st>>>(x);
  k_kgen<<<DM, 512, 0, st>>>(are, aim, bre, bim, cre, cim, logdt);
  k_conv<<<DM, 512, 0, st>>>(x, dskip);
  k_colsum<<<2 * FF / 128, 128, 0, st>>>(wg, wu);
  k_pack<<<3 * 100352 / 256, 256, 0, st>>>((const uint4*)wg, (const uint4*)wu, (const uint4*)wd);
  k_ffn<<<128, 384, B_SMEM, st>>>((__nv_bfloat16*)d_out);
}
```

```cpp
#include <cuda_runtime.h>
#include <cuda_bf16.h>
#include <stdint.h>

constexpr int LSEQ = 2048, DM = 448;

__device__ uint4    g_himg[16 * 114688 / 16];
__device__ uint4    g_cimg[8 * 2 * 224];
__device__ uint32_t g_stat2[LSEQ];
__device__ uint4    g_part[128 * 7 * 896];
__device__ uint4    g_wimg[8 * 602112 / 16];
__device__ unsigned g_epochA, g_epochB;
__device__ uint32_t g_stat1[LSEQ];
__device__ uint4    g_flag[128 * 16];

#define TR(k, i) do {} while (0)
__device__ __forceinline__ uint32_t s2u(const void* p) { return (uint32_t)__cvta_generic_to_shared(p); }
__device__ __forceinline__ void mbar_init(uint32_t b, int c) { asm volatile("mbarrier.init.shared::cta.b64 [%0], %1;" ::"r"(b), "r"(c)); }
__device__ __forceinline__ void mbar_expect(uint32_t b, int bytes) { asm volatile("mbarrier.arrive.expect_tx.shared::cta.b64 _, [%0], %1;" ::"r"(b), "r"(bytes) : "memory"); }
__device__ __forceinline__ void mbar_arrive(uint32_t b) { asm volatile("mbarrier.arrive.shared::cta.b64 _, [%0];" ::"r"(b) : "memory"); }
__device__ __forceinline__ void mbar_wait(uint32_t b, int ph) {
  asm volatile("{\n.reg .pred p;\n.reg .b32 n;\nmov.b32 n, 0;\nLW:\nmbarrier.try_wait.parity.shared::cta.b64 p, [%0], %1;\n@p bra LD;\n"
               "add.u32 n, n, 1;\nsetp.lt.u32 p, n, 4000000;\n@p bra LW;\ntrap;\nLD:\n}" ::"r"(b), "r"(ph) : "memory");
}
__device__ __forceinline__ uint64_t mkdesc(uint32_t addr, uint32_t lbo, uint32_t sbo, uint32_t sw) {
  return (uint64_t)((addr & 0x3FFFF) >> 4) | ((uint64_t)((lbo >> 4) & 0x3FFF) << 16) | ((uint64_t)((sbo >> 4) & 0x3FFF) << 32) | ((uint64_t)sw << 62);
}
__device__ __forceinline__ void wg_fence() { asm volatile("wgmma.fence.sync.aligned;" ::: "memory"); }
__device__ __forceinline__ void wg_commit() { asm volatile("wgmma.commit_group.sync.aligned;" ::: "memory"); }
template <int N> __device__ __forceinline__ void wg_wait() { asm volatile("wgmma.wait_group.sync.aligned %0;" ::"n"(N) : "memory"); }
template <int N> __device__ __forceinline__ void reg_fence(float (&a)[N]) {
#pragma unroll
  for (int i = 0; i < N; i++) asm volatile("" : "+f"(a[i])::"memory");
}
__device__ __forceinline__ uint32_t pack_bf16(float lo, float hi) {
  uint32_t r; asm("cvt.rn.bf16x2.f32 %0, %1, %2;" : "=r"(r) : "f"(hi), "f"(lo)); return r;
}
__device__ __forceinline__ float bf_lo(uint32_t v) { return __uint_as_float(v << 16); }
__device__ __forceinline__ float bf_hi(uint32_t v) { return __uint_as_float(v & 0xFFFF0000u); }
__device__ __forceinline__ float rbf(float x) { return __bfloat162float(__float2bfloat16_rn(x)); }
__device__ __forceinline__ uint32_t hmul2_bf(uint32_t a, uint32_t b) { uint32_t r; asm("mul.rn.bf16x2 %0, %1, %2;" : "=r"(r) : "r"(a), "r"(b)); return r; }
__device__ __forceinline__ uint32_t hadd2_bf(uint32_t a, uint32_t b) { uint32_t r; asm("add.rn.bf16x2 %0, %1, %2;" : "=r"(r) : "r"(a), "r"(b)); return r; }
__device__ __forceinline__ void bulk_ld(uint32_t dst, const void* src, int bytes, uint32_t bar) {
  asm volatile("cp.async.bulk.shared::cluster.global.mbarrier::complete_tx::bytes [%0], [%1], %2, [%3];"
               ::"r"(dst), "l"(src), "r"(bytes), "r"(bar) : "memory");
}

__device__ __forceinline__ void bulk_ld_mc(uint32_t dst, const void* src, int bytes, uint32_t bar) {
  asm volatile("cp.async.bulk.shared::cluster.global.mbarrier::complete_tx::bytes.multicast::cluster [%0], [%1], %2, [%3], %4;"
               ::"r"(dst), "l"(src), "r"(bytes), "r"(bar), "h"((uint16_t)3) : "memory");
}
template <int AOFF, uint32_t AHI, int BOFF, uint32_t BHI, int ACC>
__device__ __forceinline__ void wgmma_ss224(float (&d)[112], uint32_t alo, uint32_t blo) {
  asm volatile("{\n.reg .pred p;\n.reg .b32 la, lb;\n.reg .b64 ad, bd;\nsetp.ne.b32 p, %118, 0;\n"
    "add.u32 la, %112, %114;\nmov.b64 ad, {la, %115};\nadd.u32 lb, %113, %116;\nmov.b64 bd, {lb, %117};\n"
    "wgmma.mma_async.sync.aligned.m64n224k16.f32.bf16.bf16 {%0,%1,%2,%3,%4,%5,%6,%7,%8,%9,%10,%11,%12,%13,%14,%15,%16,%17,%18,%19,%20,%21,%22,%23,%24,%25,%26,%27,%28,%29,%30,%31,%32,%33,%34,%35,%36,%37,%38,%39,%40,%41,%42,%43,%44,%45,%46,%47,%48,%49,%50,%51,%52,%53,%54,%55,%56,%57,%58,%59,%60,%61,%62,%63,%64,%65,%66,%67,%68,%69,%70,%71,%72,%73,%74,%75,%76,%77,%78,%79,%80,%81,%82,%83,%84,%85,%86,%87,%88,%89,%90,%91,%92,%93,%94,%95,%96,%97,%98,%99,%100,%101,%102,%103,%104,%105,%106,%107,%108,%109,%110,%111}, ad, bd, p, 1, 1, 1, 1;\n}\n"
    : "+f"(d[0]),"+f"(d[1]),"+f"(d[2]),"+f"(d[3]),"+f"(d[4]),"+f"(d[5]),"+f"(d[6]),"+f"(d[7]),"+f"(d[8]),"+f"(d[9]),"+f"(d[10]),"+f"(d[11]),"+f"(d[12]),"+f"(d[13]),"+f"(d[14]),"+f"(d[15]),"+f"(d[16]),"+f"(d[17]),"+f"(d[18]),"+f"(d[19]),"+f"(d[20]),"+f"(d[21]),"+f"(d[22]),"+f"(d[23]),"+f"(d[24]),"+f"(d[25]),"+f"(d[26]),"+f"(d[27]),"+f"(d[28]),"+f"(d[29]),"+f"(d[30]),"+f"(d[31]),"+f"(d[32]),"+f"(d[33]),"+f"(d[34]),"+f"(d[35]),"+f"(d[36]),"+f"(d[37]),"+f"(d[38]),"+f"(d[39]),"+f"(d[40]),"+f"(d[41]),"+f"(d[42]),"+f"(d[43]),"+f"(d[44]),"+f"(d[45]),"+f"(d[46]),"+f"(d[47]),"+f"(d[48]),"+f"(d[49]),"+f"(d[50]),"+f"(d[51]),"+f"(d[52]),"+f"(d[53]),"+f"(d[54]),"+f"(d[55]),"+f"(d[56]),"+f"(d[57]),"+f"(d[58]),"+f"(d[59]),"+f"(d[60]),"+f"(d[61]),"+f"(d[62]),"+f"(d[63]),"+f"(d[64]),"+f"(d[65]),"+f"(d[66]),"+f"(d[67]),"+f"(d[68]),"+f"(d[69]),"+f"(d[70]),"+f"(d[71]),"+f"(d[72]),"+f"(d[73]),"+f"(d[74]),"+f"(d[75]),"+f"(d[76]),"+f"(d[77]),"+f"(d[78]),"+f"(d[79]),"+f"(d[80]),"+f"(d[81]),"+f"(d[82]),"+f"(d[83]),"+f"(d[84]),"+f"(d[85]),"+f"(d[86]),"+f"(d[87]),"+f"(d[88]),"+f"(d[89]),"+f"(d[90]),"+f"(d[91]),"+f"(d[92]),"+f"(d[93]),"+f"(d[94]),"+f"(d[95]),"+f"(d[96]),"+f"(d[97]),"+f"(d[98]),"+f"(d[99]),"+f"(d[100]),"+f"(d[101]),"+f"(d[102]),"+f"(d[103]),"+f"(d[104]),"+f"(d[105]),"+f"(d[106]),"+f"(d[107]),"+f"(d[108]),"+f"(d[109]),"+f"(d[110]),"+f"(d[111])
    : "r"(alo), "r"(blo), "n"(AOFF), "n"(AHI), "n"(BOFF), "n"(BHI), "n"(ACC));
}
template <int AOFF, uint32_t AHI, int BOFF, uint32_t BHI, int ACC>
__device__ __forceinline__ void wgmma_ss232(float (&d)[116], uint32_t alo, uint32_t blo) {
  asm volatile("{\n.reg .pred p;\n.reg .b32 la, lb;\n.reg .b64 ad, bd;\nsetp.ne.b32 p, %122, 0;\n"
    "add.u32 la, %116, %118;\nmov.b64 ad, {la, %119};\nadd.u32 lb, %117, %120;\nmov.b64 bd, {lb, %121};\n"
    "wgmma.mma_async.sync.aligned.m64n232k16.f32.bf16.bf16 {%0,%1,%2,%3,%4,%5,%6,%7,%8,%9,%10,%11,%12,%13,%14,%15,%16,%17,%18,%19,%20,%21,%22,%23,%24,%25,%26,%27,%28,%29,%30,%31,%32,%33,%34,%35,%36,%37,%38,%39,%40,%41,%42,%43,%44,%45,%46,%47,%48,%49,%50,%51,%52,%53,%54,%55,%56,%57,%58,%59,%60,%61,%62,%63,%64,%65,%66,%67,%68,%69,%70,%71,%72,%73,%74,%75,%76,%77,%78,%79,%80,%81,%82,%83,%84,%85,%86,%87,%88,%89,%90,%91,%92,%93,%94,%95,%96,%97,%98,%99,%100,%101,%102,%103,%104,%105,%106,%107,%108,%109,%110,%111,%112,%113,%114,%115}, ad, bd, p, 1, 1, 1, 1;\n}\n"
    : "+f"(d[0]),"+f"(d[1]),"+f"(d[2]),"+f"(d[3]),"+f"(d[4]),"+f"(d[5]),"+f"(d[6]),"+f"(d[7]),"+f"(d[8]),"+f"(d[9]),"+f"(d[10]),"+f"(d[11]),"+f"(d[12]),"+f"(d[13]),"+f"(d[14]),"+f"(d[15]),"+f"(d[16]),"+f"(d[17]),"+f"(d[18]),"+f"(d[19]),"+f"(d[20]),"+f"(d[21]),"+f"(d[22]),"+f"(d[23]),"+f"(d[24]),"+f"(d[25]),"+f"(d[26]),"+f"(d[27]),"+f"(d[28]),"+f"(d[29]),"+f"(d[30]),"+f"(d[31]),"+f"(d[32]),"+f"(d[33]),"+f"(d[34]),"+f"(d[35]),"+f"(d[36]),"+f"(d[37]),"+f"(d[38]),"+f"(d[39]),"+f"(d[40]),"+f"(d[41]),"+f"(d[42]),"+f"(d[43]),"+f"(d[44]),"+f"(d[45]),"+f"(d[46]),"+f"(d[47]),"+f"(d[48]),"+f"(d[49]),"+f"(d[50]),"+f"(d[51]),"+f"(d[52]),"+f"(d[53]),"+f"(d[54]),"+f"(d[55]),"+f"(d[56]),"+f"(d[57]),"+f"(d[58]),"+f"(d[59]),"+f"(d[60]),"+f"(d[61]),"+f"(d[62]),"+f"(d[63]),"+f"(d[64]),"+f"(d[65]),"+f"(d[66]),"+f"(d[67]),"+f"(d[68]),"+f"(d[69]),"+f"(d[70]),"+f"(d[71]),"+f"(d[72]),"+f"(d[73]),"+f"(d[74]),"+f"(d[75]),"+f"(d[76]),"+f"(d[77]),"+f"(d[78]),"+f"(d[79]),"+f"(d[80]),"+f"(d[81]),"+f"(d[82]),"+f"(d[83]),"+f"(d[84]),"+f"(d[85]),"+f"(d[86]),"+f"(d[87]),"+f"(d[88]),"+f"(d[89]),"+f"(d[90]),"+f"(d[91]),"+f"(d[92]),"+f"(d[93]),"+f"(d[94]),"+f"(d[95]),"+f"(d[96]),"+f"(d[97]),"+f"(d[98]),"+f"(d[99]),"+f"(d[100]),"+f"(d[101]),"+f"(d[102]),"+f"(d[103]),"+f"(d[104]),"+f"(d[105]),"+f"(d[106]),"+f"(d[107]),"+f"(d[108]),"+f"(d[109]),"+f"(d[110]),"+f"(d[111]),"+f"(d[112]),"+f"(d[113]),"+f"(d[114]),"+f"(d[115])
    : "r"(alo), "r"(blo), "n"(AOFF), "n"(AHI), "n"(BOFF), "n"(BHI), "n"(ACC));
}
template <int OFF, uint32_t BHI, int ACC>
__device__ __forceinline__ void wgmma_rs224(float (&d)[112], uint32_t a0, uint32_t a1, uint32_t a2, uint32_t a3, uint32_t blo) {
  asm volatile("{\n.reg .pred p;\n.reg .b32 l;\n.reg .b64 bd;\nsetp.ne.b32 p, %119, 0;\nadd.u32 l, %116, %117;\nmov.b64 bd, {l, %118};\n"
    "wgmma.mma_async.sync.aligned.m64n224k16.f32.bf16.bf16 {%0,%1,%2,%3,%4,%5,%6,%7,%8,%9,%10,%11,%12,%13,%14,%15,%16,%17,%18,%19,%20,%21,%22,%23,%24,%25,%26,%27,%28,%29,%30,%31,%32,%33,%34,%35,%36,%37,%38,%39,%40,%41,%42,%43,%44,%45,%46,%47,%48,%49,%50,%51,%52,%53,%54,%55,%56,%57,%58,%59,%60,%61,%62,%63,%64,%65,%66,%67,%68,%69,%70,%71,%72,%73,%74,%75,%76,%77,%78,%79,%80,%81,%82,%83,%84,%85,%86,%87,%88,%89,%90,%91,%92,%93,%94,%95,%96,%97,%98,%99,%100,%101,%102,%103,%104,%105,%106,%107,%108,%109,%110,%111}, {%112,%113,%114,%115}, bd, p, 1, 1, 1;\n}\n"
    : "+f"(d[0]),"+f"(d[1]),"+f"(d[2]),"+f"(d[3]),"+f"(d[4]),"+f"(d[5]),"+f"(d[6]),"+f"(d[7]),"+f"(d[8]),"+f"(d[9]),"+f"(d[10]),"+f"(d[11]),"+f"(d[12]),"+f"(d[13]),"+f"(d[14]),"+f"(d[15]),"+f"(d[16]),"+f"(d[17]),"+f"(d[18]),"+f"(d[19]),"+f"(d[20]),"+f"(d[21]),"+f"(d[22]),"+f"(d[23]),"+f"(d[24]),"+f"(d[25]),"+f"(d[26]),"+f"(d[27]),"+f"(d[28]),"+f"(d[29]),"+f"(d[30]),"+f"(d[31]),"+f"(d[32]),"+f"(d[33]),"+f"(d[34]),"+f"(d[35]),"+f"(d[36]),"+f"(d[37]),"+f"(d[38]),"+f"(d[39]),"+f"(d[40]),"+f"(d[41]),"+f"(d[42]),"+f"(d[43]),"+f"(d[44]),"+f"(d[45]),"+f"(d[46]),"+f"(d[47]),"+f"(d[48]),"+f"(d[49]),"+f"(d[50]),"+f"(d[51]),"+f"(d[52]),"+f"(d[53]),"+f"(d[54]),"+f"(d[55]),"+f"(d[56]),"+f"(d[57]),"+f"(d[58]),"+f"(d[59]),"+f"(d[60]),"+f"(d[61]),"+f"(d[62]),"+f"(d[63]),"+f"(d[64]),"+f"(d[65]),"+f"(d[66]),"+f"(d[67]),"+f"(d[68]),"+f"(d[69]),"+f"(d[70]),"+f"(d[71]),"+f"(d[72]),"+f"(d[73]),"+f"(d[74]),"+f"(d[75]),"+f"(d[76]),"+f"(d[77]),"+f"(d[78]),"+f"(d[79]),"+f"(d[80]),"+f"(d[81]),"+f"(d[82]),"+f"(d[83]),"+f"(d[84]),"+f"(d[85]),"+f"(d[86]),"+f"(d[87]),"+f"(d[88]),"+f"(d[89]),"+f"(d[90]),"+f"(d[91]),"+f"(d[92]),"+f"(d[93]),"+f"(d[94]),"+f"(d[95]),"+f"(d[96]),"+f"(d[97]),"+f"(d[98]),"+f"(d[99]),"+f"(d[100]),"+f"(d[101]),"+f"(d[102]),"+f"(d[103]),"+f"(d[104]),"+f"(d[105]),"+f"(d[106]),"+f"(d[107]),"+f"(d[108]),"+f"(d[109]),"+f"(d[110]),"+f"(d[111])
    : "r"(a0), "r"(a1), "r"(a2), "r"(a3), "r"(blo), "n"(OFF), "n"(BHI), "n"(ACC));
}
template <int OFF, uint32_t BHI, int ACC>
__device__ __forceinline__ void wgmma_rs56(float (&d)[28], uint32_t a0, uint32_t a1, uint32_t a2, uint32_t a3, uint32_t blo) {
  asm volatile("{\n.reg .pred p;\n.reg .b32 l;\n.reg .b64 bd;\nsetp.ne.b32 p, %35, 0;\nadd.u32 l, %32, %33;\nmov.b64 bd, {l, %34};\n"
    "wgmma.mma_async.sync.aligned.m64n56k16.f32.bf16.bf16 {%0,%1,%2,%3,%4,%5,%6,%7,%8,%9,%10,%11,%12,%13,%14,%15,%16,%17,%18,%19,%20,%21,%22,%23,%24,%25,%26,%27}, {%28,%29,%30,%31}, bd, p, 1, 1, 1;\n}\n"
    : "+f"(d[0]),"+f"(d[1]),"+f"(d[2]),"+f"(d[3]),"+f"(d[4]),"+f"(d[5]),"+f"(d[6]),"+f"(d[7]),"+f"(d[8]),"+f"(d[9]),"+f"(d[10]),"+f"(d[11]),"+f"(d[12]),"+f"(d[13]),"+f"(d[14]),"+f"(d[15]),"+f"(d[16]),"+f"(d[17]),"+f"(d[18]),"+f"(d[19]),"+f"(d[20]),"+f"(d[21]),"+f"(d[22]),"+f"(d[23]),"+f"(d[24]),"+f"(d[25]),"+f"(d[26]),"+f"(d[27])
    : "r"(a0), "r"(a1), "r"(a2), "r"(a3), "r"(blo), "n"(OFF), "n"(BHI), "n"(ACC));
}

__device__ __forceinline__ void st128(uint4* p, uint32_t a, uint32_t b, uint32_t c, uint32_t d) {
  asm volatile("{\n.reg .b128 v;\n.reg .b64 lo, hi;\nmov.b64 lo, {%1, %2};\nmov.b64 hi, {%3, %4};\nmov.b128 v, {lo, hi};\n"
               "st.relaxed.gpu.global.b128 [%0], v;\n}" ::"l"(p), "r"(a), "r"(b), "r"(c), "r"(d) : "memory");
}
__device__ __forceinline__ void ld128(const uint4* p, uint32_t* r) {
  asm volatile("{\n.reg .b128 v;\n.reg .b64 lo, hi;\nld.relaxed.gpu.global.b128 v, [%4];\nmov.b128 {lo, hi}, v;\n"
               "mov.b64 {%0, %1}, lo;\nmov.b64 {%2, %3}, hi;\n}" : "=r"(r[0]), "=r"(r[1]), "=r"(r[2]), "=r"(r[3]) : "l"(p) : "memory");
}

template <int OFF, uint32_t BHI, int ACC>
__device__ __forceinline__ void wgmma_rs32(float (&d)[16], uint32_t a0, uint32_t a1, uint32_t a2, uint32_t a3, uint32_t blo) {
  asm volatile("{\n.reg .pred p;\n.reg .b32 l;\n.reg .b64 bd;\nsetp.ne.b32 p, %23, 0;\nadd.u32 l, %20, %21;\nmov.b64 bd, {l, %22};\n"
    "wgmma.mma_async.sync.aligned.m64n32k16.f32.bf16.bf16 {%0,%1,%2,%3,%4,%5,%6,%7,%8,%9,%10,%11,%12,%13,%14,%15}, {%16,%17,%18,%19}, bd, p, 1, 1, 0;\n}\n"
    : "+f"(d[0]),"+f"(d[1]),"+f"(d[2]),"+f"(d[3]),"+f"(d[4]),"+f"(d[5]),"+f"(d[6]),"+f"(d[7]),"+f"(d[8]),"+f"(d[9]),"+f"(d[10]),"+f"(d[11]),"+f"(d[12]),"+f"(d[13]),"+f"(d[14]),"+f"(d[15])
    : "r"(a0), "r"(a1), "r"(a2), "r"(a3), "r"(blo), "n"(OFF), "n"(BHI), "n"(ACC));
}
template <int OFF, uint32_t BHI, int ACC>
__device__ __forceinline__ void wgmma_rs24(float (&d)[12], uint32_t a0, uint32_t a1, uint32_t a2, uint32_t a3, uint32_t blo) {
  asm volatile("{\n.reg .pred p;\n.reg .b32 l;\n.reg .b64 bd;\nsetp.ne.b32 p, %19, 0;\nadd.u32 l, %16, %17;\nmov.b64 bd, {l, %18};\n"
    "wgmma.mma_async.sync.aligned.m64n24k16.f32.bf16.bf16 {%0,%1,%2,%3,%4,%5,%6,%7,%8,%9,%10,%11}, {%12,%13,%14,%15}, bd, p, 1, 1, 1;\n}\n"
    : "+f"(d[0]),"+f"(d[1]),"+f"(d[2]),"+f"(d[3]),"+f"(d[4]),"+f"(d[5]),"+f"(d[6]),"+f"(d[7]),"+f"(d[8]),"+f"(d[9]),"+f"(d[10]),"+f"(d[11])
    : "r"(a0), "r"(a1), "r"(a2), "r"(a3), "r"(blo), "n"(OFF), "n"(BHI), "n"(ACC));
}
template <int OFF, uint32_t BHI, int ACC>
__device__ __forceinline__ void wgmma_rs16(float (&d)[8], uint32_t a0, uint32_t a1, uint32_t a2, uint32_t a3, uint32_t blo) {
  asm volatile("{\n.reg .pred p;\n.reg .b32 l;\n.reg .b64 bd;\nsetp.ne.b32 p, %15, 0;\nadd.u32 l, %12, %13;\nmov.b64 bd, {l, %14};\n"
    "wgmma.mma_async.sync.aligned.m64n16k16.f32.bf16.bf16 {%0,%1,%2,%3,%4,%5,%6,%7}, {%8,%9,%10,%11}, bd, p, 1, 1, 1;\n}\n"
    : "+f"(d[0]),"+f"(d[1]),"+f"(d[2]),"+f"(d[3]),"+f"(d[4]),"+f"(d[5]),"+f"(d[6]),"+f"(d[7])
    : "r"(a0), "r"(a1), "r"(a2), "r"(a3), "r"(blo), "n"(OFF), "n"(BHI), "n"(ACC));
}

constexpr int A_UB = 0;
constexpr int A_W5 = 5248;
constexpr int A_W3 = A_W5 + 4112;
constexpr int A_W9 = A_W3 + 4112;
constexpr int A_W7 = A_W9 + 2048;
constexpr int A_V  = A_W7 + 2048;
constexpr int A_R1 = A_V + 2048;
constexpr int A_R2A = A_R1 + 2624, A_R2B = A_R2A + 768, A_R3A = A_R2B + 768, A_R3B = A_R3A + 528;
constexpr int A_K1024 = A_R3B + 528;
constexpr int A_ZEND = A_K1024 + 16;
constexpr int A_STG = A_ZEND;
constexpr int A_Y2 = A_STG, A_Y3 = A_Y2 + 6528, A_YB = A_Y3 + 4352;
constexpr int A_CH = A_STG + 4 * 6528;
constexpr int A_SMEM = 4 * A_CH;
static_assert(A_ZEND % 16 == 0 && A_CH % 16 == 0 && A_YB + 4096 <= A_CH, "layout");

struct cf { float x, y; };
__device__ __forceinline__ cf cmul(cf a, cf b) { cf r; r.x = fmaf(a.x, b.x, -a.y * b.y); r.y = fmaf(a.x, b.y, a.y * b.x); return r; }
__device__ __forceinline__ cf cexp_l(float lr, float li, float l) {
  float mag; asm("ex2.approx.ftz.f32 %0, %1;" : "=f"(mag) : "f"((lr * l) * 1.4426950408889634f));
  const float th = li * l;
  const float k = (fmaf(th, 0.15915494f, 12582912.f)) - 12582912.f;
  float ph = fmaf(th, 0.15915494f, -k);
  ph = fmaf(th, 6.4206383e-9f, ph) * 6.2831853f;
  cf r; r.x = mag * __cosf(ph); r.y = mag * __sinf(ph); return r;
}
__device__ __forceinline__ void sts16(uint32_t a, uint32_t v) { asm volatile("st.shared.u16 [%0], %1;" ::"r"(a), "h"((uint16_t)v) : "memory"); }
__device__ __forceinline__ void sts32(uint32_t a, uint32_t v) { asm volatile("st.shared.u32 [%0], %1;" ::"r"(a), "r"(v) : "memory"); }
__device__ __forceinline__ void sts64(uint32_t a, uint32_t v0, uint32_t v1) { asm volatile("st.shared.v2.u32 [%0], {%1, %2};" ::"r"(a), "r"(v0), "r"(v1) : "memory"); }
__device__ __forceinline__ void sts128(uint32_t a, uint32_t v0, uint32_t v1, uint32_t v2, uint32_t v3) {
  asm volatile("st.shared.v4.u32 [%0], {%1, %2, %3, %4};" ::"r"(a), "r"(v0), "r"(v1), "r"(v2), "r"(v3) : "memory");
}
__device__ __forceinline__ uint32_t lds32(uint32_t a) { uint32_t v; asm volatile("ld.shared.u32 %0, [%1];" : "=r"(v) : "r"(a) : "memory"); return v; }
__device__ __forceinline__ uint4 lds128(uint32_t a) {
  uint4 v; asm volatile("ld.shared.v4.u32 {%0, %1, %2, %3}, [%4];" : "=r"(v.x), "=r"(v.y), "=r"(v.z), "=r"(v.w) : "r"(a) : "memory"); return v;
}
__device__ __forceinline__ void ldsm4(uint32_t* r, uint32_t a) {
  asm volatile("ldmatrix.sync.aligned.m8n8.x4.shared.b16 {%0,%1,%2,%3}, [%4];" : "=r"(r[0]), "=r"(r[1]), "=r"(r[2]), "=r"(r[3]) : "r"(a) : "memory");
}
__device__ __forceinline__ void mma16816(float* d, const uint32_t* a, uint32_t b0, uint32_t b1) {
  asm volatile("mma.sync.aligned.m16n8k16.row.col.f32.bf16.bf16.f32 {%0,%1,%2,%3}, {%4,%5,%6,%7}, {%8,%9}, {%0,%1,%2,%3};"
               : "+f"(d[0]), "+f"(d[1]), "+f"(d[2]), "+f"(d[3]) : "r"(a[0]), "r"(a[1]), "r"(a[2]), "r"(a[3]), "r"(b0), "r"(b1));
}
__device__ __forceinline__ uint32_t hsub2_bf(uint32_t a, uint32_t b) { uint32_t r; asm("sub.rn.bf16x2 %0, %1, %2;" : "=r"(r) : "r"(a), "r"(b)); return r; }
__device__ __forceinline__ void bar_sync(int id, int n) { asm volatile("bar.sync %0, %1;" ::"r"(id), "r"(n) : "memory"); }

template <int S> struct F1B { static constexpr int c = S / 4 + ((S & 3) == 3 ? 0 : 0), cc = (16 * S) / 64, ks = (64 * cc - (16 * S - 48)) / 16, off = (2 * ks * 656 + (9 - cc) * 16) / 16; };

template <int NS>
__device__ __forceinline__ void load_quads(uint32_t* q, uint32_t addr) {
#pragma unroll
  for (int i = 0; i < NS; i++) {
    q[4 * i] = lds32(addr + i * 64); q[4 * i + 1] = lds32(addr + i * 64 + 32);
    q[4 * i + 2] = i ? q[4 * i - 3] : lds32(addr - 32);
    q[4 * i + 3] = q[4 * i];
  }
#pragma unroll
  for (int i = 0; i < 4 * NS; i++) asm volatile("" : "+r"(q[i]));
}
template <int S0, int NS>
__device__ __forceinline__ void f1_steps(float (&acc)[16], const uint32_t* a, uint32_t blo) {
  if constexpr (NS > 0) {
    wgmma_rs32<F1B<S0>::off, 8, S0 != 0>(acc, a[0], a[1], a[2], a[3], blo);
    f1_steps<S0 + 1, NS - 1>(acc, a + 4, blo);
  }
}
template <int S0, int NS, int BASE, int FIRST>
__device__ __forceinline__ void s2_steps(float (&acc)[12], const uint32_t* a, uint32_t blo) {
  if constexpr (NS > 0) {
    wgmma_rs24<BASE / 16 + (112 - 16 * S0), 64, !(FIRST && S0 == 0)>(acc, a[0], a[1], a[2], a[3], blo);
    s2_steps<S0 + 1, NS - 1, BASE, FIRST>(acc, a + 4, blo);
  }
}
template <int S0, int NS, int BASE, int FIRST>
__device__ __forceinline__ void s3_steps(float (&acc)[8], const uint32_t* a, uint32_t blo) {
  if constexpr (NS > 0) {
    wgmma_rs16<BASE / 16 + (48 - 16 * S0), 64, !(FIRST && S0 == 0)>(acc, a[0], a[1], a[2], a[3], blo);
    s3_steps<S0 + 1, NS - 1, BASE, FIRST>(acc, a + 4, blo);
  }
}

__global__ void __launch_bounds__(512, 1)
k_front(const __nv_bfloat16* __restrict__ x, const uint32_t* __restrict__ are, const uint32_t* __restrict__ aim,
        const uint32_t* __restrict__ bre, const uint32_t* __restrict__ bim, const uint32_t* __restrict__ cre,
        const uint32_t* __restrict__ cim, const __nv_bfloat16* __restrict__ logdt, const __nv_bfloat16* __restrict__ dskip,
        const uint4* __restrict__ wgate, const uint4* __restrict__ wup, const uint4* __restrict__ wdown) {
  extern __shared__ __align__(1024) unsigned char sm[];
  const uint32_t sb = s2u(sm);
  const int tid = threadIdx.x, wg = tid >> 7, warp = tid >> 5, lane = tid & 31, wq = warp & 3, t128 = tid & 127;
  const int blk = blockIdx.x;
  const bool conv = blk < 112;
  if (tid == 0) TR(0, 0);

  uint2 xr[4];
  {
    const uint2* p = (const uint2*)(x + (size_t)(blk * 16 + warp) * DM);
    xr[0] = __ldg(p + lane); xr[1] = __ldg(p + 32 + lane); xr[2] = __ldg(p + 64 + lane);
    xr[3] = lane < 16 ? __ldg(p + 96 + lane) : make_uint2(0, 0);
  }
  const uint32_t ep = __ldcg(&g_epochA) + 1u;
  const int ch = blk * 4 + wg;
  uint32_t prm[6]; float ldt = 0.f;
  uint32_t xc[8];
  uint4 wv[4];
  const int tau = tid & 255, cp = tid >> 8;
  if (conv) {
    const int i = ch * 128 + t128;
    prm[0] = __ldg(are + i); prm[1] = __ldg(aim + i); prm[2] = __ldg(bre + i); prm[3] = __ldg(bim + i); prm[4] = __ldg(cre + i); prm[5] = __ldg(cim + i);
    ldt = __bfloat162float(logdt[ch]);
    const uint32_t* xp = (const uint32_t*)(x + (size_t)tau * 8 * DM + blk * 4 + cp * 2);
#pragma unroll
    for (int i2 = 0; i2 < 8; i2++) xc[i2] = __ldg(xp + i2 * (DM / 2));
    const uint4* wsrc = (blk < 56 ? wgate : wup) + (blk % 56) * 4 + (lane & 3) + (size_t)(warp * 8 + (lane >> 2)) * 224;
#pragma unroll
    for (int i2 = 0; i2 < 4; i2++) if (i2 < 3 || warp < 8) wv[i2] = __ldg(wsrc + (size_t)i2 * 128 * 224);
    for (int i2 = t128; i2 < A_ZEND / 16; i2 += 128) sts128(sb + wg * A_CH + i2 * 16, 0, 0, 0, 0);
  }
  {
    float v[16];
#pragma unroll
    for (int i = 0; i < 4; i++) { v[4 * i] = bf_lo(xr[i].x); v[4 * i + 1] = bf_hi(xr[i].x); v[4 * i + 2] = bf_lo(xr[i].y); v[4 * i + 3] = bf_hi(xr[i].y); }
    float s = 0.f;
#pragma unroll
    for (int i = 0; i < 16; i++) s += v[i];
#pragma unroll
    for (int o = 16; o; o >>= 1) s += __shfl_xor_sync(~0u, s, o);
    const float mean = s * (1.f / DM);
    float q = 0.f;
#pragma unroll
    for (int i = 0; i < 16; i++) { float d = v[i] - mean; if (i < 12 || lane < 16) q = fmaf(d, d, q); }
#pragma unroll
    for (int o = 16; o; o >>= 1) q += __shfl_xor_sync(~0u, q, o);
    if (lane == 0) {
      const float sd = __fsqrt_rn(rbf(rbf(q * (1.f / DM)) + 1e-5f));
      const uint32_t w = (pack_bf16(sd, mean) & 0xFFFF7FFFu) | ((ep & 1u) << 15);
      asm volatile("st.relaxed.gpu.global.u32 [%0], %1;" ::"l"(g_stat1 + blk * 16 + warp), "r"(w) : "memory");
    }
  }
  if (tid == 0) TR(0, 1);

  if (!conv) {
    const int a = blk - 112, mat = a >> 3, j = a & 7;
    if (a == 0 && tid == 0) g_epochB = ep;
    {
      const int rr = lane >> 2, cc = lane & 3;
#pragma unroll 4
      for (int it = warp; it < 196; it += 16) {
        const int rg = it / 14, cg = it % 14, k = rg * 8 + rr, ngg = cg * 4 + cc;
        const uint4 v = __ldg(wdown + (size_t)(a * 112 + k) * 56 + ngg);
        g_wimg[(size_t)(a >> 1) * 37632 + 25088 + ((ngg / 7) * 2 + (a & 1)) * 784 + (ngg % 7) * 112 + k] = v;
      }
    }
    float s[8];
#pragma unroll
    for (int k = 0; k < 8; k++) s[k] = 0.f;
    if (lane < 28) {
      const uint4* src = (mat ? wup : wgate) + j * 28 + lane + (size_t)warp * 224;
#pragma unroll 14
      for (int r = 0; r < 28; r++) {
        const uint4 v = __ldg(src + (size_t)r * 16 * 224);
        s[0] += bf_lo(v.x); s[1] += bf_hi(v.x); s[2] += bf_lo(v.y); s[3] += bf_hi(v.y);
        s[4] += bf_lo(v.z); s[5] += bf_hi(v.z); s[6] += bf_lo(v.w); s[7] += bf_hi(v.w);
      }
      float4* red = (float4*)(sm + warp * 896 + lane * 32);
      red[0] = make_float4(s[0], s[1], s[2], s[3]); red[1] = make_float4(s[4], s[5], s[6], s[7]);
    }
    __syncthreads();
    if (tid < 224) {
      float t = 0.f;
#pragma unroll
      for (int w = 0; w < 16; w++) t += *(const float*)(sm + w * 896 + tid * 4);
      const float hi = rbf(t), mid = rbf(t - hi), lo = rbf(t - hi - mid);
      const int q = tid / 112, n = tid % 112 + 112 * mat;
      __nv_bfloat16* dst = (__nv_bfloat16*)(g_cimg + (j * 2 + q) * 224 + (n >> 3) * 8) + (n & 7);
      dst[0] = __float2bfloat16_rn(hi); dst[8] = __float2bfloat16_rn(mid); dst[16] = __float2bfloat16_rn(lo);
#pragma unroll
      for (int k = 3; k < 8; k++) dst[8 * k] = __float2bfloat16_rn(0.f);
    }
    if (tid == 0) TR(0, 10);
    return;
  }

  bar_sync(5 + cp, 256);
  const uint32_t cb = sb + wg * A_CH;
  const int g = lane >> 2, t = lane & 3;
  {
    const uint32_t stg = cb + A_STG + wq * 6528;
    const float dt = rbf(expf(ldt));
    float lr[2], li[2];
    cf bq[2], b0[2], b4[2];
    uint32_t bf[48];
#pragma unroll
    for (int m = 0; m < 2; m++) {
      lr[m] = dt * (m ? bf_hi(prm[0]) : bf_lo(prm[0]));
      li[m] = dt * (m ? bf_hi(prm[1]) : bf_lo(prm[1]));
    }
    {
      cf b[2], z[2];
#pragma unroll
      for (int m = 0; m < 2; m++) {
        cf db, c;
        db.x = dt * (m ? bf_hi(prm[2]) : bf_lo(prm[2])); db.y = -dt * (m ? bf_hi(prm[3]) : bf_lo(prm[3]));
        c.x = m ? bf_hi(prm[4]) : bf_lo(prm[4]); c.y = -(m ? bf_hi(prm[5]) : bf_lo(prm[5]));
        b[m] = cmul(c, db);
        z[m] = cexp_l(lr[m], -li[m], 1.f);
        bq[m] = cexp_l(lr[m], -li[m], 256.f);
      }
#pragma unroll
      for (int i = 0; i < 8; i++) {
        sts64(stg + i * 272 + lane * 8, pack_bf16(b[0].x, b[0].y), pack_bf16(b[1].x, b[1].y));
        if (!(i & 1)) {
          cf e0 = cmul(b[0], bq[0]), e1 = cmul(b[1], bq[1]);
          sts64(stg + (8 + i / 2) * 272 + lane * 8, pack_bf16(e0.x, e0.y), pack_bf16(e1.x, e1.y));
          if (i == 0) { b0[0] = e0; b0[1] = e1; }
          if (i == 4) { b4[0] = e0; b4[1] = e1; }
        }
        if (i < 7) { b[0] = cmul(b[0], z[0]); b[1] = cmul(b[1], z[1]); }
      }
#pragma unroll
      for (int i = 0; i < 7; i++) {
        b0[0] = cmul(b0[0], bq[0]); b0[1] = cmul(b0[1], bq[1]);
        sts64(stg + (i < 2 ? 12 + 2 * i : 14 + i) * 272 + lane * 8, pack_bf16(b0[0].x, b0[0].y), pack_bf16(b0[1].x, b0[1].y));
        if (i < 2) {
          b4[0] = cmul(b4[0], bq[0]); b4[1] = cmul(b4[1], bq[1]);
          sts64(stg + (13 + 2 * i) * 272 + lane * 8, pack_bf16(b4[0].x, b4[0].y), pack_bf16(b4[1].x, b4[1].y));
        }
      }
    }
    __syncwarp();
#pragma unroll
    for (int n = 0; n < 3; n++)
#pragma unroll
      for (int k2 = 0; k2 < 4; k2++) ldsm4(bf + n * 16 + k2 * 4, stg + (n * 8 + (lane & 7)) * 272 + k2 * 64 + (lane >> 3) * 16);
    {
      const int ngg = (blk % 56) * 4 + (lane & 3), j = ngg / 28, q = (ngg % 28) / 14, ng = ngg % 14 + (blk < 56 ? 0 : 14);
      uint4* dst = g_wimg + (size_t)j * 37632 + q * 14 * 896 + ng * 32 + (warp >> 2) * 896 + (warp & 3) * 8 + (lane >> 2);
#pragma unroll
      for (int i2 = 0; i2 < 4; i2++) if (i2 < 3 || warp < 8) dst[i2 * 4 * 896] = wv[i2];
    }
    float c[6][4];
#pragma unroll
    for (int i = 0; i < 6; i++) { c[i][0] = 0.f; c[i][1] = 0.f; c[i][2] = 0.f; c[i][3] = 0.f; }
    cf p[2], v[2];
    p[0] = cexp_l(lr[0], li[0], 8.f); p[1] = cexp_l(lr[1], li[1], 8.f);
    v[0].x = 1.f; v[0].y = 0.f; v[1] = v[0];
#pragma unroll
    for (int mt = 0; mt < 2; mt++) {
      __syncwarp();
#pragma unroll
      for (int i = 0; i < 16; i++) {
        sts64(stg + i * 272 + lane * 8, pack_bf16(v[0].x, v[0].y), pack_bf16(v[1].x, v[1].y));
        if (mt == 0 && i == 0) { v[0] = p[0]; v[1] = p[1]; }
        else if (mt == 0 || i < 15) { v[0] = cmul(v[0], p[0]); v[1] = cmul(v[1], p[1]); }
      }
      __syncwarp();
#pragma unroll
      for (int ks = 0; ks < 8; ks++) {
        uint32_t a[4];
        ldsm4(a, stg + (lane & 15) * 272 + ks * 32 + (lane >> 4) * 16);
#pragma unroll
        for (int n = 0; n < 3; n++) mma16816(c[n * 2 + mt], a, bf[n * 16 + ks * 2], bf[n * 16 + ks * 2 + 1]);
      }
    }
    __syncwarp();
#pragma unroll
    for (int i = 0; i < 6; i++)
      sts128(stg + i * 512 + lane * 16, __float_as_uint(c[i][0]), __float_as_uint(c[i][1]), __float_as_uint(c[i][2]), __float_as_uint(c[i][3]));
    bar_sync(1 + wg, 128);
    if (tid == 0) TR(0, 2);
#pragma unroll
    for (int rep = 0; rep < 2; rep++) {
      const int qd = rep ? 4 + wq : wq;
      if (rep == 0 || wq < 2) {
        float s[4] = {0.f, 0.f, 0.f, 0.f};
#pragma unroll
        for (int w = 0; w < 4; w++) {
          uint4 u4 = lds128(cb + A_STG + w * 6528 + qd * 512 + lane * 16);
          s[0] += __uint_as_float(u4.x); s[1] += __uint_as_float(u4.y); s[2] += __uint_as_float(u4.z); s[3] += __uint_as_float(u4.w);
        }
#pragma unroll
        for (int hf = 0; hf < 2; hf++) {
          const int j = (qd & 1) * 16 + g + 8 * hf;
          const uint32_t pk = pack_bf16(s[2 * hf + 1], s[2 * hf]);
          const uint32_t v0 = pk >> 16, v1 = pk & 0xFFFFu, v00 = v0 * 0x10001u;
          if (rep == 1) {
            if (t < 2) {
#pragma unroll
              for (int e = 0; e < 2; e++) {
                const int lam = 128 + 32 * (2 * t + e) + j, mu = lam >> 1;
                const uint32_t val = e ? v1 : v0;
                uint32_t a = cb + ((lam & 1) ? A_R3B : A_R3A) + mu * 4;
                if (lam == 128) { a = cb + A_R2A + 128 * 4; sts32(cb + A_K1024, val << 16); }
                sts16(a, val); sts16(a + 6, val);
              }
            } else if (t == 2 && j == 0) { sts16(cb + A_R3A + 128 * 4, v0); }
          } else if (wq < 2) {
            const uint32_t a = cb + A_R1 + (62 + 8 * j + 2 * t) * 4;
            sts16(a, v0); sts32(a + 4, pk); sts16(a + 10, v1);
          } else if (t < 2) {
            const int L = 256 + 8 * j + 4 * t;
            const uint32_t a = cb + A_R1 + (62 + L) * 4;
            if (L > 256) { sts16(a - 4, v0); sts32(a, v00); } else sts16(a, v0);
            sts32(a + 4, v00); sts32(a + 8, pk); sts16(a + 14, v1);
          } else {
            const int mu = 64 + 32 * (t - 2) + j;
            if (mu == 64) {
              const uint32_t a = cb + A_R1 + (62 + 512) * 4;
              sts16(a - 4, v0); sts32(a, v00); sts32(a + 4, v00); sts32(a + 8, v00); sts16(a + 14, v0);
            } else { sts16(cb + A_R2A + mu * 4, v0); sts16(cb + A_R2A + mu * 4 + 6, v0); }
            sts16(cb + A_R2B + mu * 4, v1); sts16(cb + A_R2B + mu * 4 + 6, v1);
          }
        }
      }
    }
  }
  if (tid == 0) TR(0, 3);

  uint32_t xt[2][4], ud[2][4];
  const uint32_t pb = sb + cp * 2 * A_CH;
  {
    uint32_t st[8];
    const uint32_t par = (ep & 1u) << 15;
    int it = 0;
    while (true) {
      ld128((const uint4*)(g_stat1 + tau * 8), st); ld128((const uint4*)(g_stat1 + tau * 8 + 4), st + 4);
      uint32_t bad = 0;
#pragma unroll
      for (int i = 0; i < 8; i++) bad |= st[i] ^ par;
      if (!(bad & 0x8000u) || ++it > 200000) break;
    }
    float u[2][8];
#pragma unroll
    for (int i = 0; i < 8; i++) {
      const uint32_t d = hsub2_bf(xc[i], __byte_perm(st[i], 0, 0x3232));
      const float rs = __frcp_rn(__uint_as_float((st[i] & 0x7FFFu) << 16));
      u[0][i] = bf_lo(d) * rs; u[1][i] = bf_hi(d) * rs;
    }
    const uint32_t dk = __ldg((const uint32_t*)(dskip + blk * 4 + cp * 2));
#pragma unroll
    for (int c = 0; c < 2; c++) {
      uint32_t ut[4];
#pragma unroll
      for (int k = 0; k < 4; k++) {
        ut[k] = pack_bf16(u[c][2 * k], u[c][2 * k + 1]);
        ud[c][k] = hmul2_bf(ut[k], __byte_perm(dk, 0, c ? 0x3232 : 0x1010));
        xt[c][k] = __byte_perm(xc[2 * k], xc[2 * k + 1], c ? 0x7632 : 0x5410);
      }
      sts128(pb + c * A_CH + A_UB + (tau & 7) * 656 + ((tau >> 3) + 9) * 16, ut[0], ut[1], ut[2], ut[3]);
    }
  }
  bar_sync(5 + cp, 256);
  if (tid == 0) TR(0, 4);
  if (tau <= 192) {
    const int tp = tau == 192 ? -1 : tau;
#pragma unroll
    for (int c = 0; c < 2; c++) {
      const uint32_t b = pb + c * A_CH;
      const uint4 pv = lds128(b + A_UB + ((tp - 1) & 7) * 656 + (((tp - 1) >> 3) + 9) * 16);
      const uint4 cu = lds128(b + A_UB + (tp & 7) * 656 + ((tp >> 3) + 9) * 16);
      const uint4 nx = lds128(b + A_UB + ((tp + 1) & 7) * 656 + (((tp + 1) >> 3) + 9) * 16);
      const float e[16] = {bf_lo(pv.z), bf_hi(pv.z), bf_lo(pv.w), bf_hi(pv.w), bf_lo(cu.x), bf_hi(cu.x), bf_lo(cu.y), bf_hi(cu.y),
                           bf_lo(cu.z), bf_hi(cu.z), bf_lo(cu.w), bf_hi(cu.w), bf_lo(nx.x), bf_hi(nx.x), bf_lo(nx.y), bf_hi(nx.y)};
      float w[8];
#pragma unroll
      for (int i = 0; i < 8; i++) w[i] = e[i + 4] + (e[i + 3] + e[i + 5]);
      sts64(b + A_W3 + (tp + 64) * 16 + 8, pack_bf16(w[0], w[1]), pack_bf16(w[2], w[3]));
      sts64(b + A_W3 + (tp + 65) * 16, pack_bf16(w[4], w[5]), pack_bf16(w[6], w[7]));
#pragma unroll
      for (int i = 0; i < 8; i++) w[i] += e[i + 2] + e[i + 6];
      sts128(b + A_W5 + (tp + 64) * 16, pack_bf16(w[0], w[1]), pack_bf16(w[2], w[3]), pack_bf16(w[4], w[5]), pack_bf16(w[6], w[7]));
      if (tp < 128) {
#pragma unroll
        for (int i = 0; i < 8; i++) w[i] += e[i + 1] + e[i + 7];
        if (tp < 127) sts128(b + A_W7 + ((tp + 1) & 1) * 1024 + ((tp + 1) >> 1) * 16, pack_bf16(w[0], w[1]), pack_bf16(w[2], w[3]), pack_bf16(w[4], w[5]), pack_bf16(w[6], w[7]));
#pragma unroll
        for (int i = 0; i < 8; i++) w[i] += e[i] + e[i + 8];
        if (tp < 126) sts128(b + A_W9 + (tp & 1) * 1024 + ((tp + 2) >> 1) * 16, pack_bf16(w[0], w[1]), pack_bf16(w[2], w[3]), pack_bf16(w[4], w[5]), pack_bf16(w[6], w[7]));
        if (tp >= 0) sts128(b + A_V + tp * 16, pack_bf16(e[0] + e[1], e[1] + e[2]), pack_bf16(e[2] + e[3], e[3] + e[4]), pack_bf16(e[4] + e[5], e[5] + e[6]), pack_bf16(e[6] + e[7], e[7] + e[8]));
      }
    }
  }
  asm volatile("fence.proxy.async.shared::cta;" ::: "memory");
  bar_sync(5 + cp, 256);
  if (tid == 0) TR(0, 5);

  {
    const uint32_t cbu = __shfl_sync(~0u, cb, 0);
    const uint32_t blo_k = ((cbu & 0x3FFFF) >> 4) | (41u << 16);
    const uint32_t blo_n = ((cbu & 0x3FFFF) >> 4) | (8u << 16);
    const uint32_t tb = cb + (16 * wq + g - 2 * t) * 4;
    float y1[16], y2[12], y3[8];
    uint32_t qa[32], qb[32];
    const uint32_t t1 = tb + A_R1 + (62 - 48) * 4;
    load_quads<4>(qa, tb + A_R3A + 17 * 4); load_quads<4>(qa + 16, tb + A_R3B + 16 * 4);
    wg_fence();
    s3_steps<0, 4, A_W9, 1>(y3, qa, blo_n); s3_steps<0, 4, A_W7, 0>(y3, qa + 16, blo_n);
    wg_commit();
    load_quads<8>(qb, tb + A_R2A + 16 * 4);
    wg_fence(); s2_steps<0, 8, A_W5, 1>(y2, qb, blo_n); wg_commit();
    wg_wait<1>(); load_quads<8>(qa, tb + A_R2B + 16 * 4);
    wg_fence(); s2_steps<0, 8, A_W3, 0>(y2, qa, blo_n); wg_commit();
    wg_wait<1>(); load_quads<8>(qb, t1);
    wg_fence(); f1_steps<0, 8>(y1, qb, blo_k); wg_commit();
    wg_wait<1>(); load_quads<8>(qa, t1 + 8 * 64);
    wg_fence(); f1_steps<8, 8>(y1, qa, blo_k); wg_commit();
    reg_fence(y2); reg_fence(y3);
    {
      const float k1024 = __uint_as_float(lds32(cb + A_K1024));
#pragma unroll
      for (int i = 0; i < 2; i++)
#pragma unroll
        for (int hf = 0; hf < 2; hf++) {
          const int idx = 16 * (16 * wq + g + 8 * hf) + 8 * i + 2 * t;
          const uint32_t vv = lds32(cb + A_V + idx * 2);
          sts64(cb + A_Y3 + (idx + 4 * (idx >> 6)) * 4, __float_as_uint(fmaf(k1024, bf_lo(vv), y3[4 * i + 2 * hf])),
                __float_as_uint(fmaf(k1024, bf_hi(vv), y3[4 * i + 2 * hf + 1])));
        }
#pragma unroll
      for (int i = 0; i < 3; i++)
#pragma unroll
        for (int hf = 0; hf < 2; hf++) {
          const int idx = 512 * i + 8 * (16 * wq + g + 8 * hf) + 2 * t;
          sts64(cb + A_Y2 + (idx + 4 * (idx >> 6)) * 4, __float_as_uint(y2[4 * i + 2 * hf]), __float_as_uint(y2[4 * i + 2 * hf + 1]));
        }
    }
    wg_wait<1>(); load_quads<8>(qb, t1 + 16 * 64);
    wg_fence(); f1_steps<16, 8>(y1, qb, blo_k); wg_commit();
    wg_wait<1>(); load_quads<8>(qa, t1 + 24 * 64);
    wg_fence(); f1_steps<24, 8>(y1, qa, blo_k); wg_commit();
    wg_wait<1>(); load_quads<5>(qb, t1 + 32 * 64);
    wg_fence(); f1_steps<32, 5>(y1, qb, blo_k); wg_commit();
    bar_sync(1 + wg, 128);
    float ex[12];
#pragma unroll
    for (int i = 1; i < 4; i++)
#pragma unroll
      for (int k = 0; k < 4; k++) {
        const int aa = 8 * i + 2 * t + (k & 1), b = 16 * wq + g + 8 * (k >> 1);
        float e = __uint_as_float(lds32(cb + A_Y2 + ((aa - 8) * 68 + b) * 4));
        if (i >= 2) e += __uint_as_float(lds32(cb + A_Y3 + ((aa - 16) * 68 + b) * 4));
        ex[4 * (i - 1) + k] = e;
      }
    wg_wait<0>();
    reg_fence(y1);
    if (tid == 0) TR(0, 6);
#pragma unroll
    for (int i = 0; i < 12; i++) y1[4 + i] += ex[i];
#pragma unroll
    for (int i = 0; i < 2; i++) {
      const int mi = lane >> 3, aa = 8 * (2 * i + (mi >> 1)) + (lane & 7);
      asm volatile("stmatrix.sync.aligned.m8n8.x4.trans.shared.b16 [%0], {%1,%2,%3,%4};"
                   ::"r"(cb + A_YB + aa * 128 + (((2 * wq + (mi & 1)) ^ (lane & 7)) << 4)),
                     "r"(pack_bf16(y1[8 * i], y1[8 * i + 1])), "r"(pack_bf16(y1[8 * i + 2], y1[8 * i + 3])),
                     "r"(pack_bf16(y1[8 * i + 4], y1[8 * i + 5])), "r"(pack_bf16(y1[8 * i + 6], y1[8 * i + 7])) : "memory");
    }
  }
  bar_sync(5 + cp, 256);
#pragma unroll
  for (int c = 0; c < 2; c++) {
    const uint4 y = lds128(pb + c * A_CH + A_YB + (tau >> 3) * 128 + (((tau ^ (tau >> 3)) & 7) << 4));
    const int d = blk * 4 + cp * 2 + c, r = d & 7;
    g_himg[(size_t)(tau >> 4) * 7168 + (d >> 3) * 128 + ((tau >> 3) & 1) * 64 + r * 8 + ((tau & 7) ^ r)] =
        make_uint4(hadd2_bf(xt[c][0], hadd2_bf(y.x, ud[c][0])), hadd2_bf(xt[c][1], hadd2_bf(y.y, ud[c][1])),
                   hadd2_bf(xt[c][2], hadd2_bf(y.z, ud[c][2])), hadd2_bf(xt[c][3], hadd2_bf(y.w, ud[c][3])));
  }
  if (tid == 0) TR(0, 7);
}

constexpr int B_SA = 0, B_RING = 114688, B_SLOT = 14848, B_NSLOT = 7;
constexpr int B_CS = B_RING + B_NSLOT * B_SLOT;
constexpr int B_STAT = B_CS + 7168;
constexpr int B_BAR = B_STAT + 512;
constexpr int B_SMEM = B_BAR + 512;

__device__ __forceinline__ uint32_t mapa(uint32_t a, uint32_t r) { uint32_t o; asm("mapa.shared::cluster.u32 %0, %1, %2;" : "=r"(o) : "r"(a), "r"(r)); return o; }

template <int Q, int ST>
__device__ __forceinline__ void g1_stage(float (&acc)[116], uint32_t alo, uint32_t blo, uint32_t bar_full, uint32_t bar_h) {
  constexpr int s = Q * 14 + ST, sl = s % B_NSLOT;
  if (Q == 0) mbar_wait(bar_h + 8 * ST, 0);
  mbar_wait(bar_full + 8 * sl, (s / B_NSLOT) & 1);
  wg_fence();
  if (Q == 0) {
    wgmma_ss232<(2 * ST) * 256, 0x40000080u, (sl * B_SLOT) / 16, 32, ST != 0>(acc, alo, blo);
    wgmma_ss232<(2 * ST + 1) * 256, 0x40000080u, (sl * B_SLOT + 256) / 16, 32, 1>(acc, alo, blo);
  } else {
    wgmma_ss224<(2 * ST) * 256, 0x40000080u, (sl * B_SLOT) / 16, 32, ST != 0>(*(float(*)[112])acc, alo, blo);
    wgmma_ss224<(2 * ST + 1) * 256, 0x40000080u, (sl * B_SLOT + 256) / 16, 32, 1>(*(float(*)[112])acc, alo, blo);
  }
}

__global__ void __cluster_dims__(2, 1, 1) __launch_bounds__(384, 1) k_ffn(__nv_bfloat16* __restrict__ out) {
  extern __shared__ __align__(1024) unsigned char sm[];
  const uint32_t sb = s2u(sm);
  const int tid = threadIdx.x, wg = tid >> 7, warp = tid >> 5, lane = tid & 31;
  const int rank = blockIdx.x & 1, rt = blockIdx.x & 15, j = blockIdx.x >> 4;
  const uint32_t bar_full = sb + B_BAR, bar_empty = bar_full + 64, bar_h = bar_full + 128, bar_cs = bar_full + 240, bar_stat = bar_full + 248,
                 bar_adead = bar_full + 256, bar_in = bar_full + 264;
  if (tid == 0) {
    TR(1, 0);
    for (int i = 0; i < B_NSLOT; i++) { mbar_init(bar_full + 8 * i, 1); mbar_init(bar_empty + 8 * i, 4); }
    for (int i = 0; i < 14; i++) mbar_init(bar_h + 8 * i, 1);
    mbar_init(bar_cs, 1);
    mbar_init(bar_stat, 32);
    mbar_init(bar_adead, 2);
    for (int i = 0; i < 14; i++) mbar_init(bar_in + 8 * i, 1);
    asm volatile("fence.mbarrier_init.release.cluster;" ::: "memory");
  }
  if (tid >= 128 && tid < 128 + 224) {
    const int i = tid - 128;
    *(uint4*)(sm + B_RING + (i >> 5) * B_SLOT + 14336 + (i & 31) * 16) = make_uint4(0x3F803F80u, 0x3F803F80u, 0x3F803F80u, 0x3F803F80u);
    asm volatile("fence.proxy.async.shared::cta;" ::: "memory");
  }
  __syncthreads();
  asm volatile("barrier.cluster.arrive.release.aligned;" ::: "memory");

  if (wg == 2) {
    asm volatile("setmaxnreg.dec.sync.aligned.u32 88;");
    asm volatile("barrier.cluster.wait.acquire.aligned;" ::: "memory");
    asm volatile("griddepcontrol.wait;" ::: "memory");
    if (warp == 8) {
      if (lane == 0) {
        const char* wsrc = (const char*)g_wimg + (size_t)j * 602112;
        TR(1, 1);
        int slot = 0, ph = 0;
        for (int s = 0; s < 44; s++) {
          if (s >= B_NSLOT) mbar_wait(bar_empty + 8 * slot, ph ^ 1);
          uint32_t dst = sb + B_RING + slot * B_SLOT, fb = bar_full + 8 * slot;
          if (s < 28) {
            mbar_expect(fb, 14336);
            bulk_ld_mc(dst + rank * 7168, wsrc + s * 14336 + rank * 7168, 7168, fb);
          } else {
            const int c = (j + 1 + ((s - 28) >> 1)) & 7;
            mbar_expect(fb, 12544);
            bulk_ld_mc(dst + rank * 6272, wsrc + 401408 + (c * 2 + (s & 1)) * 12544 + rank * 6272, 6272, fb);
          }
          if (++slot == B_NSLOT) { slot = 0; ph ^= 1; }
        }
      }
    } else if (warp == 9) {
      if (lane == 0) {
        const char* hsrc = (const char*)g_himg + (size_t)rt * 114688;
        for (int i = 0; i < 14; i++) {
          mbar_expect(bar_h + 8 * i, 8192);
          bulk_ld(sb + B_SA + i * 8192, hsrc + i * 8192, 8192, bar_h + 8 * i);
        }
        mbar_expect(bar_cs, 7168);
        bulk_ld(sb + B_CS, g_cimg + j * 448, 7168, bar_cs);
      }
    } else {
      const int t64 = tid - 320;
      const uint32_t ep = __ldcg(&g_epochB), tag = ep & 1u;
      if (blockIdx.x == 0 && t64 == 0) g_epochA = ep;
      {
        const int r = (lane >> 1) & 7, c = (j & 3) * 2 + (lane & 1);
        const unsigned char* src = sm + B_SA + (t64 >> 4) * 2048 + (j >> 2) * 1024 + r * 128 + ((c ^ r) << 4);
        float a[16];
#pragma unroll
        for (int k = 0; k < 16; k++) a[k] = 0.f;
#pragma unroll 1
        for (int i = 0; i < 14; i++) {
          mbar_wait(bar_h + 8 * i, 0);
          uint4 v = *(const uint4*)(src + i * 8192);
          float e[8] = {bf_lo(v.x), bf_hi(v.x), bf_lo(v.y), bf_hi(v.y), bf_lo(v.z), bf_hi(v.z), bf_lo(v.w), bf_hi(v.w)};
#pragma unroll
          for (int k = 0; k < 8; k++) { a[2 * k] += e[k]; a[2 * k + 1] = fmaf(e[k], e[k], a[2 * k + 1]); }
          __nanosleep(160);
        }
#pragma unroll
        for (int rd = 0; rd < 4; rd++) {
          const int n = 8 >> rd;
          const bool up = lane & (2 * n);
#pragma unroll
          for (int k = 0; k < 8; k++) {
            if (k < n) {
              float keep = up ? a[k + n] : a[k], give = up ? a[k] : a[k + n];
              a[k] = keep + __shfl_xor_sync(~0u, give, 2 * n);
            }
          }
        }
        float* red = (float*)(sm + B_STAT);
        red[(warp & 1) * 32 + (lane & 1) * 16 + (lane >> 1)] = a[0];
        asm volatile("bar.sync 1, 64;" ::: "memory");
        if (t64 < 16) {
          float mean = (red[2 * t64] + red[32 + 2 * t64]) * (1.f / DM);
          float var = fmaxf(fmaf(-mean, mean, (red[2 * t64 + 1] + red[33 + 2 * t64]) * (1.f / DM)), 0.f);
          float rs = __frcp_rn(rbf(__fsqrt_rn(rbf(rbf(var) + 1e-5f))));
          asm volatile("st.relaxed.gpu.global.u32 [%0], %1;"
                       ::"l"(g_stat2 + rt * 128 + j * 16 + t64), "r"((__float_as_uint(rs * rs) & ~1u) | tag) : "memory");
        }
        if (t64 == 0) TR(1, 2);
      }
      __syncwarp();
      if (warp == 10) {
        mbar_wait(bar_adead, 0);
        uint32_t w[4];
        int it = 0;
        do { ld128((const uint4*)(g_stat2 + rt * 128) + lane, w); } while ((((w[0] ^ tag) | (w[1] ^ tag) | (w[2] ^ tag) | (w[3] ^ tag)) & 1u) && ++it < 200000);
        *(uint4*)(sm + B_STAT + lane * 16) = make_uint4(w[0], w[1], w[2], w[3]);
        mbar_arrive(bar_stat);
      }
      if (t64 == 0) TR(1, 18);
      if (warp == 11) {
        mbar_wait(bar_adead, 0);
        bool todo = lane < 14;
        int it = 0;
        while (__any_sync(~0u, todo) && ++it < 200000) {
          if (todo) {
            uint32_t w[4];
            ld128(g_flag + (rt * 8 + j) * 16 + lane, w);
            if (w[0] == ep && w[1] == ep && w[2] == ep && w[3] == ep) {
              const uint32_t b = bar_in + 8 * ((lane & 1) * 7 + (lane >> 1));
              asm volatile("fence.proxy.async.global;" ::: "memory");
              mbar_expect(b, 7168);
              bulk_ld(sb + B_SA + lane * 7168, g_part + (size_t)((rt * 8 + j) * 7) * 896 + lane * 448, 7168, b);
              todo = false;
              if (!(lane & 1)) TR(1, 24 + (lane >> 1));
            }
          }
        }
      }
    }
  } else {
    asm volatile("setmaxnreg.inc.sync.aligned.u32 208;");
    const int g = lane >> 2, t = lane & 3, wq = warp & 3, t128 = tid & 127;
    uint32_t hh[56], hres[16];
    asm volatile("barrier.cluster.wait.acquire.aligned;" ::: "memory");
    asm volatile("griddepcontrol.wait;" ::: "memory");
    const uint32_t ep = __ldcg(&g_epochB), tag = (ep & 1u) << 16;
    const uint32_t rel_bar = mapa(bar_empty, t128 & 1);
    auto release = [&](int sl) { if (t128 < 2) asm volatile("mbarrier.arrive.shared::cluster.b64 _, [%0];" ::"r"(rel_bar + 8 * sl) : "memory"); };
    const uint32_t alo = __shfl_sync(~0u, ((sb + B_SA + wg * 1024) & 0x3FFFF) >> 4, 0);
    const uint32_t blo = (((sb + B_RING) & 0x3FFFF) >> 4) | (8u << 16);
    const uint32_t clo = ((sb + B_CS) & 0x3FFFF) >> 4;
    uint32_t nm0, nm1;
    if (wg == 1) asm volatile("bar.sync 3, 256;" ::: "memory");
#define G1S(Q, ST) do { g1_stage<Q, ST>(acc, alo, blo, bar_full, bar_h); wg_commit(); \
      if (ST > 0) { wg_wait<1>(); release((Q * 14 + ST - 1) % B_NSLOT); } } while (0)
#define G1HH(Q) do { \
      _Pragma("unroll") \
      for (int i = 0; i < 28; i++) hh[28 * Q + i] = pack_bf16(acc[2 * i] * acc[56 + 2 * i], acc[2 * i + 1] * acc[57 + 2 * i]); \
    } while (0)
    {
      float acc[116];
      G1S(0, 0);
      if (tid == 0) TR(1, 3);
      G1S(0, 1);
      if (wg == 0) asm volatile("bar.arrive 3, 256;" ::: "memory");
      G1S(0, 2); G1S(0, 3); G1S(0, 4); G1S(0, 5); G1S(0, 6); G1S(0, 7); G1S(0, 8); G1S(0, 9); G1S(0, 10); G1S(0, 11); G1S(0, 12);
      G1S(0, 13);
      if (tid == 0) TR(1, 4);
      mbar_wait(bar_cs, 0);
      wg_wait<0>(); reg_fence(acc); release(13 % B_NSLOT);
      {
        const uint32_t msk = t == 0 ? 0xFFFFFFFFu : t == 1 ? 0xFFFFu : 0u;
        const float a = acc[112] * (-1.f / DM), b = acc[114] * (-1.f / DM);
        nm0 = pack_bf16(a, a) & msk; nm1 = pack_bf16(b, b) & msk;
      }
      wg_fence();
      wgmma_rs224<0, 8, 1>(*(float(*)[112])acc, nm0, nm1, 0u, 0u, clo);
      wg_commit(); wg_wait<0>(); reg_fence(acc);
      G1HH(0);
      if (tid == 0) TR(1, 5);
      G1S(1, 0); G1S(1, 1); G1S(1, 2); G1S(1, 3); G1S(1, 4); G1S(1, 5); G1S(1, 6); G1S(1, 7); G1S(1, 8); G1S(1, 9); G1S(1, 10); G1S(1, 11);
#pragma unroll
      for (int i = 0; i < 4; i++) {
        int qq = lane >> 3, r = lane & 7, kg = 7 * j + 2 * i + (qq >> 1), c = 2 * wq + (qq & 1);
        if (kg > 55) kg = 55;
        uint32_t addr = sb + B_SA + kg * 2048 + wg * 1024 + r * 128 + ((c ^ r) << 4);
        asm volatile("ldmatrix.sync.aligned.m8n8.x4.trans.shared.b16 {%0,%1,%2,%3}, [%4];"
                     : "=r"(hres[4 * i]), "=r"(hres[4 * i + 1]), "=r"(hres[4 * i + 2]), "=r"(hres[4 * i + 3]) : "r"(addr) : "memory");
      }
      G1S(1, 12);
      g1_stage<1, 13>(acc, alo, blo, bar_full, bar_h);
      wgmma_rs224<224, 8, 1>(*(float(*)[112])acc, nm0, nm1, 0u, 0u, clo);
      wg_commit(); wg_wait<1>(); release(26 % B_NSLOT);
      wg_wait<0>(); reg_fence(acc); release(27 % B_NSLOT);
      G1HH(1);
      if (t128 == 0) mbar_arrive(bar_adead);
      if (tid == 0) TR(1, 6);
    }
    float accA[28], accB[28], sum[28];
    int nxt = 0;
#pragma unroll
    for (int i = 0; i < 28; i++) sum[i] = 0.f;
#define ISSUE(acc, I, a, FIRST) do { \
      constexpr int s_ = 28 + (I), sl_ = s_ % B_NSLOT; \
      mbar_wait(bar_full + 8 * sl_, (s_ / B_NSLOT) & 1); \
      wg_fence(); \
      wgmma_rs56<(sl_ * B_SLOT + 0 * 256) / 16, 112, !(FIRST)>(acc, (a)[0], (a)[1], (a)[2], (a)[3], blo); \
      wgmma_rs56<(sl_ * B_SLOT + 1 * 256) / 16, 112, 1>(acc, (a)[4], (a)[5], (a)[6], (a)[7], blo); \
      wgmma_rs56<(sl_ * B_SLOT + 2 * 256) / 16, 112, 1>(acc, (a)[8], (a)[9], (a)[10], (a)[11], blo); \
      wgmma_rs56<(sl_ * B_SLOT + 3 * 256) / 16, 112, 1>(acc, (a)[12], (a)[13], (a)[14], (a)[15], blo); \
      wgmma_rs56<(sl_ * B_SLOT + 4 * 256) / 16, 112, 1>(acc, (a)[16], (a)[17], (a)[18], (a)[19], blo); \
      wgmma_rs56<(sl_ * B_SLOT + 5 * 256) / 16, 112, 1>(acc, (a)[20], (a)[21], (a)[22], (a)[23], blo); \
      wgmma_rs56<(sl_ * B_SLOT + 6 * 256) / 16, 112, 1>(acc, (a)[24], (a)[25], (a)[26], (a)[27], blo); \
      wg_commit(); } while (0)
    auto rel = [&](int i) { if (i < 9) release((28 + i) % B_NSLOT); };
    auto tg = [&](uint32_t v) { return (v & 0xFFFEFFFFu) | tag; };
    auto send_lo = [&](float (&acc)[28], int cc) {
      reg_fence(acc);
      uint4* dst = g_part + (size_t)((rt * 8 + ((j + 1 + cc) & 7)) * 7 + cc) * 896 + wg * 448 + t128;
#pragma unroll
      for (int q = 0; q < 2; q++)
        st128(dst + q * 128, pack_bf16(acc[8 * q], acc[8 * q + 1]), pack_bf16(acc[8 * q + 2], acc[8 * q + 3]),
              pack_bf16(acc[8 * q + 4], acc[8 * q + 5]), tg(pack_bf16(acc[8 * q + 6], acc[8 * q + 7])));
    };
    auto send_hi = [&](float (&acc)[28], int cc) {
      uint4* dst = g_part + (size_t)((rt * 8 + ((j + 1 + cc) & 7)) * 7 + cc) * 896 + wg * 448;
      st128(dst + 256 + t128, pack_bf16(acc[16], acc[17]), pack_bf16(acc[18], acc[19]), pack_bf16(acc[20], acc[21]), tg(pack_bf16(acc[22], acc[23])));
      asm volatile("{\n.reg .b64 v;\nmov.b64 v, {%1, %2};\nst.relaxed.gpu.global.b64 [%0], v;\n}"
                   ::"l"((uint2*)(dst + 384) + t128), "r"(pack_bf16(acc[24], acc[25])), "r"(tg(pack_bf16(acc[26], acc[27]))) : "memory");
      if (lane == 0)
        asm volatile("st.relaxed.gpu.global.u32 [%0], %1;" ::"l"((uint32_t*)(g_flag + (rt * 8 + ((j + 1 + cc) & 7)) * 16 + cc * 2 + wg) + wq), "r"(ep) : "memory");
    };
    auto accum = [&]() {
      const unsigned char* src = sm + B_SA + nxt * 14336 + wg * 7168;
      uint4 a = *(const uint4*)(src + t128 * 16), b = *(const uint4*)(src + 2048 + t128 * 16), c = *(const uint4*)(src + 4096 + t128 * 16);
      uint2 d = *(const uint2*)(src + 6144 + t128 * 8);
      uint32_t in[14] = {a.x, a.y, a.z, a.w, b.x, b.y, b.z, b.w, c.x, c.y, c.z, c.w, d.x, d.y};
      int it = 0;
      while ((((in[3] ^ tag) | (in[7] ^ tag) | (in[11] ^ tag) | (in[13] ^ tag)) & 0x10000u) && ++it < 200000) {
        const uint4* gs = g_part + (size_t)((rt * 8 + j) * 7 + nxt) * 896 + wg * 448;
#pragma unroll
        for (int i = 0; i < 3; i++) ld128(gs + i * 128 + t128, in + 4 * i);
        asm volatile("{\n.reg .b64 v;\nld.relaxed.gpu.global.b64 v, [%2];\nmov.b64 {%0, %1}, v;\n}"
                     : "=r"(in[12]), "=r"(in[13]) : "l"((const uint2*)(gs + 384) + t128) : "memory");
      }
#pragma unroll
      for (int i = 0; i < 14; i++) { sum[2 * i] += bf_lo(in[i]); sum[2 * i + 1] += bf_hi(in[i]); }
      nxt++;
    };
    auto try_accum = [&]() {
      uint32_t ok;
      asm volatile("{\n.reg .pred p;\nmbarrier.test_wait.parity.shared::cta.b64 p, [%1], 0;\nselp.u32 %0, 1, 0, p;\n}"
                   : "=r"(ok) : "r"(bar_in + 8 * (wg * 7 + nxt)) : "memory");
      if (__all_sync(~0u, ok)) accum();
    };
#define CHUNK(cur, prev, CC, EXTRA) do { \
      ISSUE(cur, 2 * (CC), hh, true); wg_wait<1>(); rel(2 * (CC) - 1); send_lo(prev, (CC) - 1); \
      ISSUE(cur, 2 * (CC) + 1, hh + 28, false); send_hi(prev, (CC) - 1); EXTRA; wg_wait<1>(); rel(2 * (CC)); } while (0)
    ISSUE(accA, 0, hh, true);
    ISSUE(accA, 1, hh + 28, false); wg_wait<1>(); rel(0);
    CHUNK(accB, accA, 1, );
    if (tid == 0) TR(1, 11);
    CHUNK(accA, accB, 2, );
    if (tid == 0) TR(1, 12);
    CHUNK(accB, accA, 3, try_accum());
    if (tid == 0) TR(1, 13);
    CHUNK(accA, accB, 4, try_accum());
    if (tid == 0) TR(1, 14);
    CHUNK(accB, accA, 5, try_accum());
    if (tid == 0) TR(1, 16);
    CHUNK(accA, accB, 6, try_accum());
    if (tid == 0) TR(1, 17);
    CHUNK(accB, accA, 7, try_accum());
    if (tid == 0) TR(1, 7);
#pragma unroll 1
    while (nxt < 7) { mbar_wait(bar_in + 8 * (wg * 7 + nxt), 0); accum(); }
    wg_wait<0>();
    reg_fence(accB);
    if (tid == 0) TR(1, 9);
    mbar_wait(bar_stat, 0);
    const float r20 = *(const float*)(sm + B_STAT + (wg * 64 + wq * 16 + g) * 4), r21 = *(const float*)(sm + B_STAT + (wg * 64 + wq * 16 + g + 8) * 4);
    const int row = rt * 128 + wg * 64 + wq * 16 + g;
    uint32_t* o0 = (uint32_t*)(out + (size_t)row * DM + 56 * j + 2 * t);
    uint32_t* o1 = o0 + 8 * DM / 2;
#pragma unroll
    for (int i = 0; i < 7; i++) {
      o0[4 * i] = hadd2_bf(hres[2 * i], pack_bf16((sum[4 * i] + accB[4 * i]) * r20, (sum[4 * i + 1] + accB[4 * i + 1]) * r20));
      o1[4 * i] = hadd2_bf(hres[2 * i + 1], pack_bf16((sum[4 * i + 2] + accB[4 * i + 2]) * r21, (sum[4 * i + 3] + accB[4 * i + 3]) * r21));
    }
    if (tid == 0) TR(1, 10);
    if (tid == 128) TR(1, 15);

  }
}

extern "C" void kernel_launch(void* const* d_in, const int* in_sizes, int n_in, void* d_out, int out_size) {
  const __nv_bfloat16* x = (const __nv_bfloat16*)d_in[0];
  const __nv_bfloat16 *are = (const __nv_bfloat16*)d_in[1], *aim = (const __nv_bfloat16*)d_in[2], *bre = (const __nv_bfloat16*)d_in[3],
                      *bim = (const __nv_bfloat16*)d_in[4], *cre = (const __nv_bfloat16*)d_in[5], *cim = (const __nv_bfloat16*)d_in[6],
                      *logdt = (const __nv_bfloat16*)d_in[7], *dskip = (const __nv_bfloat16*)d_in[8];
  const __nv_bfloat16 *wg = (const __nv_bfloat16*)d_in[10], *wu = (const __nv_bfloat16*)d_in[11], *wd = (const __nv_bfloat16*)d_in[12];

  static bool init = false;
  if (!init) {
    init = true;
    cudaFuncSetAttribute(k_ffn, cudaFuncAttributeMaxDynamicSharedMemorySize, B_SMEM);
    cudaFuncSetAttribute(k_front, cudaFuncAttributeMaxDynamicSharedMemorySize, A_SMEM);
  }
  cudaStream_t st = cudaStreamPerThread;
  k_front<<<128, 512, A_SMEM, st>>>(x, (const uint32_t*)are, (const uint32_t*)aim, (const uint32_t*)bre, (const uint32_t*)bim,
                                    (const uint32_t*)cre, (const uint32_t*)cim, logdt, dskip, (const uint4*)wg, (const uint4*)wu, (const uint4*)wd);
  k_ffn<<<128, 384, B_SMEM, st>>>((__nv_bfloat16*)d_out);
}
```

```cpp
#include <cuda_runtime.h>
#include <cuda_bf16.h>
#include <stdint.h>

constexpr int LSEQ = 2048, DM = 448;

__device__ uint4    g_himg[16 * 114688 / 16];
__device__ uint4    g_cimg[8 * 2 * 224];
__device__ uint32_t g_stat2[LSEQ];
__device__ uint4    g_part[128 * 7 * 896];
__device__ uint4    g_wimg[8 * 602112 / 16];
__device__ unsigned g_epochA, g_epochB;
__device__ uint4    g_ux[DM * 128 * 4];
__device__ unsigned g_cnt1;
__device__ uint4    g_flag[128 * 16];

#define TR(k, i) do {} while (0)
__device__ __forceinline__ uint32_t s2u(const void* p) { return (uint32_t)__cvta_generic_to_shared(p); }
__device__ __forceinline__ void mbar_init(uint32_t b, int c) { asm volatile("mbarrier.init.shared::cta.b64 [%0], %1;" ::"r"(b), "r"(c)); }
__device__ __forceinline__ void mbar_expect(uint32_t b, int bytes) { asm volatile("mbarrier.arrive.expect_tx.shared::cta.b64 _, [%0], %1;" ::"r"(b), "r"(bytes) : "memory"); }
__device__ __forceinline__ void mbar_arrive(uint32_t b) { asm volatile("mbarrier.arrive.shared::cta.b64 _, [%0];" ::"r"(b) : "memory"); }
__device__ __forceinline__ void mbar_wait(uint32_t b, int ph) {
  asm volatile("{\n.reg .pred p;\n.reg .b32 n;\nmov.b32 n, 0;\nLW:\nmbarrier.try_wait.parity.shared::cta.b64 p, [%0], %1;\n@p bra LD;\n"
               "add.u32 n, n, 1;\nsetp.lt.u32 p, n, 4000000;\n@p bra LW;\ntrap;\nLD:\n}" ::"r"(b), "r"(ph) : "memory");
}
__device__ __forceinline__ uint64_t mkdesc(uint32_t addr, uint32_t lbo, uint32_t sbo, uint32_t sw) {
  return (uint64_t)((addr & 0x3FFFF) >> 4) | ((uint64_t)((lbo >> 4) & 0x3FFF) << 16) | ((uint64_t)((sbo >> 4) & 0x3FFF) << 32) | ((uint64_t)sw << 62);
}
__device__ __forceinline__ void wg_fence() { asm volatile("wgmma.fence.sync.aligned;" ::: "memory"); }
__device__ __forceinline__ void wg_commit() { asm volatile("wgmma.commit_group.sync.aligned;" ::: "memory"); }
template <int N> __device__ __forceinline__ void wg_wait() { asm volatile("wgmma.wait_group.sync.aligned %0;" ::"n"(N) : "memory"); }
template <int N> __device__ __forceinline__ void reg_fence(float (&a)[N]) {
#pragma unroll
  for (int i = 0; i < N; i++) asm volatile("" : "+f"(a[i])::"memory");
}
__device__ __forceinline__ uint32_t pack_bf16(float lo, float hi) {
  uint32_t r; asm("cvt.rn.bf16x2.f32 %0, %1, %2;" : "=r"(r) : "f"(hi), "f"(lo)); return r;
}
__device__ __forceinline__ float bf_lo(uint32_t v) { return __uint_as_float(v << 16); }
__device__ __forceinline__ float bf_hi(uint32_t v) { return __uint_as_float(v & 0xFFFF0000u); }
__device__ __forceinline__ float rbf(float x) { return __bfloat162float(__float2bfloat16_rn(x)); }
__device__ __forceinline__ uint32_t hmul2_bf(uint32_t a, uint32_t b) { uint32_t r; asm("mul.rn.bf16x2 %0, %1, %2;" : "=r"(r) : "r"(a), "r"(b)); return r; }
__device__ __forceinline__ uint32_t hadd2_bf(uint32_t a, uint32_t b) { uint32_t r; asm("add.rn.bf16x2 %0, %1, %2;" : "=r"(r) : "r"(a), "r"(b)); return r; }
__device__ __forceinline__ void bulk_ld(uint32_t dst, const void* src, int bytes, uint32_t bar) {
  asm volatile("cp.async.bulk.shared::cluster.global.mbarrier::complete_tx::bytes [%0], [%1], %2, [%3];"
               ::"r"(dst), "l"(src), "r"(bytes), "r"(bar) : "memory");
}

__device__ __forceinline__ void bulk_ld_mc(uint32_t dst, const void* src, int bytes, uint32_t bar) {
  asm volatile("cp.async.bulk.shared::cluster.global.mbarrier::complete_tx::bytes.multicast::cluster [%0], [%1], %2, [%3], %4;"
               ::"r"(dst), "l"(src), "r"(bytes), "r"(bar), "h"((uint16_t)3) : "memory");
}
template <int AOFF, uint32_t AHI, int BOFF, uint32_t BHI, int ACC>
__device__ __forceinline__ void wgmma_ss224(float (&d)[112], uint32_t alo, uint32_t blo) {
  asm volatile("{\n.reg .pred p;\n.reg .b32 la, lb;\n.reg .b64 ad, bd;\nsetp.ne.b32 p, %118, 0;\n"
    "add.u32 la, %112, %114;\nmov.b64 ad, {la, %115};\nadd.u32 lb, %113, %116;\nmov.b64 bd, {lb, %117};\n"
    "wgmma.mma_async.sync.aligned.m64n224k16.f32.bf16.bf16 {%0,%1,%2,%3,%4,%5,%6,%7,%8,%9,%10,%11,%12,%13,%14,%15,%16,%17,%18,%19,%20,%21,%22,%23,%24,%25,%26,%27,%28,%29,%30,%31,%32,%33,%34,%35,%36,%37,%38,%39,%40,%41,%42,%43,%44,%45,%46,%47,%48,%49,%50,%51,%52,%53,%54,%55,%56,%57,%58,%59,%60,%61,%62,%63,%64,%65,%66,%67,%68,%69,%70,%71,%72,%73,%74,%75,%76,%77,%78,%79,%80,%81,%82,%83,%84,%85,%86,%87,%88,%89,%90,%91,%92,%93,%94,%95,%96,%97,%98,%99,%100,%101,%102,%103,%104,%105,%106,%107,%108,%109,%110,%111}, ad, bd, p, 1, 1, 1, 1;\n}\n"
    : "+f"(d[0]),"+f"(d[1]),"+f"(d[2]),"+f"(d[3]),"+f"(d[4]),"+f"(d[5]),"+f"(d[6]),"+f"(d[7]),"+f"(d[8]),"+f"(d[9]),"+f"(d[10]),"+f"(d[11]),"+f"(d[12]),"+f"(d[13]),"+f"(d[14]),"+f"(d[15]),"+f"(d[16]),"+f"(d[17]),"+f"(d[18]),"+f"(d[19]),"+f"(d[20]),"+f"(d[21]),"+f"(d[22]),"+f"(d[23]),"+f"(d[24]),"+f"(d[25]),"+f"(d[26]),"+f"(d[27]),"+f"(d[28]),"+f"(d[29]),"+f"(d[30]),"+f"(d[31]),"+f"(d[32]),"+f"(d[33]),"+f"(d[34]),"+f"(d[35]),"+f"(d[36]),"+f"(d[37]),"+f"(d[38]),"+f"(d[39]),"+f"(d[40]),"+f"(d[41]),"+f"(d[42]),"+f"(d[43]),"+f"(d[44]),"+f"(d[45]),"+f"(d[46]),"+f"(d[47]),"+f"(d[48]),"+f"(d[49]),"+f"(d[50]),"+f"(d[51]),"+f"(d[52]),"+f"(d[53]),"+f"(d[54]),"+f"(d[55]),"+f"(d[56]),"+f"(d[57]),"+f"(d[58]),"+f"(d[59]),"+f"(d[60]),"+f"(d[61]),"+f"(d[62]),"+f"(d[63]),"+f"(d[64]),"+f"(d[65]),"+f"(d[66]),"+f"(d[67]),"+f"(d[68]),"+f"(d[69]),"+f"(d[70]),"+f"(d[71]),"+f"(d[72]),"+f"(d[73]),"+f"(d[74]),"+f"(d[75]),"+f"(d[76]),"+f"(d[77]),"+f"(d[78]),"+f"(d[79]),"+f"(d[80]),"+f"(d[81]),"+f"(d[82]),"+f"(d[83]),"+f"(d[84]),"+f"(d[85]),"+f"(d[86]),"+f"(d[87]),"+f"(d[88]),"+f"(d[89]),"+f"(d[90]),"+f"(d[91]),"+f"(d[92]),"+f"(d[93]),"+f"(d[94]),"+f"(d[95]),"+f"(d[96]),"+f"(d[97]),"+f"(d[98]),"+f"(d[99]),"+f"(d[100]),"+f"(d[101]),"+f"(d[102]),"+f"(d[103]),"+f"(d[104]),"+f"(d[105]),"+f"(d[106]),"+f"(d[107]),"+f"(d[108]),"+f"(d[109]),"+f"(d[110]),"+f"(d[111])
    : "r"(alo), "r"(blo), "n"(AOFF), "n"(AHI), "n"(BOFF), "n"(BHI), "n"(ACC));
}
template <int AOFF, uint32_t AHI, int BOFF, uint32_t BHI, int ACC>
__device__ __forceinline__ void wgmma_ss232(float (&d)[116], uint32_t alo, uint32_t blo) {
  asm volatile("{\n.reg .pred p;\n.reg .b32 la, lb;\n.reg .b64 ad, bd;\nsetp.ne.b32 p, %122, 0;\n"
    "add.u32 la, %116, %118;\nmov.b64 ad, {la, %119};\nadd.u32 lb, %117, %120;\nmov.b64 bd, {lb, %121};\n"
    "wgmma.mma_async.sync.aligned.m64n232k16.f32.bf16.bf16 {%0,%1,%2,%3,%4,%5,%6,%7,%8,%9,%10,%11,%12,%13,%14,%15,%16,%17,%18,%19,%20,%21,%22,%23,%24,%25,%26,%27,%28,%29,%30,%31,%32,%33,%34,%35,%36,%37,%38,%39,%40,%41,%42,%43,%44,%45,%46,%47,%48,%49,%50,%51,%52,%53,%54,%55,%56,%57,%58,%59,%60,%61,%62,%63,%64,%65,%66,%67,%68,%69,%70,%71,%72,%73,%74,%75,%76,%77,%78,%79,%80,%81,%82,%83,%84,%85,%86,%87,%88,%89,%90,%91,%92,%93,%94,%95,%96,%97,%98,%99,%100,%101,%102,%103,%104,%105,%106,%107,%108,%109,%110,%111,%112,%113,%114,%115}, ad, bd, p, 1, 1, 1, 1;\n}\n"
    : "+f"(d[0]),"+f"(d[1]),"+f"(d[2]),"+f"(d[3]),"+f"(d[4]),"+f"(d[5]),"+f"(d[6]),"+f"(d[7]),"+f"(d[8]),"+f"(d[9]),"+f"(d[10]),"+f"(d[11]),"+f"(d[12]),"+f"(d[13]),"+f"(d[14]),"+f"(d[15]),"+f"(d[16]),"+f"(d[17]),"+f"(d[18]),"+f"(d[19]),"+f"(d[20]),"+f"(d[21]),"+f"(d[22]),"+f"(d[23]),"+f"(d[24]),"+f"(d[25]),"+f"(d[26]),"+f"(d[27]),"+f"(d[28]),"+f"(d[29]),"+f"(d[30]),"+f"(d[31]),"+f"(d[32]),"+f"(d[33]),"+f"(d[34]),"+f"(d[35]),"+f"(d[36]),"+f"(d[37]),"+f"(d[38]),"+f"(d[39]),"+f"(d[40]),"+f"(d[41]),"+f"(d[42]),"+f"(d[43]),"+f"(d[44]),"+f"(d[45]),"+f"(d[46]),"+f"(d[47]),"+f"(d[48]),"+f"(d[49]),"+f"(d[50]),"+f"(d[51]),"+f"(d[52]),"+f"(d[53]),"+f"(d[54]),"+f"(d[55]),"+f"(d[56]),"+f"(d[57]),"+f"(d[58]),"+f"(d[59]),"+f"(d[60]),"+f"(d[61]),"+f"(d[62]),"+f"(d[63]),"+f"(d[64]),"+f"(d[65]),"+f"(d[66]),"+f"(d[67]),"+f"(d[68]),"+f"(d[69]),"+f"(d[70]),"+f"(d[71]),"+f"(d[72]),"+f"(d[73]),"+f"(d[74]),"+f"(d[75]),"+f"(d[76]),"+f"(d[77]),"+f"(d[78]),"+f"(d[79]),"+f"(d[80]),"+f"(d[81]),"+f"(d[82]),"+f"(d[83]),"+f"(d[84]),"+f"(d[85]),"+f"(d[86]),"+f"(d[87]),"+f"(d[88]),"+f"(d[89]),"+f"(d[90]),"+f"(d[91]),"+f"(d[92]),"+f"(d[93]),"+f"(d[94]),"+f"(d[95]),"+f"(d[96]),"+f"(d[97]),"+f"(d[98]),"+f"(d[99]),"+f"(d[100]),"+f"(d[101]),"+f"(d[102]),"+f"(d[103]),"+f"(d[104]),"+f"(d[105]),"+f"(d[106]),"+f"(d[107]),"+f"(d[108]),"+f"(d[109]),"+f"(d[110]),"+f"(d[111]),"+f"(d[112]),"+f"(d[113]),"+f"(d[114]),"+f"(d[115])
    : "r"(alo), "r"(blo), "n"(AOFF), "n"(AHI), "n"(BOFF), "n"(BHI), "n"(ACC));
}
template <int OFF, uint32_t BHI, int ACC>
__device__ __forceinline__ void wgmma_rs224(float (&d)[112], uint32_t a0, uint32_t a1, uint32_t a2, uint32_t a3, uint32_t blo) {
  asm volatile("{\n.reg .pred p;\n.reg .b32 l;\n.reg .b64 bd;\nsetp.ne.b32 p, %119, 0;\nadd.u32 l, %116, %117;\nmov.b64 bd, {l, %118};\n"
    "wgmma.mma_async.sync.aligned.m64n224k16.f32.bf16.bf16 {%0,%1,%2,%3,%4,%5,%6,%7,%8,%9,%10,%11,%12,%13,%14,%15,%16,%17,%18,%19,%20,%21,%22,%23,%24,%25,%26,%27,%28,%29,%30,%31,%32,%33,%34,%35,%36,%37,%38,%39,%40,%41,%42,%43,%44,%45,%46,%47,%48,%49,%50,%51,%52,%53,%54,%55,%56,%57,%58,%59,%60,%61,%62,%63,%64,%65,%66,%67,%68,%69,%70,%71,%72,%73,%74,%75,%76,%77,%78,%79,%80,%81,%82,%83,%84,%85,%86,%87,%88,%89,%90,%91,%92,%93,%94,%95,%96,%97,%98,%99,%100,%101,%102,%103,%104,%105,%106,%107,%108,%109,%110,%111}, {%112,%113,%114,%115}, bd, p, 1, 1, 1;\n}\n"
    : "+f"(d[0]),"+f"(d[1]),"+f"(d[2]),"+f"(d[3]),"+f"(d[4]),"+f"(d[5]),"+f"(d[6]),"+f"(d[7]),"+f"(d[8]),"+f"(d[9]),"+f"(d[10]),"+f"(d[11]),"+f"(d[12]),"+f"(d[13]),"+f"(d[14]),"+f"(d[15]),"+f"(d[16]),"+f"(d[17]),"+f"(d[18]),"+f"(d[19]),"+f"(d[20]),"+f"(d[21]),"+f"(d[22]),"+f"(d[23]),"+f"(d[24]),"+f"(d[25]),"+f"(d[26]),"+f"(d[27]),"+f"(d[28]),"+f"(d[29]),"+f"(d[30]),"+f"(d[31]),"+f"(d[32]),"+f"(d[33]),"+f"(d[34]),"+f"(d[35]),"+f"(d[36]),"+f"(d[37]),"+f"(d[38]),"+f"(d[39]),"+f"(d[40]),"+f"(d[41]),"+f"(d[42]),"+f"(d[43]),"+f"(d[44]),"+f"(d[45]),"+f"(d[46]),"+f"(d[47]),"+f"(d[48]),"+f"(d[49]),"+f"(d[50]),"+f"(d[51]),"+f"(d[52]),"+f"(d[53]),"+f"(d[54]),"+f"(d[55]),"+f"(d[56]),"+f"(d[57]),"+f"(d[58]),"+f"(d[59]),"+f"(d[60]),"+f"(d[61]),"+f"(d[62]),"+f"(d[63]),"+f"(d[64]),"+f"(d[65]),"+f"(d[66]),"+f"(d[67]),"+f"(d[68]),"+f"(d[69]),"+f"(d[70]),"+f"(d[71]),"+f"(d[72]),"+f"(d[73]),"+f"(d[74]),"+f"(d[75]),"+f"(d[76]),"+f"(d[77]),"+f"(d[78]),"+f"(d[79]),"+f"(d[80]),"+f"(d[81]),"+f"(d[82]),"+f"(d[83]),"+f"(d[84]),"+f"(d[85]),"+f"(d[86]),"+f"(d[87]),"+f"(d[88]),"+f"(d[89]),"+f"(d[90]),"+f"(d[91]),"+f"(d[92]),"+f"(d[93]),"+f"(d[94]),"+f"(d[95]),"+f"(d[96]),"+f"(d[97]),"+f"(d[98]),"+f"(d[99]),"+f"(d[100]),"+f"(d[101]),"+f"(d[102]),"+f"(d[103]),"+f"(d[104]),"+f"(d[105]),"+f"(d[106]),"+f"(d[107]),"+f"(d[108]),"+f"(d[109]),"+f"(d[110]),"+f"(d[111])
    : "r"(a0), "r"(a1), "r"(a2), "r"(a3), "r"(blo), "n"(OFF), "n"(BHI), "n"(ACC));
}
template <int OFF, uint32_t BHI, int ACC>
__device__ __forceinline__ void wgmma_rs56(float (&d)[28], uint32_t a0, uint32_t a1, uint32_t a2, uint32_t a3, uint32_t blo) {
  asm volatile("{\n.reg .pred p;\n.reg .b32 l;\n.reg .b64 bd;\nsetp.ne.b32 p, %35, 0;\nadd.u32 l, %32, %33;\nmov.b64 bd, {l, %34};\n"
    "wgmma.mma_async.sync.aligned.m64n56k16.f32.bf16.bf16 {%0,%1,%2,%3,%4,%5,%6,%7,%8,%9,%10,%11,%12,%13,%14,%15,%16,%17,%18,%19,%20,%21,%22,%23,%24,%25,%26,%27}, {%28,%29,%30,%31}, bd, p, 1, 1, 1;\n}\n"
    : "+f"(d[0]),"+f"(d[1]),"+f"(d[2]),"+f"(d[3]),"+f"(d[4]),"+f"(d[5]),"+f"(d[6]),"+f"(d[7]),"+f"(d[8]),"+f"(d[9]),"+f"(d[10]),"+f"(d[11]),"+f"(d[12]),"+f"(d[13]),"+f"(d[14]),"+f"(d[15]),"+f"(d[16]),"+f"(d[17]),"+f"(d[18]),"+f"(d[19]),"+f"(d[20]),"+f"(d[21]),"+f"(d[22]),"+f"(d[23]),"+f"(d[24]),"+f"(d[25]),"+f"(d[26]),"+f"(d[27])
    : "r"(a0), "r"(a1), "r"(a2), "r"(a3), "r"(blo), "n"(OFF), "n"(BHI), "n"(ACC));
}

__device__ __forceinline__ void st128(uint4* p, uint32_t a, uint32_t b, uint32_t c, uint32_t d) {
  asm volatile("{\n.reg .b128 v;\n.reg .b64 lo, hi;\nmov.b64 lo, {%1, %2};\nmov.b64 hi, {%3, %4};\nmov.b128 v, {lo, hi};\n"
               "st.relaxed.gpu.global.b128 [%0], v;\n}" ::"l"(p), "r"(a), "r"(b), "r"(c), "r"(d) : "memory");
}
__device__ __forceinline__ void ld128(const uint4* p, uint32_t* r) {
  asm volatile("{\n.reg .b128 v;\n.reg .b64 lo, hi;\nld.relaxed.gpu.global.b128 v, [%4];\nmov.b128 {lo, hi}, v;\n"
               "mov.b64 {%0, %1}, lo;\nmov.b64 {%2, %3}, hi;\n}" : "=r"(r[0]), "=r"(r[1]), "=r"(r[2]), "=r"(r[3]) : "l"(p) : "memory");
}

template <int OFF, uint32_t BHI, int ACC>
__device__ __forceinline__ void wgmma_rs32(float (&d)[16], uint32_t a0, uint32_t a1, uint32_t a2, uint32_t a3, uint32_t blo) {
  asm volatile("{\n.reg .pred p;\n.reg .b32 l;\n.reg .b64 bd;\nsetp.ne.b32 p, %23, 0;\nadd.u32 l, %20, %21;\nmov.b64 bd, {l, %22};\n"
    "wgmma.mma_async.sync.aligned.m64n32k16.f32.bf16.bf16 {%0,%1,%2,%3,%4,%5,%6,%7,%8,%9,%10,%11,%12,%13,%14,%15}, {%16,%17,%18,%19}, bd, p, 1, 1, 0;\n}\n"
    : "+f"(d[0]),"+f"(d[1]),"+f"(d[2]),"+f"(d[3]),"+f"(d[4]),"+f"(d[5]),"+f"(d[6]),"+f"(d[7]),"+f"(d[8]),"+f"(d[9]),"+f"(d[10]),"+f"(d[11]),"+f"(d[12]),"+f"(d[13]),"+f"(d[14]),"+f"(d[15])
    : "r"(a0), "r"(a1), "r"(a2), "r"(a3), "r"(blo), "n"(OFF), "n"(BHI), "n"(ACC));
}
template <int OFF, uint32_t BHI, int ACC>
__device__ __forceinline__ void wgmma_rs24(float (&d)[12], uint32_t a0, uint32_t a1, uint32_t a2, uint32_t a3, uint32_t blo) {
  asm volatile("{\n.reg .pred p;\n.reg .b32 l;\n.reg .b64 bd;\nsetp.ne.b32 p, %19, 0;\nadd.u32 l, %16, %17;\nmov.b64 bd, {l, %18};\n"
    "wgmma.mma_async.sync.aligned.m64n24k16.f32.bf16.bf16 {%0,%1,%2,%3,%4,%5,%6,%7,%8,%9,%10,%11}, {%12,%13,%14,%15}, bd, p, 1, 1, 1;\n}\n"
    : "+f"(d[0]),"+f"(d[1]),"+f"(d[2]),"+f"(d[3]),"+f"(d[4]),"+f"(d[5]),"+f"(d[6]),"+f"(d[7]),"+f"(d[8]),"+f"(d[9]),"+f"(d[10]),"+f"(d[11])
    : "r"(a0), "r"(a1), "r"(a2), "r"(a3), "r"(blo), "n"(OFF), "n"(BHI), "n"(ACC));
}
template <int OFF, uint32_t BHI, int ACC>
__device__ __forceinline__ void wgmma_rs16(float (&d)[8], uint32_t a0, uint32_t a1, uint32_t a2, uint32_t a3, uint32_t blo) {
  asm volatile("{\n.reg .pred p;\n.reg .b32 l;\n.reg .b64 bd;\nsetp.ne.b32 p, %15, 0;\nadd.u32 l, %12, %13;\nmov.b64 bd, {l, %14};\n"
    "wgmma.mma_async.sync.aligned.m64n16k16.f32.bf16.bf16 {%0,%1,%2,%3,%4,%5,%6,%7}, {%8,%9,%10,%11}, bd, p, 1, 1, 1;\n}\n"
    : "+f"(d[0]),"+f"(d[1]),"+f"(d[2]),"+f"(d[3]),"+f"(d[4]),"+f"(d[5]),"+f"(d[6]),"+f"(d[7])
    : "r"(a0), "r"(a1), "r"(a2), "r"(a3), "r"(blo), "n"(OFF), "n"(BHI), "n"(ACC));
}

constexpr int A_UB = 0;
constexpr int A_W5 = 5248;
constexpr int A_W3 = A_W5 + 4112;
constexpr int A_W9 = A_W3 + 4112;
constexpr int A_W7 = A_W9 + 2048;
constexpr int A_V  = A_W7 + 2048;
constexpr int A_R1 = A_V + 2048;
constexpr int A_R2A = A_R1 + 2624, A_R2B = A_R2A + 768, A_R3A = A_R2B + 768, A_R3B = A_R3A + 528;
constexpr int A_K1024 = A_R3B + 528;
constexpr int A_ZEND = A_K1024 + 16;
constexpr int A_STG = A_ZEND;
constexpr int A_Y2 = A_STG, A_Y3 = A_Y2 + 6528, A_YB = A_Y3 + 4352;
constexpr int A_CH = A_STG + 4 * 6528;
constexpr int A_SMEM = 4 * A_CH;
static_assert(A_ZEND % 16 == 0 && A_CH % 16 == 0 && A_YB + 4096 <= A_CH, "layout");

struct cf { float x, y; };
__device__ __forceinline__ cf cmul(cf a, cf b) { cf r; r.x = fmaf(a.x, b.x, -a.y * b.y); r.y = fmaf(a.x, b.y, a.y * b.x); return r; }
__device__ __forceinline__ cf cexp_l(float lr, float li, float l) {
  float mag; asm("ex2.approx.ftz.f32 %0, %1;" : "=f"(mag) : "f"((lr * l) * 1.4426950408889634f));
  const float th = li * l;
  const float k = (fmaf(th, 0.15915494f, 12582912.f)) - 12582912.f;
  float ph = fmaf(th, 0.15915494f, -k);
  ph = fmaf(th, 6.4206383e-9f, ph) * 6.2831853f;
  cf r; r.x = mag * __cosf(ph); r.y = mag * __sinf(ph); return r;
}
__device__ __forceinline__ void sts16(uint32_t a, uint32_t v) { asm volatile("st.shared.u16 [%0], %1;" ::"r"(a), "h"((uint16_t)v) : "memory"); }
__device__ __forceinline__ void sts32(uint32_t a, uint32_t v) { asm volatile("st.shared.u32 [%0], %1;" ::"r"(a), "r"(v) : "memory"); }
__device__ __forceinline__ void sts64(uint32_t a, uint32_t v0, uint32_t v1) { asm volatile("st.shared.v2.u32 [%0], {%1, %2};" ::"r"(a), "r"(v0), "r"(v1) : "memory"); }
__device__ __forceinline__ void sts128(uint32_t a, uint32_t v0, uint32_t v1, uint32_t v2, uint32_t v3) {
  asm volatile("st.shared.v4.u32 [%0], {%1, %2, %3, %4};" ::"r"(a), "r"(v0), "r"(v1), "r"(v2), "r"(v3) : "memory");
}
__device__ __forceinline__ uint32_t lds32(uint32_t a) { uint32_t v; asm volatile("ld.shared.u32 %0, [%1];" : "=r"(v) : "r"(a) : "memory"); return v; }
__device__ __forceinline__ uint4 lds128(uint32_t a) {
  uint4 v; asm volatile("ld.shared.v4.u32 {%0, %1, %2, %3}, [%4];" : "=r"(v.x), "=r"(v.y), "=r"(v.z), "=r"(v.w) : "r"(a) : "memory"); return v;
}
__device__ __forceinline__ void ldsm4(uint32_t* r, uint32_t a) {
  asm volatile("ldmatrix.sync.aligned.m8n8.x4.shared.b16 {%0,%1,%2,%3}, [%4];" : "=r"(r[0]), "=r"(r[1]), "=r"(r[2]), "=r"(r[3]) : "r"(a) : "memory");
}
__device__ __forceinline__ void mma16816(float* d, const uint32_t* a, uint32_t b0, uint32_t b1) {
  asm volatile("mma.sync.aligned.m16n8k16.row.col.f32.bf16.bf16.f32 {%0,%1,%2,%3}, {%4,%5,%6,%7}, {%8,%9}, {%0,%1,%2,%3};"
               : "+f"(d[0]), "+f"(d[1]), "+f"(d[2]), "+f"(d[3]) : "r"(a[0]), "r"(a[1]), "r"(a[2]), "r"(a[3]), "r"(b0), "r"(b1));
}
__device__ __forceinline__ uint32_t hsub2_bf(uint32_t a, uint32_t b) { uint32_t r; asm("sub.rn.bf16x2 %0, %1, %2;" : "=r"(r) : "r"(a), "r"(b)); return r; }
__device__ __forceinline__ void bar_sync(int id, int n) { asm volatile("bar.sync %0, %1;" ::"r"(id), "r"(n) : "memory"); }

template <int S> struct F1B { static constexpr int c = S / 4 + ((S & 3) == 3 ? 0 : 0), cc = (16 * S) / 64, ks = (64 * cc - (16 * S - 48)) / 16, off = (2 * ks * 656 + (9 - cc) * 16) / 16; };

template <int NS>
__device__ __forceinline__ void load_quads(uint32_t* q, uint32_t addr) {
#pragma unroll
  for (int i = 0; i < NS; i++) {
    q[4 * i] = lds32(addr + i * 64); q[4 * i + 1] = lds32(addr + i * 64 + 32);
    q[4 * i + 2] = i ? q[4 * i - 3] : lds32(addr - 32);
    q[4 * i + 3] = q[4 * i];
  }
#pragma unroll
  for (int i = 0; i < 4 * NS; i++) asm volatile("" : "+r"(q[i]));
}
template <int S0, int NS>
__device__ __forceinline__ void f1_steps(float (&acc)[16], const uint32_t* a, uint32_t blo) {
  if constexpr (NS > 0) {
    wgmma_rs32<F1B<S0>::off, 8, S0 != 0>(acc, a[0], a[1], a[2], a[3], blo);
    f1_steps<S0 + 1, NS - 1>(acc, a + 4, blo);
  }
}
template <int S0, int NS, int BASE, int FIRST>
__device__ __forceinline__ void s2_steps(float (&acc)[12], const uint32_t* a, uint32_t blo) {
  if constexpr (NS > 0) {
    wgmma_rs24<BASE / 16 + (112 - 16 * S0), 64, !(FIRST && S0 == 0)>(acc, a[0], a[1], a[2], a[3], blo);
    s2_steps<S0 + 1, NS - 1, BASE, FIRST>(acc, a + 4, blo);
  }
}
template <int S0, int NS, int BASE, int FIRST>
__device__ __forceinline__ void s3_steps(float (&acc)[8], const uint32_t* a, uint32_t blo) {
  if constexpr (NS > 0) {
    wgmma_rs16<BASE / 16 + (48 - 16 * S0), 64, !(FIRST && S0 == 0)>(acc, a[0], a[1], a[2], a[3], blo);
    s3_steps<S0 + 1, NS - 1, BASE, FIRST>(acc, a + 4, blo);
  }
}

__global__ void __launch_bounds__(512, 1)
k_front(const __nv_bfloat16* __restrict__ x, const uint32_t* __restrict__ are, const uint32_t* __restrict__ aim,
        const uint32_t* __restrict__ bre, const uint32_t* __restrict__ bim, const uint32_t* __restrict__ cre,
        const uint32_t* __restrict__ cim, const __nv_bfloat16* __restrict__ logdt, const __nv_bfloat16* __restrict__ dskip,
        const uint4* __restrict__ wgate, const uint4* __restrict__ wup, const uint4* __restrict__ wdown) {
  extern __shared__ __align__(1024) unsigned char sm[];
  const uint32_t sb = s2u(sm);
  const int tid = threadIdx.x, wg = tid >> 7, warp = tid >> 5, lane = tid & 31, wq = warp & 3, t128 = tid & 127;
  const int blk = blockIdx.x;
  const bool conv = blk < 112;
  if (tid == 0) TR(0, 0);
  asm volatile("griddepcontrol.launch_dependents;");

  uint2 xr[4];
  {
    const uint2* p = (const uint2*)(x + (size_t)(blk * 16 + warp) * DM);
    xr[0] = __ldg(p + lane); xr[1] = __ldg(p + 32 + lane); xr[2] = __ldg(p + 64 + lane);
    xr[3] = lane < 16 ? __ldg(p + 96 + lane) : make_uint2(0, 0);
  }
  const uint32_t ep = __ldcg(&g_epochA) + 1u;
  const int ch = blk * 4 + wg;
  uint32_t prm[6]; float ldt = 0.f;
  uint4 wv[4];
  if (conv) {
    const int i = ch * 128 + t128;
    prm[0] = __ldg(are + i); prm[1] = __ldg(aim + i); prm[2] = __ldg(bre + i); prm[3] = __ldg(bim + i); prm[4] = __ldg(cre + i); prm[5] = __ldg(cim + i);
    ldt = __bfloat162float(logdt[ch]);
    for (int i2 = t128; i2 < A_ZEND / 16; i2 += 128) sts128(sb + wg * A_CH + i2 * 16, 0, 0, 0, 0);
  }
  {
    float v[16];
#pragma unroll
    for (int i = 0; i < 4; i++) { v[4 * i] = bf_lo(xr[i].x); v[4 * i + 1] = bf_hi(xr[i].x); v[4 * i + 2] = bf_lo(xr[i].y); v[4 * i + 3] = bf_hi(xr[i].y); }
    float s = 0.f;
#pragma unroll
    for (int i = 0; i < 16; i++) s += v[i];
#pragma unroll
    for (int o = 16; o; o >>= 1) s += __shfl_xor_sync(~0u, s, o);
    const float mean = s * (1.f / DM);
    float q = 0.f;
#pragma unroll
    for (int i = 0; i < 16; i++) { float d = v[i] - mean; if (i < 12 || lane < 16) q = fmaf(d, d, q); }
#pragma unroll
    for (int o = 16; o; o >>= 1) q += __shfl_xor_sync(~0u, q, o);
    const float rs = __frcp_rn(rbf(__fsqrt_rn(rbf(rbf(q * (1.f / DM)) + 1e-5f))));
    const uint32_t mm = pack_bf16(mean, mean);
    const uint32_t tu = sb + A_STG + warp * 912 + lane * 8, tx = tu + A_CH;
#pragma unroll
    for (int i = 0; i < 4; i++) {
      if (i < 3 || lane < 16) {
        const uint32_t d0 = hsub2_bf(xr[i].x, mm), d1 = hsub2_bf(xr[i].y, mm);
        sts64(tu + i * 256, pack_bf16(bf_lo(d0) * rs, bf_hi(d0) * rs), pack_bf16(bf_lo(d1) * rs, bf_hi(d1) * rs));
        sts64(tx + i * 256, xr[i].x, xr[i].y);
      }
    }
    __syncthreads();
#pragma unroll
    for (int i = 0; i < 4; i++) {
      const int cgp = warp + 16 * i;
      if (cgp < 56) {
        uint32_t r[4];
        asm volatile("ldmatrix.sync.aligned.m8n8.x4.trans.shared.b16 {%0,%1,%2,%3}, [%4];" : "=r"(r[0]), "=r"(r[1]), "=r"(r[2]), "=r"(r[3])
                     : "r"(sb + A_STG + (lane >> 4) * A_CH + (lane & 15) * 912 + cgp * 16) : "memory");
        g_ux[((size_t)(cgp * 8 + (lane >> 2)) * 128 + blk) * 4 + (lane & 3)] = make_uint4(r[0], r[1], r[2], r[3]);
      }
    }
    __syncthreads();
    if (tid == 0) asm volatile("red.release.gpu.global.add.u32 [%0], 1;" ::"l"(&g_cnt1) : "memory");
  }
  if (conv) {
    const uint4* wsrc = (blk < 56 ? wgate : wup) + (blk % 56) * 4 + (lane & 3) + (size_t)(warp * 8 + (lane >> 2)) * 224;
#pragma unroll
    for (int i2 = 0; i2 < 4; i2++) if (i2 < 3 || warp < 8) wv[i2] = __ldg(wsrc + (size_t)i2 * 128 * 224);
  }
  if (tid == 0) TR(0, 1);

  if (!conv) {
    const int a = blk - 112, mat = a >> 3, j = a & 7;
    if (a == 0 && tid == 0) g_epochB = ep;
    {
      const int rr = lane >> 2, cc = lane & 3;
#pragma unroll 4
      for (int it = warp; it < 196; it += 16) {
        const int rg = it / 14, cg = it % 14, k = rg * 8 + rr, ngg = cg * 4 + cc;
        const uint4 v = __ldg(wdown + (size_t)(a * 112 + k) * 56 + ngg);
        g_wimg[(size_t)(a >> 1) * 37632 + 25088 + ((ngg / 7) * 2 + (a & 1)) * 784 + (ngg % 7) * 112 + k] = v;
      }
    }
    float s[8];
#pragma unroll
    for (int k = 0; k < 8; k++) s[k] = 0.f;
    if (lane < 28) {
      const uint4* src = (mat ? wup : wgate) + j * 28 + lane + (size_t)warp * 224;
#pragma unroll 14
      for (int r = 0; r < 28; r++) {
        const uint4 v = __ldg(src + (size_t)r * 16 * 224);
        s[0] += bf_lo(v.x); s[1] += bf_hi(v.x); s[2] += bf_lo(v.y); s[3] += bf_hi(v.y);
        s[4] += bf_lo(v.z); s[5] += bf_hi(v.z); s[6] += bf_lo(v.w); s[7] += bf_hi(v.w);
      }
      float4* red = (float4*)(sm + warp * 896 + lane * 32);
      red[0] = make_float4(s[0], s[1], s[2], s[3]); red[1] = make_float4(s[4], s[5], s[6], s[7]);
    }
    __syncthreads();
    if (tid < 224) {
      float t = 0.f;
#pragma unroll
      for (int w = 0; w < 16; w++) t += *(const float*)(sm + w * 896 + tid * 4);
      const float hi = rbf(t), mid = rbf(t - hi), lo = rbf(t - hi - mid);
      const int q = tid / 112, n = tid % 112 + 112 * mat;
      __nv_bfloat16* dst = (__nv_bfloat16*)(g_cimg + (j * 2 + q) * 224 + (n >> 3) * 8) + (n & 7);
      dst[0] = __float2bfloat16_rn(hi); dst[8] = __float2bfloat16_rn(mid); dst[16] = __float2bfloat16_rn(lo);
#pragma unroll
      for (int k = 3; k < 8; k++) dst[8 * k] = __float2bfloat16_rn(0.f);
    }
    if (tid == 0) TR(0, 10);
    return;
  }

  const uint32_t cb = sb + wg * A_CH;
  const int g = lane >> 2, t = lane & 3;
  {
    const uint32_t stg = cb + A_STG + wq * 6528;
    const float dt = rbf(expf(ldt));
    float lr[2], li[2];
    cf bq[2], b0[2], b4[2];
    uint32_t bf[48];
#pragma unroll
    for (int m = 0; m < 2; m++) {
      lr[m] = dt * (m ? bf_hi(prm[0]) : bf_lo(prm[0]));
      li[m] = dt * (m ? bf_hi(prm[1]) : bf_lo(prm[1]));
    }
    {
      cf b[2], z[2];
#pragma unroll
      for (int m = 0; m < 2; m++) {
        cf db, c;
        db.x = dt * (m ? bf_hi(prm[2]) : bf_lo(prm[2])); db.y = -dt * (m ? bf_hi(prm[3]) : bf_lo(prm[3]));
        c.x = m ? bf_hi(prm[4]) : bf_lo(prm[4]); c.y = -(m ? bf_hi(prm[5]) : bf_lo(prm[5]));
        b[m] = cmul(c, db);
        z[m] = cexp_l(lr[m], -li[m], 1.f);
        bq[m] = cexp_l(lr[m], -li[m], 256.f);
      }
#pragma unroll
      for (int i = 0; i < 8; i++) {
        sts64(stg + i * 272 + lane * 8, pack_bf16(b[0].x, b[0].y), pack_bf16(b[1].x, b[1].y));
        if (!(i & 1)) {
          cf e0 = cmul(b[0], bq[0]), e1 = cmul(b[1], bq[1]);
          sts64(stg + (8 + i / 2) * 272 + lane * 8, pack_bf16(e0.x, e0.y), pack_bf16(e1.x, e1.y));
          if (i == 0) { b0[0] = e0; b0[1] = e1; }
          if (i == 4) { b4[0] = e0; b4[1] = e1; }
        }
        if (i < 7) { b[0] = cmul(b[0], z[0]); b[1] = cmul(b[1], z[1]); }
      }
#pragma unroll
      for (int i = 0; i < 7; i++) {
        b0[0] = cmul(b0[0], bq[0]); b0[1] = cmul(b0[1], bq[1]);
        sts64(stg + (i < 2 ? 12 + 2 * i : 14 + i) * 272 + lane * 8, pack_bf16(b0[0].x, b0[0].y), pack_bf16(b0[1].x, b0[1].y));
        if (i < 2) {
          b4[0] = cmul(b4[0], bq[0]); b4[1] = cmul(b4[1], bq[1]);
          sts64(stg + (13 + 2 * i) * 272 + lane * 8, pack_bf16(b4[0].x, b4[0].y), pack_bf16(b4[1].x, b4[1].y));
        }
      }
    }
    __syncwarp();
#pragma unroll
    for (int n = 0; n < 3; n++)
#pragma unroll
      for (int k2 = 0; k2 < 4; k2++) ldsm4(bf + n * 16 + k2 * 4, stg + (n * 8 + (lane & 7)) * 272 + k2 * 64 + (lane >> 3) * 16);
    float c[6][4];
#pragma unroll
    for (int i = 0; i < 6; i++) { c[i][0] = 0.f; c[i][1] = 0.f; c[i][2] = 0.f; c[i][3] = 0.f; }
    cf p[2], v[2];
    p[0] = cexp_l(lr[0], li[0], 8.f); p[1] = cexp_l(lr[1], li[1], 8.f);
    v[0].x = 1.f; v[0].y = 0.f; v[1] = v[0];
#pragma unroll
    for (int mt = 0; mt < 2; mt++) {
      __syncwarp();
#pragma unroll
      for (int i = 0; i < 16; i++) {
        sts64(stg + i * 272 + lane * 8, pack_bf16(v[0].x, v[0].y), pack_bf16(v[1].x, v[1].y));
        if (mt == 0 && i == 0) { v[0] = p[0]; v[1] = p[1]; }
        else if (mt == 0 || i < 15) { v[0] = cmul(v[0], p[0]); v[1] = cmul(v[1], p[1]); }
      }
      __syncwarp();
#pragma unroll
      for (int ks = 0; ks < 8; ks++) {
        uint32_t a[4];
        ldsm4(a, stg + (lane & 15) * 272 + ks * 32 + (lane >> 4) * 16);
#pragma unroll
        for (int n = 0; n < 3; n++) mma16816(c[n * 2 + mt], a, bf[n * 16 + ks * 2], bf[n * 16 + ks * 2 + 1]);
      }
    }
    __syncwarp();
#pragma unroll
    for (int i = 0; i < 6; i++)
      sts128(stg + i * 512 + lane * 16, __float_as_uint(c[i][0]), __float_as_uint(c[i][1]), __float_as_uint(c[i][2]), __float_as_uint(c[i][3]));
    {
      const int ngg = (blk % 56) * 4 + (lane & 3), j = ngg / 28, q = (ngg % 28) / 14, ng = ngg % 14 + (blk < 56 ? 0 : 14);
      uint4* dst = g_wimg + (size_t)j * 37632 + q * 14 * 896 + ng * 32 + (warp >> 2) * 896 + (warp & 3) * 8 + (lane >> 2);
#pragma unroll
      for (int i2 = 0; i2 < 4; i2++) if (i2 < 3 || warp < 8) dst[i2 * 4 * 896] = wv[i2];
    }
    bar_sync(1 + wg, 128);
    if (tid == 0) TR(0, 2);
#pragma unroll
    for (int rep = 0; rep < 2; rep++) {
      const int qd = rep ? 4 + wq : wq;
      if (rep == 0 || wq < 2) {
        float s[4] = {0.f, 0.f, 0.f, 0.f};
#pragma unroll
        for (int w = 0; w < 4; w++) {
          uint4 u4 = lds128(cb + A_STG + w * 6528 + qd * 512 + lane * 16);
          s[0] += __uint_as_float(u4.x); s[1] += __uint_as_float(u4.y); s[2] += __uint_as_float(u4.z); s[3] += __uint_as_float(u4.w);
        }
#pragma unroll
        for (int hf = 0; hf < 2; hf++) {
          const int j = (qd & 1) * 16 + g + 8 * hf;
          const uint32_t pk = pack_bf16(s[2 * hf + 1], s[2 * hf]);
          const uint32_t v0 = pk >> 16, v1 = pk & 0xFFFFu, v00 = v0 * 0x10001u;
          if (rep == 1) {
            if (t < 2) {
#pragma unroll
              for (int e = 0; e < 2; e++) {
                const int lam = 128 + 32 * (2 * t + e) + j, mu = lam >> 1;
                const uint32_t val = e ? v1 : v0;
                uint32_t a = cb + ((lam & 1) ? A_R3B : A_R3A) + mu * 4;
                if (lam == 128) { a = cb + A_R2A + 128 * 4; sts32(cb + A_K1024, val << 16); }
                sts16(a, val); sts16(a + 6, val);
              }
            } else if (t == 2 && j == 0) { sts16(cb + A_R3A + 128 * 4, v0); }
          } else if (wq < 2) {
            const uint32_t a = cb + A_R1 + (62 + 8 * j + 2 * t) * 4;
            sts16(a, v0); sts32(a + 4, pk); sts16(a + 10, v1);
          } else if (t < 2) {
            const int L = 256 + 8 * j + 4 * t;
            const uint32_t a = cb + A_R1 + (62 + L) * 4;
            if (L > 256) { sts16(a - 4, v0); sts32(a, v00); } else sts16(a, v0);
            sts32(a + 4, v00); sts32(a + 8, pk); sts16(a + 14, v1);
          } else {
            const int mu = 64 + 32 * (t - 2) + j;
            if (mu == 64) {
              const uint32_t a = cb + A_R1 + (62 + 512) * 4;
              sts16(a - 4, v0); sts32(a, v00); sts32(a + 4, v00); sts32(a + 8, v00); sts16(a + 14, v0);
            } else { sts16(cb + A_R2A + mu * 4, v0); sts16(cb + A_R2A + mu * 4 + 6, v0); }
            sts16(cb + A_R2B + mu * 4, v1); sts16(cb + A_R2B + mu * 4 + 6, v1);
          }
        }
      }
    }
  }
  if (tid == 0) TR(0, 3);

  uint32_t xt[8], ud[8];
  {
    if (lane == 0) {
      uint32_t v; int it = 0;
      do { asm volatile("ld.acquire.gpu.global.u32 %0, [%1];" : "=r"(v) : "l"(&g_cnt1) : "memory"); } while ((int)(v - ep * 128u) < 0 && ++it < 200000);
    }
    __syncwarp();
    const uint4* src = g_ux + ((size_t)ch * 128 + t128) * 4;
    uint4 r[4];
#pragma unroll
    for (int i = 0; i < 4; i++) asm volatile("ld.global.v4.u32 {%0,%1,%2,%3}, [%4];" : "=r"(r[i].x), "=r"(r[i].y), "=r"(r[i].z), "=r"(r[i].w) : "l"(src + i) : "memory");
    const uint32_t dk = (uint32_t)__ldg((const unsigned short*)dskip + ch) * 0x10001u;
    const uint32_t ua = cb + A_UB + ((2 * t128) & 7) * 656 + ((t128 >> 2) + 9) * 16;
    sts128(ua, r[0].x, r[1].x, r[2].x, r[3].x);
    sts128(ua + 656, r[0].y, r[1].y, r[2].y, r[3].y);
#pragma unroll
    for (int i = 0; i < 4; i++) { ud[i] = hmul2_bf(r[i].x, dk); ud[4 + i] = hmul2_bf(r[i].y, dk); xt[i] = r[i].z; xt[4 + i] = r[i].w; }
  }
  bar_sync(1 + wg, 128);
  if (tid == 0) TR(0, 4);
#pragma unroll
  for (int c = 0; c < 2; c++) {
    if (c == 0 || t128 <= 64) {
      const int tp = c == 0 ? t128 : t128 == 64 ? -1 : 128 + t128;
      const uint32_t b = cb;
      const uint4 pv = lds128(b + A_UB + ((tp - 1) & 7) * 656 + (((tp - 1) >> 3) + 9) * 16);
      const uint4 cu = lds128(b + A_UB + (tp & 7) * 656 + ((tp >> 3) + 9) * 16);
      const uint4 nx = lds128(b + A_UB + ((tp + 1) & 7) * 656 + (((tp + 1) >> 3) + 9) * 16);
      const float e[16] = {bf_lo(pv.z), bf_hi(pv.z), bf_lo(pv.w), bf_hi(pv.w), bf_lo(cu.x), bf_hi(cu.x), bf_lo(cu.y), bf_hi(cu.y),
                           bf_lo(cu.z), bf_hi(cu.z), bf_lo(cu.w), bf_hi(cu.w), bf_lo(nx.x), bf_hi(nx.x), bf_lo(nx.y), bf_hi(nx.y)};
      float w[8];
#pragma unroll
      for (int i = 0; i < 8; i++) w[i] = e[i + 4] + (e[i + 3] + e[i + 5]);
      sts64(b + A_W3 + (tp + 64) * 16 + 8, pack_bf16(w[0], w[1]), pack_bf16(w[2], w[3]));
      sts64(b + A_W3 + (tp + 65) * 16, pack_bf16(w[4], w[5]), pack_bf16(w[6], w[7]));
#pragma unroll
      for (int i = 0; i < 8; i++) w[i] += e[i + 2] + e[i + 6];
      sts128(b + A_W5 + (tp + 64) * 16, pack_bf16(w[0], w[1]), pack_bf16(w[2], w[3]), pack_bf16(w[4], w[5]), pack_bf16(w[6], w[7]));
      if (tp < 128) {
#pragma unroll
        for (int i = 0; i < 8; i++) w[i] += e[i + 1] + e[i + 7];
        if (tp < 127) sts128(b + A_W7 + ((tp + 1) & 1) * 1024 + ((tp + 1) >> 1) * 16, pack_bf16(w[0], w[1]), pack_bf16(w[2], w[3]), pack_bf16(w[4], w[5]), pack_bf16(w[6], w[7]));
#pragma unroll
        for (int i = 0; i < 8; i++) w[i] += e[i] + e[i + 8];
        if (tp < 126) sts128(b + A_W9 + (tp & 1) * 1024 + ((tp + 2) >> 1) * 16, pack_bf16(w[0], w[1]), pack_bf16(w[2], w[3]), pack_bf16(w[4], w[5]), pack_bf16(w[6], w[7]));
        if (tp >= 0) sts128(b + A_V + tp * 16, pack_bf16(e[0] + e[1], e[1] + e[2]), pack_bf16(e[2] + e[3], e[3] + e[4]), pack_bf16(e[4] + e[5], e[5] + e[6]), pack_bf16(e[6] + e[7], e[7] + e[8]));
      }
    }
  }
  asm volatile("fence.proxy.async.shared::cta;" ::: "memory");
  bar_sync(1 + wg, 128);
  if (tid == 0) TR(0, 5);

  {
    const uint32_t cbu = __shfl_sync(~0u, cb, 0);
    const uint32_t blo_k = ((cbu & 0x3FFFF) >> 4) | (41u << 16);
    const uint32_t blo_n = ((cbu & 0x3FFFF) >> 4) | (8u << 16);
    const uint32_t tb = cb + (16 * wq + g - 2 * t) * 4;
    float y1[16], y2[12], y3[8];
    uint32_t qa[32], qb[32];
    const uint32_t t1 = tb + A_R1 + (62 - 48) * 4;
    load_quads<4>(qa, tb + A_R3A + 17 * 4); load_quads<4>(qa + 16, tb + A_R3B + 16 * 4);
    wg_fence();
    s3_steps<0, 4, A_W9, 1>(y3, qa, blo_n); s3_steps<0, 4, A_W7, 0>(y3, qa + 16, blo_n);
    wg_commit();
    load_quads<8>(qb, tb + A_R2A + 16 * 4);
    wg_fence(); s2_steps<0, 8, A_W5, 1>(y2, qb, blo_n); wg_commit();
    wg_wait<1>(); load_quads<8>(qa, tb + A_R2B + 16 * 4);
    wg_fence(); s2_steps<0, 8, A_W3, 0>(y2, qa, blo_n); wg_commit();
    wg_wait<1>(); load_quads<8>(qb, t1);
    wg_fence(); f1_steps<0, 8>(y1, qb, blo_k); wg_commit();
    wg_wait<1>(); load_quads<8>(qa, t1 + 8 * 64);
    wg_fence(); f1_steps<8, 8>(y1, qa, blo_k); wg_commit();
    reg_fence(y2); reg_fence(y3);
    {
      const float k1024 = __uint_as_float(lds32(cb + A_K1024));
#pragma unroll
      for (int i = 0; i < 2; i++)
#pragma unroll
        for (int hf = 0; hf < 2; hf++) {
          const int idx = 16 * (16 * wq + g + 8 * hf) + 8 * i + 2 * t;
          const uint32_t vv = lds32(cb + A_V + idx * 2);
          sts64(cb + A_Y3 + (idx + 4 * (idx >> 6)) * 4, __float_as_uint(fmaf(k1024, bf_lo(vv), y3[4 * i + 2 * hf])),
                __float_as_uint(fmaf(k1024, bf_hi(vv), y3[4 * i + 2 * hf + 1])));
        }
#pragma unroll
      for (int i = 0; i < 3; i++)
#pragma unroll
        for (int hf = 0; hf < 2; hf++) {
          const int idx = 512 * i + 8 * (16 * wq + g + 8 * hf) + 2 * t;
          sts64(cb + A_Y2 + (idx + 4 * (idx >> 6)) * 4, __float_as_uint(y2[4 * i + 2 * hf]), __float_as_uint(y2[4 * i + 2 * hf + 1]));
        }
    }
    wg_wait<1>(); load_quads<8>(qb, t1 + 16 * 64);
    wg_fence(); f1_steps<16, 8>(y1, qb, blo_k); wg_commit();
    wg_wait<1>(); load_quads<8>(qa, t1 + 24 * 64);
    wg_fence(); f1_steps<24, 8>(y1, qa, blo_k); wg_commit();
    wg_wait<1>(); load_quads<5>(qb, t1 + 32 * 64);
    wg_fence(); f1_steps<32, 5>(y1, qb, blo_k); wg_commit();
    bar_sync(1 + wg, 128);
    float ex[12];
#pragma unroll
    for (int i = 1; i < 4; i++)
#pragma unroll
      for (int k = 0; k < 4; k++) {
        const int aa = 8 * i + 2 * t + (k & 1), b = 16 * wq + g + 8 * (k >> 1);
        float e = __uint_as_float(lds32(cb + A_Y2 + ((aa - 8) * 68 + b) * 4));
        if (i >= 2) e += __uint_as_float(lds32(cb + A_Y3 + ((aa - 16) * 68 + b) * 4));
        ex[4 * (i - 1) + k] = e;
      }
    wg_wait<0>();
    reg_fence(y1);
    if (tid == 0) TR(0, 6);
#pragma unroll
    for (int i = 0; i < 12; i++) y1[4 + i] += ex[i];
#pragma unroll
    for (int i = 0; i < 2; i++) {
      const int mi = lane >> 3, aa = 8 * (2 * i + (mi >> 1)) + (lane & 7);
      asm volatile("stmatrix.sync.aligned.m8n8.x4.trans.shared.b16 [%0], {%1,%2,%3,%4};"
                   ::"r"(cb + A_YB + aa * 128 + (((2 * wq + (mi & 1)) ^ (lane & 7)) << 4)),
                     "r"(pack_bf16(y1[8 * i], y1[8 * i + 1])), "r"(pack_bf16(y1[8 * i + 2], y1[8 * i + 3])),
                     "r"(pack_bf16(y1[8 * i + 4], y1[8 * i + 5])), "r"(pack_bf16(y1[8 * i + 6], y1[8 * i + 7])) : "memory");
    }
  }
  bar_sync(1 + wg, 128);
#pragma unroll
  for (int c = 0; c < 2; c++) {
    const int tau = 2 * t128 + c, r = ch & 7;
    const uint4 y = lds128(cb + A_YB + (tau >> 3) * 128 + (((tau ^ (tau >> 3)) & 7) << 4));
    g_himg[(size_t)(tau >> 4) * 7168 + (ch >> 3) * 128 + ((tau >> 3) & 1) * 64 + r * 8 + ((tau & 7) ^ r)] =
        make_uint4(hadd2_bf(xt[4 * c], hadd2_bf(y.x, ud[4 * c])), hadd2_bf(xt[4 * c + 1], hadd2_bf(y.y, ud[4 * c + 1])),
                   hadd2_bf(xt[4 * c + 2], hadd2_bf(y.z, ud[4 * c + 2])), hadd2_bf(xt[4 * c + 3], hadd2_bf(y.w, ud[4 * c + 3])));
  }
  if (tid == 0) TR(0, 7);
}

constexpr int B_SA = 0, B_RING = 114688, B_SLOT = 14848, B_NSLOT = 7;
constexpr int B_CS = B_RING + B_NSLOT * B_SLOT;
constexpr int B_STAT = B_CS + 7168;
constexpr int B_BAR = B_STAT + 512;
constexpr int B_SMEM = B_BAR + 512;

__device__ __forceinline__ uint32_t mapa(uint32_t a, uint32_t r) { uint32_t o; asm("mapa.shared::cluster.u32 %0, %1, %2;" : "=r"(o) : "r"(a), "r"(r)); return o; }

template <int Q, int ST>
__device__ __forceinline__ void g1_stage(float (&acc)[116], uint32_t alo, uint32_t blo, uint32_t bar_full, uint32_t bar_h) {
  constexpr int s = Q * 14 + ST, sl = s % B_NSLOT;
  if (Q == 0) mbar_wait(bar_h + 8 * ST, 0);
  mbar_wait(bar_full + 8 * sl, (s / B_NSLOT) & 1);
  wg_fence();
  if (Q == 0) {
    wgmma_ss232<(2 * ST) * 256, 0x40000080u, (sl * B_SLOT) / 16, 32, ST != 0>(acc, alo, blo);
    wgmma_ss232<(2 * ST + 1) * 256, 0x40000080u, (sl * B_SLOT + 256) / 16, 32, 1>(acc, alo, blo);
  } else {
    wgmma_ss224<(2 * ST) * 256, 0x40000080u, (sl * B_SLOT) / 16, 32, ST != 0>(*(float(*)[112])acc, alo, blo);
    wgmma_ss224<(2 * ST + 1) * 256, 0x40000080u, (sl * B_SLOT + 256) / 16, 32, 1>(*(float(*)[112])acc, alo, blo);
  }
}

__global__ void __cluster_dims__(2, 1, 1) __launch_bounds__(384, 1) k_ffn(__nv_bfloat16* __restrict__ out) {
  extern __shared__ __align__(1024) unsigned char sm[];
  const uint32_t sb = s2u(sm);
  const int tid = threadIdx.x, wg = tid >> 7, warp = tid >> 5, lane = tid & 31;
  const int rank = blockIdx.x & 1, rt = blockIdx.x & 15, j = blockIdx.x >> 4;
  const uint32_t bar_full = sb + B_BAR, bar_empty = bar_full + 64, bar_h = bar_full + 128, bar_cs = bar_full + 240, bar_stat = bar_full + 248,
                 bar_adead = bar_full + 256, bar_in = bar_full + 264;
  if (tid == 0) {
    TR(1, 0);
    for (int i = 0; i < B_NSLOT; i++) { mbar_init(bar_full + 8 * i, 1); mbar_init(bar_empty + 8 * i, 4); }
    for (int i = 0; i < 14; i++) mbar_init(bar_h + 8 * i, 1);
    mbar_init(bar_cs, 1);
    mbar_init(bar_stat, 32);
    mbar_init(bar_adead, 2);
    for (int i = 0; i < 14; i++) mbar_init(bar_in + 8 * i, 1);
    asm volatile("fence.mbarrier_init.release.cluster;" ::: "memory");
  }
  if (tid >= 128 && tid < 128 + 224) {
    const int i = tid - 128;
    *(uint4*)(sm + B_RING + (i >> 5) * B_SLOT + 14336 + (i & 31) * 16) = make_uint4(0x3F803F80u, 0x3F803F80u, 0x3F803F80u, 0x3F803F80u);
    asm volatile("fence.proxy.async.shared::cta;" ::: "memory");
  }
  __syncthreads();
  asm volatile("barrier.cluster.arrive.release.aligned;" ::: "memory");

  if (wg == 2) {
    asm volatile("setmaxnreg.dec.sync.aligned.u32 88;");
    asm volatile("barrier.cluster.wait.acquire.aligned;" ::: "memory");
    asm volatile("griddepcontrol.wait;" ::: "memory");
    if (warp == 8) {
      if (lane == 0) {
        const char* wsrc = (const char*)g_wimg + (size_t)j * 602112;
        TR(1, 1);
        int slot = 0, ph = 0;
        for (int s = 0; s < 44; s++) {
          if (s >= B_NSLOT) mbar_wait(bar_empty + 8 * slot, ph ^ 1);
          uint32_t dst = sb + B_RING + slot * B_SLOT, fb = bar_full + 8 * slot;
          if (s < 28) {
            mbar_expect(fb, 14336);
            bulk_ld_mc(dst + rank * 7168, wsrc + s * 14336 + rank * 7168, 7168, fb);
          } else {
            const int c = (j + 1 + ((s - 28) >> 1)) & 7;
            mbar_expect(fb, 12544);
            bulk_ld_mc(dst + rank * 6272, wsrc + 401408 + (c * 2 + (s & 1)) * 12544 + rank * 6272, 6272, fb);
          }
          if (++slot == B_NSLOT) { slot = 0; ph ^= 1; }
        }
      }
    } else if (warp == 9) {
      if (lane == 0) {
        const char* hsrc = (const char*)g_himg + (size_t)rt * 114688;
        for (int i = 0; i < 14; i++) {
          mbar_expect(bar_h + 8 * i, 8192);
          bulk_ld(sb + B_SA + i * 8192, hsrc + i * 8192, 8192, bar_h + 8 * i);
        }
        mbar_expect(bar_cs, 7168);
        bulk_ld(sb + B_CS, g_cimg + j * 448, 7168, bar_cs);
      }
    } else {
      const int t64 = tid - 320;
      const uint32_t ep = __ldcg(&g_epochB), tag = ep & 1u;
      if (blockIdx.x == 0 && t64 == 0) g_epochA = ep;
      {
        const int r = (lane >> 1) & 7, c = (j & 3) * 2 + (lane & 1);
        const unsigned char* src = sm + B_SA + (t64 >> 4) * 2048 + (j >> 2) * 1024 + r * 128 + ((c ^ r) << 4);
        float a[16];
#pragma unroll
        for (int k = 0; k < 16; k++) a[k] = 0.f;
#pragma unroll 1
        for (int i = 0; i < 14; i++) {
          mbar_wait(bar_h + 8 * i, 0);
          uint4 v = *(const uint4*)(src + i * 8192);
          float e[8] = {bf_lo(v.x), bf_hi(v.x), bf_lo(v.y), bf_hi(v.y), bf_lo(v.z), bf_hi(v.z), bf_lo(v.w), bf_hi(v.w)};
#pragma unroll
          for (int k = 0; k < 8; k++) { a[2 * k] += e[k]; a[2 * k + 1] = fmaf(e[k], e[k], a[2 * k + 1]); }
          __nanosleep(160);
        }
#pragma unroll
        for (int rd = 0; rd < 4; rd++) {
          const int n = 8 >> rd;
          const bool up = lane & (2 * n);
#pragma unroll
          for (int k = 0; k < 8; k++) {
            if (k < n) {
              float keep = up ? a[k + n] : a[k], give = up ? a[k] : a[k + n];
              a[k] = keep + __shfl_xor_sync(~0u, give, 2 * n);
            }
          }
        }
        float* red = (float*)(sm + B_STAT);
        red[(warp & 1) * 32 + (lane & 1) * 16 + (lane >> 1)] = a[0];
        asm volatile("bar.sync 1, 64;" ::: "memory");
        if (t64 < 16) {
          float mean = (red[2 * t64] + red[32 + 2 * t64]) * (1.f / DM);
          float var = fmaxf(fmaf(-mean, mean, (red[2 * t64 + 1] + red[33 + 2 * t64]) * (1.f / DM)), 0.f);
          float rs = __frcp_rn(rbf(__fsqrt_rn(rbf(rbf(var) + 1e-5f))));
          asm volatile("st.relaxed.gpu.global.u32 [%0], %1;"
                       ::"l"(g_stat2 + rt * 128 + j * 16 + t64), "r"((__float_as_uint(rs * rs) & ~1u) | tag) : "memory");
        }
        if (t64 == 0) TR(1, 2);
      }
      __syncwarp();
      if (warp == 10) {
        mbar_wait(bar_adead, 0);
        uint32_t w[4];
        int it = 0;
        do { ld128((const uint4*)(g_stat2 + rt * 128) + lane, w); } while ((((w[0] ^ tag) | (w[1] ^ tag) | (w[2] ^ tag) | (w[3] ^ tag)) & 1u) && ++it < 200000);
        *(uint4*)(sm + B_STAT + lane * 16) = make_uint4(w[0], w[1], w[2], w[3]);
        mbar_arrive(bar_stat);
      }
      if (t64 == 0) TR(1, 18);
      if (warp == 11) {
        mbar_wait(bar_adead, 0);
        bool todo = lane < 14;
        int it = 0;
        while (__any_sync(~0u, todo) && ++it < 200000) {
          if (todo) {
            uint32_t w[4];
            ld128(g_flag + (rt * 8 + j) * 16 + lane, w);
            if (w[0] == ep && w[1] == ep && w[2] == ep && w[3] == ep) {
              const uint32_t b = bar_in + 8 * ((lane & 1) * 7 + (lane >> 1));
              asm volatile("fence.proxy.async.global;" ::: "memory");
              mbar_expect(b, 7168);
              bulk_ld(sb + B_SA + lane * 7168, g_part + (size_t)((rt * 8 + j) * 7) * 896 + lane * 448, 7168, b);
              todo = false;
              if (!(lane & 1)) TR(1, 24 + (lane >> 1));
            }
          }
        }
      }
    }
  } else {
    asm volatile("setmaxnreg.inc.sync.aligned.u32 208;");
    const int g = lane >> 2, t = lane & 3, wq = warp & 3, t128 = tid & 127;
    uint32_t hh[56], hres[16];
    asm volatile("barrier.cluster.wait.acquire.aligned;" ::: "memory");
    asm volatile("griddepcontrol.wait;" ::: "memory");
    const uint32_t ep = __ldcg(&g_epochB), tag = (ep & 1u) << 16;
    const uint32_t rel_bar = mapa(bar_empty, t128 & 1);
    auto release = [&](int sl) { if (t128 < 2) asm volatile("mbarrier.arrive.shared::cluster.b64 _, [%0];" ::"r"(rel_bar + 8 * sl) : "memory"); };
    const uint32_t alo = __shfl_sync(~0u, ((sb + B_SA + wg * 1024) & 0x3FFFF) >> 4, 0);
    const uint32_t blo = (((sb + B_RING) & 0x3FFFF) >> 4) | (8u << 16);
    const uint32_t clo = ((sb + B_CS) & 0x3FFFF) >> 4;
    uint32_t nm0, nm1;
    if (wg == 1) asm volatile("bar.sync 3, 256;" ::: "memory");
#define G1S(Q, ST) do { g1_stage<Q, ST>(acc, alo, blo, bar_full, bar_h); wg_commit(); \
      if (ST > 0) { wg_wait<1>(); release((Q * 14 + ST - 1) % B_NSLOT); } } while (0)
#define G1HH(Q) do { \
      _Pragma("unroll") \
      for (int i = 0; i < 28; i++) hh[28 * Q + i] = pack_bf16(acc[2 * i] * acc[56 + 2 * i], acc[2 * i + 1] * acc[57 + 2 * i]); \
    } while (0)
    {
      float acc[116];
      G1S(0, 0);
      if (tid == 0) TR(1, 3);
      G1S(0, 1);
      if (wg == 0) asm volatile("bar.arrive 3, 256;" ::: "memory");
      G1S(0, 2); G1S(0, 3); G1S(0, 4); G1S(0, 5); G1S(0, 6); G1S(0, 7); G1S(0, 8); G1S(0, 9); G1S(0, 10); G1S(0, 11); G1S(0, 12);
      G1S(0, 13);
      if (tid == 0) TR(1, 4);
      mbar_wait(bar_cs, 0);
      wg_wait<0>(); reg_fence(acc); release(13 % B_NSLOT);
      {
        const uint32_t msk = t == 0 ? 0xFFFFFFFFu : t == 1 ? 0xFFFFu : 0u;
        const float a = acc[112] * (-1.f / DM), b = acc[114] * (-1.f / DM);
        nm0 = pack_bf16(a, a) & msk; nm1 = pack_bf16(b, b) & msk;
      }
      wg_fence();
      wgmma_rs224<0, 8, 1>(*(float(*)[112])acc, nm0, nm1, 0u, 0u, clo);
      wg_commit(); wg_wait<0>(); reg_fence(acc);
      G1HH(0);
      if (tid == 0) TR(1, 5);
      G1S(1, 0); G1S(1, 1); G1S(1, 2); G1S(1, 3); G1S(1, 4); G1S(1, 5); G1S(1, 6); G1S(1, 7); G1S(1, 8); G1S(1, 9); G1S(1, 10); G1S(1, 11);
#pragma unroll
      for (int i = 0; i < 4; i++) {
        int qq = lane >> 3, r = lane & 7, kg = 7 * j + 2 * i + (qq >> 1), c = 2 * wq + (qq & 1);
        if (kg > 55) kg = 55;
        uint32_t addr = sb + B_SA + kg * 2048 + wg * 1024 + r * 128 + ((c ^ r) << 4);
        asm volatile("ldmatrix.sync.aligned.m8n8.x4.trans.shared.b16 {%0,%1,%2,%3}, [%4];"
                     : "=r"(hres[4 * i]), "=r"(hres[4 * i + 1]), "=r"(hres[4 * i + 2]), "=r"(hres[4 * i + 3]) : "r"(addr) : "memory");
      }
      G1S(1, 12);
      g1_stage<1, 13>(acc, alo, blo, bar_full, bar_h);
      wgmma_rs224<224, 8, 1>(*(float(*)[112])acc, nm0, nm1, 0u, 0u, clo);
      wg_commit(); wg_wait<1>(); release(26 % B_NSLOT);
      wg_wait<0>(); reg_fence(acc); release(27 % B_NSLOT);
      G1HH(1);
      if (t128 == 0) mbar_arrive(bar_adead);
      if (tid == 0) TR(1, 6);
    }
    float accA[28], accB[28], sum[28];
    int nxt = 0;
#pragma unroll
    for (int i = 0; i < 28; i++) sum[i] = 0.f;
#define ISSUE(acc, I, a, FIRST) do { \
      constexpr int s_ = 28 + (I), sl_ = s_ % B_NSLOT; \
      mbar_wait(bar_full + 8 * sl_, (s_ / B_NSLOT) & 1); \
      wg_fence(); \
      wgmma_rs56<(sl_ * B_SLOT + 0 * 256) / 16, 112, !(FIRST)>(acc, (a)[0], (a)[1], (a)[2], (a)[3], blo); \
      wgmma_rs56<(sl_ * B_SLOT + 1 * 256) / 16, 112, 1>(acc, (a)[4], (a)[5], (a)[6], (a)[7], blo); \
      wgmma_rs56<(sl_ * B_SLOT + 2 * 256) / 16, 112, 1>(acc, (a)[8], (a)[9], (a)[10], (a)[11], blo); \
      wgmma_rs56<(sl_ * B_SLOT + 3 * 256) / 16, 112, 1>(acc, (a)[12], (a)[13], (a)[14], (a)[15], blo); \
      wgmma_rs56<(sl_ * B_SLOT + 4 * 256) / 16, 112, 1>(acc, (a)[16], (a)[17], (a)[18], (a)[19], blo); \
      wgmma_rs56<(sl_ * B_SLOT + 5 * 256) / 16, 112, 1>(acc, (a)[20], (a)[21], (a)[22], (a)[23], blo); \
      wgmma_rs56<(sl_ * B_SLOT + 6 * 256) / 16, 112, 1>(acc, (a)[24], (a)[25], (a)[26], (a)[27], blo); \
      wg_commit(); } while (0)
    auto rel = [&](int i) { if (i < 9) release((28 + i) % B_NSLOT); };
    auto tg = [&](uint32_t v) { return (v & 0xFFFEFFFFu) | tag; };
    auto send_lo = [&](float (&acc)[28], int cc) {
      reg_fence(acc);
      uint4* dst = g_part + (size_t)((rt * 8 + ((j + 1 + cc) & 7)) * 7 + cc) * 896 + wg * 448 + t128;
#pragma unroll
      for (int q = 0; q < 2; q++)
        st128(dst + q * 128, pack_bf16(acc[8 * q], acc[8 * q + 1]), pack_bf16(acc[8 * q + 2], acc[8 * q + 3]),
              pack_bf16(acc[8 * q + 4], acc[8 * q + 5]), tg(pack_bf16(acc[8 * q + 6], acc[8 * q + 7])));
    };
    auto send_hi = [&](float (&acc)[28], int cc) {
      uint4* dst = g_part + (size_t)((rt * 8 + ((j + 1 + cc) & 7)) * 7 + cc) * 896 + wg * 448;
      st128(dst + 256 + t128, pack_bf16(acc[16], acc[17]), pack_bf16(acc[18], acc[19]), pack_bf16(acc[20], acc[21]), tg(pack_bf16(acc[22], acc[23])));
      asm volatile("{\n.reg .b64 v;\nmov.b64 v, {%1, %2};\nst.relaxed.gpu.global.b64 [%0], v;\n}"
                   ::"l"((uint2*)(dst + 384) + t128), "r"(pack_bf16(acc[24], acc[25])), "r"(tg(pack_bf16(acc[26], acc[27]))) : "memory");
      if (lane == 0)
        asm volatile("st.relaxed.gpu.global.u32 [%0], %1;" ::"l"((uint32_t*)(g_flag + (rt * 8 + ((j + 1 + cc) & 7)) * 16 + cc * 2 + wg) + wq), "r"(ep) : "memory");
    };
    auto accum = [&]() {
      const unsigned char* src = sm + B_SA + nxt * 14336 + wg * 7168;
      uint4 a = *(const uint4*)(src + t128 * 16), b = *(const uint4*)(src + 2048 + t128 * 16), c = *(const uint4*)(src + 4096 + t128 * 16);
      uint2 d = *(const uint2*)(src + 6144 + t128 * 8);
      uint32_t in[14] = {a.x, a.y, a.z, a.w, b.x, b.y, b.z, b.w, c.x, c.y, c.z, c.w, d.x, d.y};
      int it = 0;
      while ((((in[3] ^ tag) | (in[7] ^ tag) | (in[11] ^ tag) | (in[13] ^ tag)) & 0x10000u) && ++it < 200000) {
        const uint4* gs = g_part + (size_t)((rt * 8 + j) * 7 + nxt) * 896 + wg * 448;
#pragma unroll
        for (int i = 0; i < 3; i++) ld128(gs + i * 128 + t128, in + 4 * i);
        asm volatile("{\n.reg .b64 v;\nld.relaxed.gpu.global.b64 v, [%2];\nmov.b64 {%0, %1}, v;\n}"
                     : "=r"(in[12]), "=r"(in[13]) : "l"((const uint2*)(gs + 384) + t128) : "memory");
      }
#pragma unroll
      for (int i = 0; i < 14; i++) { sum[2 * i] += bf_lo(in[i]); sum[2 * i + 1] += bf_hi(in[i]); }
      nxt++;
    };
    auto try_accum = [&]() {
      uint32_t ok;
      asm volatile("{\n.reg .pred p;\nmbarrier.test_wait.parity.shared::cta.b64 p, [%1], 0;\nselp.u32 %0, 1, 0, p;\n}"
                   : "=r"(ok) : "r"(bar_in + 8 * (wg * 7 + nxt)) : "memory");
      if (__all_sync(~0u, ok)) accum();
    };
#define CHUNK(cur, prev, CC, EXTRA) do { \
      ISSUE(cur, 2 * (CC), hh, true); wg_wait<1>(); rel(2 * (CC) - 1); send_lo(prev, (CC) - 1); \
      ISSUE(cur, 2 * (CC) + 1, hh + 28, false); send_hi(prev, (CC) - 1); EXTRA; wg_wait<1>(); rel(2 * (CC)); } while (0)
    ISSUE(accA, 0, hh, true);
    ISSUE(accA, 1, hh + 28, false); wg_wait<1>(); rel(0);
    CHUNK(accB, accA, 1, );
    if (tid == 0) TR(1, 11);
    CHUNK(accA, accB, 2, );
    if (tid == 0) TR(1, 12);
    CHUNK(accB, accA, 3, try_accum());
    if (tid == 0) TR(1, 13);
    CHUNK(accA, accB, 4, try_accum());
    if (tid == 0) TR(1, 14);
    CHUNK(accB, accA, 5, try_accum());
    if (tid == 0) TR(1, 16);
    CHUNK(accA, accB, 6, try_accum());
    if (tid == 0) TR(1, 17);
    CHUNK(accB, accA, 7, try_accum());
    if (tid == 0) TR(1, 7);
#pragma unroll 1
    while (nxt < 7) { mbar_wait(bar_in + 8 * (wg * 7 + nxt), 0); accum(); }
    wg_wait<0>();
    reg_fence(accB);
    if (tid == 0) TR(1, 9);
    mbar_wait(bar_stat, 0);
    const float r20 = *(const float*)(sm + B_STAT + (wg * 64 + wq * 16 + g) * 4), r21 = *(const float*)(sm + B_STAT + (wg * 64 + wq * 16 + g + 8) * 4);
    const int row = rt * 128 + wg * 64 + wq * 16 + g;
    uint32_t* o0 = (uint32_t*)(out + (size_t)row * DM + 56 * j + 2 * t);
    uint32_t* o1 = o0 + 8 * DM / 2;
#pragma unroll
    for (int i = 0; i < 7; i++) {
      o0[4 * i] = hadd2_bf(hres[2 * i], pack_bf16((sum[4 * i] + accB[4 * i]) * r20, (sum[4 * i + 1] + accB[4 * i + 1]) * r20));
      o1[4 * i] = hadd2_bf(hres[2 * i + 1], pack_bf16((sum[4 * i + 2] + accB[4 * i + 2]) * r21, (sum[4 * i + 3] + accB[4 * i + 3]) * r21));
    }
    if (tid == 0) TR(1, 10);
    if (tid == 128) TR(1, 15);

  }
}

extern "C" void kernel_launch(void* const* d_in, const int* in_sizes, int n_in, void* d_out, int out_size) {
  const __nv_bfloat16* x = (const __nv_bfloat16*)d_in[0];
  const __nv_bfloat16 *are = (const __nv_bfloat16*)d_in[1], *aim = (const __nv_bfloat16*)d_in[2], *bre = (const __nv_bfloat16*)d_in[3],
                      *bim = (const __nv_bfloat16*)d_in[4], *cre = (const __nv_bfloat16*)d_in[5], *cim = (const __nv_bfloat16*)d_in[6],
                      *logdt = (const __nv_bfloat16*)d_in[7], *dskip = (const __nv_bfloat16*)d_in[8];
  const __nv_bfloat16 *wg = (const __nv_bfloat16*)d_in[10], *wu = (const __nv_bfloat16*)d_in[11], *wd = (const __nv_bfloat16*)d_in[12];

  static bool init = false;
  if (!init) {
    init = true;
    cudaFuncSetAttribute(k_ffn, cudaFuncAttributeMaxDynamicSharedMemorySize, B_SMEM);
    cudaFuncSetAttribute(k_front, cudaFuncAttributeMaxDynamicSharedMemorySize, A_SMEM);
  }
  cudaStream_t st = cudaStreamPerThread;
  k_front<<<128, 512, A_SMEM, st>>>(x, (const uint32_t*)are, (const uint32_t*)aim, (const uint32_t*)bre, (const uint32_t*)bim,
                                    (const uint32_t*)cre, (const uint32_t*)cim, logdt, dskip, (const uint4*)wg, (const uint4*)wu, (const uint4*)wd);
  cudaLaunchConfig_t cfg = {};
  cfg.gridDim = dim3(128); cfg.blockDim = dim3(384); cfg.dynamicSmemBytes = B_SMEM; cfg.stream = st;
  cudaLaunchAttribute at[1];
  at[0].id = cudaLaunchAttributeProgrammaticStreamSerialization; at[0].val.programmaticStreamSerializationAllowed = 1;
  cfg.attrs = at; cfg.numAttrs = 1;
  cudaLaunchKernelEx(&cfg, k_ffn, (__nv_bfloat16*)d_out);
}
```

```cpp
#include <cuda_runtime.h>
#include <cuda_bf16.h>
#include <stdint.h>

constexpr int LSEQ = 2048, DM = 448;

__device__ uint4    g_himg[16 * 114688 / 16];
__device__ uint4    g_cimg[8 * 2 * 224];
__device__ uint32_t g_stat2[LSEQ];
__device__ uint4    g_part[128 * 7 * 896];
__device__ uint4    g_wimg[8 * 602112 / 16];
__device__ unsigned g_epochA, g_epochB;
__device__ uint4    g_ux[DM * 128 * 4];
__device__ unsigned g_cnt1;
__device__ uint4    g_flag[128 * 16];

#define TR(k, i) do {} while (0)
__device__ __forceinline__ uint32_t s2u(const void* p) { return (uint32_t)__cvta_generic_to_shared(p); }
__device__ __forceinline__ void mbar_init(uint32_t b, int c) { asm volatile("mbarrier.init.shared::cta.b64 [%0], %1;" ::"r"(b), "r"(c)); }
__device__ __forceinline__ void mbar_expect(uint32_t b, int bytes) { asm volatile("mbarrier.arrive.expect_tx.shared::cta.b64 _, [%0], %1;" ::"r"(b), "r"(bytes) : "memory"); }
__device__ __forceinline__ void mbar_arrive(uint32_t b) { asm volatile("mbarrier.arrive.shared::cta.b64 _, [%0];" ::"r"(b) : "memory"); }
__device__ __forceinline__ void mbar_wait(uint32_t b, int ph) {
  asm volatile("{\n.reg .pred p;\n.reg .b32 n;\nmov.b32 n, 0;\nLW:\nmbarrier.try_wait.parity.shared::cta.b64 p, [%0], %1;\n@p bra LD;\n"
               "add.u32 n, n, 1;\nsetp.lt.u32 p, n, 4000000;\n@p bra LW;\ntrap;\nLD:\n}" ::"r"(b), "r"(ph) : "memory");
}
__device__ __forceinline__ uint64_t mkdesc(uint32_t addr, uint32_t lbo, uint32_t sbo, uint32_t sw) {
  return (uint64_t)((addr & 0x3FFFF) >> 4) | ((uint64_t)((lbo >> 4) & 0x3FFF) << 16) | ((uint64_t)((sbo >> 4) & 0x3FFF) << 32) | ((uint64_t)sw << 62);
}
__device__ __forceinline__ void wg_fence() { asm volatile("wgmma.fence.sync.aligned;" ::: "memory"); }
__device__ __forceinline__ void wg_commit() { asm volatile("wgmma.commit_group.sync.aligned;" ::: "memory"); }
template <int N> __device__ __forceinline__ void wg_wait() { asm volatile("wgmma.wait_group.sync.aligned %0;" ::"n"(N) : "memory"); }
template <int N> __device__ __forceinline__ void reg_fence(float (&a)[N]) {
#pragma unroll
  for (int i = 0; i < N; i++) asm volatile("" : "+f"(a[i])::"memory");
}
__device__ __forceinline__ uint32_t pack_bf16(float lo, float hi) {
  uint32_t r; asm("cvt.rn.bf16x2.f32 %0, %1, %2;" : "=r"(r) : "f"(hi), "f"(lo)); return r;
}
__device__ __forceinline__ float bf_lo(uint32_t v) { return __uint_as_float(v << 16); }
__device__ __forceinline__ float bf_hi(uint32_t v) { return __uint_as_float(v & 0xFFFF0000u); }
__device__ __forceinline__ float rbf(float x) { return __bfloat162float(__float2bfloat16_rn(x)); }
__device__ __forceinline__ uint32_t hmul2_bf(uint32_t a, uint32_t b) { uint32_t r; asm("mul.rn.bf16x2 %0, %1, %2;" : "=r"(r) : "r"(a), "r"(b)); return r; }
__device__ __forceinline__ uint32_t hadd2_bf(uint32_t a, uint32_t b) { uint32_t r; asm("add.rn.bf16x2 %0, %1, %2;" : "=r"(r) : "r"(a), "r"(b)); return r; }
__device__ __forceinline__ void bulk_ld(uint32_t dst, const void* src, int bytes, uint32_t bar) {
  asm volatile("cp.async.bulk.shared::cluster.global.mbarrier::complete_tx::bytes [%0], [%1], %2, [%3];"
               ::"r"(dst), "l"(src), "r"(bytes), "r"(bar) : "memory");
}

__device__ __forceinline__ void bulk_ld_mc(uint32_t dst, const void* src, int bytes, uint32_t bar) {
  asm volatile("cp.async.bulk.shared::cluster.global.mbarrier::complete_tx::bytes.multicast::cluster [%0], [%1], %2, [%3], %4;"
               ::"r"(dst), "l"(src), "r"(bytes), "r"(bar), "h"((uint16_t)3) : "memory");
}
template <int AOFF, uint32_t AHI, int BOFF, uint32_t BHI, int ACC>
__device__ __forceinline__ void wgmma_ss224(float (&d)[112], uint32_t alo, uint32_t blo) {
  asm volatile("{\n.reg .pred p;\n.reg .b32 la, lb;\n.reg .b64 ad, bd;\nsetp.ne.b32 p, %118, 0;\n"
    "add.u32 la, %112, %114;\nmov.b64 ad, {la, %115};\nadd.u32 lb, %113, %116;\nmov.b64 bd, {lb, %117};\n"
    "wgmma.mma_async.sync.aligned.m64n224k16.f32.bf16.bf16 {%0,%1,%2,%3,%4,%5,%6,%7,%8,%9,%10,%11,%12,%13,%14,%15,%16,%17,%18,%19,%20,%21,%22,%23,%24,%25,%26,%27,%28,%29,%30,%31,%32,%33,%34,%35,%36,%37,%38,%39,%40,%41,%42,%43,%44,%45,%46,%47,%48,%49,%50,%51,%52,%53,%54,%55,%56,%57,%58,%59,%60,%61,%62,%63,%64,%65,%66,%67,%68,%69,%70,%71,%72,%73,%74,%75,%76,%77,%78,%79,%80,%81,%82,%83,%84,%85,%86,%87,%88,%89,%90,%91,%92,%93,%94,%95,%96,%97,%98,%99,%100,%101,%102,%103,%104,%105,%106,%107,%108,%109,%110,%111}, ad, bd, p, 1, 1, 1, 1;\n}\n"
    : "+f"(d[0]),"+f"(d[1]),"+f"(d[2]),"+f"(d[3]),"+f"(d[4]),"+f"(d[5]),"+f"(d[6]),"+f"(d[7]),"+f"(d[8]),"+f"(d[9]),"+f"(d[10]),"+f"(d[11]),"+f"(d[12]),"+f"(d[13]),"+f"(d[14]),"+f"(d[15]),"+f"(d[16]),"+f"(d[17]),"+f"(d[18]),"+f"(d[19]),"+f"(d[20]),"+f"(d[21]),"+f"(d[22]),"+f"(d[23]),"+f"(d[24]),"+f"(d[25]),"+f"(d[26]),"+f"(d[27]),"+f"(d[28]),"+f"(d[29]),"+f"(d[30]),"+f"(d[31]),"+f"(d[32]),"+f"(d[33]),"+f"(d[34]),"+f"(d[35]),"+f"(d[36]),"+f"(d[37]),"+f"(d[38]),"+f"(d[39]),"+f"(d[40]),"+f"(d[41]),"+f"(d[42]),"+f"(d[43]),"+f"(d[44]),"+f"(d[45]),"+f"(d[46]),"+f"(d[47]),"+f"(d[48]),"+f"(d[49]),"+f"(d[50]),"+f"(d[51]),"+f"(d[52]),"+f"(d[53]),"+f"(d[54]),"+f"(d[55]),"+f"(d[56]),"+f"(d[57]),"+f"(d[58]),"+f"(d[59]),"+f"(d[60]),"+f"(d[61]),"+f"(d[62]),"+f"(d[63]),"+f"(d[64]),"+f"(d[65]),"+f"(d[66]),"+f"(d[67]),"+f"(d[68]),"+f"(d[69]),"+f"(d[70]),"+f"(d[71]),"+f"(d[72]),"+f"(d[73]),"+f"(d[74]),"+f"(d[75]),"+f"(d[76]),"+f"(d[77]),"+f"(d[78]),"+f"(d[79]),"+f"(d[80]),"+f"(d[81]),"+f"(d[82]),"+f"(d[83]),"+f"(d[84]),"+f"(d[85]),"+f"(d[86]),"+f"(d[87]),"+f"(d[88]),"+f"(d[89]),"+f"(d[90]),"+f"(d[91]),"+f"(d[92]),"+f"(d[93]),"+f"(d[94]),"+f"(d[95]),"+f"(d[96]),"+f"(d[97]),"+f"(d[98]),"+f"(d[99]),"+f"(d[100]),"+f"(d[101]),"+f"(d[102]),"+f"(d[103]),"+f"(d[104]),"+f"(d[105]),"+f"(d[106]),"+f"(d[107]),"+f"(d[108]),"+f"(d[109]),"+f"(d[110]),"+f"(d[111])
    : "r"(alo), "r"(blo), "n"(AOFF), "n"(AHI), "n"(BOFF), "n"(BHI), "n"(ACC));
}
template <int AOFF, uint32_t AHI, int BOFF, uint32_t BHI, int ACC>
__device__ __forceinline__ void wgmma_ss232(float (&d)[116], uint32_t alo, uint32_t blo) {
  asm volatile("{\n.reg .pred p;\n.reg .b32 la, lb;\n.reg .b64 ad, bd;\nsetp.ne.b32 p, %122, 0;\n"
    "add.u32 la, %116, %118;\nmov.b64 ad, {la, %119};\nadd.u32 lb, %117, %120;\nmov.b64 bd, {lb, %121};\n"
    "wgmma.mma_async.sync.aligned.m64n232k16.f32.bf16.bf16 {%0,%1,%2,%3,%4,%5,%6,%7,%8,%9,%10,%11,%12,%13,%14,%15,%16,%17,%18,%19,%20,%21,%22,%23,%24,%25,%26,%27,%28,%29,%30,%31,%32,%33,%34,%35,%36,%37,%38,%39,%40,%41,%42,%43,%44,%45,%46,%47,%48,%49,%50,%51,%52,%53,%54,%55,%56,%57,%58,%59,%60,%61,%62,%63,%64,%65,%66,%67,%68,%69,%70,%71,%72,%73,%74,%75,%76,%77,%78,%79,%80,%81,%82,%83,%84,%85,%86,%87,%88,%89,%90,%91,%92,%93,%94,%95,%96,%97,%98,%99,%100,%101,%102,%103,%104,%105,%106,%107,%108,%109,%110,%111,%112,%113,%114,%115}, ad, bd, p, 1, 1, 1, 1;\n}\n"
    : "+f"(d[0]),"+f"(d[1]),"+f"(d[2]),"+f"(d[3]),"+f"(d[4]),"+f"(d[5]),"+f"(d[6]),"+f"(d[7]),"+f"(d[8]),"+f"(d[9]),"+f"(d[10]),"+f"(d[11]),"+f"(d[12]),"+f"(d[13]),"+f"(d[14]),"+f"(d[15]),"+f"(d[16]),"+f"(d[17]),"+f"(d[18]),"+f"(d[19]),"+f"(d[20]),"+f"(d[21]),"+f"(d[22]),"+f"(d[23]),"+f"(d[24]),"+f"(d[25]),"+f"(d[26]),"+f"(d[27]),"+f"(d[28]),"+f"(d[29]),"+f"(d[30]),"+f"(d[31]),"+f"(d[32]),"+f"(d[33]),"+f"(d[34]),"+f"(d[35]),"+f"(d[36]),"+f"(d[37]),"+f"(d[38]),"+f"(d[39]),"+f"(d[40]),"+f"(d[41]),"+f"(d[42]),"+f"(d[43]),"+f"(d[44]),"+f"(d[45]),"+f"(d[46]),"+f"(d[47]),"+f"(d[48]),"+f"(d[49]),"+f"(d[50]),"+f"(d[51]),"+f"(d[52]),"+f"(d[53]),"+f"(d[54]),"+f"(d[55]),"+f"(d[56]),"+f"(d[57]),"+f"(d[58]),"+f"(d[59]),"+f"(d[60]),"+f"(d[61]),"+f"(d[62]),"+f"(d[63]),"+f"(d[64]),"+f"(d[65]),"+f"(d[66]),"+f"(d[67]),"+f"(d[68]),"+f"(d[69]),"+f"(d[70]),"+f"(d[71]),"+f"(d[72]),"+f"(d[73]),"+f"(d[74]),"+f"(d[75]),"+f"(d[76]),"+f"(d[77]),"+f"(d[78]),"+f"(d[79]),"+f"(d[80]),"+f"(d[81]),"+f"(d[82]),"+f"(d[83]),"+f"(d[84]),"+f"(d[85]),"+f"(d[86]),"+f"(d[87]),"+f"(d[88]),"+f"(d[89]),"+f"(d[90]),"+f"(d[91]),"+f"(d[92]),"+f"(d[93]),"+f"(d[94]),"+f"(d[95]),"+f"(d[96]),"+f"(d[97]),"+f"(d[98]),"+f"(d[99]),"+f"(d[100]),"+f"(d[101]),"+f"(d[102]),"+f"(d[103]),"+f"(d[104]),"+f"(d[105]),"+f"(d[106]),"+f"(d[107]),"+f"(d[108]),"+f"(d[109]),"+f"(d[110]),"+f"(d[111]),"+f"(d[112]),"+f"(d[113]),"+f"(d[114]),"+f"(d[115])
    : "r"(alo), "r"(blo), "n"(AOFF), "n"(AHI), "n"(BOFF), "n"(BHI), "n"(ACC));
}
template <int OFF, uint32_t BHI, int ACC>
__device__ __forceinline__ void wgmma_rs224(float (&d)[112], uint32_t a0, uint32_t a1, uint32_t a2, uint32_t a3, uint32_t blo) {
  asm volatile("{\n.reg .pred p;\n.reg .b32 l;\n.reg .b64 bd;\nsetp.ne.b32 p, %119, 0;\nadd.u32 l, %116, %117;\nmov.b64 bd, {l, %118};\n"
    "wgmma.mma_async.sync.aligned.m64n224k16.f32.bf16.bf16 {%0,%1,%2,%3,%4,%5,%6,%7,%8,%9,%10,%11,%12,%13,%14,%15,%16,%17,%18,%19,%20,%21,%22,%23,%24,%25,%26,%27,%28,%29,%30,%31,%32,%33,%34,%35,%36,%37,%38,%39,%40,%41,%42,%43,%44,%45,%46,%47,%48,%49,%50,%51,%52,%53,%54,%55,%56,%57,%58,%59,%60,%61,%62,%63,%64,%65,%66,%67,%68,%69,%70,%71,%72,%73,%74,%75,%76,%77,%78,%79,%80,%81,%82,%83,%84,%85,%86,%87,%88,%89,%90,%91,%92,%93,%94,%95,%96,%97,%98,%99,%100,%101,%102,%103,%104,%105,%106,%107,%108,%109,%110,%111}, {%112,%113,%114,%115}, bd, p, 1, 1, 1;\n}\n"
    : "+f"(d[0]),"+f"(d[1]),"+f"(d[2]),"+f"(d[3]),"+f"(d[4]),"+f"(d[5]),"+f"(d[6]),"+f"(d[7]),"+f"(d[8]),"+f"(d[9]),"+f"(d[10]),"+f"(d[11]),"+f"(d[12]),"+f"(d[13]),"+f"(d[14]),"+f"(d[15]),"+f"(d[16]),"+f"(d[17]),"+f"(d[18]),"+f"(d[19]),"+f"(d[20]),"+f"(d[21]),"+f"(d[22]),"+f"(d[23]),"+f"(d[24]),"+f"(d[25]),"+f"(d[26]),"+f"(d[27]),"+f"(d[28]),"+f"(d[29]),"+f"(d[30]),"+f"(d[31]),"+f"(d[32]),"+f"(d[33]),"+f"(d[34]),"+f"(d[35]),"+f"(d[36]),"+f"(d[37]),"+f"(d[38]),"+f"(d[39]),"+f"(d[40]),"+f"(d[41]),"+f"(d[42]),"+f"(d[43]),"+f"(d[44]),"+f"(d[45]),"+f"(d[46]),"+f"(d[47]),"+f"(d[48]),"+f"(d[49]),"+f"(d[50]),"+f"(d[51]),"+f"(d[52]),"+f"(d[53]),"+f"(d[54]),"+f"(d[55]),"+f"(d[56]),"+f"(d[57]),"+f"(d[58]),"+f"(d[59]),"+f"(d[60]),"+f"(d[61]),"+f"(d[62]),"+f"(d[63]),"+f"(d[64]),"+f"(d[65]),"+f"(d[66]),"+f"(d[67]),"+f"(d[68]),"+f"(d[69]),"+f"(d[70]),"+f"(d[71]),"+f"(d[72]),"+f"(d[73]),"+f"(d[74]),"+f"(d[75]),"+f"(d[76]),"+f"(d[77]),"+f"(d[78]),"+f"(d[79]),"+f"(d[80]),"+f"(d[81]),"+f"(d[82]),"+f"(d[83]),"+f"(d[84]),"+f"(d[85]),"+f"(d[86]),"+f"(d[87]),"+f"(d[88]),"+f"(d[89]),"+f"(d[90]),"+f"(d[91]),"+f"(d[92]),"+f"(d[93]),"+f"(d[94]),"+f"(d[95]),"+f"(d[96]),"+f"(d[97]),"+f"(d[98]),"+f"(d[99]),"+f"(d[100]),"+f"(d[101]),"+f"(d[102]),"+f"(d[103]),"+f"(d[104]),"+f"(d[105]),"+f"(d[106]),"+f"(d[107]),"+f"(d[108]),"+f"(d[109]),"+f"(d[110]),"+f"(d[111])
    : "r"(a0), "r"(a1), "r"(a2), "r"(a3), "r"(blo), "n"(OFF), "n"(BHI), "n"(ACC));
}
template <int OFF, uint32_t BHI, int ACC>
__device__ __forceinline__ void wgmma_rs56(float (&d)[28], uint32_t a0, uint32_t a1, uint32_t a2, uint32_t a3, uint32_t blo) {
  asm volatile("{\n.reg .pred p;\n.reg .b32 l;\n.reg .b64 bd;\nsetp.ne.b32 p, %35, 0;\nadd.u32 l, %32, %33;\nmov.b64 bd, {l, %34};\n"
    "wgmma.mma_async.sync.aligned.m64n56k16.f32.bf16.bf16 {%0,%1,%2,%3,%4,%5,%6,%7,%8,%9,%10,%11,%12,%13,%14,%15,%16,%17,%18,%19,%20,%21,%22,%23,%24,%25,%26,%27}, {%28,%29,%30,%31}, bd, p, 1, 1, 1;\n}\n"
    : "+f"(d[0]),"+f"(d[1]),"+f"(d[2]),"+f"(d[3]),"+f"(d[4]),"+f"(d[5]),"+f"(d[6]),"+f"(d[7]),"+f"(d[8]),"+f"(d[9]),"+f"(d[10]),"+f"(d[11]),"+f"(d[12]),"+f"(d[13]),"+f"(d[14]),"+f"(d[15]),"+f"(d[16]),"+f"(d[17]),"+f"(d[18]),"+f"(d[19]),"+f"(d[20]),"+f"(d[21]),"+f"(d[22]),"+f"(d[23]),"+f"(d[24]),"+f"(d[25]),"+f"(d[26]),"+f"(d[27])
    : "r"(a0), "r"(a1), "r"(a2), "r"(a3), "r"(blo), "n"(OFF), "n"(BHI), "n"(ACC));
}

__device__ __forceinline__ void st128(uint4* p, uint32_t a, uint32_t b, uint32_t c, uint32_t d) {
  asm volatile("{\n.reg .b128 v;\n.reg .b64 lo, hi;\nmov.b64 lo, {%1, %2};\nmov.b64 hi, {%3, %4};\nmov.b128 v, {lo, hi};\n"
               "st.relaxed.gpu.global.b128 [%0], v;\n}" ::"l"(p), "r"(a), "r"(b), "r"(c), "r"(d) : "memory");
}
__device__ __forceinline__ void ld128(const uint4* p, uint32_t* r) {
  asm volatile("{\n.reg .b128 v;\n.reg .b64 lo, hi;\nld.relaxed.gpu.global.b128 v, [%4];\nmov.b128 {lo, hi}, v;\n"
               "mov.b64 {%0, %1}, lo;\nmov.b64 {%2, %3}, hi;\n}" : "=r"(r[0]), "=r"(r[1]), "=r"(r[2]), "=r"(r[3]) : "l"(p) : "memory");
}

template <int OFF, uint32_t BHI, int ACC>
__device__ __forceinline__ void wgmma_rs32(float (&d)[16], uint32_t a0, uint32_t a1, uint32_t a2, uint32_t a3, uint32_t blo) {
  asm volatile("{\n.reg .pred p;\n.reg .b32 l;\n.reg .b64 bd;\nsetp.ne.b32 p, %23, 0;\nadd.u32 l, %20, %21;\nmov.b64 bd, {l, %22};\n"
    "wgmma.mma_async.sync.aligned.m64n32k16.f32.bf16.bf16 {%0,%1,%2,%3,%4,%5,%6,%7,%8,%9,%10,%11,%12,%13,%14,%15}, {%16,%17,%18,%19}, bd, p, 1, 1, 0;\n}\n"
    : "+f"(d[0]),"+f"(d[1]),"+f"(d[2]),"+f"(d[3]),"+f"(d[4]),"+f"(d[5]),"+f"(d[6]),"+f"(d[7]),"+f"(d[8]),"+f"(d[9]),"+f"(d[10]),"+f"(d[11]),"+f"(d[12]),"+f"(d[13]),"+f"(d[14]),"+f"(d[15])
    : "r"(a0), "r"(a1), "r"(a2), "r"(a3), "r"(blo), "n"(OFF), "n"(BHI), "n"(ACC));
}
template <int OFF, uint32_t BHI, int ACC>
__device__ __forceinline__ void wgmma_rs24(float (&d)[12], uint32_t a0, uint32_t a1, uint32_t a2, uint32_t a3, uint32_t blo) {
  asm volatile("{\n.reg .pred p;\n.reg .b32 l;\n.reg .b64 bd;\nsetp.ne.b32 p, %19, 0;\nadd.u32 l, %16, %17;\nmov.b64 bd, {l, %18};\n"
    "wgmma.mma_async.sync.aligned.m64n24k16.f32.bf16.bf16 {%0,%1,%2,%3,%4,%5,%6,%7,%8,%9,%10,%11}, {%12,%13,%14,%15}, bd, p, 1, 1, 1;\n}\n"
    : "+f"(d[0]),"+f"(d[1]),"+f"(d[2]),"+f"(d[3]),"+f"(d[4]),"+f"(d[5]),"+f"(d[6]),"+f"(d[7]),"+f"(d[8]),"+f"(d[9]),"+f"(d[10]),"+f"(d[11])
    : "r"(a0), "r"(a1), "r"(a2), "r"(a3), "r"(blo), "n"(OFF), "n"(BHI), "n"(ACC));
}
template <int OFF, uint32_t BHI, int ACC>
__device__ __forceinline__ void wgmma_rs16(float (&d)[8], uint32_t a0, uint32_t a1, uint32_t a2, uint32_t a3, uint32_t blo) {
  asm volatile("{\n.reg .pred p;\n.reg .b32 l;\n.reg .b64 bd;\nsetp.ne.b32 p, %15, 0;\nadd.u32 l, %12, %13;\nmov.b64 bd, {l, %14};\n"
    "wgmma.mma_async.sync.aligned.m64n16k16.f32.bf16.bf16 {%0,%1,%2,%3,%4,%5,%6,%7}, {%8,%9,%10,%11}, bd, p, 1, 1, 1;\n}\n"
    : "+f"(d[0]),"+f"(d[1]),"+f"(d[2]),"+f"(d[3]),"+f"(d[4]),"+f"(d[5]),"+f"(d[6]),"+f"(d[7])
    : "r"(a0), "r"(a1), "r"(a2), "r"(a3), "r"(blo), "n"(OFF), "n"(BHI), "n"(ACC));
}

constexpr int A_UB = 0;
constexpr int A_W5 = 5248;
constexpr int A_W3 = A_W5 + 4112;
constexpr int A_W9 = A_W3 + 4112;
constexpr int A_W7 = A_W9 + 2048;
constexpr int A_V  = A_W7 + 2048;
constexpr int A_R1 = A_V + 2048;
constexpr int A_R2A = A_R1 + 2624, A_R2B = A_R2A + 768, A_R3A = A_R2B + 768, A_R3B = A_R3A + 528;
constexpr int A_K1024 = A_R3B + 528;
constexpr int A_ZEND = A_K1024 + 16;
constexpr int A_STG = A_ZEND;
constexpr int A_Y2 = A_STG, A_Y3 = A_Y2 + 6528, A_YB = A_Y3 + 4352;
constexpr int A_REC = A_STG + 4 * 4352;
constexpr int A_CH = A_REC + 8192;
constexpr int A_BAR = 4 * A_CH;
constexpr int A_SMEM = A_BAR + 64;
static_assert(A_ZEND % 16 == 0 && A_CH % 16 == 0 && A_YB + 4096 <= A_REC, "layout");

struct cf { float x, y; };
__device__ __forceinline__ cf cmul(cf a, cf b) { cf r; r.x = fmaf(a.x, b.x, -a.y * b.y); r.y = fmaf(a.x, b.y, a.y * b.x); return r; }
__device__ __forceinline__ cf cexp_l(float lr, float li, float l) {
  float mag; asm("ex2.approx.ftz.f32 %0, %1;" : "=f"(mag) : "f"((lr * l) * 1.4426950408889634f));
  const float th = li * l;
  const float k = (fmaf(th, 0.15915494f, 12582912.f)) - 12582912.f;
  float ph = fmaf(th, 0.15915494f, -k);
  ph = fmaf(th, 6.4206383e-9f, ph) * 6.2831853f;
  cf r; r.x = mag * __cosf(ph); r.y = mag * __sinf(ph); return r;
}
__device__ __forceinline__ void sts16(uint32_t a, uint32_t v) { asm volatile("st.shared.u16 [%0], %1;" ::"r"(a), "h"((uint16_t)v) : "memory"); }
__device__ __forceinline__ void sts32(uint32_t a, uint32_t v) { asm volatile("st.shared.u32 [%0], %1;" ::"r"(a), "r"(v) : "memory"); }
__device__ __forceinline__ void sts64(uint32_t a, uint32_t v0, uint32_t v1) { asm volatile("st.shared.v2.u32 [%0], {%1, %2};" ::"r"(a), "r"(v0), "r"(v1) : "memory"); }
__device__ __forceinline__ void sts128(uint32_t a, uint32_t v0, uint32_t v1, uint32_t v2, uint32_t v3) {
  asm volatile("st.shared.v4.u32 [%0], {%1, %2, %3, %4};" ::"r"(a), "r"(v0), "r"(v1), "r"(v2), "r"(v3) : "memory");
}
__device__ __forceinline__ uint32_t lds32(uint32_t a) { uint32_t v; asm volatile("ld.shared.u32 %0, [%1];" : "=r"(v) : "r"(a) : "memory"); return v; }
__device__ __forceinline__ uint4 lds128(uint32_t a) {
  uint4 v; asm volatile("ld.shared.v4.u32 {%0, %1, %2, %3}, [%4];" : "=r"(v.x), "=r"(v.y), "=r"(v.z), "=r"(v.w) : "r"(a) : "memory"); return v;
}
__device__ __forceinline__ void ldsm4(uint32_t* r, uint32_t a) {
  asm volatile("ldmatrix.sync.aligned.m8n8.x4.shared.b16 {%0,%1,%2,%3}, [%4];" : "=r"(r[0]), "=r"(r[1]), "=r"(r[2]), "=r"(r[3]) : "r"(a) : "memory");
}
__device__ __forceinline__ void mma16816(float* d, const uint32_t* a, uint32_t b0, uint32_t b1) {
  asm volatile("mma.sync.aligned.m16n8k16.row.col.f32.bf16.bf16.f32 {%0,%1,%2,%3}, {%4,%5,%6,%7}, {%8,%9}, {%0,%1,%2,%3};"
               : "+f"(d[0]), "+f"(d[1]), "+f"(d[2]), "+f"(d[3]) : "r"(a[0]), "r"(a[1]), "r"(a[2]), "r"(a[3]), "r"(b0), "r"(b1));
}
__device__ __forceinline__ uint32_t hsub2_bf(uint32_t a, uint32_t b) { uint32_t r; asm("sub.rn.bf16x2 %0, %1, %2;" : "=r"(r) : "r"(a), "r"(b)); return r; }
__device__ __forceinline__ void bar_sync(int id, int n) { asm volatile("bar.sync %0, %1;" ::"r"(id), "r"(n) : "memory"); }

template <int S> struct F1B { static constexpr int c = S / 4 + ((S & 3) == 3 ? 0 : 0), cc = (16 * S) / 64, ks = (64 * cc - (16 * S - 48)) / 16, off = (2 * ks * 656 + (9 - cc) * 16) / 16; };

template <int NS>
__device__ __forceinline__ void load_quads(uint32_t* q, uint32_t addr) {
#pragma unroll
  for (int i = 0; i < NS; i++) {
    q[4 * i] = lds32(addr + i * 64); q[4 * i + 1] = lds32(addr + i * 64 + 32);
    q[4 * i + 2] = i ? q[4 * i - 3] : lds32(addr - 32);
    q[4 * i + 3] = q[4 * i];
  }
#pragma unroll
  for (int i = 0; i < 4 * NS; i++) asm volatile("" : "+r"(q[i]));
}
template <int S0, int NS>
__device__ __forceinline__ void f1_steps(float (&acc)[16], const uint32_t* a, uint32_t blo) {
  if constexpr (NS > 0) {
    wgmma_rs32<F1B<S0>::off, 8, S0 != 0>(acc, a[0], a[1], a[2], a[3], blo);
    f1_steps<S0 + 1, NS - 1>(acc, a + 4, blo);
  }
}
template <int S0, int NS, int BASE, int FIRST>
__device__ __forceinline__ void s2_steps(float (&acc)[12], const uint32_t* a, uint32_t blo) {
  if constexpr (NS > 0) {
    wgmma_rs24<BASE / 16 + (112 - 16 * S0), 64, !(FIRST && S0 == 0)>(acc, a[0], a[1], a[2], a[3], blo);
    s2_steps<S0 + 1, NS - 1, BASE, FIRST>(acc, a + 4, blo);
  }
}
template <int S0, int NS, int BASE, int FIRST>
__device__ __forceinline__ void s3_steps(float (&acc)[8], const uint32_t* a, uint32_t blo) {
  if constexpr (NS > 0) {
    wgmma_rs16<BASE / 16 + (48 - 16 * S0), 64, !(FIRST && S0 == 0)>(acc, a[0], a[1], a[2], a[3], blo);
    s3_steps<S0 + 1, NS - 1, BASE, FIRST>(acc, a + 4, blo);
  }
}

__global__ void __launch_bounds__(512, 1)
k_front(const __nv_bfloat16* __restrict__ x, const uint32_t* __restrict__ are, const uint32_t* __restrict__ aim,
        const uint32_t* __restrict__ bre, const uint32_t* __restrict__ bim, const uint32_t* __restrict__ cre,
        const uint32_t* __restrict__ cim, const __nv_bfloat16* __restrict__ logdt, const __nv_bfloat16* __restrict__ dskip,
        const uint4* __restrict__ wgate, const uint4* __restrict__ wup, const uint4* __restrict__ wdown) {
  extern __shared__ __align__(1024) unsigned char sm[];
  const uint32_t sb = s2u(sm);
  const int tid = threadIdx.x, wg = tid >> 7, warp = tid >> 5, lane = tid & 31, wq = warp & 3, t128 = tid & 127;
  const int blk = blockIdx.x;
  const bool conv = blk < 112;
  if (tid == 320) TR(0, 0);
  asm volatile("griddepcontrol.launch_dependents;");
  uint32_t ep = 0;
  if (tid == 160) { ep = __ldcg(&g_epochA) + 1u; mbar_init(sb + A_BAR, 1); asm volatile("fence.mbarrier_init.release.cluster;" ::: "memory"); }

  uint2 xr[4];
  {
    const uint2* p = (const uint2*)(x + (size_t)(blk * 16 + warp) * DM);
    xr[0] = __ldg(p + lane); xr[1] = __ldg(p + 32 + lane); xr[2] = __ldg(p + 64 + lane);
    xr[3] = lane < 16 ? __ldg(p + 96 + lane) : make_uint2(0, 0);
  }
  const int ch = blk * 4 + wg;
  uint32_t prm[6], dk = 0; float ldt = 0.f;
  const uint4* wsrc = (blk < 56 ? wgate : wup) + (blk % 56) * 4 + (lane & 3) + (size_t)(warp * 8 + (lane >> 2)) * 224;
  if (conv) {
    const int i = ch * 128 + t128;
    prm[0] = __ldg(are + i); prm[1] = __ldg(aim + i); prm[2] = __ldg(bre + i); prm[3] = __ldg(bim + i); prm[4] = __ldg(cre + i); prm[5] = __ldg(cim + i);
    ldt = __bfloat162float(logdt[ch]);
    dk = (uint32_t)__ldg((const unsigned short*)dskip + ch) * 0x10001u;
    for (int i2 = t128; i2 < A_ZEND / 16; i2 += 128) sts128(sb + wg * A_CH + i2 * 16, 0, 0, 0, 0);
  }
  {
    float v[16];
#pragma unroll
    for (int i = 0; i < 4; i++) { v[4 * i] = bf_lo(xr[i].x); v[4 * i + 1] = bf_hi(xr[i].x); v[4 * i + 2] = bf_lo(xr[i].y); v[4 * i + 3] = bf_hi(xr[i].y); }
    float s = 0.f;
#pragma unroll
    for (int i = 0; i < 16; i++) s += v[i];
#pragma unroll
    for (int o = 16; o; o >>= 1) s += __shfl_xor_sync(~0u, s, o);
    const float mean = s * (1.f / DM);
    float q = 0.f;
#pragma unroll
    for (int i = 0; i < 16; i++) { float d = v[i] - mean; if (i < 12 || lane < 16) q = fmaf(d, d, q); }
#pragma unroll
    for (int o = 16; o; o >>= 1) q += __shfl_xor_sync(~0u, q, o);
    const float rs = __frcp_rn(rbf(__fsqrt_rn(rbf(rbf(q * (1.f / DM)) + 1e-5f))));
    const uint32_t mm = pack_bf16(mean, mean);
    const uint32_t tu = sb + A_STG + warp * 912 + lane * 8, tx = tu + A_CH;
#pragma unroll
    for (int i = 0; i < 4; i++) {
      if (i < 3 || lane < 16) {
        const uint32_t d0 = hsub2_bf(xr[i].x, mm), d1 = hsub2_bf(xr[i].y, mm);
        sts64(tu + i * 256, pack_bf16(bf_lo(d0) * rs, bf_hi(d0) * rs), pack_bf16(bf_lo(d1) * rs, bf_hi(d1) * rs));
        sts64(tx + i * 256, xr[i].x, xr[i].y);
      }
    }
    bar_sync(5, 512);
#pragma unroll
    for (int i = 0; i < 4; i++) {
      const int cgp = warp + 16 * i;
      if (cgp < 56) {
        uint32_t r[4];
        asm volatile("ldmatrix.sync.aligned.m8n8.x4.trans.shared.b16 {%0,%1,%2,%3}, [%4];" : "=r"(r[0]), "=r"(r[1]), "=r"(r[2]), "=r"(r[3])
                     : "r"(sb + A_STG + (lane >> 4) * A_CH + (lane & 15) * 912 + cgp * 16) : "memory");
        g_ux[((size_t)(cgp * 8 + (lane >> 2)) * 128 + blk) * 4 + ((lane ^ (blk >> 1)) & 3)] = make_uint4(r[0], r[1], r[2], r[3]);
      }
    }
    bar_sync(5, 512);
  }
  if (conv && !(lane & 1)) {
#pragma unroll
    for (int i2 = 0; i2 < 4; i2++) if (i2 < 3 || warp < 8) asm volatile("prefetch.global.L2 [%0];" ::"l"(wsrc + (size_t)i2 * 128 * 224));
  }
  if (tid == 320) TR(0, 1);

  if (!conv) {
    const int a = blk - 112, mat = a >> 3, j = a & 7;
    if (tid == 0) asm volatile("red.release.gpu.global.add.u32 [%0], 1;" ::"l"(&g_cnt1) : "memory");
    if (tid == 160 && a == 0) g_epochB = ep;
    {
      const int rr = lane >> 2, cc = lane & 3;
#pragma unroll 4
      for (int it = warp; it < 196; it += 16) {
        const int rg = it / 14, cg = it % 14, k = rg * 8 + rr, ngg = cg * 4 + cc;
        const uint4 v = __ldg(wdown + (size_t)(a * 112 + k) * 56 + ngg);
        g_wimg[(size_t)(a >> 1) * 37632 + 25088 + ((ngg / 7) * 2 + (a & 1)) * 784 + (ngg % 7) * 112 + k] = v;
      }
    }
    float s[8];
#pragma unroll
    for (int k = 0; k < 8; k++) s[k] = 0.f;
    if (lane < 28) {
      const uint4* src = (mat ? wup : wgate) + j * 28 + lane + (size_t)warp * 224;
#pragma unroll 14
      for (int r = 0; r < 28; r++) {
        const uint4 v = __ldg(src + (size_t)r * 16 * 224);
        s[0] += bf_lo(v.x); s[1] += bf_hi(v.x); s[2] += bf_lo(v.y); s[3] += bf_hi(v.y);
        s[4] += bf_lo(v.z); s[5] += bf_hi(v.z); s[6] += bf_lo(v.w); s[7] += bf_hi(v.w);
      }
      float4* red = (float4*)(sm + warp * 896 + lane * 32);
      red[0] = make_float4(s[0], s[1], s[2], s[3]); red[1] = make_float4(s[4], s[5], s[6], s[7]);
    }
    bar_sync(5, 512);
    if (tid < 224) {
      float t = 0.f;
#pragma unroll
      for (int w = 0; w < 16; w++) t += *(const float*)(sm + w * 896 + tid * 4);
      const float hi = rbf(t), mid = rbf(t - hi), lo = rbf(t - hi - mid);
      const int q = tid / 112, n = tid % 112 + 112 * mat;
      __nv_bfloat16* dst = (__nv_bfloat16*)(g_cimg + (j * 2 + q) * 224 + (n >> 3) * 8) + (n & 7);
      dst[0] = __float2bfloat16_rn(hi); dst[8] = __float2bfloat16_rn(mid); dst[16] = __float2bfloat16_rn(lo);
#pragma unroll
      for (int k = 3; k < 8; k++) dst[8 * k] = __float2bfloat16_rn(0.f);
    }
    if (tid == 320) TR(0, 10);
    return;
  }

  const uint32_t cb = sb + wg * A_CH;
  const int g = lane >> 2, t = lane & 3;
  uint4 wv[4];
  {
    const uint32_t stg = cb + A_STG + wq * 4352;
    const float dt = rbf(expf(ldt));
    float lr[2], li[2];
    cf bq[2], b0[2], b4[2];
    uint32_t bf[48];
#pragma unroll
    for (int m = 0; m < 2; m++) {
      lr[m] = dt * (m ? bf_hi(prm[0]) : bf_lo(prm[0]));
      li[m] = dt * (m ? bf_hi(prm[1]) : bf_lo(prm[1]));
    }
    {
      cf b[2], z[2];
#pragma unroll
      for (int m = 0; m < 2; m++) {
        cf db, c;
        db.x = dt * (m ? bf_hi(prm[2]) : bf_lo(prm[2])); db.y = -dt * (m ? bf_hi(prm[3]) : bf_lo(prm[3]));
        c.x = m ? bf_hi(prm[4]) : bf_lo(prm[4]); c.y = -(m ? bf_hi(prm[5]) : bf_lo(prm[5]));
        b[m] = cmul(c, db);
        z[m] = cexp_l(lr[m], -li[m], 1.f);
        bq[m] = cexp_l(lr[m], -li[m], 256.f);
      }
#pragma unroll
      for (int i = 0; i < 8; i++) {
        sts64(stg + i * 272 + lane * 8, pack_bf16(b[0].x, b[0].y), pack_bf16(b[1].x, b[1].y));
        if (!(i & 1)) {
          cf e0 = cmul(b[0], bq[0]), e1 = cmul(b[1], bq[1]);
          sts64(stg + (8 + i / 2) * 272 + lane * 8, pack_bf16(e0.x, e0.y), pack_bf16(e1.x, e1.y));
          if (i == 0) { b0[0] = e0; b0[1] = e1; }
          if (i == 4) { b4[0] = e0; b4[1] = e1; }
        }
        if (i < 7) { b[0] = cmul(b[0], z[0]); b[1] = cmul(b[1], z[1]); }
      }
#pragma unroll
      for (int i = 0; i < 7; i++) {
        b0[0] = cmul(b0[0], bq[0]); b0[1] = cmul(b0[1], bq[1]);
        sts64(stg + (i < 2 ? 12 + 2 * i : i - 2) * 272 + lane * 8, pack_bf16(b0[0].x, b0[0].y), pack_bf16(b0[1].x, b0[1].y));
        if (i < 2) {
          b4[0] = cmul(b4[0], bq[0]); b4[1] = cmul(b4[1], bq[1]);
          sts64(stg + (13 + 2 * i) * 272 + lane * 8, pack_bf16(b4[0].x, b4[0].y), pack_bf16(b4[1].x, b4[1].y));
        }
        if (i == 1) {
          __syncwarp();
#pragma unroll
          for (int n = 0; n < 2; n++)
#pragma unroll
            for (int k2 = 0; k2 < 4; k2++) ldsm4(bf + n * 16 + k2 * 4, stg + (n * 8 + (lane & 7)) * 272 + k2 * 64 + (lane >> 3) * 16);
          __syncwarp();
        }
      }
    }
    __syncwarp();
#pragma unroll
    for (int k2 = 0; k2 < 4; k2++) ldsm4(bf + 32 + k2 * 4, stg + (lane & 7) * 272 + k2 * 64 + (lane >> 3) * 16);
    if (tid == 0) { asm volatile("red.release.gpu.global.add.u32 [%0], 1;" ::"l"(&g_cnt1) : "memory"); TR(0, 8); }
    float c[6][4];
#pragma unroll
    for (int i = 0; i < 6; i++) { c[i][0] = 0.f; c[i][1] = 0.f; c[i][2] = 0.f; c[i][3] = 0.f; }
    cf p[2], v[2];
    p[0] = cexp_l(lr[0], li[0], 8.f); p[1] = cexp_l(lr[1], li[1], 8.f);
    v[0].x = 1.f; v[0].y = 0.f; v[1] = v[0];
#pragma unroll
    for (int mt = 0; mt < 2; mt++) {
      __syncwarp();
#pragma unroll
      for (int i = 0; i < 16; i++) {
        sts64(stg + i * 272 + lane * 8, pack_bf16(v[0].x, v[0].y), pack_bf16(v[1].x, v[1].y));
        if (mt == 0 && i == 0) { v[0] = p[0]; v[1] = p[1]; }
        else if (mt == 0 || i < 15) { v[0] = cmul(v[0], p[0]); v[1] = cmul(v[1], p[1]); }
      }
      __syncwarp();
#pragma unroll
      for (int ks = 0; ks < 8; ks++) {
        uint32_t a[4];
        ldsm4(a, stg + (lane & 15) * 272 + ks * 32 + (lane >> 4) * 16);
#pragma unroll
        for (int n = 0; n < 3; n++) mma16816(c[n * 2 + mt], a, bf[n * 16 + ks * 2], bf[n * 16 + ks * 2 + 1]);
      }
      if (mt == 0 && tid == 160) {
        uint32_t v; int it = 0;
        do { asm volatile("ld.acquire.gpu.global.u32 %0, [%1];" : "=r"(v) : "l"(&g_cnt1) : "memory"); } while ((int)(v - ep * 128u) < 0 && ++it < 200000);
        asm volatile("fence.proxy.async.global;" ::: "memory");
        TR(0, 9);
        mbar_expect(sb + A_BAR, 32768);
        for (int c2 = 0; c2 < 4; c2++) bulk_ld(sb + c2 * A_CH + A_REC, g_ux + (size_t)(blk * 4 + c2) * 512, 8192, sb + A_BAR);
      }
    }
    __syncwarp();
#pragma unroll
    for (int i = 0; i < 6; i++)
      sts128(stg + i * 512 + lane * 16, __float_as_uint(c[i][0]), __float_as_uint(c[i][1]), __float_as_uint(c[i][2]), __float_as_uint(c[i][3]));
#pragma unroll
    for (int i2 = 0; i2 < 4; i2++) if (i2 < 3 || warp < 8) wv[i2] = __ldg(wsrc + (size_t)i2 * 128 * 224);
    bar_sync(1 + wg, 128);
    if (tid == 320) TR(0, 2);
#pragma unroll
    for (int rep = 0; rep < 2; rep++) {
      const int qd = rep ? 4 + wq : wq;
      if (rep == 0 || wq < 2) {
        float s[4] = {0.f, 0.f, 0.f, 0.f};
#pragma unroll
        for (int w = 0; w < 4; w++) {
          uint4 u4 = lds128(cb + A_STG + w * 4352 + qd * 512 + lane * 16);
          s[0] += __uint_as_float(u4.x); s[1] += __uint_as_float(u4.y); s[2] += __uint_as_float(u4.z); s[3] += __uint_as_float(u4.w);
        }
#pragma unroll
        for (int hf = 0; hf < 2; hf++) {
          const int j = (qd & 1) * 16 + g + 8 * hf;
          const uint32_t pk = pack_bf16(s[2 * hf + 1], s[2 * hf]);
          const uint32_t v0 = pk >> 16, v1 = pk & 0xFFFFu, v00 = v0 * 0x10001u;
          if (rep == 1) {
            if (t < 2) {
#pragma unroll
              for (int e = 0; e < 2; e++) {
                const int lam = 128 + 32 * (2 * t + e) + j, mu = lam >> 1;
                const uint32_t val = e ? v1 : v0;
                uint32_t a = cb + ((lam & 1) ? A_R3B : A_R3A) + mu * 4;
                if (lam == 128) { a = cb + A_R2A + 128 * 4; sts32(cb + A_K1024, val << 16); }
                sts16(a, val); sts16(a + 6, val);
              }
            } else if (t == 2 && j == 0) { sts16(cb + A_R3A + 128 * 4, v0); }
          } else if (wq < 2) {
            const uint32_t a = cb + A_R1 + (62 + 8 * j + 2 * t) * 4;
            sts16(a, v0); sts32(a + 4, pk); sts16(a + 10, v1);
          } else if (t < 2) {
            const int L = 256 + 8 * j + 4 * t;
            const uint32_t a = cb + A_R1 + (62 + L) * 4;
            if (L > 256) { sts16(a - 4, v0); sts32(a, v00); } else sts16(a, v0);
            sts32(a + 4, v00); sts32(a + 8, pk); sts16(a + 14, v1);
          } else {
            const int mu = 64 + 32 * (t - 2) + j;
            if (mu == 64) {
              const uint32_t a = cb + A_R1 + (62 + 512) * 4;
              sts16(a - 4, v0); sts32(a, v00); sts32(a + 4, v00); sts32(a + 8, v00); sts16(a + 14, v0);
            } else { sts16(cb + A_R2A + mu * 4, v0); sts16(cb + A_R2A + mu * 4 + 6, v0); }
            sts16(cb + A_R2B + mu * 4, v1); sts16(cb + A_R2B + mu * 4 + 6, v1);
          }
        }
      }
    }
  }
  if (tid == 320) TR(0, 3);

  uint32_t xt[8], ud[8];
  {
    mbar_wait(sb + A_BAR, 0);
    uint4 r[4];
#pragma unroll
    for (int i = 0; i < 4; i++) r[i] = lds128(cb + A_REC + t128 * 64 + ((i ^ (t128 >> 1)) & 3) * 16);
    const uint32_t ua = cb + A_UB + ((2 * t128) & 7) * 656 + ((t128 >> 2) + 9) * 16;
    sts128(ua, r[0].x, r[1].x, r[2].x, r[3].x);
    sts128(ua + 656, r[0].y, r[1].y, r[2].y, r[3].y);
#pragma unroll
    for (int i = 0; i < 4; i++) { ud[i] = hmul2_bf(r[i].x, dk); ud[4 + i] = hmul2_bf(r[i].y, dk); xt[i] = r[i].z; xt[4 + i] = r[i].w; }
  }
  bar_sync(1 + wg, 128);
  if (tid == 320) TR(0, 4);
#pragma unroll
  for (int c = 0; c < 2; c++) {
    if (c == 0 || t128 <= 64) {
      const int tp = c == 0 ? t128 : t128 == 64 ? -1 : 128 + t128;
      const uint32_t b = cb;
      const uint4 pv = lds128(b + A_UB + ((tp - 1) & 7) * 656 + (((tp - 1) >> 3) + 9) * 16);
      const uint4 cu = lds128(b + A_UB + (tp & 7) * 656 + ((tp >> 3) + 9) * 16);
      const uint4 nx = lds128(b + A_UB + ((tp + 1) & 7) * 656 + (((tp + 1) >> 3) + 9) * 16);
      const float e[16] = {bf_lo(pv.z), bf_hi(pv.z), bf_lo(pv.w), bf_hi(pv.w), bf_lo(cu.x), bf_hi(cu.x), bf_lo(cu.y), bf_hi(cu.y),
                           bf_lo(cu.z), bf_hi(cu.z), bf_lo(cu.w), bf_hi(cu.w), bf_lo(nx.x), bf_hi(nx.x), bf_lo(nx.y), bf_hi(nx.y)};
      float w[8];
#pragma unroll
      for (int i = 0; i < 8; i++) w[i] = e[i + 4] + (e[i + 3] + e[i + 5]);
      sts64(b + A_W3 + (tp + 64) * 16 + 8, pack_bf16(w[0], w[1]), pack_bf16(w[2], w[3]));
      sts64(b + A_W3 + (tp + 65) * 16, pack_bf16(w[4], w[5]), pack_bf16(w[6], w[7]));
#pragma unroll
      for (int i = 0; i < 8; i++) w[i] += e[i + 2] + e[i + 6];
      sts128(b + A_W5 + (tp + 64) * 16, pack_bf16(w[0], w[1]), pack_bf16(w[2], w[3]), pack_bf16(w[4], w[5]), pack_bf16(w[6], w[7]));
      if (tp < 128) {
#pragma unroll
        for (int i = 0; i < 8; i++) w[i] += e[i + 1] + e[i + 7];
        if (tp < 127) sts128(b + A_W7 + ((tp + 1) & 1) * 1024 + ((tp + 1) >> 1) * 16, pack_bf16(w[0], w[1]), pack_bf16(w[2], w[3]), pack_bf16(w[4], w[5]), pack_bf16(w[6], w[7]));
#pragma unroll
        for (int i = 0; i < 8; i++) w[i] += e[i] + e[i + 8];
        if (tp < 126) sts128(b + A_W9 + (tp & 1) * 1024 + ((tp + 2) >> 1) * 16, pack_bf16(w[0], w[1]), pack_bf16(w[2], w[3]), pack_bf16(w[4], w[5]), pack_bf16(w[6], w[7]));
        if (tp >= 0) sts128(b + A_V + tp * 16, pack_bf16(e[0] + e[1], e[1] + e[2]), pack_bf16(e[2] + e[3], e[3] + e[4]), pack_bf16(e[4] + e[5], e[5] + e[6]), pack_bf16(e[6] + e[7], e[7] + e[8]));
      }
    }
  }
  asm volatile("fence.proxy.async.shared::cta;" ::: "memory");
    {
      const int ngg = (blk % 56) * 4 + (lane & 3), j = ngg / 28, q = (ngg % 28) / 14, ng = ngg % 14 + (blk < 56 ? 0 : 14);
      uint4* dst = g_wimg + (size_t)j * 37632 + q * 14 * 896 + ng * 32 + (warp >> 2) * 896 + (warp & 3) * 8 + (lane >> 2);
#pragma unroll
      for (int i2 = 0; i2 < 4; i2++) if (i2 < 3 || warp < 8) dst[i2 * 4 * 896] = wv[i2];
    }
  bar_sync(1 + wg, 128);
  if (tid == 320) TR(0, 5);

  {
    const uint32_t cbu = __shfl_sync(~0u, cb, 0);
    const uint32_t blo_k = ((cbu & 0x3FFFF) >> 4) | (41u << 16);
    const uint32_t blo_n = ((cbu & 0x3FFFF) >> 4) | (8u << 16);
    const uint32_t tb = cb + (16 * wq + g - 2 * t) * 4;
    float y1[16], y2[12], y3[8];
    uint32_t qa[32], qb[32];
    const uint32_t t1 = tb + A_R1 + (62 - 48) * 4;
    load_quads<4>(qa, tb + A_R3A + 17 * 4); load_quads<4>(qa + 16, tb + A_R3B + 16 * 4);
    wg_fence();
    s3_steps<0, 4, A_W9, 1>(y3, qa, blo_n); s3_steps<0, 4, A_W7, 0>(y3, qa + 16, blo_n);
    wg_commit();
    load_quads<8>(qb, tb + A_R2A + 16 * 4);
    wg_fence(); s2_steps<0, 8, A_W5, 1>(y2, qb, blo_n); wg_commit();
    wg_wait<1>(); load_quads<8>(qa, tb + A_R2B + 16 * 4);
    wg_fence(); s2_steps<0, 8, A_W3, 0>(y2, qa, blo_n); wg_commit();
    wg_wait<1>(); load_quads<8>(qb, t1);
    wg_fence(); f1_steps<0, 8>(y1, qb, blo_k); wg_commit();
    wg_wait<1>(); load_quads<8>(qa, t1 + 8 * 64);
    wg_fence(); f1_steps<8, 8>(y1, qa, blo_k); wg_commit();
    reg_fence(y2); reg_fence(y3);
    {
      const float k1024 = __uint_as_float(lds32(cb + A_K1024));
#pragma unroll
      for (int i = 0; i < 2; i++)
#pragma unroll
        for (int hf = 0; hf < 2; hf++) {
          const int idx = 16 * (16 * wq + g + 8 * hf) + 8 * i + 2 * t;
          const uint32_t vv = lds32(cb + A_V + idx * 2);
          sts64(cb + A_Y3 + (idx + 4 * (idx >> 6)) * 4, __float_as_uint(fmaf(k1024, bf_lo(vv), y3[4 * i + 2 * hf])),
                __float_as_uint(fmaf(k1024, bf_hi(vv), y3[4 * i + 2 * hf + 1])));
        }
#pragma unroll
      for (int i = 0; i < 3; i++)
#pragma unroll
        for (int hf = 0; hf < 2; hf++) {
          const int idx = 512 * i + 8 * (16 * wq + g + 8 * hf) + 2 * t;
          sts64(cb + A_Y2 + (idx + 4 * (idx >> 6)) * 4, __float_as_uint(y2[4 * i + 2 * hf]), __float_as_uint(y2[4 * i + 2 * hf + 1]));
        }
    }
    wg_wait<1>(); load_quads<8>(qb, t1 + 16 * 64);
    wg_fence(); f1_steps<16, 8>(y1, qb, blo_k); wg_commit();
    wg_wait<1>(); load_quads<8>(qa, t1 + 24 * 64);
    wg_fence(); f1_steps<24, 8>(y1, qa, blo_k); wg_commit();
    wg_wait<1>(); load_quads<5>(qb, t1 + 32 * 64);
    wg_fence(); f1_steps<32, 5>(y1, qb, blo_k); wg_commit();
    bar_sync(1 + wg, 128);
    float ex[12];
#pragma unroll
    for (int i = 1; i < 4; i++)
#pragma unroll
      for (int k = 0; k < 4; k++) {
        const int aa = 8 * i + 2 * t + (k & 1), b = 16 * wq + g + 8 * (k >> 1);
        float e = __uint_as_float(lds32(cb + A_Y2 + ((aa - 8) * 68 + b) * 4));
        if (i >= 2) e += __uint_as_float(lds32(cb + A_Y3 + ((aa - 16) * 68 + b) * 4));
        ex[4 * (i - 1) + k] = e;
      }
    wg_wait<0>();
    reg_fence(y1);
    if (tid == 320) TR(0, 6);
#pragma unroll
    for (int i = 0; i < 12; i++) y1[4 + i] += ex[i];
#pragma unroll
    for (int i = 0; i < 2; i++) {
      const int mi = lane >> 3, aa = 8 * (2 * i + (mi >> 1)) + (lane & 7);
      asm volatile("stmatrix.sync.aligned.m8n8.x4.trans.shared.b16 [%0], {%1,%2,%3,%4};"
                   ::"r"(cb + A_YB + aa * 128 + (((2 * wq + (mi & 1)) ^ (lane & 7)) << 4)),
                     "r"(pack_bf16(y1[8 * i], y1[8 * i + 1])), "r"(pack_bf16(y1[8 * i + 2], y1[8 * i + 3])),
                     "r"(pack_bf16(y1[8 * i + 4], y1[8 * i + 5])), "r"(pack_bf16(y1[8 * i + 6], y1[8 * i + 7])) : "memory");
    }
  }
  bar_sync(1 + wg, 128);
#pragma unroll
  for (int c = 0; c < 2; c++) {
    const int tau = 2 * t128 + c, r = ch & 7;
    const uint4 y = lds128(cb + A_YB + (tau >> 3) * 128 + (((tau ^ (tau >> 3)) & 7) << 4));
    g_himg[(size_t)(tau >> 4) * 7168 + (ch >> 3) * 128 + ((tau >> 3) & 1) * 64 + r * 8 + ((tau & 7) ^ r)] =
        make_uint4(hadd2_bf(xt[4 * c], hadd2_bf(y.x, ud[4 * c])), hadd2_bf(xt[4 * c + 1], hadd2_bf(y.y, ud[4 * c + 1])),
                   hadd2_bf(xt[4 * c + 2], hadd2_bf(y.z, ud[4 * c + 2])), hadd2_bf(xt[4 * c + 3], hadd2_bf(y.w, ud[4 * c + 3])));
  }
  if (tid == 320) TR(0, 7);
}

constexpr int B_SA = 0, B_RING = 114688, B_SLOT = 14848, B_NSLOT = 7;
constexpr int B_CS = B_RING + B_NSLOT * B_SLOT;
constexpr int B_STAT = B_CS + 7168;
constexpr int B_BAR = B_STAT + 512;
constexpr int B_SMEM = B_BAR + 512;

__device__ __forceinline__ uint32_t mapa(uint32_t a, uint32_t r) { uint32_t o; asm("mapa.shared::cluster.u32 %0, %1, %2;" : "=r"(o) : "r"(a), "r"(r)); return o; }

template <int Q, int ST>
__device__ __forceinline__ void g1_stage(float (&acc)[116], uint32_t alo, uint32_t blo, uint32_t bar_full, uint32_t bar_h) {
  constexpr int s = Q * 14 + ST, sl = s % B_NSLOT;
  if (Q == 0) mbar_wait(bar_h + 8 * ST, 0);
  mbar_wait(bar_full + 8 * sl, (s / B_NSLOT) & 1);
  wg_fence();
  if (Q == 0) {
    wgmma_ss232<(2 * ST) * 256, 0x40000080u, (sl * B_SLOT) / 16, 32, ST != 0>(acc, alo, blo);
    wgmma_ss232<(2 * ST + 1) * 256, 0x40000080u, (sl * B_SLOT + 256) / 16, 32, 1>(acc, alo, blo);
  } else {
    wgmma_ss224<(2 * ST) * 256, 0x40000080u, (sl * B_SLOT) / 16, 32, ST != 0>(*(float(*)[112])acc, alo, blo);
    wgmma_ss224<(2 * ST + 1) * 256, 0x40000080u, (sl * B_SLOT + 256) / 16, 32, 1>(*(float(*)[112])acc, alo, blo);
  }
}

__global__ void __cluster_dims__(2, 1, 1) __launch_bounds__(384, 1) k_ffn(__nv_bfloat16* __restrict__ out) {
  extern __shared__ __align__(1024) unsigned char sm[];
  const uint32_t sb = s2u(sm);
  const int tid = threadIdx.x, wg = tid >> 7, warp = tid >> 5, lane = tid & 31;
  const int rank = blockIdx.x & 1, rt = blockIdx.x & 15, j = blockIdx.x >> 4;
  const uint32_t bar_full = sb + B_BAR, bar_empty = bar_full + 64, bar_h = bar_full + 128, bar_cs = bar_full + 240, bar_stat = bar_full + 248,
                 bar_adead = bar_full + 256, bar_in = bar_full + 264;
  if (tid == 0) {
    TR(1, 0);
    for (int i = 0; i < B_NSLOT; i++) { mbar_init(bar_full + 8 * i, 1); mbar_init(bar_empty + 8 * i, 4); }
    for (int i = 0; i < 14; i++) mbar_init(bar_h + 8 * i, 1);
    mbar_init(bar_cs, 1);
    mbar_init(bar_stat, 32);
    mbar_init(bar_adead, 2);
    for (int i = 0; i < 14; i++) mbar_init(bar_in + 8 * i, 1);
    asm volatile("fence.mbarrier_init.release.cluster;" ::: "memory");
  }
  if (tid >= 128 && tid < 128 + 224) {
    const int i = tid - 128;
    *(uint4*)(sm + B_RING + (i >> 5) * B_SLOT + 14336 + (i & 31) * 16) = make_uint4(0x3F803F80u, 0x3F803F80u, 0x3F803F80u, 0x3F803F80u);
    asm volatile("fence.proxy.async.shared::cta;" ::: "memory");
  }
  __syncthreads();
  asm volatile("barrier.cluster.arrive.release.aligned;" ::: "memory");

  if (wg == 2) {
    asm volatile("setmaxnreg.dec.sync.aligned.u32 88;");
    asm volatile("barrier.cluster.wait.acquire.aligned;" ::: "memory");
    asm volatile("griddepcontrol.wait;" ::: "memory");
    if (warp == 8) {
      if (lane == 0) {
        const char* wsrc = (const char*)g_wimg + (size_t)j * 602112;
        TR(1, 1);
        int slot = 0, ph = 0;
        for (int s = 0; s < 44; s++) {
          if (s >= B_NSLOT) mbar_wait(bar_empty + 8 * slot, ph ^ 1);
          uint32_t dst = sb + B_RING + slot * B_SLOT, fb = bar_full + 8 * slot;
          if (s < 28) {
            mbar_expect(fb, 14336);
            bulk_ld_mc(dst + rank * 7168, wsrc + s * 14336 + rank * 7168, 7168, fb);
          } else {
            const int c = (j + 1 + ((s - 28) >> 1)) & 7;
            mbar_expect(fb, 12544);
            bulk_ld_mc(dst + rank * 6272, wsrc + 401408 + (c * 2 + (s & 1)) * 12544 + rank * 6272, 6272, fb);
          }
          if (++slot == B_NSLOT) { slot = 0; ph ^= 1; }
        }
      }
    } else if (warp == 9) {
      if (lane == 0) {
        const char* hsrc = (const char*)g_himg + (size_t)rt * 114688;
        for (int i = 0; i < 14; i++) {
          mbar_expect(bar_h + 8 * i, 8192);
          bulk_ld(sb + B_SA + i * 8192, hsrc + i * 8192, 8192, bar_h + 8 * i);
        }
        mbar_expect(bar_cs, 7168);
        bulk_ld(sb + B_CS, g_cimg + j * 448, 7168, bar_cs);
      }
    } else {
      const int t64 = tid - 320;
      const uint32_t ep = __ldcg(&g_epochB), tag = ep & 1u;
      if (blockIdx.x == 0 && t64 == 0) g_epochA = ep;
      {
        const int r = (lane >> 1) & 7, c = (j & 3) * 2 + (lane & 1);
        const unsigned char* src = sm + B_SA + (t64 >> 4) * 2048 + (j >> 2) * 1024 + r * 128 + ((c ^ r) << 4);
        float a[16];
#pragma unroll
        for (int k = 0; k < 16; k++) a[k] = 0.f;
#pragma unroll 1
        for (int i = 0; i < 14; i++) {
          mbar_wait(bar_h + 8 * i, 0);
          uint4 v = *(const uint4*)(src + i * 8192);
          float e[8] = {bf_lo(v.x), bf_hi(v.x), bf_lo(v.y), bf_hi(v.y), bf_lo(v.z), bf_hi(v.z), bf_lo(v.w), bf_hi(v.w)};
#pragma unroll
          for (int k = 0; k < 8; k++) { a[2 * k] += e[k]; a[2 * k + 1] = fmaf(e[k], e[k], a[2 * k + 1]); }
          __nanosleep(160);
        }
#pragma unroll
        for (int rd = 0; rd < 4; rd++) {
          const int n = 8 >> rd;
          const bool up = lane & (2 * n);
#pragma unroll
          for (int k = 0; k < 8; k++) {
            if (k < n) {
              float keep = up ? a[k + n] : a[k], give = up ? a[k] : a[k + n];
              a[k] = keep + __shfl_xor_sync(~0u, give, 2 * n);
            }
          }
        }
        float* red = (float*)(sm + B_STAT);
        red[(warp & 1) * 32 + (lane & 1) * 16 + (lane >> 1)] = a[0];
        asm volatile("bar.sync 1, 64;" ::: "memory");
        if (t64 < 16) {
          float mean = (red[2 * t64] + red[32 + 2 * t64]) * (1.f / DM);
          float var = fmaxf(fmaf(-mean, mean, (red[2 * t64 + 1] + red[33 + 2 * t64]) * (1.f / DM)), 0.f);
          float rs = __frcp_rn(rbf(__fsqrt_rn(rbf(rbf(var) + 1e-5f))));
          asm volatile("st.relaxed.gpu.global.u32 [%0], %1;"
                       ::"l"(g_stat2 + rt * 128 + j * 16 + t64), "r"((__float_as_uint(rs * rs) & ~1u) | tag) : "memory");
        }
        if (t64 == 0) TR(1, 2);
      }
      __syncwarp();
      if (warp == 10) {
        mbar_wait(bar_adead, 0);
        uint32_t w[4];
        int it = 0;
        do { ld128((const uint4*)(g_stat2 + rt * 128) + lane, w); } while ((((w[0] ^ tag) | (w[1] ^ tag) | (w[2] ^ tag) | (w[3] ^ tag)) & 1u) && ++it < 200000);
        *(uint4*)(sm + B_STAT + lane * 16) = make_uint4(w[0], w[1], w[2], w[3]);
        mbar_arrive(bar_stat);
      }
      if (t64 == 0) TR(1, 18);
      if (warp == 11) {
        mbar_wait(bar_adead, 0);
        bool todo = lane < 14;
        int it = 0;
        while (__any_sync(~0u, todo) && ++it < 200000) {
          if (todo) {
            uint32_t w[4];
            ld128(g_flag + (rt * 8 + j) * 16 + lane, w);
            if (w[0] == ep && w[1] == ep && w[2] == ep && w[3] == ep) {
              const uint32_t b = bar_in + 8 * ((lane & 1) * 7 + (lane >> 1));
              asm volatile("fence.proxy.async.global;" ::: "memory");
              mbar_expect(b, 7168);
              bulk_ld(sb + B_SA + lane * 7168, g_part + (size_t)((rt * 8 + j) * 7) * 896 + lane * 448, 7168, b);
              todo = false;
              if (!(lane & 1)) TR(1, 24 + (lane >> 1));
            }
          }
        }
      }
    }
  } else {
    asm volatile("setmaxnreg.inc.sync.aligned.u32 208;");
    const int g = lane >> 2, t = lane & 3, wq = warp & 3, t128 = tid & 127;
    uint32_t hh[56], hres[16];
    asm volatile("barrier.cluster.wait.acquire.aligned;" ::: "memory");
    asm volatile("griddepcontrol.wait;" ::: "memory");
    const uint32_t ep = __ldcg(&g_epochB), tag = (ep & 1u) << 16;
    const uint32_t rel_bar = mapa(bar_empty, t128 & 1);
    auto release = [&](int sl) { if (t128 < 2) asm volatile("mbarrier.arrive.shared::cluster.b64 _, [%0];" ::"r"(rel_bar + 8 * sl) : "memory"); };
    const uint32_t alo = __shfl_sync(~0u, ((sb + B_SA + wg * 1024) & 0x3FFFF) >> 4, 0);
    const uint32_t blo = (((sb + B_RING) & 0x3FFFF) >> 4) | (8u << 16);
    const uint32_t clo = ((sb + B_CS) & 0x3FFFF) >> 4;
    uint32_t nm0, nm1;
    if (wg == 1) asm volatile("bar.sync 3, 256;" ::: "memory");
#define G1S(Q, ST) do { g1_stage<Q, ST>(acc, alo, blo, bar_full, bar_h); wg_commit(); \
      if (ST > 0) { wg_wait<1>(); release((Q * 14 + ST - 1) % B_NSLOT); } } while (0)
#define G1HH(Q) do { \
      _Pragma("unroll") \
      for (int i = 0; i < 28; i++) hh[28 * Q + i] = pack_bf16(acc[2 * i] * acc[56 + 2 * i], acc[2 * i + 1] * acc[57 + 2 * i]); \
    } while (0)
    {
      float acc[116];
      G1S(0, 0);
      if (tid == 0) TR(1, 3);
      G1S(0, 1);
      if (wg == 0) asm volatile("bar.arrive 3, 256;" ::: "memory");
      G1S(0, 2); G1S(0, 3); G1S(0, 4); G1S(0, 5); G1S(0, 6); G1S(0, 7); G1S(0, 8); G1S(0, 9); G1S(0, 10); G1S(0, 11); G1S(0, 12);
      G1S(0, 13);
      if (tid == 0) TR(1, 4);
      mbar_wait(bar_cs, 0);
      wg_wait<0>(); reg_fence(acc); release(13 % B_NSLOT);
      {
        const uint32_t msk = t == 0 ? 0xFFFFFFFFu : t == 1 ? 0xFFFFu : 0u;
        const float a = acc[112] * (-1.f / DM), b = acc[114] * (-1.f / DM);
        nm0 = pack_bf16(a, a) & msk; nm1 = pack_bf16(b, b) & msk;
      }
      wg_fence();
      wgmma_rs224<0, 8, 1>(*(float(*)[112])acc, nm0, nm1, 0u, 0u, clo);
      wg_commit(); wg_wait<0>(); reg_fence(acc);
      G1HH(0);
      if (tid == 0) TR(1, 5);
      G1S(1, 0); G1S(1, 1); G1S(1, 2); G1S(1, 3); G1S(1, 4); G1S(1, 5); G1S(1, 6); G1S(1, 7); G1S(1, 8); G1S(1, 9); G1S(1, 10); G1S(1, 11);
#pragma unroll
      for (int i = 0; i < 4; i++) {
        int qq = lane >> 3, r = lane & 7, kg = 7 * j + 2 * i + (qq >> 1), c = 2 * wq + (qq & 1);
        if (kg > 55) kg = 55;
        uint32_t addr = sb + B_SA + kg * 2048 + wg * 1024 + r * 128 + ((c ^ r) << 4);
        asm volatile("ldmatrix.sync.aligned.m8n8.x4.trans.shared.b16 {%0,%1,%2,%3}, [%4];"
                     : "=r"(hres[4 * i]), "=r"(hres[4 * i + 1]), "=r"(hres[4 * i + 2]), "=r"(hres[4 * i + 3]) : "r"(addr) : "memory");
      }
      G1S(1, 12);
      g1_stage<1, 13>(acc, alo, blo, bar_full, bar_h);
      wgmma_rs224<224, 8, 1>(*(float(*)[112])acc, nm0, nm1, 0u, 0u, clo);
      wg_commit(); wg_wait<1>(); release(26 % B_NSLOT);
      wg_wait<0>(); reg_fence(acc); release(27 % B_NSLOT);
      G1HH(1);
      if (t128 == 0) mbar_arrive(bar_adead);
      if (tid == 0) TR(1, 6);
    }
    float accA[28], accB[28], sum[28];
    int nxt = 0;
#pragma unroll
    for (int i = 0; i < 28; i++) sum[i] = 0.f;
#define ISSUE(acc, I, a, FIRST) do { \
      constexpr int s_ = 28 + (I), sl_ = s_ % B_NSLOT; \
      mbar_wait(bar_full + 8 * sl_, (s_ / B_NSLOT) & 1); \
      wg_fence(); \
      wgmma_rs56<(sl_ * B_SLOT + 0 * 256) / 16, 112, !(FIRST)>(acc, (a)[0], (a)[1], (a)[2], (a)[3], blo); \
      wgmma_rs56<(sl_ * B_SLOT + 1 * 256) / 16, 112, 1>(acc, (a)[4], (a)[5], (a)[6], (a)[7], blo); \
      wgmma_rs56<(sl_ * B_SLOT + 2 * 256) / 16, 112, 1>(acc, (a)[8], (a)[9], (a)[10], (a)[11], blo); \
      wgmma_rs56<(sl_ * B_SLOT + 3 * 256) / 16, 112, 1>(acc, (a)[12], (a)[13], (a)[14], (a)[15], blo); \
      wgmma_rs56<(sl_ * B_SLOT + 4 * 256) / 16, 112, 1>(acc, (a)[16], (a)[17], (a)[18], (a)[19], blo); \
      wgmma_rs56<(sl_ * B_SLOT + 5 * 256) / 16, 112, 1>(acc, (a)[20], (a)[21], (a)[22], (a)[23], blo); \
      wgmma_rs56<(sl_ * B_SLOT + 6 * 256) / 16, 112, 1>(acc, (a)[24], (a)[25], (a)[26], (a)[27], blo); \
      wg_commit(); } while (0)
    auto rel = [&](int i) { if (i < 9) release((28 + i) % B_NSLOT); };
    auto tg = [&](uint32_t v) { return (v & 0xFFFEFFFFu) | tag; };
    auto send_lo = [&](float (&acc)[28], int cc) {
      reg_fence(acc);
      uint4* dst = g_part + (size_t)((rt * 8 + ((j + 1 + cc) & 7)) * 7 + cc) * 896 + wg * 448 + t128;
#pragma unroll
      for (int q = 0; q < 2; q++)
        st128(dst + q * 128, pack_bf16(acc[8 * q], acc[8 * q + 1]), pack_bf16(acc[8 * q + 2], acc[8 * q + 3]),
              pack_bf16(acc[8 * q + 4], acc[8 * q + 5]), tg(pack_bf16(acc[8 * q + 6], acc[8 * q + 7])));
    };
    auto send_hi = [&](float (&acc)[28], int cc) {
      uint4* dst = g_part + (size_t)((rt * 8 + ((j + 1 + cc) & 7)) * 7 + cc) * 896 + wg * 448;
      st128(dst + 256 + t128, pack_bf16(acc[16], acc[17]), pack_bf16(acc[18], acc[19]), pack_bf16(acc[20], acc[21]), tg(pack_bf16(acc[22], acc[23])));
      asm volatile("{\n.reg .b64 v;\nmov.b64 v, {%1, %2};\nst.relaxed.gpu.global.b64 [%0], v;\n}"
                   ::"l"((uint2*)(dst + 384) + t128), "r"(pack_bf16(acc[24], acc[25])), "r"(tg(pack_bf16(acc[26], acc[27]))) : "memory");
      if (lane == 0)
        asm volatile("st.relaxed.gpu.global.u32 [%0], %1;" ::"l"((uint32_t*)(g_flag + (rt * 8 + ((j + 1 + cc) & 7)) * 16 + cc * 2 + wg) + wq), "r"(ep) : "memory");
    };
    auto accum = [&]() {
      const unsigned char* src = sm + B_SA + nxt * 14336 + wg * 7168;
      uint4 a = *(const uint4*)(src + t128 * 16), b = *(const uint4*)(src + 2048 + t128 * 16), c = *(const uint4*)(src + 4096 + t128 * 16);
      uint2 d = *(const uint2*)(src + 6144 + t128 * 8);
      uint32_t in[14] = {a.x, a.y, a.z, a.w, b.x, b.y, b.z, b.w, c.x, c.y, c.z, c.w, d.x, d.y};
      int it = 0;
      while ((((in[3] ^ tag) | (in[7] ^ tag) | (in[11] ^ tag) | (in[13] ^ tag)) & 0x10000u) && ++it < 200000) {
        const uint4* gs = g_part + (size_t)((rt * 8 + j) * 7 + nxt) * 896 + wg * 448;
#pragma unroll
        for (int i = 0; i < 3; i++) ld128(gs + i * 128 + t128, in + 4 * i);
        asm volatile("{\n.reg .b64 v;\nld.relaxed.gpu.global.b64 v, [%2];\nmov.b64 {%0, %1}, v;\n}"
                     : "=r"(in[12]), "=r"(in[13]) : "l"((const uint2*)(gs + 384) + t128) : "memory");
      }
#pragma unroll
      for (int i = 0; i < 14; i++) { sum[2 * i] += bf_lo(in[i]); sum[2 * i + 1] += bf_hi(in[i]); }
      nxt++;
    };
    auto try_accum = [&]() {
      uint32_t ok;
      asm volatile("{\n.reg .pred p;\nmbarrier.test_wait.parity.shared::cta.b64 p, [%1], 0;\nselp.u32 %0, 1, 0, p;\n}"
                   : "=r"(ok) : "r"(bar_in + 8 * (wg * 7 + nxt)) : "memory");
      if (__all_sync(~0u, ok)) accum();
    };
#define CHUNK(cur, prev, CC, EXTRA) do { \
      ISSUE(cur, 2 * (CC), hh, true); wg_wait<1>(); rel(2 * (CC) - 1); send_lo(prev, (CC) - 1); \
      ISSUE(cur, 2 * (CC) + 1, hh + 28, false); send_hi(prev, (CC) - 1); EXTRA; wg_wait<1>(); rel(2 * (CC)); } while (0)
    ISSUE(accA, 0, hh, true);
    ISSUE(accA, 1, hh + 28, false); wg_wait<1>(); rel(0);
    CHUNK(accB, accA, 1, );
    if (tid == 0) TR(1, 11);
    CHUNK(accA, accB, 2, );
    if (tid == 0) TR(1, 12);
    CHUNK(accB, accA, 3, try_accum());
    if (tid == 0) TR(1, 13);
    CHUNK(accA, accB, 4, try_accum());
    if (tid == 0) TR(1, 14);
    CHUNK(accB, accA, 5, try_accum());
    if (tid == 0) TR(1, 16);
    CHUNK(accA, accB, 6, try_accum());
    if (tid == 0) TR(1, 17);
    CHUNK(accB, accA, 7, try_accum());
    if (tid == 0) TR(1, 7);
#pragma unroll 1
    while (nxt < 7) { mbar_wait(bar_in + 8 * (wg * 7 + nxt), 0); accum(); }
    wg_wait<0>();
    reg_fence(accB);
    if (tid == 0) TR(1, 9);
    mbar_wait(bar_stat, 0);
    const float r20 = *(const float*)(sm + B_STAT + (wg * 64 + wq * 16 + g) * 4), r21 = *(const float*)(sm + B_STAT + (wg * 64 + wq * 16 + g + 8) * 4);
    const int row = rt * 128 + wg * 64 + wq * 16 + g;
    uint32_t* o0 = (uint32_t*)(out + (size_t)row * DM + 56 * j + 2 * t);
    uint32_t* o1 = o0 + 8 * DM / 2;
#pragma unroll
    for (int i = 0; i < 7; i++) {
      o0[4 * i] = hadd2_bf(hres[2 * i], pack_bf16((sum[4 * i] + accB[4 * i]) * r20, (sum[4 * i + 1] + accB[4 * i + 1]) * r20));
      o1[4 * i] = hadd2_bf(hres[2 * i + 1], pack_bf16((sum[4 * i + 2] + accB[4 * i + 2]) * r21, (sum[4 * i + 3] + accB[4 * i + 3]) * r21));
    }
    if (tid == 0) TR(1, 10);
    if (tid == 128) TR(1, 15);

  }
}

extern "C" void kernel_launch(void* const* d_in, const int* in_sizes, int n_in, void* d_out, int out_size) {
  const __nv_bfloat16* x = (const __nv_bfloat16*)d_in[0];
  const __nv_bfloat16 *are = (const __nv_bfloat16*)d_in[1], *aim = (const __nv_bfloat16*)d_in[2], *bre = (const __nv_bfloat16*)d_in[3],
                      *bim = (const __nv_bfloat16*)d_in[4], *cre = (const __nv_bfloat16*)d_in[5], *cim = (const __nv_bfloat16*)d_in[6],
                      *logdt = (const __nv_bfloat16*)d_in[7], *dskip = (const __nv_bfloat16*)d_in[8];
  const __nv_bfloat16 *wg = (const __nv_bfloat16*)d_in[10], *wu = (const __nv_bfloat16*)d_in[11], *wd = (const __nv_bfloat16*)d_in[12];

  static bool init = false;
  if (!init) {
    init = true;
    cudaFuncSetAttribute(k_ffn, cudaFuncAttributeMaxDynamicSharedMemorySize, B_SMEM);
    cudaFuncSetAttribute(k_front, cudaFuncAttributeMaxDynamicSharedMemorySize, A_SMEM);
  }
  cudaStream_t st = cudaStreamPerThread;
  k_front<<<128, 512, A_SMEM, st>>>(x, (const uint32_t*)are, (const uint32_t*)aim, (const uint32_t*)bre, (const uint32_t*)bim,
                                    (const uint32_t*)cre, (const uint32_t*)cim, logdt, dskip, (const uint4*)wg, (const uint4*)wu, (const uint4*)wd);
  cudaLaunchConfig_t cfg = {};
  cfg.gridDim = dim3(128); cfg.blockDim = dim3(384); cfg.dynamicSmemBytes = B_SMEM; cfg.stream = st;
  cudaLaunchAttribute at[1];
  at[0].id = cudaLaunchAttributeProgrammaticStreamSerialization; at[0].val.programmaticStreamSerializationAllowed = 1;
  cfg.attrs = at; cfg.numAttrs = 1;
  cudaLaunchKernelEx(&cfg, k_ffn, (__nv_bfloat16*)d_out);
}
```

```cpp
#include <cuda_runtime.h>
#include <cuda_bf16.h>
#include <stdint.h>

constexpr int LSEQ = 2048, DM = 448;

__device__ uint4    g_himg[16 * 114688 / 16];
__device__ uint4    g_cimg[8 * 2 * 224];
__device__ uint32_t g_stat2[LSEQ];
__device__ uint4    g_part[128 * 7 * 896];
__device__ uint4    g_wimg[8 * 602112 / 16];
__device__ unsigned g_epochA, g_epochB;
__device__ uint4    g_ux[DM * 128 * 4];
__device__ unsigned g_cnt1;
__device__ uint4    g_flag[128 * 16];

#define TR(k, i) do {} while (0)
__device__ __forceinline__ uint32_t s2u(const void* p) { return (uint32_t)__cvta_generic_to_shared(p); }
__device__ __forceinline__ void mbar_init(uint32_t b, int c) { asm volatile("mbarrier.init.shared::cta.b64 [%0], %1;" ::"r"(b), "r"(c)); }
__device__ __forceinline__ void mbar_expect(uint32_t b, int bytes) { asm volatile("mbarrier.arrive.expect_tx.shared::cta.b64 _, [%0], %1;" ::"r"(b), "r"(bytes) : "memory"); }
__device__ __forceinline__ void mbar_arrive(uint32_t b) { asm volatile("mbarrier.arrive.shared::cta.b64 _, [%0];" ::"r"(b) : "memory"); }
__device__ __forceinline__ void mbar_wait(uint32_t b, int ph) {
  asm volatile("{\n.reg .pred p;\n.reg .b32 n;\nmov.b32 n, 0;\nLW:\nmbarrier.try_wait.parity.shared::cta.b64 p, [%0], %1;\n@p bra LD;\n"
               "add.u32 n, n, 1;\nsetp.lt.u32 p, n, 4000000;\n@p bra LW;\ntrap;\nLD:\n}" ::"r"(b), "r"(ph) : "memory");
}
__device__ __forceinline__ uint64_t mkdesc(uint32_t addr, uint32_t lbo, uint32_t sbo, uint32_t sw) {
  return (uint64_t)((addr & 0x3FFFF) >> 4) | ((uint64_t)((lbo >> 4) & 0x3FFF) << 16) | ((uint64_t)((sbo >> 4) & 0x3FFF) << 32) | ((uint64_t)sw << 62);
}
__device__ __forceinline__ void wg_fence() { asm volatile("wgmma.fence.sync.aligned;" ::: "memory"); }
__device__ __forceinline__ void wg_commit() { asm volatile("wgmma.commit_group.sync.aligned;" ::: "memory"); }
template <int N> __device__ __forceinline__ void wg_wait() { asm volatile("wgmma.wait_group.sync.aligned %0;" ::"n"(N) : "memory"); }
template <int N> __device__ __forceinline__ void reg_fence(float (&a)[N]) {
#pragma unroll
  for (int i = 0; i < N; i++) asm volatile("" : "+f"(a[i])::"memory");
}
__device__ __forceinline__ uint32_t pack_bf16(float lo, float hi) {
  uint32_t r; asm("cvt.rn.bf16x2.f32 %0, %1, %2;" : "=r"(r) : "f"(hi), "f"(lo)); return r;
}
__device__ __forceinline__ float bf_lo(uint32_t v) { return __uint_as_float(v << 16); }
__device__ __forceinline__ float bf_hi(uint32_t v) { return __uint_as_float(v & 0xFFFF0000u); }
__device__ __forceinline__ float rbf(float x) { return __bfloat162float(__float2bfloat16_rn(x)); }
__device__ __forceinline__ uint32_t hmul2_bf(uint32_t a, uint32_t b) { uint32_t r; asm("mul.rn.bf16x2 %0, %1, %2;" : "=r"(r) : "r"(a), "r"(b)); return r; }
__device__ __forceinline__ uint32_t hadd2_bf(uint32_t a, uint32_t b) { uint32_t r; asm("add.rn.bf16x2 %0, %1, %2;" : "=r"(r) : "r"(a), "r"(b)); return r; }
__device__ __forceinline__ void bulk_ld(uint32_t dst, const void* src, int bytes, uint32_t bar) {
  asm volatile("cp.async.bulk.shared::cluster.global.mbarrier::complete_tx::bytes [%0], [%1], %2, [%3];"
               ::"r"(dst), "l"(src), "r"(bytes), "r"(bar) : "memory");
}

__device__ __forceinline__ void bulk_ld_mc(uint32_t dst, const void* src, int bytes, uint32_t bar) {
  asm volatile("cp.async.bulk.shared::cluster.global.mbarrier::complete_tx::bytes.multicast::cluster [%0], [%1], %2, [%3], %4;"
               ::"r"(dst), "l"(src), "r"(bytes), "r"(bar), "h"((uint16_t)3) : "memory");
}
template <int AOFF, uint32_t AHI, int BOFF, uint32_t BHI, int ACC>
__device__ __forceinline__ void wgmma_ss224(float (&d)[112], uint32_t alo, uint32_t blo) {
  asm volatile("{\n.reg .pred p;\n.reg .b32 la, lb;\n.reg .b64 ad, bd;\nsetp.ne.b32 p, %118, 0;\n"
    "add.u32 la, %112, %114;\nmov.b64 ad, {la, %115};\nadd.u32 lb, %113, %116;\nmov.b64 bd, {lb, %117};\n"
    "wgmma.mma_async.sync.aligned.m64n224k16.f32.bf16.bf16 {%0,%1,%2,%3,%4,%5,%6,%7,%8,%9,%10,%11,%12,%13,%14,%15,%16,%17,%18,%19,%20,%21,%22,%23,%24,%25,%26,%27,%28,%29,%30,%31,%32,%33,%34,%35,%36,%37,%38,%39,%40,%41,%42,%43,%44,%45,%46,%47,%48,%49,%50,%51,%52,%53,%54,%55,%56,%57,%58,%59,%60,%61,%62,%63,%64,%65,%66,%67,%68,%69,%70,%71,%72,%73,%74,%75,%76,%77,%78,%79,%80,%81,%82,%83,%84,%85,%86,%87,%88,%89,%90,%91,%92,%93,%94,%95,%96,%97,%98,%99,%100,%101,%102,%103,%104,%105,%106,%107,%108,%109,%110,%111}, ad, bd, p, 1, 1, 1, 1;\n}\n"
    : "+f"(d[0]),"+f"(d[1]),"+f"(d[2]),"+f"(d[3]),"+f"(d[4]),"+f"(d[5]),"+f"(d[6]),"+f"(d[7]),"+f"(d[8]),"+f"(d[9]),"+f"(d[10]),"+f"(d[11]),"+f"(d[12]),"+f"(d[13]),"+f"(d[14]),"+f"(d[15]),"+f"(d[16]),"+f"(d[17]),"+f"(d[18]),"+f"(d[19]),"+f"(d[20]),"+f"(d[21]),"+f"(d[22]),"+f"(d[23]),"+f"(d[24]),"+f"(d[25]),"+f"(d[26]),"+f"(d[27]),"+f"(d[28]),"+f"(d[29]),"+f"(d[30]),"+f"(d[31]),"+f"(d[32]),"+f"(d[33]),"+f"(d[34]),"+f"(d[35]),"+f"(d[36]),"+f"(d[37]),"+f"(d[38]),"+f"(d[39]),"+f"(d[40]),"+f"(d[41]),"+f"(d[42]),"+f"(d[43]),"+f"(d[44]),"+f"(d[45]),"+f"(d[46]),"+f"(d[47]),"+f"(d[48]),"+f"(d[49]),"+f"(d[50]),"+f"(d[51]),"+f"(d[52]),"+f"(d[53]),"+f"(d[54]),"+f"(d[55]),"+f"(d[56]),"+f"(d[57]),"+f"(d[58]),"+f"(d[59]),"+f"(d[60]),"+f"(d[61]),"+f"(d[62]),"+f"(d[63]),"+f"(d[64]),"+f"(d[65]),"+f"(d[66]),"+f"(d[67]),"+f"(d[68]),"+f"(d[69]),"+f"(d[70]),"+f"(d[71]),"+f"(d[72]),"+f"(d[73]),"+f"(d[74]),"+f"(d[75]),"+f"(d[76]),"+f"(d[77]),"+f"(d[78]),"+f"(d[79]),"+f"(d[80]),"+f"(d[81]),"+f"(d[82]),"+f"(d[83]),"+f"(d[84]),"+f"(d[85]),"+f"(d[86]),"+f"(d[87]),"+f"(d[88]),"+f"(d[89]),"+f"(d[90]),"+f"(d[91]),"+f"(d[92]),"+f"(d[93]),"+f"(d[94]),"+f"(d[95]),"+f"(d[96]),"+f"(d[97]),"+f"(d[98]),"+f"(d[99]),"+f"(d[100]),"+f"(d[101]),"+f"(d[102]),"+f"(d[103]),"+f"(d[104]),"+f"(d[105]),"+f"(d[106]),"+f"(d[107]),"+f"(d[108]),"+f"(d[109]),"+f"(d[110]),"+f"(d[111])
    : "r"(alo), "r"(blo), "n"(AOFF), "n"(AHI), "n"(BOFF), "n"(BHI), "n"(ACC));
}
template <int AOFF, uint32_t AHI, int BOFF, uint32_t BHI, int ACC>
__device__ __forceinline__ void wgmma_ss232(float (&d)[116], uint32_t alo, uint32_t blo) {
  asm volatile("{\n.reg .pred p;\n.reg .b32 la, lb;\n.reg .b64 ad, bd;\nsetp.ne.b32 p, %122, 0;\n"
    "add.u32 la, %116, %118;\nmov.b64 ad, {la, %119};\nadd.u32 lb, %117, %120;\nmov.b64 bd, {lb, %121};\n"
    "wgmma.mma_async.sync.aligned.m64n232k16.f32.bf16.bf16 {%0,%1,%2,%3,%4,%5,%6,%7,%8,%9,%10,%11,%12,%13,%14,%15,%16,%17,%18,%19,%20,%21,%22,%23,%24,%25,%26,%27,%28,%29,%30,%31,%32,%33,%34,%35,%36,%37,%38,%39,%40,%41,%42,%43,%44,%45,%46,%47,%48,%49,%50,%51,%52,%53,%54,%55,%56,%57,%58,%59,%60,%61,%62,%63,%64,%65,%66,%67,%68,%69,%70,%71,%72,%73,%74,%75,%76,%77,%78,%79,%80,%81,%82,%83,%84,%85,%86,%87,%88,%89,%90,%91,%92,%93,%94,%95,%96,%97,%98,%99,%100,%101,%102,%103,%104,%105,%106,%107,%108,%109,%110,%111,%112,%113,%114,%115}, ad, bd, p, 1, 1, 1, 1;\n}\n"
    : "+f"(d[0]),"+f"(d[1]),"+f"(d[2]),"+f"(d[3]),"+f"(d[4]),"+f"(d[5]),"+f"(d[6]),"+f"(d[7]),"+f"(d[8]),"+f"(d[9]),"+f"(d[10]),"+f"(d[11]),"+f"(d[12]),"+f"(d[13]),"+f"(d[14]),"+f"(d[15]),"+f"(d[16]),"+f"(d[17]),"+f"(d[18]),"+f"(d[19]),"+f"(d[20]),"+f"(d[21]),"+f"(d[22]),"+f"(d[23]),"+f"(d[24]),"+f"(d[25]),"+f"(d[26]),"+f"(d[27]),"+f"(d[28]),"+f"(d[29]),"+f"(d[30]),"+f"(d[31]),"+f"(d[32]),"+f"(d[33]),"+f"(d[34]),"+f"(d[35]),"+f"(d[36]),"+f"(d[37]),"+f"(d[38]),"+f"(d[39]),"+f"(d[40]),"+f"(d[41]),"+f"(d[42]),"+f"(d[43]),"+f"(d[44]),"+f"(d[45]),"+f"(d[46]),"+f"(d[47]),"+f"(d[48]),"+f"(d[49]),"+f"(d[50]),"+f"(d[51]),"+f"(d[52]),"+f"(d[53]),"+f"(d[54]),"+f"(d[55]),"+f"(d[56]),"+f"(d[57]),"+f"(d[58]),"+f"(d[59]),"+f"(d[60]),"+f"(d[61]),"+f"(d[62]),"+f"(d[63]),"+f"(d[64]),"+f"(d[65]),"+f"(d[66]),"+f"(d[67]),"+f"(d[68]),"+f"(d[69]),"+f"(d[70]),"+f"(d[71]),"+f"(d[72]),"+f"(d[73]),"+f"(d[74]),"+f"(d[75]),"+f"(d[76]),"+f"(d[77]),"+f"(d[78]),"+f"(d[79]),"+f"(d[80]),"+f"(d[81]),"+f"(d[82]),"+f"(d[83]),"+f"(d[84]),"+f"(d[85]),"+f"(d[86]),"+f"(d[87]),"+f"(d[88]),"+f"(d[89]),"+f"(d[90]),"+f"(d[91]),"+f"(d[92]),"+f"(d[93]),"+f"(d[94]),"+f"(d[95]),"+f"(d[96]),"+f"(d[97]),"+f"(d[98]),"+f"(d[99]),"+f"(d[100]),"+f"(d[101]),"+f"(d[102]),"+f"(d[103]),"+f"(d[104]),"+f"(d[105]),"+f"(d[106]),"+f"(d[107]),"+f"(d[108]),"+f"(d[109]),"+f"(d[110]),"+f"(d[111]),"+f"(d[112]),"+f"(d[113]),"+f"(d[114]),"+f"(d[115])
    : "r"(alo), "r"(blo), "n"(AOFF), "n"(AHI), "n"(BOFF), "n"(BHI), "n"(ACC));
}
template <int OFF, uint32_t BHI, int ACC>
__device__ __forceinline__ void wgmma_rs224(float (&d)[112], uint32_t a0, uint32_t a1, uint32_t a2, uint32_t a3, uint32_t blo) {
  asm volatile("{\n.reg .pred p;\n.reg .b32 l;\n.reg .b64 bd;\nsetp.ne.b32 p, %119, 0;\nadd.u32 l, %116, %117;\nmov.b64 bd, {l, %118};\n"
    "wgmma.mma_async.sync.aligned.m64n224k16.f32.bf16.bf16 {%0,%1,%2,%3,%4,%5,%6,%7,%8,%9,%10,%11,%12,%13,%14,%15,%16,%17,%18,%19,%20,%21,%22,%23,%24,%25,%26,%27,%28,%29,%30,%31,%32,%33,%34,%35,%36,%37,%38,%39,%40,%41,%42,%43,%44,%45,%46,%47,%48,%49,%50,%51,%52,%53,%54,%55,%56,%57,%58,%59,%60,%61,%62,%63,%64,%65,%66,%67,%68,%69,%70,%71,%72,%73,%74,%75,%76,%77,%78,%79,%80,%81,%82,%83,%84,%85,%86,%87,%88,%89,%90,%91,%92,%93,%94,%95,%96,%97,%98,%99,%100,%101,%102,%103,%104,%105,%106,%107,%108,%109,%110,%111}, {%112,%113,%114,%115}, bd, p, 1, 1, 1;\n}\n"
    : "+f"(d[0]),"+f"(d[1]),"+f"(d[2]),"+f"(d[3]),"+f"(d[4]),"+f"(d[5]),"+f"(d[6]),"+f"(d[7]),"+f"(d[8]),"+f"(d[9]),"+f"(d[10]),"+f"(d[11]),"+f"(d[12]),"+f"(d[13]),"+f"(d[14]),"+f"(d[15]),"+f"(d[16]),"+f"(d[17]),"+f"(d[18]),"+f"(d[19]),"+f"(d[20]),"+f"(d[21]),"+f"(d[22]),"+f"(d[23]),"+f"(d[24]),"+f"(d[25]),"+f"(d[26]),"+f"(d[27]),"+f"(d[28]),"+f"(d[29]),"+f"(d[30]),"+f"(d[31]),"+f"(d[32]),"+f"(d[33]),"+f"(d[34]),"+f"(d[35]),"+f"(d[36]),"+f"(d[37]),"+f"(d[38]),"+f"(d[39]),"+f"(d[40]),"+f"(d[41]),"+f"(d[42]),"+f"(d[43]),"+f"(d[44]),"+f"(d[45]),"+f"(d[46]),"+f"(d[47]),"+f"(d[48]),"+f"(d[49]),"+f"(d[50]),"+f"(d[51]),"+f"(d[52]),"+f"(d[53]),"+f"(d[54]),"+f"(d[55]),"+f"(d[56]),"+f"(d[57]),"+f"(d[58]),"+f"(d[59]),"+f"(d[60]),"+f"(d[61]),"+f"(d[62]),"+f"(d[63]),"+f"(d[64]),"+f"(d[65]),"+f"(d[66]),"+f"(d[67]),"+f"(d[68]),"+f"(d[69]),"+f"(d[70]),"+f"(d[71]),"+f"(d[72]),"+f"(d[73]),"+f"(d[74]),"+f"(d[75]),"+f"(d[76]),"+f"(d[77]),"+f"(d[78]),"+f"(d[79]),"+f"(d[80]),"+f"(d[81]),"+f"(d[82]),"+f"(d[83]),"+f"(d[84]),"+f"(d[85]),"+f"(d[86]),"+f"(d[87]),"+f"(d[88]),"+f"(d[89]),"+f"(d[90]),"+f"(d[91]),"+f"(d[92]),"+f"(d[93]),"+f"(d[94]),"+f"(d[95]),"+f"(d[96]),"+f"(d[97]),"+f"(d[98]),"+f"(d[99]),"+f"(d[100]),"+f"(d[101]),"+f"(d[102]),"+f"(d[103]),"+f"(d[104]),"+f"(d[105]),"+f"(d[106]),"+f"(d[107]),"+f"(d[108]),"+f"(d[109]),"+f"(d[110]),"+f"(d[111])
    : "r"(a0), "r"(a1), "r"(a2), "r"(a3), "r"(blo), "n"(OFF), "n"(BHI), "n"(ACC));
}
template <int OFF, uint32_t BHI, int ACC>
__device__ __forceinline__ void wgmma_rs56(float (&d)[28], uint32_t a0, uint32_t a1, uint32_t a2, uint32_t a3, uint32_t blo) {
  asm volatile("{\n.reg .pred p;\n.reg .b32 l;\n.reg .b64 bd;\nsetp.ne.b32 p, %35, 0;\nadd.u32 l, %32, %33;\nmov.b64 bd, {l, %34};\n"
    "wgmma.mma_async.sync.aligned.m64n56k16.f32.bf16.bf16 {%0,%1,%2,%3,%4,%5,%6,%7,%8,%9,%10,%11,%12,%13,%14,%15,%16,%17,%18,%19,%20,%21,%22,%23,%24,%25,%26,%27}, {%28,%29,%30,%31}, bd, p, 1, 1, 1;\n}\n"
    : "+f"(d[0]),"+f"(d[1]),"+f"(d[2]),"+f"(d[3]),"+f"(d[4]),"+f"(d[5]),"+f"(d[6]),"+f"(d[7]),"+f"(d[8]),"+f"(d[9]),"+f"(d[10]),"+f"(d[11]),"+f"(d[12]),"+f"(d[13]),"+f"(d[14]),"+f"(d[15]),"+f"(d[16]),"+f"(d[17]),"+f"(d[18]),"+f"(d[19]),"+f"(d[20]),"+f"(d[21]),"+f"(d[22]),"+f"(d[23]),"+f"(d[24]),"+f"(d[25]),"+f"(d[26]),"+f"(d[27])
    : "r"(a0), "r"(a1), "r"(a2), "r"(a3), "r"(blo), "n"(OFF), "n"(BHI), "n"(ACC));
}

__device__ __forceinline__ void st128(uint4* p, uint32_t a, uint32_t b, uint32_t c, uint32_t d) {
  asm volatile("{\n.reg .b128 v;\n.reg .b64 lo, hi;\nmov.b64 lo, {%1, %2};\nmov.b64 hi, {%3, %4};\nmov.b128 v, {lo, hi};\n"
               "st.relaxed.gpu.global.b128 [%0], v;\n}" ::"l"(p), "r"(a), "r"(b), "r"(c), "r"(d) : "memory");
}
__device__ __forceinline__ void ld128(const uint4* p, uint32_t* r) {
  asm volatile("{\n.reg .b128 v;\n.reg .b64 lo, hi;\nld.relaxed.gpu.global.b128 v, [%4];\nmov.b128 {lo, hi}, v;\n"
               "mov.b64 {%0, %1}, lo;\nmov.b64 {%2, %3}, hi;\n}" : "=r"(r[0]), "=r"(r[1]), "=r"(r[2]), "=r"(r[3]) : "l"(p) : "memory");
}

template <int OFF, uint32_t BHI, int ACC>
__device__ __forceinline__ void wgmma_rs32(float (&d)[16], uint32_t a0, uint32_t a1, uint32_t a2, uint32_t a3, uint32_t blo) {
  asm volatile("{\n.reg .pred p;\n.reg .b32 l;\n.reg .b64 bd;\nsetp.ne.b32 p, %23, 0;\nadd.u32 l, %20, %21;\nmov.b64 bd, {l, %22};\n"
    "wgmma.mma_async.sync.aligned.m64n32k16.f32.bf16.bf16 {%0,%1,%2,%3,%4,%5,%6,%7,%8,%9,%10,%11,%12,%13,%14,%15}, {%16,%17,%18,%19}, bd, p, 1, 1, 0;\n}\n"
    : "+f"(d[0]),"+f"(d[1]),"+f"(d[2]),"+f"(d[3]),"+f"(d[4]),"+f"(d[5]),"+f"(d[6]),"+f"(d[7]),"+f"(d[8]),"+f"(d[9]),"+f"(d[10]),"+f"(d[11]),"+f"(d[12]),"+f"(d[13]),"+f"(d[14]),"+f"(d[15])
    : "r"(a0), "r"(a1), "r"(a2), "r"(a3), "r"(blo), "n"(OFF), "n"(BHI), "n"(ACC));
}
template <int OFF, uint32_t BHI, int ACC>
__device__ __forceinline__ void wgmma_rs24(float (&d)[12], uint32_t a0, uint32_t a1, uint32_t a2, uint32_t a3, uint32_t blo) {
  asm volatile("{\n.reg .pred p;\n.reg .b32 l;\n.reg .b64 bd;\nsetp.ne.b32 p, %19, 0;\nadd.u32 l, %16, %17;\nmov.b64 bd, {l, %18};\n"
    "wgmma.mma_async.sync.aligned.m64n24k16.f32.bf16.bf16 {%0,%1,%2,%3,%4,%5,%6,%7,%8,%9,%10,%11}, {%12,%13,%14,%15}, bd, p, 1, 1, 1;\n}\n"
    : "+f"(d[0]),"+f"(d[1]),"+f"(d[2]),"+f"(d[3]),"+f"(d[4]),"+f"(d[5]),"+f"(d[6]),"+f"(d[7]),"+f"(d[8]),"+f"(d[9]),"+f"(d[10]),"+f"(d[11])
    : "r"(a0), "r"(a1), "r"(a2), "r"(a3), "r"(blo), "n"(OFF), "n"(BHI), "n"(ACC));
}
template <int OFF, uint32_t BHI, int ACC>
__device__ __forceinline__ void wgmma_rs16(float (&d)[8], uint32_t a0, uint32_t a1, uint32_t a2, uint32_t a3, uint32_t blo) {
  asm volatile("{\n.reg .pred p;\n.reg .b32 l;\n.reg .b64 bd;\nsetp.ne.b32 p, %15, 0;\nadd.u32 l, %12, %13;\nmov.b64 bd, {l, %14};\n"
    "wgmma.mma_async.sync.aligned.m64n16k16.f32.bf16.bf16 {%0,%1,%2,%3,%4,%5,%6,%7}, {%8,%9,%10,%11}, bd, p, 1, 1, 1;\n}\n"
    : "+f"(d[0]),"+f"(d[1]),"+f"(d[2]),"+f"(d[3]),"+f"(d[4]),"+f"(d[5]),"+f"(d[6]),"+f"(d[7])
    : "r"(a0), "r"(a1), "r"(a2), "r"(a3), "r"(blo), "n"(OFF), "n"(BHI), "n"(ACC));
}

constexpr int A_R1 = 0;
constexpr int A_R2A = A_R1 + 2624, A_R2B = A_R2A + 768, A_R3A = A_R2B + 768, A_R3B = A_R3A + 528;
constexpr int A_K1024 = A_R3B + 528;
constexpr int A_W5 = A_K1024 + 16;
constexpr int A_W3 = A_W5 + 4096;
constexpr int A_W9 = A_W3 + 4112;
constexpr int A_W7 = A_W9 + 2048;
constexpr int A_V  = A_W7 + 2048;
constexpr int A_UB = A_V + 2048;
constexpr int A_STG = A_UB + 5248;
constexpr int A_Y2 = A_STG, A_Y3 = A_Y2 + 6528, A_YB = A_Y3 + 4352;
constexpr int A_REC = A_STG + 4 * 4352;
constexpr int A_CH = A_REC + 8192;
constexpr int A_BAR = 4 * A_CH;
constexpr int A_SMEM = A_BAR + 64;
static_assert(A_W5 % 16 == 0 && A_UB % 16 == 0 && A_CH % 16 == 0 && A_YB + 4096 <= A_REC, "layout");

struct cf { float x, y; };
__device__ __forceinline__ cf cmul(cf a, cf b) { cf r; r.x = fmaf(a.x, b.x, -a.y * b.y); r.y = fmaf(a.x, b.y, a.y * b.x); return r; }
__device__ __forceinline__ cf cexp_l(float lr, float li, float l) {
  float mag; asm("ex2.approx.ftz.f32 %0, %1;" : "=f"(mag) : "f"((lr * l) * 1.4426950408889634f));
  const float th = li * l;
  const float k = (fmaf(th, 0.15915494f, 12582912.f)) - 12582912.f;
  float ph = fmaf(th, 0.15915494f, -k);
  ph = fmaf(th, 6.4206383e-9f, ph) * 6.2831853f;
  cf r; r.x = mag * __cosf(ph); r.y = mag * __sinf(ph); return r;
}
__device__ __forceinline__ void sts16(uint32_t a, uint32_t v) { asm volatile("st.shared.u16 [%0], %1;" ::"r"(a), "h"((uint16_t)v) : "memory"); }
__device__ __forceinline__ void sts32(uint32_t a, uint32_t v) { asm volatile("st.shared.u32 [%0], %1;" ::"r"(a), "r"(v) : "memory"); }
__device__ __forceinline__ void sts64(uint32_t a, uint32_t v0, uint32_t v1) { asm volatile("st.shared.v2.u32 [%0], {%1, %2};" ::"r"(a), "r"(v0), "r"(v1) : "memory"); }
__device__ __forceinline__ void sts128(uint32_t a, uint32_t v0, uint32_t v1, uint32_t v2, uint32_t v3) {
  asm volatile("st.shared.v4.u32 [%0], {%1, %2, %3, %4};" ::"r"(a), "r"(v0), "r"(v1), "r"(v2), "r"(v3) : "memory");
}
__device__ __forceinline__ uint32_t lds32(uint32_t a) { uint32_t v; asm volatile("ld.shared.u32 %0, [%1];" : "=r"(v) : "r"(a) : "memory"); return v; }
__device__ __forceinline__ uint4 lds128(uint32_t a) {
  uint4 v; asm volatile("ld.shared.v4.u32 {%0, %1, %2, %3}, [%4];" : "=r"(v.x), "=r"(v.y), "=r"(v.z), "=r"(v.w) : "r"(a) : "memory"); return v;
}
__device__ __forceinline__ void ldsm4(uint32_t* r, uint32_t a) {
  asm volatile("ldmatrix.sync.aligned.m8n8.x4.shared.b16 {%0,%1,%2,%3}, [%4];" : "=r"(r[0]), "=r"(r[1]), "=r"(r[2]), "=r"(r[3]) : "r"(a) : "memory");
}
__device__ __forceinline__ void mma16816(float* d, const uint32_t* a, uint32_t b0, uint32_t b1) {
  asm volatile("mma.sync.aligned.m16n8k16.row.col.f32.bf16.bf16.f32 {%0,%1,%2,%3}, {%4,%5,%6,%7}, {%8,%9}, {%0,%1,%2,%3};"
               : "+f"(d[0]), "+f"(d[1]), "+f"(d[2]), "+f"(d[3]) : "r"(a[0]), "r"(a[1]), "r"(a[2]), "r"(a[3]), "r"(b0), "r"(b1));
}
__device__ __forceinline__ uint32_t hsub2_bf(uint32_t a, uint32_t b) { uint32_t r; asm("sub.rn.bf16x2 %0, %1, %2;" : "=r"(r) : "r"(a), "r"(b)); return r; }
__device__ __forceinline__ void bar_sync(int id, int n) { asm volatile("bar.sync %0, %1;" ::"r"(id), "r"(n) : "memory"); }

template <int S> struct F1B { static constexpr int c = S / 4 + ((S & 3) == 3 ? 0 : 0), cc = (16 * S) / 64, ks = (64 * cc - (16 * S - 48)) / 16, off = (A_UB + 2 * ks * 656 + (9 - cc) * 16) / 16; };

template <int NS>
__device__ __forceinline__ void load_quads(uint32_t* q, uint32_t addr) {
#pragma unroll
  for (int i = 0; i < NS; i++) {
    q[4 * i] = lds32(addr + i * 64); q[4 * i + 1] = lds32(addr + i * 64 + 32);
    q[4 * i + 2] = i ? q[4 * i - 3] : lds32(addr - 32);
    q[4 * i + 3] = q[4 * i];
  }
#pragma unroll
  for (int i = 0; i < 4 * NS; i++) asm volatile("" : "+r"(q[i]));
}
template <int S0, int NS>
__device__ __forceinline__ void f1_steps(float (&acc)[16], const uint32_t* a, uint32_t blo) {
  if constexpr (NS > 0) {
    wgmma_rs32<F1B<S0>::off, 8, S0 != 0>(acc, a[0], a[1], a[2], a[3], blo);
    f1_steps<S0 + 1, NS - 1>(acc, a + 4, blo);
  }
}
template <int S0, int NS, int BASE, int FIRST>
__device__ __forceinline__ void s2_steps(float (&acc)[12], const uint32_t* a, uint32_t blo) {
  if constexpr (NS > 0) {
    wgmma_rs24<BASE / 16 + (112 - 16 * S0), 64, !(FIRST && S0 == 0)>(acc, a[0], a[1], a[2], a[3], blo);
    s2_steps<S0 + 1, NS - 1, BASE, FIRST>(acc, a + 4, blo);
  }
}
template <int S0, int NS, int BASE, int FIRST>
__device__ __forceinline__ void s3_steps(float (&acc)[8], const uint32_t* a, uint32_t blo) {
  if constexpr (NS > 0) {
    wgmma_rs16<BASE / 16 + (48 - 16 * S0), 64, !(FIRST && S0 == 0)>(acc, a[0], a[1], a[2], a[3], blo);
    s3_steps<S0 + 1, NS - 1, BASE, FIRST>(acc, a + 4, blo);
  }
}

__global__ void __launch_bounds__(512, 1)
k_front(const __nv_bfloat16* __restrict__ x, const uint32_t* __restrict__ are, const uint32_t* __restrict__ aim,
        const uint32_t* __restrict__ bre, const uint32_t* __restrict__ bim, const uint32_t* __restrict__ cre,
        const uint32_t* __restrict__ cim, const unsigned short* __restrict__ logdt, const unsigned short* __restrict__ dskip,
        const uint4* __restrict__ wgate, const uint4* __restrict__ wup, const uint4* __restrict__ wdown) {
  extern __shared__ __align__(1024) unsigned char sm[];
  const uint32_t sb = s2u(sm);
  const int tid = threadIdx.x, wg = tid >> 7, warp = tid >> 5, lane = tid & 31, wq = warp & 3, t128 = tid & 127;
  const int blk = blockIdx.x;
  const bool conv = blk < 112;
  if (tid == 320) TR(0, 0);
  asm volatile("griddepcontrol.launch_dependents;");

  uint2 xr[4];
  {
    const uint2* p = (const uint2*)(x + (size_t)(blk * 16 + warp) * DM);
    xr[0] = __ldg(p + lane); xr[1] = __ldg(p + 32 + lane); xr[2] = __ldg(p + 64 + lane);
    xr[3] = lane < 16 ? __ldg(p + 96 + lane) : make_uint2(0, 0);
  }
  const int ch = conv ? blk * 4 + wg : 0;
  const uint32_t cb = sb + wg * A_CH;
  uint32_t prm[6];
  {
    const int i = ch * 128 + t128;
    prm[0] = __ldg(are + i); prm[1] = __ldg(aim + i); prm[2] = __ldg(bre + i); prm[3] = __ldg(bim + i); prm[4] = __ldg(cre + i); prm[5] = __ldg(cim + i);
  }
  const uint32_t ldt = __ldg(logdt + ch);
  if (tid == 160) { mbar_init(sb + A_BAR, 1); asm volatile("fence.mbarrier_init.release.cluster;" ::: "memory"); }
#pragma unroll
  for (int i = 0; i < 4; i++) if (i < 3 || t128 < (A_W5 + 1024) / 16 - 384) sts128(cb + (i * 128 + t128) * 16, 0, 0, 0, 0);
  if (t128 < 65) sts128(cb + (t128 < 64 ? A_W3 + t128 * 16 : A_W9), 0, 0, 0, 0);
  if (t128 < 72) sts128(cb + A_UB + (t128 / 9) * 656 + (t128 % 9) * 16, 0, 0, 0, 0);
  {
    float s = 0.f, q = 0.f;
#pragma unroll
    for (int i = 0; i < 4; i++) {
      const float a = bf_lo(xr[i].x), b = bf_hi(xr[i].x), c = bf_lo(xr[i].y), d = bf_hi(xr[i].y);
      s += (a + b) + (c + d);
      q = fmaf(a, a, q); q = fmaf(b, b, q); q = fmaf(c, c, q); q = fmaf(d, d, q);
    }
#pragma unroll
    for (int o = 16; o; o >>= 1) { s += __shfl_xor_sync(~0u, s, o); q += __shfl_xor_sync(~0u, q, o); }
    const float mean = s * (1.f / DM);
    const float var = fmaxf(fmaf(-mean, mean, q * (1.f / DM)), 0.f);
    const float rs = __frcp_rn(rbf(__fsqrt_rn(rbf(rbf(var) + 1e-5f))));
    const uint32_t mm = pack_bf16(mean, mean);
    const uint32_t tu = sb + A_REC + (warp >> 3) * A_CH + (warp & 7) * 912 + lane * 8, tx = tu + 2 * A_CH;
#pragma unroll
    for (int i = 0; i < 4; i++) {
      if (i < 3 || lane < 16) {
        const uint32_t d0 = hsub2_bf(xr[i].x, mm), d1 = hsub2_bf(xr[i].y, mm);
        sts64(tu + i * 256, pack_bf16(bf_lo(d0) * rs, bf_hi(d0) * rs), pack_bf16(bf_lo(d1) * rs, bf_hi(d1) * rs));
        sts64(tx + i * 256, xr[i].x, xr[i].y);
      }
    }
  }
  if (tid == 320) TR(0, 1);
  auto publish_rows = [&]() {
    bar_sync(5, 512);
    uint4* dst = g_ux + ((size_t)(warp * 8 + (lane >> 2)) * 128 + blk) * 4 + ((lane ^ (blk >> 1)) & 3);
#pragma unroll
    for (int i = 0; i < 4; i++) {
      if (i < 3 || warp < 8) {
        uint32_t r[4];
        asm volatile("ldmatrix.sync.aligned.m8n8.x4.trans.shared.b16 {%0,%1,%2,%3}, [%4];" : "=r"(r[0]), "=r"(r[1]), "=r"(r[2]), "=r"(r[3])
                     : "r"(sb + A_REC + (lane >> 3) * A_CH + (lane & 7) * 912 + (warp + 16 * i) * 16) : "memory");
        dst[i * 65536] = make_uint4(r[0], r[1], r[2], r[3]);
      }
    }
    if (warp != 0) asm volatile("bar.arrive 6, 512;" ::: "memory");
  };
  auto release_rows = [&]() {
    if (warp == 0) {
      bar_sync(6, 512);
      if (lane == 0) { asm volatile("red.release.gpu.global.add.u32 [%0], 1;" ::"l"(&g_cnt1) : "memory"); TR(0, 8); }
      __syncwarp();
    }
  };

  if (!conv) {
    publish_rows();
    release_rows();
    const int a = blk - 112, mat = a >> 3, j = a & 7;
    if (tid == 160 && a == 0) g_epochB = __ldcg(&g_epochA) + 1u;
    float s[8];
#pragma unroll
    for (int k = 0; k < 8; k++) s[k] = 0.f;
    if (lane < 28) {
      const uint4* src = (mat ? wup : wgate) + j * 28 + lane + (size_t)warp * 224;
#pragma unroll
      for (int hb = 0; hb < 2; hb++) {
        uint4 v[14];
#pragma unroll
        for (int r = 0; r < 14; r++) v[r] = __ldg(src + (size_t)(hb * 14 + r) * 16 * 224);
#pragma unroll
        for (int r = 0; r < 14; r++) {
          s[0] += bf_lo(v[r].x); s[1] += bf_hi(v[r].x); s[2] += bf_lo(v[r].y); s[3] += bf_hi(v[r].y);
          s[4] += bf_lo(v[r].z); s[5] += bf_hi(v[r].z); s[6] += bf_lo(v[r].w); s[7] += bf_hi(v[r].w);
        }
      }
      float4* red = (float4*)(sm + A_STG + warp * 896 + lane * 32);
      red[0] = make_float4(s[0], s[1], s[2], s[3]); red[1] = make_float4(s[4], s[5], s[6], s[7]);
    }
    bar_sync(5, 512);
    if (tid < 224) {
      float t = 0.f;
#pragma unroll
      for (int w = 0; w < 16; w++) t += *(const float*)(sm + A_STG + w * 896 + tid * 4);
      const float hi = rbf(t), mid = rbf(t - hi), lo = rbf(t - hi - mid);
      const int q = tid / 112, n = tid % 112 + 112 * mat;
      __nv_bfloat16* dst = (__nv_bfloat16*)(g_cimg + (j * 2 + q) * 224 + (n >> 3) * 8) + (n & 7);
      dst[0] = __float2bfloat16_rn(hi); dst[8] = __float2bfloat16_rn(mid); dst[16] = __float2bfloat16_rn(lo);
#pragma unroll
      for (int k = 3; k < 8; k++) dst[8 * k] = __float2bfloat16_rn(0.f);
    }
    if (tid == 320) TR(0, 10);
    return;
  }

  const int g = lane >> 2, t = lane & 3;
  const int wr = (wq + wg) & 3;
  uint4 wv[6];
  auto w_src = [&](int i) -> const uint4* {
    if (i < 4) return (blk < 56 ? wgate : wup) + (blk % 56) * 4 + (lane & 3) + (size_t)(i * 128 + warp * 8 + (lane >> 2)) * 224;
    const int it = warp + 16 * (i - 4);
    return wdown + (size_t)(blk * 16 + (it / 14) * 8 + (lane >> 2)) * 56 + (it % 14) * 4 + (lane & 3);
  };
  auto w_on = [&](int i) { return i == 3 ? warp < 8 : i == 5 ? warp < 12 : true; };
  {
    const uint32_t stg = cb + A_STG + wq * 4352;
    const float dt = rbf(expf(__uint_as_float(ldt << 16)));
    float lr[2], li[2];
    cf bq[2], b0[2], b4[2];
    uint32_t bf[48];
#pragma unroll
    for (int m = 0; m < 2; m++) {
      lr[m] = dt * (m ? bf_hi(prm[0]) : bf_lo(prm[0]));
      li[m] = dt * (m ? bf_hi(prm[1]) : bf_lo(prm[1]));
    }
    {
      cf b[2], z[2];
#pragma unroll
      for (int m = 0; m < 2; m++) {
        cf db, c;
        db.x = dt * (m ? bf_hi(prm[2]) : bf_lo(prm[2])); db.y = -dt * (m ? bf_hi(prm[3]) : bf_lo(prm[3]));
        c.x = m ? bf_hi(prm[4]) : bf_lo(prm[4]); c.y = -(m ? bf_hi(prm[5]) : bf_lo(prm[5]));
        b[m] = cmul(c, db);
        z[m] = cexp_l(lr[m], -li[m], 1.f);
        bq[m] = cexp_l(lr[m], -li[m], 256.f);
      }
#pragma unroll
      for (int i = 0; i < 8; i++) {
        sts64(stg + i * 272 + lane * 8, pack_bf16(b[0].x, b[0].y), pack_bf16(b[1].x, b[1].y));
        if (!(i & 1)) {
          cf e0 = cmul(b[0], bq[0]), e1 = cmul(b[1], bq[1]);
          sts64(stg + (8 + i / 2) * 272 + lane * 8, pack_bf16(e0.x, e0.y), pack_bf16(e1.x, e1.y));
          if (i == 0) { b0[0] = e0; b0[1] = e1; }
          if (i == 4) { b4[0] = e0; b4[1] = e1; }
        }
        if (i < 7) { b[0] = cmul(b[0], z[0]); b[1] = cmul(b[1], z[1]); }
        if (i == 1) publish_rows();
      }
#pragma unroll
      for (int i = 0; i < 7; i++) {
        b0[0] = cmul(b0[0], bq[0]); b0[1] = cmul(b0[1], bq[1]);
        sts64(stg + (i < 2 ? 12 + 2 * i : i - 2) * 272 + lane * 8, pack_bf16(b0[0].x, b0[0].y), pack_bf16(b0[1].x, b0[1].y));
        if (i < 2) {
          b4[0] = cmul(b4[0], bq[0]); b4[1] = cmul(b4[1], bq[1]);
          sts64(stg + (13 + 2 * i) * 272 + lane * 8, pack_bf16(b4[0].x, b4[0].y), pack_bf16(b4[1].x, b4[1].y));
        }
        if (i == 1) {
          __syncwarp();
#pragma unroll
          for (int n = 0; n < 2; n++)
#pragma unroll
            for (int k2 = 0; k2 < 4; k2++) ldsm4(bf + n * 16 + k2 * 4, stg + (n * 8 + (lane & 7)) * 272 + k2 * 64 + (lane >> 3) * 16);
          __syncwarp();
        }
      }
    }
    __syncwarp();
#pragma unroll
    for (int k2 = 0; k2 < 4; k2++) ldsm4(bf + 32 + k2 * 4, stg + (lane & 7) * 272 + k2 * 64 + (lane >> 3) * 16);
    release_rows();
    if (!(lane & 1)) {
#pragma unroll
      for (int i = 0; i < 6; i++) if (w_on(i)) asm volatile("prefetch.global.L2 [%0];" ::"l"(w_src(i)));
    }
    if (tid == 320) TR(0, 16);
    float c[6][4];
#pragma unroll
    for (int i = 0; i < 6; i++) { c[i][0] = 0.f; c[i][1] = 0.f; c[i][2] = 0.f; c[i][3] = 0.f; }
    cf p[2], v[2];
    p[0] = cexp_l(lr[0], li[0], 8.f); p[1] = cexp_l(lr[1], li[1], 8.f);
    v[0].x = 1.f; v[0].y = 0.f; v[1] = v[0];
#pragma unroll
    for (int mt = 0; mt < 2; mt++) {
      __syncwarp();
#pragma unroll
      for (int i = 0; i < 16; i++) {
        sts64(stg + i * 272 + lane * 8, pack_bf16(v[0].x, v[0].y), pack_bf16(v[1].x, v[1].y));
        if (mt == 0 && i == 0) { v[0] = p[0]; v[1] = p[1]; }
        else if (mt == 0 || i < 15) { v[0] = cmul(v[0], p[0]); v[1] = cmul(v[1], p[1]); }
      }
      __syncwarp();
      if (mt == 1 && tid == 160) {
        const uint32_t tgt = (__ldcg(&g_epochA) + 1u) * 128u;
        uint32_t cv; int it = 0;
        do { asm volatile("ld.acquire.gpu.global.u32 %0, [%1];" : "=r"(cv) : "l"(&g_cnt1) : "memory"); } while ((int)(cv - tgt) < 0 && ++it < 200000);
        asm volatile("fence.proxy.async;" ::: "memory");
        TR(0, 9);
        mbar_expect(sb + A_BAR, 32768);
        for (int c2 = 0; c2 < 4; c2++) bulk_ld(sb + c2 * A_CH + A_REC, g_ux + (size_t)(blk * 4 + c2) * 512, 8192, sb + A_BAR);
      }
#pragma unroll
      for (int ks = 0; ks < 8; ks++) {
        uint32_t a[4];
        ldsm4(a, stg + (lane & 15) * 272 + ks * 32 + (lane >> 4) * 16);
#pragma unroll
        for (int n = 0; n < 3; n++) mma16816(c[n * 2 + mt], a, bf[n * 16 + ks * 2], bf[n * 16 + ks * 2 + 1]);
      }
    }
    __syncwarp();
#pragma unroll
    for (int i = 0; i < 6; i++)
      sts128(stg + i * 512 + lane * 16, __float_as_uint(c[i][0]), __float_as_uint(c[i][1]), __float_as_uint(c[i][2]), __float_as_uint(c[i][3]));
#pragma unroll
    for (int i = 0; i < 6; i++) if (w_on(i)) wv[i] = __ldg(w_src(i));
    bar_sync(1 + wg, 128);
    if (tid == 320) TR(0, 2);
#pragma unroll
    for (int rep = 0; rep < 2; rep++) {
      const int qd = rep ? 2 + wr : 3 - wr;
      if (rep == 0 || wr >= 2) {
        float s[4] = {0.f, 0.f, 0.f, 0.f};
#pragma unroll
        for (int w = 0; w < 4; w++) {
          uint4 u4 = lds128(cb + A_STG + w * 4352 + qd * 512 + lane * 16);
          s[0] += __uint_as_float(u4.x); s[1] += __uint_as_float(u4.y); s[2] += __uint_as_float(u4.z); s[3] += __uint_as_float(u4.w);
        }
#pragma unroll
        for (int hf = 0; hf < 2; hf++) {
          const int j = (qd & 1) * 16 + g + 8 * hf;
          const uint32_t pk = pack_bf16(s[2 * hf + 1], s[2 * hf]);
          const uint32_t v0 = pk >> 16, v1 = pk & 0xFFFFu, v00 = v0 * 0x10001u;
          if (rep == 1) {
            if (t < 2) {
#pragma unroll
              for (int e = 0; e < 2; e++) {
                const int lam = 128 + 32 * (2 * t + e) + j, mu = lam >> 1;
                const uint32_t val = e ? v1 : v0;
                uint32_t a = cb + ((lam & 1) ? A_R3B : A_R3A) + mu * 4;
                if (lam == 128) { a = cb + A_R2A + 128 * 4; sts32(cb + A_K1024, val << 16); }
                sts16(a, val); sts16(a + 6, val);
              }
            } else if (t == 2 && j == 0) { sts16(cb + A_R3A + 128 * 4, v0); }
          } else if (qd < 2) {
            const uint32_t a = cb + A_R1 + (62 + 8 * j + 2 * t) * 4;
            sts16(a, v0); sts32(a + 4, pk); sts16(a + 10, v1);
          } else if (t < 2) {
            const int L = 256 + 8 * j + 4 * t;
            const uint32_t a = cb + A_R1 + (62 + L) * 4;
            if (L > 256) { sts16(a - 4, v0); sts32(a, v00); } else sts16(a, v0);
            sts32(a + 4, v00); sts32(a + 8, pk); sts16(a + 14, v1);
          } else {
            const int mu = 64 + 32 * (t - 2) + j;
            if (mu == 64) {
              const uint32_t a = cb + A_R1 + (62 + 512) * 4;
              sts16(a - 4, v0); sts32(a, v00); sts32(a + 4, v00); sts32(a + 8, v00); sts16(a + 14, v0);
            } else { sts16(cb + A_R2A + mu * 4, v0); sts16(cb + A_R2A + mu * 4 + 6, v0); }
            sts16(cb + A_R2B + mu * 4, v1); sts16(cb + A_R2B + mu * 4 + 6, v1);
          }
        }
      }
    }
  }
  {
    const int ngg = (blk % 56) * 4 + (lane & 3), j = ngg / 28, q = (ngg % 28) / 14, ng = ngg % 14 + (blk < 56 ? 0 : 14);
    uint4* dst = g_wimg + (size_t)j * 37632 + q * 14 * 896 + ng * 32 + (warp >> 2) * 896 + (warp & 3) * 8 + (lane >> 2);
#pragma unroll
    for (int i = 0; i < 4; i++) if (w_on(i)) dst[i * 4 * 896] = wv[i];
#pragma unroll
    for (int i = 4; i < 6; i++) {
      const int it = warp + 16 * (i - 4), n2 = (it % 14) * 4 + (lane & 3), k = (blk % 7) * 16 + (it / 14) * 8 + (lane >> 2);
      if (w_on(i)) g_wimg[(size_t)(blk / 14) * 37632 + 25088 + ((n2 / 7) * 2 + (blk / 7) % 2) * 784 + (n2 % 7) * 112 + k] = wv[i];
    }
  }
  if (tid == 320) TR(0, 3);

  const int bk = wr * 32 + lane;
  uint32_t xt[8], ud[8];
  {
    mbar_wait(sb + A_BAR, 0);
    if (tid == 320) TR(0, 4);
    uint4 r[4];
#pragma unroll
    for (int i = 0; i < 4; i++) r[i] = lds128(cb + A_REC + bk * 64 + ((i ^ (bk >> 1)) & 3) * 16);
    const uint32_t ua = cb + A_UB + ((2 * bk) & 7) * 656 + ((bk >> 2) + 9) * 16;
    sts128(ua, r[0].x, r[1].x, r[2].x, r[3].x);
    sts128(ua + 656, r[0].y, r[1].y, r[2].y, r[3].y);
    if (bk <= 96) {
      const bool neg = bk == 96;
      const int bp = neg ? -1 : bk;
      uint32_t h[4];
      h[0] = lds32(cb + A_REC + ((bp - 1) & 127) * 64 + ((2 ^ ((bp - 1) >> 1)) & 3) * 16 + 4);
      h[1] = lds32(cb + A_REC + ((bp - 1) & 127) * 64 + ((3 ^ ((bp - 1) >> 1)) & 3) * 16 + 4);
      h[2] = lds32(cb + A_REC + (bp + 1) * 64 + ((0 ^ ((bp + 1) >> 1)) & 3) * 16);
      h[3] = lds32(cb + A_REC + (bp + 1) * 64 + ((1 ^ ((bp + 1) >> 1)) & 3) * 16);
      if (bp <= 0) { h[0] = 0; h[1] = 0; }
      const uint32_t wd[12] = {h[0], h[1], neg ? 0 : r[0].x, neg ? 0 : r[1].x, neg ? 0 : r[2].x, neg ? 0 : r[3].x,
                               neg ? 0 : r[0].y, neg ? 0 : r[1].y, neg ? 0 : r[2].y, neg ? 0 : r[3].y, h[2], h[3]};
      float P[25];
      P[0] = 0.f;
#pragma unroll
      for (int i = 0; i < 12; i++) { P[2 * i + 1] = P[2 * i] + bf_lo(wd[i]); P[2 * i + 2] = P[2 * i + 1] + bf_hi(wd[i]); }
#define WIN(i, hw) (P[(i) + 5 + (hw)] - P[(i) + 4 - (hw)])
#define WPK(i, hw) pack_bf16(WIN(i, hw), WIN((i) + 1, hw))
      const int tp = 2 * bp;
      const uint32_t a3 = cb + A_W3 + (tp + 64) * 16 + 8, a5 = cb + A_W5 + (tp + 64) * 16;
      if (!neg) sts64(a3, WPK(0, 1), WPK(2, 1));
      if (!neg) sts128(a3 + 8, WPK(4, 1), WPK(6, 1), WPK(8, 1), WPK(10, 1));
      sts64(a3 + 24, WPK(12, 1), WPK(14, 1));
      sts128(a5, WPK(0, 2), WPK(2, 2), WPK(4, 2), WPK(6, 2));
      sts128(a5 + 16, WPK(8, 2), WPK(10, 2), WPK(12, 2), WPK(14, 2));
      if (bp < 64) {
        if (!neg) sts128(cb + A_W7 + 1024 + bp * 16, WPK(0, 3), WPK(2, 3), WPK(4, 3), WPK(6, 3));
        if (bp < 63) {
          sts128(cb + A_W7 + (bp + 1) * 16, WPK(8, 3), WPK(10, 3), WPK(12, 3), WPK(14, 3));
          sts128(cb + A_W9 + (bp + 1) * 16, WPK(0, 4), WPK(2, 4), WPK(4, 4), WPK(6, 4));
          sts128(cb + A_W9 + 1024 + (bp + 1) * 16, WPK(8, 4), WPK(10, 4), WPK(12, 4), WPK(14, 4));
        }
        if (!neg) {
#define VPK(i) pack_bf16(P[(i) + 2] - P[i], P[(i) + 3] - P[(i) + 1])
          sts128(cb + A_V + bp * 32, VPK(0), VPK(2), VPK(4), VPK(6));
          sts128(cb + A_V + bp * 32 + 16, VPK(8), VPK(10), VPK(12), VPK(14));
        }
      }
    }
  }
  asm volatile("fence.proxy.async.shared::cta;" ::: "memory");
  bar_sync(1 + wg, 128);
  if (tid == 320) TR(0, 5);

  {
    const uint32_t cbu = __shfl_sync(~0u, cb, 0);
    const uint32_t blo_k = ((cbu & 0x3FFFF) >> 4) | (41u << 16);
    const uint32_t blo_n = ((cbu & 0x3FFFF) >> 4) | (8u << 16);
    const uint32_t tb = cb + (16 * wq + g - 2 * t) * 4;
    float y1[16], y2[12], y3[8];
    const uint32_t dk16 = __ldg(dskip + ch);
    uint32_t qa[32], qb[32];
    const uint32_t t1 = tb + A_R1 + (62 - 48) * 4;
    load_quads<4>(qa, tb + A_R3A + 17 * 4); load_quads<4>(qa + 16, tb + A_R3B + 16 * 4);
    wg_fence();
    s3_steps<0, 4, A_W9, 1>(y3, qa, blo_n); s3_steps<0, 4, A_W7, 0>(y3, qa + 16, blo_n);
    wg_commit();
    load_quads<8>(qb, tb + A_R2A + 16 * 4);
    wg_fence(); s2_steps<0, 8, A_W5, 1>(y2, qb, blo_n); wg_commit();
    wg_wait<1>(); load_quads<8>(qa, tb + A_R2B + 16 * 4);
    wg_fence(); s2_steps<0, 8, A_W3, 0>(y2, qa, blo_n); wg_commit();
    wg_wait<1>(); load_quads<8>(qb, t1);
    wg_fence(); f1_steps<0, 8>(y1, qb, blo_k); wg_commit();
    wg_wait<1>(); load_quads<8>(qa, t1 + 8 * 64);
    wg_fence(); f1_steps<8, 8>(y1, qa, blo_k); wg_commit();
    reg_fence(y2); reg_fence(y3);
    if (tid == 320) TR(0, 18);
    {
      const float k1024 = __uint_as_float(lds32(cb + A_K1024));
#pragma unroll
      for (int i = 0; i < 2; i++)
#pragma unroll
        for (int hf = 0; hf < 2; hf++) {
          const int idx = 16 * (16 * wq + g + 8 * hf) + 8 * i + 2 * t;
          const uint32_t vv = lds32(cb + A_V + idx * 2);
          sts64(cb + A_Y3 + (idx + 4 * (idx >> 6)) * 4, __float_as_uint(fmaf(k1024, bf_lo(vv), y3[4 * i + 2 * hf])),
                __float_as_uint(fmaf(k1024, bf_hi(vv), y3[4 * i + 2 * hf + 1])));
        }
#pragma unroll
      for (int i = 0; i < 3; i++)
#pragma unroll
        for (int hf = 0; hf < 2; hf++) {
          const int idx = 512 * i + 8 * (16 * wq + g + 8 * hf) + 2 * t;
          sts64(cb + A_Y2 + (idx + 4 * (idx >> 6)) * 4, __float_as_uint(y2[4 * i + 2 * hf]), __float_as_uint(y2[4 * i + 2 * hf + 1]));
        }
    }
    wg_wait<1>(); load_quads<8>(qb, t1 + 16 * 64);
    wg_fence(); f1_steps<16, 8>(y1, qb, blo_k); wg_commit();
    wg_wait<1>(); load_quads<8>(qa, t1 + 24 * 64);
    wg_fence(); f1_steps<24, 8>(y1, qa, blo_k); wg_commit();
    wg_wait<1>(); load_quads<5>(qb, t1 + 32 * 64);
    wg_fence(); f1_steps<32, 5>(y1, qb, blo_k); wg_commit();
    bar_sync(1 + wg, 128);
    float ex[12];
#pragma unroll
    for (int i = 1; i < 4; i++)
#pragma unroll
      for (int k = 0; k < 4; k++) {
        const int aa = 8 * i + 2 * t + (k & 1), b = 16 * wq + g + 8 * (k >> 1);
        float e = __uint_as_float(lds32(cb + A_Y2 + ((aa - 8) * 68 + b) * 4));
        if (i >= 2) e += __uint_as_float(lds32(cb + A_Y3 + ((aa - 16) * 68 + b) * 4));
        ex[4 * (i - 1) + k] = e;
      }
    {
      const uint32_t dk = dk16 * 0x10001u;
#pragma unroll
      for (int i = 0; i < 4; i++) {
        const uint4 r = lds128(cb + A_REC + bk * 64 + ((i ^ (bk >> 1)) & 3) * 16);
        ud[i] = hmul2_bf(r.x, dk); ud[4 + i] = hmul2_bf(r.y, dk); xt[i] = r.z; xt[4 + i] = r.w;
      }
    }
    wg_wait<0>();
    reg_fence(y1);
    if (tid == 320) TR(0, 6);
#pragma unroll
    for (int i = 0; i < 12; i++) y1[4 + i] += ex[i];
#pragma unroll
    for (int i = 0; i < 2; i++) {
      const int mi = lane >> 3, aa = 8 * (2 * i + (mi >> 1)) + (lane & 7);
      asm volatile("stmatrix.sync.aligned.m8n8.x4.trans.shared.b16 [%0], {%1,%2,%3,%4};"
                   ::"r"(cb + A_YB + aa * 128 + (((2 * wq + (mi & 1)) ^ (lane & 7)) << 4)),
                     "r"(pack_bf16(y1[8 * i], y1[8 * i + 1])), "r"(pack_bf16(y1[8 * i + 2], y1[8 * i + 3])),
                     "r"(pack_bf16(y1[8 * i + 4], y1[8 * i + 5])), "r"(pack_bf16(y1[8 * i + 6], y1[8 * i + 7])) : "memory");
    }
  }
  bar_sync(1 + wg, 128);
#pragma unroll
  for (int c = 0; c < 2; c++) {
    const int tau = 2 * bk + c, r = ch & 7;
    const uint4 y = lds128(cb + A_YB + (tau >> 3) * 128 + (((tau ^ (tau >> 3)) & 7) << 4));
    g_himg[(size_t)(tau >> 4) * 7168 + (ch >> 3) * 128 + ((tau >> 3) & 1) * 64 + r * 8 + ((tau & 7) ^ r)] =
        make_uint4(hadd2_bf(xt[4 * c], hadd2_bf(y.x, ud[4 * c])), hadd2_bf(xt[4 * c + 1], hadd2_bf(y.y, ud[4 * c + 1])),
                   hadd2_bf(xt[4 * c + 2], hadd2_bf(y.z, ud[4 * c + 2])), hadd2_bf(xt[4 * c + 3], hadd2_bf(y.w, ud[4 * c + 3])));
  }
  if (tid == 320) TR(0, 7);
}

constexpr int B_SA = 0, B_RING = 114688, B_SLOT = 14848, B_NSLOT = 7;
constexpr int B_CS = B_RING + B_NSLOT * B_SLOT;
constexpr int B_STAT = B_CS + 7168;
constexpr int B_BAR = B_STAT + 512;
constexpr int B_SMEM = B_BAR + 512;

__device__ __forceinline__ uint32_t mapa(uint32_t a, uint32_t r) { uint32_t o; asm("mapa.shared::cluster.u32 %0, %1, %2;" : "=r"(o) : "r"(a), "r"(r)); return o; }

template <int Q, int ST>
__device__ __forceinline__ void g1_stage(float (&acc)[116], uint32_t alo, uint32_t blo, uint32_t bar_full, uint32_t bar_h) {
  constexpr int s = Q * 14 + ST, sl = s % B_NSLOT;
  if (Q == 0) mbar_wait(bar_h + 8 * ST, 0);
  mbar_wait(bar_full + 8 * sl, (s / B_NSLOT) & 1);
  wg_fence();
  if (Q == 0) {
    wgmma_ss232<(2 * ST) * 256, 0x40000080u, (sl * B_SLOT) / 16, 32, ST != 0>(acc, alo, blo);
    wgmma_ss232<(2 * ST + 1) * 256, 0x40000080u, (sl * B_SLOT + 256) / 16, 32, 1>(acc, alo, blo);
  } else {
    wgmma_ss224<(2 * ST) * 256, 0x40000080u, (sl * B_SLOT) / 16, 32, ST != 0>(*(float(*)[112])acc, alo, blo);
    wgmma_ss224<(2 * ST + 1) * 256, 0x40000080u, (sl * B_SLOT + 256) / 16, 32, 1>(*(float(*)[112])acc, alo, blo);
  }
}

__global__ void __cluster_dims__(2, 1, 1) __launch_bounds__(384, 1) k_ffn(__nv_bfloat16* __restrict__ out) {
  extern __shared__ __align__(1024) unsigned char sm[];
  const uint32_t sb = s2u(sm);
  const int tid = threadIdx.x, wg = tid >> 7, warp = tid >> 5, lane = tid & 31;
  const int rank = blockIdx.x & 1, rt = blockIdx.x & 15, j = blockIdx.x >> 4;
  const uint32_t bar_full = sb + B_BAR, bar_empty = bar_full + 64, bar_h = bar_full + 128, bar_cs = bar_full + 240, bar_stat = bar_full + 248,
                 bar_adead = bar_full + 256, bar_in = bar_full + 264;
  if (tid == 0) {
    TR(1, 0);
    for (int i = 0; i < B_NSLOT; i++) { mbar_init(bar_full + 8 * i, 1); mbar_init(bar_empty + 8 * i, 4); }
    for (int i = 0; i < 14; i++) mbar_init(bar_h + 8 * i, 1);
    mbar_init(bar_cs, 1);
    mbar_init(bar_stat, 32);
    mbar_init(bar_adead, 2);
    for (int i = 0; i < 14; i++) mbar_init(bar_in + 8 * i, 1);
    asm volatile("fence.mbarrier_init.release.cluster;" ::: "memory");
  }
  if (tid >= 128 && tid < 128 + 224) {
    const int i = tid - 128;
    *(uint4*)(sm + B_RING + (i >> 5) * B_SLOT + 14336 + (i & 31) * 16) = make_uint4(0x3F803F80u, 0x3F803F80u, 0x3F803F80u, 0x3F803F80u);
    asm volatile("fence.proxy.async.shared::cta;" ::: "memory");
  }
  __syncthreads();
  asm volatile("barrier.cluster.arrive.release.aligned;" ::: "memory");

  if (wg == 2) {
    asm volatile("setmaxnreg.dec.sync.aligned.u32 88;");
    asm volatile("barrier.cluster.wait.acquire.aligned;" ::: "memory");
    asm volatile("griddepcontrol.wait;" ::: "memory");
    if (warp == 8) {
      if (lane == 0) {
        const char* wsrc = (const char*)g_wimg + (size_t)j * 602112;
        TR(1, 1);
        int slot = 0, ph = 0;
        for (int s = 0; s < 44; s++) {
          if (s >= B_NSLOT) mbar_wait(bar_empty + 8 * slot, ph ^ 1);
          uint32_t dst = sb + B_RING + slot * B_SLOT, fb = bar_full + 8 * slot;
          if (s < 28) {
            mbar_expect(fb, 14336);
            bulk_ld_mc(dst + rank * 7168, wsrc + s * 14336 + rank * 7168, 7168, fb);
          } else {
            const int c = (j + 1 + ((s - 28) >> 1)) & 7;
            mbar_expect(fb, 12544);
            bulk_ld_mc(dst + rank * 6272, wsrc + 401408 + (c * 2 + (s & 1)) * 12544 + rank * 6272, 6272, fb);
          }
          if (++slot == B_NSLOT) { slot = 0; ph ^= 1; }
        }
      }
    } else if (warp == 9) {
      if (lane == 0) {
        const char* hsrc = (const char*)g_himg + (size_t)rt * 114688;
        for (int i = 0; i < 14; i++) {
          mbar_expect(bar_h + 8 * i, 8192);
          bulk_ld(sb + B_SA + i * 8192, hsrc + i * 8192, 8192, bar_h + 8 * i);
        }
        mbar_expect(bar_cs, 7168);
        bulk_ld(sb + B_CS, g_cimg + j * 448, 7168, bar_cs);
      }
    } else {
      const int t64 = tid - 320;
      const uint32_t ep = __ldcg(&g_epochB), tag = ep & 1u;
      if (blockIdx.x == 0 && t64 == 0) g_epochA = ep;
      {
        const int r = (lane >> 1) & 7, c = (j & 3) * 2 + (lane & 1);
        const unsigned char* src = sm + B_SA + (t64 >> 4) * 2048 + (j >> 2) * 1024 + r * 128 + ((c ^ r) << 4);
        float a[16];
#pragma unroll
        for (int k = 0; k < 16; k++) a[k] = 0.f;
#pragma unroll 1
        for (int i = 0; i < 14; i++) {
          mbar_wait(bar_h + 8 * i, 0);
          uint4 v = *(const uint4*)(src + i * 8192);
          float e[8] = {bf_lo(v.x), bf_hi(v.x), bf_lo(v.y), bf_hi(v.y), bf_lo(v.z), bf_hi(v.z), bf_lo(v.w), bf_hi(v.w)};
#pragma unroll
          for (int k = 0; k < 8; k++) { a[2 * k] += e[k]; a[2 * k + 1] = fmaf(e[k], e[k], a[2 * k + 1]); }
          __nanosleep(160);
        }
#pragma unroll
        for (int rd = 0; rd < 4; rd++) {
          const int n = 8 >> rd;
          const bool up = lane & (2 * n);
#pragma unroll
          for (int k = 0; k < 8; k++) {
            if (k < n) {
              float keep = up ? a[k + n] : a[k], give = up ? a[k] : a[k + n];
              a[k] = keep + __shfl_xor_sync(~0u, give, 2 * n);
            }
          }
        }
        float* red = (float*)(sm + B_STAT);
        red[(warp & 1) * 32 + (lane & 1) * 16 + (lane >> 1)] = a[0];
        asm volatile("bar.sync 1, 64;" ::: "memory");
        if (t64 < 16) {
          float mean = (red[2 * t64] + red[32 + 2 * t64]) * (1.f / DM);
          float var = fmaxf(fmaf(-mean, mean, (red[2 * t64 + 1] + red[33 + 2 * t64]) * (1.f / DM)), 0.f);
          float rs = __frcp_rn(rbf(__fsqrt_rn(rbf(rbf(var) + 1e-5f))));
          asm volatile("st.relaxed.gpu.global.u32 [%0], %1;"
                       ::"l"(g_stat2 + rt * 128 + j * 16 + t64), "r"((__float_as_uint(rs * rs) & ~1u) | tag) : "memory");
        }
        if (t64 == 0) TR(1, 2);
      }
      __syncwarp();
      if (warp == 10) {
        mbar_wait(bar_adead, 0);
        uint32_t w[4];
        int it = 0;
        do { ld128((const uint4*)(g_stat2 + rt * 128) + lane, w); } while ((((w[0] ^ tag) | (w[1] ^ tag) | (w[2] ^ tag) | (w[3] ^ tag)) & 1u) && ++it < 200000);
        *(uint4*)(sm + B_STAT + lane * 16) = make_uint4(w[0], w[1], w[2], w[3]);
        mbar_arrive(bar_stat);
      }
      if (t64 == 0) TR(1, 18);
      if (warp == 11) {
        mbar_wait(bar_adead, 0);
        bool todo = lane < 14;
        int it = 0;
        while (__any_sync(~0u, todo) && ++it < 200000) {
          if (todo) {
            uint32_t w[4];
            ld128(g_flag + (rt * 8 + j) * 16 + lane, w);
            if (w[0] == ep && w[1] == ep && w[2] == ep && w[3] == ep) {
              const uint32_t b = bar_in + 8 * ((lane & 1) * 7 + (lane >> 1));
              asm volatile("fence.proxy.async.global;" ::: "memory");
              mbar_expect(b, 7168);
              bulk_ld(sb + B_SA + lane * 7168, g_part + (size_t)((rt * 8 + j) * 7) * 896 + lane * 448, 7168, b);
              todo = false;
              if (!(lane & 1)) TR(1, 24 + (lane >> 1));
            }
          }
        }
      }
    }
  } else {
    asm volatile("setmaxnreg.inc.sync.aligned.u32 208;");
    const int g = lane >> 2, t = lane & 3, wq = warp & 3, t128 = tid & 127;
    uint32_t hh[56], hres[16];
    asm volatile("barrier.cluster.wait.acquire.aligned;" ::: "memory");
    asm volatile("griddepcontrol.wait;" ::: "memory");
    const uint32_t ep = __ldcg(&g_epochB), tag = (ep & 1u) << 16;
    const uint32_t rel_bar = mapa(bar_empty, t128 & 1);
    auto release = [&](int sl) { if (t128 < 2) asm volatile("mbarrier.arrive.shared::cluster.b64 _, [%0];" ::"r"(rel_bar + 8 * sl) : "memory"); };
    const uint32_t alo = __shfl_sync(~0u, ((sb + B_SA + wg * 1024) & 0x3FFFF) >> 4, 0);
    const uint32_t blo = (((sb + B_RING) & 0x3FFFF) >> 4) | (8u << 16);
    const uint32_t clo = ((sb + B_CS) & 0x3FFFF) >> 4;
    uint32_t nm0, nm1;
    if (wg == 1) asm volatile("bar.sync 3, 256;" ::: "memory");
#define G1S(Q, ST) do { g1_stage<Q, ST>(acc, alo, blo, bar_full, bar_h); wg_commit(); \
      if (ST > 0) { wg_wait<1>(); release((Q * 14 + ST - 1) % B_NSLOT); } } while (0)
#define G1HH(Q) do { \
      _Pragma("unroll") \
      for (int i = 0; i < 28; i++) hh[28 * Q + i] = pack_bf16(acc[2 * i] * acc[56 + 2 * i], acc[2 * i + 1] * acc[57 + 2 * i]); \
    } while (0)
    {
      float acc[116];
      G1S(0, 0);
      if (tid == 0) TR(1, 3);
      G1S(0, 1);
      if (wg == 0) asm volatile("bar.arrive 3, 256;" ::: "memory");
      G1S(0, 2); G1S(0, 3); G1S(0, 4); G1S(0, 5); G1S(0, 6); G1S(0, 7); G1S(0, 8); G1S(0, 9); G1S(0, 10); G1S(0, 11); G1S(0, 12);
      G1S(0, 13);
      if (tid == 0) TR(1, 4);
      mbar_wait(bar_cs, 0);
      wg_wait<0>(); reg_fence(acc); release(13 % B_NSLOT);
      {
        const uint32_t msk = t == 0 ? 0xFFFFFFFFu : t == 1 ? 0xFFFFu : 0u;
        const float a = acc[112] * (-1.f / DM), b = acc[114] * (-1.f / DM);
        nm0 = pack_bf16(a, a) & msk; nm1 = pack_bf16(b, b) & msk;
      }
      wg_fence();
      wgmma_rs224<0, 8, 1>(*(float(*)[112])acc, nm0, nm1, 0u, 0u, clo);
      wg_commit(); wg_wait<0>(); reg_fence(acc);
      G1HH(0);
      if (tid == 0) TR(1, 5);
      G1S(1, 0); G1S(1, 1); G1S(1, 2); G1S(1, 3); G1S(1, 4); G1S(1, 5); G1S(1, 6); G1S(1, 7); G1S(1, 8); G1S(1, 9); G1S(1, 10); G1S(1, 11);
#pragma unroll
      for (int i = 0; i < 4; i++) {
        int qq = lane >> 3, r = lane & 7, kg = 7 * j + 2 * i + (qq >> 1), c = 2 * wq + (qq & 1);
        if (kg > 55) kg = 55;
        uint32_t addr = sb + B_SA + kg * 2048 + wg * 1024 + r * 128 + ((c ^ r) << 4);
        asm volatile("ldmatrix.sync.aligned.m8n8.x4.trans.shared.b16 {%0,%1,%2,%3}, [%4];"
                     : "=r"(hres[4 * i]), "=r"(hres[4 * i + 1]), "=r"(hres[4 * i + 2]), "=r"(hres[4 * i + 3]) : "r"(addr) : "memory");
      }
      G1S(1, 12);
      g1_stage<1, 13>(acc, alo, blo, bar_full, bar_h);
      wgmma_rs224<224, 8, 1>(*(float(*)[112])acc, nm0, nm1, 0u, 0u, clo);
      wg_commit(); wg_wait<1>(); release(26 % B_NSLOT);
      wg_wait<0>(); reg_fence(acc); release(27 % B_NSLOT);
      G1HH(1);
      if (t128 == 0) mbar_arrive(bar_adead);
      if (tid == 0) TR(1, 6);
    }
    float accA[28], accB[28], sum[28];
    int nxt = 0;
#pragma unroll
    for (int i = 0; i < 28; i++) sum[i] = 0.f;
#define ISSUE(acc, I, a, FIRST) do { \
      constexpr int s_ = 28 + (I), sl_ = s_ % B_NSLOT; \
      mbar_wait(bar_full + 8 * sl_, (s_ / B_NSLOT) & 1); \
      wg_fence(); \
      wgmma_rs56<(sl_ * B_SLOT + 0 * 256) / 16, 112, !(FIRST)>(acc, (a)[0], (a)[1], (a)[2], (a)[3], blo); \
      wgmma_rs56<(sl_ * B_SLOT + 1 * 256) / 16, 112, 1>(acc, (a)[4], (a)[5], (a)[6], (a)[7], blo); \
      wgmma_rs56<(sl_ * B_SLOT + 2 * 256) / 16, 112, 1>(acc, (a)[8], (a)[9], (a)[10], (a)[11], blo); \
      wgmma_rs56<(sl_ * B_SLOT + 3 * 256) / 16, 112, 1>(acc, (a)[12], (a)[13], (a)[14], (a)[15], blo); \
      wgmma_rs56<(sl_ * B_SLOT + 4 * 256) / 16, 112, 1>(acc, (a)[16], (a)[17], (a)[18], (a)[19], blo); \
      wgmma_rs56<(sl_ * B_SLOT + 5 * 256) / 16, 112, 1>(acc, (a)[20], (a)[21], (a)[22], (a)[23], blo); \
      wgmma_rs56<(sl_ * B_SLOT + 6 * 256) / 16, 112, 1>(acc, (a)[24], (a)[25], (a)[26], (a)[27], blo); \
      wg_commit(); } while (0)
    auto rel = [&](int i) { if (i < 9) release((28 + i) % B_NSLOT); };
    auto tg = [&](uint32_t v) { return (v & 0xFFFEFFFFu) | tag; };
    auto send_lo = [&](float (&acc)[28], int cc) {
      reg_fence(acc);
      uint4* dst = g_part + (size_t)((rt * 8 + ((j + 1 + cc) & 7)) * 7 + cc) * 896 + wg * 448 + t128;
#pragma unroll
      for (int q = 0; q < 2; q++)
        st128(dst + q * 128, pack_bf16(acc[8 * q], acc[8 * q + 1]), pack_bf16(acc[8 * q + 2], acc[8 * q + 3]),
              pack_bf16(acc[8 * q + 4], acc[8 * q + 5]), tg(pack_bf16(acc[8 * q + 6], acc[8 * q + 7])));
    };
    auto send_hi = [&](float (&acc)[28], int cc) {
      uint4* dst = g_part + (size_t)((rt * 8 + ((j + 1 + cc) & 7)) * 7 + cc) * 896 + wg * 448;
      st128(dst + 256 + t128, pack_bf16(acc[16], acc[17]), pack_bf16(acc[18], acc[19]), pack_bf16(acc[20], acc[21]), tg(pack_bf16(acc[22], acc[23])));
      asm volatile("{\n.reg .b64 v;\nmov.b64 v, {%1, %2};\nst.relaxed.gpu.global.b64 [%0], v;\n}"
                   ::"l"((uint2*)(dst + 384) + t128), "r"(pack_bf16(acc[24], acc[25])), "r"(tg(pack_bf16(acc[26], acc[27]))) : "memory");
      if (lane == 0)
        asm volatile("st.relaxed.gpu.global.u32 [%0], %1;" ::"l"((uint32_t*)(g_flag + (rt * 8 + ((j + 1 + cc) & 7)) * 16 + cc * 2 + wg) + wq), "r"(ep) : "memory");
    };
    auto accum = [&]() {
      const unsigned char* src = sm + B_SA + nxt * 14336 + wg * 7168;
      uint4 a = *(const uint4*)(src + t128 * 16), b = *(const uint4*)(src + 2048 + t128 * 16), c = *(const uint4*)(src + 4096 + t128 * 16);
      uint2 d = *(const uint2*)(src + 6144 + t128 * 8);
      uint32_t in[14] = {a.x, a.y, a.z, a.w, b.x, b.y, b.z, b.w, c.x, c.y, c.z, c.w, d.x, d.y};
      int it = 0;
      while ((((in[3] ^ tag) | (in[7] ^ tag) | (in[11] ^ tag) | (in[13] ^ tag)) & 0x10000u) && ++it < 200000) {
        const uint4* gs = g_part + (size_t)((rt * 8 + j) * 7 + nxt) * 896 + wg * 448;
#pragma unroll
        for (int i = 0; i < 3; i++) ld128(gs + i * 128 + t128, in + 4 * i);
        asm volatile("{\n.reg .b64 v;\nld.relaxed.gpu.global.b64 v, [%2];\nmov.b64 {%0, %1}, v;\n}"
                     : "=r"(in[12]), "=r"(in[13]) : "l"((const uint2*)(gs + 384) + t128) : "memory");
      }
#pragma unroll
      for (int i = 0; i < 14; i++) { sum[2 * i] += bf_lo(in[i]); sum[2 * i + 1] += bf_hi(in[i]); }
      nxt++;
    };
    auto try_accum = [&]() {
      uint32_t ok;
      asm volatile("{\n.reg .pred p;\nmbarrier.test_wait.parity.shared::cta.b64 p, [%1], 0;\nselp.u32 %0, 1, 0, p;\n}"
                   : "=r"(ok) : "r"(bar_in + 8 * (wg * 7 + nxt)) : "memory");
      if (__all_sync(~0u, ok)) accum();
    };
#define CHUNK(cur, prev, CC, EXTRA) do { \
      ISSUE(cur, 2 * (CC), hh, true); wg_wait<1>(); rel(2 * (CC) - 1); send_lo(prev, (CC) - 1); \
      ISSUE(cur, 2 * (CC) + 1, hh + 28, false); send_hi(prev, (CC) - 1); EXTRA; wg_wait<1>(); rel(2 * (CC)); } while (0)
    ISSUE(accA, 0, hh, true);
    ISSUE(accA, 1, hh + 28, false); wg_wait<1>(); rel(0);
    CHUNK(accB, accA, 1, );
    if (tid == 0) TR(1, 11);
    CHUNK(accA, accB, 2, );
    if (tid == 0) TR(1, 12);
    CHUNK(accB, accA, 3, try_accum());
    if (tid == 0) TR(1, 13);
    CHUNK(accA, accB, 4, try_accum());
    if (tid == 0) TR(1, 14);
    CHUNK(accB, accA, 5, try_accum());
    if (tid == 0) TR(1, 16);
    CHUNK(accA, accB, 6, try_accum());
    if (tid == 0) TR(1, 17);
    CHUNK(accB, accA, 7, try_accum());
    if (tid == 0) TR(1, 7);
#pragma unroll 1
    while (nxt < 7) { mbar_wait(bar_in + 8 * (wg * 7 + nxt), 0); accum(); }
    wg_wait<0>();
    reg_fence(accB);
    if (tid == 0) TR(1, 9);
    mbar_wait(bar_stat, 0);
    const float r20 = *(const float*)(sm + B_STAT + (wg * 64 + wq * 16 + g) * 4), r21 = *(const float*)(sm + B_STAT + (wg * 64 + wq * 16 + g + 8) * 4);
    const int row = rt * 128 + wg * 64 + wq * 16 + g;
    uint32_t* o0 = (uint32_t*)(out + (size_t)row * DM + 56 * j + 2 * t);
    uint32_t* o1 = o0 + 8 * DM / 2;
#pragma unroll
    for (int i = 0; i < 7; i++) {
      o0[4 * i] = hadd2_bf(hres[2 * i], pack_bf16((sum[4 * i] + accB[4 * i]) * r20, (sum[4 * i + 1] + accB[4 * i + 1]) * r20));
      o1[4 * i] = hadd2_bf(hres[2 * i + 1], pack_bf16((sum[4 * i + 2] + accB[4 * i + 2]) * r21, (sum[4 * i + 3] + accB[4 * i + 3]) * r21));
    }
    if (tid == 0) TR(1, 10);
    if (tid == 128) TR(1, 15);

  }
}

extern "C" void kernel_launch(void* const* d_in, const int* in_sizes, int n_in, void* d_out, int out_size) {
  const __nv_bfloat16* x = (const __nv_bfloat16*)d_in[0];
  const __nv_bfloat16 *are = (const __nv_bfloat16*)d_in[1], *aim = (const __nv_bfloat16*)d_in[2], *bre = (const __nv_bfloat16*)d_in[3],
                      *bim = (const __nv_bfloat16*)d_in[4], *cre = (const __nv_bfloat16*)d_in[5], *cim = (const __nv_bfloat16*)d_in[6],
                      *logdt = (const __nv_bfloat16*)d_in[7], *dskip = (const __nv_bfloat16*)d_in[8];
  const __nv_bfloat16 *wg = (const __nv_bfloat16*)d_in[10], *wu = (const __nv_bfloat16*)d_in[11], *wd = (const __nv_bfloat16*)d_in[12];

  static bool init = false;
  if (!init) {
    init = true;
    cudaFuncSetAttribute(k_ffn, cudaFuncAttributeMaxDynamicSharedMemorySize, B_SMEM);
    cudaFuncSetAttribute(k_front, cudaFuncAttributeMaxDynamicSharedMemorySize, A_SMEM);
  }
  cudaStream_t st = cudaStreamPerThread;
  k_front<<<128, 512, A_SMEM, st>>>(x, (const uint32_t*)are, (const uint32_t*)aim, (const uint32_t*)bre, (const uint32_t*)bim,
                                    (const uint32_t*)cre, (const uint32_t*)cim, (const unsigned short*)logdt, (const unsigned short*)dskip, (const uint4*)wg, (const uint4*)wu, (const uint4*)wd);
  cudaLaunchConfig_t cfg = {};
  cfg.gridDim = dim3(128); cfg.blockDim = dim3(384); cfg.dynamicSmemBytes = B_SMEM; cfg.stream = st;
  cudaLaunchAttribute at[1];
  at[0].id = cudaLaunchAttributeProgrammaticStreamSerialization; at[0].val.programmaticStreamSerializationAllowed = 1;
  cfg.attrs = at; cfg.numAttrs = 1;
  cudaLaunchKernelEx(&cfg, k_ffn, (__nv_bfloat16*)d_out);
}
```

```cpp
#include <cuda_runtime.h>
#include <cuda_bf16.h>
#include <stdint.h>

constexpr int LSEQ = 2048, DM = 448;

__device__ uint4    g_himg[16 * 114688 / 16];
__device__ uint4    g_cimg[8 * 2 * 224];
__device__ uint32_t g_stat2[LSEQ];
__device__ uint4    g_part[128 * 7 * 896];
__device__ uint4    g_wimg[8 * 602112 / 16];
__device__ uint4    g_ux[DM * 128 * 4];
__device__ unsigned g_cnt1, g_cnt2, g_cnt3;
__device__ uint32_t g_flag[128 * 64];

#define TR(k, i) do {} while (0)
__device__ __forceinline__ uint32_t s2u(const void* p) { return (uint32_t)__cvta_generic_to_shared(p); }
__device__ __forceinline__ void mbar_init(uint32_t b, int c) { asm volatile("mbarrier.init.shared::cta.b64 [%0], %1;" ::"r"(b), "r"(c)); }
__device__ __forceinline__ void mbar_expect(uint32_t b, int bytes) { asm volatile("mbarrier.arrive.expect_tx.shared::cta.b64 _, [%0], %1;" ::"r"(b), "r"(bytes) : "memory"); }
__device__ __forceinline__ void mbar_arrive(uint32_t b) { asm volatile("mbarrier.arrive.shared::cta.b64 _, [%0];" ::"r"(b) : "memory"); }
__device__ __forceinline__ void mbar_wait(uint32_t b, int ph) {
  asm volatile("{\n.reg .pred p;\n.reg .b32 n;\nmov.b32 n, 0;\nLW:\nmbarrier.try_wait.parity.shared::cta.b64 p, [%0], %1;\n@p bra LD;\n"
               "add.u32 n, n, 1;\nsetp.lt.u32 p, n, 4000000;\n@p bra LW;\ntrap;\nLD:\n}" ::"r"(b), "r"(ph) : "memory");
}
__device__ __forceinline__ void wg_fence() { asm volatile("wgmma.fence.sync.aligned;" ::: "memory"); }
__device__ __forceinline__ void wg_commit() { asm volatile("wgmma.commit_group.sync.aligned;" ::: "memory"); }
template <int N> __device__ __forceinline__ void wg_wait() { asm volatile("wgmma.wait_group.sync.aligned %0;" ::"n"(N) : "memory"); }
template <int N> __device__ __forceinline__ void reg_fence(float (&a)[N]) {
#pragma unroll
  for (int i = 0; i < N; i++) asm volatile("" : "+f"(a[i])::"memory");
}
__device__ __forceinline__ uint32_t pack_bf16(float lo, float hi) {
  uint32_t r; asm("cvt.rn.bf16x2.f32 %0, %1, %2;" : "=r"(r) : "f"(hi), "f"(lo)); return r;
}
__device__ __forceinline__ float bf_lo(uint32_t v) { return __uint_as_float(v << 16); }
__device__ __forceinline__ float bf_hi(uint32_t v) { return __uint_as_float(v & 0xFFFF0000u); }
__device__ __forceinline__ float rbf(float x) { return __bfloat162float(__float2bfloat16_rn(x)); }
__device__ __forceinline__ uint32_t hmul2_bf(uint32_t a, uint32_t b) { uint32_t r; asm("mul.rn.bf16x2 %0, %1, %2;" : "=r"(r) : "r"(a), "r"(b)); return r; }
__device__ __forceinline__ uint32_t hadd2_bf(uint32_t a, uint32_t b) { uint32_t r; asm("add.rn.bf16x2 %0, %1, %2;" : "=r"(r) : "r"(a), "r"(b)); return r; }
__device__ __forceinline__ void bulk_ld(uint32_t dst, const void* src, int bytes, uint32_t bar) {
  asm volatile("cp.async.bulk.shared::cluster.global.mbarrier::complete_tx::bytes [%0], [%1], %2, [%3];"
               ::"r"(dst), "l"(src), "r"(bytes), "r"(bar) : "memory");
}

__device__ __forceinline__ void bulk_ld_mc(uint32_t dst, const void* src, int bytes, uint32_t bar) {
  asm volatile("cp.async.bulk.shared::cluster.global.mbarrier::complete_tx::bytes.multicast::cluster [%0], [%1], %2, [%3], %4;"
               ::"r"(dst), "l"(src), "r"(bytes), "r"(bar), "h"((uint16_t)3) : "memory");
}
template <int AOFF, uint32_t AHI, int BOFF, uint32_t BHI, int ACC>
__device__ __forceinline__ void wgmma_ss224(float (&d)[112], uint32_t alo, uint32_t blo) {
  asm volatile("{\n.reg .pred p;\n.reg .b32 la, lb;\n.reg .b64 ad, bd;\nsetp.ne.b32 p, %118, 0;\n"
    "add.u32 la, %112, %114;\nmov.b64 ad, {la, %115};\nadd.u32 lb, %113, %116;\nmov.b64 bd, {lb, %117};\n"
    "wgmma.mma_async.sync.aligned.m64n224k16.f32.bf16.bf16 {%0,%1,%2,%3,%4,%5,%6,%7,%8,%9,%10,%11,%12,%13,%14,%15,%16,%17,%18,%19,%20,%21,%22,%23,%24,%25,%26,%27,%28,%29,%30,%31,%32,%33,%34,%35,%36,%37,%38,%39,%40,%41,%42,%43,%44,%45,%46,%47,%48,%49,%50,%51,%52,%53,%54,%55,%56,%57,%58,%59,%60,%61,%62,%63,%64,%65,%66,%67,%68,%69,%70,%71,%72,%73,%74,%75,%76,%77,%78,%79,%80,%81,%82,%83,%84,%85,%86,%87,%88,%89,%90,%91,%92,%93,%94,%95,%96,%97,%98,%99,%100,%101,%102,%103,%104,%105,%106,%107,%108,%109,%110,%111}, ad, bd, p, 1, 1, 1, 1;\n}\n"
    : "+f"(d[0]),"+f"(d[1]),"+f"(d[2]),"+f"(d[3]),"+f"(d[4]),"+f"(d[5]),"+f"(d[6]),"+f"(d[7]),"+f"(d[8]),"+f"(d[9]),"+f"(d[10]),"+f"(d[11]),"+f"(d[12]),"+f"(d[13]),"+f"(d[14]),"+f"(d[15]),"+f"(d[16]),"+f"(d[17]),"+f"(d[18]),"+f"(d[19]),"+f"(d[20]),"+f"(d[21]),"+f"(d[22]),"+f"(d[23]),"+f"(d[24]),"+f"(d[25]),"+f"(d[26]),"+f"(d[27]),"+f"(d[28]),"+f"(d[29]),"+f"(d[30]),"+f"(d[31]),"+f"(d[32]),"+f"(d[33]),"+f"(d[34]),"+f"(d[35]),"+f"(d[36]),"+f"(d[37]),"+f"(d[38]),"+f"(d[39]),"+f"(d[40]),"+f"(d[41]),"+f"(d[42]),"+f"(d[43]),"+f"(d[44]),"+f"(d[45]),"+f"(d[46]),"+f"(d[47]),"+f"(d[48]),"+f"(d[49]),"+f"(d[50]),"+f"(d[51]),"+f"(d[52]),"+f"(d[53]),"+f"(d[54]),"+f"(d[55]),"+f"(d[56]),"+f"(d[57]),"+f"(d[58]),"+f"(d[59]),"+f"(d[60]),"+f"(d[61]),"+f"(d[62]),"+f"(d[63]),"+f"(d[64]),"+f"(d[65]),"+f"(d[66]),"+f"(d[67]),"+f"(d[68]),"+f"(d[69]),"+f"(d[70]),"+f"(d[71]),"+f"(d[72]),"+f"(d[73]),"+f"(d[74]),"+f"(d[75]),"+f"(d[76]),"+f"(d[77]),"+f"(d[78]),"+f"(d[79]),"+f"(d[80]),"+f"(d[81]),"+f"(d[82]),"+f"(d[83]),"+f"(d[84]),"+f"(d[85]),"+f"(d[86]),"+f"(d[87]),"+f"(d[88]),"+f"(d[89]),"+f"(d[90]),"+f"(d[91]),"+f"(d[92]),"+f"(d[93]),"+f"(d[94]),"+f"(d[95]),"+f"(d[96]),"+f"(d[97]),"+f"(d[98]),"+f"(d[99]),"+f"(d[100]),"+f"(d[101]),"+f"(d[102]),"+f"(d[103]),"+f"(d[104]),"+f"(d[105]),"+f"(d[106]),"+f"(d[107]),"+f"(d[108]),"+f"(d[109]),"+f"(d[110]),"+f"(d[111])
    : "r"(alo), "r"(blo), "n"(AOFF), "n"(AHI), "n"(BOFF), "n"(BHI), "n"(ACC));
}
template <int AOFF, uint32_t AHI, int BOFF, uint32_t BHI, int ACC>
__device__ __forceinline__ void wgmma_ss232(float (&d)[116], uint32_t alo, uint32_t blo) {
  asm volatile("{\n.reg .pred p;\n.reg .b32 la, lb;\n.reg .b64 ad, bd;\nsetp.ne.b32 p, %122, 0;\n"
    "add.u32 la, %116, %118;\nmov.b64 ad, {la, %119};\nadd.u32 lb, %117, %120;\nmov.b64 bd, {lb, %121};\n"
    "wgmma.mma_async.sync.aligned.m64n232k16.f32.bf16.bf16 {%0,%1,%2,%3,%4,%5,%6,%7,%8,%9,%10,%11,%12,%13,%14,%15,%16,%17,%18,%19,%20,%21,%22,%23,%24,%25,%26,%27,%28,%29,%30,%31,%32,%33,%34,%35,%36,%37,%38,%39,%40,%41,%42,%43,%44,%45,%46,%47,%48,%49,%50,%51,%52,%53,%54,%55,%56,%57,%58,%59,%60,%61,%62,%63,%64,%65,%66,%67,%68,%69,%70,%71,%72,%73,%74,%75,%76,%77,%78,%79,%80,%81,%82,%83,%84,%85,%86,%87,%88,%89,%90,%91,%92,%93,%94,%95,%96,%97,%98,%99,%100,%101,%102,%103,%104,%105,%106,%107,%108,%109,%110,%111,%112,%113,%114,%115}, ad, bd, p, 1, 1, 1, 1;\n}\n"
    : "+f"(d[0]),"+f"(d[1]),"+f"(d[2]),"+f"(d[3]),"+f"(d[4]),"+f"(d[5]),"+f"(d[6]),"+f"(d[7]),"+f"(d[8]),"+f"(d[9]),"+f"(d[10]),"+f"(d[11]),"+f"(d[12]),"+f"(d[13]),"+f"(d[14]),"+f"(d[15]),"+f"(d[16]),"+f"(d[17]),"+f"(d[18]),"+f"(d[19]),"+f"(d[20]),"+f"(d[21]),"+f"(d[22]),"+f"(d[23]),"+f"(d[24]),"+f"(d[25]),"+f"(d[26]),"+f"(d[27]),"+f"(d[28]),"+f"(d[29]),"+f"(d[30]),"+f"(d[31]),"+f"(d[32]),"+f"(d[33]),"+f"(d[34]),"+f"(d[35]),"+f"(d[36]),"+f"(d[37]),"+f"(d[38]),"+f"(d[39]),"+f"(d[40]),"+f"(d[41]),"+f"(d[42]),"+f"(d[43]),"+f"(d[44]),"+f"(d[45]),"+f"(d[46]),"+f"(d[47]),"+f"(d[48]),"+f"(d[49]),"+f"(d[50]),"+f"(d[51]),"+f"(d[52]),"+f"(d[53]),"+f"(d[54]),"+f"(d[55]),"+f"(d[56]),"+f"(d[57]),"+f"(d[58]),"+f"(d[59]),"+f"(d[60]),"+f"(d[61]),"+f"(d[62]),"+f"(d[63]),"+f"(d[64]),"+f"(d[65]),"+f"(d[66]),"+f"(d[67]),"+f"(d[68]),"+f"(d[69]),"+f"(d[70]),"+f"(d[71]),"+f"(d[72]),"+f"(d[73]),"+f"(d[74]),"+f"(d[75]),"+f"(d[76]),"+f"(d[77]),"+f"(d[78]),"+f"(d[79]),"+f"(d[80]),"+f"(d[81]),"+f"(d[82]),"+f"(d[83]),"+f"(d[84]),"+f"(d[85]),"+f"(d[86]),"+f"(d[87]),"+f"(d[88]),"+f"(d[89]),"+f"(d[90]),"+f"(d[91]),"+f"(d[92]),"+f"(d[93]),"+f"(d[94]),"+f"(d[95]),"+f"(d[96]),"+f"(d[97]),"+f"(d[98]),"+f"(d[99]),"+f"(d[100]),"+f"(d[101]),"+f"(d[102]),"+f"(d[103]),"+f"(d[104]),"+f"(d[105]),"+f"(d[106]),"+f"(d[107]),"+f"(d[108]),"+f"(d[109]),"+f"(d[110]),"+f"(d[111]),"+f"(d[112]),"+f"(d[113]),"+f"(d[114]),"+f"(d[115])
    : "r"(alo), "r"(blo), "n"(AOFF), "n"(AHI), "n"(BOFF), "n"(BHI), "n"(ACC));
}
template <int OFF, uint32_t BHI, int ACC>
__device__ __forceinline__ void wgmma_rs224(float (&d)[112], uint32_t a0, uint32_t a1, uint32_t a2, uint32_t a3, uint32_t blo) {
  asm volatile("{\n.reg .pred p;\n.reg .b32 l;\n.reg .b64 bd;\nsetp.ne.b32 p, %119, 0;\nadd.u32 l, %116, %117;\nmov.b64 bd, {l, %118};\n"
    "wgmma.mma_async.sync.aligned.m64n224k16.f32.bf16.bf16 {%0,%1,%2,%3,%4,%5,%6,%7,%8,%9,%10,%11,%12,%13,%14,%15,%16,%17,%18,%19,%20,%21,%22,%23,%24,%25,%26,%27,%28,%29,%30,%31,%32,%33,%34,%35,%36,%37,%38,%39,%40,%41,%42,%43,%44,%45,%46,%47,%48,%49,%50,%51,%52,%53,%54,%55,%56,%57,%58,%59,%60,%61,%62,%63,%64,%65,%66,%67,%68,%69,%70,%71,%72,%73,%74,%75,%76,%77,%78,%79,%80,%81,%82,%83,%84,%85,%86,%87,%88,%89,%90,%91,%92,%93,%94,%95,%96,%97,%98,%99,%100,%101,%102,%103,%104,%105,%106,%107,%108,%109,%110,%111}, {%112,%113,%114,%115}, bd, p, 1, 1, 1;\n}\n"
    : "+f"(d[0]),"+f"(d[1]),"+f"(d[2]),"+f"(d[3]),"+f"(d[4]),"+f"(d[5]),"+f"(d[6]),"+f"(d[7]),"+f"(d[8]),"+f"(d[9]),"+f"(d[10]),"+f"(d[11]),"+f"(d[12]),"+f"(d[13]),"+f"(d[14]),"+f"(d[15]),"+f"(d[16]),"+f"(d[17]),"+f"(d[18]),"+f"(d[19]),"+f"(d[20]),"+f"(d[21]),"+f"(d[22]),"+f"(d[23]),"+f"(d[24]),"+f"(d[25]),"+f"(d[26]),"+f"(d[27]),"+f"(d[28]),"+f"(d[29]),"+f"(d[30]),"+f"(d[31]),"+f"(d[32]),"+f"(d[33]),"+f"(d[34]),"+f"(d[35]),"+f"(d[36]),"+f"(d[37]),"+f"(d[38]),"+f"(d[39]),"+f"(d[40]),"+f"(d[41]),"+f"(d[42]),"+f"(d[43]),"+f"(d[44]),"+f"(d[45]),"+f"(d[46]),"+f"(d[47]),"+f"(d[48]),"+f"(d[49]),"+f"(d[50]),"+f"(d[51]),"+f"(d[52]),"+f"(d[53]),"+f"(d[54]),"+f"(d[55]),"+f"(d[56]),"+f"(d[57]),"+f"(d[58]),"+f"(d[59]),"+f"(d[60]),"+f"(d[61]),"+f"(d[62]),"+f"(d[63]),"+f"(d[64]),"+f"(d[65]),"+f"(d[66]),"+f"(d[67]),"+f"(d[68]),"+f"(d[69]),"+f"(d[70]),"+f"(d[71]),"+f"(d[72]),"+f"(d[73]),"+f"(d[74]),"+f"(d[75]),"+f"(d[76]),"+f"(d[77]),"+f"(d[78]),"+f"(d[79]),"+f"(d[80]),"+f"(d[81]),"+f"(d[82]),"+f"(d[83]),"+f"(d[84]),"+f"(d[85]),"+f"(d[86]),"+f"(d[87]),"+f"(d[88]),"+f"(d[89]),"+f"(d[90]),"+f"(d[91]),"+f"(d[92]),"+f"(d[93]),"+f"(d[94]),"+f"(d[95]),"+f"(d[96]),"+f"(d[97]),"+f"(d[98]),"+f"(d[99]),"+f"(d[100]),"+f"(d[101]),"+f"(d[102]),"+f"(d[103]),"+f"(d[104]),"+f"(d[105]),"+f"(d[106]),"+f"(d[107]),"+f"(d[108]),"+f"(d[109]),"+f"(d[110]),"+f"(d[111])
    : "r"(a0), "r"(a1), "r"(a2), "r"(a3), "r"(blo), "n"(OFF), "n"(BHI), "n"(ACC));
}
template <int OFF, uint32_t BHI, int ACC>
__device__ __forceinline__ void wgmma_rs56(float (&d)[28], uint32_t a0, uint32_t a1, uint32_t a2, uint32_t a3, uint32_t blo) {
  asm volatile("{\n.reg .pred p;\n.reg .b32 l;\n.reg .b64 bd;\nsetp.ne.b32 p, %35, 0;\nadd.u32 l, %32, %33;\nmov.b64 bd, {l, %34};\n"
    "wgmma.mma_async.sync.aligned.m64n56k16.f32.bf16.bf16 {%0,%1,%2,%3,%4,%5,%6,%7,%8,%9,%10,%11,%12,%13,%14,%15,%16,%17,%18,%19,%20,%21,%22,%23,%24,%25,%26,%27}, {%28,%29,%30,%31}, bd, p, 1, 1, 1;\n}\n"
    : "+f"(d[0]),"+f"(d[1]),"+f"(d[2]),"+f"(d[3]),"+f"(d[4]),"+f"(d[5]),"+f"(d[6]),"+f"(d[7]),"+f"(d[8]),"+f"(d[9]),"+f"(d[10]),"+f"(d[11]),"+f"(d[12]),"+f"(d[13]),"+f"(d[14]),"+f"(d[15]),"+f"(d[16]),"+f"(d[17]),"+f"(d[18]),"+f"(d[19]),"+f"(d[20]),"+f"(d[21]),"+f"(d[22]),"+f"(d[23]),"+f"(d[24]),"+f"(d[25]),"+f"(d[26]),"+f"(d[27])
    : "r"(a0), "r"(a1), "r"(a2), "r"(a3), "r"(blo), "n"(OFF), "n"(BHI), "n"(ACC));
}

__device__ __forceinline__ void st128(uint4* p, uint32_t a, uint32_t b, uint32_t c, uint32_t d) {
  asm volatile("{\n.reg .b128 v;\n.reg .b64 lo, hi;\nmov.b64 lo, {%1, %2};\nmov.b64 hi, {%3, %4};\nmov.b128 v, {lo, hi};\n"
               "st.relaxed.gpu.global.b128 [%0], v;\n}" ::"l"(p), "r"(a), "r"(b), "r"(c), "r"(d) : "memory");
}
__device__ __forceinline__ void ld128(const uint4* p, uint32_t* r) {
  asm volatile("{\n.reg .b128 v;\n.reg .b64 lo, hi;\nld.relaxed.gpu.global.b128 v, [%4];\nmov.b128 {lo, hi}, v;\n"
               "mov.b64 {%0, %1}, lo;\nmov.b64 {%2, %3}, hi;\n}" : "=r"(r[0]), "=r"(r[1]), "=r"(r[2]), "=r"(r[3]) : "l"(p) : "memory");
}

template <int OFF, uint32_t BHI, int ACC>
__device__ __forceinline__ void wgmma_rs32(float (&d)[16], uint32_t a0, uint32_t a1, uint32_t a2, uint32_t a3, uint32_t blo) {
  asm volatile("{\n.reg .pred p;\n.reg .b32 l;\n.reg .b64 bd;\nsetp.ne.b32 p, %23, 0;\nadd.u32 l, %20, %21;\nmov.b64 bd, {l, %22};\n"
    "wgmma.mma_async.sync.aligned.m64n32k16.f32.bf16.bf16 {%0,%1,%2,%3,%4,%5,%6,%7,%8,%9,%10,%11,%12,%13,%14,%15}, {%16,%17,%18,%19}, bd, p, 1, 1, 0;\n}\n"
    : "+f"(d[0]),"+f"(d[1]),"+f"(d[2]),"+f"(d[3]),"+f"(d[4]),"+f"(d[5]),"+f"(d[6]),"+f"(d[7]),"+f"(d[8]),"+f"(d[9]),"+f"(d[10]),"+f"(d[11]),"+f"(d[12]),"+f"(d[13]),"+f"(d[14]),"+f"(d[15])
    : "r"(a0), "r"(a1), "r"(a2), "r"(a3), "r"(blo), "n"(OFF), "n"(BHI), "n"(ACC));
}
template <int OFF, uint32_t BHI, int ACC>
__device__ __forceinline__ void wgmma_rs24(float (&d)[12], uint32_t a0, uint32_t a1, uint32_t a2, uint32_t a3, uint32_t blo) {
  asm volatile("{\n.reg .pred p;\n.reg .b32 l;\n.reg .b64 bd;\nsetp.ne.b32 p, %19, 0;\nadd.u32 l, %16, %17;\nmov.b64 bd, {l, %18};\n"
    "wgmma.mma_async.sync.aligned.m64n24k16.f32.bf16.bf16 {%0,%1,%2,%3,%4,%5,%6,%7,%8,%9,%10,%11}, {%12,%13,%14,%15}, bd, p, 1, 1, 1;\n}\n"
    : "+f"(d[0]),"+f"(d[1]),"+f"(d[2]),"+f"(d[3]),"+f"(d[4]),"+f"(d[5]),"+f"(d[6]),"+f"(d[7]),"+f"(d[8]),"+f"(d[9]),"+f"(d[10]),"+f"(d[11])
    : "r"(a0), "r"(a1), "r"(a2), "r"(a3), "r"(blo), "n"(OFF), "n"(BHI), "n"(ACC));
}
template <int OFF, uint32_t BHI, int ACC>
__device__ __forceinline__ void wgmma_rs16(float (&d)[8], uint32_t a0, uint32_t a1, uint32_t a2, uint32_t a3, uint32_t blo) {
  asm volatile("{\n.reg .pred p;\n.reg .b32 l;\n.reg .b64 bd;\nsetp.ne.b32 p, %15, 0;\nadd.u32 l, %12, %13;\nmov.b64 bd, {l, %14};\n"
    "wgmma.mma_async.sync.aligned.m64n16k16.f32.bf16.bf16 {%0,%1,%2,%3,%4,%5,%6,%7}, {%8,%9,%10,%11}, bd, p, 1, 1, 1;\n}\n"
    : "+f"(d[0]),"+f"(d[1]),"+f"(d[2]),"+f"(d[3]),"+f"(d[4]),"+f"(d[5]),"+f"(d[6]),"+f"(d[7])
    : "r"(a0), "r"(a1), "r"(a2), "r"(a3), "r"(blo), "n"(OFF), "n"(BHI), "n"(ACC));
}

constexpr int A_R1 = 0;
constexpr int A_R2A = A_R1 + 2624, A_R2B = A_R2A + 768, A_R3A = A_R2B + 768, A_R3B = A_R3A + 528;
constexpr int A_K1024 = A_R3B + 528;
constexpr int A_W5 = A_K1024 + 16;
constexpr int A_W3 = A_W5 + 4096;
constexpr int A_W9 = A_W3 + 4112;
constexpr int A_W7 = A_W9 + 2048;
constexpr int A_V  = A_W7 + 2048;
constexpr int A_UB = A_V + 2048;
constexpr int A_STG = A_UB + 5248;
constexpr int A_Y2 = A_STG, A_Y3 = A_Y2 + 6528, A_YB = A_Y3 + 4352;
constexpr int A_REC = A_STG + 4 * 4352;
constexpr int A_CH = A_REC + 8192;
static_assert(A_W5 % 16 == 0 && A_UB % 16 == 0 && A_CH % 16 == 0 && A_YB + 4096 <= A_REC, "layout");

struct cf { float x, y; };
__device__ __forceinline__ cf cmul(cf a, cf b) { cf r; r.x = fmaf(a.x, b.x, -a.y * b.y); r.y = fmaf(a.x, b.y, a.y * b.x); return r; }
__device__ __forceinline__ cf cexp_l(float lr, float li, float l) {
  float mag; asm("ex2.approx.ftz.f32 %0, %1;" : "=f"(mag) : "f"((lr * l) * 1.4426950408889634f));
  const float th = li * l;
  const float k = (fmaf(th, 0.15915494f, 12582912.f)) - 12582912.f;
  float ph = fmaf(th, 0.15915494f, -k);
  ph = fmaf(th, 6.4206383e-9f, ph) * 6.2831853f;
  cf r; r.x = mag * __cosf(ph); r.y = mag * __sinf(ph); return r;
}
__device__ __forceinline__ void sts16(uint32_t a, uint32_t v) { asm volatile("st.shared.u16 [%0], %1;" ::"r"(a), "h"((uint16_t)v) : "memory"); }
__device__ __forceinline__ void sts32(uint32_t a, uint32_t v) { asm volatile("st.shared.u32 [%0], %1;" ::"r"(a), "r"(v) : "memory"); }
__device__ __forceinline__ void sts64(uint32_t a, uint32_t v0, uint32_t v1) { asm volatile("st.shared.v2.u32 [%0], {%1, %2};" ::"r"(a), "r"(v0), "r"(v1) : "memory"); }
__device__ __forceinline__ void sts128(uint32_t a, uint32_t v0, uint32_t v1, uint32_t v2, uint32_t v3) {
  asm volatile("st.shared.v4.u32 [%0], {%1, %2, %3, %4};" ::"r"(a), "r"(v0), "r"(v1), "r"(v2), "r"(v3) : "memory");
}
__device__ __forceinline__ uint32_t lds32(uint32_t a) { uint32_t v; asm volatile("ld.shared.u32 %0, [%1];" : "=r"(v) : "r"(a) : "memory"); return v; }
__device__ __forceinline__ uint4 lds128(uint32_t a) {
  uint4 v; asm volatile("ld.shared.v4.u32 {%0, %1, %2, %3}, [%4];" : "=r"(v.x), "=r"(v.y), "=r"(v.z), "=r"(v.w) : "r"(a) : "memory"); return v;
}
__device__ __forceinline__ void ldsm4(uint32_t* r, uint32_t a) {
  asm volatile("ldmatrix.sync.aligned.m8n8.x4.shared.b16 {%0,%1,%2,%3}, [%4];" : "=r"(r[0]), "=r"(r[1]), "=r"(r[2]), "=r"(r[3]) : "r"(a) : "memory");
}
__device__ __forceinline__ void mma16816(float* d, const uint32_t* a, uint32_t b0, uint32_t b1) {
  asm volatile("mma.sync.aligned.m16n8k16.row.col.f32.bf16.bf16.f32 {%0,%1,%2,%3}, {%4,%5,%6,%7}, {%8,%9}, {%0,%1,%2,%3};"
               : "+f"(d[0]), "+f"(d[1]), "+f"(d[2]), "+f"(d[3]) : "r"(a[0]), "r"(a[1]), "r"(a[2]), "r"(a[3]), "r"(b0), "r"(b1));
}
__device__ __forceinline__ uint32_t hsub2_bf(uint32_t a, uint32_t b) { uint32_t r; asm("sub.rn.bf16x2 %0, %1, %2;" : "=r"(r) : "r"(a), "r"(b)); return r; }
__device__ __forceinline__ void bar_sync(int id, int n) { asm volatile("bar.sync %0, %1;" ::"r"(id), "r"(n) : "memory"); }

template <int S> struct F1B { static constexpr int c = S / 4 + ((S & 3) == 3 ? 0 : 0), cc = (16 * S) / 64, ks = (64 * cc - (16 * S - 48)) / 16, off = (A_UB + 2 * ks * 656 + (9 - cc) * 16) / 16; };

template <int NS>
__device__ __forceinline__ void load_quads(uint32_t* q, uint32_t addr) {
#pragma unroll
  for (int i = 0; i < NS; i++) {
    q[4 * i] = lds32(addr + i * 64); q[4 * i + 1] = lds32(addr + i * 64 + 32);
    q[4 * i + 2] = i ? q[4 * i - 3] : lds32(addr - 32);
    q[4 * i + 3] = q[4 * i];
  }
#pragma unroll
  for (int i = 0; i < 4 * NS; i++) asm volatile("" : "+r"(q[i]));
}
template <int S0, int NS>
__device__ __forceinline__ void f1_steps(float (&acc)[16], const uint32_t* a, uint32_t blo) {
  if constexpr (NS > 0) {
    wgmma_rs32<F1B<S0>::off, 8, S0 != 0>(acc, a[0], a[1], a[2], a[3], blo);
    f1_steps<S0 + 1, NS - 1>(acc, a + 4, blo);
  }
}
template <int S0, int NS, int BASE, int FIRST>
__device__ __forceinline__ void s2_steps(float (&acc)[12], const uint32_t* a, uint32_t blo) {
  if constexpr (NS > 0) {
    wgmma_rs24<BASE / 16 + (112 - 16 * S0), 64, !(FIRST && S0 == 0)>(acc, a[0], a[1], a[2], a[3], blo);
    s2_steps<S0 + 1, NS - 1, BASE, FIRST>(acc, a + 4, blo);
  }
}
template <int S0, int NS, int BASE, int FIRST>
__device__ __forceinline__ void s3_steps(float (&acc)[8], const uint32_t* a, uint32_t blo) {
  if constexpr (NS > 0) {
    wgmma_rs16<BASE / 16 + (48 - 16 * S0), 64, !(FIRST && S0 == 0)>(acc, a[0], a[1], a[2], a[3], blo);
    s3_steps<S0 + 1, NS - 1, BASE, FIRST>(acc, a + 4, blo);
  }
}

__device__ __forceinline__ void phase_a(
        unsigned char* sm, const uint32_t bar_rec, const uint32_t ep_addr,
        const __nv_bfloat16* __restrict__ x, const uint32_t* __restrict__ are, const uint32_t* __restrict__ aim,
        const uint32_t* __restrict__ bre, const uint32_t* __restrict__ bim, const uint32_t* __restrict__ cre,
        const uint32_t* __restrict__ cim, const unsigned short* __restrict__ logdt, const unsigned short* __restrict__ dskip,
        const uint4* __restrict__ wgate, const uint4* __restrict__ wup, const uint4* __restrict__ wdown) {
  const uint32_t sb = s2u(sm);
  const int tid = threadIdx.x, wg = tid >> 7, warp = tid >> 5, lane = tid & 31, wq = warp & 3, t128 = tid & 127;
  const int blk = blockIdx.x;
  const bool conv = blk < 112;

  uint2 xr[4];
  {
    const uint2* p = (const uint2*)(x + (size_t)(blk * 16 + warp) * DM);
    xr[0] = __ldg(p + lane); xr[1] = __ldg(p + 32 + lane); xr[2] = __ldg(p + 64 + lane);
    xr[3] = lane < 16 ? __ldg(p + 96 + lane) : make_uint2(0, 0);
  }
  const int ch = conv ? blk * 4 + wg : 0;
  const uint32_t cb = sb + wg * A_CH;
  uint32_t prm[6];
  {
    const int i = ch * 128 + t128;
    prm[0] = __ldg(are + i); prm[1] = __ldg(aim + i); prm[2] = __ldg(bre + i); prm[3] = __ldg(bim + i); prm[4] = __ldg(cre + i); prm[5] = __ldg(cim + i);
  }
  const uint32_t ldt = __ldg(logdt + ch);
  uint32_t cnt0 = 0;
  if (tid == 0) cnt0 = __ldcg(&g_cnt1);
#pragma unroll
  for (int i = 0; i < 4; i++) if (i < 3 || t128 < (A_W5 + 1024) / 16 - 384) sts128(cb + (i * 128 + t128) * 16, 0, 0, 0, 0);
  if (t128 < 65) sts128(cb + (t128 < 64 ? A_W3 + t128 * 16 : A_W9), 0, 0, 0, 0);
  if (t128 < 72) sts128(cb + A_UB + (t128 / 9) * 656 + (t128 % 9) * 16, 0, 0, 0, 0);
  {
    float s = 0.f, q = 0.f;
#pragma unroll
    for (int i = 0; i < 4; i++) {
      const float a = bf_lo(xr[i].x), b = bf_hi(xr[i].x), c = bf_lo(xr[i].y), d = bf_hi(xr[i].y);
      s += (a + b) + (c + d);
      q = fmaf(a, a, q); q = fmaf(b, b, q); q = fmaf(c, c, q); q = fmaf(d, d, q);
    }
#pragma unroll
    for (int o = 16; o; o >>= 1) { s += __shfl_xor_sync(~0u, s, o); q += __shfl_xor_sync(~0u, q, o); }
    const float mean = s * (1.f / DM);
    const float var = fmaxf(fmaf(-mean, mean, q * (1.f / DM)), 0.f);
    const float rs = __frcp_rn(rbf(__fsqrt_rn(rbf(rbf(var) + 1e-5f))));
    const uint32_t mm = pack_bf16(mean, mean);
    const uint32_t tu = sb + A_REC + (warp >> 3) * A_CH + (warp & 7) * 912 + lane * 8, tx = tu + 2 * A_CH;
#pragma unroll
    for (int i = 0; i < 4; i++) {
      if (i < 3 || lane < 16) {
        const uint32_t d0 = hsub2_bf(xr[i].x, mm), d1 = hsub2_bf(xr[i].y, mm);
        sts64(tu + i * 256, pack_bf16(bf_lo(d0) * rs, bf_hi(d0) * rs), pack_bf16(bf_lo(d1) * rs, bf_hi(d1) * rs));
        sts64(tx + i * 256, xr[i].x, xr[i].y);
      }
    }
  }
  if (tid == 0) sts32(ep_addr, (cnt0 >> 7) + 1u);
  if (tid == 320) TR(0, 1);
  auto publish_rows = [&]() {
    bar_sync(5, 512);
    uint4* dst = g_ux + ((size_t)(warp * 8 + (lane >> 2)) * 128 + blk) * 4 + ((lane ^ (blk >> 1)) & 3);
#pragma unroll
    for (int i = 0; i < 4; i++) {
      if (i < 3 || warp < 8) {
        uint32_t r[4];
        asm volatile("ldmatrix.sync.aligned.m8n8.x4.trans.shared.b16 {%0,%1,%2,%3}, [%4];" : "=r"(r[0]), "=r"(r[1]), "=r"(r[2]), "=r"(r[3])
                     : "r"(sb + A_REC + (lane >> 3) * A_CH + (lane & 7) * 912 + (warp + 16 * i) * 16) : "memory");
        dst[i * 65536] = make_uint4(r[0], r[1], r[2], r[3]);
      }
    }
    if (warp != 0) asm volatile("bar.arrive 6, 512;" ::: "memory");
  };
  auto release_rows = [&]() {
    if (warp == 0) {
      bar_sync(6, 512);
      if (lane == 0) { asm volatile("red.release.gpu.global.add.u32 [%0], 1;" ::"l"(&g_cnt1) : "memory"); TR(0, 8); }
      __syncwarp();
    }
  };

  if (!conv) {
    publish_rows();
    release_rows();
    const int a = blk - 112, mat = a >> 3, j = a & 7;
    float s[8];
#pragma unroll
    for (int k = 0; k < 8; k++) s[k] = 0.f;
    if (lane < 28) {
      const uint4* src = (mat ? wup : wgate) + j * 28 + lane + (size_t)warp * 224;
#pragma unroll
      for (int hb = 0; hb < 2; hb++) {
        uint4 v[14];
#pragma unroll
        for (int r = 0; r < 14; r++) v[r] = __ldg(src + (size_t)(hb * 14 + r) * 16 * 224);
#pragma unroll
        for (int r = 0; r < 14; r++) {
          s[0] += bf_lo(v[r].x); s[1] += bf_hi(v[r].x); s[2] += bf_lo(v[r].y); s[3] += bf_hi(v[r].y);
          s[4] += bf_lo(v[r].z); s[5] += bf_hi(v[r].z); s[6] += bf_lo(v[r].w); s[7] += bf_hi(v[r].w);
        }
      }
      float4* red = (float4*)(sm + A_STG + warp * 896 + lane * 32);
      red[0] = make_float4(s[0], s[1], s[2], s[3]); red[1] = make_float4(s[4], s[5], s[6], s[7]);
    }
    bar_sync(5, 512);
    if (tid < 224) {
      float t = 0.f;
#pragma unroll
      for (int w = 0; w < 16; w++) t += *(const float*)(sm + A_STG + w * 896 + tid * 4);
      const float hi = rbf(t), mid = rbf(t - hi), lo = rbf(t - hi - mid);
      const int q = tid / 112, n = tid % 112 + 112 * mat;
      __nv_bfloat16* dst = (__nv_bfloat16*)(g_cimg + (j * 2 + q) * 224 + (n >> 3) * 8) + (n & 7);
      dst[0] = __float2bfloat16_rn(hi); dst[8] = __float2bfloat16_rn(mid); dst[16] = __float2bfloat16_rn(lo);
#pragma unroll
      for (int k = 3; k < 8; k++) dst[8 * k] = __float2bfloat16_rn(0.f);
    }
    if (tid == 320) TR(0, 10);
    return;
  }

  const int g = lane >> 2, t = lane & 3;
  const int wr = (wq + wg) & 3;
  uint4 wv[6];
  auto w_src = [&](int i) -> const uint4* {
    if (i < 4) return (blk < 56 ? wgate : wup) + (blk % 56) * 4 + (lane & 3) + (size_t)(i * 128 + warp * 8 + (lane >> 2)) * 224;
    const int it = warp + 16 * (i - 4);
    return wdown + (size_t)(blk * 16 + (it / 14) * 8 + (lane >> 2)) * 56 + (it % 14) * 4 + (lane & 3);
  };
  auto w_on = [&](int i) { return i == 3 ? warp < 8 : i == 5 ? warp < 12 : true; };
  {
    const uint32_t stg = cb + A_STG + wq * 4352;
    const float dt = rbf(expf(__uint_as_float(ldt << 16)));
    float lr[2], li[2];
    cf bq[2], b0[2], b4[2];
    uint32_t bf[48];
#pragma unroll
    for (int m = 0; m < 2; m++) {
      lr[m] = dt * (m ? bf_hi(prm[0]) : bf_lo(prm[0]));
      li[m] = dt * (m ? bf_hi(prm[1]) : bf_lo(prm[1]));
    }
    {
      cf b[2], z[2];
#pragma unroll
      for (int m = 0; m < 2; m++) {
        cf db, c;
        db.x = dt * (m ? bf_hi(prm[2]) : bf_lo(prm[2])); db.y = -dt * (m ? bf_hi(prm[3]) : bf_lo(prm[3]));
        c.x = m ? bf_hi(prm[4]) : bf_lo(prm[4]); c.y = -(m ? bf_hi(prm[5]) : bf_lo(prm[5]));
        b[m] = cmul(c, db);
        z[m] = cexp_l(lr[m], -li[m], 1.f);
        bq[m] = cexp_l(lr[m], -li[m], 256.f);
      }
#pragma unroll
      for (int i = 0; i < 8; i++) {
        sts64(stg + i * 272 + lane * 8, pack_bf16(b[0].x, b[0].y), pack_bf16(b[1].x, b[1].y));
        if (!(i & 1)) {
          cf e0 = cmul(b[0], bq[0]), e1 = cmul(b[1], bq[1]);
          sts64(stg + (8 + i / 2) * 272 + lane * 8, pack_bf16(e0.x, e0.y), pack_bf16(e1.x, e1.y));
          if (i == 0) { b0[0] = e0; b0[1] = e1; }
          if (i == 4) { b4[0] = e0; b4[1] = e1; }
        }
        if (i < 7) { b[0] = cmul(b[0], z[0]); b[1] = cmul(b[1], z[1]); }
        if (i == 1) publish_rows();
      }
#pragma unroll
      for (int i = 0; i < 7; i++) {
        b0[0] = cmul(b0[0], bq[0]); b0[1] = cmul(b0[1], bq[1]);
        sts64(stg + (i < 2 ? 12 + 2 * i : i - 2) * 272 + lane * 8, pack_bf16(b0[0].x, b0[0].y), pack_bf16(b0[1].x, b0[1].y));
        if (i < 2) {
          b4[0] = cmul(b4[0], bq[0]); b4[1] = cmul(b4[1], bq[1]);
          sts64(stg + (13 + 2 * i) * 272 + lane * 8, pack_bf16(b4[0].x, b4[0].y), pack_bf16(b4[1].x, b4[1].y));
        }
        if (i == 1) {
          __syncwarp();
#pragma unroll
          for (int n = 0; n < 2; n++)
#pragma unroll
            for (int k2 = 0; k2 < 4; k2++) ldsm4(bf + n * 16 + k2 * 4, stg + (n * 8 + (lane & 7)) * 272 + k2 * 64 + (lane >> 3) * 16);
          __syncwarp();
        }
      }
    }
    __syncwarp();
#pragma unroll
    for (int k2 = 0; k2 < 4; k2++) ldsm4(bf + 32 + k2 * 4, stg + (lane & 7) * 272 + k2 * 64 + (lane >> 3) * 16);
    release_rows();
    if (!(lane & 1)) {
#pragma unroll
      for (int i = 0; i < 6; i++) if (w_on(i)) asm volatile("prefetch.global.L2 [%0];" ::"l"(w_src(i)));
    }
    if (tid == 320) TR(0, 16);
    float c[6][4];
#pragma unroll
    for (int i = 0; i < 6; i++) { c[i][0] = 0.f; c[i][1] = 0.f; c[i][2] = 0.f; c[i][3] = 0.f; }
    cf p[2], v[2];
    p[0] = cexp_l(lr[0], li[0], 8.f); p[1] = cexp_l(lr[1], li[1], 8.f);
    v[0].x = 1.f; v[0].y = 0.f; v[1] = v[0];
#pragma unroll
    for (int mt = 0; mt < 2; mt++) {
      __syncwarp();
#pragma unroll
      for (int i = 0; i < 16; i++) {
        sts64(stg + i * 272 + lane * 8, pack_bf16(v[0].x, v[0].y), pack_bf16(v[1].x, v[1].y));
        if (mt == 0 && i == 0) { v[0] = p[0]; v[1] = p[1]; }
        else if (mt == 0 || i < 15) { v[0] = cmul(v[0], p[0]); v[1] = cmul(v[1], p[1]); }
      }
      __syncwarp();
      if (mt == 1 && tid == 160) {
        const uint32_t tgt = lds32(ep_addr) * 128u;
        uint32_t cv; int it = 0;
        do { asm volatile("ld.acquire.gpu.global.u32 %0, [%1];" : "=r"(cv) : "l"(&g_cnt1) : "memory"); } while ((int)(cv - tgt) < 0 && ++it < 200000);
        asm volatile("fence.proxy.async;" ::: "memory");
        TR(0, 9);
        mbar_expect(bar_rec, 32768);
        for (int c2 = 0; c2 < 4; c2++) bulk_ld(sb + c2 * A_CH + A_REC, g_ux + (size_t)(blk * 4 + c2) * 512, 8192, bar_rec);
      }
#pragma unroll
      for (int ks = 0; ks < 8; ks++) {
        uint32_t a[4];
        ldsm4(a, stg + (lane & 15) * 272 + ks * 32 + (lane >> 4) * 16);
#pragma unroll
        for (int n = 0; n < 3; n++) mma16816(c[n * 2 + mt], a, bf[n * 16 + ks * 2], bf[n * 16 + ks * 2 + 1]);
      }
    }
    __syncwarp();
#pragma unroll
    for (int i = 0; i < 6; i++)
      sts128(stg + i * 512 + lane * 16, __float_as_uint(c[i][0]), __float_as_uint(c[i][1]), __float_as_uint(c[i][2]), __float_as_uint(c[i][3]));
#pragma unroll
    for (int i = 0; i < 6; i++) if (w_on(i)) wv[i] = __ldg(w_src(i));
    bar_sync(1 + wg, 128);
    if (tid == 320) TR(0, 2);
#pragma unroll
    for (int rep = 0; rep < 2; rep++) {
      const int qd = rep ? 2 + wr : 3 - wr;
      if (rep == 0 || wr >= 2) {
        float s[4] = {0.f, 0.f, 0.f, 0.f};
#pragma unroll
        for (int w = 0; w < 4; w++) {
          uint4 u4 = lds128(cb + A_STG + w * 4352 + qd * 512 + lane * 16);
          s[0] += __uint_as_float(u4.x); s[1] += __uint_as_float(u4.y); s[2] += __uint_as_float(u4.z); s[3] += __uint_as_float(u4.w);
        }
#pragma unroll
        for (int hf = 0; hf < 2; hf++) {
          const int j = (qd & 1) * 16 + g + 8 * hf;
          const uint32_t pk = pack_bf16(s[2 * hf + 1], s[2 * hf]);
          const uint32_t v0 = pk >> 16, v1 = pk & 0xFFFFu, v00 = v0 * 0x10001u;
          if (rep == 1) {
            if (t < 2) {
#pragma unroll
              for (int e = 0; e < 2; e++) {
                const int lam = 128 + 32 * (2 * t + e) + j, mu = lam >> 1;
                const uint32_t val = e ? v1 : v0;
                uint32_t a = cb + ((lam & 1) ? A_R3B : A_R3A) + mu * 4;
                if (lam == 128) { a = cb + A_R2A + 128 * 4; sts32(cb + A_K1024, val << 16); }
                sts16(a, val); sts16(a + 6, val);
              }
            } else if (t == 2 && j == 0) { sts16(cb + A_R3A + 128 * 4, v0); }
          } else if (qd < 2) {
            const uint32_t a = cb + A_R1 + (62 + 8 * j + 2 * t) * 4;
            sts16(a, v0); sts32(a + 4, pk); sts16(a + 10, v1);
          } else if (t < 2) {
            const int L = 256 + 8 * j + 4 * t;
            const uint32_t a = cb + A_R1 + (62 + L) * 4;
            if (L > 256) { sts16(a - 4, v0); sts32(a, v00); } else sts16(a, v0);
            sts32(a + 4, v00); sts32(a + 8, pk); sts16(a + 14, v1);
          } else {
            const int mu = 64 + 32 * (t - 2) + j;
            if (mu == 64) {
              const uint32_t a = cb + A_R1 + (62 + 512) * 4;
              sts16(a - 4, v0); sts32(a, v00); sts32(a + 4, v00); sts32(a + 8, v00); sts16(a + 14, v0);
            } else { sts16(cb + A_R2A + mu * 4, v0); sts16(cb + A_R2A + mu * 4 + 6, v0); }
            sts16(cb + A_R2B + mu * 4, v1); sts16(cb + A_R2B + mu * 4 + 6, v1);
          }
        }
      }
    }
  }
  {
    const int ngg = (blk % 56) * 4 + (lane & 3), j = ngg / 28, q = (ngg % 28) / 14, ng = ngg % 14 + (blk < 56 ? 0 : 14);
    uint4* dst = g_wimg + (size_t)j * 37632 + q * 14 * 896 + ng * 32 + (warp >> 2) * 896 + (warp & 3) * 8 + (lane >> 2);
#pragma unroll
    for (int i = 0; i < 4; i++) if (w_on(i)) dst[i * 4 * 896] = wv[i];
#pragma unroll
    for (int i = 4; i < 6; i++) {
      const int it = warp + 16 * (i - 4), n2 = (it % 14) * 4 + (lane & 3), k = (blk % 7) * 16 + (it / 14) * 8 + (lane >> 2);
      if (w_on(i)) g_wimg[(size_t)(blk / 14) * 37632 + 25088 + ((n2 / 7) * 2 + (blk / 7) % 2) * 784 + (n2 % 7) * 112 + k] = wv[i];
    }
  }
  if (tid == 320) TR(0, 3);

  const int bk = wr * 32 + lane;
  uint32_t xt[8], ud[8];
  {
    mbar_wait(bar_rec, 0);
    if (tid == 320) TR(0, 4);
    uint4 r[4];
#pragma unroll
    for (int i = 0; i < 4; i++) r[i] = lds128(cb + A_REC + bk * 64 + ((i ^ (bk >> 1)) & 3) * 16);
    const uint32_t ua = cb + A_UB + ((2 * bk) & 7) * 656 + ((bk >> 2) + 9) * 16;
    sts128(ua, r[0].x, r[1].x, r[2].x, r[3].x);
    sts128(ua + 656, r[0].y, r[1].y, r[2].y, r[3].y);
    if (bk <= 96) {
      const bool neg = bk == 96;
      const int bp = neg ? -1 : bk;
      uint32_t h[4];
      h[0] = lds32(cb + A_REC + ((bp - 1) & 127) * 64 + ((2 ^ ((bp - 1) >> 1)) & 3) * 16 + 4);
      h[1] = lds32(cb + A_REC + ((bp - 1) & 127) * 64 + ((3 ^ ((bp - 1) >> 1)) & 3) * 16 + 4);
      h[2] = lds32(cb + A_REC + (bp + 1) * 64 + ((0 ^ ((bp + 1) >> 1)) & 3) * 16);
      h[3] = lds32(cb + A_REC + (bp + 1) * 64 + ((1 ^ ((bp + 1) >> 1)) & 3) * 16);
      if (bp <= 0) { h[0] = 0; h[1] = 0; }
      const uint32_t wd[12] = {h[0], h[1], neg ? 0 : r[0].x, neg ? 0 : r[1].x, neg ? 0 : r[2].x, neg ? 0 : r[3].x,
                               neg ? 0 : r[0].y, neg ? 0 : r[1].y, neg ? 0 : r[2].y, neg ? 0 : r[3].y, h[2], h[3]};
      float P[25];
      P[0] = 0.f;
#pragma unroll
      for (int i = 0; i < 12; i++) { P[2 * i + 1] = P[2 * i] + bf_lo(wd[i]); P[2 * i + 2] = P[2 * i + 1] + bf_hi(wd[i]); }
#define WIN(i, hw) (P[(i) + 5 + (hw)] - P[(i) + 4 - (hw)])
#define WPK(i, hw) pack_bf16(WIN(i, hw), WIN((i) + 1, hw))
      const int tp = 2 * bp;
      const uint32_t a3 = cb + A_W3 + (tp + 64) * 16 + 8, a5 = cb + A_W5 + (tp + 64) * 16;
      if (!neg) sts64(a3, WPK(0, 1), WPK(2, 1));
      if (!neg) sts128(a3 + 8, WPK(4, 1), WPK(6, 1), WPK(8, 1), WPK(10, 1));
      sts64(a3 + 24, WPK(12, 1), WPK(14, 1));
      sts128(a5, WPK(0, 2), WPK(2, 2), WPK(4, 2), WPK(6, 2));
      sts128(a5 + 16, WPK(8, 2), WPK(10, 2), WPK(12, 2), WPK(14, 2));
      if (bp < 64) {
        if (!neg) sts128(cb + A_W7 + 1024 + bp * 16, WPK(0, 3), WPK(2, 3), WPK(4, 3), WPK(6, 3));
        if (bp < 63) {
          sts128(cb + A_W7 + (bp + 1) * 16, WPK(8, 3), WPK(10, 3), WPK(12, 3), WPK(14, 3));
          sts128(cb + A_W9 + (bp + 1) * 16, WPK(0, 4), WPK(2, 4), WPK(4, 4), WPK(6, 4));
          sts128(cb + A_W9 + 1024 + (bp + 1) * 16, WPK(8, 4), WPK(10, 4), WPK(12, 4), WPK(14, 4));
        }
        if (!neg) {
#define VPK(i) pack_bf16(P[(i) + 2] - P[i], P[(i) + 3] - P[(i) + 1])
          sts128(cb + A_V + bp * 32, VPK(0), VPK(2), VPK(4), VPK(6));
          sts128(cb + A_V + bp * 32 + 16, VPK(8), VPK(10), VPK(12), VPK(14));
        }
      }
    }
  }
  asm volatile("fence.proxy.async.shared::cta;" ::: "memory");
  bar_sync(1 + wg, 128);
  if (tid == 320) TR(0, 5);

  {
    const uint32_t cbu = __shfl_sync(~0u, cb, 0);
    const uint32_t blo_k = ((cbu & 0x3FFFF) >> 4) | (41u << 16);
    const uint32_t blo_n = ((cbu & 0x3FFFF) >> 4) | (8u << 16);
    const uint32_t tb = cb + (16 * wq + g - 2 * t) * 4;
    float y1[16], y2[12], y3[8];
    const uint32_t dk16 = __ldg(dskip + ch);
    uint32_t qa[32], qb[32];
    const uint32_t t1 = tb + A_R1 + (62 - 48) * 4;
    load_quads<4>(qa, tb + A_R3A + 17 * 4); load_quads<4>(qa + 16, tb + A_R3B + 16 * 4);
    wg_fence();
    s3_steps<0, 4, A_W9, 1>(y3, qa, blo_n); s3_steps<0, 4, A_W7, 0>(y3, qa + 16, blo_n);
    wg_commit();
    load_quads<8>(qb, tb + A_R2A + 16 * 4);
    wg_fence(); s2_steps<0, 8, A_W5, 1>(y2, qb, blo_n); wg_commit();
    wg_wait<1>(); load_quads<8>(qa, tb + A_R2B + 16 * 4);
    wg_fence(); s2_steps<0, 8, A_W3, 0>(y2, qa, blo_n); wg_commit();
    wg_wait<1>(); load_quads<8>(qb, t1);
    wg_fence(); f1_steps<0, 8>(y1, qb, blo_k); wg_commit();
    wg_wait<1>(); load_quads<8>(qa, t1 + 8 * 64);
    wg_fence(); f1_steps<8, 8>(y1, qa, blo_k); wg_commit();
    reg_fence(y2); reg_fence(y3);
    if (tid == 320) TR(0, 18);
    {
      const float k1024 = __uint_as_float(lds32(cb + A_K1024));
#pragma unroll
      for (int i = 0; i < 2; i++)
#pragma unroll
        for (int hf = 0; hf < 2; hf++) {
          const int idx = 16 * (16 * wq + g + 8 * hf) + 8 * i + 2 * t;
          const uint32_t vv = lds32(cb + A_V + idx * 2);
          sts64(cb + A_Y3 + (idx + 4 * (idx >> 6)) * 4, __float_as_uint(fmaf(k1024, bf_lo(vv), y3[4 * i + 2 * hf])),
                __float_as_uint(fmaf(k1024, bf_hi(vv), y3[4 * i + 2 * hf + 1])));
        }
#pragma unroll
      for (int i = 0; i < 3; i++)
#pragma unroll
        for (int hf = 0; hf < 2; hf++) {
          const int idx = 512 * i + 8 * (16 * wq + g + 8 * hf) + 2 * t;
          sts64(cb + A_Y2 + (idx + 4 * (idx >> 6)) * 4, __float_as_uint(y2[4 * i + 2 * hf]), __float_as_uint(y2[4 * i + 2 * hf + 1]));
        }
    }
    wg_wait<1>(); load_quads<8>(qb, t1 + 16 * 64);
    wg_fence(); f1_steps<16, 8>(y1, qb, blo_k); wg_commit();
    wg_wait<1>(); load_quads<8>(qa, t1 + 24 * 64);
    wg_fence(); f1_steps<24, 8>(y1, qa, blo_k); wg_commit();
    wg_wait<1>(); load_quads<5>(qb, t1 + 32 * 64);
    wg_fence(); f1_steps<32, 5>(y1, qb, blo_k); wg_commit();
    bar_sync(1 + wg, 128);
    float ex[12];
#pragma unroll
    for (int i = 1; i < 4; i++)
#pragma unroll
      for (int k = 0; k < 4; k++) {
        const int aa = 8 * i + 2 * t + (k & 1), b = 16 * wq + g + 8 * (k >> 1);
        float e = __uint_as_float(lds32(cb + A_Y2 + ((aa - 8) * 68 + b) * 4));
        if (i >= 2) e += __uint_as_float(lds32(cb + A_Y3 + ((aa - 16) * 68 + b) * 4));
        ex[4 * (i - 1) + k] = e;
      }
    {
      const uint32_t dk = dk16 * 0x10001u;
#pragma unroll
      for (int i = 0; i < 4; i++) {
        const uint4 r = lds128(cb + A_REC + bk * 64 + ((i ^ (bk >> 1)) & 3) * 16);
        ud[i] = hmul2_bf(r.x, dk); ud[4 + i] = hmul2_bf(r.y, dk); xt[i] = r.z; xt[4 + i] = r.w;
      }
    }
    wg_wait<0>();
    reg_fence(y1);
    if (tid == 320) TR(0, 6);
#pragma unroll
    for (int i = 0; i < 12; i++) y1[4 + i] += ex[i];
#pragma unroll
    for (int i = 0; i < 2; i++) {
      const int mi = lane >> 3, aa = 8 * (2 * i + (mi >> 1)) + (lane & 7);
      asm volatile("stmatrix.sync.aligned.m8n8.x4.trans.shared.b16 [%0], {%1,%2,%3,%4};"
                   ::"r"(cb + A_YB + aa * 128 + (((2 * wq + (mi & 1)) ^ (lane & 7)) << 4)),
                     "r"(pack_bf16(y1[8 * i], y1[8 * i + 1])), "r"(pack_bf16(y1[8 * i + 2], y1[8 * i + 3])),
                     "r"(pack_bf16(y1[8 * i + 4], y1[8 * i + 5])), "r"(pack_bf16(y1[8 * i + 6], y1[8 * i + 7])) : "memory");
    }
  }
  bar_sync(1 + wg, 128);
#pragma unroll
  for (int c = 0; c < 2; c++) {
    const int tau = 2 * bk + c, r = ch & 7;
    const uint4 y = lds128(cb + A_YB + (tau >> 3) * 128 + (((tau ^ (tau >> 3)) & 7) << 4));
    g_himg[(size_t)(tau >> 4) * 7168 + (ch >> 3) * 128 + ((tau >> 3) & 1) * 64 + r * 8 + ((tau & 7) ^ r)] =
        make_uint4(hadd2_bf(xt[4 * c], hadd2_bf(y.x, ud[4 * c])), hadd2_bf(xt[4 * c + 1], hadd2_bf(y.y, ud[4 * c + 1])),
                   hadd2_bf(xt[4 * c + 2], hadd2_bf(y.z, ud[4 * c + 2])), hadd2_bf(xt[4 * c + 3], hadd2_bf(y.w, ud[4 * c + 3])));
  }
  if (tid == 320) TR(0, 7);
}

constexpr int B_SA = 0, B_RING = 114688, B_SLOT = 14848, B_NSLOT = 7;
constexpr int B_CS = B_RING + B_NSLOT * B_SLOT;
constexpr int B_RED = B_CS + 7168;
constexpr int B_BAR = B_RED + 256;
constexpr int B_SMEM = B_BAR + 512, A_SMEM = 4 * A_CH + 64;

__device__ __forceinline__ uint32_t mapa(uint32_t a, uint32_t r) { uint32_t o; asm("mapa.shared::cluster.u32 %0, %1, %2;" : "=r"(o) : "r"(a), "r"(r)); return o; }
template <class T> __device__ __forceinline__ T* pin(T* p) { asm volatile("" : "+l"(p)); return p; }
__device__ __forceinline__ uint32_t pin(uint32_t v) { asm volatile("" : "+r"(v)); return v; }
__device__ __forceinline__ void wait_count(const unsigned* c, uint32_t tgt) {
  uint32_t v; int it = 0;
  do { asm volatile("ld.acquire.gpu.global.u32 %0, [%1];" : "=r"(v) : "l"(c) : "memory"); } while ((int)(v - tgt) < 0 && ++it < 400000);
  asm volatile("fence.proxy.async;" ::: "memory");
}

template <int Q, int ST>
__device__ __forceinline__ void g1_stage(float (&acc)[116], uint32_t alo, uint32_t blo, uint32_t bar_full, uint32_t bar_h) {
  constexpr int s = Q * 14 + ST, sl = s % B_NSLOT;
  if (Q == 0) mbar_wait(bar_h + 8 * ST, 0);
  mbar_wait(bar_full + 8 * sl, (s / B_NSLOT) & 1);
  wg_fence();
  if (Q == 0) {
    wgmma_ss232<(2 * ST) * 256, 0x40000080u, (sl * B_SLOT) / 16, 32, ST != 0>(acc, alo, blo);
    wgmma_ss232<(2 * ST + 1) * 256, 0x40000080u, (sl * B_SLOT + 256) / 16, 32, 1>(acc, alo, blo);
  } else {
    wgmma_ss224<(2 * ST) * 256, 0x40000080u, (sl * B_SLOT) / 16, 32, ST != 0>(*(float(*)[112])acc, alo, blo);
    wgmma_ss224<(2 * ST + 1) * 256, 0x40000080u, (sl * B_SLOT + 256) / 16, 32, 1>(*(float(*)[112])acc, alo, blo);
  }
}

__global__ void __launch_bounds__(512, 1)
k_front(const __nv_bfloat16* __restrict__ x, const uint32_t* __restrict__ are, const uint32_t* __restrict__ aim,
        const uint32_t* __restrict__ bre, const uint32_t* __restrict__ bim, const uint32_t* __restrict__ cre,
        const uint32_t* __restrict__ cim, const unsigned short* __restrict__ logdt, const unsigned short* __restrict__ dskip,
        const uint4* __restrict__ wgate, const uint4* __restrict__ wup, const uint4* __restrict__ wdown) {
  extern __shared__ __align__(1024) unsigned char sm[];
  const uint32_t bar_rec = s2u(sm) + 4 * A_CH;
  if (threadIdx.x == 320) TR(0, 0);
  asm volatile("griddepcontrol.launch_dependents;");
  if (threadIdx.x == 160) { mbar_init(bar_rec, 1); asm volatile("fence.mbarrier_init.release.cluster;" ::: "memory"); }
  phase_a(sm, bar_rec, bar_rec + 8, x, are, aim, bre, bim, cre, cim, logdt, dskip, wgate, wup, wdown);
  bar_sync(0, 512);
  if (threadIdx.x == 0) { asm volatile("red.release.gpu.global.add.u32 [%0], 1;" ::"l"(&g_cnt2) : "memory"); TR(0, 11); }
}

__global__ void __cluster_dims__(2, 1, 1) __launch_bounds__(384, 1) k_ffn(__nv_bfloat16* __restrict__ out) {
  extern __shared__ __align__(1024) unsigned char sm[];
  const uint32_t sb = s2u(sm);
  const int tid = threadIdx.x, wg = tid >> 7, warp = tid >> 5, lane = tid & 31;
  const uint32_t bar_full = sb + B_BAR, bar_empty = bar_full + 64, bar_h = bar_full + 128, bar_cs = bar_full + 240,
                 bar_var = bar_full + 248, bar_own = bar_full + 256, bar_g2 = bar_full + 320;
  const uint32_t ep = (__ldcg(&g_cnt3) >> 7) + 1u;
  if (tid == 0) {
    TR(1, 0);
    for (int i = 0; i < B_NSLOT; i++) { mbar_init(bar_full + 8 * i, 1); mbar_init(bar_empty + 8 * i, 4); }
    asm volatile("fence.mbarrier_init.release.cluster;" ::: "memory");
  } else if (tid == 32) {
    for (int i = 0; i < 14; i++) mbar_init(bar_h + 8 * i, 1);
  } else if (tid == 64) {
    mbar_init(bar_cs, 1);
    mbar_init(bar_var, 64);
    mbar_init(bar_g2, 1);
    for (int i = 0; i < 8; i++) mbar_init(bar_own + 8 * i, 32);
  } else if (tid >= 128 && tid < 352) {
    sts128(sb + B_RING + ((tid - 128) >> 5) * B_SLOT + 14336 + (tid & 31) * 16, 0x3F803F80u, 0x3F803F80u, 0x3F803F80u, 0x3F803F80u);
  }
  asm volatile("fence.proxy.async.shared::cta;" ::: "memory");
  __syncthreads();
  asm volatile("barrier.cluster.arrive.relaxed.aligned;" ::: "memory");
  const int rank = blockIdx.x & 1, rt = blockIdx.x & 15, j = blockIdx.x >> 4;
  const int wq = warp & 3, t128 = tid & 127, g = lane >> 2, t = lane & 3;
  const uint32_t own_buf = sb + B_SA + (j < 4 ? 65536 : 0);

  if (wg == 2) {
    asm volatile("setmaxnreg.dec.sync.aligned.u32 88;");
    if (warp != 9) asm volatile("barrier.cluster.wait.aligned;" ::: "memory");
    if (warp == 8) {
      if (lane == 0) {
        const char* wsrc = (const char*)g_wimg + (size_t)j * 602112;
        wait_count(&g_cnt2, ep * 128u);
        TR(1, 1);
        int slot = 0, ph = 0;
        for (int s = 0; s < 44; s++) {
          if (s >= B_NSLOT) mbar_wait(bar_empty + 8 * slot, ph ^ 1);
          uint32_t dst = sb + B_RING + slot * B_SLOT, fb = bar_full + 8 * slot;
          if (s < 28) {
            mbar_expect(fb, 14336);
            bulk_ld_mc(dst + rank * 7168, wsrc + s * 14336 + rank * 7168, 7168, fb);
          } else {
            const int c = (j + 1 + ((s - 28) >> 1)) & 7;
            mbar_expect(fb, 12544);
            bulk_ld_mc(dst + rank * 6272, wsrc + 401408 + (c * 2 + (s & 1)) * 12544 + rank * 6272, 6272, fb);
          }
          if (++slot == B_NSLOT) { slot = 0; ph ^= 1; }
        }
      }
    } else if (warp == 9) {
      if (lane == 0) {
        const char* hsrc = (const char*)g_himg + (size_t)rt * 114688;
        wait_count(&g_cnt2, ep * 128u);
        for (int i = 0; i < 14; i++) {
          mbar_expect(bar_h + 8 * i, 8192);
          bulk_ld(sb + B_SA + i * 8192, hsrc + i * 8192, 8192, bar_h + 8 * i);
        }
        mbar_expect(bar_cs, 7168);
        bulk_ld(sb + B_CS, g_cimg + j * 448, 7168, bar_cs);
      }
      __syncwarp();
      asm volatile("barrier.cluster.wait.aligned;" ::: "memory");
    } else {
      const int t64 = tid - 320;
      const int r = (lane >> 1) & 7, c = (j & 3) * 2 + (lane & 1);
      const uint32_t src = sb + B_SA + (t64 >> 4) * 2048 + (j >> 2) * 1024 + r * 128 + ((c ^ r) << 4);
      float a[16];
#pragma unroll
      for (int k = 0; k < 16; k++) a[k] = 0.f;
#pragma unroll 1
      for (int i = 0; i < 14; i++) {
        mbar_wait(bar_h + 8 * i, 0);
        uint4 v = lds128(src + i * 8192);
        float e[8] = {bf_lo(v.x), bf_hi(v.x), bf_lo(v.y), bf_hi(v.y), bf_lo(v.z), bf_hi(v.z), bf_lo(v.w), bf_hi(v.w)};
#pragma unroll
        for (int k = 0; k < 8; k++) { a[2 * k] += e[k]; a[2 * k + 1] = fmaf(e[k], e[k], a[2 * k + 1]); }
        __nanosleep(160);
      }
      mbar_arrive(bar_var);
#pragma unroll
      for (int rd = 0; rd < 4; rd++) {
        const int n = 8 >> rd;
        const bool up = lane & (2 * n);
#pragma unroll
        for (int k = 0; k < 8; k++) {
          if (k < n) {
            float keep = up ? a[k + n] : a[k], give = up ? a[k] : a[k + n];
            a[k] = keep + __shfl_xor_sync(~0u, give, 2 * n);
          }
        }
      }
      float* red = (float*)(sm + B_RED);
      red[(warp & 1) * 32 + (lane & 1) * 16 + (lane >> 1)] = a[0];
      bar_sync(1, 64);
      if (t64 < 16) {
        float mean = (red[2 * t64] + red[32 + 2 * t64]) * (1.f / DM);
        float var = fmaxf(fmaf(-mean, mean, (red[2 * t64 + 1] + red[33 + 2 * t64]) * (1.f / DM)), 0.f);
        float rs = __frcp_rn(rbf(__fsqrt_rn(rbf(rbf(var) + 1e-5f))));
        asm volatile("st.relaxed.gpu.global.u32 [%0], %1;"
                     ::"l"(g_stat2 + rt * 128 + j * 16 + t64), "r"((__float_as_uint(rs * rs) & ~1u) | (ep & 1u)) : "memory");
      }
      if (t64 == 0) TR(1, 2);
    }
    __syncwarp();
    const uint32_t tag = (ep & 1u) << 16;
    float sum[2][28];
#pragma unroll
    for (int i = 0; i < 28; i++) { sum[0][i] = 0.f; sum[1][i] = 0.f; }
    mbar_wait(bar_g2, 0);
    if (tid == 352) asm volatile("red.relaxed.gpu.global.add.u32 [%0], 1;" ::"l"(&g_cnt3) : "memory");
    {
      const uint32_t* fl = g_flag + (rt * 8 + ((j + 7 - (lane >> 1)) & 7)) * 64 + ((lane >> 1) & 7) * 8 + (lane & 1) * 4 + wq;
      uint32_t todo = 0x3FFF;
      int it = 0;
      while (todo && ++it < 400000) {
        uint32_t f = 0;
        if ((todo >> lane) & 1) asm volatile("ld.relaxed.gpu.global.u32 %0, [%1];" : "=r"(f) : "l"(fl) : "memory");
        uint32_t rdy = __ballot_sync(~0u, f == ep) & todo;
        while (rdy) {
          const int b = __ffs(rdy) - 1, q = b >> 1;
          rdy &= rdy - 1;
          const uint4* src = g_part + (size_t)((rt * 8 + ((j + 7 - q) & 7)) * 7 + q) * 896 + (b & 1) * 448;
          uint32_t in[14];
#pragma unroll
          for (int i = 0; i < 3; i++) ld128(src + i * 128 + t128, in + 4 * i);
          asm volatile("{\n.reg .b64 v;\nld.relaxed.gpu.global.b64 v, [%2];\nmov.b64 {%0, %1}, v;\n}"
                       : "=r"(in[12]), "=r"(in[13]) : "l"((const uint2*)(src + 384) + t128) : "memory");
          const bool ok = (((in[3] ^ tag) | (in[7] ^ tag) | (in[11] ^ tag) | (in[13] ^ tag)) & 0x10000u) == 0;
          if (__all_sync(~0u, ok)) {
            if (b & 1) {
#pragma unroll
              for (int i = 0; i < 14; i++) { sum[1][2 * i] += bf_lo(in[i]); sum[1][2 * i + 1] += bf_hi(in[i]); }
            } else {
#pragma unroll
              for (int i = 0; i < 14; i++) { sum[0][2 * i] += bf_lo(in[i]); sum[0][2 * i + 1] += bf_hi(in[i]); }
            }
            todo &= ~(1u << b);
            if (tid == 320 && (b & 1)) TR(1, 24 + q);
          }
        }
      }
    }
    if (tid == 320) TR(1, 8);
    uint32_t r2[4];
    {
      const uint32_t* sp = g_stat2 + rt * 128 + wq * 16 + g;
      int it = 0;
      do {
#pragma unroll
        for (int i = 0; i < 4; i++) asm volatile("ld.relaxed.gpu.global.u32 %0, [%1];" : "=r"(r2[i]) : "l"(sp + (i >> 1) * 64 + (i & 1) * 8) : "memory");
      } while ((((r2[0] ^ ep) | (r2[1] ^ ep) | (r2[2] ^ ep) | (r2[3] ^ ep)) & 1u) && ++it < 400000);
    }
#pragma unroll
    for (int wgc = 0; wgc < 2; wgc++) {
      mbar_wait(bar_own + 8 * (wgc * 4 + wq), 0);
#pragma unroll
      for (int i = 0; i < 7; i++) {
        const uint4 v = lds128(own_buf + i * 4096 + wgc * 2048 + t128 * 16);
        sum[wgc][4 * i] += __uint_as_float(v.x); sum[wgc][4 * i + 1] += __uint_as_float(v.y);
        sum[wgc][4 * i + 2] += __uint_as_float(v.z); sum[wgc][4 * i + 3] += __uint_as_float(v.w);
      }
      const float r20 = __uint_as_float(r2[2 * wgc]), r21 = __uint_as_float(r2[2 * wgc + 1]);
      uint32_t* o0 = (uint32_t*)(out + (size_t)(rt * 128 + wgc * 64 + wq * 16 + g) * DM + 56 * j + 2 * t);
      uint32_t* o1 = o0 + 8 * DM / 2;
#pragma unroll
      for (int i = 0; i < 4; i++) {
        uint32_t hres[4];
        int qq = lane >> 3, r = lane & 7, kg = 7 * j + 2 * i + (qq >> 1), c = 2 * wq + (qq & 1);
        if (kg > 55) kg = 55;
        asm volatile("ldmatrix.sync.aligned.m8n8.x4.trans.shared.b16 {%0,%1,%2,%3}, [%4];"
                     : "=r"(hres[0]), "=r"(hres[1]), "=r"(hres[2]), "=r"(hres[3])
                     : "r"(sb + B_SA + kg * 2048 + wgc * 1024 + r * 128 + ((c ^ r) << 4)) : "memory");
#pragma unroll
        for (int k = 0; k < 2; k++) {
          const int n = 2 * i + k;
          if (n < 7) {
            o0[4 * n] = hadd2_bf(hres[2 * k], pack_bf16(sum[wgc][4 * n] * r20, sum[wgc][4 * n + 1] * r20));
            o1[4 * n] = hadd2_bf(hres[2 * k + 1], pack_bf16(sum[wgc][4 * n + 2] * r21, sum[wgc][4 * n + 3] * r21));
          }
        }
      }
    }
    if (tid == 320) TR(1, 10);
    if (tid == 256) TR(1, 15);
    asm volatile("griddepcontrol.wait;" ::: "memory");
  } else {
    asm volatile("setmaxnreg.inc.sync.aligned.u32 208;");
    asm volatile("barrier.cluster.wait.aligned;" ::: "memory");
    uint32_t hh[56];
    const uint32_t tag = pin((ep & 1u) << 16);
    const uint32_t rel_bar = pin(mapa(bar_empty, t128 & 1));
    const bool relt = t128 < 2;
    auto release = [&](int sl) { if (relt) asm volatile("mbarrier.arrive.shared::cluster.b64 _, [%0];" ::"r"(rel_bar + 8 * sl) : "memory"); };
    const uint32_t alo = __shfl_sync(~0u, ((sb + B_SA + wg * 1024) & 0x3FFFF) >> 4, 0);
    const uint32_t blo = (((sb + B_RING) & 0x3FFFF) >> 4) | (8u << 16);
    const uint32_t clo = ((sb + B_CS) & 0x3FFFF) >> 4;
    uint32_t nm0, nm1;
    if (wg == 1) bar_sync(3, 256);
#define G1S(Q, ST) do { g1_stage<Q, ST>(acc, alo, blo, bar_full, bar_h); wg_commit(); \
      if (ST > 0) { wg_wait<1>(); release((Q * 14 + ST - 1) % B_NSLOT); } } while (0)
#define G1HH(Q) do { \
      _Pragma("unroll") \
      for (int i = 0; i < 28; i++) hh[28 * Q + i] = pack_bf16(acc[2 * i] * acc[56 + 2 * i], acc[2 * i + 1] * acc[57 + 2 * i]); \
    } while (0)
    {
      float acc[116];
      G1S(0, 0);
      if (tid == 0) TR(1, 3);
      G1S(0, 1);
      if (wg == 0) asm volatile("bar.arrive 3, 256;" ::: "memory");
      G1S(0, 2); G1S(0, 3); G1S(0, 4); G1S(0, 5); G1S(0, 6); G1S(0, 7); G1S(0, 8); G1S(0, 9); G1S(0, 10); G1S(0, 11); G1S(0, 12);
      G1S(0, 13);
      if (tid == 0) TR(1, 4);
      mbar_wait(bar_cs, 0);
      wg_wait<0>(); reg_fence(acc); release(13 % B_NSLOT);
      {
        const uint32_t msk = t == 0 ? 0xFFFFFFFFu : t == 1 ? 0xFFFFu : 0u;
        const float a = acc[112] * (-1.f / DM), b = acc[114] * (-1.f / DM);
        nm0 = pack_bf16(a, a) & msk; nm1 = pack_bf16(b, b) & msk;
      }
      wg_fence();
      wgmma_rs224<0, 8, 1>(*(float(*)[112])acc, nm0, nm1, 0u, 0u, clo);
      wg_commit(); wg_wait<0>(); reg_fence(acc);
      G1HH(0);
      if (tid == 0) TR(1, 5);
      G1S(1, 0); G1S(1, 1); G1S(1, 2); G1S(1, 3); G1S(1, 4); G1S(1, 5); G1S(1, 6); G1S(1, 7); G1S(1, 8); G1S(1, 9); G1S(1, 10); G1S(1, 11);
      G1S(1, 12);
      g1_stage<1, 13>(acc, alo, blo, bar_full, bar_h);
      wgmma_rs224<224, 8, 1>(*(float(*)[112])acc, nm0, nm1, 0u, 0u, clo);
      wg_commit(); wg_wait<1>(); release(26 % B_NSLOT);
      wg_wait<0>(); reg_fence(acc); release(27 % B_NSLOT);
      if (tid == 0) mbar_arrive(bar_g2);
      G1HH(1);
      if (tid == 0) TR(1, 6);
    }
    float accA[28], accB[28];
#define ISSUE(acc, I, a, FIRST) do { \
      constexpr int s_ = 28 + (I), sl_ = s_ % B_NSLOT; \
      mbar_wait(bar_full + 8 * sl_, (s_ / B_NSLOT) & 1); \
      wg_fence(); \
      wgmma_rs56<(sl_ * B_SLOT + 0 * 256) / 16, 112, !(FIRST)>(acc, (a)[0], (a)[1], (a)[2], (a)[3], blo); \
      wgmma_rs56<(sl_ * B_SLOT + 1 * 256) / 16, 112, 1>(acc, (a)[4], (a)[5], (a)[6], (a)[7], blo); \
      wgmma_rs56<(sl_ * B_SLOT + 2 * 256) / 16, 112, 1>(acc, (a)[8], (a)[9], (a)[10], (a)[11], blo); \
      wgmma_rs56<(sl_ * B_SLOT + 3 * 256) / 16, 112, 1>(acc, (a)[12], (a)[13], (a)[14], (a)[15], blo); \
      wgmma_rs56<(sl_ * B_SLOT + 4 * 256) / 16, 112, 1>(acc, (a)[16], (a)[17], (a)[18], (a)[19], blo); \
      wgmma_rs56<(sl_ * B_SLOT + 5 * 256) / 16, 112, 1>(acc, (a)[20], (a)[21], (a)[22], (a)[23], blo); \
      wgmma_rs56<(sl_ * B_SLOT + 6 * 256) / 16, 112, 1>(acc, (a)[24], (a)[25], (a)[26], (a)[27], blo); \
      wg_commit(); } while (0)
    uint4* const pdst = pin(g_part + (size_t)((rt * 8 + j) * 7) * 896 + wg * 448 + t128);
    uint2* const pdst2 = pin((uint2*)(g_part + (size_t)((rt * 8 + j) * 7) * 896 + wg * 448 + 384) + t128);
    uint32_t* const fdst = pin(g_flag + (rt * 8 + j) * 64 + warp);
    const bool flt = lane == 0;
    auto rel = [&](int i) { if (i < 9) release((28 + i) % B_NSLOT); };
    auto tg = [&](uint32_t v) { return (v & 0xFFFEFFFFu) | tag; };
    auto send_lo = [&](float (&acc)[28], int cc) {
      reg_fence(acc);
#pragma unroll
      for (int q = 0; q < 2; q++)
        st128(pdst + cc * 896 + q * 128, pack_bf16(acc[8 * q], acc[8 * q + 1]), pack_bf16(acc[8 * q + 2], acc[8 * q + 3]),
              pack_bf16(acc[8 * q + 4], acc[8 * q + 5]), tg(pack_bf16(acc[8 * q + 6], acc[8 * q + 7])));
    };
    auto send_hi = [&](float (&acc)[28], int cc) {
      st128(pdst + cc * 896 + 256, pack_bf16(acc[16], acc[17]), pack_bf16(acc[18], acc[19]), pack_bf16(acc[20], acc[21]), tg(pack_bf16(acc[22], acc[23])));
      asm volatile("{\n.reg .b64 v;\nmov.b64 v, {%1, %2};\nst.relaxed.gpu.global.b64 [%0], v;\n}"
                   ::"l"(pdst2 + cc * 1792), "r"(pack_bf16(acc[24], acc[25])), "r"(tg(pack_bf16(acc[26], acc[27]))) : "memory");
      if (flt) asm volatile("st.relaxed.gpu.global.u32 [%0], %1;" ::"l"(fdst + cc * 8), "r"(ep) : "memory");
    };
#define CHUNK(cur, prev, CC) do { \
      ISSUE(cur, 2 * (CC), hh, true); wg_wait<1>(); rel(2 * (CC) - 1); send_lo(prev, (CC) - 1); \
      ISSUE(cur, 2 * (CC) + 1, hh + 28, false); send_hi(prev, (CC) - 1); wg_wait<1>(); rel(2 * (CC)); } while (0)
    ISSUE(accA, 0, hh, true);
    ISSUE(accA, 1, hh + 28, false); wg_wait<1>(); rel(0);
    CHUNK(accB, accA, 1);
    if (tid == 0) TR(1, 11);
    CHUNK(accA, accB, 2);
    CHUNK(accB, accA, 3);
    if (tid == 0) TR(1, 13);
    CHUNK(accA, accB, 4);
    CHUNK(accB, accA, 5);
    if (tid == 0) TR(1, 16);
    CHUNK(accA, accB, 6);
    CHUNK(accB, accA, 7);
    if (tid == 0) TR(1, 7);
    mbar_wait(bar_var, 0);
    wg_wait<0>();
    reg_fence(accB);
#pragma unroll
    for (int i = 0; i < 7; i++)
      sts128(own_buf + i * 4096 + tid * 16, __float_as_uint(accB[4 * i]), __float_as_uint(accB[4 * i + 1]), __float_as_uint(accB[4 * i + 2]), __float_as_uint(accB[4 * i + 3]));
    mbar_arrive(bar_own + 8 * warp);
    if (tid == 0) TR(1, 9);
  }
}

extern "C" void kernel_launch(void* const* d_in, const int* in_sizes, int n_in, void* d_out, int out_size) {
  const __nv_bfloat16* x = (const __nv_bfloat16*)d_in[0];
  const __nv_bfloat16 *are = (const __nv_bfloat16*)d_in[1], *aim = (const __nv_bfloat16*)d_in[2], *bre = (const __nv_bfloat16*)d_in[3],
                      *bim = (const __nv_bfloat16*)d_in[4], *cre = (const __nv_bfloat16*)d_in[5], *cim = (const __nv_bfloat16*)d_in[6],
                      *logdt = (const __nv_bfloat16*)d_in[7], *dskip = (const __nv_bfloat16*)d_in[8];
  const __nv_bfloat16 *wg = (const __nv_bfloat16*)d_in[10], *wu = (const __nv_bfloat16*)d_in[11], *wd = (const __nv_bfloat16*)d_in[12];

  static bool init = false;
  if (!init) {
    init = true;
    cudaFuncSetAttribute(k_ffn, cudaFuncAttributeMaxDynamicSharedMemorySize, B_SMEM);
    cudaFuncSetAttribute(k_front, cudaFuncAttributeMaxDynamicSharedMemorySize, A_SMEM);
  }
  cudaStream_t st = cudaStreamPerThread;
  k_front<<<128, 512, A_SMEM, st>>>(
      x, (const uint32_t*)are, (const uint32_t*)aim, (const uint32_t*)bre, (const uint32_t*)bim, (const uint32_t*)cre, (const uint32_t*)cim,
      (const unsigned short*)logdt, (const unsigned short*)dskip, (const uint4*)wg, (const uint4*)wu, (const uint4*)wd);
  cudaLaunchConfig_t cfg = {};
  cfg.gridDim = dim3(128); cfg.blockDim = dim3(384); cfg.dynamicSmemBytes = B_SMEM; cfg.stream = st;
  cudaLaunchAttribute at[1];
  at[0].id = cudaLaunchAttributeProgrammaticStreamSerialization; at[0].val.programmaticStreamSerializationAllowed = 1;
  cfg.attrs = at; cfg.numAttrs = 1;
  cudaLaunchKernelEx(&cfg, k_ffn, (__nv_bfloat16*)d_out);
}
```

```cpp
#include <cuda_runtime.h>
#include <cuda_bf16.h>
#include <stdint.h>

constexpr int LSEQ = 2048, DM = 448;

__device__ uint4    g_himg[16 * 114688 / 16];
__device__ uint4    g_cimg[8 * 2 * 224];
__device__ uint32_t g_stat2[LSEQ];
__device__ uint4    g_part[128 * 7 * 896];
__device__ uint4    g_wimg[8 * 602112 / 16];
__device__ uint4    g_ux[DM * 128 * 4];
__device__ unsigned g_cnt1, g_cnt2, g_cnt3;
__device__ uint32_t g_flag[128 * 64];

#define TR(k, i) do {} while (0)
__device__ __forceinline__ uint32_t s2u(const void* p) { return (uint32_t)__cvta_generic_to_shared(p); }
__device__ __forceinline__ void mbar_init(uint32_t b, int c) { asm volatile("mbarrier.init.shared::cta.b64 [%0], %1;" ::"r"(b), "r"(c)); }
__device__ __forceinline__ void mbar_expect(uint32_t b, int bytes) { asm volatile("mbarrier.arrive.expect_tx.shared::cta.b64 _, [%0], %1;" ::"r"(b), "r"(bytes) : "memory"); }
__device__ __forceinline__ void mbar_arrive(uint32_t b) { asm volatile("mbarrier.arrive.shared::cta.b64 _, [%0];" ::"r"(b) : "memory"); }
__device__ __forceinline__ void mbar_wait(uint32_t b, int ph) {
  asm volatile("{\n.reg .pred p;\n.reg .b32 n;\nmov.b32 n, 0;\nLW:\nmbarrier.try_wait.parity.shared::cta.b64 p, [%0], %1;\n@p bra LD;\n"
               "add.u32 n, n, 1;\nsetp.lt.u32 p, n, 4000000;\n@p bra LW;\ntrap;\nLD:\n}" ::"r"(b), "r"(ph) : "memory");
}
__device__ __forceinline__ bool mbar_test(uint32_t b, int ph) {
  uint32_t ok;
  asm volatile("{\n.reg .pred p;\nmbarrier.test_wait.parity.shared::cta.b64 p, [%1], %2;\nselp.u32 %0, 1, 0, p;\n}" : "=r"(ok) : "r"(b), "r"(ph) : "memory");
  return ok;
}
__device__ __forceinline__ void wg_fence() { asm volatile("wgmma.fence.sync.aligned;" ::: "memory"); }
__device__ __forceinline__ void wg_commit() { asm volatile("wgmma.commit_group.sync.aligned;" ::: "memory"); }
template <int N> __device__ __forceinline__ void wg_wait() { asm volatile("wgmma.wait_group.sync.aligned %0;" ::"n"(N) : "memory"); }
template <int N> __device__ __forceinline__ void reg_fence(float (&a)[N]) {
#pragma unroll
  for (int i = 0; i < N; i++) asm volatile("" : "+f"(a[i])::"memory");
}
__device__ __forceinline__ uint32_t pack_bf16(float lo, float hi) {
  uint32_t r; asm("cvt.rn.bf16x2.f32 %0, %1, %2;" : "=r"(r) : "f"(hi), "f"(lo)); return r;
}
__device__ __forceinline__ float bf_lo(uint32_t v) { return __uint_as_float(v << 16); }
__device__ __forceinline__ float bf_hi(uint32_t v) { return __uint_as_float(v & 0xFFFF0000u); }
__device__ __forceinline__ float rbf(float x) { return __bfloat162float(__float2bfloat16_rn(x)); }
__device__ __forceinline__ uint32_t hmul2_bf(uint32_t a, uint32_t b) { uint32_t r; asm("mul.rn.bf16x2 %0, %1, %2;" : "=r"(r) : "r"(a), "r"(b)); return r; }
__device__ __forceinline__ uint32_t hadd2_bf(uint32_t a, uint32_t b) { uint32_t r; asm("add.rn.bf16x2 %0, %1, %2;" : "=r"(r) : "r"(a), "r"(b)); return r; }
__device__ __forceinline__ void bulk_ld(uint32_t dst, const void* src, int bytes, uint32_t bar) {
  asm volatile("cp.async.bulk.shared::cluster.global.mbarrier::complete_tx::bytes [%0], [%1], %2, [%3];"
               ::"r"(dst), "l"(src), "r"(bytes), "r"(bar) : "memory");
}

__device__ __forceinline__ void bulk_ld_mc(uint32_t dst, const void* src, int bytes, uint32_t bar) {
  asm volatile("cp.async.bulk.shared::cluster.global.mbarrier::complete_tx::bytes.multicast::cluster [%0], [%1], %2, [%3], %4;"
               ::"r"(dst), "l"(src), "r"(bytes), "r"(bar), "h"((uint16_t)3) : "memory");
}
template <int AOFF, uint32_t AHI, int BOFF, uint32_t BHI, int ACC>
__device__ __forceinline__ void wgmma_ss224(float (&d)[112], uint32_t alo, uint32_t blo) {
  asm volatile("{\n.reg .pred p;\n.reg .b32 la, lb;\n.reg .b64 ad, bd;\nsetp.ne.b32 p, %118, 0;\n"
    "add.u32 la, %112, %114;\nmov.b64 ad, {la, %115};\nadd.u32 lb, %113, %116;\nmov.b64 bd, {lb, %117};\n"
    "wgmma.mma_async.sync.aligned.m64n224k16.f32.bf16.bf16 {%0,%1,%2,%3,%4,%5,%6,%7,%8,%9,%10,%11,%12,%13,%14,%15,%16,%17,%18,%19,%20,%21,%22,%23,%24,%25,%26,%27,%28,%29,%30,%31,%32,%33,%34,%35,%36,%37,%38,%39,%40,%41,%42,%43,%44,%45,%46,%47,%48,%49,%50,%51,%52,%53,%54,%55,%56,%57,%58,%59,%60,%61,%62,%63,%64,%65,%66,%67,%68,%69,%70,%71,%72,%73,%74,%75,%76,%77,%78,%79,%80,%81,%82,%83,%84,%85,%86,%87,%88,%89,%90,%91,%92,%93,%94,%95,%96,%97,%98,%99,%100,%101,%102,%103,%104,%105,%106,%107,%108,%109,%110,%111}, ad, bd, p, 1, 1, 1, 1;\n}\n"
    : "+f"(d[0]),"+f"(d[1]),"+f"(d[2]),"+f"(d[3]),"+f"(d[4]),"+f"(d[5]),"+f"(d[6]),"+f"(d[7]),"+f"(d[8]),"+f"(d[9]),"+f"(d[10]),"+f"(d[11]),"+f"(d[12]),"+f"(d[13]),"+f"(d[14]),"+f"(d[15]),"+f"(d[16]),"+f"(d[17]),"+f"(d[18]),"+f"(d[19]),"+f"(d[20]),"+f"(d[21]),"+f"(d[22]),"+f"(d[23]),"+f"(d[24]),"+f"(d[25]),"+f"(d[26]),"+f"(d[27]),"+f"(d[28]),"+f"(d[29]),"+f"(d[30]),"+f"(d[31]),"+f"(d[32]),"+f"(d[33]),"+f"(d[34]),"+f"(d[35]),"+f"(d[36]),"+f"(d[37]),"+f"(d[38]),"+f"(d[39]),"+f"(d[40]),"+f"(d[41]),"+f"(d[42]),"+f"(d[43]),"+f"(d[44]),"+f"(d[45]),"+f"(d[46]),"+f"(d[47]),"+f"(d[48]),"+f"(d[49]),"+f"(d[50]),"+f"(d[51]),"+f"(d[52]),"+f"(d[53]),"+f"(d[54]),"+f"(d[55]),"+f"(d[56]),"+f"(d[57]),"+f"(d[58]),"+f"(d[59]),"+f"(d[60]),"+f"(d[61]),"+f"(d[62]),"+f"(d[63]),"+f"(d[64]),"+f"(d[65]),"+f"(d[66]),"+f"(d[67]),"+f"(d[68]),"+f"(d[69]),"+f"(d[70]),"+f"(d[71]),"+f"(d[72]),"+f"(d[73]),"+f"(d[74]),"+f"(d[75]),"+f"(d[76]),"+f"(d[77]),"+f"(d[78]),"+f"(d[79]),"+f"(d[80]),"+f"(d[81]),"+f"(d[82]),"+f"(d[83]),"+f"(d[84]),"+f"(d[85]),"+f"(d[86]),"+f"(d[87]),"+f"(d[88]),"+f"(d[89]),"+f"(d[90]),"+f"(d[91]),"+f"(d[92]),"+f"(d[93]),"+f"(d[94]),"+f"(d[95]),"+f"(d[96]),"+f"(d[97]),"+f"(d[98]),"+f"(d[99]),"+f"(d[100]),"+f"(d[101]),"+f"(d[102]),"+f"(d[103]),"+f"(d[104]),"+f"(d[105]),"+f"(d[106]),"+f"(d[107]),"+f"(d[108]),"+f"(d[109]),"+f"(d[110]),"+f"(d[111])
    : "r"(alo), "r"(blo), "n"(AOFF), "n"(AHI), "n"(BOFF), "n"(BHI), "n"(ACC));
}
template <int AOFF, uint32_t AHI, int BOFF, uint32_t BHI, int ACC>
__device__ __forceinline__ void wgmma_ss232(float (&d)[116], uint32_t alo, uint32_t blo) {
  asm volatile("{\n.reg .pred p;\n.reg .b32 la, lb;\n.reg .b64 ad, bd;\nsetp.ne.b32 p, %122, 0;\n"
    "add.u32 la, %116, %118;\nmov.b64 ad, {la, %119};\nadd.u32 lb, %117, %120;\nmov.b64 bd, {lb, %121};\n"
    "wgmma.mma_async.sync.aligned.m64n232k16.f32.bf16.bf16 {%0,%1,%2,%3,%4,%5,%6,%7,%8,%9,%10,%11,%12,%13,%14,%15,%16,%17,%18,%19,%20,%21,%22,%23,%24,%25,%26,%27,%28,%29,%30,%31,%32,%33,%34,%35,%36,%37,%38,%39,%40,%41,%42,%43,%44,%45,%46,%47,%48,%49,%50,%51,%52,%53,%54,%55,%56,%57,%58,%59,%60,%61,%62,%63,%64,%65,%66,%67,%68,%69,%70,%71,%72,%73,%74,%75,%76,%77,%78,%79,%80,%81,%82,%83,%84,%85,%86,%87,%88,%89,%90,%91,%92,%93,%94,%95,%96,%97,%98,%99,%100,%101,%102,%103,%104,%105,%106,%107,%108,%109,%110,%111,%112,%113,%114,%115}, ad, bd, p, 1, 1, 1, 1;\n}\n"
    : "+f"(d[0]),"+f"(d[1]),"+f"(d[2]),"+f"(d[3]),"+f"(d[4]),"+f"(d[5]),"+f"(d[6]),"+f"(d[7]),"+f"(d[8]),"+f"(d[9]),"+f"(d[10]),"+f"(d[11]),"+f"(d[12]),"+f"(d[13]),"+f"(d[14]),"+f"(d[15]),"+f"(d[16]),"+f"(d[17]),"+f"(d[18]),"+f"(d[19]),"+f"(d[20]),"+f"(d[21]),"+f"(d[22]),"+f"(d[23]),"+f"(d[24]),"+f"(d[25]),"+f"(d[26]),"+f"(d[27]),"+f"(d[28]),"+f"(d[29]),"+f"(d[30]),"+f"(d[31]),"+f"(d[32]),"+f"(d[33]),"+f"(d[34]),"+f"(d[35]),"+f"(d[36]),"+f"(d[37]),"+f"(d[38]),"+f"(d[39]),"+f"(d[40]),"+f"(d[41]),"+f"(d[42]),"+f"(d[43]),"+f"(d[44]),"+f"(d[45]),"+f"(d[46]),"+f"(d[47]),"+f"(d[48]),"+f"(d[49]),"+f"(d[50]),"+f"(d[51]),"+f"(d[52]),"+f"(d[53]),"+f"(d[54]),"+f"(d[55]),"+f"(d[56]),"+f"(d[57]),"+f"(d[58]),"+f"(d[59]),"+f"(d[60]),"+f"(d[61]),"+f"(d[62]),"+f"(d[63]),"+f"(d[64]),"+f"(d[65]),"+f"(d[66]),"+f"(d[67]),"+f"(d[68]),"+f"(d[69]),"+f"(d[70]),"+f"(d[71]),"+f"(d[72]),"+f"(d[73]),"+f"(d[74]),"+f"(d[75]),"+f"(d[76]),"+f"(d[77]),"+f"(d[78]),"+f"(d[79]),"+f"(d[80]),"+f"(d[81]),"+f"(d[82]),"+f"(d[83]),"+f"(d[84]),"+f"(d[85]),"+f"(d[86]),"+f"(d[87]),"+f"(d[88]),"+f"(d[89]),"+f"(d[90]),"+f"(d[91]),"+f"(d[92]),"+f"(d[93]),"+f"(d[94]),"+f"(d[95]),"+f"(d[96]),"+f"(d[97]),"+f"(d[98]),"+f"(d[99]),"+f"(d[100]),"+f"(d[101]),"+f"(d[102]),"+f"(d[103]),"+f"(d[104]),"+f"(d[105]),"+f"(d[106]),"+f"(d[107]),"+f"(d[108]),"+f"(d[109]),"+f"(d[110]),"+f"(d[111]),"+f"(d[112]),"+f"(d[113]),"+f"(d[114]),"+f"(d[115])
    : "r"(alo), "r"(blo), "n"(AOFF), "n"(AHI), "n"(BOFF), "n"(BHI), "n"(ACC));
}
template <int OFF, uint32_t BHI, int ACC>
__device__ __forceinline__ void wgmma_rs224(float (&d)[112], uint32_t a0, uint32_t a1, uint32_t a2, uint32_t a3, uint32_t blo) {
  asm volatile("{\n.reg .pred p;\n.reg .b32 l;\n.reg .b64 bd;\nsetp.ne.b32 p, %119, 0;\nadd.u32 l, %116, %117;\nmov.b64 bd, {l, %118};\n"
    "wgmma.mma_async.sync.aligned.m64n224k16.f32.bf16.bf16 {%0,%1,%2,%3,%4,%5,%6,%7,%8,%9,%10,%11,%12,%13,%14,%15,%16,%17,%18,%19,%20,%21,%22,%23,%24,%25,%26,%27,%28,%29,%30,%31,%32,%33,%34,%35,%36,%37,%38,%39,%40,%41,%42,%43,%44,%45,%46,%47,%48,%49,%50,%51,%52,%53,%54,%55,%56,%57,%58,%59,%60,%61,%62,%63,%64,%65,%66,%67,%68,%69,%70,%71,%72,%73,%74,%75,%76,%77,%78,%79,%80,%81,%82,%83,%84,%85,%86,%87,%88,%89,%90,%91,%92,%93,%94,%95,%96,%97,%98,%99,%100,%101,%102,%103,%104,%105,%106,%107,%108,%109,%110,%111}, {%112,%113,%114,%115}, bd, p, 1, 1, 1;\n}\n"
    : "+f"(d[0]),"+f"(d[1]),"+f"(d[2]),"+f"(d[3]),"+f"(d[4]),"+f"(d[5]),"+f"(d[6]),"+f"(d[7]),"+f"(d[8]),"+f"(d[9]),"+f"(d[10]),"+f"(d[11]),"+f"(d[12]),"+f"(d[13]),"+f"(d[14]),"+f"(d[15]),"+f"(d[16]),"+f"(d[17]),"+f"(d[18]),"+f"(d[19]),"+f"(d[20]),"+f"(d[21]),"+f"(d[22]),"+f"(d[23]),"+f"(d[24]),"+f"(d[25]),"+f"(d[26]),"+f"(d[27]),"+f"(d[28]),"+f"(d[29]),"+f"(d[30]),"+f"(d[31]),"+f"(d[32]),"+f"(d[33]),"+f"(d[34]),"+f"(d[35]),"+f"(d[36]),"+f"(d[37]),"+f"(d[38]),"+f"(d[39]),"+f"(d[40]),"+f"(d[41]),"+f"(d[42]),"+f"(d[43]),"+f"(d[44]),"+f"(d[45]),"+f"(d[46]),"+f"(d[47]),"+f"(d[48]),"+f"(d[49]),"+f"(d[50]),"+f"(d[51]),"+f"(d[52]),"+f"(d[53]),"+f"(d[54]),"+f"(d[55]),"+f"(d[56]),"+f"(d[57]),"+f"(d[58]),"+f"(d[59]),"+f"(d[60]),"+f"(d[61]),"+f"(d[62]),"+f"(d[63]),"+f"(d[64]),"+f"(d[65]),"+f"(d[66]),"+f"(d[67]),"+f"(d[68]),"+f"(d[69]),"+f"(d[70]),"+f"(d[71]),"+f"(d[72]),"+f"(d[73]),"+f"(d[74]),"+f"(d[75]),"+f"(d[76]),"+f"(d[77]),"+f"(d[78]),"+f"(d[79]),"+f"(d[80]),"+f"(d[81]),"+f"(d[82]),"+f"(d[83]),"+f"(d[84]),"+f"(d[85]),"+f"(d[86]),"+f"(d[87]),"+f"(d[88]),"+f"(d[89]),"+f"(d[90]),"+f"(d[91]),"+f"(d[92]),"+f"(d[93]),"+f"(d[94]),"+f"(d[95]),"+f"(d[96]),"+f"(d[97]),"+f"(d[98]),"+f"(d[99]),"+f"(d[100]),"+f"(d[101]),"+f"(d[102]),"+f"(d[103]),"+f"(d[104]),"+f"(d[105]),"+f"(d[106]),"+f"(d[107]),"+f"(d[108]),"+f"(d[109]),"+f"(d[110]),"+f"(d[111])
    : "r"(a0), "r"(a1), "r"(a2), "r"(a3), "r"(blo), "n"(OFF), "n"(BHI), "n"(ACC));
}
template <int OFF, uint32_t BHI, int ACC>
__device__ __forceinline__ void wgmma_rs56(float (&d)[28], uint32_t a0, uint32_t a1, uint32_t a2, uint32_t a3, uint32_t blo) {
  asm volatile("{\n.reg .pred p;\n.reg .b32 l;\n.reg .b64 bd;\nsetp.ne.b32 p, %35, 0;\nadd.u32 l, %32, %33;\nmov.b64 bd, {l, %34};\n"
    "wgmma.mma_async.sync.aligned.m64n56k16.f32.bf16.bf16 {%0,%1,%2,%3,%4,%5,%6,%7,%8,%9,%10,%11,%12,%13,%14,%15,%16,%17,%18,%19,%20,%21,%22,%23,%24,%25,%26,%27}, {%28,%29,%30,%31}, bd, p, 1, 1, 1;\n}\n"
    : "+f"(d[0]),"+f"(d[1]),"+f"(d[2]),"+f"(d[3]),"+f"(d[4]),"+f"(d[5]),"+f"(d[6]),"+f"(d[7]),"+f"(d[8]),"+f"(d[9]),"+f"(d[10]),"+f"(d[11]),"+f"(d[12]),"+f"(d[13]),"+f"(d[14]),"+f"(d[15]),"+f"(d[16]),"+f"(d[17]),"+f"(d[18]),"+f"(d[19]),"+f"(d[20]),"+f"(d[21]),"+f"(d[22]),"+f"(d[23]),"+f"(d[24]),"+f"(d[25]),"+f"(d[26]),"+f"(d[27])
    : "r"(a0), "r"(a1), "r"(a2), "r"(a3), "r"(blo), "n"(OFF), "n"(BHI), "n"(ACC));
}

__device__ __forceinline__ void st128(uint4* p, uint32_t a, uint32_t b, uint32_t c, uint32_t d) {
  asm volatile("{\n.reg .b128 v;\n.reg .b64 lo, hi;\nmov.b64 lo, {%1, %2};\nmov.b64 hi, {%3, %4};\nmov.b128 v, {lo, hi};\n"
               "st.relaxed.gpu.global.b128 [%0], v;\n}" ::"l"(p), "r"(a), "r"(b), "r"(c), "r"(d) : "memory");
}
__device__ __forceinline__ void ld128(const uint4* p, uint32_t* r) {
  asm volatile("{\n.reg .b128 v;\n.reg .b64 lo, hi;\nld.relaxed.gpu.global.b128 v, [%4];\nmov.b128 {lo, hi}, v;\n"
               "mov.b64 {%0, %1}, lo;\nmov.b64 {%2, %3}, hi;\n}" : "=r"(r[0]), "=r"(r[1]), "=r"(r[2]), "=r"(r[3]) : "l"(p) : "memory");
}

template <int OFF, uint32_t BHI, int ACC>
__device__ __forceinline__ void wgmma_rs32(float (&d)[16], uint32_t a0, uint32_t a1, uint32_t a2, uint32_t a3, uint32_t blo) {
  asm volatile("{\n.reg .pred p;\n.reg .b32 l;\n.reg .b64 bd;\nsetp.ne.b32 p, %23, 0;\nadd.u32 l, %20, %21;\nmov.b64 bd, {l, %22};\n"
    "wgmma.mma_async.sync.aligned.m64n32k16.f32.bf16.bf16 {%0,%1,%2,%3,%4,%5,%6,%7,%8,%9,%10,%11,%12,%13,%14,%15}, {%16,%17,%18,%19}, bd, p, 1, 1, 0;\n}\n"
    : "+f"(d[0]),"+f"(d[1]),"+f"(d[2]),"+f"(d[3]),"+f"(d[4]),"+f"(d[5]),"+f"(d[6]),"+f"(d[7]),"+f"(d[8]),"+f"(d[9]),"+f"(d[10]),"+f"(d[11]),"+f"(d[12]),"+f"(d[13]),"+f"(d[14]),"+f"(d[15])
    : "r"(a0), "r"(a1), "r"(a2), "r"(a3), "r"(blo), "n"(OFF), "n"(BHI), "n"(ACC));
}
template <int OFF, uint32_t BHI, int ACC>
__device__ __forceinline__ void wgmma_rs24(float (&d)[12], uint32_t a0, uint32_t a1, uint32_t a2, uint32_t a3, uint32_t blo) {
  asm volatile("{\n.reg .pred p;\n.reg .b32 l;\n.reg .b64 bd;\nsetp.ne.b32 p, %19, 0;\nadd.u32 l, %16, %17;\nmov.b64 bd, {l, %18};\n"
    "wgmma.mma_async.sync.aligned.m64n24k16.f32.bf16.bf16 {%0,%1,%2,%3,%4,%5,%6,%7,%8,%9,%10,%11}, {%12,%13,%14,%15}, bd, p, 1, 1, 1;\n}\n"
    : "+f"(d[0]),"+f"(d[1]),"+f"(d[2]),"+f"(d[3]),"+f"(d[4]),"+f"(d[5]),"+f"(d[6]),"+f"(d[7]),"+f"(d[8]),"+f"(d[9]),"+f"(d[10]),"+f"(d[11])
    : "r"(a0), "r"(a1), "r"(a2), "r"(a3), "r"(blo), "n"(OFF), "n"(BHI), "n"(ACC));
}
template <int OFF, uint32_t BHI, int ACC>
__device__ __forceinline__ void wgmma_rs16(float (&d)[8], uint32_t a0, uint32_t a1, uint32_t a2, uint32_t a3, uint32_t blo) {
  asm volatile("{\n.reg .pred p;\n.reg .b32 l;\n.reg .b64 bd;\nsetp.ne.b32 p, %15, 0;\nadd.u32 l, %12, %13;\nmov.b64 bd, {l, %14};\n"
    "wgmma.mma_async.sync.aligned.m64n16k16.f32.bf16.bf16 {%0,%1,%2,%3,%4,%5,%6,%7}, {%8,%9,%10,%11}, bd, p, 1, 1, 1;\n}\n"
    : "+f"(d[0]),"+f"(d[1]),"+f"(d[2]),"+f"(d[3]),"+f"(d[4]),"+f"(d[5]),"+f"(d[6]),"+f"(d[7])
    : "r"(a0), "r"(a1), "r"(a2), "r"(a3), "r"(blo), "n"(OFF), "n"(BHI), "n"(ACC));
}

constexpr int A_R1 = 0;
constexpr int A_R2A = A_R1 + 2624, A_R2B = A_R2A + 768, A_R3A = A_R2B + 768, A_R3B = A_R3A + 528;
constexpr int A_K1024 = A_R3B + 528;
constexpr int A_W5 = A_K1024 + 16;
constexpr int A_W3 = A_W5 + 4096;
constexpr int A_W9 = A_W3 + 4112;
constexpr int A_W7 = A_W9 + 2048;
constexpr int A_V  = A_W7 + 2048;
constexpr int A_UB = A_V + 2048;
constexpr int A_STG = A_UB + 5248;
constexpr int A_Y2 = A_STG, A_Y3 = A_Y2 + 6528, A_YB = A_Y3 + 4352;
constexpr int A_REC = A_STG + 4 * 4352;
constexpr int A_CH = A_REC + 8192;
static_assert(A_W5 % 16 == 0 && A_UB % 16 == 0 && A_CH % 16 == 0 && A_YB + 4096 <= A_REC, "layout");

struct cf { float x, y; };
__device__ __forceinline__ cf cmul(cf a, cf b) { cf r; r.x = fmaf(a.x, b.x, -a.y * b.y); r.y = fmaf(a.x, b.y, a.y * b.x); return r; }
__device__ __forceinline__ cf cexp_l(float lr, float li, float l) {
  float mag; asm("ex2.approx.ftz.f32 %0, %1;" : "=f"(mag) : "f"((lr * l) * 1.4426950408889634f));
  const float th = li * l;
  const float k = (fmaf(th, 0.15915494f, 12582912.f)) - 12582912.f;
  float ph = fmaf(th, 0.15915494f, -k);
  ph = fmaf(th, 6.4206383e-9f, ph) * 6.2831853f;
  cf r; r.x = mag * __cosf(ph); r.y = mag * __sinf(ph); return r;
}
__device__ __forceinline__ void sts16(uint32_t a, uint32_t v) { asm volatile("st.shared.u16 [%0], %1;" ::"r"(a), "h"((uint16_t)v) : "memory"); }
__device__ __forceinline__ void sts32(uint32_t a, uint32_t v) { asm volatile("st.shared.u32 [%0], %1;" ::"r"(a), "r"(v) : "memory"); }
__device__ __forceinline__ void sts64(uint32_t a, uint32_t v0, uint32_t v1) { asm volatile("st.shared.v2.u32 [%0], {%1, %2};" ::"r"(a), "r"(v0), "r"(v1) : "memory"); }
__device__ __forceinline__ void sts128(uint32_t a, uint32_t v0, uint32_t v1, uint32_t v2, uint32_t v3) {
  asm volatile("st.shared.v4.u32 [%0], {%1, %2, %3, %4};" ::"r"(a), "r"(v0), "r"(v1), "r"(v2), "r"(v3) : "memory");
}
__device__ __forceinline__ uint32_t lds32(uint32_t a) { uint32_t v; asm volatile("ld.shared.u32 %0, [%1];" : "=r"(v) : "r"(a) : "memory"); return v; }
__device__ __forceinline__ uint4 lds128(uint32_t a) {
  uint4 v; asm volatile("ld.shared.v4.u32 {%0, %1, %2, %3}, [%4];" : "=r"(v.x), "=r"(v.y), "=r"(v.z), "=r"(v.w) : "r"(a) : "memory"); return v;
}
__device__ __forceinline__ void ldsm4(uint32_t* r, uint32_t a) {
  asm volatile("ldmatrix.sync.aligned.m8n8.x4.shared.b16 {%0,%1,%2,%3}, [%4];" : "=r"(r[0]), "=r"(r[1]), "=r"(r[2]), "=r"(r[3]) : "r"(a) : "memory");
}
__device__ __forceinline__ void mma16816(float* d, const uint32_t* a, uint32_t b0, uint32_t b1) {
  asm volatile("mma.sync.aligned.m16n8k16.row.col.f32.bf16.bf16.f32 {%0,%1,%2,%3}, {%4,%5,%6,%7}, {%8,%9}, {%0,%1,%2,%3};"
               : "+f"(d[0]), "+f"(d[1]), "+f"(d[2]), "+f"(d[3]) : "r"(a[0]), "r"(a[1]), "r"(a[2]), "r"(a[3]), "r"(b0), "r"(b1));
}
__device__ __forceinline__ uint32_t hsub2_bf(uint32_t a, uint32_t b) { uint32_t r; asm("sub.rn.bf16x2 %0, %1, %2;" : "=r"(r) : "r"(a), "r"(b)); return r; }
__device__ __forceinline__ void bar_sync(int id, int n) { asm volatile("bar.sync %0, %1;" ::"r"(id), "r"(n) : "memory"); }

template <int S> struct F1B { static constexpr int c = S / 4 + ((S & 3) == 3 ? 0 : 0), cc = (16 * S) / 64, ks = (64 * cc - (16 * S - 48)) / 16, off = (A_UB + 2 * ks * 656 + (9 - cc) * 16) / 16; };

template <int NS>
__device__ __forceinline__ void load_quads(uint32_t* q, uint32_t addr) {
#pragma unroll
  for (int i = 0; i < NS; i++) {
    q[4 * i] = lds32(addr + i * 64); q[4 * i + 1] = lds32(addr + i * 64 + 32);
    q[4 * i + 2] = i ? q[4 * i - 3] : lds32(addr - 32);
    q[4 * i + 3] = q[4 * i];
  }
#pragma unroll
  for (int i = 0; i < 4 * NS; i++) asm volatile("" : "+r"(q[i]));
}
template <int S0, int NS>
__device__ __forceinline__ void f1_steps(float (&acc)[16], const uint32_t* a, uint32_t blo) {
  if constexpr (NS > 0) {
    wgmma_rs32<F1B<S0>::off, 8, S0 != 0>(acc, a[0], a[1], a[2], a[3], blo);
    f1_steps<S0 + 1, NS - 1>(acc, a + 4, blo);
  }
}
template <int S0, int NS, int BASE, int FIRST>
__device__ __forceinline__ void s2_steps(float (&acc)[12], const uint32_t* a, uint32_t blo) {
  if constexpr (NS > 0) {
    wgmma_rs24<BASE / 16 + (112 - 16 * S0), 64, !(FIRST && S0 == 0)>(acc, a[0], a[1], a[2], a[3], blo);
    s2_steps<S0 + 1, NS - 1, BASE, FIRST>(acc, a + 4, blo);
  }
}
template <int S0, int NS, int BASE, int FIRST>
__device__ __forceinline__ void s3_steps(float (&acc)[8], const uint32_t* a, uint32_t blo) {
  if constexpr (NS > 0) {
    wgmma_rs16<BASE / 16 + (48 - 16 * S0), 64, !(FIRST && S0 == 0)>(acc, a[0], a[1], a[2], a[3], blo);
    s3_steps<S0 + 1, NS - 1, BASE, FIRST>(acc, a + 4, blo);
  }
}

__device__ __forceinline__ void phase_a(
        unsigned char* sm, const uint32_t bar_rec, const uint32_t ep_addr,
        const __nv_bfloat16* __restrict__ x, const uint32_t* __restrict__ are, const uint32_t* __restrict__ aim,
        const uint32_t* __restrict__ bre, const uint32_t* __restrict__ bim, const uint32_t* __restrict__ cre,
        const uint32_t* __restrict__ cim, const unsigned short* __restrict__ logdt, const unsigned short* __restrict__ dskip,
        const uint4* __restrict__ wgate, const uint4* __restrict__ wup, const uint4* __restrict__ wdown) {
  const uint32_t sb = s2u(sm);
  const int tid = threadIdx.x, wg = tid >> 7, warp = tid >> 5, lane = tid & 31, wq = warp & 3, t128 = tid & 127;
  const int blk = blockIdx.x;
  const bool conv = blk < 112;

  uint2 xr[4];
  {
    const uint2* p = (const uint2*)(x + (size_t)(blk * 16 + warp) * DM);
    xr[0] = __ldg(p + lane); xr[1] = __ldg(p + 32 + lane); xr[2] = __ldg(p + 64 + lane);
    xr[3] = lane < 16 ? __ldg(p + 96 + lane) : make_uint2(0, 0);
  }
  const int ch = conv ? blk * 4 + wg : 0;
  const uint32_t cb = sb + wg * A_CH;
  uint32_t prm[6];
  {
    const int i = ch * 128 + t128;
    prm[0] = __ldg(are + i); prm[1] = __ldg(aim + i); prm[2] = __ldg(bre + i); prm[3] = __ldg(bim + i); prm[4] = __ldg(cre + i); prm[5] = __ldg(cim + i);
  }
  const uint32_t ldt = __ldg(logdt + ch);
  uint32_t cnt0 = 0;
  if (tid == 0) cnt0 = __ldcg(&g_cnt1);
#pragma unroll
  for (int i = 0; i < 4; i++) if (i < 3 || t128 < (A_W5 + 1024) / 16 - 384) sts128(cb + (i * 128 + t128) * 16, 0, 0, 0, 0);
  if (t128 < 65) sts128(cb + (t128 < 64 ? A_W3 + t128 * 16 : A_W9), 0, 0, 0, 0);
  if (t128 < 72) sts128(cb + A_UB + (t128 / 9) * 656 + (t128 % 9) * 16, 0, 0, 0, 0);
  {
    float s = 0.f, q = 0.f;
#pragma unroll
    for (int i = 0; i < 4; i++) {
      const float a = bf_lo(xr[i].x), b = bf_hi(xr[i].x), c = bf_lo(xr[i].y), d = bf_hi(xr[i].y);
      s += (a + b) + (c + d);
      q = fmaf(a, a, q); q = fmaf(b, b, q); q = fmaf(c, c, q); q = fmaf(d, d, q);
    }
#pragma unroll
    for (int o = 16; o; o >>= 1) { s += __shfl_xor_sync(~0u, s, o); q += __shfl_xor_sync(~0u, q, o); }
    const float mean = s * (1.f / DM);
    const float var = fmaxf(fmaf(-mean, mean, q * (1.f / DM)), 0.f);
    const float rs = __frcp_rn(rbf(__fsqrt_rn(rbf(rbf(var) + 1e-5f))));
    const uint32_t mm = pack_bf16(mean, mean);
    const uint32_t tu = sb + A_REC + (warp >> 3) * A_CH + (warp & 7) * 912 + lane * 8, tx = tu + 2 * A_CH;
#pragma unroll
    for (int i = 0; i < 4; i++) {
      if (i < 3 || lane < 16) {
        const uint32_t d0 = hsub2_bf(xr[i].x, mm), d1 = hsub2_bf(xr[i].y, mm);
        sts64(tu + i * 256, pack_bf16(bf_lo(d0) * rs, bf_hi(d0) * rs), pack_bf16(bf_lo(d1) * rs, bf_hi(d1) * rs));
        sts64(tx + i * 256, xr[i].x, xr[i].y);
      }
    }
  }
  if (tid == 0) sts32(ep_addr, (cnt0 >> 7) + 1u);
  if (tid == 320) TR(0, 1);
  auto publish_rows = [&]() {
    bar_sync(5, 512);
    uint4* dst = g_ux + ((size_t)(warp * 8 + (lane >> 2)) * 128 + blk) * 4 + ((lane ^ (blk >> 1)) & 3);
#pragma unroll
    for (int i = 0; i < 4; i++) {
      if (i < 3 || warp < 8) {
        uint32_t r[4];
        asm volatile("ldmatrix.sync.aligned.m8n8.x4.trans.shared.b16 {%0,%1,%2,%3}, [%4];" : "=r"(r[0]), "=r"(r[1]), "=r"(r[2]), "=r"(r[3])
                     : "r"(sb + A_REC + (lane >> 3) * A_CH + (lane & 7) * 912 + (warp + 16 * i) * 16) : "memory");
        dst[i * 65536] = make_uint4(r[0], r[1], r[2], r[3]);
      }
    }
    if (warp != 0) asm volatile("bar.arrive 6, 512;" ::: "memory");
  };
  auto release_rows = [&]() {
    if (warp == 0) {
      bar_sync(6, 512);
      if (lane == 0) { asm volatile("red.release.gpu.global.add.u32 [%0], 1;" ::"l"(&g_cnt1) : "memory"); TR(0, 8); }
      __syncwarp();
    }
  };

  if (!conv) {
    publish_rows();
    release_rows();
    const int a = blk - 112, mat = a >> 3, j = a & 7;
    float s[8];
#pragma unroll
    for (int k = 0; k < 8; k++) s[k] = 0.f;
    if (lane < 28) {
      const uint4* src = (mat ? wup : wgate) + j * 28 + lane + (size_t)warp * 224;
#pragma unroll
      for (int hb = 0; hb < 2; hb++) {
        uint4 v[14];
#pragma unroll
        for (int r = 0; r < 14; r++) v[r] = __ldg(src + (size_t)(hb * 14 + r) * 16 * 224);
#pragma unroll
        for (int r = 0; r < 14; r++) {
          s[0] += bf_lo(v[r].x); s[1] += bf_hi(v[r].x); s[2] += bf_lo(v[r].y); s[3] += bf_hi(v[r].y);
          s[4] += bf_lo(v[r].z); s[5] += bf_hi(v[r].z); s[6] += bf_lo(v[r].w); s[7] += bf_hi(v[r].w);
        }
      }
      float4* red = (float4*)(sm + A_STG + warp * 896 + lane * 32);
      red[0] = make_float4(s[0], s[1], s[2], s[3]); red[1] = make_float4(s[4], s[5], s[6], s[7]);
    }
    bar_sync(5, 512);
    if (tid < 224) {
      float t = 0.f;
#pragma unroll
      for (int w = 0; w < 16; w++) t += *(const float*)(sm + A_STG + w * 896 + tid * 4);
      const float hi = rbf(t), mid = rbf(t - hi), lo = rbf(t - hi - mid);
      const int q = tid / 112, n = tid % 112 + 112 * mat;
      __nv_bfloat16* dst = (__nv_bfloat16*)(g_cimg + (j * 2 + q) * 224 + (n >> 3) * 8) + (n & 7);
      dst[0] = __float2bfloat16_rn(hi); dst[8] = __float2bfloat16_rn(mid); dst[16] = __float2bfloat16_rn(lo);
#pragma unroll
      for (int k = 3; k < 8; k++) dst[8 * k] = __float2bfloat16_rn(0.f);
    }
    if (tid == 320) TR(0, 10);
    return;
  }

  const int g = lane >> 2, t = lane & 3;
  const int wr = (wq + wg) & 3;
  uint4 wv[6];
  auto w_src = [&](int i) -> const uint4* {
    if (i < 4) return (blk < 56 ? wgate : wup) + (blk % 56) * 4 + (lane & 3) + (size_t)(i * 128 + warp * 8 + (lane >> 2)) * 224;
    const int it = warp + 16 * (i - 4);
    return wdown + (size_t)(blk * 16 + (it / 14) * 8 + (lane >> 2)) * 56 + (it % 14) * 4 + (lane & 3);
  };
  auto w_on = [&](int i) { return i == 3 ? warp < 8 : i == 5 ? warp < 12 : true; };
  {
    const uint32_t stg = cb + A_STG + wq * 4352;
    const float dt = rbf(expf(__uint_as_float(ldt << 16)));
    float lr[2], li[2];
    cf bq[2], b0[2], b4[2];
    uint32_t bf[48];
#pragma unroll
    for (int m = 0; m < 2; m++) {
      lr[m] = dt * (m ? bf_hi(prm[0]) : bf_lo(prm[0]));
      li[m] = dt * (m ? bf_hi(prm[1]) : bf_lo(prm[1]));
    }
    {
      cf b[2], z[2];
#pragma unroll
      for (int m = 0; m < 2; m++) {
        cf db, c;
        db.x = dt * (m ? bf_hi(prm[2]) : bf_lo(prm[2])); db.y = -dt * (m ? bf_hi(prm[3]) : bf_lo(prm[3]));
        c.x = m ? bf_hi(prm[4]) : bf_lo(prm[4]); c.y = -(m ? bf_hi(prm[5]) : bf_lo(prm[5]));
        b[m] = cmul(c, db);
        z[m] = cexp_l(lr[m], -li[m], 1.f);
        bq[m] = cexp_l(lr[m], -li[m], 256.f);
      }
#pragma unroll
      for (int i = 0; i < 8; i++) {
        sts64(stg + i * 272 + lane * 8, pack_bf16(b[0].x, b[0].y), pack_bf16(b[1].x, b[1].y));
        if (!(i & 1)) {
          cf e0 = cmul(b[0], bq[0]), e1 = cmul(b[1], bq[1]);
          sts64(stg + (8 + i / 2) * 272 + lane * 8, pack_bf16(e0.x, e0.y), pack_bf16(e1.x, e1.y));
          if (i == 0) { b0[0] = e0; b0[1] = e1; }
          if (i == 4) { b4[0] = e0; b4[1] = e1; }
        }
        if (i < 7) { b[0] = cmul(b[0], z[0]); b[1] = cmul(b[1], z[1]); }
        if (i == 1) publish_rows();
      }
#pragma unroll
      for (int i = 0; i < 7; i++) {
        b0[0] = cmul(b0[0], bq[0]); b0[1] = cmul(b0[1], bq[1]);
        sts64(stg + (i < 2 ? 12 + 2 * i : i - 2) * 272 + lane * 8, pack_bf16(b0[0].x, b0[0].y), pack_bf16(b0[1].x, b0[1].y));
        if (i < 2) {
          b4[0] = cmul(b4[0], bq[0]); b4[1] = cmul(b4[1], bq[1]);
          sts64(stg + (13 + 2 * i) * 272 + lane * 8, pack_bf16(b4[0].x, b4[0].y), pack_bf16(b4[1].x, b4[1].y));
        }
        if (i == 1) {
          __syncwarp();
#pragma unroll
          for (int n = 0; n < 2; n++)
#pragma unroll
            for (int k2 = 0; k2 < 4; k2++) ldsm4(bf + n * 16 + k2 * 4, stg + (n * 8 + (lane & 7)) * 272 + k2 * 64 + (lane >> 3) * 16);
          __syncwarp();
        }
      }
    }
    __syncwarp();
#pragma unroll
    for (int k2 = 0; k2 < 4; k2++) ldsm4(bf + 32 + k2 * 4, stg + (lane & 7) * 272 + k2 * 64 + (lane >> 3) * 16);
    release_rows();
    if (!(lane & 1)) {
#pragma unroll
      for (int i = 0; i < 6; i++) if (w_on(i)) asm volatile("prefetch.global.L2 [%0];" ::"l"(w_src(i)));
    }
    if (tid == 320) TR(0, 16);
    float c[6][4];
#pragma unroll
    for (int i = 0; i < 6; i++) { c[i][0] = 0.f; c[i][1] = 0.f; c[i][2] = 0.f; c[i][3] = 0.f; }
    cf p[2], v[2];
    p[0] = cexp_l(lr[0], li[0], 8.f); p[1] = cexp_l(lr[1], li[1], 8.f);
    v[0].x = 1.f; v[0].y = 0.f; v[1] = v[0];
#pragma unroll
    for (int mt = 0; mt < 2; mt++) {
      __syncwarp();
#pragma unroll
      for (int i = 0; i < 16; i++) {
        sts64(stg + i * 272 + lane * 8, pack_bf16(v[0].x, v[0].y), pack_bf16(v[1].x, v[1].y));
        if (mt == 0 && i == 0) { v[0] = p[0]; v[1] = p[1]; }
        else if (mt == 0 || i < 15) { v[0] = cmul(v[0], p[0]); v[1] = cmul(v[1], p[1]); }
      }
      __syncwarp();
      if (mt == 1 && tid == 160) {
        const uint32_t tgt = lds32(ep_addr) * 128u;
        uint32_t cv; int it = 0;
        do { asm volatile("ld.acquire.gpu.global.u32 %0, [%1];" : "=r"(cv) : "l"(&g_cnt1) : "memory"); } while ((int)(cv - tgt) < 0 && ++it < 200000);
        asm volatile("fence.proxy.async;" ::: "memory");
        TR(0, 9);
        mbar_expect(bar_rec, 32768);
        for (int c2 = 0; c2 < 4; c2++) bulk_ld(sb + c2 * A_CH + A_REC, g_ux + (size_t)(blk * 4 + c2) * 512, 8192, bar_rec);
      }
#pragma unroll
      for (int ks = 0; ks < 8; ks++) {
        uint32_t a[4];
        ldsm4(a, stg + (lane & 15) * 272 + ks * 32 + (lane >> 4) * 16);
#pragma unroll
        for (int n = 0; n < 3; n++) mma16816(c[n * 2 + mt], a, bf[n * 16 + ks * 2], bf[n * 16 + ks * 2 + 1]);
      }
    }
    __syncwarp();
#pragma unroll
    for (int i = 0; i < 6; i++)
      sts128(stg + i * 512 + lane * 16, __float_as_uint(c[i][0]), __float_as_uint(c[i][1]), __float_as_uint(c[i][2]), __float_as_uint(c[i][3]));
#pragma unroll
    for (int i = 0; i < 6; i++) if (w_on(i)) wv[i] = __ldg(w_src(i));
    bar_sync(1 + wg, 128);
    if (tid == 320) TR(0, 2);
#pragma unroll
    for (int rep = 0; rep < 2; rep++) {
      const int qd = rep ? 2 + wr : 3 - wr;
      if (rep == 0 || wr >= 2) {
        float s[4] = {0.f, 0.f, 0.f, 0.f};
#pragma unroll
        for (int w = 0; w < 4; w++) {
          uint4 u4 = lds128(cb + A_STG + w * 4352 + qd * 512 + lane * 16);
          s[0] += __uint_as_float(u4.x); s[1] += __uint_as_float(u4.y); s[2] += __uint_as_float(u4.z); s[3] += __uint_as_float(u4.w);
        }
#pragma unroll
        for (int hf = 0; hf < 2; hf++) {
          const int j = (qd & 1) * 16 + g + 8 * hf;
          const uint32_t pk = pack_bf16(s[2 * hf + 1], s[2 * hf]);
          const uint32_t v0 = pk >> 16, v1 = pk & 0xFFFFu, v00 = v0 * 0x10001u;
          if (rep == 1) {
            if (t < 2) {
#pragma unroll
              for (int e = 0; e < 2; e++) {
                const int lam = 128 + 32 * (2 * t + e) + j, mu = lam >> 1;
                const uint32_t val = e ? v1 : v0;
                uint32_t a = cb + ((lam & 1) ? A_R3B : A_R3A) + mu * 4;
                if (lam == 128) { a = cb + A_R2A + 128 * 4; sts32(cb + A_K1024, val << 16); }
                sts16(a, val); sts16(a + 6, val);
              }
            } else if (t == 2 && j == 0) { sts16(cb + A_R3A + 128 * 4, v0); }
          } else if (qd < 2) {
            const uint32_t a = cb + A_R1 + (62 + 8 * j + 2 * t) * 4;
            sts16(a, v0); sts32(a + 4, pk); sts16(a + 10, v1);
          } else if (t < 2) {
            const int L = 256 + 8 * j + 4 * t;
            const uint32_t a = cb + A_R1 + (62 + L) * 4;
            if (L > 256) { sts16(a - 4, v0); sts32(a, v00); } else sts16(a, v0);
            sts32(a + 4, v00); sts32(a + 8, pk); sts16(a + 14, v1);
          } else {
            const int mu = 64 + 32 * (t - 2) + j;
            if (mu == 64) {
              const uint32_t a = cb + A_R1 + (62 + 512) * 4;
              sts16(a - 4, v0); sts32(a, v00); sts32(a + 4, v00); sts32(a + 8, v00); sts16(a + 14, v0);
            } else { sts16(cb + A_R2A + mu * 4, v0); sts16(cb + A_R2A + mu * 4 + 6, v0); }
            sts16(cb + A_R2B + mu * 4, v1); sts16(cb + A_R2B + mu * 4 + 6, v1);
          }
        }
      }
    }
  }
  {
    const int ngg = (blk % 56) * 4 + (lane & 3), j = ngg / 28, q = (ngg % 28) / 14, ng = ngg % 14 + (blk < 56 ? 0 : 14);
    uint4* dst = g_wimg + (size_t)j * 37632 + q * 14 * 896 + ng * 32 + (warp >> 2) * 896 + (warp & 3) * 8 + (lane >> 2);
#pragma unroll
    for (int i = 0; i < 4; i++) if (w_on(i)) dst[i * 4 * 896] = wv[i];
#pragma unroll
    for (int i = 4; i < 6; i++) {
      const int it = warp + 16 * (i - 4), n2 = (it % 14) * 4 + (lane & 3), k = (blk % 7) * 16 + (it / 14) * 8 + (lane >> 2);
      if (w_on(i)) g_wimg[(size_t)(blk / 14) * 37632 + 25088 + ((n2 / 7) * 2 + (blk / 7) % 2) * 784 + (n2 % 7) * 112 + k] = wv[i];
    }
  }
  if (tid == 320) TR(0, 3);

  const int bk = wr * 32 + lane;
  uint32_t xt[8], ud[8];
  {
    mbar_wait(bar_rec, 0);
    if (tid == 320) TR(0, 4);
    uint4 r[4];
#pragma unroll
    for (int i = 0; i < 4; i++) r[i] = lds128(cb + A_REC + bk * 64 + ((i ^ (bk >> 1)) & 3) * 16);
    const uint32_t ua = cb + A_UB + ((2 * bk) & 7) * 656 + ((bk >> 2) + 9) * 16;
    sts128(ua, r[0].x, r[1].x, r[2].x, r[3].x);
    sts128(ua + 656, r[0].y, r[1].y, r[2].y, r[3].y);
    if (bk <= 96) {
      const bool neg = bk == 96;
      const int bp = neg ? -1 : bk;
      uint32_t h[4];
      h[0] = lds32(cb + A_REC + ((bp - 1) & 127) * 64 + ((2 ^ ((bp - 1) >> 1)) & 3) * 16 + 4);
      h[1] = lds32(cb + A_REC + ((bp - 1) & 127) * 64 + ((3 ^ ((bp - 1) >> 1)) & 3) * 16 + 4);
      h[2] = lds32(cb + A_REC + (bp + 1) * 64 + ((0 ^ ((bp + 1) >> 1)) & 3) * 16);
      h[3] = lds32(cb + A_REC + (bp + 1) * 64 + ((1 ^ ((bp + 1) >> 1)) & 3) * 16);
      if (bp <= 0) { h[0] = 0; h[1] = 0; }
      const uint32_t wd[12] = {h[0], h[1], neg ? 0 : r[0].x, neg ? 0 : r[1].x, neg ? 0 : r[2].x, neg ? 0 : r[3].x,
                               neg ? 0 : r[0].y, neg ? 0 : r[1].y, neg ? 0 : r[2].y, neg ? 0 : r[3].y, h[2], h[3]};
      float P[25];
      P[0] = 0.f;
#pragma unroll
      for (int i = 0; i < 12; i++) { P[2 * i + 1] = P[2 * i] + bf_lo(wd[i]); P[2 * i + 2] = P[2 * i + 1] + bf_hi(wd[i]); }
#define WIN(i, hw) (P[(i) + 5 + (hw)] - P[(i) + 4 - (hw)])
#define WPK(i, hw) pack_bf16(WIN(i, hw), WIN((i) + 1, hw))
      const int tp = 2 * bp;
      const uint32_t a3 = cb + A_W3 + (tp + 64) * 16 + 8, a5 = cb + A_W5 + (tp + 64) * 16;
      if (!neg) sts64(a3, WPK(0, 1), WPK(2, 1));
      if (!neg) sts128(a3 + 8, WPK(4, 1), WPK(6, 1), WPK(8, 1), WPK(10, 1));
      sts64(a3 + 24, WPK(12, 1), WPK(14, 1));
      sts128(a5, WPK(0, 2), WPK(2, 2), WPK(4, 2), WPK(6, 2));
      sts128(a5 + 16, WPK(8, 2), WPK(10, 2), WPK(12, 2), WPK(14, 2));
      if (bp < 64) {
        if (!neg) sts128(cb + A_W7 + 1024 + bp * 16, WPK(0, 3), WPK(2, 3), WPK(4, 3), WPK(6, 3));
        if (bp < 63) {
          sts128(cb + A_W7 + (bp + 1) * 16, WPK(8, 3), WPK(10, 3), WPK(12, 3), WPK(14, 3));
          sts128(cb + A_W9 + (bp + 1) * 16, WPK(0, 4), WPK(2, 4), WPK(4, 4), WPK(6, 4));
          sts128(cb + A_W9 + 1024 + (bp + 1) * 16, WPK(8, 4), WPK(10, 4), WPK(12, 4), WPK(14, 4));
        }
        if (!neg) {
#define VPK(i) pack_bf16(P[(i) + 2] - P[i], P[(i) + 3] - P[(i) + 1])
          sts128(cb + A_V + bp * 32, VPK(0), VPK(2), VPK(4), VPK(6));
          sts128(cb + A_V + bp * 32 + 16, VPK(8), VPK(10), VPK(12), VPK(14));
        }
      }
    }
  }
  asm volatile("fence.proxy.async.shared::cta;" ::: "memory");
  bar_sync(1 + wg, 128);
  if (tid == 320) TR(0, 5);

  {
    const uint32_t cbu = __shfl_sync(~0u, cb, 0);
    const uint32_t blo_k = ((cbu & 0x3FFFF) >> 4) | (41u << 16);
    const uint32_t blo_n = ((cbu & 0x3FFFF) >> 4) | (8u << 16);
    const uint32_t tb = cb + (16 * wq + g - 2 * t) * 4;
    float y1[16], y2[12], y3[8];
    const uint32_t dk16 = __ldg(dskip + ch);
    uint32_t qa[32], qb[32];
    const uint32_t t1 = tb + A_R1 + (62 - 48) * 4;
    load_quads<4>(qa, tb + A_R3A + 17 * 4); load_quads<4>(qa + 16, tb + A_R3B + 16 * 4);
    wg_fence();
    s3_steps<0, 4, A_W9, 1>(y3, qa, blo_n); s3_steps<0, 4, A_W7, 0>(y3, qa + 16, blo_n);
    wg_commit();
    load_quads<8>(qb, tb + A_R2A + 16 * 4);
    wg_fence(); s2_steps<0, 8, A_W5, 1>(y2, qb, blo_n); wg_commit();
    wg_wait<1>(); load_quads<8>(qa, tb + A_R2B + 16 * 4);
    wg_fence(); s2_steps<0, 8, A_W3, 0>(y2, qa, blo_n); wg_commit();
    wg_wait<1>(); load_quads<8>(qb, t1);
    wg_fence(); f1_steps<0, 8>(y1, qb, blo_k); wg_commit();
    wg_wait<1>(); load_quads<8>(qa, t1 + 8 * 64);
    wg_fence(); f1_steps<8, 8>(y1, qa, blo_k); wg_commit();
    reg_fence(y2); reg_fence(y3);
    if (tid == 320) TR(0, 18);
    {
      const float k1024 = __uint_as_float(lds32(cb + A_K1024));
#pragma unroll
      for (int i = 0; i < 2; i++)
#pragma unroll
        for (int hf = 0; hf < 2; hf++) {
          const int idx = 16 * (16 * wq + g + 8 * hf) + 8 * i + 2 * t;
          const uint32_t vv = lds32(cb + A_V + idx * 2);
          sts64(cb + A_Y3 + (idx + 4 * (idx >> 6)) * 4, __float_as_uint(fmaf(k1024, bf_lo(vv), y3[4 * i + 2 * hf])),
                __float_as_uint(fmaf(k1024, bf_hi(vv), y3[4 * i + 2 * hf + 1])));
        }
#pragma unroll
      for (int i = 0; i < 3; i++)
#pragma unroll
        for (int hf = 0; hf < 2; hf++) {
          const int idx = 512 * i + 8 * (16 * wq + g + 8 * hf) + 2 * t;
          sts64(cb + A_Y2 + (idx + 4 * (idx >> 6)) * 4, __float_as_uint(y2[4 * i + 2 * hf]), __float_as_uint(y2[4 * i + 2 * hf + 1]));
        }
    }
    wg_wait<1>(); load_quads<8>(qb, t1 + 16 * 64);
    wg_fence(); f1_steps<16, 8>(y1, qb, blo_k); wg_commit();
    wg_wait<1>(); load_quads<8>(qa, t1 + 24 * 64);
    wg_fence(); f1_steps<24, 8>(y1, qa, blo_k); wg_commit();
    wg_wait<1>(); load_quads<5>(qb, t1 + 32 * 64);
    wg_fence(); f1_steps<32, 5>(y1, qb, blo_k); wg_commit();
    bar_sync(1 + wg, 128);
    float ex[12];
#pragma unroll
    for (int i = 1; i < 4; i++)
#pragma unroll
      for (int k = 0; k < 4; k++) {
        const int aa = 8 * i + 2 * t + (k & 1), b = 16 * wq + g + 8 * (k >> 1);
        float e = __uint_as_float(lds32(cb + A_Y2 + ((aa - 8) * 68 + b) * 4));
        if (i >= 2) e += __uint_as_float(lds32(cb + A_Y3 + ((aa - 16) * 68 + b) * 4));
        ex[4 * (i - 1) + k] = e;
      }
    {
      const uint32_t dk = dk16 * 0x10001u;
#pragma unroll
      for (int i = 0; i < 4; i++) {
        const uint4 r = lds128(cb + A_REC + bk * 64 + ((i ^ (bk >> 1)) & 3) * 16);
        ud[i] = hmul2_bf(r.x, dk); ud[4 + i] = hmul2_bf(r.y, dk); xt[i] = r.z; xt[4 + i] = r.w;
      }
    }
    wg_wait<0>();
    reg_fence(y1);
    if (tid == 320) TR(0, 6);
#pragma unroll
    for (int i = 0; i < 12; i++) y1[4 + i] += ex[i];
#pragma unroll
    for (int i = 0; i < 2; i++) {
      const int mi = lane >> 3, aa = 8 * (2 * i + (mi >> 1)) + (lane & 7);
      asm volatile("stmatrix.sync.aligned.m8n8.x4.trans.shared.b16 [%0], {%1,%2,%3,%4};"
                   ::"r"(cb + A_YB + aa * 128 + (((2 * wq + (mi & 1)) ^ (lane & 7)) << 4)),
                     "r"(pack_bf16(y1[8 * i], y1[8 * i + 1])), "r"(pack_bf16(y1[8 * i + 2], y1[8 * i + 3])),
                     "r"(pack_bf16(y1[8 * i + 4], y1[8 * i + 5])), "r"(pack_bf16(y1[8 * i + 6], y1[8 * i + 7])) : "memory");
    }
  }
  bar_sync(1 + wg, 128);
#pragma unroll
  for (int c = 0; c < 2; c++) {
    const int tau = 2 * bk + c, r = ch & 7;
    const uint4 y = lds128(cb + A_YB + (tau >> 3) * 128 + (((tau ^ (tau >> 3)) & 7) << 4));
    g_himg[(size_t)(tau >> 4) * 7168 + (ch >> 3) * 128 + ((tau >> 3) & 1) * 64 + r * 8 + ((tau & 7) ^ r)] =
        make_uint4(hadd2_bf(xt[4 * c], hadd2_bf(y.x, ud[4 * c])), hadd2_bf(xt[4 * c + 1], hadd2_bf(y.y, ud[4 * c + 1])),
                   hadd2_bf(xt[4 * c + 2], hadd2_bf(y.z, ud[4 * c + 2])), hadd2_bf(xt[4 * c + 3], hadd2_bf(y.w, ud[4 * c + 3])));
  }
  if (tid == 320) TR(0, 7);
}

constexpr int B_SA = 0, B_RING = 114688, B_SLOT = 14848, B_NSLOT = 7;
constexpr int B_CS = B_RING + B_NSLOT * B_SLOT;
constexpr int B_RED = B_CS + 7168;
constexpr int B_BAR = B_RED + 256;
constexpr int B_SMEM = B_BAR + 1024, A_SMEM = 4 * A_CH + 64;

__device__ __forceinline__ uint32_t mapa(uint32_t a, uint32_t r) { uint32_t o; asm("mapa.shared::cluster.u32 %0, %1, %2;" : "=r"(o) : "r"(a), "r"(r)); return o; }
template <class T> __device__ __forceinline__ T* pin(T* p) { asm volatile("" : "+l"(p)); return p; }
__device__ __forceinline__ uint32_t pin(uint32_t v) { asm volatile("" : "+r"(v)); return v; }
__device__ __forceinline__ void wait_count(const unsigned* c, uint32_t tgt) {
  uint32_t v; int it = 0;
  do { asm volatile("ld.acquire.gpu.global.u32 %0, [%1];" : "=r"(v) : "l"(c) : "memory"); } while ((int)(v - tgt) < 0 && ++it < 400000);
  asm volatile("fence.proxy.async;" ::: "memory");
}

template <int Q, int ST>
__device__ __forceinline__ void g1_stage(float (&acc)[116], uint32_t alo, uint32_t blo, uint32_t bar_full, uint32_t bar_h) {
  constexpr int s = Q * 14 + ST, sl = s % B_NSLOT;
  if (Q == 0) mbar_wait(bar_h + 8 * ST, 0);
  mbar_wait(bar_full + 8 * sl, (s / B_NSLOT) & 1);
  wg_fence();
  if (Q == 0) {
    wgmma_ss232<(2 * ST) * 256, 0x40000080u, (sl * B_SLOT) / 16, 32, ST != 0>(acc, alo, blo);
    wgmma_ss232<(2 * ST + 1) * 256, 0x40000080u, (sl * B_SLOT + 256) / 16, 32, 1>(acc, alo, blo);
  } else {
    wgmma_ss224<(2 * ST) * 256, 0x40000080u, (sl * B_SLOT) / 16, 32, ST != 0>(*(float(*)[112])acc, alo, blo);
    wgmma_ss224<(2 * ST + 1) * 256, 0x40000080u, (sl * B_SLOT + 256) / 16, 32, 1>(*(float(*)[112])acc, alo, blo);
  }
}

__global__ void __launch_bounds__(512, 1)
k_front(const __nv_bfloat16* __restrict__ x, const uint32_t* __restrict__ are, const uint32_t* __restrict__ aim,
        const uint32_t* __restrict__ bre, const uint32_t* __restrict__ bim, const uint32_t* __restrict__ cre,
        const uint32_t* __restrict__ cim, const unsigned short* __restrict__ logdt, const unsigned short* __restrict__ dskip,
        const uint4* __restrict__ wgate, const uint4* __restrict__ wup, const uint4* __restrict__ wdown) {
  extern __shared__ __align__(1024) unsigned char sm[];
  const uint32_t bar_rec = s2u(sm) + 4 * A_CH;
  if (threadIdx.x == 320) TR(0, 0);
  asm volatile("griddepcontrol.launch_dependents;");
  if (threadIdx.x == 160) { mbar_init(bar_rec, 1); asm volatile("fence.mbarrier_init.release.cluster;" ::: "memory"); }
  phase_a(sm, bar_rec, bar_rec + 8, x, are, aim, bre, bim, cre, cim, logdt, dskip, wgate, wup, wdown);
  bar_sync(0, 512);
  if (threadIdx.x == 0) { asm volatile("red.release.gpu.global.add.u32 [%0], 1;" ::"l"(&g_cnt2) : "memory"); TR(0, 11); }
}

__global__ void __cluster_dims__(2, 1, 1) __launch_bounds__(384, 1) k_ffn(__nv_bfloat16* __restrict__ out) {
  extern __shared__ __align__(1024) unsigned char sm[];
  const uint32_t sb = s2u(sm);
  const int tid = threadIdx.x, wg = tid >> 7, warp = tid >> 5, lane = tid & 31;
  const uint32_t bar_full = sb + B_BAR, bar_empty = bar_full + 64, bar_h = bar_full + 128, bar_cs = bar_full + 240,
                 bar_g2 = bar_full + 248, bar_sum = bar_full + 256, bar_in = bar_full + 320;
  const uint32_t ep = (__ldcg(&g_cnt3) >> 7) + 1u;
  if (tid == 0) {
    TR(1, 0);
    for (int i = 0; i < B_NSLOT; i++) { mbar_init(bar_full + 8 * i, 1); mbar_init(bar_empty + 8 * i, 4); }
    asm volatile("fence.mbarrier_init.release.cluster;" ::: "memory");
  } else if (tid == 32) {
    for (int i = 0; i < 14; i++) mbar_init(bar_h + 8 * i, 1);
  } else if (tid == 64) {
    mbar_init(bar_cs, 1);
    mbar_init(bar_g2, 4);
    for (int i = 0; i < 4; i++) mbar_init(bar_sum + 8 * i, 32);
  } else if (tid >= 72 && tid < 128) {
    mbar_init(bar_in + 8 * (tid - 72), 1);
  } else if (tid >= 128 && tid < 352) {
    sts128(sb + B_RING + ((tid - 128) >> 5) * B_SLOT + 14336 + (tid & 31) * 16, 0x3F803F80u, 0x3F803F80u, 0x3F803F80u, 0x3F803F80u);
  }
  asm volatile("fence.proxy.async.shared::cta;" ::: "memory");
  __syncthreads();
  asm volatile("barrier.cluster.arrive.relaxed.aligned;" ::: "memory");
  const int rank = blockIdx.x & 1, rt = blockIdx.x & 15, j = blockIdx.x >> 4;
  const int wq = warp & 3, t128 = tid & 127, g = lane >> 2, t = lane & 3;
  const uint32_t tag = pin((ep & 1u) << 16);
  auto in_addr = [&](int q, int cw) { return sb + B_SA + ((j + 1 + q) & 7) * 14336 + cw * 1792; };
  auto in_src = [&](int q, int cw) { return g_part + (size_t)((rt * 8 + ((j + 7 - q) & 7)) * 7 + q) * 896 + cw * 112; };
  auto add_in = [&](float (&sum)[28], int q, int cw) {
    const uint32_t a = in_addr(q, cw);
    const uint4 v0 = lds128(a + lane * 16), v1 = lds128(a + 512 + lane * 16), v2 = lds128(a + 1024 + lane * 16);
    uint32_t in[14] = {v0.x, v0.y, v0.z, v0.w, v1.x, v1.y, v1.z, v1.w, v2.x, v2.y, v2.z, v2.w, 0, 0};
    asm volatile("ld.shared.v2.u32 {%0, %1}, [%2];" : "=r"(in[12]), "=r"(in[13]) : "r"(a + 1536 + lane * 8) : "memory");
    int it = 0;
    while ((((in[3] ^ tag) | (in[7] ^ tag) | (in[11] ^ tag) | (in[13] ^ tag)) & 0x10000u) && ++it < 400000) {
      const uint4* gs = pin(in_src(q, cw));
#pragma unroll
      for (int i = 0; i < 3; i++) ld128(gs + i * 32 + lane, in + 4 * i);
      asm volatile("{\n.reg .b64 v;\nld.relaxed.gpu.global.b64 v, [%2];\nmov.b64 {%0, %1}, v;\n}"
                   : "=r"(in[12]), "=r"(in[13]) : "l"((const uint2*)(gs + 96) + lane) : "memory");
    }
#pragma unroll
    for (int i = 0; i < 14; i++) { sum[2 * i] += bf_lo(in[i]); sum[2 * i + 1] += bf_hi(in[i]); }
  };
  auto w_issue = [&](int s) {
    const char* wsrc = (const char*)g_wimg + (size_t)j * 602112;
    const int slot = s % B_NSLOT;
    const uint32_t dst = sb + B_RING + slot * B_SLOT, fb = bar_full + 8 * slot;
    if (s < 28) {
      mbar_expect(fb, 14336);
      bulk_ld_mc(dst + rank * 7168, wsrc + s * 14336 + rank * 7168, 7168, fb);
    } else {
      const int c = (j + 1 + ((s - 28) >> 1)) & 7;
      mbar_expect(fb, 12544);
      bulk_ld_mc(dst + rank * 6272, wsrc + 401408 + (c * 2 + (s & 1)) * 12544 + rank * 6272, 6272, fb);
    }
  };

  if (wg == 2) {
    asm volatile("setmaxnreg.dec.sync.aligned.u32 104;");
    if (warp != 9) asm volatile("barrier.cluster.wait.aligned;" ::: "memory");
    if (warp == 8) {
      if (lane == 0) {
        wait_count(&g_cnt2, ep * 128u);
        TR(1, 1);
        for (int s = 0; s < 35; s++) {
          if (s >= B_NSLOT) mbar_wait(bar_empty + 8 * (s % B_NSLOT), (s / B_NSLOT - 1) & 1);
          w_issue(s);
        }
      }
    } else if (warp == 9) {
      if (lane == 0) {
        const char* hsrc = (const char*)g_himg + (size_t)rt * 114688;
        wait_count(&g_cnt2, ep * 128u);
        for (int i = 0; i < 14; i++) {
          mbar_expect(bar_h + 8 * i, 8192);
          bulk_ld(sb + B_SA + i * 8192, hsrc + i * 8192, 8192, bar_h + 8 * i);
        }
        mbar_expect(bar_cs, 7168);
        bulk_ld(sb + B_CS, g_cimg + j * 448, 7168, bar_cs);
      }
      __syncwarp();
      asm volatile("barrier.cluster.wait.aligned;" ::: "memory");
    } else {
      const int t64 = tid - 320;
      const int r = (lane >> 1) & 7, c = (j & 3) * 2 + (lane & 1);
      const uint32_t src = sb + B_SA + (t64 >> 4) * 2048 + (j >> 2) * 1024 + r * 128 + ((c ^ r) << 4);
      float a[16];
#pragma unroll
      for (int k = 0; k < 16; k++) a[k] = 0.f;
#pragma unroll 1
      for (int i = 0; i < 14; i++) {
        mbar_wait(bar_h + 8 * i, 0);
        uint4 v = lds128(src + i * 8192);
        float e[8] = {bf_lo(v.x), bf_hi(v.x), bf_lo(v.y), bf_hi(v.y), bf_lo(v.z), bf_hi(v.z), bf_lo(v.w), bf_hi(v.w)};
#pragma unroll
        for (int k = 0; k < 8; k++) { a[2 * k] += e[k]; a[2 * k + 1] = fmaf(e[k], e[k], a[2 * k + 1]); }
        __nanosleep(160);
      }
      __syncwarp();
      if (lane == 0) mbar_arrive(bar_g2);
#pragma unroll
      for (int rd = 0; rd < 4; rd++) {
        const int n = 8 >> rd;
        const bool up = lane & (2 * n);
#pragma unroll
        for (int k = 0; k < 8; k++) {
          if (k < n) {
            float keep = up ? a[k + n] : a[k], give = up ? a[k] : a[k + n];
            a[k] = keep + __shfl_xor_sync(~0u, give, 2 * n);
          }
        }
      }
      float* red = (float*)(sm + B_RED);
      red[(warp & 1) * 32 + (lane & 1) * 16 + (lane >> 1)] = a[0];
      bar_sync(1, 64);
      if (t64 < 16) {
        float mean = (red[2 * t64] + red[32 + 2 * t64]) * (1.f / DM);
        float var = fmaxf(fmaf(-mean, mean, (red[2 * t64 + 1] + red[33 + 2 * t64]) * (1.f / DM)), 0.f);
        float rs = __frcp_rn(rbf(__fsqrt_rn(rbf(rbf(var) + 1e-5f))));
        asm volatile("st.relaxed.gpu.global.u32 [%0], %1;"
                     ::"l"(g_stat2 + rt * 128 + j * 16 + t64), "r"((__float_as_uint(rs * rs) & ~1u) | (ep & 1u)) : "memory");
      }
      if (t64 == 0) TR(1, 2);
    }
    __syncwarp();
    float sum0[28], sum1[28];
#pragma unroll
    for (int i = 0; i < 28; i++) { sum0[i] = 0.f; sum1[i] = 0.f; }
    mbar_wait(bar_g2, 0);
    if (tid == 352) asm volatile("red.relaxed.gpu.global.add.u32 [%0], 1;" ::"l"(&g_cnt3) : "memory");
    {
      const int lq = (lane >> 1) & 7, lcw = (lane & 1) * 4 + wq;
      const uint32_t* fl = g_flag + (rt * 8 + ((j + 7 - lq) & 7)) * 64 + lq * 8 + lcw;
      bool todo = lane < 14;
      int ws = (warp == 8 && lane == 31) ? 35 : 44, nacc = 0, it = 0;
      while ((__any_sync(~0u, todo || ws < 44) || nacc < 5) && ++it < 400000) {
        uint32_t f = 0;
        if (todo) asm volatile("ld.relaxed.gpu.global.u32 %0, [%1];" : "=r"(f) : "l"(fl) : "memory");
        while (ws < 44 && mbar_test(bar_empty + 8 * (ws % B_NSLOT), (ws / B_NSLOT - 1) & 1)) { w_issue(ws); ws++; }
        __syncwarp();
        while (nacc < 5 && __all_sync(~0u, mbar_test(bar_in + 8 * (nacc * 8 + lcw), 0))) {
          add_in(sum0, nacc, wq); add_in(sum1, nacc, wq + 4);
          if (++nacc == 5) {
            __syncwarp();
#pragma unroll
            for (int i = 0; i < 7; i++) {
              sts128(in_addr(i / 3, wq) + (i % 3) * 512 + lane * 16, __float_as_uint(sum0[4 * i]), __float_as_uint(sum0[4 * i + 1]), __float_as_uint(sum0[4 * i + 2]), __float_as_uint(sum0[4 * i + 3]));
              sts128(in_addr(i / 3, wq + 4) + (i % 3) * 512 + lane * 16, __float_as_uint(sum1[4 * i]), __float_as_uint(sum1[4 * i + 1]), __float_as_uint(sum1[4 * i + 2]), __float_as_uint(sum1[4 * i + 3]));
            }
            mbar_arrive(bar_sum + 8 * wq);
            if (tid == 320) TR(1, 8);
          }
        }
        if (todo && f == ep) {
          asm volatile("fence.proxy.async;" ::: "memory");
          mbar_expect(bar_in + 8 * (lq * 8 + lcw), 1792);
          bulk_ld(in_addr(lq, lcw), in_src(lq, lcw), 1792, bar_in + 8 * (lq * 8 + lcw));
          todo = false;
          if (warp == 10 && (lane & 1)) TR(1, 24 + lq);
        }
      }
    }
    asm volatile("griddepcontrol.wait;" ::: "memory");
  } else {
    asm volatile("setmaxnreg.inc.sync.aligned.u32 200;");
    asm volatile("barrier.cluster.wait.aligned;" ::: "memory");
    uint32_t hh[56];
    const uint32_t rel_bar = pin(mapa(bar_empty, t128 & 1));
    const bool relt = t128 < 2;
    auto release = [&](int sl) { if (relt) asm volatile("mbarrier.arrive.shared::cluster.b64 _, [%0];" ::"r"(rel_bar + 8 * sl) : "memory"); };
    const uint32_t alo = __shfl_sync(~0u, ((sb + B_SA + wg * 1024) & 0x3FFFF) >> 4, 0);
    const uint32_t blo = (((sb + B_RING) & 0x3FFFF) >> 4) | (8u << 16);
    const uint32_t clo = ((sb + B_CS) & 0x3FFFF) >> 4;
    uint32_t nm0, nm1;
    if (wg == 1) bar_sync(3, 256);
#define G1S(Q, ST) do { g1_stage<Q, ST>(acc, alo, blo, bar_full, bar_h); wg_commit(); \
      if (ST > 0) { wg_wait<1>(); release((Q * 14 + ST - 1) % B_NSLOT); } } while (0)
#define G1HH(Q) do { \
      _Pragma("unroll") \
      for (int i = 0; i < 28; i++) hh[28 * Q + i] = pack_bf16(acc[2 * i] * acc[56 + 2 * i], acc[2 * i + 1] * acc[57 + 2 * i]); \
    } while (0)
    {
      float acc[116];
      G1S(0, 0);
      if (tid == 0) TR(1, 3);
      G1S(0, 1);
      if (wg == 0) asm volatile("bar.arrive 3, 256;" ::: "memory");
      G1S(0, 2); G1S(0, 3); G1S(0, 4); G1S(0, 5); G1S(0, 6); G1S(0, 7); G1S(0, 8); G1S(0, 9); G1S(0, 10); G1S(0, 11); G1S(0, 12);
      G1S(0, 13);
      if (tid == 0) TR(1, 4);
      mbar_wait(bar_cs, 0);
      wg_wait<0>(); reg_fence(acc); release(13 % B_NSLOT);
      {
        const uint32_t msk = t == 0 ? 0xFFFFFFFFu : t == 1 ? 0xFFFFu : 0u;
        const float a = acc[112] * (-1.f / DM), b = acc[114] * (-1.f / DM);
        nm0 = pack_bf16(a, a) & msk; nm1 = pack_bf16(b, b) & msk;
      }
      wg_fence();
      wgmma_rs224<0, 8, 1>(*(float(*)[112])acc, nm0, nm1, 0u, 0u, clo);
      wg_commit(); wg_wait<0>(); reg_fence(acc);
      G1HH(0);
      if (tid == 0) TR(1, 5);
      G1S(1, 0); G1S(1, 1); G1S(1, 2); G1S(1, 3); G1S(1, 4); G1S(1, 5); G1S(1, 6); G1S(1, 7); G1S(1, 8); G1S(1, 9); G1S(1, 10); G1S(1, 11);
      G1S(1, 12);
      g1_stage<1, 13>(acc, alo, blo, bar_full, bar_h);
      wgmma_rs224<224, 8, 1>(*(float(*)[112])acc, nm0, nm1, 0u, 0u, clo);
      wg_commit(); wg_wait<1>(); release(26 % B_NSLOT);
      wg_wait<0>(); reg_fence(acc); release(27 % B_NSLOT);
      if (t128 == 0) mbar_arrive(bar_g2);
      G1HH(1);
      if (tid == 0) TR(1, 6);
    }
    float accA[28], accB[28];
#define ISSUE(acc, I, a, FIRST) do { \
      constexpr int s_ = 28 + (I), sl_ = s_ % B_NSLOT; \
      mbar_wait(bar_full + 8 * sl_, (s_ / B_NSLOT) & 1); \
      wg_fence(); \
      wgmma_rs56<(sl_ * B_SLOT + 0 * 256) / 16, 112, !(FIRST)>(acc, (a)[0], (a)[1], (a)[2], (a)[3], blo); \
      wgmma_rs56<(sl_ * B_SLOT + 1 * 256) / 16, 112, 1>(acc, (a)[4], (a)[5], (a)[6], (a)[7], blo); \
      wgmma_rs56<(sl_ * B_SLOT + 2 * 256) / 16, 112, 1>(acc, (a)[8], (a)[9], (a)[10], (a)[11], blo); \
      wgmma_rs56<(sl_ * B_SLOT + 3 * 256) / 16, 112, 1>(acc, (a)[12], (a)[13], (a)[14], (a)[15], blo); \
      wgmma_rs56<(sl_ * B_SLOT + 4 * 256) / 16, 112, 1>(acc, (a)[16], (a)[17], (a)[18], (a)[19], blo); \
      wgmma_rs56<(sl_ * B_SLOT + 5 * 256) / 16, 112, 1>(acc, (a)[20], (a)[21], (a)[22], (a)[23], blo); \
      wgmma_rs56<(sl_ * B_SLOT + 6 * 256) / 16, 112, 1>(acc, (a)[24], (a)[25], (a)[26], (a)[27], blo); \
      wg_commit(); } while (0)
    uint4* const pdst = pin(g_part + (size_t)((rt * 8 + j) * 7) * 896 + warp * 112 + lane);
    uint2* const pdst2 = pin((uint2*)(g_part + (size_t)((rt * 8 + j) * 7) * 896 + warp * 112 + 96) + lane);
    uint32_t* const fdst = pin(g_flag + (rt * 8 + j) * 64 + warp);
    const bool flt = lane == 0;
    auto rel = [&](int i) { if (i < 9) release((28 + i) % B_NSLOT); };
    auto tg = [&](uint32_t v) { return (v & 0xFFFEFFFFu) | tag; };
    auto send_lo = [&](float (&acc)[28], int cc) {
      reg_fence(acc);
#pragma unroll
      for (int q = 0; q < 2; q++)
        st128(pdst + cc * 896 + q * 32, pack_bf16(acc[8 * q], acc[8 * q + 1]), pack_bf16(acc[8 * q + 2], acc[8 * q + 3]),
              pack_bf16(acc[8 * q + 4], acc[8 * q + 5]), tg(pack_bf16(acc[8 * q + 6], acc[8 * q + 7])));
    };
    auto send_hi = [&](float (&acc)[28], int cc) {
      st128(pdst + cc * 896 + 64, pack_bf16(acc[16], acc[17]), pack_bf16(acc[18], acc[19]), pack_bf16(acc[20], acc[21]), tg(pack_bf16(acc[22], acc[23])));
      asm volatile("{\n.reg .b64 v;\nmov.b64 v, {%1, %2};\nst.relaxed.gpu.global.b64 [%0], v;\n}"
                   ::"l"(pdst2 + cc * 1792), "r"(pack_bf16(acc[24], acc[25])), "r"(tg(pack_bf16(acc[26], acc[27]))) : "memory");
      if (flt) asm volatile("st.relaxed.gpu.global.u32 [%0], %1;" ::"l"(fdst + cc * 8), "r"(ep) : "memory");
    };
#define CHUNK(cur, prev, CC) do { \
      ISSUE(cur, 2 * (CC), hh, true); wg_wait<1>(); rel(2 * (CC) - 1); send_lo(prev, (CC) - 1); \
      ISSUE(cur, 2 * (CC) + 1, hh + 28, false); send_hi(prev, (CC) - 1); wg_wait<1>(); rel(2 * (CC)); } while (0)
    ISSUE(accA, 0, hh, true);
    ISSUE(accA, 1, hh + 28, false); wg_wait<1>(); rel(0);
    CHUNK(accB, accA, 1);
    if (tid == 0) TR(1, 11);
    CHUNK(accA, accB, 2);
    CHUNK(accB, accA, 3);
    if (tid == 0) TR(1, 13);
    CHUNK(accA, accB, 4);
    CHUNK(accB, accA, 5);
    if (tid == 0) TR(1, 16);
    CHUNK(accA, accB, 6);
    const int row = rt * 128 + wg * 64 + wq * 16 + g;
    uint32_t r20, r21;
    asm volatile("ld.relaxed.gpu.global.u32 %0, [%1];" : "=r"(r20) : "l"(g_stat2 + row) : "memory");
    asm volatile("ld.relaxed.gpu.global.u32 %0, [%1];" : "=r"(r21) : "l"(g_stat2 + row + 8) : "memory");
    CHUNK(accB, accA, 7);
    if (tid == 0) TR(1, 7);
    uint32_t hres[16];
#pragma unroll
    for (int i = 0; i < 4; i++) {
      int qq = lane >> 3, r = lane & 7, kg = 7 * j + 2 * i + (qq >> 1), c = 2 * wq + (qq & 1);
      if (kg > 55) kg = 55;
      asm volatile("ldmatrix.sync.aligned.m8n8.x4.trans.shared.b16 {%0,%1,%2,%3}, [%4];"
                   : "=r"(hres[4 * i]), "=r"(hres[4 * i + 1]), "=r"(hres[4 * i + 2]), "=r"(hres[4 * i + 3])
                   : "r"(sb + B_SA + kg * 2048 + wg * 1024 + r * 128 + ((c ^ r) << 4)) : "memory");
    }
    {
      int it = 0;
      while ((((r20 ^ ep) | (r21 ^ ep)) & 1u) && ++it < 400000) {
        asm volatile("ld.relaxed.gpu.global.u32 %0, [%1];" : "=r"(r20) : "l"(g_stat2 + row) : "memory");
        asm volatile("ld.relaxed.gpu.global.u32 %0, [%1];" : "=r"(r21) : "l"(g_stat2 + row + 8) : "memory");
      }
    }
    mbar_wait(bar_sum + 8 * wq, 0);
#pragma unroll
    for (int i = 0; i < 7; i++) {
      const uint4 v = lds128(in_addr(i / 3, warp) + (i % 3) * 512 + lane * 16);
      accA[4 * i] = __uint_as_float(v.x); accA[4 * i + 1] = __uint_as_float(v.y); accA[4 * i + 2] = __uint_as_float(v.z); accA[4 * i + 3] = __uint_as_float(v.w);
    }
    mbar_wait(bar_in + 8 * (40 + warp), 0);
    add_in(accA, 5, warp);
    wg_wait<0>();
    reg_fence(accB);
#pragma unroll
    for (int i = 0; i < 28; i++) accA[i] += accB[i];
    if (tid == 0) TR(1, 9);
    mbar_wait(bar_in + 8 * (48 + warp), 0);
    add_in(accA, 6, warp);
    uint32_t* o0 = (uint32_t*)(out + (size_t)row * DM + 56 * j + 2 * t);
    uint32_t* o1 = o0 + 8 * DM / 2;
#pragma unroll
    for (int i = 0; i < 7; i++) {
      o0[4 * i] = hadd2_bf(hres[2 * i], pack_bf16(accA[4 * i] * __uint_as_float(r20), accA[4 * i + 1] * __uint_as_float(r20)));
      o1[4 * i] = hadd2_bf(hres[2 * i + 1], pack_bf16(accA[4 * i + 2] * __uint_as_float(r21), accA[4 * i + 3] * __uint_as_float(r21)));
    }
    if (tid == 0) TR(1, 10);
    if (tid == 128) TR(1, 15);
  }
}

extern "C" void kernel_launch(void* const* d_in, const int* in_sizes, int n_in, void* d_out, int out_size) {
  const __nv_bfloat16* x = (const __nv_bfloat16*)d_in[0];
  const __nv_bfloat16 *are = (const __nv_bfloat16*)d_in[1], *aim = (const __nv_bfloat16*)d_in[2], *bre = (const __nv_bfloat16*)d_in[3],
                      *bim = (const __nv_bfloat16*)d_in[4], *cre = (const __nv_bfloat16*)d_in[5], *cim = (const __nv_bfloat16*)d_in[6],
                      *logdt = (const __nv_bfloat16*)d_in[7], *dskip = (const __nv_bfloat16*)d_in[8];
  const __nv_bfloat16 *wg = (const __nv_bfloat16*)d_in[10], *wu = (const __nv_bfloat16*)d_in[11], *wd = (const __nv_bfloat16*)d_in[12];

  static bool init = false;
  if (!init) {
    init = true;
    cudaFuncSetAttribute(k_ffn, cudaFuncAttributeMaxDynamicSharedMemorySize, B_SMEM);
    cudaFuncSetAttribute(k_front, cudaFuncAttributeMaxDynamicSharedMemorySize, A_SMEM);
  }
  cudaStream_t st = cudaStreamPerThread;
  k_front<<<128, 512, A_SMEM, st>>>(
      x, (const uint32_t*)are, (const uint32_t*)aim, (const uint32_t*)bre, (const uint32_t*)bim, (const uint32_t*)cre, (const uint32_t*)cim,
      (const unsigned short*)logdt, (const unsigned short*)dskip, (const uint4*)wg, (const uint4*)wu, (const uint4*)wd);
  cudaLaunchConfig_t cfg = {};
  cfg.gridDim = dim3(128); cfg.blockDim = dim3(384); cfg.dynamicSmemBytes = B_SMEM; cfg.stream = st;
  cudaLaunchAttribute at[1];
  at[0].id = cudaLaunchAttributeProgrammaticStreamSerialization; at[0].val.programmaticStreamSerializationAllowed = 1;
  cfg.attrs = at; cfg.numAttrs = 1;
  cudaLaunchKernelEx(&cfg, k_ffn, (__nv_bfloat16*)d_out);
}
```

```cpp
#include <cuda_runtime.h>
#include <cuda_bf16.h>
#include <stdint.h>

constexpr int LSEQ = 2048, DM = 448;

__device__ uint4    g_himg[16 * 114688 / 16];
__device__ uint4    g_cimg[8 * 2 * 224];
__device__ uint32_t g_stat2[LSEQ];
__device__ uint4    g_part[128 * 7 * 896];
__device__ uint4    g_wimg[8 * 602112 / 16];
__device__ uint4    g_ux[DM * 128 * 4];
__device__ unsigned g_cnt1;
__device__ uint32_t g_flag[128 * 64];

#define TR(k, i) do {} while (0)
__device__ __forceinline__ uint32_t s2u(const void* p) { return (uint32_t)__cvta_generic_to_shared(p); }
__device__ __forceinline__ void mbar_init(uint32_t b, int c) { asm volatile("mbarrier.init.shared::cta.b64 [%0], %1;" ::"r"(b), "r"(c)); }
__device__ __forceinline__ void mbar_expect(uint32_t b, int bytes) { asm volatile("mbarrier.arrive.expect_tx.shared::cta.b64 _, [%0], %1;" ::"r"(b), "r"(bytes) : "memory"); }
__device__ __forceinline__ void mbar_arrive(uint32_t b) { asm volatile("mbarrier.arrive.shared::cta.b64 _, [%0];" ::"r"(b) : "memory"); }
__device__ __forceinline__ void mbar_wait(uint32_t b, int ph) {
  asm volatile("{\n.reg .pred p;\n.reg .b32 n;\nmov.b32 n, 0;\nLW:\nmbarrier.try_wait.parity.shared::cta.b64 p, [%0], %1;\n@p bra LD;\n"
               "add.u32 n, n, 1;\nsetp.lt.u32 p, n, 4000000;\n@p bra LW;\ntrap;\nLD:\n}" ::"r"(b), "r"(ph) : "memory");
}
__device__ __forceinline__ bool mbar_test(uint32_t b, int ph) {
  uint32_t ok;
  asm volatile("{\n.reg .pred p;\nmbarrier.test_wait.parity.shared::cta.b64 p, [%1], %2;\nselp.u32 %0, 1, 0, p;\n}" : "=r"(ok) : "r"(b), "r"(ph) : "memory");
  return ok;
}
__device__ __forceinline__ void wg_fence() { asm volatile("wgmma.fence.sync.aligned;" ::: "memory"); }
__device__ __forceinline__ void wg_commit() { asm volatile("wgmma.commit_group.sync.aligned;" ::: "memory"); }
template <int N> __device__ __forceinline__ void wg_wait() { asm volatile("wgmma.wait_group.sync.aligned %0;" ::"n"(N) : "memory"); }
template <int N> __device__ __forceinline__ void reg_fence(float (&a)[N]) {
#pragma unroll
  for (int i = 0; i < N; i++) asm volatile("" : "+f"(a[i])::"memory");
}
__device__ __forceinline__ uint32_t pack_bf16(float lo, float hi) {
  uint32_t r; asm("cvt.rn.bf16x2.f32 %0, %1, %2;" : "=r"(r) : "f"(hi), "f"(lo)); return r;
}
__device__ __forceinline__ float bf_lo(uint32_t v) { return __uint_as_float(v << 16); }
__device__ __forceinline__ float bf_hi(uint32_t v) { return __uint_as_float(v & 0xFFFF0000u); }
__device__ __forceinline__ float rbf(float x) { return __bfloat162float(__float2bfloat16_rn(x)); }
__device__ __forceinline__ uint32_t hmul2_bf(uint32_t a, uint32_t b) { uint32_t r; asm("mul.rn.bf16x2 %0, %1, %2;" : "=r"(r) : "r"(a), "r"(b)); return r; }
__device__ __forceinline__ uint32_t hadd2_bf(uint32_t a, uint32_t b) { uint32_t r; asm("add.rn.bf16x2 %0, %1, %2;" : "=r"(r) : "r"(a), "r"(b)); return r; }
__device__ __forceinline__ void bulk_ld(uint32_t dst, const void* src, int bytes, uint32_t bar) {
  asm volatile("cp.async.bulk.shared::cluster.global.mbarrier::complete_tx::bytes [%0], [%1], %2, [%3];"
               ::"r"(dst), "l"(src), "r"(bytes), "r"(bar) : "memory");
}

__device__ __forceinline__ void bulk_ld_mc(uint32_t dst, const void* src, int bytes, uint32_t bar) {
  asm volatile("cp.async.bulk.shared::cluster.global.mbarrier::complete_tx::bytes.multicast::cluster [%0], [%1], %2, [%3], %4;"
               ::"r"(dst), "l"(src), "r"(bytes), "r"(bar), "h"((uint16_t)3) : "memory");
}
template <int AOFF, uint32_t AHI, int BOFF, uint32_t BHI, int ACC>
__device__ __forceinline__ void wgmma_ss224(float (&d)[112], uint32_t alo, uint32_t blo) {
  asm volatile("{\n.reg .pred p;\n.reg .b32 la, lb;\n.reg .b64 ad, bd;\nsetp.ne.b32 p, %118, 0;\n"
    "add.u32 la, %112, %114;\nmov.b64 ad, {la, %115};\nadd.u32 lb, %113, %116;\nmov.b64 bd, {lb, %117};\n"
    "wgmma.mma_async.sync.aligned.m64n224k16.f32.bf16.bf16 {%0,%1,%2,%3,%4,%5,%6,%7,%8,%9,%10,%11,%12,%13,%14,%15,%16,%17,%18,%19,%20,%21,%22,%23,%24,%25,%26,%27,%28,%29,%30,%31,%32,%33,%34,%35,%36,%37,%38,%39,%40,%41,%42,%43,%44,%45,%46,%47,%48,%49,%50,%51,%52,%53,%54,%55,%56,%57,%58,%59,%60,%61,%62,%63,%64,%65,%66,%67,%68,%69,%70,%71,%72,%73,%74,%75,%76,%77,%78,%79,%80,%81,%82,%83,%84,%85,%86,%87,%88,%89,%90,%91,%92,%93,%94,%95,%96,%97,%98,%99,%100,%101,%102,%103,%104,%105,%106,%107,%108,%109,%110,%111}, ad, bd, p, 1, 1, 1, 1;\n}\n"
    : "+f"(d[0]),"+f"(d[1]),"+f"(d[2]),"+f"(d[3]),"+f"(d[4]),"+f"(d[5]),"+f"(d[6]),"+f"(d[7]),"+f"(d[8]),"+f"(d[9]),"+f"(d[10]),"+f"(d[11]),"+f"(d[12]),"+f"(d[13]),"+f"(d[14]),"+f"(d[15]),"+f"(d[16]),"+f"(d[17]),"+f"(d[18]),"+f"(d[19]),"+f"(d[20]),"+f"(d[21]),"+f"(d[22]),"+f"(d[23]),"+f"(d[24]),"+f"(d[25]),"+f"(d[26]),"+f"(d[27]),"+f"(d[28]),"+f"(d[29]),"+f"(d[30]),"+f"(d[31]),"+f"(d[32]),"+f"(d[33]),"+f"(d[34]),"+f"(d[35]),"+f"(d[36]),"+f"(d[37]),"+f"(d[38]),"+f"(d[39]),"+f"(d[40]),"+f"(d[41]),"+f"(d[42]),"+f"(d[43]),"+f"(d[44]),"+f"(d[45]),"+f"(d[46]),"+f"(d[47]),"+f"(d[48]),"+f"(d[49]),"+f"(d[50]),"+f"(d[51]),"+f"(d[52]),"+f"(d[53]),"+f"(d[54]),"+f"(d[55]),"+f"(d[56]),"+f"(d[57]),"+f"(d[58]),"+f"(d[59]),"+f"(d[60]),"+f"(d[61]),"+f"(d[62]),"+f"(d[63]),"+f"(d[64]),"+f"(d[65]),"+f"(d[66]),"+f"(d[67]),"+f"(d[68]),"+f"(d[69]),"+f"(d[70]),"+f"(d[71]),"+f"(d[72]),"+f"(d[73]),"+f"(d[74]),"+f"(d[75]),"+f"(d[76]),"+f"(d[77]),"+f"(d[78]),"+f"(d[79]),"+f"(d[80]),"+f"(d[81]),"+f"(d[82]),"+f"(d[83]),"+f"(d[84]),"+f"(d[85]),"+f"(d[86]),"+f"(d[87]),"+f"(d[88]),"+f"(d[89]),"+f"(d[90]),"+f"(d[91]),"+f"(d[92]),"+f"(d[93]),"+f"(d[94]),"+f"(d[95]),"+f"(d[96]),"+f"(d[97]),"+f"(d[98]),"+f"(d[99]),"+f"(d[100]),"+f"(d[101]),"+f"(d[102]),"+f"(d[103]),"+f"(d[104]),"+f"(d[105]),"+f"(d[106]),"+f"(d[107]),"+f"(d[108]),"+f"(d[109]),"+f"(d[110]),"+f"(d[111])
    : "r"(alo), "r"(blo), "n"(AOFF), "n"(AHI), "n"(BOFF), "n"(BHI), "n"(ACC));
}
template <int AOFF, uint32_t AHI, int BOFF, uint32_t BHI, int ACC>
__device__ __forceinline__ void wgmma_ss232(float (&d)[116], uint32_t alo, uint32_t blo) {
  asm volatile("{\n.reg .pred p;\n.reg .b32 la, lb;\n.reg .b64 ad, bd;\nsetp.ne.b32 p, %122, 0;\n"
    "add.u32 la, %116, %118;\nmov.b64 ad, {la, %119};\nadd.u32 lb, %117, %120;\nmov.b64 bd, {lb, %121};\n"
    "wgmma.mma_async.sync.aligned.m64n232k16.f32.bf16.bf16 {%0,%1,%2,%3,%4,%5,%6,%7,%8,%9,%10,%11,%12,%13,%14,%15,%16,%17,%18,%19,%20,%21,%22,%23,%24,%25,%26,%27,%28,%29,%30,%31,%32,%33,%34,%35,%36,%37,%38,%39,%40,%41,%42,%43,%44,%45,%46,%47,%48,%49,%50,%51,%52,%53,%54,%55,%56,%57,%58,%59,%60,%61,%62,%63,%64,%65,%66,%67,%68,%69,%70,%71,%72,%73,%74,%75,%76,%77,%78,%79,%80,%81,%82,%83,%84,%85,%86,%87,%88,%89,%90,%91,%92,%93,%94,%95,%96,%97,%98,%99,%100,%101,%102,%103,%104,%105,%106,%107,%108,%109,%110,%111,%112,%113,%114,%115}, ad, bd, p, 1, 1, 1, 1;\n}\n"
    : "+f"(d[0]),"+f"(d[1]),"+f"(d[2]),"+f"(d[3]),"+f"(d[4]),"+f"(d[5]),"+f"(d[6]),"+f"(d[7]),"+f"(d[8]),"+f"(d[9]),"+f"(d[10]),"+f"(d[11]),"+f"(d[12]),"+f"(d[13]),"+f"(d[14]),"+f"(d[15]),"+f"(d[16]),"+f"(d[17]),"+f"(d[18]),"+f"(d[19]),"+f"(d[20]),"+f"(d[21]),"+f"(d[22]),"+f"(d[23]),"+f"(d[24]),"+f"(d[25]),"+f"(d[26]),"+f"(d[27]),"+f"(d[28]),"+f"(d[29]),"+f"(d[30]),"+f"(d[31]),"+f"(d[32]),"+f"(d[33]),"+f"(d[34]),"+f"(d[35]),"+f"(d[36]),"+f"(d[37]),"+f"(d[38]),"+f"(d[39]),"+f"(d[40]),"+f"(d[41]),"+f"(d[42]),"+f"(d[43]),"+f"(d[44]),"+f"(d[45]),"+f"(d[46]),"+f"(d[47]),"+f"(d[48]),"+f"(d[49]),"+f"(d[50]),"+f"(d[51]),"+f"(d[52]),"+f"(d[53]),"+f"(d[54]),"+f"(d[55]),"+f"(d[56]),"+f"(d[57]),"+f"(d[58]),"+f"(d[59]),"+f"(d[60]),"+f"(d[61]),"+f"(d[62]),"+f"(d[63]),"+f"(d[64]),"+f"(d[65]),"+f"(d[66]),"+f"(d[67]),"+f"(d[68]),"+f"(d[69]),"+f"(d[70]),"+f"(d[71]),"+f"(d[72]),"+f"(d[73]),"+f"(d[74]),"+f"(d[75]),"+f"(d[76]),"+f"(d[77]),"+f"(d[78]),"+f"(d[79]),"+f"(d[80]),"+f"(d[81]),"+f"(d[82]),"+f"(d[83]),"+f"(d[84]),"+f"(d[85]),"+f"(d[86]),"+f"(d[87]),"+f"(d[88]),"+f"(d[89]),"+f"(d[90]),"+f"(d[91]),"+f"(d[92]),"+f"(d[93]),"+f"(d[94]),"+f"(d[95]),"+f"(d[96]),"+f"(d[97]),"+f"(d[98]),"+f"(d[99]),"+f"(d[100]),"+f"(d[101]),"+f"(d[102]),"+f"(d[103]),"+f"(d[104]),"+f"(d[105]),"+f"(d[106]),"+f"(d[107]),"+f"(d[108]),"+f"(d[109]),"+f"(d[110]),"+f"(d[111]),"+f"(d[112]),"+f"(d[113]),"+f"(d[114]),"+f"(d[115])
    : "r"(alo), "r"(blo), "n"(AOFF), "n"(AHI), "n"(BOFF), "n"(BHI), "n"(ACC));
}
template <int OFF, uint32_t BHI, int ACC>
__device__ __forceinline__ void wgmma_rs224(float (&d)[112], uint32_t a0, uint32_t a1, uint32_t a2, uint32_t a3, uint32_t blo) {
  asm volatile("{\n.reg .pred p;\n.reg .b32 l;\n.reg .b64 bd;\nsetp.ne.b32 p, %119, 0;\nadd.u32 l, %116, %117;\nmov.b64 bd, {l, %118};\n"
    "wgmma.mma_async.sync.aligned.m64n224k16.f32.bf16.bf16 {%0,%1,%2,%3,%4,%5,%6,%7,%8,%9,%10,%11,%12,%13,%14,%15,%16,%17,%18,%19,%20,%21,%22,%23,%24,%25,%26,%27,%28,%29,%30,%31,%32,%33,%34,%35,%36,%37,%38,%39,%40,%41,%42,%43,%44,%45,%46,%47,%48,%49,%50,%51,%52,%53,%54,%55,%56,%57,%58,%59,%60,%61,%62,%63,%64,%65,%66,%67,%68,%69,%70,%71,%72,%73,%74,%75,%76,%77,%78,%79,%80,%81,%82,%83,%84,%85,%86,%87,%88,%89,%90,%91,%92,%93,%94,%95,%96,%97,%98,%99,%100,%101,%102,%103,%104,%105,%106,%107,%108,%109,%110,%111}, {%112,%113,%114,%115}, bd, p, 1, 1, 1;\n}\n"
    : "+f"(d[0]),"+f"(d[1]),"+f"(d[2]),"+f"(d[3]),"+f"(d[4]),"+f"(d[5]),"+f"(d[6]),"+f"(d[7]),"+f"(d[8]),"+f"(d[9]),"+f"(d[10]),"+f"(d[11]),"+f"(d[12]),"+f"(d[13]),"+f"(d[14]),"+f"(d[15]),"+f"(d[16]),"+f"(d[17]),"+f"(d[18]),"+f"(d[19]),"+f"(d[20]),"+f"(d[21]),"+f"(d[22]),"+f"(d[23]),"+f"(d[24]),"+f"(d[25]),"+f"(d[26]),"+f"(d[27]),"+f"(d[28]),"+f"(d[29]),"+f"(d[30]),"+f"(d[31]),"+f"(d[32]),"+f"(d[33]),"+f"(d[34]),"+f"(d[35]),"+f"(d[36]),"+f"(d[37]),"+f"(d[38]),"+f"(d[39]),"+f"(d[40]),"+f"(d[41]),"+f"(d[42]),"+f"(d[43]),"+f"(d[44]),"+f"(d[45]),"+f"(d[46]),"+f"(d[47]),"+f"(d[48]),"+f"(d[49]),"+f"(d[50]),"+f"(d[51]),"+f"(d[52]),"+f"(d[53]),"+f"(d[54]),"+f"(d[55]),"+f"(d[56]),"+f"(d[57]),"+f"(d[58]),"+f"(d[59]),"+f"(d[60]),"+f"(d[61]),"+f"(d[62]),"+f"(d[63]),"+f"(d[64]),"+f"(d[65]),"+f"(d[66]),"+f"(d[67]),"+f"(d[68]),"+f"(d[69]),"+f"(d[70]),"+f"(d[71]),"+f"(d[72]),"+f"(d[73]),"+f"(d[74]),"+f"(d[75]),"+f"(d[76]),"+f"(d[77]),"+f"(d[78]),"+f"(d[79]),"+f"(d[80]),"+f"(d[81]),"+f"(d[82]),"+f"(d[83]),"+f"(d[84]),"+f"(d[85]),"+f"(d[86]),"+f"(d[87]),"+f"(d[88]),"+f"(d[89]),"+f"(d[90]),"+f"(d[91]),"+f"(d[92]),"+f"(d[93]),"+f"(d[94]),"+f"(d[95]),"+f"(d[96]),"+f"(d[97]),"+f"(d[98]),"+f"(d[99]),"+f"(d[100]),"+f"(d[101]),"+f"(d[102]),"+f"(d[103]),"+f"(d[104]),"+f"(d[105]),"+f"(d[106]),"+f"(d[107]),"+f"(d[108]),"+f"(d[109]),"+f"(d[110]),"+f"(d[111])
    : "r"(a0), "r"(a1), "r"(a2), "r"(a3), "r"(blo), "n"(OFF), "n"(BHI), "n"(ACC));
}
template <int OFF, uint32_t BHI, int ACC>
__device__ __forceinline__ void wgmma_rs56(float (&d)[28], uint32_t a0, uint32_t a1, uint32_t a2, uint32_t a3, uint32_t blo) {
  asm volatile("{\n.reg .pred p;\n.reg .b32 l;\n.reg .b64 bd;\nsetp.ne.b32 p, %35, 0;\nadd.u32 l, %32, %33;\nmov.b64 bd, {l, %34};\n"
    "wgmma.mma_async.sync.aligned.m64n56k16.f32.bf16.bf16 {%0,%1,%2,%3,%4,%5,%6,%7,%8,%9,%10,%11,%12,%13,%14,%15,%16,%17,%18,%19,%20,%21,%22,%23,%24,%25,%26,%27}, {%28,%29,%30,%31}, bd, p, 1, 1, 1;\n}\n"
    : "+f"(d[0]),"+f"(d[1]),"+f"(d[2]),"+f"(d[3]),"+f"(d[4]),"+f"(d[5]),"+f"(d[6]),"+f"(d[7]),"+f"(d[8]),"+f"(d[9]),"+f"(d[10]),"+f"(d[11]),"+f"(d[12]),"+f"(d[13]),"+f"(d[14]),"+f"(d[15]),"+f"(d[16]),"+f"(d[17]),"+f"(d[18]),"+f"(d[19]),"+f"(d[20]),"+f"(d[21]),"+f"(d[22]),"+f"(d[23]),"+f"(d[24]),"+f"(d[25]),"+f"(d[26]),"+f"(d[27])
    : "r"(a0), "r"(a1), "r"(a2), "r"(a3), "r"(blo), "n"(OFF), "n"(BHI), "n"(ACC));
}

__device__ __forceinline__ void st128(uint4* p, uint32_t a, uint32_t b, uint32_t c, uint32_t d) {
  asm volatile("{\n.reg .b128 v;\n.reg .b64 lo, hi;\nmov.b64 lo, {%1, %2};\nmov.b64 hi, {%3, %4};\nmov.b128 v, {lo, hi};\n"
               "st.relaxed.gpu.global.b128 [%0], v;\n}" ::"l"(p), "r"(a), "r"(b), "r"(c), "r"(d) : "memory");
}
__device__ __forceinline__ void ld128(const uint4* p, uint32_t* r) {
  asm volatile("{\n.reg .b128 v;\n.reg .b64 lo, hi;\nld.relaxed.gpu.global.b128 v, [%4];\nmov.b128 {lo, hi}, v;\n"
               "mov.b64 {%0, %1}, lo;\nmov.b64 {%2, %3}, hi;\n}" : "=r"(r[0]), "=r"(r[1]), "=r"(r[2]), "=r"(r[3]) : "l"(p) : "memory");
}

template <int OFF, uint32_t BHI, int ACC>
__device__ __forceinline__ void wgmma_rs32(float (&d)[16], uint32_t a0, uint32_t a1, uint32_t a2, uint32_t a3, uint32_t blo) {
  asm volatile("{\n.reg .pred p;\n.reg .b32 l;\n.reg .b64 bd;\nsetp.ne.b32 p, %23, 0;\nadd.u32 l, %20, %21;\nmov.b64 bd, {l, %22};\n"
    "wgmma.mma_async.sync.aligned.m64n32k16.f32.bf16.bf16 {%0,%1,%2,%3,%4,%5,%6,%7,%8,%9,%10,%11,%12,%13,%14,%15}, {%16,%17,%18,%19}, bd, p, 1, 1, 0;\n}\n"
    : "+f"(d[0]),"+f"(d[1]),"+f"(d[2]),"+f"(d[3]),"+f"(d[4]),"+f"(d[5]),"+f"(d[6]),"+f"(d[7]),"+f"(d[8]),"+f"(d[9]),"+f"(d[10]),"+f"(d[11]),"+f"(d[12]),"+f"(d[13]),"+f"(d[14]),"+f"(d[15])
    : "r"(a0), "r"(a1), "r"(a2), "r"(a3), "r"(blo), "n"(OFF), "n"(BHI), "n"(ACC));
}
template <int OFF, uint32_t BHI, int ACC>
__device__ __forceinline__ void wgmma_rs24(float (&d)[12], uint32_t a0, uint32_t a1, uint32_t a2, uint32_t a3, uint32_t blo) {
  asm volatile("{\n.reg .pred p;\n.reg .b32 l;\n.reg .b64 bd;\nsetp.ne.b32 p, %19, 0;\nadd.u32 l, %16, %17;\nmov.b64 bd, {l, %18};\n"
    "wgmma.mma_async.sync.aligned.m64n24k16.f32.bf16.bf16 {%0,%1,%2,%3,%4,%5,%6,%7,%8,%9,%10,%11}, {%12,%13,%14,%15}, bd, p, 1, 1, 1;\n}\n"
    : "+f"(d[0]),"+f"(d[1]),"+f"(d[2]),"+f"(d[3]),"+f"(d[4]),"+f"(d[5]),"+f"(d[6]),"+f"(d[7]),"+f"(d[8]),"+f"(d[9]),"+f"(d[10]),"+f"(d[11])
    : "r"(a0), "r"(a1), "r"(a2), "r"(a3), "r"(blo), "n"(OFF), "n"(BHI), "n"(ACC));
}
template <int OFF, uint32_t BHI, int ACC>
__device__ __forceinline__ void wgmma_rs16(float (&d)[8], uint32_t a0, uint32_t a1, uint32_t a2, uint32_t a3, uint32_t blo) {
  asm volatile("{\n.reg .pred p;\n.reg .b32 l;\n.reg .b64 bd;\nsetp.ne.b32 p, %15, 0;\nadd.u32 l, %12, %13;\nmov.b64 bd, {l, %14};\n"
    "wgmma.mma_async.sync.aligned.m64n16k16.f32.bf16.bf16 {%0,%1,%2,%3,%4,%5,%6,%7}, {%8,%9,%10,%11}, bd, p, 1, 1, 1;\n}\n"
    : "+f"(d[0]),"+f"(d[1]),"+f"(d[2]),"+f"(d[3]),"+f"(d[4]),"+f"(d[5]),"+f"(d[6]),"+f"(d[7])
    : "r"(a0), "r"(a1), "r"(a2), "r"(a3), "r"(blo), "n"(OFF), "n"(BHI), "n"(ACC));
}

constexpr int A_R1 = 0;
constexpr int A_R2A = A_R1 + 2624, A_R2B = A_R2A + 768, A_R3A = A_R2B + 768, A_R3B = A_R3A + 528;
constexpr int A_K1024 = A_R3B + 528;
constexpr int A_W5 = A_K1024 + 16;
constexpr int A_W3 = A_W5 + 4096;
constexpr int A_W9 = A_W3 + 4112;
constexpr int A_W7 = A_W9 + 2048;
constexpr int A_V  = A_W7 + 2048;
constexpr int A_UB = A_V + 2048;
constexpr int A_STG = A_UB + 5248;
constexpr int A_Y2 = A_STG, A_Y3 = A_Y2 + 6528, A_YB = A_Y3 + 4352;
constexpr int A_REC = A_STG + 4 * 4352;
constexpr int A_CH = A_REC + 8192;
static_assert(A_W5 % 16 == 0 && A_UB % 16 == 0 && A_CH % 16 == 0 && A_YB + 4096 <= A_REC, "layout");

struct cf { float x, y; };
__device__ __forceinline__ cf cmul(cf a, cf b) { cf r; r.x = fmaf(a.x, b.x, -a.y * b.y); r.y = fmaf(a.x, b.y, a.y * b.x); return r; }
__device__ __forceinline__ cf cexp_l(float lr, float li, float l) {
  float mag; asm("ex2.approx.ftz.f32 %0, %1;" : "=f"(mag) : "f"((lr * l) * 1.4426950408889634f));
  const float th = li * l;
  const float k = (fmaf(th, 0.15915494f, 12582912.f)) - 12582912.f;
  float ph = fmaf(th, 0.15915494f, -k);
  ph = fmaf(th, 6.4206383e-9f, ph) * 6.2831853f;
  cf r; r.x = mag * __cosf(ph); r.y = mag * __sinf(ph); return r;
}
__device__ __forceinline__ void sts16(uint32_t a, uint32_t v) { asm volatile("st.shared.u16 [%0], %1;" ::"r"(a), "h"((uint16_t)v) : "memory"); }
__device__ __forceinline__ void sts32(uint32_t a, uint32_t v) { asm volatile("st.shared.u32 [%0], %1;" ::"r"(a), "r"(v) : "memory"); }
__device__ __forceinline__ void sts64(uint32_t a, uint32_t v0, uint32_t v1) { asm volatile("st.shared.v2.u32 [%0], {%1, %2};" ::"r"(a), "r"(v0), "r"(v1) : "memory"); }
__device__ __forceinline__ void sts128(uint32_t a, uint32_t v0, uint32_t v1, uint32_t v2, uint32_t v3) {
  asm volatile("st.shared.v4.u32 [%0], {%1, %2, %3, %4};" ::"r"(a), "r"(v0), "r"(v1), "r"(v2), "r"(v3) : "memory");
}
__device__ __forceinline__ uint32_t lds32(uint32_t a) { uint32_t v; asm volatile("ld.shared.u32 %0, [%1];" : "=r"(v) : "r"(a) : "memory"); return v; }
__device__ __forceinline__ uint4 lds128(uint32_t a) {
  uint4 v; asm volatile("ld.shared.v4.u32 {%0, %1, %2, %3}, [%4];" : "=r"(v.x), "=r"(v.y), "=r"(v.z), "=r"(v.w) : "r"(a) : "memory"); return v;
}
__device__ __forceinline__ void ldsm4(uint32_t* r, uint32_t a) {
  asm volatile("ldmatrix.sync.aligned.m8n8.x4.shared.b16 {%0,%1,%2,%3}, [%4];" : "=r"(r[0]), "=r"(r[1]), "=r"(r[2]), "=r"(r[3]) : "r"(a) : "memory");
}
__device__ __forceinline__ void mma16816(float* d, const uint32_t* a, uint32_t b0, uint32_t b1) {
  asm volatile("mma.sync.aligned.m16n8k16.row.col.f32.bf16.bf16.f32 {%0,%1,%2,%3}, {%4,%5,%6,%7}, {%8,%9}, {%0,%1,%2,%3};"
               : "+f"(d[0]), "+f"(d[1]), "+f"(d[2]), "+f"(d[3]) : "r"(a[0]), "r"(a[1]), "r"(a[2]), "r"(a[3]), "r"(b0), "r"(b1));
}
__device__ __forceinline__ uint32_t hsub2_bf(uint32_t a, uint32_t b) { uint32_t r; asm("sub.rn.bf16x2 %0, %1, %2;" : "=r"(r) : "r"(a), "r"(b)); return r; }
__device__ __forceinline__ void bar_sync(int id, int n) { asm volatile("bar.sync %0, %1;" ::"r"(id), "r"(n) : "memory"); }

template <int S> struct F1B { static constexpr int c = S / 4 + ((S & 3) == 3 ? 0 : 0), cc = (16 * S) / 64, ks = (64 * cc - (16 * S - 48)) / 16, off = (A_UB + 2 * ks * 656 + (9 - cc) * 16) / 16; };

template <int NS>
__device__ __forceinline__ void load_quads(uint32_t* q, uint32_t addr) {
#pragma unroll
  for (int i = 0; i < NS; i++) {
    q[4 * i] = lds32(addr + i * 64); q[4 * i + 1] = lds32(addr + i * 64 + 32);
    q[4 * i + 2] = i ? q[4 * i - 3] : lds32(addr - 32);
    q[4 * i + 3] = q[4 * i];
  }
#pragma unroll
  for (int i = 0; i < 4 * NS; i++) asm volatile("" : "+r"(q[i]));
}
template <int S0, int NS>
__device__ __forceinline__ void f1_steps(float (&acc)[16], const uint32_t* a, uint32_t blo) {
  if constexpr (NS > 0) {
    wgmma_rs32<F1B<S0>::off, 8, S0 != 0>(acc, a[0], a[1], a[2], a[3], blo);
    f1_steps<S0 + 1, NS - 1>(acc, a + 4, blo);
  }
}
template <int S0, int NS, int BASE, int FIRST>
__device__ __forceinline__ void s2_steps(float (&acc)[12], const uint32_t* a, uint32_t blo) {
  if constexpr (NS > 0) {
    wgmma_rs24<BASE / 16 + (112 - 16 * S0), 64, !(FIRST && S0 == 0)>(acc, a[0], a[1], a[2], a[3], blo);
    s2_steps<S0 + 1, NS - 1, BASE, FIRST>(acc, a + 4, blo);
  }
}
template <int S0, int NS, int BASE, int FIRST>
__device__ __forceinline__ void s3_steps(float (&acc)[8], const uint32_t* a, uint32_t blo) {
  if constexpr (NS > 0) {
    wgmma_rs16<BASE / 16 + (48 - 16 * S0), 64, !(FIRST && S0 == 0)>(acc, a[0], a[1], a[2], a[3], blo);
    s3_steps<S0 + 1, NS - 1, BASE, FIRST>(acc, a + 4, blo);
  }
}

__device__ __forceinline__ void phase_a(
        unsigned char* sm, const uint32_t bar_rec, const uint32_t ep_addr,
        const __nv_bfloat16* __restrict__ x, const uint32_t* __restrict__ are, const uint32_t* __restrict__ aim,
        const uint32_t* __restrict__ bre, const uint32_t* __restrict__ bim, const uint32_t* __restrict__ cre,
        const uint32_t* __restrict__ cim, const unsigned short* __restrict__ logdt, const unsigned short* __restrict__ dskip,
        const uint4* __restrict__ wgate, const uint4* __restrict__ wup, const uint4* __restrict__ wdown) {
  const uint32_t sb = s2u(sm);
  const int tid = threadIdx.x, wg = tid >> 7, warp = tid >> 5, lane = tid & 31, wq = warp & 3, t128 = tid & 127;
  const int blk = blockIdx.x;
  const bool conv = blk < 112;

  uint2 xr[4];
  {
    const uint2* p = (const uint2*)(x + (size_t)(blk * 16 + warp) * DM);
    xr[0] = __ldg(p + lane); xr[1] = __ldg(p + 32 + lane); xr[2] = __ldg(p + 64 + lane);
    xr[3] = lane < 16 ? __ldg(p + 96 + lane) : make_uint2(0, 0);
  }
  const int ch = conv ? blk * 4 + wg : 0;
  const uint32_t cb = sb + wg * A_CH;
  uint32_t prm[6];
  {
    const int i = ch * 128 + t128;
    prm[0] = __ldg(are + i); prm[1] = __ldg(aim + i); prm[2] = __ldg(bre + i); prm[3] = __ldg(bim + i); prm[4] = __ldg(cre + i); prm[5] = __ldg(cim + i);
  }
  const uint32_t ldt = __ldg(logdt + ch);
  uint32_t cnt0 = 0;
  if (tid == 0) cnt0 = __ldcg(&g_cnt1);
#pragma unroll
  for (int i = 0; i < 4; i++) if (i < 3 || t128 < (A_W5 + 1024) / 16 - 384) sts128(cb + (i * 128 + t128) * 16, 0, 0, 0, 0);
  if (t128 < 65) sts128(cb + (t128 < 64 ? A_W3 + t128 * 16 : A_W9), 0, 0, 0, 0);
  if (t128 < 72) sts128(cb + A_UB + (t128 / 9) * 656 + (t128 % 9) * 16, 0, 0, 0, 0);
  {
    float s = 0.f, q = 0.f;
#pragma unroll
    for (int i = 0; i < 4; i++) {
      const float a = bf_lo(xr[i].x), b = bf_hi(xr[i].x), c = bf_lo(xr[i].y), d = bf_hi(xr[i].y);
      s += (a + b) + (c + d);
      q = fmaf(a, a, q); q = fmaf(b, b, q); q = fmaf(c, c, q); q = fmaf(d, d, q);
    }
#pragma unroll
    for (int o = 16; o; o >>= 1) { s += __shfl_xor_sync(~0u, s, o); q += __shfl_xor_sync(~0u, q, o); }
    const float mean = s * (1.f / DM);
    const float var = fmaxf(fmaf(-mean, mean, q * (1.f / DM)), 0.f);
    const float rs = __frcp_rn(rbf(__fsqrt_rn(rbf(rbf(var) + 1e-5f))));
    const uint32_t mm = pack_bf16(mean, mean);
    const uint32_t tu = sb + A_REC + (warp >> 3) * A_CH + (warp & 7) * 912 + lane * 8, tx = tu + 2 * A_CH;
#pragma unroll
    for (int i = 0; i < 4; i++) {
      if (i < 3 || lane < 16) {
        const uint32_t d0 = hsub2_bf(xr[i].x, mm), d1 = hsub2_bf(xr[i].y, mm);
        sts64(tu + i * 256, pack_bf16(bf_lo(d0) * rs, bf_hi(d0) * rs), pack_bf16(bf_lo(d1) * rs, bf_hi(d1) * rs));
        sts64(tx + i * 256, xr[i].x, xr[i].y);
      }
    }
  }
  if (tid == 0) sts32(ep_addr, (cnt0 >> 7) + 1u);
  if (tid == 320) TR(0, 1);
  auto publish_rows = [&]() {
    bar_sync(5, 512);
    uint4* dst = g_ux + ((size_t)(warp * 8 + (lane >> 2)) * 128 + blk) * 4 + ((lane ^ (blk >> 1)) & 3);
#pragma unroll
    for (int i = 0; i < 4; i++) {
      if (i < 3 || warp < 8) {
        uint32_t r[4];
        asm volatile("ldmatrix.sync.aligned.m8n8.x4.trans.shared.b16 {%0,%1,%2,%3}, [%4];" : "=r"(r[0]), "=r"(r[1]), "=r"(r[2]), "=r"(r[3])
                     : "r"(sb + A_REC + (lane >> 3) * A_CH + (lane & 7) * 912 + (warp + 16 * i) * 16) : "memory");
        dst[i * 65536] = make_uint4(r[0], r[1], r[2], r[3]);
      }
    }
    if (warp != 0) asm volatile("bar.arrive 6, 512;" ::: "memory");
  };
  auto release_rows = [&]() {
    if (warp == 0) {
      bar_sync(6, 512);
      if (lane == 0) { asm volatile("red.release.gpu.global.add.u32 [%0], 1;" ::"l"(&g_cnt1) : "memory"); TR(0, 8); }
      __syncwarp();
    }
  };

  if (!conv) {
    publish_rows();
    release_rows();
    const int a = blk - 112, mat = a >> 3, j = a & 7;
    float s[8];
#pragma unroll
    for (int k = 0; k < 8; k++) s[k] = 0.f;
    if (lane < 28) {
      const uint4* src = (mat ? wup : wgate) + j * 28 + lane + (size_t)warp * 224;
#pragma unroll
      for (int hb = 0; hb < 2; hb++) {
        uint4 v[14];
#pragma unroll
        for (int r = 0; r < 14; r++) v[r] = __ldg(src + (size_t)(hb * 14 + r) * 16 * 224);
#pragma unroll
        for (int r = 0; r < 14; r++) {
          s[0] += bf_lo(v[r].x); s[1] += bf_hi(v[r].x); s[2] += bf_lo(v[r].y); s[3] += bf_hi(v[r].y);
          s[4] += bf_lo(v[r].z); s[5] += bf_hi(v[r].z); s[6] += bf_lo(v[r].w); s[7] += bf_hi(v[r].w);
        }
      }
      float4* red = (float4*)(sm + A_STG + warp * 896 + lane * 32);
      red[0] = make_float4(s[0], s[1], s[2], s[3]); red[1] = make_float4(s[4], s[5], s[6], s[7]);
    }
    bar_sync(5, 512);
    if (tid < 224) {
      float t = 0.f;
#pragma unroll
      for (int w = 0; w < 16; w++) t += *(const float*)(sm + A_STG + w * 896 + tid * 4);
      const float hi = rbf(t), mid = rbf(t - hi), lo = rbf(t - hi - mid);
      const int q = tid / 112, n = tid % 112 + 112 * mat;
      __nv_bfloat16* dst = (__nv_bfloat16*)(g_cimg + (j * 2 + q) * 224 + (n >> 3) * 8) + (n & 7);
      dst[0] = __float2bfloat16_rn(hi); dst[8] = __float2bfloat16_rn(mid); dst[16] = __float2bfloat16_rn(lo);
#pragma unroll
      for (int k = 3; k < 8; k++) dst[8 * k] = __float2bfloat16_rn(0.f);
    }
    if (tid == 320) TR(0, 10);
    return;
  }

  const int g = lane >> 2, t = lane & 3;
  const int wr = (wq + wg) & 3;
  uint4 wv[6];
  auto w_src = [&](int i) -> const uint4* {
    if (i < 4) return (blk < 56 ? wgate : wup) + (blk % 56) * 4 + (lane & 3) + (size_t)(i * 128 + warp * 8 + (lane >> 2)) * 224;
    const int it = warp + 16 * (i - 4);
    return wdown + (size_t)(blk * 16 + (it / 14) * 8 + (lane >> 2)) * 56 + (it % 14) * 4 + (lane & 3);
  };
  auto w_on = [&](int i) { return i == 3 ? warp < 8 : i == 5 ? warp < 12 : true; };
  {
    const uint32_t stg = cb + A_STG + wq * 4352;
    const float dt = rbf(expf(__uint_as_float(ldt << 16)));
    float lr[2], li[2];
    cf bq[2], b0[2], b4[2];
    uint32_t bf[48];
#pragma unroll
    for (int m = 0; m < 2; m++) {
      lr[m] = dt * (m ? bf_hi(prm[0]) : bf_lo(prm[0]));
      li[m] = dt * (m ? bf_hi(prm[1]) : bf_lo(prm[1]));
    }
    {
      cf b[2], z[2];
#pragma unroll
      for (int m = 0; m < 2; m++) {
        cf db, c;
        db.x = dt * (m ? bf_hi(prm[2]) : bf_lo(prm[2])); db.y = -dt * (m ? bf_hi(prm[3]) : bf_lo(prm[3]));
        c.x = m ? bf_hi(prm[4]) : bf_lo(prm[4]); c.y = -(m ? bf_hi(prm[5]) : bf_lo(prm[5]));
        b[m] = cmul(c, db);
        z[m] = cexp_l(lr[m], -li[m], 1.f);
        bq[m] = cexp_l(lr[m], -li[m], 256.f);
      }
#pragma unroll
      for (int i = 0; i < 8; i++) {
        sts64(stg + i * 272 + lane * 8, pack_bf16(b[0].x, b[0].y), pack_bf16(b[1].x, b[1].y));
        if (!(i & 1)) {
          cf e0 = cmul(b[0], bq[0]), e1 = cmul(b[1], bq[1]);
          sts64(stg + (8 + i / 2) * 272 + lane * 8, pack_bf16(e0.x, e0.y), pack_bf16(e1.x, e1.y));
          if (i == 0) { b0[0] = e0; b0[1] = e1; }
          if (i == 4) { b4[0] = e0; b4[1] = e1; }
        }
        if (i < 7) { b[0] = cmul(b[0], z[0]); b[1] = cmul(b[1], z[1]); }
        if (i == 1) publish_rows();
      }
#pragma unroll
      for (int i = 0; i < 7; i++) {
        b0[0] = cmul(b0[0], bq[0]); b0[1] = cmul(b0[1], bq[1]);
        sts64(stg + (i < 2 ? 12 + 2 * i : i - 2) * 272 + lane * 8, pack_bf16(b0[0].x, b0[0].y), pack_bf16(b0[1].x, b0[1].y));
        if (i < 2) {
          b4[0] = cmul(b4[0], bq[0]); b4[1] = cmul(b4[1], bq[1]);
          sts64(stg + (13 + 2 * i) * 272 + lane * 8, pack_bf16(b4[0].x, b4[0].y), pack_bf16(b4[1].x, b4[1].y));
        }
        if (i == 1) {
          __syncwarp();
#pragma unroll
          for (int n = 0; n < 2; n++)
#pragma unroll
            for (int k2 = 0; k2 < 4; k2++) ldsm4(bf + n * 16 + k2 * 4, stg + (n * 8 + (lane & 7)) * 272 + k2 * 64 + (lane >> 3) * 16);
          __syncwarp();
        }
      }
    }
    __syncwarp();
#pragma unroll
    for (int k2 = 0; k2 < 4; k2++) ldsm4(bf + 32 + k2 * 4, stg + (lane & 7) * 272 + k2 * 64 + (lane >> 3) * 16);
    release_rows();
    if (!(lane & 1)) {
#pragma unroll
      for (int i = 0; i < 6; i++) if (w_on(i)) asm volatile("prefetch.global.L2 [%0];" ::"l"(w_src(i)));
    }
    if (tid == 320) TR(0, 16);
    float c[6][4];
#pragma unroll
    for (int i = 0; i < 6; i++) { c[i][0] = 0.f; c[i][1] = 0.f; c[i][2] = 0.f; c[i][3] = 0.f; }
    cf p[2], v[2];
    p[0] = cexp_l(lr[0], li[0], 8.f); p[1] = cexp_l(lr[1], li[1], 8.f);
    v[0].x = 1.f; v[0].y = 0.f; v[1] = v[0];
#pragma unroll
    for (int mt = 0; mt < 2; mt++) {
      __syncwarp();
#pragma unroll
      for (int i = 0; i < 16; i++) {
        sts64(stg + i * 272 + lane * 8, pack_bf16(v[0].x, v[0].y), pack_bf16(v[1].x, v[1].y));
        if (mt == 0 && i == 0) { v[0] = p[0]; v[1] = p[1]; }
        else if (mt == 0 || i < 15) { v[0] = cmul(v[0], p[0]); v[1] = cmul(v[1], p[1]); }
      }
      __syncwarp();
      if (mt == 1 && tid == 160) {
        const uint32_t tgt = lds32(ep_addr) * 128u;
        uint32_t cv; int it = 0;
        do { asm volatile("ld.acquire.gpu.global.u32 %0, [%1];" : "=r"(cv) : "l"(&g_cnt1) : "memory"); } while ((int)(cv - tgt) < 0 && ++it < 200000);
        asm volatile("fence.proxy.async;" ::: "memory");
        TR(0, 9);
        mbar_expect(bar_rec, 32768);
        for (int c2 = 0; c2 < 4; c2++) bulk_ld(sb + c2 * A_CH + A_REC, g_ux + (size_t)(blk * 4 + c2) * 512, 8192, bar_rec);
      }
#pragma unroll
      for (int ks = 0; ks < 8; ks++) {
        uint32_t a[4];
        ldsm4(a, stg + (lane & 15) * 272 + ks * 32 + (lane >> 4) * 16);
#pragma unroll
        for (int n = 0; n < 3; n++) mma16816(c[n * 2 + mt], a, bf[n * 16 + ks * 2], bf[n * 16 + ks * 2 + 1]);
      }
    }
    __syncwarp();
#pragma unroll
    for (int i = 0; i < 6; i++)
      sts128(stg + i * 512 + lane * 16, __float_as_uint(c[i][0]), __float_as_uint(c[i][1]), __float_as_uint(c[i][2]), __float_as_uint(c[i][3]));
#pragma unroll
    for (int i = 0; i < 6; i++) if (w_on(i)) wv[i] = __ldg(w_src(i));
    bar_sync(1 + wg, 128);
    if (tid == 320) TR(0, 2);
#pragma unroll
    for (int rep = 0; rep < 2; rep++) {
      const int qd = rep ? 2 + wr : 3 - wr;
      if (rep == 0 || wr >= 2) {
        float s[4] = {0.f, 0.f, 0.f, 0.f};
#pragma unroll
        for (int w = 0; w < 4; w++) {
          uint4 u4 = lds128(cb + A_STG + w * 4352 + qd * 512 + lane * 16);
          s[0] += __uint_as_float(u4.x); s[1] += __uint_as_float(u4.y); s[2] += __uint_as_float(u4.z); s[3] += __uint_as_float(u4.w);
        }
#pragma unroll
        for (int hf = 0; hf < 2; hf++) {
          const int j = (qd & 1) * 16 + g + 8 * hf;
          const uint32_t pk = pack_bf16(s[2 * hf + 1], s[2 * hf]);
          const uint32_t v0 = pk >> 16, v1 = pk & 0xFFFFu, v00 = v0 * 0x10001u;
          if (rep == 1) {
            if (t < 2) {
#pragma unroll
              for (int e = 0; e < 2; e++) {
                const int lam = 128 + 32 * (2 * t + e) + j, mu = lam >> 1;
                const uint32_t val = e ? v1 : v0;
                uint32_t a = cb + ((lam & 1) ? A_R3B : A_R3A) + mu * 4;
                if (lam == 128) { a = cb + A_R2A + 128 * 4; sts32(cb + A_K1024, val << 16); }
                sts16(a, val); sts16(a + 6, val);
              }
            } else if (t == 2 && j == 0) { sts16(cb + A_R3A + 128 * 4, v0); }
          } else if (qd < 2) {
            const uint32_t a = cb + A_R1 + (62 + 8 * j + 2 * t) * 4;
            sts16(a, v0); sts32(a + 4, pk); sts16(a + 10, v1);
          } else if (t < 2) {
            const int L = 256 + 8 * j + 4 * t;
            const uint32_t a = cb + A_R1 + (62 + L) * 4;
            if (L > 256) { sts16(a - 4, v0); sts32(a, v00); } else sts16(a, v0);
            sts32(a + 4, v00); sts32(a + 8, pk); sts16(a + 14, v1);
          } else {
            const int mu = 64 + 32 * (t - 2) + j;
            if (mu == 64) {
              const uint32_t a = cb + A_R1 + (62 + 512) * 4;
              sts16(a - 4, v0); sts32(a, v00); sts32(a + 4, v00); sts32(a + 8, v00); sts16(a + 14, v0);
            } else { sts16(cb + A_R2A + mu * 4, v0); sts16(cb + A_R2A + mu * 4 + 6, v0); }
            sts16(cb + A_R2B + mu * 4, v1); sts16(cb + A_R2B + mu * 4 + 6, v1);
          }
        }
      }
    }
  }
  {
    const int ngg = (blk % 56) * 4 + (lane & 3), j = ngg / 28, q = (ngg % 28) / 14, ng = ngg % 14 + (blk < 56 ? 0 : 14);
    uint4* dst = g_wimg + (size_t)j * 37632 + q * 14 * 896 + ng * 32 + (warp >> 2) * 896 + (warp & 3) * 8 + (lane >> 2);
#pragma unroll
    for (int i = 0; i < 4; i++) if (w_on(i)) dst[i * 4 * 896] = wv[i];
#pragma unroll
    for (int i = 4; i < 6; i++) {
      const int it = warp + 16 * (i - 4), n2 = (it % 14) * 4 + (lane & 3), k = (blk % 7) * 16 + (it / 14) * 8 + (lane >> 2);
      if (w_on(i)) g_wimg[(size_t)(blk / 14) * 37632 + 25088 + ((n2 / 7) * 2 + (blk / 7) % 2) * 784 + (n2 % 7) * 112 + k] = wv[i];
    }
  }
  if (tid == 320) TR(0, 3);

  const int bk = wr * 32 + lane;
  uint32_t xt[8], ud[8];
  {
    mbar_wait(bar_rec, 0);
    if (tid == 320) TR(0, 4);
    uint4 r[4];
#pragma unroll
    for (int i = 0; i < 4; i++) r[i] = lds128(cb + A_REC + bk * 64 + ((i ^ (bk >> 1)) & 3) * 16);
    const uint32_t ua = cb + A_UB + ((2 * bk) & 7) * 656 + ((bk >> 2) + 9) * 16;
    sts128(ua, r[0].x, r[1].x, r[2].x, r[3].x);
    sts128(ua + 656, r[0].y, r[1].y, r[2].y, r[3].y);
    if (bk <= 96) {
      const bool neg = bk == 96;
      const int bp = neg ? -1 : bk;
      uint32_t h[4];
      h[0] = lds32(cb + A_REC + ((bp - 1) & 127) * 64 + ((2 ^ ((bp - 1) >> 1)) & 3) * 16 + 4);
      h[1] = lds32(cb + A_REC + ((bp - 1) & 127) * 64 + ((3 ^ ((bp - 1) >> 1)) & 3) * 16 + 4);
      h[2] = lds32(cb + A_REC + (bp + 1) * 64 + ((0 ^ ((bp + 1) >> 1)) & 3) * 16);
      h[3] = lds32(cb + A_REC + (bp + 1) * 64 + ((1 ^ ((bp + 1) >> 1)) & 3) * 16);
      if (bp <= 0) { h[0] = 0; h[1] = 0; }
      const uint32_t wd[12] = {h[0], h[1], neg ? 0 : r[0].x, neg ? 0 : r[1].x, neg ? 0 : r[2].x, neg ? 0 : r[3].x,
                               neg ? 0 : r[0].y, neg ? 0 : r[1].y, neg ? 0 : r[2].y, neg ? 0 : r[3].y, h[2], h[3]};
      float P[25];
      P[0] = 0.f;
#pragma unroll
      for (int i = 0; i < 12; i++) { P[2 * i + 1] = P[2 * i] + bf_lo(wd[i]); P[2 * i + 2] = P[2 * i + 1] + bf_hi(wd[i]); }
#define WIN(i, hw) (P[(i) + 5 + (hw)] - P[(i) + 4 - (hw)])
#define WPK(i, hw) pack_bf16(WIN(i, hw), WIN((i) + 1, hw))
      const int tp = 2 * bp;
      const uint32_t a3 = cb + A_W3 + (tp + 64) * 16 + 8, a5 = cb + A_W5 + (tp + 64) * 16;
      if (!neg) sts64(a3, WPK(0, 1), WPK(2, 1));
      if (!neg) sts128(a3 + 8, WPK(4, 1), WPK(6, 1), WPK(8, 1), WPK(10, 1));
      sts64(a3 + 24, WPK(12, 1), WPK(14, 1));
      sts128(a5, WPK(0, 2), WPK(2, 2), WPK(4, 2), WPK(6, 2));
      sts128(a5 + 16, WPK(8, 2), WPK(10, 2), WPK(12, 2), WPK(14, 2));
      if (bp < 64) {
        if (!neg) sts128(cb + A_W7 + 1024 + bp * 16, WPK(0, 3), WPK(2, 3), WPK(4, 3), WPK(6, 3));
        if (bp < 63) {
          sts128(cb + A_W7 + (bp + 1) * 16, WPK(8, 3), WPK(10, 3), WPK(12, 3), WPK(14, 3));
          sts128(cb + A_W9 + (bp + 1) * 16, WPK(0, 4), WPK(2, 4), WPK(4, 4), WPK(6, 4));
          sts128(cb + A_W9 + 1024 + (bp + 1) * 16, WPK(8, 4), WPK(10, 4), WPK(12, 4), WPK(14, 4));
        }
        if (!neg) {
#define VPK(i) pack_bf16(P[(i) + 2] - P[i], P[(i) + 3] - P[(i) + 1])
          sts128(cb + A_V + bp * 32, VPK(0), VPK(2), VPK(4), VPK(6));
          sts128(cb + A_V + bp * 32 + 16, VPK(8), VPK(10), VPK(12), VPK(14));
        }
      }
    }
  }
  asm volatile("fence.proxy.async.shared::cta;" ::: "memory");
  bar_sync(1 + wg, 128);
  if (tid == 320) TR(0, 5);

  {
    const uint32_t cbu = __shfl_sync(~0u, cb, 0);
    const uint32_t blo_k = ((cbu & 0x3FFFF) >> 4) | (41u << 16);
    const uint32_t blo_n = ((cbu & 0x3FFFF) >> 4) | (8u << 16);
    const uint32_t tb = cb + (16 * wq + g - 2 * t) * 4;
    float y1[16], y2[12], y3[8];
    const uint32_t dk16 = __ldg(dskip + ch);
    uint32_t qa[32], qb[32];
    const uint32_t t1 = tb + A_R1 + (62 - 48) * 4;
    load_quads<4>(qa, tb + A_R3A + 17 * 4); load_quads<4>(qa + 16, tb + A_R3B + 16 * 4);
    wg_fence();
    s3_steps<0, 4, A_W9, 1>(y3, qa, blo_n); s3_steps<0, 4, A_W7, 0>(y3, qa + 16, blo_n);
    wg_commit();
    load_quads<8>(qb, tb + A_R2A + 16 * 4);
    wg_fence(); s2_steps<0, 8, A_W5, 1>(y2, qb, blo_n); wg_commit();
    wg_wait<1>(); load_quads<8>(qa, tb + A_R2B + 16 * 4);
    wg_fence(); s2_steps<0, 8, A_W3, 0>(y2, qa, blo_n); wg_commit();
    wg_wait<1>(); load_quads<8>(qb, t1);
    wg_fence(); f1_steps<0, 8>(y1, qb, blo_k); wg_commit();
    wg_wait<1>(); load_quads<8>(qa, t1 + 8 * 64);
    wg_fence(); f1_steps<8, 8>(y1, qa, blo_k); wg_commit();
    reg_fence(y2); reg_fence(y3);
    if (tid == 320) TR(0, 18);
    {
      const float k1024 = __uint_as_float(lds32(cb + A_K1024));
#pragma unroll
      for (int i = 0; i < 2; i++)
#pragma unroll
        for (int hf = 0; hf < 2; hf++) {
          const int idx = 16 * (16 * wq + g + 8 * hf) + 8 * i + 2 * t;
          const uint32_t vv = lds32(cb + A_V + idx * 2);
          sts64(cb + A_Y3 + (idx + 4 * (idx >> 6)) * 4, __float_as_uint(fmaf(k1024, bf_lo(vv), y3[4 * i + 2 * hf])),
                __float_as_uint(fmaf(k1024, bf_hi(vv), y3[4 * i + 2 * hf + 1])));
        }
#pragma unroll
      for (int i = 0; i < 3; i++)
#pragma unroll
        for (int hf = 0; hf < 2; hf++) {
          const int idx = 512 * i + 8 * (16 * wq + g + 8 * hf) + 2 * t;
          sts64(cb + A_Y2 + (idx + 4 * (idx >> 6)) * 4, __float_as_uint(y2[4 * i + 2 * hf]), __float_as_uint(y2[4 * i + 2 * hf + 1]));
        }
    }
    wg_wait<1>(); load_quads<8>(qb, t1 + 16 * 64);
    wg_fence(); f1_steps<16, 8>(y1, qb, blo_k); wg_commit();
    wg_wait<1>(); load_quads<8>(qa, t1 + 24 * 64);
    wg_fence(); f1_steps<24, 8>(y1, qa, blo_k); wg_commit();
    wg_wait<1>(); load_quads<5>(qb, t1 + 32 * 64);
    wg_fence(); f1_steps<32, 5>(y1, qb, blo_k); wg_commit();
    bar_sync(1 + wg, 128);
    float ex[12];
#pragma unroll
    for (int i = 1; i < 4; i++)
#pragma unroll
      for (int k = 0; k < 4; k++) {
        const int aa = 8 * i + 2 * t + (k & 1), b = 16 * wq + g + 8 * (k >> 1);
        float e = __uint_as_float(lds32(cb + A_Y2 + ((aa - 8) * 68 + b) * 4));
        if (i >= 2) e += __uint_as_float(lds32(cb + A_Y3 + ((aa - 16) * 68 + b) * 4));
        ex[4 * (i - 1) + k] = e;
      }
    {
      const uint32_t dk = dk16 * 0x10001u;
#pragma unroll
      for (int i = 0; i < 4; i++) {
        const uint4 r = lds128(cb + A_REC + bk * 64 + ((i ^ (bk >> 1)) & 3) * 16);
        ud[i] = hmul2_bf(r.x, dk); ud[4 + i] = hmul2_bf(r.y, dk); xt[i] = r.z; xt[4 + i] = r.w;
      }
    }
    wg_wait<0>();
    reg_fence(y1);
    if (tid == 320) TR(0, 6);
#pragma unroll
    for (int i = 0; i < 12; i++) y1[4 + i] += ex[i];
#pragma unroll
    for (int i = 0; i < 2; i++) {
      const int mi = lane >> 3, aa = 8 * (2 * i + (mi >> 1)) + (lane & 7);
      asm volatile("stmatrix.sync.aligned.m8n8.x4.trans.shared.b16 [%0], {%1,%2,%3,%4};"
                   ::"r"(cb + A_YB + aa * 128 + (((2 * wq + (mi & 1)) ^ (lane & 7)) << 4)),
                     "r"(pack_bf16(y1[8 * i], y1[8 * i + 1])), "r"(pack_bf16(y1[8 * i + 2], y1[8 * i + 3])),
                     "r"(pack_bf16(y1[8 * i + 4], y1[8 * i + 5])), "r"(pack_bf16(y1[8 * i + 6], y1[8 * i + 7])) : "memory");
    }
  }
  bar_sync(1 + wg, 128);
#pragma unroll
  for (int c = 0; c < 2; c++) {
    const int tau = 2 * bk + c, r = ch & 7;
    const uint4 y = lds128(cb + A_YB + (tau >> 3) * 128 + (((tau ^ (tau >> 3)) & 7) << 4));
    g_himg[(size_t)(tau >> 4) * 7168 + (ch >> 3) * 128 + ((tau >> 3) & 1) * 64 + r * 8 + ((tau & 7) ^ r)] =
        make_uint4(hadd2_bf(xt[4 * c], hadd2_bf(y.x, ud[4 * c])), hadd2_bf(xt[4 * c + 1], hadd2_bf(y.y, ud[4 * c + 1])),
                   hadd2_bf(xt[4 * c + 2], hadd2_bf(y.z, ud[4 * c + 2])), hadd2_bf(xt[4 * c + 3], hadd2_bf(y.w, ud[4 * c + 3])));
  }
  if (tid == 320) TR(0, 7);
}

constexpr int B_SA = 0, B_RING = 114688, B_SLOT = 14848, B_NSLOT = 7;
constexpr int B_CS = B_RING + B_NSLOT * B_SLOT;
constexpr int B_RED = B_CS + 7168;
constexpr int B_BAR = B_RED + 256;
constexpr int B_SMEM = B_BAR + 1024, A_SMEM = 4 * A_CH + 64;

__device__ __forceinline__ uint32_t mapa(uint32_t a, uint32_t r) { uint32_t o; asm("mapa.shared::cluster.u32 %0, %1, %2;" : "=r"(o) : "r"(a), "r"(r)); return o; }
template <class T> __device__ __forceinline__ T* pin(T* p) { asm volatile("" : "+l"(p)); return p; }
__device__ __forceinline__ uint32_t pin(uint32_t v) { asm volatile("" : "+r"(v)); return v; }
template <int Q, int ST>
__device__ __forceinline__ void g1_stage(float (&acc)[116], uint32_t alo, uint32_t blo, uint32_t bar_full, uint32_t bar_h) {
  constexpr int s = Q * 14 + ST, sl = s % B_NSLOT;
  if (Q == 0) mbar_wait(bar_h + 8 * ST, 0);
  mbar_wait(bar_full + 8 * sl, (s / B_NSLOT) & 1);
  wg_fence();
  if (Q == 0) {
    wgmma_ss232<(2 * ST) * 256, 0x40000080u, (sl * B_SLOT) / 16, 32, ST != 0>(acc, alo, blo);
    wgmma_ss232<(2 * ST + 1) * 256, 0x40000080u, (sl * B_SLOT + 256) / 16, 32, 1>(acc, alo, blo);
  } else {
    wgmma_ss224<(2 * ST) * 256, 0x40000080u, (sl * B_SLOT) / 16, 32, ST != 0>(*(float(*)[112])acc, alo, blo);
    wgmma_ss224<(2 * ST + 1) * 256, 0x40000080u, (sl * B_SLOT + 256) / 16, 32, 1>(*(float(*)[112])acc, alo, blo);
  }
}

__global__ void __launch_bounds__(512, 1)
k_front(const __nv_bfloat16* __restrict__ x, const uint32_t* __restrict__ are, const uint32_t* __restrict__ aim,
        const uint32_t* __restrict__ bre, const uint32_t* __restrict__ bim, const uint32_t* __restrict__ cre,
        const uint32_t* __restrict__ cim, const unsigned short* __restrict__ logdt, const unsigned short* __restrict__ dskip,
        const uint4* __restrict__ wgate, const uint4* __restrict__ wup, const uint4* __restrict__ wdown) {
  extern __shared__ __align__(1024) unsigned char sm[];
  const uint32_t bar_rec = s2u(sm) + 4 * A_CH;
  if (threadIdx.x == 320) TR(0, 0);
  asm volatile("griddepcontrol.launch_dependents;");
  if (threadIdx.x == 160) { mbar_init(bar_rec, 1); asm volatile("fence.mbarrier_init.release.cluster;" ::: "memory"); }
  phase_a(sm, bar_rec, bar_rec + 8, x, are, aim, bre, bim, cre, cim, logdt, dskip, wgate, wup, wdown);
}

__global__ void __cluster_dims__(2, 1, 1) __launch_bounds__(384, 1) k_ffn(__nv_bfloat16* __restrict__ out) {
  extern __shared__ __align__(1024) unsigned char sm[];
  const uint32_t sb = s2u(sm);
  const int tid = threadIdx.x, wg = tid >> 7, warp = tid >> 5, lane = tid & 31;
  const uint32_t bar_full = sb + B_BAR, bar_empty = bar_full + 64, bar_h = bar_full + 128, bar_cs = bar_full + 240,
                 bar_g2 = bar_full + 248, bar_in = bar_full + 256;
  if (tid == 0) {
    TR(1, 0);
    for (int i = 0; i < B_NSLOT; i++) { mbar_init(bar_full + 8 * i, 1); mbar_init(bar_empty + 8 * i, 4); }
    asm volatile("fence.mbarrier_init.release.cluster;" ::: "memory");
  } else if (tid == 32) {
    for (int i = 0; i < 14; i++) mbar_init(bar_h + 8 * i, 1);
  } else if (tid == 64) {
    mbar_init(bar_cs, 1);
    mbar_init(bar_g2, 4);
    for (int i = 0; i < 14; i++) mbar_init(bar_in + 8 * i, 1);
  } else if (tid >= 128 && tid < 352) {
    sts128(sb + B_RING + ((tid - 128) >> 5) * B_SLOT + 14336 + (tid & 31) * 16, 0x3F803F80u, 0x3F803F80u, 0x3F803F80u, 0x3F803F80u);
  }
  asm volatile("fence.proxy.async.shared::cta;" ::: "memory");
  __syncthreads();
  asm volatile("barrier.cluster.arrive.relaxed.aligned;" ::: "memory");
  const int rank = blockIdx.x & 1, rt = blockIdx.x & 15, j = blockIdx.x >> 4;
  const int wq = warp & 3, t128 = tid & 127, g = lane >> 2, t = lane & 3;
  asm volatile("griddepcontrol.wait;" ::: "memory");
  const uint32_t ep = __ldcg(&g_cnt1) >> 7;
  const uint32_t tag = (ep & 1u) << 16;
  auto in_addr = [&](int q, int cw) { return sb + B_SA + ((j + 1 + q) & 7) * 14336 + cw * 1792; };
  auto in_src = [&](int q, int cw) { return g_part + (size_t)((rt * 8 + ((j + 7 - q) & 7)) * 7 + q) * 896 + cw * 112; };
  auto add_in = [&](float (&sum)[28], int q, int cw) {
    const uint32_t a = in_addr(q, cw);
    const uint4 v0 = lds128(a + lane * 16), v1 = lds128(a + 512 + lane * 16), v2 = lds128(a + 1024 + lane * 16);
    uint32_t in[14] = {v0.x, v0.y, v0.z, v0.w, v1.x, v1.y, v1.z, v1.w, v2.x, v2.y, v2.z, v2.w, 0, 0};
    asm volatile("ld.shared.v2.u32 {%0, %1}, [%2];" : "=r"(in[12]), "=r"(in[13]) : "r"(a + 1536 + lane * 8) : "memory");
    int it = 0;
    while ((((in[3] ^ tag) | (in[7] ^ tag) | (in[11] ^ tag) | (in[13] ^ tag)) & 0x10000u) && ++it < 400000) {
      const uint4* gs = pin(in_src(q, cw));
#pragma unroll
      for (int i = 0; i < 3; i++) ld128(gs + i * 32 + lane, in + 4 * i);
      asm volatile("{\n.reg .b64 v;\nld.relaxed.gpu.global.b64 v, [%2];\nmov.b64 {%0, %1}, v;\n}"
                   : "=r"(in[12]), "=r"(in[13]) : "l"((const uint2*)(gs + 96) + lane) : "memory");
    }
#pragma unroll
    for (int i = 0; i < 14; i++) { sum[2 * i] += bf_lo(in[i]); sum[2 * i + 1] += bf_hi(in[i]); }
  };
  auto w_issue = [&](int s) {
    const char* wsrc = (const char*)g_wimg + (size_t)j * 602112;
    const int slot = s % B_NSLOT;
    const uint32_t dst = sb + B_RING + slot * B_SLOT, fb = bar_full + 8 * slot;
    if (s < 28) {
      mbar_expect(fb, 14336);
      bulk_ld_mc(dst + rank * 7168, wsrc + s * 14336 + rank * 7168, 7168, fb);
    } else {
      const int c = (j + 1 + ((s - 28) >> 1)) & 7;
      mbar_expect(fb, 12544);
      bulk_ld_mc(dst + rank * 6272, wsrc + 401408 + (c * 2 + (s & 1)) * 12544 + rank * 6272, 6272, fb);
    }
  };

  if (wg == 2) {
    asm volatile("setmaxnreg.dec.sync.aligned.u32 56;");
    if (warp != 9) asm volatile("barrier.cluster.wait.aligned;" ::: "memory");
    if (warp == 8) {
      if (lane == 0) {
        TR(1, 1);
        for (int s = 0; s < 44; s++) {
          if (s >= B_NSLOT) mbar_wait(bar_empty + 8 * (s % B_NSLOT), (s / B_NSLOT - 1) & 1);
          w_issue(s);
        }
      }
    } else if (warp == 9) {
      if (lane == 0) {
        const char* hsrc = (const char*)g_himg + (size_t)rt * 114688;
        for (int i = 0; i < 14; i++) {
          mbar_expect(bar_h + 8 * i, 8192);
          bulk_ld(sb + B_SA + i * 8192, hsrc + i * 8192, 8192, bar_h + 8 * i);
        }
        mbar_expect(bar_cs, 7168);
        bulk_ld(sb + B_CS, g_cimg + j * 448, 7168, bar_cs);
      }
      __syncwarp();
      asm volatile("barrier.cluster.wait.aligned;" ::: "memory");
      mbar_wait(bar_g2, 0);
      const int lq = (lane >> 1) & 7, lcw = (lane & 1) * 4;
      const uint4* fl = (const uint4*)(g_flag + (rt * 8 + ((j + 7 - lq) & 7)) * 64 + lq * 8 + lcw);
      bool todo = lane < 14;
      int it = 0;
      while (__any_sync(~0u, todo) && ++it < 400000) {
        if (todo) {
          uint32_t w[4];
          ld128(fl, w);
          if (w[0] == ep && w[1] == ep && w[2] == ep && w[3] == ep) {
            asm volatile("fence.proxy.async;" ::: "memory");
            mbar_expect(bar_in + 8 * lane, 7168);
            bulk_ld(in_addr(lq, lcw), in_src(lq, lcw), 7168, bar_in + 8 * lane);
            todo = false;
            if (lane & 1) TR(1, 24 + lq);
          }
        }
      }
    } else {
      const int t64 = tid - 320;
      const int r = (lane >> 1) & 7, c = (j & 3) * 2 + (lane & 1);
      const uint32_t src = sb + B_SA + (t64 >> 4) * 2048 + (j >> 2) * 1024 + r * 128 + ((c ^ r) << 4);
      float a[16];
#pragma unroll
      for (int k = 0; k < 16; k++) a[k] = 0.f;
#pragma unroll 1
      for (int i = 0; i < 14; i++) {
        mbar_wait(bar_h + 8 * i, 0);
        uint4 v = lds128(src + i * 8192);
        float e[8] = {bf_lo(v.x), bf_hi(v.x), bf_lo(v.y), bf_hi(v.y), bf_lo(v.z), bf_hi(v.z), bf_lo(v.w), bf_hi(v.w)};
#pragma unroll
        for (int k = 0; k < 8; k++) { a[2 * k] += e[k]; a[2 * k + 1] = fmaf(e[k], e[k], a[2 * k + 1]); }
        __nanosleep(160);
      }
      __syncwarp();
      if (lane == 0) mbar_arrive(bar_g2);
#pragma unroll
      for (int rd = 0; rd < 4; rd++) {
        const int n = 8 >> rd;
        const bool up = lane & (2 * n);
#pragma unroll
        for (int k = 0; k < 8; k++) {
          if (k < n) {
            float keep = up ? a[k + n] : a[k], give = up ? a[k] : a[k + n];
            a[k] = keep + __shfl_xor_sync(~0u, give, 2 * n);
          }
        }
      }
      float* red = (float*)(sm + B_RED);
      red[(warp & 1) * 32 + (lane & 1) * 16 + (lane >> 1)] = a[0];
      bar_sync(1, 64);
      if (t64 < 16) {
        float mean = (red[2 * t64] + red[32 + 2 * t64]) * (1.f / DM);
        float var = fmaxf(fmaf(-mean, mean, (red[2 * t64 + 1] + red[33 + 2 * t64]) * (1.f / DM)), 0.f);
        float rs = __frcp_rn(rbf(__fsqrt_rn(rbf(rbf(var) + 1e-5f))));
        asm volatile("st.relaxed.gpu.global.u32 [%0], %1;"
                     ::"l"(g_stat2 + rt * 128 + j * 16 + t64), "r"((__float_as_uint(rs * rs) & ~1u) | (ep & 1u)) : "memory");
      }
      if (t64 == 0) TR(1, 2);
    }
  } else {
    asm volatile("setmaxnreg.inc.sync.aligned.u32 224;");
    asm volatile("barrier.cluster.wait.aligned;" ::: "memory");
    uint32_t hh[56];
    const uint32_t rel_bar = pin(mapa(bar_empty, t128 & 1));
    const bool relt = t128 < 2;
    auto release = [&](int sl) { if (relt) asm volatile("mbarrier.arrive.shared::cluster.b64 _, [%0];" ::"r"(rel_bar + 8 * sl) : "memory"); };
    const uint32_t alo = __shfl_sync(~0u, ((sb + B_SA + wg * 1024) & 0x3FFFF) >> 4, 0);
    const uint32_t blo = (((sb + B_RING) & 0x3FFFF) >> 4) | (8u << 16);
    const uint32_t clo = ((sb + B_CS) & 0x3FFFF) >> 4;
    uint32_t nm0, nm1;
    if (wg == 1) bar_sync(3, 256);
#define G1S(Q, ST) do { g1_stage<Q, ST>(acc, alo, blo, bar_full, bar_h); wg_commit(); \
      if (ST > 0) { wg_wait<1>(); release((Q * 14 + ST - 1) % B_NSLOT); } } while (0)
#define G1HH(Q) do { \
      _Pragma("unroll") \
      for (int i = 0; i < 28; i++) hh[28 * Q + i] = pack_bf16(acc[2 * i] * acc[56 + 2 * i], acc[2 * i + 1] * acc[57 + 2 * i]); \
    } while (0)
    {
      float acc[116];
      G1S(0, 0);
      if (tid == 0) TR(1, 3);
      G1S(0, 1);
      if (wg == 0) asm volatile("bar.arrive 3, 256;" ::: "memory");
      G1S(0, 2); G1S(0, 3); G1S(0, 4); G1S(0, 5); G1S(0, 6); G1S(0, 7); G1S(0, 8); G1S(0, 9); G1S(0, 10); G1S(0, 11); G1S(0, 12);
      G1S(0, 13);
      if (tid == 0) TR(1, 4);
      mbar_wait(bar_cs, 0);
      wg_wait<0>(); reg_fence(acc); release(13 % B_NSLOT);
      {
        const uint32_t msk = t == 0 ? 0xFFFFFFFFu : t == 1 ? 0xFFFFu : 0u;
        const float a = acc[112] * (-1.f / DM), b = acc[114] * (-1.f / DM);
        nm0 = pack_bf16(a, a) & msk; nm1 = pack_bf16(b, b) & msk;
      }
      wg_fence();
      wgmma_rs224<0, 8, 1>(*(float(*)[112])acc, nm0, nm1, 0u, 0u, clo);
      wg_commit(); wg_wait<0>(); reg_fence(acc);
      G1HH(0);
      if (tid == 0) TR(1, 5);
      G1S(1, 0); G1S(1, 1); G1S(1, 2); G1S(1, 3); G1S(1, 4); G1S(1, 5); G1S(1, 6); G1S(1, 7); G1S(1, 8); G1S(1, 9); G1S(1, 10); G1S(1, 11);
      G1S(1, 12);
      g1_stage<1, 13>(acc, alo, blo, bar_full, bar_h);
      wgmma_rs224<224, 8, 1>(*(float(*)[112])acc, nm0, nm1, 0u, 0u, clo);
      wg_commit(); wg_wait<1>(); release(26 % B_NSLOT);
      wg_wait<0>(); reg_fence(acc); release(27 % B_NSLOT);
      if (t128 == 0) mbar_arrive(bar_g2);
      G1HH(1);
      if (tid == 0) TR(1, 6);
    }
    float accA[28], accB[28];
#define ISSUE(acc, I, a, FIRST) do { \
      constexpr int s_ = 28 + (I), sl_ = s_ % B_NSLOT; \
      mbar_wait(bar_full + 8 * sl_, (s_ / B_NSLOT) & 1); \
      wg_fence(); \
      wgmma_rs56<(sl_ * B_SLOT + 0 * 256) / 16, 112, !(FIRST)>(acc, (a)[0], (a)[1], (a)[2], (a)[3], blo); \
      wgmma_rs56<(sl_ * B_SLOT + 1 * 256) / 16, 112, 1>(acc, (a)[4], (a)[5], (a)[6], (a)[7], blo); \
      wgmma_rs56<(sl_ * B_SLOT + 2 * 256) / 16, 112, 1>(acc, (a)[8], (a)[9], (a)[10], (a)[11], blo); \
      wgmma_rs56<(sl_ * B_SLOT + 3 * 256) / 16, 112, 1>(acc, (a)[12], (a)[13], (a)[14], (a)[15], blo); \
      wgmma_rs56<(sl_ * B_SLOT + 4 * 256) / 16, 112, 1>(acc, (a)[16], (a)[17], (a)[18], (a)[19], blo); \
      wgmma_rs56<(sl_ * B_SLOT + 5 * 256) / 16, 112, 1>(acc, (a)[20], (a)[21], (a)[22], (a)[23], blo); \
      wgmma_rs56<(sl_ * B_SLOT + 6 * 256) / 16, 112, 1>(acc, (a)[24], (a)[25], (a)[26], (a)[27], blo); \
      wg_commit(); } while (0)
    uint4* const pdst = pin(g_part + (size_t)((rt * 8 + j) * 7) * 896 + warp * 112 + lane);
    uint2* const pdst2 = pin((uint2*)(g_part + (size_t)((rt * 8 + j) * 7) * 896 + warp * 112 + 96) + lane);
    uint32_t* const fdst = pin(g_flag + (rt * 8 + j) * 64 + warp);
    const bool flt = lane == 0;
    auto rel = [&](int i) { if (i < 9) release((28 + i) % B_NSLOT); };
    auto tg = [&](uint32_t v) { return (v & 0xFFFEFFFFu) | tag; };
    auto send_lo = [&](float (&acc)[28], int cc) {
      reg_fence(acc);
#pragma unroll
      for (int q = 0; q < 2; q++)
        st128(pdst + cc * 896 + q * 32, pack_bf16(acc[8 * q], acc[8 * q + 1]), pack_bf16(acc[8 * q + 2], acc[8 * q + 3]),
              pack_bf16(acc[8 * q + 4], acc[8 * q + 5]), tg(pack_bf16(acc[8 * q + 6], acc[8 * q + 7])));
    };
    auto send_hi = [&](float (&acc)[28], int cc) {
      st128(pdst + cc * 896 + 64, pack_bf16(acc[16], acc[17]), pack_bf16(acc[18], acc[19]), pack_bf16(acc[20], acc[21]), tg(pack_bf16(acc[22], acc[23])));
      asm volatile("{\n.reg .b64 v;\nmov.b64 v, {%1, %2};\nst.relaxed.gpu.global.b64 [%0], v;\n}"
                   ::"l"(pdst2 + cc * 1792), "r"(pack_bf16(acc[24], acc[25])), "r"(tg(pack_bf16(acc[26], acc[27]))) : "memory");
      if (flt) asm volatile("st.relaxed.gpu.global.u32 [%0], %1;" ::"l"(fdst + cc * 8), "r"(ep) : "memory");
    };
#define CHUNK(cur, prev, CC) do { \
      ISSUE(cur, 2 * (CC), hh, true); wg_wait<1>(); rel(2 * (CC) - 1); send_lo(prev, (CC) - 1); \
      ISSUE(cur, 2 * (CC) + 1, hh + 28, false); send_hi(prev, (CC) - 1); wg_wait<1>(); rel(2 * (CC)); } while (0)
    ISSUE(accA, 0, hh, true);
    ISSUE(accA, 1, hh + 28, false); wg_wait<1>(); rel(0);
    CHUNK(accB, accA, 1);
    if (tid == 0) TR(1, 11);
    CHUNK(accA, accB, 2);
    CHUNK(accB, accA, 3);
    if (tid == 0) TR(1, 13);
    CHUNK(accA, accB, 4);
    CHUNK(accB, accA, 5);
    if (tid == 0) TR(1, 16);
    CHUNK(accA, accB, 6);
    const int row = rt * 128 + wg * 64 + wq * 16 + g;
    uint32_t r20, r21;
    asm volatile("ld.relaxed.gpu.global.u32 %0, [%1];" : "=r"(r20) : "l"(g_stat2 + row) : "memory");
    asm volatile("ld.relaxed.gpu.global.u32 %0, [%1];" : "=r"(r21) : "l"(g_stat2 + row + 8) : "memory");
    CHUNK(accB, accA, 7);
    if (tid == 0) TR(1, 7);
    uint32_t hres[16];
#pragma unroll
    for (int i = 0; i < 4; i++) {
      int qq = lane >> 3, r = lane & 7, kg = 7 * j + 2 * i + (qq >> 1), c = 2 * wq + (qq & 1);
      if (kg > 55) kg = 55;
      asm volatile("ldmatrix.sync.aligned.m8n8.x4.trans.shared.b16 {%0,%1,%2,%3}, [%4];"
                   : "=r"(hres[4 * i]), "=r"(hres[4 * i + 1]), "=r"(hres[4 * i + 2]), "=r"(hres[4 * i + 3])
                   : "r"(sb + B_SA + kg * 2048 + wg * 1024 + r * 128 + ((c ^ r) << 4)) : "memory");
    }
    {
      int it = 0;
      while ((((r20 ^ ep) | (r21 ^ ep)) & 1u) && ++it < 400000) {
        asm volatile("ld.relaxed.gpu.global.u32 %0, [%1];" : "=r"(r20) : "l"(g_stat2 + row) : "memory");
        asm volatile("ld.relaxed.gpu.global.u32 %0, [%1];" : "=r"(r21) : "l"(g_stat2 + row + 8) : "memory");
      }
    }
    wg_wait<0>();
    reg_fence(accB);
    if (tid == 0) TR(1, 9);
#pragma unroll 1
    for (int q = 0; q < 7; q++) {
      mbar_wait(bar_in + 8 * (2 * q + wg), 0);
      add_in(accB, q, warp);
      if (tid == 0 && q == 5) TR(1, 12);
    }
    uint32_t* o0 = (uint32_t*)(out + (size_t)row * DM + 56 * j + 2 * t);
    uint32_t* o1 = o0 + 8 * DM / 2;
#pragma unroll
    for (int i = 0; i < 7; i++) {
      o0[4 * i] = hadd2_bf(hres[2 * i], pack_bf16(accB[4 * i] * __uint_as_float(r20), accB[4 * i + 1] * __uint_as_float(r20)));
      o1[4 * i] = hadd2_bf(hres[2 * i + 1], pack_bf16(accB[4 * i + 2] * __uint_as_float(r21), accB[4 * i + 3] * __uint_as_float(r21)));
    }
    if (tid == 0) TR(1, 10);
    if (tid == 128) TR(1, 15);
  }
}

extern "C" void kernel_launch(void* const* d_in, const int* in_sizes, int n_in, void* d_out, int out_size) {
  const __nv_bfloat16* x = (const __nv_bfloat16*)d_in[0];
  const __nv_bfloat16 *are = (const __nv_bfloat16*)d_in[1], *aim = (const __nv_bfloat16*)d_in[2], *bre = (const __nv_bfloat16*)d_in[3],
                      *bim = (const __nv_bfloat16*)d_in[4], *cre = (const __nv_bfloat16*)d_in[5], *cim = (const __nv_bfloat16*)d_in[6],
                      *logdt = (const __nv_bfloat16*)d_in[7], *dskip = (const __nv_bfloat16*)d_in[8];
  const __nv_bfloat16 *wg = (const __nv_bfloat16*)d_in[10], *wu = (const __nv_bfloat16*)d_in[11], *wd = (const __nv_bfloat16*)d_in[12];

  static bool init = false;
  if (!init) {
    init = true;
    cudaFuncSetAttribute(k_ffn, cudaFuncAttributeMaxDynamicSharedMemorySize, B_SMEM);
    cudaFuncSetAttribute(k_front, cudaFuncAttributeMaxDynamicSharedMemorySize, A_SMEM);
  }
  cudaStream_t st = cudaStreamPerThread;
  k_front<<<128, 512, A_SMEM, st>>>(
      x, (const uint32_t*)are, (const uint32_t*)aim, (const uint32_t*)bre, (const uint32_t*)bim, (const uint32_t*)cre, (const uint32_t*)cim,
      (const unsigned short*)logdt, (const unsigned short*)dskip, (const uint4*)wg, (const uint4*)wu, (const uint4*)wd);
  cudaLaunchConfig_t cfg = {};
  cfg.gridDim = dim3(128); cfg.blockDim = dim3(384); cfg.dynamicSmemBytes = B_SMEM; cfg.stream = st;
  cudaLaunchAttribute at[1];
  at[0].id = cudaLaunchAttributeProgrammaticStreamSerialization; at[0].val.programmaticStreamSerializationAllowed = 1;
  cfg.attrs = at; cfg.numAttrs = 1;
  cudaLaunchKernelEx(&cfg, k_ffn, (__nv_bfloat16*)d_out);
}
```

```cpp
#include <cuda_runtime.h>
#include <cuda_bf16.h>
#include <stdint.h>

constexpr int LSEQ = 2048, DM = 448;

__device__ uint4    g_himg[16 * 114688 / 16];
__device__ uint4    g_cimg[8 * 2 * 224];
__device__ uint32_t g_stat2[LSEQ];
__device__ uint4    g_part[128 * 7 * 896];
__device__ uint4    g_wimg[8 * 602112 / 16];
__device__ uint4    g_ux[DM * 128 * 4];
__device__ unsigned g_cnt1;
__device__ uint32_t g_flag[128 * 64];

#define TR(k, i) do {} while (0)
__device__ __forceinline__ uint32_t s2u(const void* p) { return (uint32_t)__cvta_generic_to_shared(p); }
__device__ __forceinline__ void mbar_init(uint32_t b, int c) { asm volatile("mbarrier.init.shared::cta.b64 [%0], %1;" ::"r"(b), "r"(c)); }
__device__ __forceinline__ void mbar_expect(uint32_t b, int bytes) { asm volatile("mbarrier.arrive.expect_tx.shared::cta.b64 _, [%0], %1;" ::"r"(b), "r"(bytes) : "memory"); }
__device__ __forceinline__ void mbar_arrive(uint32_t b) { asm volatile("mbarrier.arrive.shared::cta.b64 _, [%0];" ::"r"(b) : "memory"); }
__device__ __forceinline__ void mbar_wait(uint32_t b, int ph) {
  asm volatile("{\n.reg .pred p;\n.reg .b32 n;\nmov.b32 n, 0;\nLW:\nmbarrier.try_wait.parity.shared::cta.b64 p, [%0], %1;\n@p bra LD;\n"
               "add.u32 n, n, 1;\nsetp.lt.u32 p, n, 4000000;\n@p bra LW;\ntrap;\nLD:\n}" ::"r"(b), "r"(ph) : "memory");
}
__device__ __forceinline__ bool mbar_test(uint32_t b, int ph) {
  uint32_t ok;
  asm volatile("{\n.reg .pred p;\nmbarrier.test_wait.parity.shared::cta.b64 p, [%1], %2;\nselp.u32 %0, 1, 0, p;\n}" : "=r"(ok) : "r"(b), "r"(ph) : "memory");
  return ok;
}
__device__ __forceinline__ void wg_fence() { asm volatile("wgmma.fence.sync.aligned;" ::: "memory"); }
__device__ __forceinline__ void wg_commit() { asm volatile("wgmma.commit_group.sync.aligned;" ::: "memory"); }
template <int N> __device__ __forceinline__ void wg_wait() { asm volatile("wgmma.wait_group.sync.aligned %0;" ::"n"(N) : "memory"); }
template <int N> __device__ __forceinline__ void reg_fence(float (&a)[N]) {
#pragma unroll
  for (int i = 0; i < N; i++) asm volatile("" : "+f"(a[i])::"memory");
}
__device__ __forceinline__ uint32_t pack_bf16(float lo, float hi) {
  uint32_t r; asm("cvt.rn.bf16x2.f32 %0, %1, %2;" : "=r"(r) : "f"(hi), "f"(lo)); return r;
}
__device__ __forceinline__ float bf_lo(uint32_t v) { return __uint_as_float(v << 16); }
__device__ __forceinline__ float bf_hi(uint32_t v) { return __uint_as_float(v & 0xFFFF0000u); }
__device__ __forceinline__ float rbf(float x) { return __bfloat162float(__float2bfloat16_rn(x)); }
__device__ __forceinline__ uint32_t hmul2_bf(uint32_t a, uint32_t b) { uint32_t r; asm("mul.rn.bf16x2 %0, %1, %2;" : "=r"(r) : "r"(a), "r"(b)); return r; }
__device__ __forceinline__ uint32_t hadd2_bf(uint32_t a, uint32_t b) { uint32_t r; asm("add.rn.bf16x2 %0, %1, %2;" : "=r"(r) : "r"(a), "r"(b)); return r; }
__device__ __forceinline__ void bulk_ld(uint32_t dst, const void* src, int bytes, uint32_t bar) {
  asm volatile("cp.async.bulk.shared::cluster.global.mbarrier::complete_tx::bytes [%0], [%1], %2, [%3];"
               ::"r"(dst), "l"(src), "r"(bytes), "r"(bar) : "memory");
}

__device__ __forceinline__ void bulk_ld_mc(uint32_t dst, const void* src, int bytes, uint32_t bar) {
  asm volatile("cp.async.bulk.shared::cluster.global.mbarrier::complete_tx::bytes.multicast::cluster [%0], [%1], %2, [%3], %4;"
               ::"r"(dst), "l"(src), "r"(bytes), "r"(bar), "h"((uint16_t)3) : "memory");
}
template <int AOFF, uint32_t AHI, int BOFF, uint32_t BHI, int ACC>
__device__ __forceinline__ void wgmma_ss224(float (&d)[112], uint32_t alo, uint32_t blo) {
  asm volatile("{\n.reg .pred p;\n.reg .b32 la, lb;\n.reg .b64 ad, bd;\nsetp.ne.b32 p, %118, 0;\n"
    "add.u32 la, %112, %114;\nmov.b64 ad, {la, %115};\nadd.u32 lb, %113, %116;\nmov.b64 bd, {lb, %117};\n"
    "wgmma.mma_async.sync.aligned.m64n224k16.f32.bf16.bf16 {%0,%1,%2,%3,%4,%5,%6,%7,%8,%9,%10,%11,%12,%13,%14,%15,%16,%17,%18,%19,%20,%21,%22,%23,%24,%25,%26,%27,%28,%29,%30,%31,%32,%33,%34,%35,%36,%37,%38,%39,%40,%41,%42,%43,%44,%45,%46,%47,%48,%49,%50,%51,%52,%53,%54,%55,%56,%57,%58,%59,%60,%61,%62,%63,%64,%65,%66,%67,%68,%69,%70,%71,%72,%73,%74,%75,%76,%77,%78,%79,%80,%81,%82,%83,%84,%85,%86,%87,%88,%89,%90,%91,%92,%93,%94,%95,%96,%97,%98,%99,%100,%101,%102,%103,%104,%105,%106,%107,%108,%109,%110,%111}, ad, bd, p, 1, 1, 1, 1;\n}\n"
    : "+f"(d[0]),"+f"(d[1]),"+f"(d[2]),"+f"(d[3]),"+f"(d[4]),"+f"(d[5]),"+f"(d[6]),"+f"(d[7]),"+f"(d[8]),"+f"(d[9]),"+f"(d[10]),"+f"(d[11]),"+f"(d[12]),"+f"(d[13]),"+f"(d[14]),"+f"(d[15]),"+f"(d[16]),"+f"(d[17]),"+f"(d[18]),"+f"(d[19]),"+f"(d[20]),"+f"(d[21]),"+f"(d[22]),"+f"(d[23]),"+f"(d[24]),"+f"(d[25]),"+f"(d[26]),"+f"(d[27]),"+f"(d[28]),"+f"(d[29]),"+f"(d[30]),"+f"(d[31]),"+f"(d[32]),"+f"(d[33]),"+f"(d[34]),"+f"(d[35]),"+f"(d[36]),"+f"(d[37]),"+f"(d[38]),"+f"(d[39]),"+f"(d[40]),"+f"(d[41]),"+f"(d[42]),"+f"(d[43]),"+f"(d[44]),"+f"(d[45]),"+f"(d[46]),"+f"(d[47]),"+f"(d[48]),"+f"(d[49]),"+f"(d[50]),"+f"(d[51]),"+f"(d[52]),"+f"(d[53]),"+f"(d[54]),"+f"(d[55]),"+f"(d[56]),"+f"(d[57]),"+f"(d[58]),"+f"(d[59]),"+f"(d[60]),"+f"(d[61]),"+f"(d[62]),"+f"(d[63]),"+f"(d[64]),"+f"(d[65]),"+f"(d[66]),"+f"(d[67]),"+f"(d[68]),"+f"(d[69]),"+f"(d[70]),"+f"(d[71]),"+f"(d[72]),"+f"(d[73]),"+f"(d[74]),"+f"(d[75]),"+f"(d[76]),"+f"(d[77]),"+f"(d[78]),"+f"(d[79]),"+f"(d[80]),"+f"(d[81]),"+f"(d[82]),"+f"(d[83]),"+f"(d[84]),"+f"(d[85]),"+f"(d[86]),"+f"(d[87]),"+f"(d[88]),"+f"(d[89]),"+f"(d[90]),"+f"(d[91]),"+f"(d[92]),"+f"(d[93]),"+f"(d[94]),"+f"(d[95]),"+f"(d[96]),"+f"(d[97]),"+f"(d[98]),"+f"(d[99]),"+f"(d[100]),"+f"(d[101]),"+f"(d[102]),"+f"(d[103]),"+f"(d[104]),"+f"(d[105]),"+f"(d[106]),"+f"(d[107]),"+f"(d[108]),"+f"(d[109]),"+f"(d[110]),"+f"(d[111])
    : "r"(alo), "r"(blo), "n"(AOFF), "n"(AHI), "n"(BOFF), "n"(BHI), "n"(ACC));
}
template <int AOFF, uint32_t AHI, int BOFF, uint32_t BHI, int ACC>
__device__ __forceinline__ void wgmma_ss232(float (&d)[116], uint32_t alo, uint32_t blo) {
  asm volatile("{\n.reg .pred p;\n.reg .b32 la, lb;\n.reg .b64 ad, bd;\nsetp.ne.b32 p, %122, 0;\n"
    "add.u32 la, %116, %118;\nmov.b64 ad, {la, %119};\nadd.u32 lb, %117, %120;\nmov.b64 bd, {lb, %121};\n"
    "wgmma.mma_async.sync.aligned.m64n232k16.f32.bf16.bf16 {%0,%1,%2,%3,%4,%5,%6,%7,%8,%9,%10,%11,%12,%13,%14,%15,%16,%17,%18,%19,%20,%21,%22,%23,%24,%25,%26,%27,%28,%29,%30,%31,%32,%33,%34,%35,%36,%37,%38,%39,%40,%41,%42,%43,%44,%45,%46,%47,%48,%49,%50,%51,%52,%53,%54,%55,%56,%57,%58,%59,%60,%61,%62,%63,%64,%65,%66,%67,%68,%69,%70,%71,%72,%73,%74,%75,%76,%77,%78,%79,%80,%81,%82,%83,%84,%85,%86,%87,%88,%89,%90,%91,%92,%93,%94,%95,%96,%97,%98,%99,%100,%101,%102,%103,%104,%105,%106,%107,%108,%109,%110,%111,%112,%113,%114,%115}, ad, bd, p, 1, 1, 1, 1;\n}\n"
    : "+f"(d[0]),"+f"(d[1]),"+f"(d[2]),"+f"(d[3]),"+f"(d[4]),"+f"(d[5]),"+f"(d[6]),"+f"(d[7]),"+f"(d[8]),"+f"(d[9]),"+f"(d[10]),"+f"(d[11]),"+f"(d[12]),"+f"(d[13]),"+f"(d[14]),"+f"(d[15]),"+f"(d[16]),"+f"(d[17]),"+f"(d[18]),"+f"(d[19]),"+f"(d[20]),"+f"(d[21]),"+f"(d[22]),"+f"(d[23]),"+f"(d[24]),"+f"(d[25]),"+f"(d[26]),"+f"(d[27]),"+f"(d[28]),"+f"(d[29]),"+f"(d[30]),"+f"(d[31]),"+f"(d[32]),"+f"(d[33]),"+f"(d[34]),"+f"(d[35]),"+f"(d[36]),"+f"(d[37]),"+f"(d[38]),"+f"(d[39]),"+f"(d[40]),"+f"(d[41]),"+f"(d[42]),"+f"(d[43]),"+f"(d[44]),"+f"(d[45]),"+f"(d[46]),"+f"(d[47]),"+f"(d[48]),"+f"(d[49]),"+f"(d[50]),"+f"(d[51]),"+f"(d[52]),"+f"(d[53]),"+f"(d[54]),"+f"(d[55]),"+f"(d[56]),"+f"(d[57]),"+f"(d[58]),"+f"(d[59]),"+f"(d[60]),"+f"(d[61]),"+f"(d[62]),"+f"(d[63]),"+f"(d[64]),"+f"(d[65]),"+f"(d[66]),"+f"(d[67]),"+f"(d[68]),"+f"(d[69]),"+f"(d[70]),"+f"(d[71]),"+f"(d[72]),"+f"(d[73]),"+f"(d[74]),"+f"(d[75]),"+f"(d[76]),"+f"(d[77]),"+f"(d[78]),"+f"(d[79]),"+f"(d[80]),"+f"(d[81]),"+f"(d[82]),"+f"(d[83]),"+f"(d[84]),"+f"(d[85]),"+f"(d[86]),"+f"(d[87]),"+f"(d[88]),"+f"(d[89]),"+f"(d[90]),"+f"(d[91]),"+f"(d[92]),"+f"(d[93]),"+f"(d[94]),"+f"(d[95]),"+f"(d[96]),"+f"(d[97]),"+f"(d[98]),"+f"(d[99]),"+f"(d[100]),"+f"(d[101]),"+f"(d[102]),"+f"(d[103]),"+f"(d[104]),"+f"(d[105]),"+f"(d[106]),"+f"(d[107]),"+f"(d[108]),"+f"(d[109]),"+f"(d[110]),"+f"(d[111]),"+f"(d[112]),"+f"(d[113]),"+f"(d[114]),"+f"(d[115])
    : "r"(alo), "r"(blo), "n"(AOFF), "n"(AHI), "n"(BOFF), "n"(BHI), "n"(ACC));
}
template <int OFF, uint32_t BHI, int ACC>
__device__ __forceinline__ void wgmma_rs224(float (&d)[112], uint32_t a0, uint32_t a1, uint32_t a2, uint32_t a3, uint32_t blo) {
  asm volatile("{\n.reg .pred p;\n.reg .b32 l;\n.reg .b64 bd;\nsetp.ne.b32 p, %119, 0;\nadd.u32 l, %116, %117;\nmov.b64 bd, {l, %118};\n"
    "wgmma.mma_async.sync.aligned.m64n224k16.f32.bf16.bf16 {%0,%1,%2,%3,%4,%5,%6,%7,%8,%9,%10,%11,%12,%13,%14,%15,%16,%17,%18,%19,%20,%21,%22,%23,%24,%25,%26,%27,%28,%29,%30,%31,%32,%33,%34,%35,%36,%37,%38,%39,%40,%41,%42,%43,%44,%45,%46,%47,%48,%49,%50,%51,%52,%53,%54,%55,%56,%57,%58,%59,%60,%61,%62,%63,%64,%65,%66,%67,%68,%69,%70,%71,%72,%73,%74,%75,%76,%77,%78,%79,%80,%81,%82,%83,%84,%85,%86,%87,%88,%89,%90,%91,%92,%93,%94,%95,%96,%97,%98,%99,%100,%101,%102,%103,%104,%105,%106,%107,%108,%109,%110,%111}, {%112,%113,%114,%115}, bd, p, 1, 1, 1;\n}\n"
    : "+f"(d[0]),"+f"(d[1]),"+f"(d[2]),"+f"(d[3]),"+f"(d[4]),"+f"(d[5]),"+f"(d[6]),"+f"(d[7]),"+f"(d[8]),"+f"(d[9]),"+f"(d[10]),"+f"(d[11]),"+f"(d[12]),"+f"(d[13]),"+f"(d[14]),"+f"(d[15]),"+f"(d[16]),"+f"(d[17]),"+f"(d[18]),"+f"(d[19]),"+f"(d[20]),"+f"(d[21]),"+f"(d[22]),"+f"(d[23]),"+f"(d[24]),"+f"(d[25]),"+f"(d[26]),"+f"(d[27]),"+f"(d[28]),"+f"(d[29]),"+f"(d[30]),"+f"(d[31]),"+f"(d[32]),"+f"(d[33]),"+f"(d[34]),"+f"(d[35]),"+f"(d[36]),"+f"(d[37]),"+f"(d[38]),"+f"(d[39]),"+f"(d[40]),"+f"(d[41]),"+f"(d[42]),"+f"(d[43]),"+f"(d[44]),"+f"(d[45]),"+f"(d[46]),"+f"(d[47]),"+f"(d[48]),"+f"(d[49]),"+f"(d[50]),"+f"(d[51]),"+f"(d[52]),"+f"(d[53]),"+f"(d[54]),"+f"(d[55]),"+f"(d[56]),"+f"(d[57]),"+f"(d[58]),"+f"(d[59]),"+f"(d[60]),"+f"(d[61]),"+f"(d[62]),"+f"(d[63]),"+f"(d[64]),"+f"(d[65]),"+f"(d[66]),"+f"(d[67]),"+f"(d[68]),"+f"(d[69]),"+f"(d[70]),"+f"(d[71]),"+f"(d[72]),"+f"(d[73]),"+f"(d[74]),"+f"(d[75]),"+f"(d[76]),"+f"(d[77]),"+f"(d[78]),"+f"(d[79]),"+f"(d[80]),"+f"(d[81]),"+f"(d[82]),"+f"(d[83]),"+f"(d[84]),"+f"(d[85]),"+f"(d[86]),"+f"(d[87]),"+f"(d[88]),"+f"(d[89]),"+f"(d[90]),"+f"(d[91]),"+f"(d[92]),"+f"(d[93]),"+f"(d[94]),"+f"(d[95]),"+f"(d[96]),"+f"(d[97]),"+f"(d[98]),"+f"(d[99]),"+f"(d[100]),"+f"(d[101]),"+f"(d[102]),"+f"(d[103]),"+f"(d[104]),"+f"(d[105]),"+f"(d[106]),"+f"(d[107]),"+f"(d[108]),"+f"(d[109]),"+f"(d[110]),"+f"(d[111])
    : "r"(a0), "r"(a1), "r"(a2), "r"(a3), "r"(blo), "n"(OFF), "n"(BHI), "n"(ACC));
}
template <int OFF, uint32_t BHI, int ACC>
__device__ __forceinline__ void wgmma_rs56(float (&d)[28], uint32_t a0, uint32_t a1, uint32_t a2, uint32_t a3, uint32_t blo) {
  asm volatile("{\n.reg .pred p;\n.reg .b32 l;\n.reg .b64 bd;\nsetp.ne.b32 p, %35, 0;\nadd.u32 l, %32, %33;\nmov.b64 bd, {l, %34};\n"
    "wgmma.mma_async.sync.aligned.m64n56k16.f32.bf16.bf16 {%0,%1,%2,%3,%4,%5,%6,%7,%8,%9,%10,%11,%12,%13,%14,%15,%16,%17,%18,%19,%20,%21,%22,%23,%24,%25,%26,%27}, {%28,%29,%30,%31}, bd, p, 1, 1, 1;\n}\n"
    : "+f"(d[0]),"+f"(d[1]),"+f"(d[2]),"+f"(d[3]),"+f"(d[4]),"+f"(d[5]),"+f"(d[6]),"+f"(d[7]),"+f"(d[8]),"+f"(d[9]),"+f"(d[10]),"+f"(d[11]),"+f"(d[12]),"+f"(d[13]),"+f"(d[14]),"+f"(d[15]),"+f"(d[16]),"+f"(d[17]),"+f"(d[18]),"+f"(d[19]),"+f"(d[20]),"+f"(d[21]),"+f"(d[22]),"+f"(d[23]),"+f"(d[24]),"+f"(d[25]),"+f"(d[26]),"+f"(d[27])
    : "r"(a0), "r"(a1), "r"(a2), "r"(a3), "r"(blo), "n"(OFF), "n"(BHI), "n"(ACC));
}

__device__ __forceinline__ void st128(uint4* p, uint32_t a, uint32_t b, uint32_t c, uint32_t d) {
  asm volatile("{\n.reg .b128 v;\n.reg .b64 lo, hi;\nmov.b64 lo, {%1, %2};\nmov.b64 hi, {%3, %4};\nmov.b128 v, {lo, hi};\n"
               "st.relaxed.gpu.global.b128 [%0], v;\n}" ::"l"(p), "r"(a), "r"(b), "r"(c), "r"(d) : "memory");
}
__device__ __forceinline__ void ld128(const uint4* p, uint32_t* r) {
  asm volatile("{\n.reg .b128 v;\n.reg .b64 lo, hi;\nld.relaxed.gpu.global.b128 v, [%4];\nmov.b128 {lo, hi}, v;\n"
               "mov.b64 {%0, %1}, lo;\nmov.b64 {%2, %3}, hi;\n}" : "=r"(r[0]), "=r"(r[1]), "=r"(r[2]), "=r"(r[3]) : "l"(p) : "memory");
}

template <int OFF, uint32_t BHI, int ACC>
__device__ __forceinline__ void wgmma_rs32(float (&d)[16], uint32_t a0, uint32_t a1, uint32_t a2, uint32_t a3, uint32_t blo) {
  asm volatile("{\n.reg .pred p;\n.reg .b32 l;\n.reg .b64 bd;\nsetp.ne.b32 p, %23, 0;\nadd.u32 l, %20, %21;\nmov.b64 bd, {l, %22};\n"
    "wgmma.mma_async.sync.aligned.m64n32k16.f32.bf16.bf16 {%0,%1,%2,%3,%4,%5,%6,%7,%8,%9,%10,%11,%12,%13,%14,%15}, {%16,%17,%18,%19}, bd, p, 1, 1, 0;\n}\n"
    : "+f"(d[0]),"+f"(d[1]),"+f"(d[2]),"+f"(d[3]),"+f"(d[4]),"+f"(d[5]),"+f"(d[6]),"+f"(d[7]),"+f"(d[8]),"+f"(d[9]),"+f"(d[10]),"+f"(d[11]),"+f"(d[12]),"+f"(d[13]),"+f"(d[14]),"+f"(d[15])
    : "r"(a0), "r"(a1), "r"(a2), "r"(a3), "r"(blo), "n"(OFF), "n"(BHI), "n"(ACC));
}
template <int OFF, uint32_t BHI, int ACC>
__device__ __forceinline__ void wgmma_rs24(float (&d)[12], uint32_t a0, uint32_t a1, uint32_t a2, uint32_t a3, uint32_t blo) {
  asm volatile("{\n.reg .pred p;\n.reg .b32 l;\n.reg .b64 bd;\nsetp.ne.b32 p, %19, 0;\nadd.u32 l, %16, %17;\nmov.b64 bd, {l, %18};\n"
    "wgmma.mma_async.sync.aligned.m64n24k16.f32.bf16.bf16 {%0,%1,%2,%3,%4,%5,%6,%7,%8,%9,%10,%11}, {%12,%13,%14,%15}, bd, p, 1, 1, 1;\n}\n"
    : "+f"(d[0]),"+f"(d[1]),"+f"(d[2]),"+f"(d[3]),"+f"(d[4]),"+f"(d[5]),"+f"(d[6]),"+f"(d[7]),"+f"(d[8]),"+f"(d[9]),"+f"(d[10]),"+f"(d[11])
    : "r"(a0), "r"(a1), "r"(a2), "r"(a3), "r"(blo), "n"(OFF), "n"(BHI), "n"(ACC));
}
template <int OFF, uint32_t BHI, int ACC>
__device__ __forceinline__ void wgmma_rs16(float (&d)[8], uint32_t a0, uint32_t a1, uint32_t a2, uint32_t a3, uint32_t blo) {
  asm volatile("{\n.reg .pred p;\n.reg .b32 l;\n.reg .b64 bd;\nsetp.ne.b32 p, %15, 0;\nadd.u32 l, %12, %13;\nmov.b64 bd, {l, %14};\n"
    "wgmma.mma_async.sync.aligned.m64n16k16.f32.bf16.bf16 {%0,%1,%2,%3,%4,%5,%6,%7}, {%8,%9,%10,%11}, bd, p, 1, 1, 1;\n}\n"
    : "+f"(d[0]),"+f"(d[1]),"+f"(d[2]),"+f"(d[3]),"+f"(d[4]),"+f"(d[5]),"+f"(d[6]),"+f"(d[7])
    : "r"(a0), "r"(a1), "r"(a2), "r"(a3), "r"(blo), "n"(OFF), "n"(BHI), "n"(ACC));
}

constexpr int A_R1 = 0;
constexpr int A_R2A = A_R1 + 2624, A_R2B = A_R2A + 768, A_R3A = A_R2B + 768, A_R3B = A_R3A + 528;
constexpr int A_K1024 = A_R3B + 528;
constexpr int A_W5 = A_K1024 + 16;
constexpr int A_W3 = A_W5 + 4096;
constexpr int A_W9 = A_W3 + 4112;
constexpr int A_W7 = A_W9 + 2048;
constexpr int A_V  = A_W7 + 2048;
constexpr int A_UB = A_V + 2048;
constexpr int A_STG = A_UB + 5248;
constexpr int A_Y2 = A_STG, A_Y3 = A_Y2 + 6528, A_YB = A_Y3 + 4352;
constexpr int A_REC = A_STG + 4 * 4352;
constexpr int A_CH = A_REC + 8192;
static_assert(A_W5 % 16 == 0 && A_UB % 16 == 0 && A_CH % 16 == 0 && A_YB + 4096 <= A_REC, "layout");

struct cf { float x, y; };
__device__ __forceinline__ cf cmul(cf a, cf b) { cf r; r.x = fmaf(a.x, b.x, -a.y * b.y); r.y = fmaf(a.x, b.y, a.y * b.x); return r; }
__device__ __forceinline__ cf cexp_l(float lr, float li, float l) {
  float mag; asm("ex2.approx.ftz.f32 %0, %1;" : "=f"(mag) : "f"((lr * l) * 1.4426950408889634f));
  const float th = li * l;
  const float k = (fmaf(th, 0.15915494f, 12582912.f)) - 12582912.f;
  float ph = fmaf(th, 0.15915494f, -k);
  ph = fmaf(th, 6.4206383e-9f, ph) * 6.2831853f;
  cf r; r.x = mag * __cosf(ph); r.y = mag * __sinf(ph); return r;
}
__device__ __forceinline__ void sts16(uint32_t a, uint32_t v) { asm volatile("st.shared.u16 [%0], %1;" ::"r"(a), "h"((uint16_t)v) : "memory"); }
__device__ __forceinline__ void sts32(uint32_t a, uint32_t v) { asm volatile("st.shared.u32 [%0], %1;" ::"r"(a), "r"(v) : "memory"); }
__device__ __forceinline__ void sts64(uint32_t a, uint32_t v0, uint32_t v1) { asm volatile("st.shared.v2.u32 [%0], {%1, %2};" ::"r"(a), "r"(v0), "r"(v1) : "memory"); }
__device__ __forceinline__ void sts128(uint32_t a, uint32_t v0, uint32_t v1, uint32_t v2, uint32_t v3) {
  asm volatile("st.shared.v4.u32 [%0], {%1, %2, %3, %4};" ::"r"(a), "r"(v0), "r"(v1), "r"(v2), "r"(v3) : "memory");
}
__device__ __forceinline__ uint32_t lds32(uint32_t a) { uint32_t v; asm volatile("ld.shared.u32 %0, [%1];" : "=r"(v) : "r"(a) : "memory"); return v; }
__device__ __forceinline__ uint4 lds128(uint32_t a) {
  uint4 v; asm volatile("ld.shared.v4.u32 {%0, %1, %2, %3}, [%4];" : "=r"(v.x), "=r"(v.y), "=r"(v.z), "=r"(v.w) : "r"(a) : "memory"); return v;
}
__device__ __forceinline__ void ldsm4(uint32_t* r, uint32_t a) {
  asm volatile("ldmatrix.sync.aligned.m8n8.x4.shared.b16 {%0,%1,%2,%3}, [%4];" : "=r"(r[0]), "=r"(r[1]), "=r"(r[2]), "=r"(r[3]) : "r"(a) : "memory");
}
__device__ __forceinline__ void mma16816(float* d, const uint32_t* a, uint32_t b0, uint32_t b1) {
  asm volatile("mma.sync.aligned.m16n8k16.row.col.f32.bf16.bf16.f32 {%0,%1,%2,%3}, {%4,%5,%6,%7}, {%8,%9}, {%0,%1,%2,%3};"
               : "+f"(d[0]), "+f"(d[1]), "+f"(d[2]), "+f"(d[3]) : "r"(a[0]), "r"(a[1]), "r"(a[2]), "r"(a[3]), "r"(b0), "r"(b1));
}
__device__ __forceinline__ uint32_t hsub2_bf(uint32_t a, uint32_t b) { uint32_t r; asm("sub.rn.bf16x2 %0, %1, %2;" : "=r"(r) : "r"(a), "r"(b)); return r; }
__device__ __forceinline__ void bar_sync(int id, int n) { asm volatile("bar.sync %0, %1;" ::"r"(id), "r"(n) : "memory"); }

template <int S> struct F1B { static constexpr int c = S / 4 + ((S & 3) == 3 ? 0 : 0), cc = (16 * S) / 64, ks = (64 * cc - (16 * S - 48)) / 16, off = (A_UB + 2 * ks * 656 + (9 - cc) * 16) / 16; };

template <int NS>
__device__ __forceinline__ void load_quads(uint32_t* q, uint32_t addr) {
#pragma unroll
  for (int i = 0; i < NS; i++) {
    q[4 * i] = lds32(addr + i * 64); q[4 * i + 1] = lds32(addr + i * 64 + 32);
    q[4 * i + 2] = i ? q[4 * i - 3] : lds32(addr - 32);
    q[4 * i + 3] = q[4 * i];
  }
#pragma unroll
  for (int i = 0; i < 4 * NS; i++) asm volatile("" : "+r"(q[i]));
}
template <int S0, int NS>
__device__ __forceinline__ void f1_steps(float (&acc)[16], const uint32_t* a, uint32_t blo) {
  if constexpr (NS > 0) {
    wgmma_rs32<F1B<S0>::off, 8, S0 != 0>(acc, a[0], a[1], a[2], a[3], blo);
    f1_steps<S0 + 1, NS - 1>(acc, a + 4, blo);
  }
}
template <int S0, int NS, int BASE, int FIRST>
__device__ __forceinline__ void s2_steps(float (&acc)[12], const uint32_t* a, uint32_t blo) {
  if constexpr (NS > 0) {
    wgmma_rs24<BASE / 16 + (112 - 16 * S0), 64, !(FIRST && S0 == 0)>(acc, a[0], a[1], a[2], a[3], blo);
    s2_steps<S0 + 1, NS - 1, BASE, FIRST>(acc, a + 4, blo);
  }
}
template <int S0, int NS, int BASE, int FIRST>
__device__ __forceinline__ void s3_steps(float (&acc)[8], const uint32_t* a, uint32_t blo) {
  if constexpr (NS > 0) {
    wgmma_rs16<BASE / 16 + (48 - 16 * S0), 64, !(FIRST && S0 == 0)>(acc, a[0], a[1], a[2], a[3], blo);
    s3_steps<S0 + 1, NS - 1, BASE, FIRST>(acc, a + 4, blo);
  }
}

__device__ __forceinline__ void phase_a(
        unsigned char* sm, const uint32_t bar_rec, const uint32_t ep_addr,
        const __nv_bfloat16* __restrict__ x, const uint32_t* __restrict__ are, const uint32_t* __restrict__ aim,
        const uint32_t* __restrict__ bre, const uint32_t* __restrict__ bim, const uint32_t* __restrict__ cre,
        const uint32_t* __restrict__ cim, const unsigned short* __restrict__ logdt, const unsigned short* __restrict__ dskip,
        const uint4* __restrict__ wgate, const uint4* __restrict__ wup, const uint4* __restrict__ wdown) {
  const uint32_t sb = s2u(sm);
  const int tid = threadIdx.x, wg = tid >> 7, warp = tid >> 5, lane = tid & 31, wq = warp & 3, t128 = tid & 127;
  const int blk = blockIdx.x;
  const bool conv = blk < 112;

  uint2 xr[4];
  {
    const uint2* p = (const uint2*)(x + (size_t)(blk * 16 + warp) * DM);
    xr[0] = __ldg(p + lane); xr[1] = __ldg(p + 32 + lane); xr[2] = __ldg(p + 64 + lane);
    xr[3] = lane < 16 ? __ldg(p + 96 + lane) : make_uint2(0, 0);
  }
  const int ch = conv ? blk * 4 + wg : 0;
  const uint32_t cb = sb + wg * A_CH;
  uint32_t prm[6];
  {
    const int i = ch * 128 + t128;
    prm[0] = __ldg(are + i); prm[1] = __ldg(aim + i); prm[2] = __ldg(bre + i); prm[3] = __ldg(bim + i); prm[4] = __ldg(cre + i); prm[5] = __ldg(cim + i);
  }
  const uint32_t ldt = __ldg(logdt + ch);
  uint32_t cnt0 = 0;
  if (tid == 0) cnt0 = __ldcg(&g_cnt1);
#pragma unroll
  for (int i = 0; i < 4; i++) if (i < 3 || t128 < (A_W5 + 1024) / 16 - 384) sts128(cb + (i * 128 + t128) * 16, 0, 0, 0, 0);
  if (t128 < 65) sts128(cb + (t128 < 64 ? A_W3 + t128 * 16 : A_W9), 0, 0, 0, 0);
  if (t128 < 72) sts128(cb + A_UB + (t128 / 9) * 656 + (t128 % 9) * 16, 0, 0, 0, 0);
  {
    float s = 0.f, q = 0.f;
#pragma unroll
    for (int i = 0; i < 4; i++) {
      const float a = bf_lo(xr[i].x), b = bf_hi(xr[i].x), c = bf_lo(xr[i].y), d = bf_hi(xr[i].y);
      s += (a + b) + (c + d);
      q = fmaf(a, a, q); q = fmaf(b, b, q); q = fmaf(c, c, q); q = fmaf(d, d, q);
    }
#pragma unroll
    for (int o = 16; o; o >>= 1) { s += __shfl_xor_sync(~0u, s, o); q += __shfl_xor_sync(~0u, q, o); }
    const float mean = s * (1.f / DM);
    const float var = fmaxf(fmaf(-mean, mean, q * (1.f / DM)), 0.f);
    const float rs = __frcp_rn(rbf(__fsqrt_rn(rbf(rbf(var) + 1e-5f))));
    const uint32_t mm = pack_bf16(mean, mean);
    const uint32_t tu = sb + A_REC + (warp >> 3) * A_CH + (warp & 7) * 912 + lane * 8, tx = tu + 2 * A_CH;
#pragma unroll
    for (int i = 0; i < 4; i++) {
      if (i < 3 || lane < 16) {
        const uint32_t d0 = hsub2_bf(xr[i].x, mm), d1 = hsub2_bf(xr[i].y, mm);
        sts64(tu + i * 256, pack_bf16(bf_lo(d0) * rs, bf_hi(d0) * rs), pack_bf16(bf_lo(d1) * rs, bf_hi(d1) * rs));
        sts64(tx + i * 256, xr[i].x, xr[i].y);
      }
    }
  }
  if (tid == 0) sts32(ep_addr, (cnt0 >> 7) + 1u);
  if (tid == 320) TR(0, 1);
  auto publish_rows = [&]() {
    bar_sync(5, 512);
    uint4* dst = g_ux + ((size_t)(warp * 8 + (lane >> 2)) * 128 + blk) * 4 + ((lane ^ (blk >> 1)) & 3);
#pragma unroll
    for (int i = 0; i < 4; i++) {
      if (i < 3 || warp < 8) {
        uint32_t r[4];
        asm volatile("ldmatrix.sync.aligned.m8n8.x4.trans.shared.b16 {%0,%1,%2,%3}, [%4];" : "=r"(r[0]), "=r"(r[1]), "=r"(r[2]), "=r"(r[3])
                     : "r"(sb + A_REC + (lane >> 3) * A_CH + (lane & 7) * 912 + (warp + 16 * i) * 16) : "memory");
        dst[i * 65536] = make_uint4(r[0], r[1], r[2], r[3]);
      }
    }
    if (warp != 0) asm volatile("bar.arrive 6, 512;" ::: "memory");
  };
  auto release_rows = [&]() {
    if (warp == 0) {
      bar_sync(6, 512);
      if (lane == 0) { asm volatile("red.release.gpu.global.add.u32 [%0], 1;" ::"l"(&g_cnt1) : "memory"); TR(0, 8); }
      __syncwarp();
    }
  };

  if (!conv) {
    publish_rows();
    release_rows();
    const int a = blk - 112, mat = a >> 3, j = a & 7;
    float s[8];
#pragma unroll
    for (int k = 0; k < 8; k++) s[k] = 0.f;
    if (lane < 28) {
      const uint4* src = (mat ? wup : wgate) + j * 28 + lane + (size_t)warp * 224;
#pragma unroll
      for (int hb = 0; hb < 2; hb++) {
        uint4 v[14];
#pragma unroll
        for (int r = 0; r < 14; r++) v[r] = __ldg(src + (size_t)(hb * 14 + r) * 16 * 224);
#pragma unroll
        for (int r = 0; r < 14; r++) {
          s[0] += bf_lo(v[r].x); s[1] += bf_hi(v[r].x); s[2] += bf_lo(v[r].y); s[3] += bf_hi(v[r].y);
          s[4] += bf_lo(v[r].z); s[5] += bf_hi(v[r].z); s[6] += bf_lo(v[r].w); s[7] += bf_hi(v[r].w);
        }
      }
      float4* red = (float4*)(sm + A_STG + warp * 896 + lane * 32);
      red[0] = make_float4(s[0], s[1], s[2], s[3]); red[1] = make_float4(s[4], s[5], s[6], s[7]);
    }
    bar_sync(5, 512);
    if (tid < 224) {
      float t = 0.f;
#pragma unroll
      for (int w = 0; w < 16; w++) t += *(const float*)(sm + A_STG + w * 896 + tid * 4);
      const float hi = rbf(t), mid = rbf(t - hi), lo = rbf(t - hi - mid);
      const int q = tid / 112, n = tid % 112 + 112 * mat;
      __nv_bfloat16* dst = (__nv_bfloat16*)(g_cimg + (j * 2 + q) * 224 + (n >> 3) * 8) + (n & 7);
      dst[0] = __float2bfloat16_rn(hi); dst[8] = __float2bfloat16_rn(mid); dst[16] = __float2bfloat16_rn(lo);
#pragma unroll
      for (int k = 3; k < 8; k++) dst[8 * k] = __float2bfloat16_rn(0.f);
    }
    if (tid == 320) TR(0, 10);
    return;
  }

  const int g = lane >> 2, t = lane & 3;
  const int wr = (wq + wg) & 3;
  uint4 wv[6];
  auto w_src = [&](int i) -> const uint4* {
    if (i < 4) return (blk < 56 ? wgate : wup) + (blk % 56) * 4 + (lane & 3) + (size_t)(i * 128 + warp * 8 + (lane >> 2)) * 224;
    const int it = warp + 16 * (i - 4);
    return wdown + (size_t)(blk * 16 + (it / 14) * 8 + (lane >> 2)) * 56 + (it % 14) * 4 + (lane & 3);
  };
  auto w_on = [&](int i) { return i == 3 ? warp < 8 : i == 5 ? warp < 12 : true; };
  {
    const uint32_t stg = cb + A_STG + wq * 4352;
    const float dt = rbf(expf(__uint_as_float(ldt << 16)));
    float lr[2], li[2];
    cf bq[2], b0[2], b4[2];
    uint32_t bf[48];
#pragma unroll
    for (int m = 0; m < 2; m++) {
      lr[m] = dt * (m ? bf_hi(prm[0]) : bf_lo(prm[0]));
      li[m] = dt * (m ? bf_hi(prm[1]) : bf_lo(prm[1]));
    }
    {
      cf b[2], z[2];
#pragma unroll
      for (int m = 0; m < 2; m++) {
        cf db, c;
        db.x = dt * (m ? bf_hi(prm[2]) : bf_lo(prm[2])); db.y = -dt * (m ? bf_hi(prm[3]) : bf_lo(prm[3]));
        c.x = m ? bf_hi(prm[4]) : bf_lo(prm[4]); c.y = -(m ? bf_hi(prm[5]) : bf_lo(prm[5]));
        b[m] = cmul(c, db);
        z[m] = cexp_l(lr[m], -li[m], 1.f);
        bq[m] = cexp_l(lr[m], -li[m], 256.f);
      }
#pragma unroll
      for (int i = 0; i < 8; i++) {
        sts64(stg + i * 272 + lane * 8, pack_bf16(b[0].x, b[0].y), pack_bf16(b[1].x, b[1].y));
        if (!(i & 1)) {
          cf e0 = cmul(b[0], bq[0]), e1 = cmul(b[1], bq[1]);
          sts64(stg + (8 + i / 2) * 272 + lane * 8, pack_bf16(e0.x, e0.y), pack_bf16(e1.x, e1.y));
          if (i == 0) { b0[0] = e0; b0[1] = e1; }
          if (i == 4) { b4[0] = e0; b4[1] = e1; }
        }
        if (i < 7) { b[0] = cmul(b[0], z[0]); b[1] = cmul(b[1], z[1]); }
        if (i == 1) publish_rows();
      }
#pragma unroll
      for (int i = 0; i < 7; i++) {
        b0[0] = cmul(b0[0], bq[0]); b0[1] = cmul(b0[1], bq[1]);
        sts64(stg + (i < 2 ? 12 + 2 * i : i - 2) * 272 + lane * 8, pack_bf16(b0[0].x, b0[0].y), pack_bf16(b0[1].x, b0[1].y));
        if (i < 2) {
          b4[0] = cmul(b4[0], bq[0]); b4[1] = cmul(b4[1], bq[1]);
          sts64(stg + (13 + 2 * i) * 272 + lane * 8, pack_bf16(b4[0].x, b4[0].y), pack_bf16(b4[1].x, b4[1].y));
        }
        if (i == 1) {
          __syncwarp();
#pragma unroll
          for (int n = 0; n < 2; n++)
#pragma unroll
            for (int k2 = 0; k2 < 4; k2++) ldsm4(bf + n * 16 + k2 * 4, stg + (n * 8 + (lane & 7)) * 272 + k2 * 64 + (lane >> 3) * 16);
          __syncwarp();
        }
      }
    }
    __syncwarp();
#pragma unroll
    for (int k2 = 0; k2 < 4; k2++) ldsm4(bf + 32 + k2 * 4, stg + (lane & 7) * 272 + k2 * 64 + (lane >> 3) * 16);
    release_rows();
    if (!(lane & 1)) {
#pragma unroll
      for (int i = 0; i < 6; i++) if (w_on(i)) asm volatile("prefetch.global.L2 [%0];" ::"l"(w_src(i)));
    }
    if (tid == 320) TR(0, 16);
    float c[6][4];
#pragma unroll
    for (int i = 0; i < 6; i++) { c[i][0] = 0.f; c[i][1] = 0.f; c[i][2] = 0.f; c[i][3] = 0.f; }
    cf p[2], v[2];
    p[0] = cexp_l(lr[0], li[0], 8.f); p[1] = cexp_l(lr[1], li[1], 8.f);
    v[0].x = 1.f; v[0].y = 0.f; v[1] = v[0];
#pragma unroll
    for (int mt = 0; mt < 2; mt++) {
      __syncwarp();
#pragma unroll
      for (int i = 0; i < 16; i++) {
        sts64(stg + i * 272 + lane * 8, pack_bf16(v[0].x, v[0].y), pack_bf16(v[1].x, v[1].y));
        if (mt == 0 && i == 0) { v[0] = p[0]; v[1] = p[1]; }
        else if (mt == 0 || i < 15) { v[0] = cmul(v[0], p[0]); v[1] = cmul(v[1], p[1]); }
      }
      __syncwarp();
      if (mt == 1 && tid == 160) {
        const uint32_t tgt = lds32(ep_addr) * 128u;
        uint32_t cv; int it = 0;
        do { asm volatile("ld.acquire.gpu.global.u32 %0, [%1];" : "=r"(cv) : "l"(&g_cnt1) : "memory"); } while ((int)(cv - tgt) < 0 && ++it < 200000);
        asm volatile("fence.proxy.async;" ::: "memory");
        TR(0, 9);
        mbar_expect(bar_rec, 32768);
        for (int c2 = 0; c2 < 4; c2++) bulk_ld(sb + c2 * A_CH + A_REC, g_ux + (size_t)(blk * 4 + c2) * 512, 8192, bar_rec);
      }
#pragma unroll
      for (int ks = 0; ks < 8; ks++) {
        uint32_t a[4];
        ldsm4(a, stg + (lane & 15) * 272 + ks * 32 + (lane >> 4) * 16);
#pragma unroll
        for (int n = 0; n < 3; n++) mma16816(c[n * 2 + mt], a, bf[n * 16 + ks * 2], bf[n * 16 + ks * 2 + 1]);
      }
    }
    __syncwarp();
#pragma unroll
    for (int i = 0; i < 6; i++)
      sts128(stg + i * 512 + lane * 16, __float_as_uint(c[i][0]), __float_as_uint(c[i][1]), __float_as_uint(c[i][2]), __float_as_uint(c[i][3]));
#pragma unroll
    for (int i = 0; i < 6; i++) if (w_on(i)) wv[i] = __ldg(w_src(i));
    bar_sync(1 + wg, 128);
    if (tid == 320) TR(0, 2);
#pragma unroll
    for (int rep = 0; rep < 2; rep++) {
      const int qd = rep ? 2 + wr : 3 - wr;
      if (rep == 0 || wr >= 2) {
        float s[4] = {0.f, 0.f, 0.f, 0.f};
#pragma unroll
        for (int w = 0; w < 4; w++) {
          uint4 u4 = lds128(cb + A_STG + w * 4352 + qd * 512 + lane * 16);
          s[0] += __uint_as_float(u4.x); s[1] += __uint_as_float(u4.y); s[2] += __uint_as_float(u4.z); s[3] += __uint_as_float(u4.w);
        }
#pragma unroll
        for (int hf = 0; hf < 2; hf++) {
          const int j = (qd & 1) * 16 + g + 8 * hf;
          const uint32_t pk = pack_bf16(s[2 * hf + 1], s[2 * hf]);
          const uint32_t v0 = pk >> 16, v1 = pk & 0xFFFFu, v00 = v0 * 0x10001u;
          if (rep == 1) {
            if (t < 2) {
#pragma unroll
              for (int e = 0; e < 2; e++) {
                const int lam = 128 + 32 * (2 * t + e) + j, mu = lam >> 1;
                const uint32_t val = e ? v1 : v0;
                uint32_t a = cb + ((lam & 1) ? A_R3B : A_R3A) + mu * 4;
                if (lam == 128) { a = cb + A_R2A + 128 * 4; sts32(cb + A_K1024, val << 16); }
                sts16(a, val); sts16(a + 6, val);
              }
            } else if (t == 2 && j == 0) { sts16(cb + A_R3A + 128 * 4, v0); }
          } else if (qd < 2) {
            const uint32_t a = cb + A_R1 + (62 + 8 * j + 2 * t) * 4;
            sts16(a, v0); sts32(a + 4, pk); sts16(a + 10, v1);
          } else if (t < 2) {
            const int L = 256 + 8 * j + 4 * t;
            const uint32_t a = cb + A_R1 + (62 + L) * 4;
            if (L > 256) { sts16(a - 4, v0); sts32(a, v00); } else sts16(a, v0);
            sts32(a + 4, v00); sts32(a + 8, pk); sts16(a + 14, v1);
          } else {
            const int mu = 64 + 32 * (t - 2) + j;
            if (mu == 64) {
              const uint32_t a = cb + A_R1 + (62 + 512) * 4;
              sts16(a - 4, v0); sts32(a, v00); sts32(a + 4, v00); sts32(a + 8, v00); sts16(a + 14, v0);
            } else { sts16(cb + A_R2A + mu * 4, v0); sts16(cb + A_R2A + mu * 4 + 6, v0); }
            sts16(cb + A_R2B + mu * 4, v1); sts16(cb + A_R2B + mu * 4 + 6, v1);
          }
        }
      }
    }
  }
  {
    const int ngg = (blk % 56) * 4 + (lane & 3), j = ngg / 28, q = (ngg % 28) / 14, ng = ngg % 14 + (blk < 56 ? 0 : 14);
    uint4* dst = g_wimg + (size_t)j * 37632 + q * 14 * 896 + ng * 32 + (warp >> 2) * 896 + (warp & 3) * 8 + (lane >> 2);
#pragma unroll
    for (int i = 0; i < 4; i++) if (w_on(i)) dst[i * 4 * 896] = wv[i];
#pragma unroll
    for (int i = 4; i < 6; i++) {
      const int it = warp + 16 * (i - 4), n2 = (it % 14) * 4 + (lane & 3), k = (blk % 7) * 16 + (it / 14) * 8 + (lane >> 2);
      if (w_on(i)) g_wimg[(size_t)(blk / 14) * 37632 + 25088 + ((n2 / 7) * 2 + (blk / 7) % 2) * 784 + (n2 % 7) * 112 + k] = wv[i];
    }
  }
  if (tid == 320) TR(0, 3);

  const int bk = wr * 32 + lane;
  uint32_t xt[8], ud[8];
  {
    mbar_wait(bar_rec, 0);
    if (tid == 320) TR(0, 4);
    uint4 r[4];
#pragma unroll
    for (int i = 0; i < 4; i++) r[i] = lds128(cb + A_REC + bk * 64 + ((i ^ (bk >> 1)) & 3) * 16);
    const uint32_t ua = cb + A_UB + ((2 * bk) & 7) * 656 + ((bk >> 2) + 9) * 16;
    sts128(ua, r[0].x, r[1].x, r[2].x, r[3].x);
    sts128(ua + 656, r[0].y, r[1].y, r[2].y, r[3].y);
    if (bk <= 96) {
      const bool neg = bk == 96;
      const int bp = neg ? -1 : bk;
      uint32_t h[4];
      h[0] = lds32(cb + A_REC + ((bp - 1) & 127) * 64 + ((2 ^ ((bp - 1) >> 1)) & 3) * 16 + 4);
      h[1] = lds32(cb + A_REC + ((bp - 1) & 127) * 64 + ((3 ^ ((bp - 1) >> 1)) & 3) * 16 + 4);
      h[2] = lds32(cb + A_REC + (bp + 1) * 64 + ((0 ^ ((bp + 1) >> 1)) & 3) * 16);
      h[3] = lds32(cb + A_REC + (bp + 1) * 64 + ((1 ^ ((bp + 1) >> 1)) & 3) * 16);
      if (bp <= 0) { h[0] = 0; h[1] = 0; }
      const uint32_t wd[12] = {h[0], h[1], neg ? 0 : r[0].x, neg ? 0 : r[1].x, neg ? 0 : r[2].x, neg ? 0 : r[3].x,
                               neg ? 0 : r[0].y, neg ? 0 : r[1].y, neg ? 0 : r[2].y, neg ? 0 : r[3].y, h[2], h[3]};
      float P[25];
      P[0] = 0.f;
#pragma unroll
      for (int i = 0; i < 12; i++) { P[2 * i + 1] = P[2 * i] + bf_lo(wd[i]); P[2 * i + 2] = P[2 * i + 1] + bf_hi(wd[i]); }
#define WIN(i, hw) (P[(i) + 5 + (hw)] - P[(i) + 4 - (hw)])
#define WPK(i, hw) pack_bf16(WIN(i, hw), WIN((i) + 1, hw))
      const int tp = 2 * bp;
      const uint32_t a3 = cb + A_W3 + (tp + 64) * 16 + 8, a5 = cb + A_W5 + (tp + 64) * 16;
      if (!neg) sts64(a3, WPK(0, 1), WPK(2, 1));
      if (!neg) sts128(a3 + 8, WPK(4, 1), WPK(6, 1), WPK(8, 1), WPK(10, 1));
      sts64(a3 + 24, WPK(12, 1), WPK(14, 1));
      sts128(a5, WPK(0, 2), WPK(2, 2), WPK(4, 2), WPK(6, 2));
      sts128(a5 + 16, WPK(8, 2), WPK(10, 2), WPK(12, 2), WPK(14, 2));
      if (bp < 64) {
        if (!neg) sts128(cb + A_W7 + 1024 + bp * 16, WPK(0, 3), WPK(2, 3), WPK(4, 3), WPK(6, 3));
        if (bp < 63) {
          sts128(cb + A_W7 + (bp + 1) * 16, WPK(8, 3), WPK(10, 3), WPK(12, 3), WPK(14, 3));
          sts128(cb + A_W9 + (bp + 1) * 16, WPK(0, 4), WPK(2, 4), WPK(4, 4), WPK(6, 4));
          sts128(cb + A_W9 + 1024 + (bp + 1) * 16, WPK(8, 4), WPK(10, 4), WPK(12, 4), WPK(14, 4));
        }
        if (!neg) {
#define VPK(i) pack_bf16(P[(i) + 2] - P[i], P[(i) + 3] - P[(i) + 1])
          sts128(cb + A_V + bp * 32, VPK(0), VPK(2), VPK(4), VPK(6));
          sts128(cb + A_V + bp * 32 + 16, VPK(8), VPK(10), VPK(12), VPK(14));
        }
      }
    }
  }
  asm volatile("fence.proxy.async.shared::cta;" ::: "memory");
  bar_sync(1 + wg, 128);
  if (tid == 320) TR(0, 5);

  {
    const uint32_t cbu = __shfl_sync(~0u, cb, 0);
    const uint32_t blo_k = ((cbu & 0x3FFFF) >> 4) | (41u << 16);
    const uint32_t blo_n = ((cbu & 0x3FFFF) >> 4) | (8u << 16);
    const uint32_t tb = cb + (16 * wq + g - 2 * t) * 4;
    float y1[16], y2[12], y3[8];
    const uint32_t dk16 = __ldg(dskip + ch);
    uint32_t qa[32], qb[32];
    const uint32_t t1 = tb + A_R1 + (62 - 48) * 4;
    load_quads<4>(qa, tb + A_R3A + 17 * 4); load_quads<4>(qa + 16, tb + A_R3B + 16 * 4);
    wg_fence();
    s3_steps<0, 4, A_W9, 1>(y3, qa, blo_n); s3_steps<0, 4, A_W7, 0>(y3, qa + 16, blo_n);
    wg_commit();
    load_quads<8>(qb, tb + A_R2A + 16 * 4);
    wg_fence(); s2_steps<0, 8, A_W5, 1>(y2, qb, blo_n); wg_commit();
    wg_wait<1>(); load_quads<8>(qa, tb + A_R2B + 16 * 4);
    wg_fence(); s2_steps<0, 8, A_W3, 0>(y2, qa, blo_n); wg_commit();
    wg_wait<1>(); load_quads<8>(qb, t1);
    wg_fence(); f1_steps<0, 8>(y1, qb, blo_k); wg_commit();
    wg_wait<1>(); load_quads<8>(qa, t1 + 8 * 64);
    wg_fence(); f1_steps<8, 8>(y1, qa, blo_k); wg_commit();
    reg_fence(y2); reg_fence(y3);
    if (tid == 320) TR(0, 18);
    {
      const float k1024 = __uint_as_float(lds32(cb + A_K1024));
#pragma unroll
      for (int i = 0; i < 2; i++)
#pragma unroll
        for (int hf = 0; hf < 2; hf++) {
          const int idx = 16 * (16 * wq + g + 8 * hf) + 8 * i + 2 * t;
          const uint32_t vv = lds32(cb + A_V + idx * 2);
          sts64(cb + A_Y3 + (idx + 4 * (idx >> 6)) * 4, __float_as_uint(fmaf(k1024, bf_lo(vv), y3[4 * i + 2 * hf])),
                __float_as_uint(fmaf(k1024, bf_hi(vv), y3[4 * i + 2 * hf + 1])));
        }
#pragma unroll
      for (int i = 0; i < 3; i++)
#pragma unroll
        for (int hf = 0; hf < 2; hf++) {
          const int idx = 512 * i + 8 * (16 * wq + g + 8 * hf) + 2 * t;
          sts64(cb + A_Y2 + (idx + 4 * (idx >> 6)) * 4, __float_as_uint(y2[4 * i + 2 * hf]), __float_as_uint(y2[4 * i + 2 * hf + 1]));
        }
    }
    wg_wait<1>(); load_quads<8>(qb, t1 + 16 * 64);
    wg_fence(); f1_steps<16, 8>(y1, qb, blo_k); wg_commit();
    wg_wait<1>(); load_quads<8>(qa, t1 + 24 * 64);
    wg_fence(); f1_steps<24, 8>(y1, qa, blo_k); wg_commit();
    wg_wait<1>(); load_quads<5>(qb, t1 + 32 * 64);
    wg_fence(); f1_steps<32, 5>(y1, qb, blo_k); wg_commit();
    bar_sync(1 + wg, 128);
    float ex[12];
#pragma unroll
    for (int i = 1; i < 4; i++)
#pragma unroll
      for (int k = 0; k < 4; k++) {
        const int aa = 8 * i + 2 * t + (k & 1), b = 16 * wq + g + 8 * (k >> 1);
        float e = __uint_as_float(lds32(cb + A_Y2 + ((aa - 8) * 68 + b) * 4));
        if (i >= 2) e += __uint_as_float(lds32(cb + A_Y3 + ((aa - 16) * 68 + b) * 4));
        ex[4 * (i - 1) + k] = e;
      }
    {
      const uint32_t dk = dk16 * 0x10001u;
#pragma unroll
      for (int i = 0; i < 4; i++) {
        const uint4 r = lds128(cb + A_REC + bk * 64 + ((i ^ (bk >> 1)) & 3) * 16);
        ud[i] = hmul2_bf(r.x, dk); ud[4 + i] = hmul2_bf(r.y, dk); xt[i] = r.z; xt[4 + i] = r.w;
      }
    }
    wg_wait<0>();
    reg_fence(y1);
    if (tid == 320) TR(0, 6);
#pragma unroll
    for (int i = 0; i < 12; i++) y1[4 + i] += ex[i];
#pragma unroll
    for (int i = 0; i < 2; i++) {
      const int mi = lane >> 3, aa = 8 * (2 * i + (mi >> 1)) + (lane & 7);
      asm volatile("stmatrix.sync.aligned.m8n8.x4.trans.shared.b16 [%0], {%1,%2,%3,%4};"
                   ::"r"(cb + A_YB + aa * 128 + (((2 * wq + (mi & 1)) ^ (lane & 7)) << 4)),
                     "r"(pack_bf16(y1[8 * i], y1[8 * i + 1])), "r"(pack_bf16(y1[8 * i + 2], y1[8 * i + 3])),
                     "r"(pack_bf16(y1[8 * i + 4], y1[8 * i + 5])), "r"(pack_bf16(y1[8 * i + 6], y1[8 * i + 7])) : "memory");
    }
  }
  bar_sync(1 + wg, 128);
#pragma unroll
  for (int c = 0; c < 2; c++) {
    const int tau = 2 * bk + c, r = ch & 7;
    const uint4 y = lds128(cb + A_YB + (tau >> 3) * 128 + (((tau ^ (tau >> 3)) & 7) << 4));
    g_himg[(size_t)(tau >> 4) * 7168 + (ch >> 3) * 128 + ((tau >> 3) & 1) * 64 + r * 8 + ((tau & 7) ^ r)] =
        make_uint4(hadd2_bf(xt[4 * c], hadd2_bf(y.x, ud[4 * c])), hadd2_bf(xt[4 * c + 1], hadd2_bf(y.y, ud[4 * c + 1])),
                   hadd2_bf(xt[4 * c + 2], hadd2_bf(y.z, ud[4 * c + 2])), hadd2_bf(xt[4 * c + 3], hadd2_bf(y.w, ud[4 * c + 3])));
  }
  if (tid == 320) TR(0, 7);
}

constexpr int B_SA = 0, B_RING = 114688, B_SLOT = 14848, B_NSLOT = 7;
constexpr int B_CS = B_RING + B_NSLOT * B_SLOT;
constexpr int B_RED = B_CS + 7168;
constexpr int B_BAR = B_RED + 256;
constexpr int B_SMEM = B_BAR + 1024, A_SMEM = 4 * A_CH + 64;

__device__ __forceinline__ uint32_t mapa(uint32_t a, uint32_t r) { uint32_t o; asm("mapa.shared::cluster.u32 %0, %1, %2;" : "=r"(o) : "r"(a), "r"(r)); return o; }
template <class T> __device__ __forceinline__ T* pin(T* p) { asm volatile("" : "+l"(p)); return p; }
__device__ __forceinline__ uint32_t pin(uint32_t v) { asm volatile("" : "+r"(v)); return v; }
template <int Q, int ST>
__device__ __forceinline__ void g1_stage(float (&acc)[116], uint32_t alo, uint32_t blo, uint32_t bar_full, uint32_t bar_h) {
  constexpr int s = Q * 14 + ST, sl = s % B_NSLOT;
  if (Q == 0) mbar_wait(bar_h + 8 * ST, 0);
  mbar_wait(bar_full + 8 * sl, (s / B_NSLOT) & 1);
  wg_fence();
  if (Q == 0) {
    wgmma_ss232<(2 * ST) * 256, 0x40000080u, (sl * B_SLOT) / 16, 32, ST != 0>(acc, alo, blo);
    wgmma_ss232<(2 * ST + 1) * 256, 0x40000080u, (sl * B_SLOT + 256) / 16, 32, 1>(acc, alo, blo);
  } else {
    wgmma_ss224<(2 * ST) * 256, 0x40000080u, (sl * B_SLOT) / 16, 32, ST != 0>(*(float(*)[112])acc, alo, blo);
    wgmma_ss224<(2 * ST + 1) * 256, 0x40000080u, (sl * B_SLOT + 256) / 16, 32, 1>(*(float(*)[112])acc, alo, blo);
  }
}

__global__ void __launch_bounds__(512, 1)
k_front(const __nv_bfloat16* __restrict__ x, const uint32_t* __restrict__ are, const uint32_t* __restrict__ aim,
        const uint32_t* __restrict__ bre, const uint32_t* __restrict__ bim, const uint32_t* __restrict__ cre,
        const uint32_t* __restrict__ cim, const unsigned short* __restrict__ logdt, const unsigned short* __restrict__ dskip,
        const uint4* __restrict__ wgate, const uint4* __restrict__ wup, const uint4* __restrict__ wdown) {
  extern __shared__ __align__(1024) unsigned char sm[];
  const uint32_t bar_rec = s2u(sm) + 4 * A_CH;
  if (threadIdx.x == 320) TR(0, 0);
  asm volatile("griddepcontrol.launch_dependents;");
  if (threadIdx.x == 160) { mbar_init(bar_rec, 1); asm volatile("fence.mbarrier_init.release.cluster;" ::: "memory"); }
  phase_a(sm, bar_rec, bar_rec + 8, x, are, aim, bre, bim, cre, cim, logdt, dskip, wgate, wup, wdown);
}

__global__ void __cluster_dims__(2, 1, 1) __launch_bounds__(384, 1) k_ffn(__nv_bfloat16* __restrict__ out) {
  extern __shared__ __align__(1024) unsigned char sm[];
  const uint32_t sb = s2u(sm);
  const int tid = threadIdx.x, wg = tid >> 7, warp = tid >> 5, lane = tid & 31;
  const uint32_t bar_full = sb + B_BAR, bar_empty = bar_full + 64, bar_h = bar_full + 128, bar_cs = bar_full + 240,
                 bar_g2 = bar_full + 248, bar_in = bar_full + 256;
  if (tid == 0) {
    TR(1, 0);
    for (int i = 0; i < B_NSLOT; i++) { mbar_init(bar_full + 8 * i, 1); mbar_init(bar_empty + 8 * i, 4); }
    asm volatile("fence.mbarrier_init.release.cluster;" ::: "memory");
  } else if (tid == 32) {
    for (int i = 0; i < 14; i++) mbar_init(bar_h + 8 * i, 1);
  } else if (tid == 64) {
    mbar_init(bar_cs, 1);
    mbar_init(bar_g2, 4);
    for (int i = 0; i < 14; i++) mbar_init(bar_in + 8 * i, 1);
  } else if (tid >= 128 && tid < 352) {
    sts128(sb + B_RING + ((tid - 128) >> 5) * B_SLOT + 14336 + (tid & 31) * 16, 0x3F803F80u, 0x3F803F80u, 0x3F803F80u, 0x3F803F80u);
  }
  asm volatile("fence.proxy.async.shared::cta;" ::: "memory");
  __syncthreads();
  asm volatile("barrier.cluster.arrive.relaxed.aligned;" ::: "memory");
  const int rank = blockIdx.x & 1, rt = blockIdx.x & 15, j = blockIdx.x >> 4;
  const int wq = warp & 3, t128 = tid & 127, g = lane >> 2, t = lane & 3;
  asm volatile("griddepcontrol.wait;" ::: "memory");
  uint32_t ep, tag;
  auto load_ep = [&]() { asm volatile("ld.relaxed.gpu.global.u32 %0, [%1];" : "=r"(ep) : "l"(&g_cnt1) : "memory"); };
  auto in_addr = [&](int q, int cw) { return sb + B_SA + ((j + 1 + q) & 7) * 14336 + cw * 1792; };
  auto in_src = [&](int q, int cw) { return g_part + (size_t)((rt * 8 + ((j + 7 - q) & 7)) * 7 + q) * 896 + cw * 112; };
  auto add_in = [&](float (&sum)[28], int q, int cw) {
    const uint32_t a = in_addr(q, cw);
    const uint4 v0 = lds128(a + lane * 16), v1 = lds128(a + 512 + lane * 16), v2 = lds128(a + 1024 + lane * 16);
    uint32_t in[14] = {v0.x, v0.y, v0.z, v0.w, v1.x, v1.y, v1.z, v1.w, v2.x, v2.y, v2.z, v2.w, 0, 0};
    asm volatile("ld.shared.v2.u32 {%0, %1}, [%2];" : "=r"(in[12]), "=r"(in[13]) : "r"(a + 1536 + lane * 8) : "memory");
    int it = 0;
    while ((((in[3] ^ tag) | (in[7] ^ tag) | (in[11] ^ tag) | (in[13] ^ tag)) & 0x10000u) && ++it < 400000) {
      const uint4* gs = pin(in_src(q, cw));
#pragma unroll
      for (int i = 0; i < 3; i++) ld128(gs + i * 32 + lane, in + 4 * i);
      asm volatile("{\n.reg .b64 v;\nld.relaxed.gpu.global.b64 v, [%2];\nmov.b64 {%0, %1}, v;\n}"
                   : "=r"(in[12]), "=r"(in[13]) : "l"((const uint2*)(gs + 96) + lane) : "memory");
    }
#pragma unroll
    for (int i = 0; i < 14; i++) { sum[2 * i] += bf_lo(in[i]); sum[2 * i + 1] += bf_hi(in[i]); }
  };
  auto w_issue = [&](int s) {
    const char* wsrc = (const char*)g_wimg + (size_t)j * 602112;
    const int slot = s % B_NSLOT;
    const uint32_t dst = sb + B_RING + slot * B_SLOT, fb = bar_full + 8 * slot;
    if (s < 28) {
      mbar_expect(fb, 14336);
      bulk_ld_mc(dst + rank * 7168, wsrc + s * 14336 + rank * 7168, 7168, fb);
    } else {
      const int c = (j + 1 + ((s - 28) >> 1)) & 7;
      mbar_expect(fb, 12544);
      bulk_ld_mc(dst + rank * 6272, wsrc + 401408 + (c * 2 + (s & 1)) * 12544 + rank * 6272, 6272, fb);
    }
  };

  if (wg == 2) {
    asm volatile("setmaxnreg.dec.sync.aligned.u32 56;");
    if (warp != 9) asm volatile("barrier.cluster.wait.aligned;" ::: "memory");
    if (warp == 8) {
      if (lane == 0) {
        TR(1, 1);
        for (int s = 0; s < 44; s++) {
          if (s >= B_NSLOT) mbar_wait(bar_empty + 8 * (s % B_NSLOT), (s / B_NSLOT - 1) & 1);
          w_issue(s);
        }
      }
    } else if (warp == 9) {
      if (lane == 0) {
        const char* hsrc = (const char*)g_himg + (size_t)rt * 114688;
        for (int i = 0; i < 14; i++) {
          mbar_expect(bar_h + 8 * i, 8192);
          bulk_ld(sb + B_SA + i * 8192, hsrc + i * 8192, 8192, bar_h + 8 * i);
        }
        mbar_expect(bar_cs, 7168);
        bulk_ld(sb + B_CS, g_cimg + j * 448, 7168, bar_cs);
      }
      __syncwarp();
      asm volatile("barrier.cluster.wait.aligned;" ::: "memory");
      load_ep(); ep >>= 7;
      const int lq = (lane >> 1) & 7, lcw = (lane & 1) * 4;
      const uint4* fl = (const uint4*)(g_flag + (rt * 8 + ((j + 7 - lq) & 7)) * 64 + lq * 8 + lcw);
      bool todo = lane < 14, live = false;
      int it = 0;
      while (__any_sync(~0u, todo) && ++it < 400000) {
        if (!live) { __nanosleep(400); live = mbar_test(bar_g2, 0); }
        if (todo) {
          uint32_t w[4];
          ld128(fl, w);
          if (live && w[0] == ep && w[1] == ep && w[2] == ep && w[3] == ep) {
            asm volatile("fence.proxy.async;" ::: "memory");
            mbar_expect(bar_in + 8 * lane, 7168);
            bulk_ld(in_addr(lq, lcw), in_src(lq, lcw), 7168, bar_in + 8 * lane);
            todo = false;
            if (lane & 1) TR(1, 24 + lq);
          }
        }
      }
    } else {
      const int t64 = tid - 320;
      load_ep();
      const int r = (lane >> 1) & 7, c = (j & 3) * 2 + (lane & 1);
      const uint32_t src = sb + B_SA + (t64 >> 4) * 2048 + (j >> 2) * 1024 + r * 128 + ((c ^ r) << 4);
      float a[16];
#pragma unroll
      for (int k = 0; k < 16; k++) a[k] = 0.f;
#pragma unroll 1
      for (int i = 0; i < 14; i++) {
        mbar_wait(bar_h + 8 * i, 0);
        uint4 v = lds128(src + i * 8192);
        float e[8] = {bf_lo(v.x), bf_hi(v.x), bf_lo(v.y), bf_hi(v.y), bf_lo(v.z), bf_hi(v.z), bf_lo(v.w), bf_hi(v.w)};
#pragma unroll
        for (int k = 0; k < 8; k++) { a[2 * k] += e[k]; a[2 * k + 1] = fmaf(e[k], e[k], a[2 * k + 1]); }
        __nanosleep(160);
      }
      __syncwarp();
      if (lane == 0) mbar_arrive(bar_g2);
#pragma unroll
      for (int rd = 0; rd < 4; rd++) {
        const int n = 8 >> rd;
        const bool up = lane & (2 * n);
#pragma unroll
        for (int k = 0; k < 8; k++) {
          if (k < n) {
            float keep = up ? a[k + n] : a[k], give = up ? a[k] : a[k + n];
            a[k] = keep + __shfl_xor_sync(~0u, give, 2 * n);
          }
        }
      }
      float* red = (float*)(sm + B_RED);
      red[(warp & 1) * 32 + (lane & 1) * 16 + (lane >> 1)] = a[0];
      bar_sync(1, 64);
      if (t64 < 16) {
        float mean = (red[2 * t64] + red[32 + 2 * t64]) * (1.f / DM);
        float var = fmaxf(fmaf(-mean, mean, (red[2 * t64 + 1] + red[33 + 2 * t64]) * (1.f / DM)), 0.f);
        float rs = __frcp_rn(rbf(__fsqrt_rn(rbf(rbf(var) + 1e-5f))));
        asm volatile("st.relaxed.gpu.global.u32 [%0], %1;"
                     ::"l"(g_stat2 + rt * 128 + j * 16 + t64), "r"((__float_as_uint(rs * rs) & ~1u) | ((ep >> 7) & 1u)) : "memory");
      }
      if (t64 == 0) TR(1, 2);
    }
  } else {
    asm volatile("setmaxnreg.inc.sync.aligned.u32 224;");
    asm volatile("barrier.cluster.wait.aligned;" ::: "memory");
    uint32_t hh[56];
    const uint32_t rel_bar = pin(mapa(bar_empty, t128 & 1));
    const bool relt = t128 < 2;
    auto release = [&](int sl) { if (relt) asm volatile("mbarrier.arrive.shared::cluster.b64 _, [%0];" ::"r"(rel_bar + 8 * sl) : "memory"); };
    const uint32_t alo = __shfl_sync(~0u, ((sb + B_SA + wg * 1024) & 0x3FFFF) >> 4, 0);
    const uint32_t blo = (((sb + B_RING) & 0x3FFFF) >> 4) | (8u << 16);
    const uint32_t clo = ((sb + B_CS) & 0x3FFFF) >> 4;
    uint32_t nm0, nm1;
    if (wg == 1) bar_sync(3, 256);
#define G1S(Q, ST) do { g1_stage<Q, ST>(acc, alo, blo, bar_full, bar_h); wg_commit(); \
      if (ST > 0) { wg_wait<1>(); release((Q * 14 + ST - 1) % B_NSLOT); } } while (0)
#define G1HH(Q) do { \
      _Pragma("unroll") \
      for (int i = 0; i < 28; i++) hh[28 * Q + i] = pack_bf16(acc[2 * i] * acc[56 + 2 * i], acc[2 * i + 1] * acc[57 + 2 * i]); \
    } while (0)
    {
      float acc[116];
      G1S(0, 0);
      if (tid == 0) TR(1, 3);
      G1S(0, 1);
      if (wg == 0) asm volatile("bar.arrive 3, 256;" ::: "memory");
      G1S(0, 2); G1S(0, 3); G1S(0, 4); G1S(0, 5); G1S(0, 6); G1S(0, 7); G1S(0, 8); G1S(0, 9); G1S(0, 10); G1S(0, 11); G1S(0, 12);
      G1S(0, 13);
      if (tid == 0) TR(1, 4);
      mbar_wait(bar_cs, 0);
      wg_wait<0>(); reg_fence(acc); release(13 % B_NSLOT);
      {
        const uint32_t msk = t == 0 ? 0xFFFFFFFFu : t == 1 ? 0xFFFFu : 0u;
        const float a = acc[112] * (-1.f / DM), b = acc[114] * (-1.f / DM);
        nm0 = pack_bf16(a, a) & msk; nm1 = pack_bf16(b, b) & msk;
      }
      wg_fence();
      wgmma_rs224<0, 8, 1>(*(float(*)[112])acc, nm0, nm1, 0u, 0u, clo);
      wg_commit(); wg_wait<0>(); reg_fence(acc);
      G1HH(0);
      if (tid == 0) TR(1, 5);
      G1S(1, 0); G1S(1, 1); G1S(1, 2); G1S(1, 3); G1S(1, 4); G1S(1, 5); G1S(1, 6); G1S(1, 7); G1S(1, 8); G1S(1, 9); G1S(1, 10); G1S(1, 11);
      G1S(1, 12);
      load_ep();
      g1_stage<1, 13>(acc, alo, blo, bar_full, bar_h);
      wgmma_rs224<224, 8, 1>(*(float(*)[112])acc, nm0, nm1, 0u, 0u, clo);
      wg_commit(); wg_wait<1>(); release(26 % B_NSLOT);
      wg_wait<0>(); reg_fence(acc); release(27 % B_NSLOT);
      if (t128 == 0) mbar_arrive(bar_g2);
      G1HH(1);
      if (tid == 0) TR(1, 6);
    }
    float accA[28], accB[28];
    ep = pin(ep >> 7); tag = pin((ep & 1u) << 16);
#define ISSUE(acc, I, a, FIRST) do { \
      constexpr int s_ = 28 + (I), sl_ = s_ % B_NSLOT; \
      mbar_wait(bar_full + 8 * sl_, (s_ / B_NSLOT) & 1); \
      wg_fence(); \
      wgmma_rs56<(sl_ * B_SLOT + 0 * 256) / 16, 112, !(FIRST)>(acc, (a)[0], (a)[1], (a)[2], (a)[3], blo); \
      wgmma_rs56<(sl_ * B_SLOT + 1 * 256) / 16, 112, 1>(acc, (a)[4], (a)[5], (a)[6], (a)[7], blo); \
      wgmma_rs56<(sl_ * B_SLOT + 2 * 256) / 16, 112, 1>(acc, (a)[8], (a)[9], (a)[10], (a)[11], blo); \
      wgmma_rs56<(sl_ * B_SLOT + 3 * 256) / 16, 112, 1>(acc, (a)[12], (a)[13], (a)[14], (a)[15], blo); \
      wgmma_rs56<(sl_ * B_SLOT + 4 * 256) / 16, 112, 1>(acc, (a)[16], (a)[17], (a)[18], (a)[19], blo); \
      wgmma_rs56<(sl_ * B_SLOT + 5 * 256) / 16, 112, 1>(acc, (a)[20], (a)[21], (a)[22], (a)[23], blo); \
      wgmma_rs56<(sl_ * B_SLOT + 6 * 256) / 16, 112, 1>(acc, (a)[24], (a)[25], (a)[26], (a)[27], blo); \
      wg_commit(); } while (0)
    uint4* const pdst = pin(g_part + (size_t)((rt * 8 + j) * 7) * 896 + warp * 112 + lane);
    uint2* const pdst2 = pin((uint2*)(g_part + (size_t)((rt * 8 + j) * 7) * 896 + warp * 112 + 96) + lane);
    uint32_t* const fdst = pin(g_flag + (rt * 8 + j) * 64 + warp);
    const bool flt = lane == 0;
    auto rel = [&](int i) { if (i < 9) release((28 + i) % B_NSLOT); };
    auto tg = [&](uint32_t v) { return (v & 0xFFFEFFFFu) | tag; };
    auto send_lo = [&](float (&acc)[28], int cc) {
      reg_fence(acc);
#pragma unroll
      for (int q = 0; q < 2; q++)
        st128(pdst + cc * 896 + q * 32, pack_bf16(acc[8 * q], acc[8 * q + 1]), pack_bf16(acc[8 * q + 2], acc[8 * q + 3]),
              pack_bf16(acc[8 * q + 4], acc[8 * q + 5]), tg(pack_bf16(acc[8 * q + 6], acc[8 * q + 7])));
    };
    auto send_hi = [&](float (&acc)[28], int cc) {
      st128(pdst + cc * 896 + 64, pack_bf16(acc[16], acc[17]), pack_bf16(acc[18], acc[19]), pack_bf16(acc[20], acc[21]), tg(pack_bf16(acc[22], acc[23])));
      asm volatile("{\n.reg .b64 v;\nmov.b64 v, {%1, %2};\nst.relaxed.gpu.global.b64 [%0], v;\n}"
                   ::"l"(pdst2 + cc * 1792), "r"(pack_bf16(acc[24], acc[25])), "r"(tg(pack_bf16(acc[26], acc[27]))) : "memory");
      if (flt) asm volatile("st.relaxed.gpu.global.u32 [%0], %1;" ::"l"(fdst + cc * 8), "r"(ep) : "memory");
    };
#define CHUNK(cur, prev, CC) do { \
      ISSUE(cur, 2 * (CC), hh, true); wg_wait<1>(); rel(2 * (CC) - 1); send_lo(prev, (CC) - 1); \
      ISSUE(cur, 2 * (CC) + 1, hh + 28, false); send_hi(prev, (CC) - 1); wg_wait<1>(); rel(2 * (CC)); } while (0)
    ISSUE(accA, 0, hh, true);
    ISSUE(accA, 1, hh + 28, false); wg_wait<1>(); rel(0);
    CHUNK(accB, accA, 1);
    if (tid == 0) TR(1, 11);
    CHUNK(accA, accB, 2);
    CHUNK(accB, accA, 3);
    if (tid == 0) TR(1, 13);
    CHUNK(accA, accB, 4);
    CHUNK(accB, accA, 5);
    if (tid == 0) TR(1, 16);
    CHUNK(accA, accB, 6);
    const int row = rt * 128 + wg * 64 + wq * 16 + g;
    uint32_t r20, r21;
    asm volatile("ld.relaxed.gpu.global.u32 %0, [%1];" : "=r"(r20) : "l"(g_stat2 + row) : "memory");
    asm volatile("ld.relaxed.gpu.global.u32 %0, [%1];" : "=r"(r21) : "l"(g_stat2 + row + 8) : "memory");
    CHUNK(accB, accA, 7);
    if (tid == 0) TR(1, 7);
    uint32_t hres[16];
#pragma unroll
    for (int i = 0; i < 4; i++) {
      int qq = lane >> 3, r = lane & 7, kg = 7 * j + 2 * i + (qq >> 1), c = 2 * wq + (qq & 1);
      if (kg > 55) kg = 55;
      asm volatile("ldmatrix.sync.aligned.m8n8.x4.trans.shared.b16 {%0,%1,%2,%3}, [%4];"
                   : "=r"(hres[4 * i]), "=r"(hres[4 * i + 1]), "=r"(hres[4 * i + 2]), "=r"(hres[4 * i + 3])
                   : "r"(sb + B_SA + kg * 2048 + wg * 1024 + r * 128 + ((c ^ r) << 4)) : "memory");
    }
    {
      int it = 0;
      while ((((r20 ^ ep) | (r21 ^ ep)) & 1u) && ++it < 400000) {
        asm volatile("ld.relaxed.gpu.global.u32 %0, [%1];" : "=r"(r20) : "l"(g_stat2 + row) : "memory");
        asm volatile("ld.relaxed.gpu.global.u32 %0, [%1];" : "=r"(r21) : "l"(g_stat2 + row + 8) : "memory");
      }
    }
    wg_wait<0>();
    reg_fence(accB);
    if (tid == 0) TR(1, 9);
#pragma unroll 1
    for (int q = 0; q < 7; q++) {
      mbar_wait(bar_in + 8 * (2 * q + wg), 0);
      add_in(accB, q, warp);
      if (tid == 0 && q == 5) TR(1, 12);
    }
    uint32_t* o0 = (uint32_t*)(out + (size_t)row * DM + 56 * j + 2 * t);
    uint32_t* o1 = o0 + 8 * DM / 2;
#pragma unroll
    for (int i = 0; i < 7; i++) {
      o0[4 * i] = hadd2_bf(hres[2 * i], pack_bf16(accB[4 * i] * __uint_as_float(r20), accB[4 * i + 1] * __uint_as_float(r20)));
      o1[4 * i] = hadd2_bf(hres[2 * i + 1], pack_bf16(accB[4 * i + 2] * __uint_as_float(r21), accB[4 * i + 3] * __uint_as_float(r21)));
    }
    if (tid == 0) TR(1, 10);
    if (tid == 128) TR(1, 15);
  }
}

extern "C" void kernel_launch(void* const* d_in, const int* in_sizes, int n_in, void* d_out, int out_size) {
  const __nv_bfloat16* x = (const __nv_bfloat16*)d_in[0];
  const __nv_bfloat16 *are = (const __nv_bfloat16*)d_in[1], *aim = (const __nv_bfloat16*)d_in[2], *bre = (const __nv_bfloat16*)d_in[3],
                      *bim = (const __nv_bfloat16*)d_in[4], *cre = (const __nv_bfloat16*)d_in[5], *cim = (const __nv_bfloat16*)d_in[6],
                      *logdt = (const __nv_bfloat16*)d_in[7], *dskip = (const __nv_bfloat16*)d_in[8];
  const __nv_bfloat16 *wg = (const __nv_bfloat16*)d_in[10], *wu = (const __nv_bfloat16*)d_in[11], *wd = (const __nv_bfloat16*)d_in[12];

  static bool init = false;
  if (!init) {
    init = true;
    cudaFuncSetAttribute(k_ffn, cudaFuncAttributeMaxDynamicSharedMemorySize, B_SMEM);
    cudaFuncSetAttribute(k_front, cudaFuncAttributeMaxDynamicSharedMemorySize, A_SMEM);
  }
  cudaStream_t st = cudaStreamPerThread;
  k_front<<<128, 512, A_SMEM, st>>>(
      x, (const uint32_t*)are, (const uint32_t*)aim, (const uint32_t*)bre, (const uint32_t*)bim, (const uint32_t*)cre, (const uint32_t*)cim,
      (const unsigned short*)logdt, (const unsigned short*)dskip, (const uint4*)wg, (const uint4*)wu, (const uint4*)wd);
  cudaLaunchConfig_t cfg = {};
  cfg.gridDim = dim3(128); cfg.blockDim = dim3(384); cfg.dynamicSmemBytes = B_SMEM; cfg.stream = st;
  cudaLaunchAttribute at[1];
  at[0].id = cudaLaunchAttributeProgrammaticStreamSerialization; at[0].val.programmaticStreamSerializationAllowed = 1;
  cfg.attrs = at; cfg.numAttrs = 1;
  cudaLaunchKernelEx(&cfg, k_ffn, (__nv_bfloat16*)d_out);
}
```

```cpp
#include <cuda_runtime.h>
#include <cuda_bf16.h>
#include <stdint.h>

constexpr int LSEQ = 2048, DM = 448;

__device__ uint4    g_himg[16 * 114688 / 16];
__device__ uint4    g_cimg[8 * 2 * 224];
__device__ uint32_t g_stat2[LSEQ];
__device__ uint4    g_part[128 * 3 * 896];
__device__ uint4    g_wimg[8 * 602112 / 16];
__device__ uint4    g_ux[DM * 128 * 4];
__device__ unsigned g_cnt1;
__device__ uint32_t g_flag[128 * 32];

#define TR(k, i) do {} while (0)
__device__ __forceinline__ uint32_t s2u(const void* p) { return (uint32_t)__cvta_generic_to_shared(p); }
__device__ __forceinline__ void mbar_init(uint32_t b, int c) { asm volatile("mbarrier.init.shared::cta.b64 [%0], %1;" ::"r"(b), "r"(c)); }
__device__ __forceinline__ void mbar_expect(uint32_t b, int bytes) { asm volatile("mbarrier.arrive.expect_tx.shared::cta.b64 _, [%0], %1;" ::"r"(b), "r"(bytes) : "memory"); }
__device__ __forceinline__ void mbar_arrive(uint32_t b) { asm volatile("mbarrier.arrive.shared::cta.b64 _, [%0];" ::"r"(b) : "memory"); }
__device__ __forceinline__ void mbar_wait(uint32_t b, int ph) {
  asm volatile("{\n.reg .pred p;\n.reg .b32 n;\nmov.b32 n, 0;\nLW:\nmbarrier.try_wait.parity.shared::cta.b64 p, [%0], %1;\n@p bra LD;\n"
               "add.u32 n, n, 1;\nsetp.lt.u32 p, n, 4000000;\n@p bra LW;\ntrap;\nLD:\n}" ::"r"(b), "r"(ph) : "memory");
}
__device__ __forceinline__ bool mbar_test(uint32_t b, int ph) {
  uint32_t ok;
  asm volatile("{\n.reg .pred p;\nmbarrier.test_wait.parity.shared::cta.b64 p, [%1], %2;\nselp.u32 %0, 1, 0, p;\n}" : "=r"(ok) : "r"(b), "r"(ph) : "memory");
  return ok;
}
__device__ __forceinline__ void wg_fence() { asm volatile("wgmma.fence.sync.aligned;" ::: "memory"); }
__device__ __forceinline__ void wg_commit() { asm volatile("wgmma.commit_group.sync.aligned;" ::: "memory"); }
template <int N> __device__ __forceinline__ void wg_wait() { asm volatile("wgmma.wait_group.sync.aligned %0;" ::"n"(N) : "memory"); }
template <int N> __device__ __forceinline__ void reg_fence(float (&a)[N]) {
#pragma unroll
  for (int i = 0; i < N; i++) asm volatile("" : "+f"(a[i])::"memory");
}
__device__ __forceinline__ uint32_t pack_bf16(float lo, float hi) {
  uint32_t r; asm("cvt.rn.bf16x2.f32 %0, %1, %2;" : "=r"(r) : "f"(hi), "f"(lo)); return r;
}
__device__ __forceinline__ float bf_lo(uint32_t v) { return __uint_as_float(v << 16); }
__device__ __forceinline__ float bf_hi(uint32_t v) { return __uint_as_float(v & 0xFFFF0000u); }
__device__ __forceinline__ float rbf(float x) { return __bfloat162float(__float2bfloat16_rn(x)); }
__device__ __forceinline__ uint32_t hmul2_bf(uint32_t a, uint32_t b) { uint32_t r; asm("mul.rn.bf16x2 %0, %1, %2;" : "=r"(r) : "r"(a), "r"(b)); return r; }
__device__ __forceinline__ uint32_t hadd2_bf(uint32_t a, uint32_t b) { uint32_t r; asm("add.rn.bf16x2 %0, %1, %2;" : "=r"(r) : "r"(a), "r"(b)); return r; }
__device__ __forceinline__ void bulk_ld(uint32_t dst, const void* src, int bytes, uint32_t bar) {
  asm volatile("cp.async.bulk.shared::cluster.global.mbarrier::complete_tx::bytes [%0], [%1], %2, [%3];"
               ::"r"(dst), "l"(src), "r"(bytes), "r"(bar) : "memory");
}

__device__ __forceinline__ void bulk_ld_mc(uint32_t dst, const void* src, int bytes, uint32_t bar) {
  asm volatile("cp.async.bulk.shared::cluster.global.mbarrier::complete_tx::bytes.multicast::cluster [%0], [%1], %2, [%3], %4;"
               ::"r"(dst), "l"(src), "r"(bytes), "r"(bar), "h"((uint16_t)3) : "memory");
}
template <int AOFF, uint32_t AHI, int BOFF, uint32_t BHI, int ACC>
__device__ __forceinline__ void wgmma_ss224(float (&d)[112], uint32_t alo, uint32_t blo) {
  asm volatile("{\n.reg .pred p;\n.reg .b32 la, lb;\n.reg .b64 ad, bd;\nsetp.ne.b32 p, %118, 0;\n"
    "add.u32 la, %112, %114;\nmov.b64 ad, {la, %115};\nadd.u32 lb, %113, %116;\nmov.b64 bd, {lb, %117};\n"
    "wgmma.mma_async.sync.aligned.m64n224k16.f32.bf16.bf16 {%0,%1,%2,%3,%4,%5,%6,%7,%8,%9,%10,%11,%12,%13,%14,%15,%16,%17,%18,%19,%20,%21,%22,%23,%24,%25,%26,%27,%28,%29,%30,%31,%32,%33,%34,%35,%36,%37,%38,%39,%40,%41,%42,%43,%44,%45,%46,%47,%48,%49,%50,%51,%52,%53,%54,%55,%56,%57,%58,%59,%60,%61,%62,%63,%64,%65,%66,%67,%68,%69,%70,%71,%72,%73,%74,%75,%76,%77,%78,%79,%80,%81,%82,%83,%84,%85,%86,%87,%88,%89,%90,%91,%92,%93,%94,%95,%96,%97,%98,%99,%100,%101,%102,%103,%104,%105,%106,%107,%108,%109,%110,%111}, ad, bd, p, 1, 1, 1, 1;\n}\n"
    : "+f"(d[0]),"+f"(d[1]),"+f"(d[2]),"+f"(d[3]),"+f"(d[4]),"+f"(d[5]),"+f"(d[6]),"+f"(d[7]),"+f"(d[8]),"+f"(d[9]),"+f"(d[10]),"+f"(d[11]),"+f"(d[12]),"+f"(d[13]),"+f"(d[14]),"+f"(d[15]),"+f"(d[16]),"+f"(d[17]),"+f"(d[18]),"+f"(d[19]),"+f"(d[20]),"+f"(d[21]),"+f"(d[22]),"+f"(d[23]),"+f"(d[24]),"+f"(d[25]),"+f"(d[26]),"+f"(d[27]),"+f"(d[28]),"+f"(d[29]),"+f"(d[30]),"+f"(d[31]),"+f"(d[32]),"+f"(d[33]),"+f"(d[34]),"+f"(d[35]),"+f"(d[36]),"+f"(d[37]),"+f"(d[38]),"+f"(d[39]),"+f"(d[40]),"+f"(d[41]),"+f"(d[42]),"+f"(d[43]),"+f"(d[44]),"+f"(d[45]),"+f"(d[46]),"+f"(d[47]),"+f"(d[48]),"+f"(d[49]),"+f"(d[50]),"+f"(d[51]),"+f"(d[52]),"+f"(d[53]),"+f"(d[54]),"+f"(d[55]),"+f"(d[56]),"+f"(d[57]),"+f"(d[58]),"+f"(d[59]),"+f"(d[60]),"+f"(d[61]),"+f"(d[62]),"+f"(d[63]),"+f"(d[64]),"+f"(d[65]),"+f"(d[66]),"+f"(d[67]),"+f"(d[68]),"+f"(d[69]),"+f"(d[70]),"+f"(d[71]),"+f"(d[72]),"+f"(d[73]),"+f"(d[74]),"+f"(d[75]),"+f"(d[76]),"+f"(d[77]),"+f"(d[78]),"+f"(d[79]),"+f"(d[80]),"+f"(d[81]),"+f"(d[82]),"+f"(d[83]),"+f"(d[84]),"+f"(d[85]),"+f"(d[86]),"+f"(d[87]),"+f"(d[88]),"+f"(d[89]),"+f"(d[90]),"+f"(d[91]),"+f"(d[92]),"+f"(d[93]),"+f"(d[94]),"+f"(d[95]),"+f"(d[96]),"+f"(d[97]),"+f"(d[98]),"+f"(d[99]),"+f"(d[100]),"+f"(d[101]),"+f"(d[102]),"+f"(d[103]),"+f"(d[104]),"+f"(d[105]),"+f"(d[106]),"+f"(d[107]),"+f"(d[108]),"+f"(d[109]),"+f"(d[110]),"+f"(d[111])
    : "r"(alo), "r"(blo), "n"(AOFF), "n"(AHI), "n"(BOFF), "n"(BHI), "n"(ACC));
}
template <int AOFF, uint32_t AHI, int BOFF, uint32_t BHI, int ACC>
__device__ __forceinline__ void wgmma_ss232(float (&d)[116], uint32_t alo, uint32_t blo) {
  asm volatile("{\n.reg .pred p;\n.reg .b32 la, lb;\n.reg .b64 ad, bd;\nsetp.ne.b32 p, %122, 0;\n"
    "add.u32 la, %116, %118;\nmov.b64 ad, {la, %119};\nadd.u32 lb, %117, %120;\nmov.b64 bd, {lb, %121};\n"
    "wgmma.mma_async.sync.aligned.m64n232k16.f32.bf16.bf16 {%0,%1,%2,%3,%4,%5,%6,%7,%8,%9,%10,%11,%12,%13,%14,%15,%16,%17,%18,%19,%20,%21,%22,%23,%24,%25,%26,%27,%28,%29,%30,%31,%32,%33,%34,%35,%36,%37,%38,%39,%40,%41,%42,%43,%44,%45,%46,%47,%48,%49,%50,%51,%52,%53,%54,%55,%56,%57,%58,%59,%60,%61,%62,%63,%64,%65,%66,%67,%68,%69,%70,%71,%72,%73,%74,%75,%76,%77,%78,%79,%80,%81,%82,%83,%84,%85,%86,%87,%88,%89,%90,%91,%92,%93,%94,%95,%96,%97,%98,%99,%100,%101,%102,%103,%104,%105,%106,%107,%108,%109,%110,%111,%112,%113,%114,%115}, ad, bd, p, 1, 1, 1, 1;\n}\n"
    : "+f"(d[0]),"+f"(d[1]),"+f"(d[2]),"+f"(d[3]),"+f"(d[4]),"+f"(d[5]),"+f"(d[6]),"+f"(d[7]),"+f"(d[8]),"+f"(d[9]),"+f"(d[10]),"+f"(d[11]),"+f"(d[12]),"+f"(d[13]),"+f"(d[14]),"+f"(d[15]),"+f"(d[16]),"+f"(d[17]),"+f"(d[18]),"+f"(d[19]),"+f"(d[20]),"+f"(d[21]),"+f"(d[22]),"+f"(d[23]),"+f"(d[24]),"+f"(d[25]),"+f"(d[26]),"+f"(d[27]),"+f"(d[28]),"+f"(d[29]),"+f"(d[30]),"+f"(d[31]),"+f"(d[32]),"+f"(d[33]),"+f"(d[34]),"+f"(d[35]),"+f"(d[36]),"+f"(d[37]),"+f"(d[38]),"+f"(d[39]),"+f"(d[40]),"+f"(d[41]),"+f"(d[42]),"+f"(d[43]),"+f"(d[44]),"+f"(d[45]),"+f"(d[46]),"+f"(d[47]),"+f"(d[48]),"+f"(d[49]),"+f"(d[50]),"+f"(d[51]),"+f"(d[52]),"+f"(d[53]),"+f"(d[54]),"+f"(d[55]),"+f"(d[56]),"+f"(d[57]),"+f"(d[58]),"+f"(d[59]),"+f"(d[60]),"+f"(d[61]),"+f"(d[62]),"+f"(d[63]),"+f"(d[64]),"+f"(d[65]),"+f"(d[66]),"+f"(d[67]),"+f"(d[68]),"+f"(d[69]),"+f"(d[70]),"+f"(d[71]),"+f"(d[72]),"+f"(d[73]),"+f"(d[74]),"+f"(d[75]),"+f"(d[76]),"+f"(d[77]),"+f"(d[78]),"+f"(d[79]),"+f"(d[80]),"+f"(d[81]),"+f"(d[82]),"+f"(d[83]),"+f"(d[84]),"+f"(d[85]),"+f"(d[86]),"+f"(d[87]),"+f"(d[88]),"+f"(d[89]),"+f"(d[90]),"+f"(d[91]),"+f"(d[92]),"+f"(d[93]),"+f"(d[94]),"+f"(d[95]),"+f"(d[96]),"+f"(d[97]),"+f"(d[98]),"+f"(d[99]),"+f"(d[100]),"+f"(d[101]),"+f"(d[102]),"+f"(d[103]),"+f"(d[104]),"+f"(d[105]),"+f"(d[106]),"+f"(d[107]),"+f"(d[108]),"+f"(d[109]),"+f"(d[110]),"+f"(d[111]),"+f"(d[112]),"+f"(d[113]),"+f"(d[114]),"+f"(d[115])
    : "r"(alo), "r"(blo), "n"(AOFF), "n"(AHI), "n"(BOFF), "n"(BHI), "n"(ACC));
}
template <int OFF, uint32_t BHI, int ACC>
__device__ __forceinline__ void wgmma_rs224(float (&d)[112], uint32_t a0, uint32_t a1, uint32_t a2, uint32_t a3, uint32_t blo) {
  asm volatile("{\n.reg .pred p;\n.reg .b32 l;\n.reg .b64 bd;\nsetp.ne.b32 p, %119, 0;\nadd.u32 l, %116, %117;\nmov.b64 bd, {l, %118};\n"
    "wgmma.mma_async.sync.aligned.m64n224k16.f32.bf16.bf16 {%0,%1,%2,%3,%4,%5,%6,%7,%8,%9,%10,%11,%12,%13,%14,%15,%16,%17,%18,%19,%20,%21,%22,%23,%24,%25,%26,%27,%28,%29,%30,%31,%32,%33,%34,%35,%36,%37,%38,%39,%40,%41,%42,%43,%44,%45,%46,%47,%48,%49,%50,%51,%52,%53,%54,%55,%56,%57,%58,%59,%60,%61,%62,%63,%64,%65,%66,%67,%68,%69,%70,%71,%72,%73,%74,%75,%76,%77,%78,%79,%80,%81,%82,%83,%84,%85,%86,%87,%88,%89,%90,%91,%92,%93,%94,%95,%96,%97,%98,%99,%100,%101,%102,%103,%104,%105,%106,%107,%108,%109,%110,%111}, {%112,%113,%114,%115}, bd, p, 1, 1, 1;\n}\n"
    : "+f"(d[0]),"+f"(d[1]),"+f"(d[2]),"+f"(d[3]),"+f"(d[4]),"+f"(d[5]),"+f"(d[6]),"+f"(d[7]),"+f"(d[8]),"+f"(d[9]),"+f"(d[10]),"+f"(d[11]),"+f"(d[12]),"+f"(d[13]),"+f"(d[14]),"+f"(d[15]),"+f"(d[16]),"+f"(d[17]),"+f"(d[18]),"+f"(d[19]),"+f"(d[20]),"+f"(d[21]),"+f"(d[22]),"+f"(d[23]),"+f"(d[24]),"+f"(d[25]),"+f"(d[26]),"+f"(d[27]),"+f"(d[28]),"+f"(d[29]),"+f"(d[30]),"+f"(d[31]),"+f"(d[32]),"+f"(d[33]),"+f"(d[34]),"+f"(d[35]),"+f"(d[36]),"+f"(d[37]),"+f"(d[38]),"+f"(d[39]),"+f"(d[40]),"+f"(d[41]),"+f"(d[42]),"+f"(d[43]),"+f"(d[44]),"+f"(d[45]),"+f"(d[46]),"+f"(d[47]),"+f"(d[48]),"+f"(d[49]),"+f"(d[50]),"+f"(d[51]),"+f"(d[52]),"+f"(d[53]),"+f"(d[54]),"+f"(d[55]),"+f"(d[56]),"+f"(d[57]),"+f"(d[58]),"+f"(d[59]),"+f"(d[60]),"+f"(d[61]),"+f"(d[62]),"+f"(d[63]),"+f"(d[64]),"+f"(d[65]),"+f"(d[66]),"+f"(d[67]),"+f"(d[68]),"+f"(d[69]),"+f"(d[70]),"+f"(d[71]),"+f"(d[72]),"+f"(d[73]),"+f"(d[74]),"+f"(d[75]),"+f"(d[76]),"+f"(d[77]),"+f"(d[78]),"+f"(d[79]),"+f"(d[80]),"+f"(d[81]),"+f"(d[82]),"+f"(d[83]),"+f"(d[84]),"+f"(d[85]),"+f"(d[86]),"+f"(d[87]),"+f"(d[88]),"+f"(d[89]),"+f"(d[90]),"+f"(d[91]),"+f"(d[92]),"+f"(d[93]),"+f"(d[94]),"+f"(d[95]),"+f"(d[96]),"+f"(d[97]),"+f"(d[98]),"+f"(d[99]),"+f"(d[100]),"+f"(d[101]),"+f"(d[102]),"+f"(d[103]),"+f"(d[104]),"+f"(d[105]),"+f"(d[106]),"+f"(d[107]),"+f"(d[108]),"+f"(d[109]),"+f"(d[110]),"+f"(d[111])
    : "r"(a0), "r"(a1), "r"(a2), "r"(a3), "r"(blo), "n"(OFF), "n"(BHI), "n"(ACC));
}
template <int OFF, uint32_t BHI, int ACC>
__device__ __forceinline__ void wgmma_rs56(float (&d)[28], uint32_t a0, uint32_t a1, uint32_t a2, uint32_t a3, uint32_t blo) {
  asm volatile("{\n.reg .pred p;\n.reg .b32 l;\n.reg .b64 bd;\nsetp.ne.b32 p, %35, 0;\nadd.u32 l, %32, %33;\nmov.b64 bd, {l, %34};\n"
    "wgmma.mma_async.sync.aligned.m64n56k16.f32.bf16.bf16 {%0,%1,%2,%3,%4,%5,%6,%7,%8,%9,%10,%11,%12,%13,%14,%15,%16,%17,%18,%19,%20,%21,%22,%23,%24,%25,%26,%27}, {%28,%29,%30,%31}, bd, p, 1, 1, 1;\n}\n"
    : "+f"(d[0]),"+f"(d[1]),"+f"(d[2]),"+f"(d[3]),"+f"(d[4]),"+f"(d[5]),"+f"(d[6]),"+f"(d[7]),"+f"(d[8]),"+f"(d[9]),"+f"(d[10]),"+f"(d[11]),"+f"(d[12]),"+f"(d[13]),"+f"(d[14]),"+f"(d[15]),"+f"(d[16]),"+f"(d[17]),"+f"(d[18]),"+f"(d[19]),"+f"(d[20]),"+f"(d[21]),"+f"(d[22]),"+f"(d[23]),"+f"(d[24]),"+f"(d[25]),"+f"(d[26]),"+f"(d[27])
    : "r"(a0), "r"(a1), "r"(a2), "r"(a3), "r"(blo), "n"(OFF), "n"(BHI), "n"(ACC));
}

__device__ __forceinline__ void st128(uint4* p, uint32_t a, uint32_t b, uint32_t c, uint32_t d) {
  asm volatile("{\n.reg .b128 v;\n.reg .b64 lo, hi;\nmov.b64 lo, {%1, %2};\nmov.b64 hi, {%3, %4};\nmov.b128 v, {lo, hi};\n"
               "st.relaxed.gpu.global.b128 [%0], v;\n}" ::"l"(p), "r"(a), "r"(b), "r"(c), "r"(d) : "memory");
}
__device__ __forceinline__ void ld128(const uint4* p, uint32_t* r) {
  asm volatile("{\n.reg .b128 v;\n.reg .b64 lo, hi;\nld.relaxed.gpu.global.b128 v, [%4];\nmov.b128 {lo, hi}, v;\n"
               "mov.b64 {%0, %1}, lo;\nmov.b64 {%2, %3}, hi;\n}" : "=r"(r[0]), "=r"(r[1]), "=r"(r[2]), "=r"(r[3]) : "l"(p) : "memory");
}

template <int OFF, uint32_t BHI, int ACC>
__device__ __forceinline__ void wgmma_rs32(float (&d)[16], uint32_t a0, uint32_t a1, uint32_t a2, uint32_t a3, uint32_t blo) {
  asm volatile("{\n.reg .pred p;\n.reg .b32 l;\n.reg .b64 bd;\nsetp.ne.b32 p, %23, 0;\nadd.u32 l, %20, %21;\nmov.b64 bd, {l, %22};\n"
    "wgmma.mma_async.sync.aligned.m64n32k16.f32.bf16.bf16 {%0,%1,%2,%3,%4,%5,%6,%7,%8,%9,%10,%11,%12,%13,%14,%15}, {%16,%17,%18,%19}, bd, p, 1, 1, 0;\n}\n"
    : "+f"(d[0]),"+f"(d[1]),"+f"(d[2]),"+f"(d[3]),"+f"(d[4]),"+f"(d[5]),"+f"(d[6]),"+f"(d[7]),"+f"(d[8]),"+f"(d[9]),"+f"(d[10]),"+f"(d[11]),"+f"(d[12]),"+f"(d[13]),"+f"(d[14]),"+f"(d[15])
    : "r"(a0), "r"(a1), "r"(a2), "r"(a3), "r"(blo), "n"(OFF), "n"(BHI), "n"(ACC));
}
template <int OFF, uint32_t BHI, int ACC>
__device__ __forceinline__ void wgmma_rs24(float (&d)[12], uint32_t a0, uint32_t a1, uint32_t a2, uint32_t a3, uint32_t blo) {
  asm volatile("{\n.reg .pred p;\n.reg .b32 l;\n.reg .b64 bd;\nsetp.ne.b32 p, %19, 0;\nadd.u32 l, %16, %17;\nmov.b64 bd, {l, %18};\n"
    "wgmma.mma_async.sync.aligned.m64n24k16.f32.bf16.bf16 {%0,%1,%2,%3,%4,%5,%6,%7,%8,%9,%10,%11}, {%12,%13,%14,%15}, bd, p, 1, 1, 1;\n}\n"
    : "+f"(d[0]),"+f"(d[1]),"+f"(d[2]),"+f"(d[3]),"+f"(d[4]),"+f"(d[5]),"+f"(d[6]),"+f"(d[7]),"+f"(d[8]),"+f"(d[9]),"+f"(d[10]),"+f"(d[11])
    : "r"(a0), "r"(a1), "r"(a2), "r"(a3), "r"(blo), "n"(OFF), "n"(BHI), "n"(ACC));
}
template <int OFF, uint32_t BHI, int ACC>
__device__ __forceinline__ void wgmma_rs16(float (&d)[8], uint32_t a0, uint32_t a1, uint32_t a2, uint32_t a3, uint32_t blo) {
  asm volatile("{\n.reg .pred p;\n.reg .b32 l;\n.reg .b64 bd;\nsetp.ne.b32 p, %15, 0;\nadd.u32 l, %12, %13;\nmov.b64 bd, {l, %14};\n"
    "wgmma.mma_async.sync.aligned.m64n16k16.f32.bf16.bf16 {%0,%1,%2,%3,%4,%5,%6,%7}, {%8,%9,%10,%11}, bd, p, 1, 1, 1;\n}\n"
    : "+f"(d[0]),"+f"(d[1]),"+f"(d[2]),"+f"(d[3]),"+f"(d[4]),"+f"(d[5]),"+f"(d[6]),"+f"(d[7])
    : "r"(a0), "r"(a1), "r"(a2), "r"(a3), "r"(blo), "n"(OFF), "n"(BHI), "n"(ACC));
}

constexpr int A_R1 = 0;
constexpr int A_R2A = A_R1 + 2624, A_R2B = A_R2A + 768, A_R3A = A_R2B + 768, A_R3B = A_R3A + 528;
constexpr int A_K1024 = A_R3B + 528;
constexpr int A_W5 = A_K1024 + 16;
constexpr int A_W3 = A_W5 + 4096;
constexpr int A_W9 = A_W3 + 4112;
constexpr int A_W7 = A_W9 + 2048;
constexpr int A_V  = A_W7 + 2048;
constexpr int A_UB = A_V + 2048;
constexpr int A_STG = A_UB + 5248;
constexpr int A_Y2 = A_STG, A_Y3 = A_Y2 + 6528, A_YB = A_Y3 + 4352;
constexpr int A_REC = A_STG + 4 * 4352;
constexpr int A_CH = A_REC + 8192;
static_assert(A_W5 % 16 == 0 && A_UB % 16 == 0 && A_CH % 16 == 0 && A_YB + 4096 <= A_REC, "layout");

struct cf { float x, y; };
__device__ __forceinline__ cf cmul(cf a, cf b) { cf r; r.x = fmaf(a.x, b.x, -a.y * b.y); r.y = fmaf(a.x, b.y, a.y * b.x); return r; }
__device__ __forceinline__ cf cexp_l(float lr, float li, float l) {
  float mag; asm("ex2.approx.ftz.f32 %0, %1;" : "=f"(mag) : "f"((lr * l) * 1.4426950408889634f));
  const float th = li * l;
  const float k = (fmaf(th, 0.15915494f, 12582912.f)) - 12582912.f;
  float ph = fmaf(th, 0.15915494f, -k);
  ph = fmaf(th, 6.4206383e-9f, ph) * 6.2831853f;
  cf r; r.x = mag * __cosf(ph); r.y = mag * __sinf(ph); return r;
}
__device__ __forceinline__ void sts16(uint32_t a, uint32_t v) { asm volatile("st.shared.u16 [%0], %1;" ::"r"(a), "h"((uint16_t)v) : "memory"); }
__device__ __forceinline__ void sts32(uint32_t a, uint32_t v) { asm volatile("st.shared.u32 [%0], %1;" ::"r"(a), "r"(v) : "memory"); }
__device__ __forceinline__ void sts64(uint32_t a, uint32_t v0, uint32_t v1) { asm volatile("st.shared.v2.u32 [%0], {%1, %2};" ::"r"(a), "r"(v0), "r"(v1) : "memory"); }
__device__ __forceinline__ void sts128(uint32_t a, uint32_t v0, uint32_t v1, uint32_t v2, uint32_t v3) {
  asm volatile("st.shared.v4.u32 [%0], {%1, %2, %3, %4};" ::"r"(a), "r"(v0), "r"(v1), "r"(v2), "r"(v3) : "memory");
}
__device__ __forceinline__ uint32_t lds32(uint32_t a) { uint32_t v; asm volatile("ld.shared.u32 %0, [%1];" : "=r"(v) : "r"(a) : "memory"); return v; }
__device__ __forceinline__ uint4 lds128(uint32_t a) {
  uint4 v; asm volatile("ld.shared.v4.u32 {%0, %1, %2, %3}, [%4];" : "=r"(v.x), "=r"(v.y), "=r"(v.z), "=r"(v.w) : "r"(a) : "memory"); return v;
}
__device__ __forceinline__ void ldsm4(uint32_t* r, uint32_t a) {
  asm volatile("ldmatrix.sync.aligned.m8n8.x4.shared.b16 {%0,%1,%2,%3}, [%4];" : "=r"(r[0]), "=r"(r[1]), "=r"(r[2]), "=r"(r[3]) : "r"(a) : "memory");
}
__device__ __forceinline__ void mma16816(float* d, const uint32_t* a, uint32_t b0, uint32_t b1) {
  asm volatile("mma.sync.aligned.m16n8k16.row.col.f32.bf16.bf16.f32 {%0,%1,%2,%3}, {%4,%5,%6,%7}, {%8,%9}, {%0,%1,%2,%3};"
               : "+f"(d[0]), "+f"(d[1]), "+f"(d[2]), "+f"(d[3]) : "r"(a[0]), "r"(a[1]), "r"(a[2]), "r"(a[3]), "r"(b0), "r"(b1));
}
__device__ __forceinline__ uint32_t hsub2_bf(uint32_t a, uint32_t b) { uint32_t r; asm("sub.rn.bf16x2 %0, %1, %2;" : "=r"(r) : "r"(a), "r"(b)); return r; }
__device__ __forceinline__ void bar_sync(int id, int n) { asm volatile("bar.sync %0, %1;" ::"r"(id), "r"(n) : "memory"); }

template <int S> struct F1B { static constexpr int c = S / 4 + ((S & 3) == 3 ? 0 : 0), cc = (16 * S) / 64, ks = (64 * cc - (16 * S - 48)) / 16, off = (A_UB + 2 * ks * 656 + (9 - cc) * 16) / 16; };

template <int NS>
__device__ __forceinline__ void load_quads(uint32_t* q, uint32_t addr) {
#pragma unroll
  for (int i = 0; i < NS; i++) {
    q[4 * i] = lds32(addr + i * 64); q[4 * i + 1] = lds32(addr + i * 64 + 32);
    q[4 * i + 2] = i ? q[4 * i - 3] : lds32(addr - 32);
    q[4 * i + 3] = q[4 * i];
  }
#pragma unroll
  for (int i = 0; i < 4 * NS; i++) asm volatile("" : "+r"(q[i]));
}
template <int S0, int NS>
__device__ __forceinline__ void f1_steps(float (&acc)[16], const uint32_t* a, uint32_t blo) {
  if constexpr (NS > 0) {
    wgmma_rs32<F1B<S0>::off, 8, S0 != 0>(acc, a[0], a[1], a[2], a[3], blo);
    f1_steps<S0 + 1, NS - 1>(acc, a + 4, blo);
  }
}
template <int S0, int NS, int BASE, int FIRST>
__device__ __forceinline__ void s2_steps(float (&acc)[12], const uint32_t* a, uint32_t blo) {
  if constexpr (NS > 0) {
    wgmma_rs24<BASE / 16 + (112 - 16 * S0), 64, !(FIRST && S0 == 0)>(acc, a[0], a[1], a[2], a[3], blo);
    s2_steps<S0 + 1, NS - 1, BASE, FIRST>(acc, a + 4, blo);
  }
}
template <int S0, int NS, int BASE, int FIRST>
__device__ __forceinline__ void s3_steps(float (&acc)[8], const uint32_t* a, uint32_t blo) {
  if constexpr (NS > 0) {
    wgmma_rs16<BASE / 16 + (48 - 16 * S0), 64, !(FIRST && S0 == 0)>(acc, a[0], a[1], a[2], a[3], blo);
    s3_steps<S0 + 1, NS - 1, BASE, FIRST>(acc, a + 4, blo);
  }
}

__device__ __forceinline__ void phase_a(
        unsigned char* sm, const uint32_t bar_rec, const uint32_t ep_addr,
        const __nv_bfloat16* __restrict__ x, const uint32_t* __restrict__ are, const uint32_t* __restrict__ aim,
        const uint32_t* __restrict__ bre, const uint32_t* __restrict__ bim, const uint32_t* __restrict__ cre,
        const uint32_t* __restrict__ cim, const unsigned short* __restrict__ logdt, const unsigned short* __restrict__ dskip,
        const uint4* __restrict__ wgate, const uint4* __restrict__ wup, const uint4* __restrict__ wdown) {
  const uint32_t sb = s2u(sm);
  const int tid = threadIdx.x, wg = tid >> 7, warp = tid >> 5, lane = tid & 31, wq = warp & 3, t128 = tid & 127;
  const int blk = blockIdx.x;
  const bool conv = blk < 112;

  uint2 xr[4];
  {
    const uint2* p = (const uint2*)(x + (size_t)(blk * 16 + warp) * DM);
    xr[0] = __ldg(p + lane); xr[1] = __ldg(p + 32 + lane); xr[2] = __ldg(p + 64 + lane);
    xr[3] = lane < 16 ? __ldg(p + 96 + lane) : make_uint2(0, 0);
  }
  const int ch = conv ? blk * 4 + wg : 0;
  const uint32_t cb = sb + wg * A_CH;
  uint32_t prm[6];
  {
    const int i = ch * 128 + t128;
    prm[0] = __ldg(are + i); prm[1] = __ldg(aim + i); prm[2] = __ldg(bre + i); prm[3] = __ldg(bim + i); prm[4] = __ldg(cre + i); prm[5] = __ldg(cim + i);
  }
  const uint32_t ldt = __ldg(logdt + ch);
  uint32_t cnt0 = 0;
  if (tid == 0) cnt0 = __ldcg(&g_cnt1);
#pragma unroll
  for (int i = 0; i < 4; i++) if (i < 3 || t128 < (A_W5 + 1024) / 16 - 384) sts128(cb + (i * 128 + t128) * 16, 0, 0, 0, 0);
  if (t128 < 65) sts128(cb + (t128 < 64 ? A_W3 + t128 * 16 : A_W9), 0, 0, 0, 0);
  if (t128 < 72) sts128(cb + A_UB + (t128 / 9) * 656 + (t128 % 9) * 16, 0, 0, 0, 0);
  {
    float s = 0.f, q = 0.f;
#pragma unroll
    for (int i = 0; i < 4; i++) {
      const float a = bf_lo(xr[i].x), b = bf_hi(xr[i].x), c = bf_lo(xr[i].y), d = bf_hi(xr[i].y);
      s += (a + b) + (c + d);
      q = fmaf(a, a, q); q = fmaf(b, b, q); q = fmaf(c, c, q); q = fmaf(d, d, q);
    }
#pragma unroll
    for (int o = 16; o; o >>= 1) { s += __shfl_xor_sync(~0u, s, o); q += __shfl_xor_sync(~0u, q, o); }
    const float mean = s * (1.f / DM);
    const float var = fmaxf(fmaf(-mean, mean, q * (1.f / DM)), 0.f);
    const float rs = __frcp_rn(rbf(__fsqrt_rn(rbf(rbf(var) + 1e-5f))));
    const uint32_t mm = pack_bf16(mean, mean);
    const uint32_t tu = sb + A_REC + (warp >> 3) * A_CH + (warp & 7) * 912 + lane * 8, tx = tu + 2 * A_CH;
#pragma unroll
    for (int i = 0; i < 4; i++) {
      if (i < 3 || lane < 16) {
        const uint32_t d0 = hsub2_bf(xr[i].x, mm), d1 = hsub2_bf(xr[i].y, mm);
        sts64(tu + i * 256, pack_bf16(bf_lo(d0) * rs, bf_hi(d0) * rs), pack_bf16(bf_lo(d1) * rs, bf_hi(d1) * rs));
        sts64(tx + i * 256, xr[i].x, xr[i].y);
      }
    }
  }
  if (tid == 0) sts32(ep_addr, (cnt0 >> 7) + 1u);
  if (tid == 320) TR(0, 1);
  auto publish_rows = [&]() {
    bar_sync(5, 512);
    uint4* dst = g_ux + ((size_t)(warp * 8 + (lane >> 2)) * 128 + blk) * 4 + ((lane ^ (blk >> 1)) & 3);
#pragma unroll
    for (int i = 0; i < 4; i++) {
      if (i < 3 || warp < 8) {
        uint32_t r[4];
        asm volatile("ldmatrix.sync.aligned.m8n8.x4.trans.shared.b16 {%0,%1,%2,%3}, [%4];" : "=r"(r[0]), "=r"(r[1]), "=r"(r[2]), "=r"(r[3])
                     : "r"(sb + A_REC + (lane >> 3) * A_CH + (lane & 7) * 912 + (warp + 16 * i) * 16) : "memory");
        dst[i * 65536] = make_uint4(r[0], r[1], r[2], r[3]);
      }
    }
    if (warp != 0) asm volatile("bar.arrive 6, 512;" ::: "memory");
  };
  auto release_rows = [&]() {
    if (warp == 0) {
      bar_sync(6, 512);
      if (lane == 0) { asm volatile("red.release.gpu.global.add.u32 [%0], 1;" ::"l"(&g_cnt1) : "memory"); TR(0, 8); }
      __syncwarp();
    }
  };

  if (!conv) {
    publish_rows();
    release_rows();
    const int a = blk - 112, mat = a >> 3, j = a & 7;
    float s[8];
#pragma unroll
    for (int k = 0; k < 8; k++) s[k] = 0.f;
    if (lane < 28) {
      const uint4* src = (mat ? wup : wgate) + j * 28 + lane + (size_t)warp * 224;
#pragma unroll
      for (int hb = 0; hb < 2; hb++) {
        uint4 v[14];
#pragma unroll
        for (int r = 0; r < 14; r++) v[r] = __ldg(src + (size_t)(hb * 14 + r) * 16 * 224);
#pragma unroll
        for (int r = 0; r < 14; r++) {
          s[0] += bf_lo(v[r].x); s[1] += bf_hi(v[r].x); s[2] += bf_lo(v[r].y); s[3] += bf_hi(v[r].y);
          s[4] += bf_lo(v[r].z); s[5] += bf_hi(v[r].z); s[6] += bf_lo(v[r].w); s[7] += bf_hi(v[r].w);
        }
      }
      float4* red = (float4*)(sm + A_STG + warp * 896 + lane * 32);
      red[0] = make_float4(s[0], s[1], s[2], s[3]); red[1] = make_float4(s[4], s[5], s[6], s[7]);
    }
    bar_sync(5, 512);
    if (tid < 224) {
      float t = 0.f;
#pragma unroll
      for (int w = 0; w < 16; w++) t += *(const float*)(sm + A_STG + w * 896 + tid * 4);
      const float hi = rbf(t), mid = rbf(t - hi), lo = rbf(t - hi - mid);
      const int q = tid / 112, n = tid % 112 + 112 * mat;
      __nv_bfloat16* dst = (__nv_bfloat16*)(g_cimg + (j * 2 + q) * 224 + (n >> 3) * 8) + (n & 7);
      dst[0] = __float2bfloat16_rn(hi); dst[8] = __float2bfloat16_rn(mid); dst[16] = __float2bfloat16_rn(lo);
#pragma unroll
      for (int k = 3; k < 8; k++) dst[8 * k] = __float2bfloat16_rn(0.f);
    }
    if (tid == 320) TR(0, 10);
    return;
  }

  const int g = lane >> 2, t = lane & 3;
  const int wr = (wq + wg) & 3;
  uint4 wv[6];
  auto w_src = [&](int i) -> const uint4* {
    if (i < 4) return (blk < 56 ? wgate : wup) + (blk % 56) * 4 + (lane & 3) + (size_t)(i * 128 + warp * 8 + (lane >> 2)) * 224;
    const int it = warp + 16 * (i - 4);
    return wdown + (size_t)(blk * 16 + (it / 14) * 8 + (lane >> 2)) * 56 + (it % 14) * 4 + (lane & 3);
  };
  auto w_on = [&](int i) { return i == 3 ? warp < 8 : i == 5 ? warp < 12 : true; };
  {
    const uint32_t stg = cb + A_STG + wq * 4352;
    const float dt = rbf(expf(__uint_as_float(ldt << 16)));
    float lr[2], li[2];
    cf bq[2], b0[2], b4[2];
    uint32_t bf[48];
#pragma unroll
    for (int m = 0; m < 2; m++) {
      lr[m] = dt * (m ? bf_hi(prm[0]) : bf_lo(prm[0]));
      li[m] = dt * (m ? bf_hi(prm[1]) : bf_lo(prm[1]));
    }
    {
      cf b[2], z[2];
#pragma unroll
      for (int m = 0; m < 2; m++) {
        cf db, c;
        db.x = dt * (m ? bf_hi(prm[2]) : bf_lo(prm[2])); db.y = -dt * (m ? bf_hi(prm[3]) : bf_lo(prm[3]));
        c.x = m ? bf_hi(prm[4]) : bf_lo(prm[4]); c.y = -(m ? bf_hi(prm[5]) : bf_lo(prm[5]));
        b[m] = cmul(c, db);
        z[m] = cexp_l(lr[m], -li[m], 1.f);
        bq[m] = cexp_l(lr[m], -li[m], 256.f);
      }
#pragma unroll
      for (int i = 0; i < 8; i++) {
        sts64(stg + i * 272 + lane * 8, pack_bf16(b[0].x, b[0].y), pack_bf16(b[1].x, b[1].y));
        if (!(i & 1)) {
          cf e0 = cmul(b[0], bq[0]), e1 = cmul(b[1], bq[1]);
          sts64(stg + (8 + i / 2) * 272 + lane * 8, pack_bf16(e0.x, e0.y), pack_bf16(e1.x, e1.y));
          if (i == 0) { b0[0] = e0; b0[1] = e1; }
          if (i == 4) { b4[0] = e0; b4[1] = e1; }
        }
        if (i < 7) { b[0] = cmul(b[0], z[0]); b[1] = cmul(b[1], z[1]); }
        if (i == 1) publish_rows();
      }
#pragma unroll
      for (int i = 0; i < 7; i++) {
        b0[0] = cmul(b0[0], bq[0]); b0[1] = cmul(b0[1], bq[1]);
        sts64(stg + (i < 2 ? 12 + 2 * i : i - 2) * 272 + lane * 8, pack_bf16(b0[0].x, b0[0].y), pack_bf16(b0[1].x, b0[1].y));
        if (i < 2) {
          b4[0] = cmul(b4[0], bq[0]); b4[1] = cmul(b4[1], bq[1]);
          sts64(stg + (13 + 2 * i) * 272 + lane * 8, pack_bf16(b4[0].x, b4[0].y), pack_bf16(b4[1].x, b4[1].y));
        }
        if (i == 1) {
          __syncwarp();
#pragma unroll
          for (int n = 0; n < 2; n++)
#pragma unroll
            for (int k2 = 0; k2 < 4; k2++) ldsm4(bf + n * 16 + k2 * 4, stg + (n * 8 + (lane & 7)) * 272 + k2 * 64 + (lane >> 3) * 16);
          __syncwarp();
        }
      }
    }
    __syncwarp();
#pragma unroll
    for (int k2 = 0; k2 < 4; k2++) ldsm4(bf + 32 + k2 * 4, stg + (lane & 7) * 272 + k2 * 64 + (lane >> 3) * 16);
    release_rows();
    if (!(lane & 1)) {
#pragma unroll
      for (int i = 0; i < 6; i++) if (w_on(i)) asm volatile("prefetch.global.L2 [%0];" ::"l"(w_src(i)));
    }
    if (tid == 320) TR(0, 16);
    float c[6][4];
#pragma unroll
    for (int i = 0; i < 6; i++) { c[i][0] = 0.f; c[i][1] = 0.f; c[i][2] = 0.f; c[i][3] = 0.f; }
    cf p[2], v[2];
    p[0] = cexp_l(lr[0], li[0], 8.f); p[1] = cexp_l(lr[1], li[1], 8.f);
    v[0].x = 1.f; v[0].y = 0.f; v[1] = v[0];
#pragma unroll
    for (int mt = 0; mt < 2; mt++) {
      __syncwarp();
#pragma unroll
      for (int i = 0; i < 16; i++) {
        sts64(stg + i * 272 + lane * 8, pack_bf16(v[0].x, v[0].y), pack_bf16(v[1].x, v[1].y));
        if (mt == 0 && i == 0) { v[0] = p[0]; v[1] = p[1]; }
        else if (mt == 0 || i < 15) { v[0] = cmul(v[0], p[0]); v[1] = cmul(v[1], p[1]); }
      }
      __syncwarp();
      if (mt == 1 && tid == 160) {
        const uint32_t tgt = lds32(ep_addr) * 128u;
        uint32_t cv; int it = 0;
        do { asm volatile("ld.acquire.gpu.global.u32 %0, [%1];" : "=r"(cv) : "l"(&g_cnt1) : "memory"); } while ((int)(cv - tgt) < 0 && ++it < 200000);
        asm volatile("fence.proxy.async;" ::: "memory");
        TR(0, 9);
        mbar_expect(bar_rec, 32768);
        for (int c2 = 0; c2 < 4; c2++) bulk_ld(sb + c2 * A_CH + A_REC, g_ux + (size_t)(blk * 4 + c2) * 512, 8192, bar_rec);
      }
#pragma unroll
      for (int ks = 0; ks < 8; ks++) {
        uint32_t a[4];
        ldsm4(a, stg + (lane & 15) * 272 + ks * 32 + (lane >> 4) * 16);
#pragma unroll
        for (int n = 0; n < 3; n++) mma16816(c[n * 2 + mt], a, bf[n * 16 + ks * 2], bf[n * 16 + ks * 2 + 1]);
      }
    }
    __syncwarp();
#pragma unroll
    for (int i = 0; i < 6; i++)
      sts128(stg + i * 512 + lane * 16, __float_as_uint(c[i][0]), __float_as_uint(c[i][1]), __float_as_uint(c[i][2]), __float_as_uint(c[i][3]));
#pragma unroll
    for (int i = 0; i < 6; i++) if (w_on(i)) wv[i] = __ldg(w_src(i));
    bar_sync(1 + wg, 128);
    if (tid == 320) TR(0, 2);
#pragma unroll
    for (int rep = 0; rep < 2; rep++) {
      const int qd = rep ? 2 + wr : 3 - wr;
      if (rep == 0 || wr >= 2) {
        float s[4] = {0.f, 0.f, 0.f, 0.f};
#pragma unroll
        for (int w = 0; w < 4; w++) {
          uint4 u4 = lds128(cb + A_STG + w * 4352 + qd * 512 + lane * 16);
          s[0] += __uint_as_float(u4.x); s[1] += __uint_as_float(u4.y); s[2] += __uint_as_float(u4.z); s[3] += __uint_as_float(u4.w);
        }
#pragma unroll
        for (int hf = 0; hf < 2; hf++) {
          const int j = (qd & 1) * 16 + g + 8 * hf;
          const uint32_t pk = pack_bf16(s[2 * hf + 1], s[2 * hf]);
          const uint32_t v0 = pk >> 16, v1 = pk & 0xFFFFu, v00 = v0 * 0x10001u;
          if (rep == 1) {
            if (t < 2) {
#pragma unroll
              for (int e = 0; e < 2; e++) {
                const int lam = 128 + 32 * (2 * t + e) + j, mu = lam >> 1;
                const uint32_t val = e ? v1 : v0;
                uint32_t a = cb + ((lam & 1) ? A_R3B : A_R3A) + mu * 4;
                if (lam == 128) { a = cb + A_R2A + 128 * 4; sts32(cb + A_K1024, val << 16); }
                sts16(a, val); sts16(a + 6, val);
              }
            } else if (t == 2 && j == 0) { sts16(cb + A_R3A + 128 * 4, v0); }
          } else if (qd < 2) {
            const uint32_t a = cb + A_R1 + (62 + 8 * j + 2 * t) * 4;
            sts16(a, v0); sts32(a + 4, pk); sts16(a + 10, v1);
          } else if (t < 2) {
            const int L = 256 + 8 * j + 4 * t;
            const uint32_t a = cb + A_R1 + (62 + L) * 4;
            if (L > 256) { sts16(a - 4, v0); sts32(a, v00); } else sts16(a, v0);
            sts32(a + 4, v00); sts32(a + 8, pk); sts16(a + 14, v1);
          } else {
            const int mu = 64 + 32 * (t - 2) + j;
            if (mu == 64) {
              const uint32_t a = cb + A_R1 + (62 + 512) * 4;
              sts16(a - 4, v0); sts32(a, v00); sts32(a + 4, v00); sts32(a + 8, v00); sts16(a + 14, v0);
            } else { sts16(cb + A_R2A + mu * 4, v0); sts16(cb + A_R2A + mu * 4 + 6, v0); }
            sts16(cb + A_R2B + mu * 4, v1); sts16(cb + A_R2B + mu * 4 + 6, v1);
          }
        }
      }
    }
  }
  {
    const int ngg = (blk % 56) * 4 + (lane & 3), j = ngg / 28, q = (ngg % 28) / 14, ng = ngg % 14 + (blk < 56 ? 0 : 14);
    uint4* dst = g_wimg + (size_t)j * 37632 + q * 14 * 896 + ng * 32 + (warp >> 2) * 896 + (warp & 3) * 8 + (lane >> 2);
#pragma unroll
    for (int i = 0; i < 4; i++) if (w_on(i)) dst[i * 4 * 896] = wv[i];
#pragma unroll
    for (int i = 4; i < 6; i++) {
      const int it = warp + 16 * (i - 4), n2 = (it % 14) * 4 + (lane & 3), k = (blk % 7) * 16 + (it / 14) * 8 + (lane >> 2);
      if (w_on(i)) g_wimg[(size_t)(blk / 14) * 37632 + 25088 + ((n2 / 7) * 2 + (blk / 7) % 2) * 784 + (n2 % 7) * 112 + k] = wv[i];
    }
  }
  if (tid == 320) TR(0, 3);

  const int bk = wr * 32 + lane;
  uint32_t xt[8], ud[8];
  {
    mbar_wait(bar_rec, 0);
    if (tid == 320) TR(0, 4);
    uint4 r[4];
#pragma unroll
    for (int i = 0; i < 4; i++) r[i] = lds128(cb + A_REC + bk * 64 + ((i ^ (bk >> 1)) & 3) * 16);
    const uint32_t ua = cb + A_UB + ((2 * bk) & 7) * 656 + ((bk >> 2) + 9) * 16;
    sts128(ua, r[0].x, r[1].x, r[2].x, r[3].x);
    sts128(ua + 656, r[0].y, r[1].y, r[2].y, r[3].y);
    if (bk <= 96) {
      const bool neg = bk == 96;
      const int bp = neg ? -1 : bk;
      uint32_t h[4];
      h[0] = lds32(cb + A_REC + ((bp - 1) & 127) * 64 + ((2 ^ ((bp - 1) >> 1)) & 3) * 16 + 4);
      h[1] = lds32(cb + A_REC + ((bp - 1) & 127) * 64 + ((3 ^ ((bp - 1) >> 1)) & 3) * 16 + 4);
      h[2] = lds32(cb + A_REC + (bp + 1) * 64 + ((0 ^ ((bp + 1) >> 1)) & 3) * 16);
      h[3] = lds32(cb + A_REC + (bp + 1) * 64 + ((1 ^ ((bp + 1) >> 1)) & 3) * 16);
      if (bp <= 0) { h[0] = 0; h[1] = 0; }
      const uint32_t wd[12] = {h[0], h[1], neg ? 0 : r[0].x, neg ? 0 : r[1].x, neg ? 0 : r[2].x, neg ? 0 : r[3].x,
                               neg ? 0 : r[0].y, neg ? 0 : r[1].y, neg ? 0 : r[2].y, neg ? 0 : r[3].y, h[2], h[3]};
      float P[25];
      P[0] = 0.f;
#pragma unroll
      for (int i = 0; i < 12; i++) { P[2 * i + 1] = P[2 * i] + bf_lo(wd[i]); P[2 * i + 2] = P[2 * i + 1] + bf_hi(wd[i]); }
#define WIN(i, hw) (P[(i) + 5 + (hw)] - P[(i) + 4 - (hw)])
#define WPK(i, hw) pack_bf16(WIN(i, hw), WIN((i) + 1, hw))
      const int tp = 2 * bp;
      const uint32_t a3 = cb + A_W3 + (tp + 64) * 16 + 8, a5 = cb + A_W5 + (tp + 64) * 16;
      if (!neg) sts64(a3, WPK(0, 1), WPK(2, 1));
      if (!neg) sts128(a3 + 8, WPK(4, 1), WPK(6, 1), WPK(8, 1), WPK(10, 1));
      sts64(a3 + 24, WPK(12, 1), WPK(14, 1));
      sts128(a5, WPK(0, 2), WPK(2, 2), WPK(4, 2), WPK(6, 2));
      sts128(a5 + 16, WPK(8, 2), WPK(10, 2), WPK(12, 2), WPK(14, 2));
      if (bp < 64) {
        if (!neg) sts128(cb + A_W7 + 1024 + bp * 16, WPK(0, 3), WPK(2, 3), WPK(4, 3), WPK(6, 3));
        if (bp < 63) {
          sts128(cb + A_W7 + (bp + 1) * 16, WPK(8, 3), WPK(10, 3), WPK(12, 3), WPK(14, 3));
          sts128(cb + A_W9 + (bp + 1) * 16, WPK(0, 4), WPK(2, 4), WPK(4, 4), WPK(6, 4));
          sts128(cb + A_W9 + 1024 + (bp + 1) * 16, WPK(8, 4), WPK(10, 4), WPK(12, 4), WPK(14, 4));
        }
        if (!neg) {
#define VPK(i) pack_bf16(P[(i) + 2] - P[i], P[(i) + 3] - P[(i) + 1])
          sts128(cb + A_V + bp * 32, VPK(0), VPK(2), VPK(4), VPK(6));
          sts128(cb + A_V + bp * 32 + 16, VPK(8), VPK(10), VPK(12), VPK(14));
        }
      }
    }
  }
  asm volatile("fence.proxy.async.shared::cta;" ::: "memory");
  bar_sync(1 + wg, 128);
  if (tid == 320) TR(0, 5);

  {
    const uint32_t cbu = __shfl_sync(~0u, cb, 0);
    const uint32_t blo_k = ((cbu & 0x3FFFF) >> 4) | (41u << 16);
    const uint32_t blo_n = ((cbu & 0x3FFFF) >> 4) | (8u << 16);
    const uint32_t tb = cb + (16 * wq + g - 2 * t) * 4;
    float y1[16], y2[12], y3[8];
    const uint32_t dk16 = __ldg(dskip + ch);
    uint32_t qa[32], qb[32];
    const uint32_t t1 = tb + A_R1 + (62 - 48) * 4;
    load_quads<4>(qa, tb + A_R3A + 17 * 4); load_quads<4>(qa + 16, tb + A_R3B + 16 * 4);
    wg_fence();
    s3_steps<0, 4, A_W9, 1>(y3, qa, blo_n); s3_steps<0, 4, A_W7, 0>(y3, qa + 16, blo_n);
    wg_commit();
    load_quads<8>(qb, tb + A_R2A + 16 * 4);
    wg_fence(); s2_steps<0, 8, A_W5, 1>(y2, qb, blo_n); wg_commit();
    wg_wait<1>(); load_quads<8>(qa, tb + A_R2B + 16 * 4);
    wg_fence(); s2_steps<0, 8, A_W3, 0>(y2, qa, blo_n); wg_commit();
    wg_wait<1>(); load_quads<8>(qb, t1);
    wg_fence(); f1_steps<0, 8>(y1, qb, blo_k); wg_commit();
    wg_wait<1>(); load_quads<8>(qa, t1 + 8 * 64);
    wg_fence(); f1_steps<8, 8>(y1, qa, blo_k); wg_commit();
    reg_fence(y2); reg_fence(y3);
    if (tid == 320) TR(0, 18);
    {
      const float k1024 = __uint_as_float(lds32(cb + A_K1024));
#pragma unroll
      for (int i = 0; i < 2; i++)
#pragma unroll
        for (int hf = 0; hf < 2; hf++) {
          const int idx = 16 * (16 * wq + g + 8 * hf) + 8 * i + 2 * t;
          const uint32_t vv = lds32(cb + A_V + idx * 2);
          sts64(cb + A_Y3 + (idx + 4 * (idx >> 6)) * 4, __float_as_uint(fmaf(k1024, bf_lo(vv), y3[4 * i + 2 * hf])),
                __float_as_uint(fmaf(k1024, bf_hi(vv), y3[4 * i + 2 * hf + 1])));
        }
#pragma unroll
      for (int i = 0; i < 3; i++)
#pragma unroll
        for (int hf = 0; hf < 2; hf++) {
          const int idx = 512 * i + 8 * (16 * wq + g + 8 * hf) + 2 * t;
          sts64(cb + A_Y2 + (idx + 4 * (idx >> 6)) * 4, __float_as_uint(y2[4 * i + 2 * hf]), __float_as_uint(y2[4 * i + 2 * hf + 1]));
        }
    }
    wg_wait<1>(); load_quads<8>(qb, t1 + 16 * 64);
    wg_fence(); f1_steps<16, 8>(y1, qb, blo_k); wg_commit();
    wg_wait<1>(); load_quads<8>(qa, t1 + 24 * 64);
    wg_fence(); f1_steps<24, 8>(y1, qa, blo_k); wg_commit();
    wg_wait<1>(); load_quads<5>(qb, t1 + 32 * 64);
    wg_fence(); f1_steps<32, 5>(y1, qb, blo_k); wg_commit();
    bar_sync(1 + wg, 128);
    float ex[12];
#pragma unroll
    for (int i = 1; i < 4; i++)
#pragma unroll
      for (int k = 0; k < 4; k++) {
        const int aa = 8 * i + 2 * t + (k & 1), b = 16 * wq + g + 8 * (k >> 1);
        float e = __uint_as_float(lds32(cb + A_Y2 + ((aa - 8) * 68 + b) * 4));
        if (i >= 2) e += __uint_as_float(lds32(cb + A_Y3 + ((aa - 16) * 68 + b) * 4));
        ex[4 * (i - 1) + k] = e;
      }
    {
      const uint32_t dk = dk16 * 0x10001u;
#pragma unroll
      for (int i = 0; i < 4; i++) {
        const uint4 r = lds128(cb + A_REC + bk * 64 + ((i ^ (bk >> 1)) & 3) * 16);
        ud[i] = hmul2_bf(r.x, dk); ud[4 + i] = hmul2_bf(r.y, dk); xt[i] = r.z; xt[4 + i] = r.w;
      }
    }
    wg_wait<0>();
    reg_fence(y1);
    if (tid == 320) TR(0, 6);
#pragma unroll
    for (int i = 0; i < 12; i++) y1[4 + i] += ex[i];
#pragma unroll
    for (int i = 0; i < 2; i++) {
      const int mi = lane >> 3, aa = 8 * (2 * i + (mi >> 1)) + (lane & 7);
      asm volatile("stmatrix.sync.aligned.m8n8.x4.trans.shared.b16 [%0], {%1,%2,%3,%4};"
                   ::"r"(cb + A_YB + aa * 128 + (((2 * wq + (mi & 1)) ^ (lane & 7)) << 4)),
                     "r"(pack_bf16(y1[8 * i], y1[8 * i + 1])), "r"(pack_bf16(y1[8 * i + 2], y1[8 * i + 3])),
                     "r"(pack_bf16(y1[8 * i + 4], y1[8 * i + 5])), "r"(pack_bf16(y1[8 * i + 6], y1[8 * i + 7])) : "memory");
    }
  }
  bar_sync(1 + wg, 128);
#pragma unroll
  for (int c = 0; c < 2; c++) {
    const int tau = 2 * bk + c, r = ch & 7;
    const uint4 y = lds128(cb + A_YB + (tau >> 3) * 128 + (((tau ^ (tau >> 3)) & 7) << 4));
    g_himg[(size_t)(tau >> 4) * 7168 + (ch >> 3) * 128 + ((tau >> 3) & 1) * 64 + r * 8 + ((tau & 7) ^ r)] =
        make_uint4(hadd2_bf(xt[4 * c], hadd2_bf(y.x, ud[4 * c])), hadd2_bf(xt[4 * c + 1], hadd2_bf(y.y, ud[4 * c + 1])),
                   hadd2_bf(xt[4 * c + 2], hadd2_bf(y.z, ud[4 * c + 2])), hadd2_bf(xt[4 * c + 3], hadd2_bf(y.w, ud[4 * c + 3])));
  }
  if (tid == 320) TR(0, 7);
}

constexpr int B_SA = 0, B_RING = 114688, B_SLOT = 14848, B_NSLOT = 7;
constexpr int B_CS = B_RING + B_NSLOT * B_SLOT;
constexpr int B_RED = B_CS + 7168;
constexpr int B_BAR = B_RED + 256;
constexpr int B_SMEM = B_BAR + 1024, A_SMEM = 4 * A_CH + 64;

__device__ __forceinline__ uint32_t mapa(uint32_t a, uint32_t r) { uint32_t o; asm("mapa.shared::cluster.u32 %0, %1, %2;" : "=r"(o) : "r"(a), "r"(r)); return o; }
template <class T> __device__ __forceinline__ T* pin(T* p) { asm volatile("" : "+l"(p)); return p; }
__device__ __forceinline__ uint32_t pin(uint32_t v) { asm volatile("" : "+r"(v)); return v; }
template <int Q, int ST>
__device__ __forceinline__ void g1_stage(float (&acc)[116], uint32_t alo, uint32_t blo, uint32_t bar_full, uint32_t bar_h) {
  constexpr int s = Q * 14 + ST, sl = s % B_NSLOT;
  if (Q == 0) mbar_wait(bar_h + 8 * ST, 0);
  mbar_wait(bar_full + 8 * sl, (s / B_NSLOT) & 1);
  wg_fence();
  if (Q == 0) {
    wgmma_ss232<(2 * ST) * 256, 0x40000080u, (sl * B_SLOT) / 16, 32, ST != 0>(acc, alo, blo);
    wgmma_ss232<(2 * ST + 1) * 256, 0x40000080u, (sl * B_SLOT + 256) / 16, 32, 1>(acc, alo, blo);
  } else {
    wgmma_ss224<(2 * ST) * 256, 0x40000080u, (sl * B_SLOT) / 16, 32, ST != 0>(*(float(*)[112])acc, alo, blo);
    wgmma_ss224<(2 * ST + 1) * 256, 0x40000080u, (sl * B_SLOT + 256) / 16, 32, 1>(*(float(*)[112])acc, alo, blo);
  }
}

__global__ void __launch_bounds__(512, 1)
k_front(const __nv_bfloat16* __restrict__ x, const uint32_t* __restrict__ are, const uint32_t* __restrict__ aim,
        const uint32_t* __restrict__ bre, const uint32_t* __restrict__ bim, const uint32_t* __restrict__ cre,
        const uint32_t* __restrict__ cim, const unsigned short* __restrict__ logdt, const unsigned short* __restrict__ dskip,
        const uint4* __restrict__ wgate, const uint4* __restrict__ wup, const uint4* __restrict__ wdown) {
  extern __shared__ __align__(1024) unsigned char sm[];
  const uint32_t bar_rec = s2u(sm) + 4 * A_CH;
  if (threadIdx.x == 320) TR(0, 0);
  asm volatile("griddepcontrol.launch_dependents;");
  if (threadIdx.x == 160) { mbar_init(bar_rec, 1); asm volatile("fence.mbarrier_init.release.cluster;" ::: "memory"); }
  phase_a(sm, bar_rec, bar_rec + 8, x, are, aim, bre, bim, cre, cim, logdt, dskip, wgate, wup, wdown);
}

__global__ void __cluster_dims__(2, 1, 1) __launch_bounds__(384, 1) k_ffn(__nv_bfloat16* __restrict__ out) {
  extern __shared__ __align__(1024) unsigned char sm[];
  const uint32_t sb = s2u(sm);
  const int tid = threadIdx.x, wg = tid >> 7, warp = tid >> 5, lane = tid & 31;
  const uint32_t bar_full = sb + B_BAR, bar_empty = bar_full + 64, bar_h = bar_full + 128, bar_cs = bar_full + 240,
                 bar_g2 = bar_full + 248, bar_in = bar_full + 256, bar_hh = bar_full + 304, bar_afree = bar_full + 336;
  if (tid == 0) {
    TR(1, 0);
    for (int i = 0; i < B_NSLOT; i++) { mbar_init(bar_full + 8 * i, 1); mbar_init(bar_empty + 8 * i, 2); }
    asm volatile("fence.mbarrier_init.release.cluster;" ::: "memory");
  } else if (tid == 32) {
    for (int i = 0; i < 14; i++) mbar_init(bar_h + 8 * i, 1);
    asm volatile("fence.mbarrier_init.release.cluster;" ::: "memory");
  } else if (tid == 64) {
    mbar_init(bar_cs, 1);
    mbar_init(bar_g2, 4);
    for (int i = 0; i < 6; i++) mbar_init(bar_in + 8 * i, 1);
    for (int i = 0; i < 4; i++) { mbar_init(bar_hh + 8 * i, 1); mbar_expect(bar_hh + 8 * i, 14336); }
    mbar_init(bar_afree, 4);
    asm volatile("fence.mbarrier_init.release.cluster;" ::: "memory");
  } else if (tid >= 128 && tid < 352) {
    sts128(sb + B_RING + ((tid - 128) >> 5) * B_SLOT + 14336 + (tid & 31) * 16, 0x3F803F80u, 0x3F803F80u, 0x3F803F80u, 0x3F803F80u);
  }
  asm volatile("fence.proxy.async.shared::cta;" ::: "memory");
  __syncthreads();
  asm volatile("barrier.cluster.arrive.relaxed.aligned;" ::: "memory");
  const int rank = blockIdx.x & 1, rt = blockIdx.x >> 3, j = blockIdx.x & 7, p = j >> 1, cg = 4 * rank + p;
  const int wq = warp & 3, t128 = tid & 127, g = lane >> 2, t = lane & 3;
  uint32_t ep, tag;
  auto load_ep = [&]() { asm volatile("ld.relaxed.gpu.global.u32 %0, [%1];" : "=r"(ep) : "l"(&g_cnt1) : "memory"); };
  auto a_slot = [&](int i, int own) { return B_SA + (i + (i >= own)) * 14336; };
  auto in_addr = [&](int q, int cw) { return sb + a_slot(4 + q, cg) + cw * 1792; };
  auto in_cta = [&](int q) { return rt * 8 + ((p + 3 - q) & 3) * 2 + rank; };
  auto in_src = [&](int q, int cw) { return g_part + (size_t)(in_cta(q) * 3 + q) * 896 + cw * 112; };
  auto add_in = [&](float (&sum)[28], int q, int cw) {
    const uint32_t a = in_addr(q, cw);
    const uint4 v0 = lds128(a + lane * 16), v1 = lds128(a + 512 + lane * 16), v2 = lds128(a + 1024 + lane * 16);
    uint32_t in[14] = {v0.x, v0.y, v0.z, v0.w, v1.x, v1.y, v1.z, v1.w, v2.x, v2.y, v2.z, v2.w, 0, 0};
    asm volatile("ld.shared.v2.u32 {%0, %1}, [%2];" : "=r"(in[12]), "=r"(in[13]) : "r"(a + 1536 + lane * 8) : "memory");
    int it = 0;
    while ((((in[3] ^ tag) | (in[7] ^ tag) | (in[11] ^ tag) | (in[13] ^ tag)) & 0x10000u) && ++it < 400000) {
      const uint4* gs = pin(in_src(q, cw));
#pragma unroll
      for (int i = 0; i < 3; i++) ld128(gs + i * 32 + lane, in + 4 * i);
      asm volatile("{\n.reg .b64 v;\nld.relaxed.gpu.global.b64 v, [%2];\nmov.b64 {%0, %1}, v;\n}"
                   : "=r"(in[12]), "=r"(in[13]) : "l"((const uint2*)(gs + 96) + lane) : "memory");
    }
#pragma unroll
    for (int i = 0; i < 14; i++) { sum[2 * i] += bf_lo(in[i]); sum[2 * i + 1] += bf_hi(in[i]); }
  };
  auto w_issue = [&](int s) {
    const char* wsrc = (const char*)g_wimg + (size_t)j * 602112;
    const int slot = s % B_NSLOT;
    const uint32_t dst = sb + B_RING + slot * B_SLOT, fb = bar_full + 8 * slot;
    if (s < 28) {
      mbar_expect(fb, 14336);
      bulk_ld(dst, wsrc + s * 14336, 14336, fb);
    } else {
      const int i = s - 28;
      const int ci = i < 3 ? 0 : i < 6 ? 1 : i < 8 ? i - 6 : i < 12 ? 2 : 3;
      const int kp = i < 3 ? i : i < 6 ? i - 3 : i < 8 ? 3 : (i & 3);
      mbar_expect(fb, 12544);
      bulk_ld(dst, (const char*)g_wimg + (size_t)(j ^ (kp >> 1)) * 602112 + 401408 + ((4 * rank + ((p + 1 + ci) & 3)) * 2 + (kp & 1)) * 12544, 12544, fb);
    }
  };

  if (wg == 2) {
    asm volatile("setmaxnreg.dec.sync.aligned.u32 40;");
    asm volatile("barrier.cluster.wait.aligned;" ::: "memory");
    asm volatile("griddepcontrol.wait;" ::: "memory");
    if (warp == 8) {
      if (lane == 0) {
        TR(1, 1);
        for (int s = 0; s < 44; s++) {
          if (s >= B_NSLOT) mbar_wait(bar_empty + 8 * (s % B_NSLOT), (s / B_NSLOT - 1) & 1);
          w_issue(s);
        }
      }
    } else if (warp == 9) {
      if (lane == 0) {
        const char* hsrc = (const char*)g_himg + (size_t)rt * 114688;
        for (int i = 0; i < 14; i++) {
          mbar_expect(bar_h + 8 * i, 8192);
          bulk_ld_mc(sb + B_SA + i * 8192 + rank * 4096, hsrc + i * 8192 + rank * 4096, 4096, bar_h + 8 * i);
        }
        mbar_expect(bar_cs, 7168);
        bulk_ld(sb + B_CS, g_cimg + j * 448, 7168, bar_cs);
      }
      __syncwarp();
      load_ep(); ep >>= 7;
      const int lq = (lane >> 1) & 3, lcw = (lane & 1) * 4;
      const uint4* fl = (const uint4*)(g_flag + in_cta(lq) * 32 + lq * 8 + lcw);
      bool todo = lane < 6, live = false;
      int it = 0;
      while (__any_sync(~0u, todo) && ++it < 400000) {
        if (!live) { __nanosleep(400); live = mbar_test(bar_g2, 0); }
        if (todo) {
          uint32_t w[4];
          ld128(fl, w);
          if (live && w[0] == ep && w[1] == ep && w[2] == ep && w[3] == ep) {
            mbar_expect(bar_in + 8 * lane, 7168);
            bulk_ld(in_addr(lq, lcw), in_src(lq, lcw), 7168, bar_in + 8 * lane);
            todo = false;
            if (lane & 1) TR(1, 24 + lq);
          }
        }
      }
    } else {
      const int t64 = tid - 320;
      load_ep();
      const int r = (lane >> 1) & 7, c = (j & 3) * 2 + (lane & 1);
      const uint32_t src = sb + B_SA + (t64 >> 4) * 2048 + (j >> 2) * 1024 + r * 128 + ((c ^ r) << 4);
      float a[16];
#pragma unroll
      for (int k = 0; k < 16; k++) a[k] = 0.f;
#pragma unroll 1
      for (int i = 0; i < 14; i++) {
        mbar_wait(bar_h + 8 * i, 0);
        uint4 v = lds128(src + i * 8192);
        float e[8] = {bf_lo(v.x), bf_hi(v.x), bf_lo(v.y), bf_hi(v.y), bf_lo(v.z), bf_hi(v.z), bf_lo(v.w), bf_hi(v.w)};
#pragma unroll
        for (int k = 0; k < 8; k++) { a[2 * k] += e[k]; a[2 * k + 1] = fmaf(e[k], e[k], a[2 * k + 1]); }
        __nanosleep(160);
      }
      __syncwarp();
      if (lane == 0) { mbar_arrive(bar_g2); asm volatile("mbarrier.arrive.shared::cluster.b64 _, [%0];" ::"r"(mapa(bar_afree, rank ^ 1)) : "memory"); }
#pragma unroll
      for (int rd = 0; rd < 4; rd++) {
        const int n = 8 >> rd;
        const bool up = lane & (2 * n);
#pragma unroll
        for (int k = 0; k < 8; k++) {
          if (k < n) {
            float keep = up ? a[k + n] : a[k], give = up ? a[k] : a[k + n];
            a[k] = keep + __shfl_xor_sync(~0u, give, 2 * n);
          }
        }
      }
      float* red = (float*)(sm + B_RED);
      red[(warp & 1) * 32 + (lane & 1) * 16 + (lane >> 1)] = a[0];
      bar_sync(1, 64);
      if (t64 < 16) {
        float mean = (red[2 * t64] + red[32 + 2 * t64]) * (1.f / DM);
        float var = fmaxf(fmaf(-mean, mean, (red[2 * t64 + 1] + red[33 + 2 * t64]) * (1.f / DM)), 0.f);
        float rs = __frcp_rn(rbf(__fsqrt_rn(rbf(rbf(var) + 1e-5f))));
        asm volatile("st.relaxed.gpu.global.u32 [%0], %1;"
                     ::"l"(g_stat2 + rt * 128 + j * 16 + t64), "r"((__float_as_uint(rs * rs) & ~1u) | ((ep >> 7) & 1u)) : "memory");
      }
      if (t64 == 0) TR(1, 2);
    }
  } else {
    asm volatile("setmaxnreg.inc.sync.aligned.u32 232;");
    asm volatile("barrier.cluster.wait.aligned;" ::: "memory");
    uint32_t hh[56];
    const bool relt = t128 == 0;
    auto release = [&](int sl) { if (relt) mbar_arrive(bar_empty + 8 * sl); };
    auto send_hh = [&](int q) {
      const uint32_t da = mapa(sb + a_slot(2 * q + wg, cg ^ 4) + t128 * 16, rank ^ 1), db = mapa(bar_hh + 8 * (2 * q + wg), rank ^ 1);
#pragma unroll
      for (int i = 0; i < 7; i++)
        asm volatile("st.async.weak.shared::cluster.mbarrier::complete_tx::bytes.v4.b32 [%0], {%1, %2, %3, %4}, [%5];"
                     ::"r"(da + i * 2048), "r"(hh[28 * q + 4 * i]), "r"(hh[28 * q + 4 * i + 1]),
                       "r"(hh[28 * q + 4 * i + 2]), "r"(hh[28 * q + 4 * i + 3]), "r"(db) : "memory");
    };
    const uint32_t alo = __shfl_sync(~0u, ((sb + B_SA + wg * 1024) & 0x3FFFF) >> 4, 0);
    const uint32_t blo = (((sb + B_RING) & 0x3FFFF) >> 4) | (8u << 16);
    const uint32_t clo = ((sb + B_CS) & 0x3FFFF) >> 4;
    uint32_t nm0, nm1;
    if (wg == 1) bar_sync(3, 256);
#define G1S(Q, ST) do { g1_stage<Q, ST>(acc, alo, blo, bar_full, bar_h); wg_commit(); \
      if (ST > 0) { wg_wait<1>(); release((Q * 14 + ST - 1) % B_NSLOT); } } while (0)
#define G1HH(Q) do { \
      _Pragma("unroll") \
      for (int i = 0; i < 28; i++) hh[28 * Q + i] = pack_bf16(acc[2 * i] * acc[56 + 2 * i], acc[2 * i + 1] * acc[57 + 2 * i]); \
    } while (0)
    {
      float acc[116];
      G1S(0, 0);
      if (tid == 0) TR(1, 3);
      G1S(0, 1);
      if (wg == 0) asm volatile("bar.arrive 3, 256;" ::: "memory");
      G1S(0, 2); G1S(0, 3); G1S(0, 4); G1S(0, 5); G1S(0, 6); G1S(0, 7); G1S(0, 8); G1S(0, 9); G1S(0, 10); G1S(0, 11); G1S(0, 12);
      G1S(0, 13);
      if (tid == 0) TR(1, 4);
      mbar_wait(bar_cs, 0);
      wg_wait<0>(); reg_fence(acc); release(13 % B_NSLOT);
      {
        const uint32_t msk = t == 0 ? 0xFFFFFFFFu : t == 1 ? 0xFFFFu : 0u;
        const float a = acc[112] * (-1.f / DM), b = acc[114] * (-1.f / DM);
        nm0 = pack_bf16(a, a) & msk; nm1 = pack_bf16(b, b) & msk;
      }
      wg_fence();
      wgmma_rs224<0, 8, 1>(*(float(*)[112])acc, nm0, nm1, 0u, 0u, clo);
      wg_commit(); wg_wait<0>(); reg_fence(acc);
      G1HH(0);
      if (tid == 0) TR(1, 5);
      G1S(1, 0); G1S(1, 1); G1S(1, 2); G1S(1, 3); G1S(1, 4); G1S(1, 5); G1S(1, 6); G1S(1, 7); G1S(1, 8); G1S(1, 9);
      if (relt) asm volatile("mbarrier.arrive.shared::cluster.b64 _, [%0];" ::"r"(mapa(bar_afree, rank ^ 1)) : "memory");
      G1S(1, 10); G1S(1, 11);
      G1S(1, 12);
      mbar_wait(bar_afree, 0);
      send_hh(0);
      load_ep();
      g1_stage<1, 13>(acc, alo, blo, bar_full, bar_h);
      wgmma_rs224<224, 8, 1>(*(float(*)[112])acc, nm0, nm1, 0u, 0u, clo);
      wg_commit(); wg_wait<1>(); release(26 % B_NSLOT);
      wg_wait<0>(); reg_fence(acc); release(27 % B_NSLOT);
      if (t128 == 0) mbar_arrive(bar_g2);
      G1HH(1);
      if (tid == 0) TR(1, 6);
    }
    float accA[28], accB[28], accC[28];
    uint32_t ph0[28], ph1[28];
    ep = pin(ep >> 7); tag = pin((ep & 1u) << 16);
#define ISSUE(acc, I, a, FIRST) do { \
      constexpr int s_ = 28 + (I), sl_ = s_ % B_NSLOT; \
      mbar_wait(bar_full + 8 * sl_, (s_ / B_NSLOT) & 1); \
      wg_fence(); \
      wgmma_rs56<(sl_ * B_SLOT + 0 * 256) / 16, 112, !(FIRST)>(acc, (a)[0], (a)[1], (a)[2], (a)[3], blo); \
      wgmma_rs56<(sl_ * B_SLOT + 1 * 256) / 16, 112, 1>(acc, (a)[4], (a)[5], (a)[6], (a)[7], blo); \
      wgmma_rs56<(sl_ * B_SLOT + 2 * 256) / 16, 112, 1>(acc, (a)[8], (a)[9], (a)[10], (a)[11], blo); \
      wgmma_rs56<(sl_ * B_SLOT + 3 * 256) / 16, 112, 1>(acc, (a)[12], (a)[13], (a)[14], (a)[15], blo); \
      wgmma_rs56<(sl_ * B_SLOT + 4 * 256) / 16, 112, 1>(acc, (a)[16], (a)[17], (a)[18], (a)[19], blo); \
      wgmma_rs56<(sl_ * B_SLOT + 5 * 256) / 16, 112, 1>(acc, (a)[20], (a)[21], (a)[22], (a)[23], blo); \
      wgmma_rs56<(sl_ * B_SLOT + 6 * 256) / 16, 112, 1>(acc, (a)[24], (a)[25], (a)[26], (a)[27], blo); \
      wg_commit(); } while (0)
    uint4* const pdst = pin(g_part + (size_t)blockIdx.x * 3 * 896 + warp * 112 + lane);
    uint32_t* const fdst = pin(g_flag + blockIdx.x * 32 + warp);
    auto rel = [&](int i) { release((28 + i) % B_NSLOT); };
    auto tg = [&](uint32_t v) { return (v & 0xFFFEFFFFu) | tag; };
    auto send = [&](float (&acc)[28], int cc) {
      reg_fence(acc);
#pragma unroll
      for (int q = 0; q < 3; q++)
        st128(pdst + cc * 896 + q * 32, pack_bf16(acc[8 * q], acc[8 * q + 1]), pack_bf16(acc[8 * q + 2], acc[8 * q + 3]),
              pack_bf16(acc[8 * q + 4], acc[8 * q + 5]), tg(pack_bf16(acc[8 * q + 6], acc[8 * q + 7])));
      asm volatile("{\n.reg .b64 v;\nmov.b64 v, {%1, %2};\nst.relaxed.gpu.global.b64 [%0], v;\n}"
                   ::"l"((uint2*)(pdst + cc * 896 + 96) - lane), "r"(pack_bf16(acc[24], acc[25])), "r"(tg(pack_bf16(acc[26], acc[27]))) : "memory");
    };
    auto flag = [&](int cc) { if (lane == 0) asm volatile("st.relaxed.gpu.global.u32 [%0], %1;" ::"l"(fdst + cc * 8), "r"(ep) : "memory"); };
    auto load_hh = [&](uint32_t (&d)[28], int q) {
      mbar_wait(bar_hh + 8 * (2 * q + wg), 0);
      const uint32_t a = sb + a_slot(2 * q + wg, cg) + t128 * 16;
#pragma unroll
      for (int i = 0; i < 7; i++) {
        const uint4 v = lds128(a + i * 2048);
        d[4 * i] = v.x; d[4 * i + 1] = v.y; d[4 * i + 2] = v.z; d[4 * i + 3] = v.w;
      }
    };
    ISSUE(accA, 0, hh, true);
    send_hh(1);
    ISSUE(accA, 1, hh + 28, false);
    load_hh(ph0, 0);
    wg_wait<1>(); rel(0);
    ISSUE(accA, 2, ph0, false);      wg_wait<1>(); rel(1);
    ISSUE(accB, 3, hh, true);        wg_wait<1>(); rel(2);
    ISSUE(accB, 4, hh + 28, false);  wg_wait<1>(); rel(3);
    ISSUE(accB, 5, ph0, false);
    if (tid == 0) TR(1, 11);
    load_hh(ph1, 1);
    wg_wait<1>(); rel(4);
    ISSUE(accA, 6, ph1, false);      wg_wait<1>(); rel(5);
    ISSUE(accB, 7, ph1, false);      wg_wait<1>(); rel(6);
    ISSUE(accC, 8, hh, true);        send(accA, 0); wg_wait<1>(); rel(7);
    if (tid == 0) TR(1, 13);
    ISSUE(accC, 9, hh + 28, false);  send(accB, 1); flag(0); wg_wait<1>(); rel(8);
    ISSUE(accC, 10, ph0, false);     flag(1);
    ISSUE(accC, 11, ph1, false);
    const int row = rt * 128 + wg * 64 + wq * 16 + g;
    uint32_t r20, r21;
    asm volatile("ld.relaxed.gpu.global.u32 %0, [%1];" : "=r"(r20) : "l"(g_stat2 + row) : "memory");
    asm volatile("ld.relaxed.gpu.global.u32 %0, [%1];" : "=r"(r21) : "l"(g_stat2 + row + 8) : "memory");
    ISSUE(accB, 12, hh, true);
    wg_wait<1>();
    send(accC, 2);
    if (tid == 0) TR(1, 16);
    ISSUE(accB, 13, hh + 28, false);
    flag(2);
    ISSUE(accB, 14, ph0, false);
    ISSUE(accB, 15, ph1, false);
    if (tid == 0) TR(1, 7);
    uint32_t hres[16];
#pragma unroll
    for (int i = 0; i < 4; i++) {
      int qq = lane >> 3, r = lane & 7, kg = 7 * cg + 2 * i + (qq >> 1), c = 2 * wq + (qq & 1);
      if (kg > 55) kg = 55;
      asm volatile("ldmatrix.sync.aligned.m8n8.x4.trans.shared.b16 {%0,%1,%2,%3}, [%4];"
                   : "=r"(hres[4 * i]), "=r"(hres[4 * i + 1]), "=r"(hres[4 * i + 2]), "=r"(hres[4 * i + 3])
                   : "r"(sb + B_SA + kg * 2048 + wg * 1024 + r * 128 + ((c ^ r) << 4)) : "memory");
    }
    {
      int it = 0;
      while ((((r20 ^ ep) | (r21 ^ ep)) & 1u) && ++it < 400000) {
        asm volatile("ld.relaxed.gpu.global.u32 %0, [%1];" : "=r"(r20) : "l"(g_stat2 + row) : "memory");
        asm volatile("ld.relaxed.gpu.global.u32 %0, [%1];" : "=r"(r21) : "l"(g_stat2 + row + 8) : "memory");
      }
    }
    wg_wait<0>();
    reg_fence(accB);
    if (tid == 0) TR(1, 9);
#pragma unroll 1
    for (int q = 0; q < 3; q++) {
      mbar_wait(bar_in + 8 * (2 * q + wg), 0);
      add_in(accB, q, warp);
      if (tid == 0 && q == 1) TR(1, 12);
    }
    uint32_t* o0 = (uint32_t*)(out + (size_t)row * DM + 56 * cg + 2 * t);
    uint32_t* o1 = o0 + 8 * DM / 2;
#pragma unroll
    for (int i = 0; i < 7; i++) {
      o0[4 * i] = hadd2_bf(hres[2 * i], pack_bf16(accB[4 * i] * __uint_as_float(r20), accB[4 * i + 1] * __uint_as_float(r20)));
      o1[4 * i] = hadd2_bf(hres[2 * i + 1], pack_bf16(accB[4 * i + 2] * __uint_as_float(r21), accB[4 * i + 3] * __uint_as_float(r21)));
    }
    if (tid == 0) TR(1, 10);
    if (tid == 128) TR(1, 15);
  }
}

extern "C" void kernel_launch(void* const* d_in, const int* in_sizes, int n_in, void* d_out, int out_size) {
  const __nv_bfloat16* x = (const __nv_bfloat16*)d_in[0];
  const __nv_bfloat16 *are = (const __nv_bfloat16*)d_in[1], *aim = (const __nv_bfloat16*)d_in[2], *bre = (const __nv_bfloat16*)d_in[3],
                      *bim = (const __nv_bfloat16*)d_in[4], *cre = (const __nv_bfloat16*)d_in[5], *cim = (const __nv_bfloat16*)d_in[6],
                      *logdt = (const __nv_bfloat16*)d_in[7], *dskip = (const __nv_bfloat16*)d_in[8];
  const __nv_bfloat16 *wg = (const __nv_bfloat16*)d_in[10], *wu = (const __nv_bfloat16*)d_in[11], *wd = (const __nv_bfloat16*)d_in[12];

  static bool init = false;
  if (!init) {
    init = true;
    cudaFuncSetAttribute(k_ffn, cudaFuncAttributeMaxDynamicSharedMemorySize, B_SMEM);
    cudaFuncSetAttribute(k_front, cudaFuncAttributeMaxDynamicSharedMemorySize, A_SMEM);
  }
  cudaStream_t st = cudaStreamPerThread;
  k_front<<<128, 512, A_SMEM, st>>>(
      x, (const uint32_t*)are, (const uint32_t*)aim, (const uint32_t*)bre, (const uint32_t*)bim, (const uint32_t*)cre, (const uint32_t*)cim,
      (const unsigned short*)logdt, (const unsigned short*)dskip, (const uint4*)wg, (const uint4*)wu, (const uint4*)wd);
  cudaLaunchConfig_t cfg = {};
  cfg.gridDim = dim3(128); cfg.blockDim = dim3(384); cfg.dynamicSmemBytes = B_SMEM; cfg.stream = st;
  cudaLaunchAttribute at[1];
  at[0].id = cudaLaunchAttributeProgrammaticStreamSerialization; at[0].val.programmaticStreamSerializationAllowed = 1;
  cfg.attrs = at; cfg.numAttrs = 1;
  cudaLaunchKernelEx(&cfg, k_ffn, (__nv_bfloat16*)d_out);
}
```

```cpp
#include <cuda_runtime.h>
#include <cuda_bf16.h>
#include <stdint.h>

constexpr int LSEQ = 2048, DM = 448;

__device__ uint4    g_himg[16 * 114688 / 16];
__device__ uint4    g_cimg[8 * 2 * 224];
__device__ uint32_t g_stat2[LSEQ];
__device__ uint4    g_part[128 * 3 * 896];
__device__ uint4    g_wimg[8 * 602112 / 16];
__device__ uint4    g_ux[DM * 128 * 4];
__device__ unsigned g_cnt1;
__device__ uint32_t g_flag[128 * 8];

#define TR(k, i) do {} while (0)
__device__ __forceinline__ uint32_t s2u(const void* p) { return (uint32_t)__cvta_generic_to_shared(p); }
__device__ __forceinline__ void mbar_init(uint32_t b, int c) { asm volatile("mbarrier.init.shared::cta.b64 [%0], %1;" ::"r"(b), "r"(c)); }
__device__ __forceinline__ void mbar_expect(uint32_t b, int bytes) { asm volatile("mbarrier.arrive.expect_tx.shared::cta.b64 _, [%0], %1;" ::"r"(b), "r"(bytes) : "memory"); }
__device__ __forceinline__ void mbar_arrive(uint32_t b) { asm volatile("mbarrier.arrive.shared::cta.b64 _, [%0];" ::"r"(b) : "memory"); }
__device__ __forceinline__ void mbar_wait(uint32_t b, int ph) {
  asm volatile("{\n.reg .pred p;\n.reg .b32 n;\nmov.b32 n, 0;\nLW:\nmbarrier.try_wait.parity.shared::cta.b64 p, [%0], %1;\n@p bra LD;\n"
               "add.u32 n, n, 1;\nsetp.lt.u32 p, n, 4000000;\n@p bra LW;\ntrap;\nLD:\n}" ::"r"(b), "r"(ph) : "memory");
}
__device__ __forceinline__ bool mbar_test(uint32_t b, int ph) {
  uint32_t ok;
  asm volatile("{\n.reg .pred p;\nmbarrier.test_wait.parity.shared::cta.b64 p, [%1], %2;\nselp.u32 %0, 1, 0, p;\n}" : "=r"(ok) : "r"(b), "r"(ph) : "memory");
  return ok;
}
__device__ __forceinline__ void wg_fence() { asm volatile("wgmma.fence.sync.aligned;" ::: "memory"); }
__device__ __forceinline__ void wg_commit() { asm volatile("wgmma.commit_group.sync.aligned;" ::: "memory"); }
template <int N> __device__ __forceinline__ void wg_wait() { asm volatile("wgmma.wait_group.sync.aligned %0;" ::"n"(N) : "memory"); }
template <int N> __device__ __forceinline__ void reg_fence(float (&a)[N]) {
#pragma unroll
  for (int i = 0; i < N; i++) asm volatile("" : "+f"(a[i])::"memory");
}
__device__ __forceinline__ uint32_t pack_bf16(float lo, float hi) {
  uint32_t r; asm("cvt.rn.bf16x2.f32 %0, %1, %2;" : "=r"(r) : "f"(hi), "f"(lo)); return r;
}
__device__ __forceinline__ float bf_lo(uint32_t v) { return __uint_as_float(v << 16); }
__device__ __forceinline__ float bf_hi(uint32_t v) { return __uint_as_float(v & 0xFFFF0000u); }
__device__ __forceinline__ float rbf(float x) { return __bfloat162float(__float2bfloat16_rn(x)); }
__device__ __forceinline__ uint32_t hmul2_bf(uint32_t a, uint32_t b) { uint32_t r; asm("mul.rn.bf16x2 %0, %1, %2;" : "=r"(r) : "r"(a), "r"(b)); return r; }
__device__ __forceinline__ uint32_t hadd2_bf(uint32_t a, uint32_t b) { uint32_t r; asm("add.rn.bf16x2 %0, %1, %2;" : "=r"(r) : "r"(a), "r"(b)); return r; }
__device__ __forceinline__ void bulk_ld(uint32_t dst, const void* src, int bytes, uint32_t bar) {
  asm volatile("cp.async.bulk.shared::cluster.global.mbarrier::complete_tx::bytes [%0], [%1], %2, [%3];"
               ::"r"(dst), "l"(src), "r"(bytes), "r"(bar) : "memory");
}

__device__ __forceinline__ void bulk_ld_mc(uint32_t dst, const void* src, int bytes, uint32_t bar) {
  asm volatile("cp.async.bulk.shared::cluster.global.mbarrier::complete_tx::bytes.multicast::cluster [%0], [%1], %2, [%3], %4;"
               ::"r"(dst), "l"(src), "r"(bytes), "r"(bar), "h"((uint16_t)3) : "memory");
}
template <int AOFF, uint32_t AHI, int BOFF, uint32_t BHI, int ACC>
__device__ __forceinline__ void wgmma_ss224(float (&d)[112], uint32_t alo, uint32_t blo) {
  asm volatile("{\n.reg .pred p;\n.reg .b32 la, lb;\n.reg .b64 ad, bd;\nsetp.ne.b32 p, %118, 0;\n"
    "add.u32 la, %112, %114;\nmov.b64 ad, {la, %115};\nadd.u32 lb, %113, %116;\nmov.b64 bd, {lb, %117};\n"
    "wgmma.mma_async.sync.aligned.m64n224k16.f32.bf16.bf16 {%0,%1,%2,%3,%4,%5,%6,%7,%8,%9,%10,%11,%12,%13,%14,%15,%16,%17,%18,%19,%20,%21,%22,%23,%24,%25,%26,%27,%28,%29,%30,%31,%32,%33,%34,%35,%36,%37,%38,%39,%40,%41,%42,%43,%44,%45,%46,%47,%48,%49,%50,%51,%52,%53,%54,%55,%56,%57,%58,%59,%60,%61,%62,%63,%64,%65,%66,%67,%68,%69,%70,%71,%72,%73,%74,%75,%76,%77,%78,%79,%80,%81,%82,%83,%84,%85,%86,%87,%88,%89,%90,%91,%92,%93,%94,%95,%96,%97,%98,%99,%100,%101,%102,%103,%104,%105,%106,%107,%108,%109,%110,%111}, ad, bd, p, 1, 1, 1, 1;\n}\n"
    : "+f"(d[0]),"+f"(d[1]),"+f"(d[2]),"+f"(d[3]),"+f"(d[4]),"+f"(d[5]),"+f"(d[6]),"+f"(d[7]),"+f"(d[8]),"+f"(d[9]),"+f"(d[10]),"+f"(d[11]),"+f"(d[12]),"+f"(d[13]),"+f"(d[14]),"+f"(d[15]),"+f"(d[16]),"+f"(d[17]),"+f"(d[18]),"+f"(d[19]),"+f"(d[20]),"+f"(d[21]),"+f"(d[22]),"+f"(d[23]),"+f"(d[24]),"+f"(d[25]),"+f"(d[26]),"+f"(d[27]),"+f"(d[28]),"+f"(d[29]),"+f"(d[30]),"+f"(d[31]),"+f"(d[32]),"+f"(d[33]),"+f"(d[34]),"+f"(d[35]),"+f"(d[36]),"+f"(d[37]),"+f"(d[38]),"+f"(d[39]),"+f"(d[40]),"+f"(d[41]),"+f"(d[42]),"+f"(d[43]),"+f"(d[44]),"+f"(d[45]),"+f"(d[46]),"+f"(d[47]),"+f"(d[48]),"+f"(d[49]),"+f"(d[50]),"+f"(d[51]),"+f"(d[52]),"+f"(d[53]),"+f"(d[54]),"+f"(d[55]),"+f"(d[56]),"+f"(d[57]),"+f"(d[58]),"+f"(d[59]),"+f"(d[60]),"+f"(d[61]),"+f"(d[62]),"+f"(d[63]),"+f"(d[64]),"+f"(d[65]),"+f"(d[66]),"+f"(d[67]),"+f"(d[68]),"+f"(d[69]),"+f"(d[70]),"+f"(d[71]),"+f"(d[72]),"+f"(d[73]),"+f"(d[74]),"+f"(d[75]),"+f"(d[76]),"+f"(d[77]),"+f"(d[78]),"+f"(d[79]),"+f"(d[80]),"+f"(d[81]),"+f"(d[82]),"+f"(d[83]),"+f"(d[84]),"+f"(d[85]),"+f"(d[86]),"+f"(d[87]),"+f"(d[88]),"+f"(d[89]),"+f"(d[90]),"+f"(d[91]),"+f"(d[92]),"+f"(d[93]),"+f"(d[94]),"+f"(d[95]),"+f"(d[96]),"+f"(d[97]),"+f"(d[98]),"+f"(d[99]),"+f"(d[100]),"+f"(d[101]),"+f"(d[102]),"+f"(d[103]),"+f"(d[104]),"+f"(d[105]),"+f"(d[106]),"+f"(d[107]),"+f"(d[108]),"+f"(d[109]),"+f"(d[110]),"+f"(d[111])
    : "r"(alo), "r"(blo), "n"(AOFF), "n"(AHI), "n"(BOFF), "n"(BHI), "n"(ACC));
}
template <int AOFF, uint32_t AHI, int BOFF, uint32_t BHI, int ACC>
__device__ __forceinline__ void wgmma_ss232(float (&d)[116], uint32_t alo, uint32_t blo) {
  asm volatile("{\n.reg .pred p;\n.reg .b32 la, lb;\n.reg .b64 ad, bd;\nsetp.ne.b32 p, %122, 0;\n"
    "add.u32 la, %116, %118;\nmov.b64 ad, {la, %119};\nadd.u32 lb, %117, %120;\nmov.b64 bd, {lb, %121};\n"
    "wgmma.mma_async.sync.aligned.m64n232k16.f32.bf16.bf16 {%0,%1,%2,%3,%4,%5,%6,%7,%8,%9,%10,%11,%12,%13,%14,%15,%16,%17,%18,%19,%20,%21,%22,%23,%24,%25,%26,%27,%28,%29,%30,%31,%32,%33,%34,%35,%36,%37,%38,%39,%40,%41,%42,%43,%44,%45,%46,%47,%48,%49,%50,%51,%52,%53,%54,%55,%56,%57,%58,%59,%60,%61,%62,%63,%64,%65,%66,%67,%68,%69,%70,%71,%72,%73,%74,%75,%76,%77,%78,%79,%80,%81,%82,%83,%84,%85,%86,%87,%88,%89,%90,%91,%92,%93,%94,%95,%96,%97,%98,%99,%100,%101,%102,%103,%104,%105,%106,%107,%108,%109,%110,%111,%112,%113,%114,%115}, ad, bd, p, 1, 1, 1, 1;\n}\n"
    : "+f"(d[0]),"+f"(d[1]),"+f"(d[2]),"+f"(d[3]),"+f"(d[4]),"+f"(d[5]),"+f"(d[6]),"+f"(d[7]),"+f"(d[8]),"+f"(d[9]),"+f"(d[10]),"+f"(d[11]),"+f"(d[12]),"+f"(d[13]),"+f"(d[14]),"+f"(d[15]),"+f"(d[16]),"+f"(d[17]),"+f"(d[18]),"+f"(d[19]),"+f"(d[20]),"+f"(d[21]),"+f"(d[22]),"+f"(d[23]),"+f"(d[24]),"+f"(d[25]),"+f"(d[26]),"+f"(d[27]),"+f"(d[28]),"+f"(d[29]),"+f"(d[30]),"+f"(d[31]),"+f"(d[32]),"+f"(d[33]),"+f"(d[34]),"+f"(d[35]),"+f"(d[36]),"+f"(d[37]),"+f"(d[38]),"+f"(d[39]),"+f"(d[40]),"+f"(d[41]),"+f"(d[42]),"+f"(d[43]),"+f"(d[44]),"+f"(d[45]),"+f"(d[46]),"+f"(d[47]),"+f"(d[48]),"+f"(d[49]),"+f"(d[50]),"+f"(d[51]),"+f"(d[52]),"+f"(d[53]),"+f"(d[54]),"+f"(d[55]),"+f"(d[56]),"+f"(d[57]),"+f"(d[58]),"+f"(d[59]),"+f"(d[60]),"+f"(d[61]),"+f"(d[62]),"+f"(d[63]),"+f"(d[64]),"+f"(d[65]),"+f"(d[66]),"+f"(d[67]),"+f"(d[68]),"+f"(d[69]),"+f"(d[70]),"+f"(d[71]),"+f"(d[72]),"+f"(d[73]),"+f"(d[74]),"+f"(d[75]),"+f"(d[76]),"+f"(d[77]),"+f"(d[78]),"+f"(d[79]),"+f"(d[80]),"+f"(d[81]),"+f"(d[82]),"+f"(d[83]),"+f"(d[84]),"+f"(d[85]),"+f"(d[86]),"+f"(d[87]),"+f"(d[88]),"+f"(d[89]),"+f"(d[90]),"+f"(d[91]),"+f"(d[92]),"+f"(d[93]),"+f"(d[94]),"+f"(d[95]),"+f"(d[96]),"+f"(d[97]),"+f"(d[98]),"+f"(d[99]),"+f"(d[100]),"+f"(d[101]),"+f"(d[102]),"+f"(d[103]),"+f"(d[104]),"+f"(d[105]),"+f"(d[106]),"+f"(d[107]),"+f"(d[108]),"+f"(d[109]),"+f"(d[110]),"+f"(d[111]),"+f"(d[112]),"+f"(d[113]),"+f"(d[114]),"+f"(d[115])
    : "r"(alo), "r"(blo), "n"(AOFF), "n"(AHI), "n"(BOFF), "n"(BHI), "n"(ACC));
}
template <int OFF, uint32_t BHI, int ACC>
__device__ __forceinline__ void wgmma_rs224(float (&d)[112], uint32_t a0, uint32_t a1, uint32_t a2, uint32_t a3, uint32_t blo) {
  asm volatile("{\n.reg .pred p;\n.reg .b32 l;\n.reg .b64 bd;\nsetp.ne.b32 p, %119, 0;\nadd.u32 l, %116, %117;\nmov.b64 bd, {l, %118};\n"
    "wgmma.mma_async.sync.aligned.m64n224k16.f32.bf16.bf16 {%0,%1,%2,%3,%4,%5,%6,%7,%8,%9,%10,%11,%12,%13,%14,%15,%16,%17,%18,%19,%20,%21,%22,%23,%24,%25,%26,%27,%28,%29,%30,%31,%32,%33,%34,%35,%36,%37,%38,%39,%40,%41,%42,%43,%44,%45,%46,%47,%48,%49,%50,%51,%52,%53,%54,%55,%56,%57,%58,%59,%60,%61,%62,%63,%64,%65,%66,%67,%68,%69,%70,%71,%72,%73,%74,%75,%76,%77,%78,%79,%80,%81,%82,%83,%84,%85,%86,%87,%88,%89,%90,%91,%92,%93,%94,%95,%96,%97,%98,%99,%100,%101,%102,%103,%104,%105,%106,%107,%108,%109,%110,%111}, {%112,%113,%114,%115}, bd, p, 1, 1, 1;\n}\n"
    : "+f"(d[0]),"+f"(d[1]),"+f"(d[2]),"+f"(d[3]),"+f"(d[4]),"+f"(d[5]),"+f"(d[6]),"+f"(d[7]),"+f"(d[8]),"+f"(d[9]),"+f"(d[10]),"+f"(d[11]),"+f"(d[12]),"+f"(d[13]),"+f"(d[14]),"+f"(d[15]),"+f"(d[16]),"+f"(d[17]),"+f"(d[18]),"+f"(d[19]),"+f"(d[20]),"+f"(d[21]),"+f"(d[22]),"+f"(d[23]),"+f"(d[24]),"+f"(d[25]),"+f"(d[26]),"+f"(d[27]),"+f"(d[28]),"+f"(d[29]),"+f"(d[30]),"+f"(d[31]),"+f"(d[32]),"+f"(d[33]),"+f"(d[34]),"+f"(d[35]),"+f"(d[36]),"+f"(d[37]),"+f"(d[38]),"+f"(d[39]),"+f"(d[40]),"+f"(d[41]),"+f"(d[42]),"+f"(d[43]),"+f"(d[44]),"+f"(d[45]),"+f"(d[46]),"+f"(d[47]),"+f"(d[48]),"+f"(d[49]),"+f"(d[50]),"+f"(d[51]),"+f"(d[52]),"+f"(d[53]),"+f"(d[54]),"+f"(d[55]),"+f"(d[56]),"+f"(d[57]),"+f"(d[58]),"+f"(d[59]),"+f"(d[60]),"+f"(d[61]),"+f"(d[62]),"+f"(d[63]),"+f"(d[64]),"+f"(d[65]),"+f"(d[66]),"+f"(d[67]),"+f"(d[68]),"+f"(d[69]),"+f"(d[70]),"+f"(d[71]),"+f"(d[72]),"+f"(d[73]),"+f"(d[74]),"+f"(d[75]),"+f"(d[76]),"+f"(d[77]),"+f"(d[78]),"+f"(d[79]),"+f"(d[80]),"+f"(d[81]),"+f"(d[82]),"+f"(d[83]),"+f"(d[84]),"+f"(d[85]),"+f"(d[86]),"+f"(d[87]),"+f"(d[88]),"+f"(d[89]),"+f"(d[90]),"+f"(d[91]),"+f"(d[92]),"+f"(d[93]),"+f"(d[94]),"+f"(d[95]),"+f"(d[96]),"+f"(d[97]),"+f"(d[98]),"+f"(d[99]),"+f"(d[100]),"+f"(d[101]),"+f"(d[102]),"+f"(d[103]),"+f"(d[104]),"+f"(d[105]),"+f"(d[106]),"+f"(d[107]),"+f"(d[108]),"+f"(d[109]),"+f"(d[110]),"+f"(d[111])
    : "r"(a0), "r"(a1), "r"(a2), "r"(a3), "r"(blo), "n"(OFF), "n"(BHI), "n"(ACC));
}
template <int OFF, uint32_t BHI, int ACC>
__device__ __forceinline__ void wgmma_rs56(float (&d)[28], uint32_t a0, uint32_t a1, uint32_t a2, uint32_t a3, uint32_t blo) {
  asm volatile("{\n.reg .pred p;\n.reg .b32 l;\n.reg .b64 bd;\nsetp.ne.b32 p, %35, 0;\nadd.u32 l, %32, %33;\nmov.b64 bd, {l, %34};\n"
    "wgmma.mma_async.sync.aligned.m64n56k16.f32.bf16.bf16 {%0,%1,%2,%3,%4,%5,%6,%7,%8,%9,%10,%11,%12,%13,%14,%15,%16,%17,%18,%19,%20,%21,%22,%23,%24,%25,%26,%27}, {%28,%29,%30,%31}, bd, p, 1, 1, 1;\n}\n"
    : "+f"(d[0]),"+f"(d[1]),"+f"(d[2]),"+f"(d[3]),"+f"(d[4]),"+f"(d[5]),"+f"(d[6]),"+f"(d[7]),"+f"(d[8]),"+f"(d[9]),"+f"(d[10]),"+f"(d[11]),"+f"(d[12]),"+f"(d[13]),"+f"(d[14]),"+f"(d[15]),"+f"(d[16]),"+f"(d[17]),"+f"(d[18]),"+f"(d[19]),"+f"(d[20]),"+f"(d[21]),"+f"(d[22]),"+f"(d[23]),"+f"(d[24]),"+f"(d[25]),"+f"(d[26]),"+f"(d[27])
    : "r"(a0), "r"(a1), "r"(a2), "r"(a3), "r"(blo), "n"(OFF), "n"(BHI), "n"(ACC));
}

__device__ __forceinline__ void st128(uint4* p, uint32_t a, uint32_t b, uint32_t c, uint32_t d) {
  asm volatile("{\n.reg .b128 v;\n.reg .b64 lo, hi;\nmov.b64 lo, {%1, %2};\nmov.b64 hi, {%3, %4};\nmov.b128 v, {lo, hi};\n"
               "st.relaxed.gpu.global.b128 [%0], v;\n}" ::"l"(p), "r"(a), "r"(b), "r"(c), "r"(d) : "memory");
}
__device__ __forceinline__ void ld128(const uint4* p, uint32_t* r) {
  asm volatile("{\n.reg .b128 v;\n.reg .b64 lo, hi;\nld.relaxed.gpu.global.b128 v, [%4];\nmov.b128 {lo, hi}, v;\n"
               "mov.b64 {%0, %1}, lo;\nmov.b64 {%2, %3}, hi;\n}" : "=r"(r[0]), "=r"(r[1]), "=r"(r[2]), "=r"(r[3]) : "l"(p) : "memory");
}

template <int OFF, uint32_t BHI, int ACC>
__device__ __forceinline__ void wgmma_rs32(float (&d)[16], uint32_t a0, uint32_t a1, uint32_t a2, uint32_t a3, uint32_t blo) {
  asm volatile("{\n.reg .pred p;\n.reg .b32 l;\n.reg .b64 bd;\nsetp.ne.b32 p, %23, 0;\nadd.u32 l, %20, %21;\nmov.b64 bd, {l, %22};\n"
    "wgmma.mma_async.sync.aligned.m64n32k16.f32.bf16.bf16 {%0,%1,%2,%3,%4,%5,%6,%7,%8,%9,%10,%11,%12,%13,%14,%15}, {%16,%17,%18,%19}, bd, p, 1, 1, 0;\n}\n"
    : "+f"(d[0]),"+f"(d[1]),"+f"(d[2]),"+f"(d[3]),"+f"(d[4]),"+f"(d[5]),"+f"(d[6]),"+f"(d[7]),"+f"(d[8]),"+f"(d[9]),"+f"(d[10]),"+f"(d[11]),"+f"(d[12]),"+f"(d[13]),"+f"(d[14]),"+f"(d[15])
    : "r"(a0), "r"(a1), "r"(a2), "r"(a3), "r"(blo), "n"(OFF), "n"(BHI), "n"(ACC));
}
template <int OFF, uint32_t BHI, int ACC>
__device__ __forceinline__ void wgmma_rs24(float (&d)[12], uint32_t a0, uint32_t a1, uint32_t a2, uint32_t a3, uint32_t blo) {
  asm volatile("{\n.reg .pred p;\n.reg .b32 l;\n.reg .b64 bd;\nsetp.ne.b32 p, %19, 0;\nadd.u32 l, %16, %17;\nmov.b64 bd, {l, %18};\n"
    "wgmma.mma_async.sync.aligned.m64n24k16.f32.bf16.bf16 {%0,%1,%2,%3,%4,%5,%6,%7,%8,%9,%10,%11}, {%12,%13,%14,%15}, bd, p, 1, 1, 1;\n}\n"
    : "+f"(d[0]),"+f"(d[1]),"+f"(d[2]),"+f"(d[3]),"+f"(d[4]),"+f"(d[5]),"+f"(d[6]),"+f"(d[7]),"+f"(d[8]),"+f"(d[9]),"+f"(d[10]),"+f"(d[11])
    : "r"(a0), "r"(a1), "r"(a2), "r"(a3), "r"(blo), "n"(OFF), "n"(BHI), "n"(ACC));
}
template <int OFF, uint32_t BHI, int ACC>
__device__ __forceinline__ void wgmma_rs16(float (&d)[8], uint32_t a0, uint32_t a1, uint32_t a2, uint32_t a3, uint32_t blo) {
  asm volatile("{\n.reg .pred p;\n.reg .b32 l;\n.reg .b64 bd;\nsetp.ne.b32 p, %15, 0;\nadd.u32 l, %12, %13;\nmov.b64 bd, {l, %14};\n"
    "wgmma.mma_async.sync.aligned.m64n16k16.f32.bf16.bf16 {%0,%1,%2,%3,%4,%5,%6,%7}, {%8,%9,%10,%11}, bd, p, 1, 1, 1;\n}\n"
    : "+f"(d[0]),"+f"(d[1]),"+f"(d[2]),"+f"(d[3]),"+f"(d[4]),"+f"(d[5]),"+f"(d[6]),"+f"(d[7])
    : "r"(a0), "r"(a1), "r"(a2), "r"(a3), "r"(blo), "n"(OFF), "n"(BHI), "n"(ACC));
}

constexpr int A_R1 = 0;
constexpr int A_R2A = A_R1 + 2624, A_R2B = A_R2A + 768, A_R3A = A_R2B + 768, A_R3B = A_R3A + 528;
constexpr int A_K1024 = A_R3B + 528;
constexpr int A_W5 = A_K1024 + 16;
constexpr int A_W3 = A_W5 + 4096;
constexpr int A_W9 = A_W3 + 4112;
constexpr int A_W7 = A_W9 + 2048;
constexpr int A_V  = A_W7 + 2048;
constexpr int A_UB = A_V + 2048;
constexpr int A_STG = A_UB + 5248;
constexpr int A_Y2 = A_STG, A_Y3 = A_Y2 + 6528, A_YB = A_Y3 + 4352;
constexpr int A_REC = A_STG + 4 * 4352;
constexpr int A_CH = A_REC + 8192;
static_assert(A_W5 % 16 == 0 && A_UB % 16 == 0 && A_CH % 16 == 0 && A_YB + 4096 <= A_REC, "layout");

struct cf { float x, y; };
__device__ __forceinline__ cf cmul(cf a, cf b) { cf r; r.x = fmaf(a.x, b.x, -a.y * b.y); r.y = fmaf(a.x, b.y, a.y * b.x); return r; }
__device__ __forceinline__ cf cexp_l(float lr, float li, float l) {
  float mag; asm("ex2.approx.ftz.f32 %0, %1;" : "=f"(mag) : "f"((lr * l) * 1.4426950408889634f));
  const float th = li * l;
  const float k = (fmaf(th, 0.15915494f, 12582912.f)) - 12582912.f;
  float ph = fmaf(th, 0.15915494f, -k);
  ph = fmaf(th, 6.4206383e-9f, ph) * 6.2831853f;
  cf r; r.x = mag * __cosf(ph); r.y = mag * __sinf(ph); return r;
}
__device__ __forceinline__ void sts16(uint32_t a, uint32_t v) { asm volatile("st.shared.u16 [%0], %1;" ::"r"(a), "h"((uint16_t)v) : "memory"); }
__device__ __forceinline__ void sts32(uint32_t a, uint32_t v) { asm volatile("st.shared.u32 [%0], %1;" ::"r"(a), "r"(v) : "memory"); }
__device__ __forceinline__ void sts64(uint32_t a, uint32_t v0, uint32_t v1) { asm volatile("st.shared.v2.u32 [%0], {%1, %2};" ::"r"(a), "r"(v0), "r"(v1) : "memory"); }
__device__ __forceinline__ void sts128(uint32_t a, uint32_t v0, uint32_t v1, uint32_t v2, uint32_t v3) {
  asm volatile("st.shared.v4.u32 [%0], {%1, %2, %3, %4};" ::"r"(a), "r"(v0), "r"(v1), "r"(v2), "r"(v3) : "memory");
}
__device__ __forceinline__ uint32_t lds32(uint32_t a) { uint32_t v; asm volatile("ld.shared.u32 %0, [%1];" : "=r"(v) : "r"(a) : "memory"); return v; }
__device__ __forceinline__ uint4 lds128(uint32_t a) {
  uint4 v; asm volatile("ld.shared.v4.u32 {%0, %1, %2, %3}, [%4];" : "=r"(v.x), "=r"(v.y), "=r"(v.z), "=r"(v.w) : "r"(a) : "memory"); return v;
}
__device__ __forceinline__ void ldsm4(uint32_t* r, uint32_t a) {
  asm volatile("ldmatrix.sync.aligned.m8n8.x4.shared.b16 {%0,%1,%2,%3}, [%4];" : "=r"(r[0]), "=r"(r[1]), "=r"(r[2]), "=r"(r[3]) : "r"(a) : "memory");
}
__device__ __forceinline__ void mma16816(float* d, const uint32_t* a, uint32_t b0, uint32_t b1) {
  asm volatile("mma.sync.aligned.m16n8k16.row.col.f32.bf16.bf16.f32 {%0,%1,%2,%3}, {%4,%5,%6,%7}, {%8,%9}, {%0,%1,%2,%3};"
               : "+f"(d[0]), "+f"(d[1]), "+f"(d[2]), "+f"(d[3]) : "r"(a[0]), "r"(a[1]), "r"(a[2]), "r"(a[3]), "r"(b0), "r"(b1));
}
__device__ __forceinline__ uint32_t hsub2_bf(uint32_t a, uint32_t b) { uint32_t r; asm("sub.rn.bf16x2 %0, %1, %2;" : "=r"(r) : "r"(a), "r"(b)); return r; }
__device__ __forceinline__ void bar_sync(int id, int n) { asm volatile("bar.sync %0, %1;" ::"r"(id), "r"(n) : "memory"); }

template <int S> struct F1B { static constexpr int c = S / 4 + ((S & 3) == 3 ? 0 : 0), cc = (16 * S) / 64, ks = (64 * cc - (16 * S - 48)) / 16, off = (A_UB + 2 * ks * 656 + (9 - cc) * 16) / 16; };

template <int NS>
__device__ __forceinline__ void load_quads(uint32_t* q, uint32_t addr) {
#pragma unroll
  for (int i = 0; i < NS; i++) {
    q[4 * i] = lds32(addr + i * 64); q[4 * i + 1] = lds32(addr + i * 64 + 32);
    q[4 * i + 2] = i ? q[4 * i - 3] : lds32(addr - 32);
    q[4 * i + 3] = q[4 * i];
  }
#pragma unroll
  for (int i = 0; i < 4 * NS; i++) asm volatile("" : "+r"(q[i]));
}
template <int S0, int NS>
__device__ __forceinline__ void f1_steps(float (&acc)[16], const uint32_t* a, uint32_t blo) {
  if constexpr (NS > 0) {
    wgmma_rs32<F1B<S0>::off, 8, S0 != 0>(acc, a[0], a[1], a[2], a[3], blo);
    f1_steps<S0 + 1, NS - 1>(acc, a + 4, blo);
  }
}
template <int S0, int NS, int BASE, int FIRST>
__device__ __forceinline__ void s2_steps(float (&acc)[12], const uint32_t* a, uint32_t blo) {
  if constexpr (NS > 0) {
    wgmma_rs24<BASE / 16 + (112 - 16 * S0), 64, !(FIRST && S0 == 0)>(acc, a[0], a[1], a[2], a[3], blo);
    s2_steps<S0 + 1, NS - 1, BASE, FIRST>(acc, a + 4, blo);
  }
}
template <int S0, int NS, int BASE, int FIRST>
__device__ __forceinline__ void s3_steps(float (&acc)[8], const uint32_t* a, uint32_t blo) {
  if constexpr (NS > 0) {
    wgmma_rs16<BASE / 16 + (48 - 16 * S0), 64, !(FIRST && S0 == 0)>(acc, a[0], a[1], a[2], a[3], blo);
    s3_steps<S0 + 1, NS - 1, BASE, FIRST>(acc, a + 4, blo);
  }
}

__device__ __forceinline__ void phase_a(
        unsigned char* sm, const uint32_t bar_rec, const uint32_t ep_addr,
        const __nv_bfloat16* __restrict__ x, const uint32_t* __restrict__ are, const uint32_t* __restrict__ aim,
        const uint32_t* __restrict__ bre, const uint32_t* __restrict__ bim, const uint32_t* __restrict__ cre,
        const uint32_t* __restrict__ cim, const unsigned short* __restrict__ logdt, const unsigned short* __restrict__ dskip,
        const uint4* __restrict__ wgate, const uint4* __restrict__ wup, const uint4* __restrict__ wdown) {
  const uint32_t sb = s2u(sm);
  const int tid = threadIdx.x, wg = tid >> 7, warp = tid >> 5, lane = tid & 31, wq = warp & 3, t128 = tid & 127;
  const int blk = blockIdx.x;
  const bool conv = blk < 112;

  uint2 xr[4];
  {
    const uint2* p = (const uint2*)(x + (size_t)(blk * 16 + warp) * DM);
    xr[0] = __ldg(p + lane); xr[1] = __ldg(p + 32 + lane); xr[2] = __ldg(p + 64 + lane);
    xr[3] = lane < 16 ? __ldg(p + 96 + lane) : make_uint2(0, 0);
  }
  const int ch = conv ? blk * 4 + wg : 0;
  const uint32_t cb = sb + wg * A_CH;
  uint32_t prm[6];
  {
    const int i = ch * 128 + t128;
    prm[0] = __ldg(are + i); prm[1] = __ldg(aim + i); prm[2] = __ldg(bre + i); prm[3] = __ldg(bim + i); prm[4] = __ldg(cre + i); prm[5] = __ldg(cim + i);
  }
  const uint32_t ldt = __ldg(logdt + ch);
  uint32_t cnt0 = 0;
  if (tid == 0) cnt0 = __ldcg(&g_cnt1);
#pragma unroll
  for (int i = 0; i < 4; i++) if (i < 3 || t128 < (A_W5 + 1024) / 16 - 384) sts128(cb + (i * 128 + t128) * 16, 0, 0, 0, 0);
  if (t128 < 65) sts128(cb + (t128 < 64 ? A_W3 + t128 * 16 : A_W9), 0, 0, 0, 0);
  if (t128 < 72) sts128(cb + A_UB + (t128 / 9) * 656 + (t128 % 9) * 16, 0, 0, 0, 0);
  {
    float s = 0.f, q = 0.f;
#pragma unroll
    for (int i = 0; i < 4; i++) {
      const float a = bf_lo(xr[i].x), b = bf_hi(xr[i].x), c = bf_lo(xr[i].y), d = bf_hi(xr[i].y);
      s += (a + b) + (c + d);
      q = fmaf(a, a, q); q = fmaf(b, b, q); q = fmaf(c, c, q); q = fmaf(d, d, q);
    }
#pragma unroll
    for (int o = 16; o; o >>= 1) { s += __shfl_xor_sync(~0u, s, o); q += __shfl_xor_sync(~0u, q, o); }
    const float mean = s * (1.f / DM);
    const float var = fmaxf(fmaf(-mean, mean, q * (1.f / DM)), 0.f);
    const float rs = __frcp_rn(rbf(__fsqrt_rn(rbf(rbf(var) + 1e-5f))));
    const uint32_t mm = pack_bf16(mean, mean);
    const uint32_t tu = sb + A_REC + (warp >> 3) * A_CH + (warp & 7) * 912 + lane * 8, tx = tu + 2 * A_CH;
#pragma unroll
    for (int i = 0; i < 4; i++) {
      if (i < 3 || lane < 16) {
        const uint32_t d0 = hsub2_bf(xr[i].x, mm), d1 = hsub2_bf(xr[i].y, mm);
        sts64(tu + i * 256, pack_bf16(bf_lo(d0) * rs, bf_hi(d0) * rs), pack_bf16(bf_lo(d1) * rs, bf_hi(d1) * rs));
        sts64(tx + i * 256, xr[i].x, xr[i].y);
      }
    }
  }
  if (tid == 0) sts32(ep_addr, (cnt0 >> 7) + 1u);
  if (tid == 320) TR(0, 1);
  auto publish_rows = [&]() {
    bar_sync(5, 512);
    uint4* dst = g_ux + ((size_t)(warp * 8 + (lane >> 2)) * 128 + blk) * 4 + ((lane ^ (blk >> 1)) & 3);
#pragma unroll
    for (int i = 0; i < 4; i++) {
      if (i < 3 || warp < 8) {
        uint32_t r[4];
        asm volatile("ldmatrix.sync.aligned.m8n8.x4.trans.shared.b16 {%0,%1,%2,%3}, [%4];" : "=r"(r[0]), "=r"(r[1]), "=r"(r[2]), "=r"(r[3])
                     : "r"(sb + A_REC + (lane >> 3) * A_CH + (lane & 7) * 912 + (warp + 16 * i) * 16) : "memory");
        dst[i * 65536] = make_uint4(r[0], r[1], r[2], r[3]);
      }
    }
    if (warp != 0) asm volatile("bar.arrive 6, 512;" ::: "memory");
  };
  auto release_rows = [&]() {
    if (warp == 0) {
      bar_sync(6, 512);
      if (lane == 0) { asm volatile("red.release.gpu.global.add.u32 [%0], 1;" ::"l"(&g_cnt1) : "memory"); TR(0, 8); }
      __syncwarp();
    }
  };

  if (!conv) {
    publish_rows();
    release_rows();
    const int a = blk - 112, mat = a >> 3, j = a & 7;
    float s[8];
#pragma unroll
    for (int k = 0; k < 8; k++) s[k] = 0.f;
    if (lane < 28) {
      const uint4* src = (mat ? wup : wgate) + j * 28 + lane + (size_t)warp * 224;
#pragma unroll
      for (int hb = 0; hb < 2; hb++) {
        uint4 v[14];
#pragma unroll
        for (int r = 0; r < 14; r++) v[r] = __ldg(src + (size_t)(hb * 14 + r) * 16 * 224);
#pragma unroll
        for (int r = 0; r < 14; r++) {
          s[0] += bf_lo(v[r].x); s[1] += bf_hi(v[r].x); s[2] += bf_lo(v[r].y); s[3] += bf_hi(v[r].y);
          s[4] += bf_lo(v[r].z); s[5] += bf_hi(v[r].z); s[6] += bf_lo(v[r].w); s[7] += bf_hi(v[r].w);
        }
      }
      float4* red = (float4*)(sm + A_STG + warp * 896 + lane * 32);
      red[0] = make_float4(s[0], s[1], s[2], s[3]); red[1] = make_float4(s[4], s[5], s[6], s[7]);
    }
    bar_sync(5, 512);
    if (tid < 224) {
      float t = 0.f;
#pragma unroll
      for (int w = 0; w < 16; w++) t += *(const float*)(sm + A_STG + w * 896 + tid * 4);
      const float hi = rbf(t), mid = rbf(t - hi), lo = rbf(t - hi - mid);
      const int q = tid / 112, n = tid % 112 + 112 * mat;
      __nv_bfloat16* dst = (__nv_bfloat16*)(g_cimg + (j * 2 + q) * 224 + (n >> 3) * 8) + (n & 7);
      dst[0] = __float2bfloat16_rn(hi); dst[8] = __float2bfloat16_rn(mid); dst[16] = __float2bfloat16_rn(lo);
#pragma unroll
      for (int k = 3; k < 8; k++) dst[8 * k] = __float2bfloat16_rn(0.f);
    }
    if (tid == 320) TR(0, 10);
    return;
  }

  const int g = lane >> 2, t = lane & 3;
  const int wr = (wq + wg) & 3;
  uint4 wv[6];
  auto w_src = [&](int i) -> const uint4* {
    if (i < 4) return (blk < 56 ? wgate : wup) + (blk % 56) * 4 + (lane & 3) + (size_t)(i * 128 + warp * 8 + (lane >> 2)) * 224;
    const int it = warp + 16 * (i - 4);
    return wdown + (size_t)(blk * 16 + (it / 14) * 8 + (lane >> 2)) * 56 + (it % 14) * 4 + (lane & 3);
  };
  auto w_on = [&](int i) { return i == 3 ? warp < 8 : i == 5 ? warp < 12 : true; };
  {
    const uint32_t stg = cb + A_STG + wq * 4352;
    const float dt = rbf(expf(__uint_as_float(ldt << 16)));
    float lr[2], li[2];
    cf bq[2], b0[2], b4[2];
    uint32_t bf[48];
#pragma unroll
    for (int m = 0; m < 2; m++) {
      lr[m] = dt * (m ? bf_hi(prm[0]) : bf_lo(prm[0]));
      li[m] = dt * (m ? bf_hi(prm[1]) : bf_lo(prm[1]));
    }
    {
      cf b[2], z[2];
#pragma unroll
      for (int m = 0; m < 2; m++) {
        cf db, c;
        db.x = dt * (m ? bf_hi(prm[2]) : bf_lo(prm[2])); db.y = -dt * (m ? bf_hi(prm[3]) : bf_lo(prm[3]));
        c.x = m ? bf_hi(prm[4]) : bf_lo(prm[4]); c.y = -(m ? bf_hi(prm[5]) : bf_lo(prm[5]));
        b[m] = cmul(c, db);
        z[m] = cexp_l(lr[m], -li[m], 1.f);
        bq[m] = cexp_l(lr[m], -li[m], 256.f);
      }
#pragma unroll
      for (int i = 0; i < 8; i++) {
        sts64(stg + i * 272 + lane * 8, pack_bf16(b[0].x, b[0].y), pack_bf16(b[1].x, b[1].y));
        if (!(i & 1)) {
          cf e0 = cmul(b[0], bq[0]), e1 = cmul(b[1], bq[1]);
          sts64(stg + (8 + i / 2) * 272 + lane * 8, pack_bf16(e0.x, e0.y), pack_bf16(e1.x, e1.y));
          if (i == 0) { b0[0] = e0; b0[1] = e1; }
          if (i == 4) { b4[0] = e0; b4[1] = e1; }
        }
        if (i < 7) { b[0] = cmul(b[0], z[0]); b[1] = cmul(b[1], z[1]); }
        if (i == 1) publish_rows();
      }
#pragma unroll
      for (int i = 0; i < 7; i++) {
        b0[0] = cmul(b0[0], bq[0]); b0[1] = cmul(b0[1], bq[1]);
        sts64(stg + (i < 2 ? 12 + 2 * i : i - 2) * 272 + lane * 8, pack_bf16(b0[0].x, b0[0].y), pack_bf16(b0[1].x, b0[1].y));
        if (i < 2) {
          b4[0] = cmul(b4[0], bq[0]); b4[1] = cmul(b4[1], bq[1]);
          sts64(stg + (13 + 2 * i) * 272 + lane * 8, pack_bf16(b4[0].x, b4[0].y), pack_bf16(b4[1].x, b4[1].y));
        }
        if (i == 1) {
          __syncwarp();
#pragma unroll
          for (int n = 0; n < 2; n++)
#pragma unroll
            for (int k2 = 0; k2 < 4; k2++) ldsm4(bf + n * 16 + k2 * 4, stg + (n * 8 + (lane & 7)) * 272 + k2 * 64 + (lane >> 3) * 16);
          __syncwarp();
        }
      }
    }
    __syncwarp();
#pragma unroll
    for (int k2 = 0; k2 < 4; k2++) ldsm4(bf + 32 + k2 * 4, stg + (lane & 7) * 272 + k2 * 64 + (lane >> 3) * 16);
    release_rows();
    if (!(lane & 1)) {
#pragma unroll
      for (int i = 0; i < 6; i++) if (w_on(i)) asm volatile("prefetch.global.L2 [%0];" ::"l"(w_src(i)));
    }
    if (tid == 320) TR(0, 16);
    float c[6][4];
#pragma unroll
    for (int i = 0; i < 6; i++) { c[i][0] = 0.f; c[i][1] = 0.f; c[i][2] = 0.f; c[i][3] = 0.f; }
    cf p[2], v[2];
    p[0] = cexp_l(lr[0], li[0], 8.f); p[1] = cexp_l(lr[1], li[1], 8.f);
    v[0].x = 1.f; v[0].y = 0.f; v[1] = v[0];
#pragma unroll
    for (int mt = 0; mt < 2; mt++) {
      __syncwarp();
#pragma unroll
      for (int i = 0; i < 16; i++) {
        sts64(stg + i * 272 + lane * 8, pack_bf16(v[0].x, v[0].y), pack_bf16(v[1].x, v[1].y));
        if (mt == 0 && i == 0) { v[0] = p[0]; v[1] = p[1]; }
        else if (mt == 0 || i < 15) { v[0] = cmul(v[0], p[0]); v[1] = cmul(v[1], p[1]); }
      }
      __syncwarp();
      if (mt == 1 && tid == 160) {
        const uint32_t tgt = lds32(ep_addr) * 128u;
        uint32_t cv; int it = 0;
        do { asm volatile("ld.acquire.gpu.global.u32 %0, [%1];" : "=r"(cv) : "l"(&g_cnt1) : "memory"); } while ((int)(cv - tgt) < 0 && ++it < 200000);
        asm volatile("fence.proxy.async;" ::: "memory");
        TR(0, 9);
        mbar_expect(bar_rec, 32768);
        for (int c2 = 0; c2 < 4; c2++) bulk_ld(sb + c2 * A_CH + A_REC, g_ux + (size_t)(blk * 4 + c2) * 512, 8192, bar_rec);
      }
#pragma unroll
      for (int ks = 0; ks < 8; ks++) {
        uint32_t a[4];
        ldsm4(a, stg + (lane & 15) * 272 + ks * 32 + (lane >> 4) * 16);
#pragma unroll
        for (int n = 0; n < 3; n++) mma16816(c[n * 2 + mt], a, bf[n * 16 + ks * 2], bf[n * 16 + ks * 2 + 1]);
      }
    }
    __syncwarp();
#pragma unroll
    for (int i = 0; i < 6; i++)
      sts128(stg + i * 512 + lane * 16, __float_as_uint(c[i][0]), __float_as_uint(c[i][1]), __float_as_uint(c[i][2]), __float_as_uint(c[i][3]));
#pragma unroll
    for (int i = 0; i < 6; i++) if (w_on(i)) wv[i] = __ldg(w_src(i));
    bar_sync(1 + wg, 128);
    if (tid == 320) TR(0, 2);
#pragma unroll
    for (int rep = 0; rep < 2; rep++) {
      const int qd = rep ? 2 + wr : 3 - wr;
      if (rep == 0 || wr >= 2) {
        float s[4] = {0.f, 0.f, 0.f, 0.f};
#pragma unroll
        for (int w = 0; w < 4; w++) {
          uint4 u4 = lds128(cb + A_STG + w * 4352 + qd * 512 + lane * 16);
          s[0] += __uint_as_float(u4.x); s[1] += __uint_as_float(u4.y); s[2] += __uint_as_float(u4.z); s[3] += __uint_as_float(u4.w);
        }
#pragma unroll
        for (int hf = 0; hf < 2; hf++) {
          const int j = (qd & 1) * 16 + g + 8 * hf;
          const uint32_t pk = pack_bf16(s[2 * hf + 1], s[2 * hf]);
          const uint32_t v0 = pk >> 16, v1 = pk & 0xFFFFu, v00 = v0 * 0x10001u;
          if (rep == 1) {
            if (t < 2) {
#pragma unroll
              for (int e = 0; e < 2; e++) {
                const int lam = 128 + 32 * (2 * t + e) + j, mu = lam >> 1;
                const uint32_t val = e ? v1 : v0;
                uint32_t a = cb + ((lam & 1) ? A_R3B : A_R3A) + mu * 4;
                if (lam == 128) { a = cb + A_R2A + 128 * 4; sts32(cb + A_K1024, val << 16); }
                sts16(a, val); sts16(a + 6, val);
              }
            } else if (t == 2 && j == 0) { sts16(cb + A_R3A + 128 * 4, v0); }
          } else if (qd < 2) {
            const uint32_t a = cb + A_R1 + (62 + 8 * j + 2 * t) * 4;
            sts16(a, v0); sts32(a + 4, pk); sts16(a + 10, v1);
          } else if (t < 2) {
            const int L = 256 + 8 * j + 4 * t;
            const uint32_t a = cb + A_R1 + (62 + L) * 4;
            if (L > 256) { sts16(a - 4, v0); sts32(a, v00); } else sts16(a, v0);
            sts32(a + 4, v00); sts32(a + 8, pk); sts16(a + 14, v1);
          } else {
            const int mu = 64 + 32 * (t - 2) + j;
            if (mu == 64) {
              const uint32_t a = cb + A_R1 + (62 + 512) * 4;
              sts16(a - 4, v0); sts32(a, v00); sts32(a + 4, v00); sts32(a + 8, v00); sts16(a + 14, v0);
            } else { sts16(cb + A_R2A + mu * 4, v0); sts16(cb + A_R2A + mu * 4 + 6, v0); }
            sts16(cb + A_R2B + mu * 4, v1); sts16(cb + A_R2B + mu * 4 + 6, v1);
          }
        }
      }
    }
  }
  {
    const int ngg = (blk % 56) * 4 + (lane & 3), j = ngg / 28, q = (ngg % 28) / 14, ng = ngg % 14 + (blk < 56 ? 0 : 14);
    uint4* dst = g_wimg + (size_t)j * 37632 + q * 14 * 896 + ng * 32 + (warp >> 2) * 896 + (warp & 3) * 8 + (lane >> 2);
#pragma unroll
    for (int i = 0; i < 4; i++) if (w_on(i)) dst[i * 4 * 896] = wv[i];
#pragma unroll
    for (int i = 4; i < 6; i++) {
      const int it = warp + 16 * (i - 4), n2 = (it % 14) * 4 + (lane & 3), k = (blk % 7) * 16 + (it / 14) * 8 + (lane >> 2);
      if (w_on(i)) g_wimg[(size_t)(blk / 14) * 37632 + 25088 + ((n2 / 7) * 2 + (blk / 7) % 2) * 784 + (n2 % 7) * 112 + k] = wv[i];
    }
  }
  if (tid == 320) TR(0, 3);

  const int bk = wr * 32 + lane;
  uint32_t xt[8], ud[8];
  {
    mbar_wait(bar_rec, 0);
    if (tid == 320) TR(0, 4);
    uint4 r[4];
#pragma unroll
    for (int i = 0; i < 4; i++) r[i] = lds128(cb + A_REC + bk * 64 + ((i ^ (bk >> 1)) & 3) * 16);
    const uint32_t ua = cb + A_UB + ((2 * bk) & 7) * 656 + ((bk >> 2) + 9) * 16;
    sts128(ua, r[0].x, r[1].x, r[2].x, r[3].x);
    sts128(ua + 656, r[0].y, r[1].y, r[2].y, r[3].y);
    if (bk <= 96) {
      const bool neg = bk == 96;
      const int bp = neg ? -1 : bk;
      uint32_t h[4];
      h[0] = lds32(cb + A_REC + ((bp - 1) & 127) * 64 + ((2 ^ ((bp - 1) >> 1)) & 3) * 16 + 4);
      h[1] = lds32(cb + A_REC + ((bp - 1) & 127) * 64 + ((3 ^ ((bp - 1) >> 1)) & 3) * 16 + 4);
      h[2] = lds32(cb + A_REC + (bp + 1) * 64 + ((0 ^ ((bp + 1) >> 1)) & 3) * 16);
      h[3] = lds32(cb + A_REC + (bp + 1) * 64 + ((1 ^ ((bp + 1) >> 1)) & 3) * 16);
      if (bp <= 0) { h[0] = 0; h[1] = 0; }
      const uint32_t wd[12] = {h[0], h[1], neg ? 0 : r[0].x, neg ? 0 : r[1].x, neg ? 0 : r[2].x, neg ? 0 : r[3].x,
                               neg ? 0 : r[0].y, neg ? 0 : r[1].y, neg ? 0 : r[2].y, neg ? 0 : r[3].y, h[2], h[3]};
      float P[25];
      P[0] = 0.f;
#pragma unroll
      for (int i = 0; i < 12; i++) { P[2 * i + 1] = P[2 * i] + bf_lo(wd[i]); P[2 * i + 2] = P[2 * i + 1] + bf_hi(wd[i]); }
#define WIN(i, hw) (P[(i) + 5 + (hw)] - P[(i) + 4 - (hw)])
#define WPK(i, hw) pack_bf16(WIN(i, hw), WIN((i) + 1, hw))
      const int tp = 2 * bp;
      const uint32_t a3 = cb + A_W3 + (tp + 64) * 16 + 8, a5 = cb + A_W5 + (tp + 64) * 16;
      if (!neg) sts64(a3, WPK(0, 1), WPK(2, 1));
      if (!neg) sts128(a3 + 8, WPK(4, 1), WPK(6, 1), WPK(8, 1), WPK(10, 1));
      sts64(a3 + 24, WPK(12, 1), WPK(14, 1));
      sts128(a5, WPK(0, 2), WPK(2, 2), WPK(4, 2), WPK(6, 2));
      sts128(a5 + 16, WPK(8, 2), WPK(10, 2), WPK(12, 2), WPK(14, 2));
      if (bp < 64) {
        if (!neg) sts128(cb + A_W7 + 1024 + bp * 16, WPK(0, 3), WPK(2, 3), WPK(4, 3), WPK(6, 3));
        if (bp < 63) {
          sts128(cb + A_W7 + (bp + 1) * 16, WPK(8, 3), WPK(10, 3), WPK(12, 3), WPK(14, 3));
          sts128(cb + A_W9 + (bp + 1) * 16, WPK(0, 4), WPK(2, 4), WPK(4, 4), WPK(6, 4));
          sts128(cb + A_W9 + 1024 + (bp + 1) * 16, WPK(8, 4), WPK(10, 4), WPK(12, 4), WPK(14, 4));
        }
        if (!neg) {
#define VPK(i) pack_bf16(P[(i) + 2] - P[i], P[(i) + 3] - P[(i) + 1])
          sts128(cb + A_V + bp * 32, VPK(0), VPK(2), VPK(4), VPK(6));
          sts128(cb + A_V + bp * 32 + 16, VPK(8), VPK(10), VPK(12), VPK(14));
        }
      }
    }
  }
  asm volatile("fence.proxy.async.shared::cta;" ::: "memory");
  bar_sync(1 + wg, 128);
  if (tid == 320) TR(0, 5);

  {
    const uint32_t cbu = __shfl_sync(~0u, cb, 0);
    const uint32_t blo_k = ((cbu & 0x3FFFF) >> 4) | (41u << 16);
    const uint32_t blo_n = ((cbu & 0x3FFFF) >> 4) | (8u << 16);
    const uint32_t tb = cb + (16 * wq + g - 2 * t) * 4;
    float y1[16], y2[12], y3[8];
    const uint32_t dk16 = __ldg(dskip + ch);
    uint32_t qa[32], qb[32];
    const uint32_t t1 = tb + A_R1 + (62 - 48) * 4;
    load_quads<4>(qa, tb + A_R3A + 17 * 4); load_quads<4>(qa + 16, tb + A_R3B + 16 * 4);
    wg_fence();
    s3_steps<0, 4, A_W9, 1>(y3, qa, blo_n); s3_steps<0, 4, A_W7, 0>(y3, qa + 16, blo_n);
    wg_commit();
    load_quads<8>(qb, tb + A_R2A + 16 * 4);
    wg_fence(); s2_steps<0, 8, A_W5, 1>(y2, qb, blo_n); wg_commit();
    wg_wait<1>(); load_quads<8>(qa, tb + A_R2B + 16 * 4);
    wg_fence(); s2_steps<0, 8, A_W3, 0>(y2, qa, blo_n); wg_commit();
    wg_wait<1>(); load_quads<8>(qb, t1);
    wg_fence(); f1_steps<0, 8>(y1, qb, blo_k); wg_commit();
    wg_wait<1>(); load_quads<8>(qa, t1 + 8 * 64);
    wg_fence(); f1_steps<8, 8>(y1, qa, blo_k); wg_commit();
    reg_fence(y2); reg_fence(y3);
    if (tid == 320) TR(0, 18);
    {
      const float k1024 = __uint_as_float(lds32(cb + A_K1024));
#pragma unroll
      for (int i = 0; i < 2; i++)
#pragma unroll
        for (int hf = 0; hf < 2; hf++) {
          const int idx = 16 * (16 * wq + g + 8 * hf) + 8 * i + 2 * t;
          const uint32_t vv = lds32(cb + A_V + idx * 2);
          sts64(cb + A_Y3 + (idx + 4 * (idx >> 6)) * 4, __float_as_uint(fmaf(k1024, bf_lo(vv), y3[4 * i + 2 * hf])),
                __float_as_uint(fmaf(k1024, bf_hi(vv), y3[4 * i + 2 * hf + 1])));
        }
#pragma unroll
      for (int i = 0; i < 3; i++)
#pragma unroll
        for (int hf = 0; hf < 2; hf++) {
          const int idx = 512 * i + 8 * (16 * wq + g + 8 * hf) + 2 * t;
          sts64(cb + A_Y2 + (idx + 4 * (idx >> 6)) * 4, __float_as_uint(y2[4 * i + 2 * hf]), __float_as_uint(y2[4 * i + 2 * hf + 1]));
        }
    }
    wg_wait<1>(); load_quads<8>(qb, t1 + 16 * 64);
    wg_fence(); f1_steps<16, 8>(y1, qb, blo_k); wg_commit();
    wg_wait<1>(); load_quads<8>(qa, t1 + 24 * 64);
    wg_fence(); f1_steps<24, 8>(y1, qa, blo_k); wg_commit();
    wg_wait<1>(); load_quads<5>(qb, t1 + 32 * 64);
    wg_fence(); f1_steps<32, 5>(y1, qb, blo_k); wg_commit();
    bar_sync(1 + wg, 128);
    float ex[12];
#pragma unroll
    for (int i = 1; i < 4; i++)
#pragma unroll
      for (int k = 0; k < 4; k++) {
        const int aa = 8 * i + 2 * t + (k & 1), b = 16 * wq + g + 8 * (k >> 1);
        float e = __uint_as_float(lds32(cb + A_Y2 + ((aa - 8) * 68 + b) * 4));
        if (i >= 2) e += __uint_as_float(lds32(cb + A_Y3 + ((aa - 16) * 68 + b) * 4));
        ex[4 * (i - 1) + k] = e;
      }
    {
      const uint32_t dk = dk16 * 0x10001u;
#pragma unroll
      for (int i = 0; i < 4; i++) {
        const uint4 r = lds128(cb + A_REC + bk * 64 + ((i ^ (bk >> 1)) & 3) * 16);
        ud[i] = hmul2_bf(r.x, dk); ud[4 + i] = hmul2_bf(r.y, dk); xt[i] = r.z; xt[4 + i] = r.w;
      }
    }
    wg_wait<0>();
    reg_fence(y1);
    if (tid == 320) TR(0, 6);
#pragma unroll
    for (int i = 0; i < 12; i++) y1[4 + i] += ex[i];
#pragma unroll
    for (int i = 0; i < 2; i++) {
      const int mi = lane >> 3, aa = 8 * (2 * i + (mi >> 1)) + (lane & 7);
      asm volatile("stmatrix.sync.aligned.m8n8.x4.trans.shared.b16 [%0], {%1,%2,%3,%4};"
                   ::"r"(cb + A_YB + aa * 128 + (((2 * wq + (mi & 1)) ^ (lane & 7)) << 4)),
                     "r"(pack_bf16(y1[8 * i], y1[8 * i + 1])), "r"(pack_bf16(y1[8 * i + 2], y1[8 * i + 3])),
                     "r"(pack_bf16(y1[8 * i + 4], y1[8 * i + 5])), "r"(pack_bf16(y1[8 * i + 6], y1[8 * i + 7])) : "memory");
    }
  }
  bar_sync(1 + wg, 128);
#pragma unroll
  for (int c = 0; c < 2; c++) {
    const int tau = 2 * bk + c, r = ch & 7;
    const uint4 y = lds128(cb + A_YB + (tau >> 3) * 128 + (((tau ^ (tau >> 3)) & 7) << 4));
    g_himg[(size_t)(tau >> 4) * 7168 + (ch >> 3) * 128 + ((tau >> 3) & 1) * 64 + r * 8 + ((tau & 7) ^ r)] =
        make_uint4(hadd2_bf(xt[4 * c], hadd2_bf(y.x, ud[4 * c])), hadd2_bf(xt[4 * c + 1], hadd2_bf(y.y, ud[4 * c + 1])),
                   hadd2_bf(xt[4 * c + 2], hadd2_bf(y.z, ud[4 * c + 2])), hadd2_bf(xt[4 * c + 3], hadd2_bf(y.w, ud[4 * c + 3])));
  }
  if (tid == 320) TR(0, 7);
}

constexpr int B_SA = 0, B_RING = 114688, B_SLOT = 14848, B_NSLOT = 7;
constexpr int B_CS = B_RING + B_NSLOT * B_SLOT;
constexpr int B_RED = B_CS + 7168;
constexpr int B_BAR = B_RED + 256;
constexpr int B_SMEM = B_BAR + 1024, A_SMEM = 4 * A_CH + 64;

__device__ __forceinline__ uint32_t mapa(uint32_t a, uint32_t r) { uint32_t o; asm("mapa.shared::cluster.u32 %0, %1, %2;" : "=r"(o) : "r"(a), "r"(r)); return o; }
template <class T> __device__ __forceinline__ T* pin(T* p) { asm volatile("" : "+l"(p)); return p; }
__device__ __forceinline__ uint32_t pin(uint32_t v) { asm volatile("" : "+r"(v)); return v; }
template <int Q, int ST>
__device__ __forceinline__ void g1_stage(float (&acc)[116], uint32_t alo, uint32_t blo, uint32_t bar_full, uint32_t bar_h) {
  constexpr int s = Q * 14 + ST, sl = s % B_NSLOT;
  if (Q == 0) mbar_wait(bar_h + 8 * ST, 0);
  mbar_wait(bar_full + 8 * sl, (s / B_NSLOT) & 1);
  wg_fence();
  if (Q == 0) {
    wgmma_ss232<(2 * ST) * 256, 0x40000080u, (sl * B_SLOT) / 16, 32, ST != 0>(acc, alo, blo);
    wgmma_ss232<(2 * ST + 1) * 256, 0x40000080u, (sl * B_SLOT + 256) / 16, 32, 1>(acc, alo, blo);
  } else {
    wgmma_ss224<(2 * ST) * 256, 0x40000080u, (sl * B_SLOT) / 16, 32, ST != 0>(*(float(*)[112])acc, alo, blo);
    wgmma_ss224<(2 * ST + 1) * 256, 0x40000080u, (sl * B_SLOT + 256) / 16, 32, 1>(*(float(*)[112])acc, alo, blo);
  }
}

__global__ void __launch_bounds__(512, 1)
k_front(const __nv_bfloat16* __restrict__ x, const uint32_t* __restrict__ are, const uint32_t* __restrict__ aim,
        const uint32_t* __restrict__ bre, const uint32_t* __restrict__ bim, const uint32_t* __restrict__ cre,
        const uint32_t* __restrict__ cim, const unsigned short* __restrict__ logdt, const unsigned short* __restrict__ dskip,
        const uint4* __restrict__ wgate, const uint4* __restrict__ wup, const uint4* __restrict__ wdown) {
  extern __shared__ __align__(1024) unsigned char sm[];
  const uint32_t bar_rec = s2u(sm) + 4 * A_CH;
  if (threadIdx.x == 320) TR(0, 0);
  asm volatile("griddepcontrol.launch_dependents;");
  if (threadIdx.x == 160) { mbar_init(bar_rec, 1); asm volatile("fence.mbarrier_init.release.cluster;" ::: "memory"); }
  phase_a(sm, bar_rec, bar_rec + 8, x, are, aim, bre, bim, cre, cim, logdt, dskip, wgate, wup, wdown);
}

__global__ void __cluster_dims__(2, 1, 1) __launch_bounds__(384, 1) k_ffn(__nv_bfloat16* __restrict__ out) {
  extern __shared__ __align__(1024) unsigned char sm[];
  const uint32_t sb = s2u(sm);
  const int tid = threadIdx.x, wg = tid >> 7, warp = tid >> 5, lane = tid & 31;
  const uint32_t bar_full = sb + B_BAR, bar_empty = bar_full + 64, bar_h = bar_full + 128, bar_cs = bar_full + 240,
                 bar_g2 = bar_full + 248, bar_in = bar_full + 256, bar_hh = bar_full + 304, bar_afree = bar_full + 336, bar_out = bar_full + 344;
  if (tid == 0) {
    TR(1, 0);
    for (int i = 0; i < B_NSLOT; i++) { mbar_init(bar_full + 8 * i, 1); mbar_init(bar_empty + 8 * i, 2); }
    asm volatile("fence.mbarrier_init.release.cluster;" ::: "memory");
  } else if (tid == 32) {
    for (int i = 0; i < 14; i++) mbar_init(bar_h + 8 * i, 1);
    asm volatile("fence.mbarrier_init.release.cluster;" ::: "memory");
  } else if (tid == 64) {
    mbar_init(bar_cs, 1);
    mbar_init(bar_g2, 4);
    for (int i = 0; i < 6; i++) mbar_init(bar_in + 8 * i, 1);
    for (int i = 0; i < 4; i++) { mbar_init(bar_hh + 8 * i, 1); mbar_expect(bar_hh + 8 * i, 14336); }
    mbar_init(bar_afree, 4);
    for (int i = 0; i < 6; i++) mbar_init(bar_out + 8 * i, 128);
    asm volatile("fence.mbarrier_init.release.cluster;" ::: "memory");
  } else if (tid >= 128 && tid < 352) {
    sts128(sb + B_RING + ((tid - 128) >> 5) * B_SLOT + 14336 + (tid & 31) * 16, 0x3F803F80u, 0x3F803F80u, 0x3F803F80u, 0x3F803F80u);
  }
  asm volatile("fence.proxy.async.shared::cta;" ::: "memory");
  __syncthreads();
  asm volatile("barrier.cluster.arrive.relaxed.aligned;" ::: "memory");
  const int rank = blockIdx.x & 1, rt = blockIdx.x >> 3, j = blockIdx.x & 7, p = j >> 1, cg = 4 * rank + p;
  const int wq = warp & 3, t128 = tid & 127, g = lane >> 2, t = lane & 3;
  uint32_t ep, tag;
  auto load_ep = [&]() { asm volatile("ld.relaxed.gpu.global.u32 %0, [%1];" : "=r"(ep) : "l"(&g_cnt1) : "memory"); };
  auto a_slot = [&](int i, int own) { return B_SA + (i + (i >= own)) * 14336; };
  auto in_addr = [&](int q, int cw) { return sb + a_slot(4 + q, cg) + cw * 1792; };
  auto out_addr = [&](int cc, int w) { return sb + a_slot((cc & 2) + w, cg) + (cc & 1) * 7168; };
  auto in_cta = [&](int q) { return rt * 8 + ((p + 3 - q) & 3) * 2 + rank; };
  auto in_src = [&](int q, int cw) { return g_part + (size_t)(in_cta(q) * 3 + q) * 896 + cw * 112; };
  auto add_in = [&](float (&sum)[28], int q, int cw) {
    const uint32_t a = in_addr(q, cw);
    const uint4 v0 = lds128(a + lane * 16), v1 = lds128(a + 512 + lane * 16), v2 = lds128(a + 1024 + lane * 16);
    uint32_t in[14] = {v0.x, v0.y, v0.z, v0.w, v1.x, v1.y, v1.z, v1.w, v2.x, v2.y, v2.z, v2.w, 0, 0};
    asm volatile("ld.shared.v2.u32 {%0, %1}, [%2];" : "=r"(in[12]), "=r"(in[13]) : "r"(a + 1536 + lane * 8) : "memory");
    int it = 0;
    while ((((in[3] ^ tag) | (in[7] ^ tag) | (in[11] ^ tag) | (in[13] ^ tag)) & 0x10000u) && ++it < 400000) {
      const uint4* gs = pin(in_src(q, cw));
#pragma unroll
      for (int i = 0; i < 3; i++) ld128(gs + i * 32 + lane, in + 4 * i);
      asm volatile("{\n.reg .b64 v;\nld.relaxed.gpu.global.b64 v, [%2];\nmov.b64 {%0, %1}, v;\n}"
                   : "=r"(in[12]), "=r"(in[13]) : "l"((const uint2*)(gs + 96) + lane) : "memory");
    }
#pragma unroll
    for (int i = 0; i < 14; i++) { sum[2 * i] += bf_lo(in[i]); sum[2 * i + 1] += bf_hi(in[i]); }
  };
  auto w_issue = [&](int s) {
    const char* wsrc = (const char*)g_wimg + (size_t)j * 602112;
    const int slot = s % B_NSLOT;
    const uint32_t dst = sb + B_RING + slot * B_SLOT, fb = bar_full + 8 * slot;
    if (s < 28) {
      mbar_expect(fb, 14336);
      bulk_ld(dst, wsrc + s * 14336, 14336, fb);
    } else {
      const int i = s - 28;
      const int ci = i < 3 ? 0 : i < 6 ? 1 : i < 8 ? i - 6 : i < 12 ? 2 : 3;
      const int kp = i < 3 ? i : i < 6 ? i - 3 : i < 8 ? 3 : (i & 3);
      mbar_expect(fb, 12544);
      bulk_ld(dst, (const char*)g_wimg + (size_t)(j ^ (kp >> 1)) * 602112 + 401408 + ((4 * rank + ((p + 1 + ci) & 3)) * 2 + (kp & 1)) * 12544, 12544, fb);
    }
  };

  if (wg == 2) {
    asm volatile("setmaxnreg.dec.sync.aligned.u32 40;");
    asm volatile("barrier.cluster.wait.aligned;" ::: "memory");
    asm volatile("griddepcontrol.wait;" ::: "memory");
    if (warp == 8) {
      if (lane == 0) {
        TR(1, 1);
        for (int s = 0; s < 44; s++) {
          if (s >= B_NSLOT) mbar_wait(bar_empty + 8 * (s % B_NSLOT), (s / B_NSLOT - 1) & 1);
          w_issue(s);
        }
      }
    } else if (warp == 9) {
      if (lane == 0) {
        const char* hsrc = (const char*)g_himg + (size_t)rt * 114688;
        for (int i = 0; i < 14; i++) {
          mbar_expect(bar_h + 8 * i, 8192);
          bulk_ld_mc(sb + B_SA + i * 8192 + rank * 4096, hsrc + i * 8192 + rank * 4096, 4096, bar_h + 8 * i);
        }
        mbar_expect(bar_cs, 7168);
        bulk_ld(sb + B_CS, g_cimg + j * 448, 7168, bar_cs);
      }
      __syncwarp();
      load_ep(); ep >>= 7;
      const int lq = (lane >> 1) & 3, lcw = (lane & 1) * 4;
      const uint32_t* fl = g_flag + in_cta(lq) * 8 + (lane & 7);
      bool todo = lane < 6, live = false;
      int it = 0;
      while (__any_sync(~0u, todo) && ++it < 400000) {
        if (!live) { __nanosleep(400); live = mbar_test(bar_g2, 0); }
        if (todo) {
          uint32_t w;
          asm volatile("ld.relaxed.gpu.global.u32 %0, [%1];" : "=r"(w) : "l"(fl) : "memory");
          if (live && w == ep) {
            mbar_expect(bar_in + 8 * lane, 7168);
            bulk_ld(in_addr(lq, lcw), in_src(lq, lcw), 7168, bar_in + 8 * lane);
            todo = false;
            if (lane & 1) TR(1, 24 + lq);
          }
        }
      }
    } else {
      const int t64 = tid - 320;
      load_ep();
      const int r = (lane >> 1) & 7, c = (j & 3) * 2 + (lane & 1);
      const uint32_t src = sb + B_SA + (t64 >> 4) * 2048 + (j >> 2) * 1024 + r * 128 + ((c ^ r) << 4);
      float a[16];
#pragma unroll
      for (int k = 0; k < 16; k++) a[k] = 0.f;
#pragma unroll 1
      for (int i = 0; i < 14; i++) {
        mbar_wait(bar_h + 8 * i, 0);
        uint4 v = lds128(src + i * 8192);
        float e[8] = {bf_lo(v.x), bf_hi(v.x), bf_lo(v.y), bf_hi(v.y), bf_lo(v.z), bf_hi(v.z), bf_lo(v.w), bf_hi(v.w)};
#pragma unroll
        for (int k = 0; k < 8; k++) { a[2 * k] += e[k]; a[2 * k + 1] = fmaf(e[k], e[k], a[2 * k + 1]); }
        __nanosleep(160);
      }
      __syncwarp();
      if (lane == 0) { mbar_arrive(bar_g2); asm volatile("mbarrier.arrive.shared::cluster.b64 _, [%0];" ::"r"(mapa(bar_afree, rank ^ 1)) : "memory"); }
#pragma unroll
      for (int rd = 0; rd < 4; rd++) {
        const int n = 8 >> rd;
        const bool up = lane & (2 * n);
#pragma unroll
        for (int k = 0; k < 8; k++) {
          if (k < n) {
            float keep = up ? a[k + n] : a[k], give = up ? a[k] : a[k + n];
            a[k] = keep + __shfl_xor_sync(~0u, give, 2 * n);
          }
        }
      }
      float* red = (float*)(sm + B_RED);
      red[(warp & 1) * 32 + (lane & 1) * 16 + (lane >> 1)] = a[0];
      bar_sync(1, 64);
      if (t64 < 16) {
        float mean = (red[2 * t64] + red[32 + 2 * t64]) * (1.f / DM);
        float var = fmaxf(fmaf(-mean, mean, (red[2 * t64 + 1] + red[33 + 2 * t64]) * (1.f / DM)), 0.f);
        float rs = __frcp_rn(rbf(__fsqrt_rn(rbf(rbf(var) + 1e-5f))));
        asm volatile("st.relaxed.gpu.global.u32 [%0], %1;"
                     ::"l"(g_stat2 + rt * 128 + j * 16 + t64), "r"((__float_as_uint(rs * rs) & ~1u) | ((ep >> 7) & 1u)) : "memory");
      }
      if (t64 == 0) TR(1, 2);
      if (lane == 0) {
        const int w = warp & 1;
        for (int cc = 0; cc < 3; cc++) {
          mbar_wait(bar_out + 8 * (cc * 2 + w), 0);
          asm volatile("cp.async.bulk.global.shared::cta.bulk_group [%0], [%1], 7168;"
                       ::"l"(g_part + (size_t)(blockIdx.x * 3 + cc) * 896 + w * 448), "r"(out_addr(cc, w)) : "memory");
          asm volatile("cp.async.bulk.commit_group;" ::: "memory");
          asm volatile("cp.async.bulk.wait_group 0;" ::: "memory");
          asm volatile("st.relaxed.gpu.global.u32 [%0], %1;" ::"l"(g_flag + blockIdx.x * 8 + cc * 2 + w), "r"(ep >> 7) : "memory");
          if (w) TR(1, 27 + cc);
        }
      }
    }
  } else {
    asm volatile("setmaxnreg.inc.sync.aligned.u32 232;");
    asm volatile("barrier.cluster.wait.aligned;" ::: "memory");
    uint32_t hh[56];
    const bool relt = t128 == 0;
    auto release = [&](int sl) { if (relt) mbar_arrive(bar_empty + 8 * sl); };
    auto send_hh = [&](int q) {
      const uint32_t da = mapa(sb + a_slot(2 * q + wg, cg ^ 4) + t128 * 16, rank ^ 1), db = mapa(bar_hh + 8 * (2 * q + wg), rank ^ 1);
#pragma unroll
      for (int i = 0; i < 7; i++)
        asm volatile("st.async.weak.shared::cluster.mbarrier::complete_tx::bytes.v4.b32 [%0], {%1, %2, %3, %4}, [%5];"
                     ::"r"(da + i * 2048), "r"(hh[28 * q + 4 * i]), "r"(hh[28 * q + 4 * i + 1]),
                       "r"(hh[28 * q + 4 * i + 2]), "r"(hh[28 * q + 4 * i + 3]), "r"(db) : "memory");
    };
    const uint32_t alo = __shfl_sync(~0u, ((sb + B_SA + wg * 1024) & 0x3FFFF) >> 4, 0);
    const uint32_t blo = (((sb + B_RING) & 0x3FFFF) >> 4) | (8u << 16);
    const uint32_t clo = ((sb + B_CS) & 0x3FFFF) >> 4;
    uint32_t nm0, nm1;
    if (wg == 1) bar_sync(3, 256);
#define G1S(Q, ST) do { g1_stage<Q, ST>(acc, alo, blo, bar_full, bar_h); wg_commit(); \
      if (ST > 0) { wg_wait<1>(); release((Q * 14 + ST - 1) % B_NSLOT); } } while (0)
#define G1HH(Q) do { \
      _Pragma("unroll") \
      for (int i = 0; i < 28; i++) hh[28 * Q + i] = pack_bf16(acc[2 * i] * acc[56 + 2 * i], acc[2 * i + 1] * acc[57 + 2 * i]); \
    } while (0)
    {
      float acc[116];
      G1S(0, 0);
      if (tid == 0) TR(1, 3);
      G1S(0, 1);
      if (wg == 0) asm volatile("bar.arrive 3, 256;" ::: "memory");
      G1S(0, 2); G1S(0, 3); G1S(0, 4); G1S(0, 5); G1S(0, 6); G1S(0, 7); G1S(0, 8); G1S(0, 9); G1S(0, 10); G1S(0, 11); G1S(0, 12);
      G1S(0, 13);
      if (tid == 0) TR(1, 4);
      mbar_wait(bar_cs, 0);
      wg_wait<0>(); reg_fence(acc); release(13 % B_NSLOT);
      {
        const uint32_t msk = t == 0 ? 0xFFFFFFFFu : t == 1 ? 0xFFFFu : 0u;
        const float a = acc[112] * (-1.f / DM), b = acc[114] * (-1.f / DM);
        nm0 = pack_bf16(a, a) & msk; nm1 = pack_bf16(b, b) & msk;
      }
      wg_fence();
      wgmma_rs224<0, 8, 1>(*(float(*)[112])acc, nm0, nm1, 0u, 0u, clo);
      wg_commit(); wg_wait<0>(); reg_fence(acc);
      G1HH(0);
      if (tid == 0) TR(1, 5);
      G1S(1, 0); G1S(1, 1); G1S(1, 2); G1S(1, 3); G1S(1, 4); G1S(1, 5); G1S(1, 6); G1S(1, 7); G1S(1, 8); G1S(1, 9);
      if (relt) asm volatile("mbarrier.arrive.shared::cluster.b64 _, [%0];" ::"r"(mapa(bar_afree, rank ^ 1)) : "memory");
      G1S(1, 10); G1S(1, 11);
      G1S(1, 12);
      mbar_wait(bar_afree, 0);
      send_hh(0);
      load_ep();
      g1_stage<1, 13>(acc, alo, blo, bar_full, bar_h);
      wgmma_rs224<224, 8, 1>(*(float(*)[112])acc, nm0, nm1, 0u, 0u, clo);
      wg_commit(); wg_wait<1>(); release(26 % B_NSLOT);
      wg_wait<0>(); reg_fence(acc); release(27 % B_NSLOT);
      if (t128 == 0) mbar_arrive(bar_g2);
      G1HH(1);
      if (tid == 0) TR(1, 6);
    }
    float accA[28], accB[28], accC[28];
    uint32_t ph0[28], ph1[28];
    ep = pin(ep >> 7); tag = pin((ep & 1u) << 16);
#define ISSUE(acc, I, a, FIRST) do { \
      constexpr int s_ = 28 + (I), sl_ = s_ % B_NSLOT; \
      mbar_wait(bar_full + 8 * sl_, (s_ / B_NSLOT) & 1); \
      wg_fence(); \
      wgmma_rs56<(sl_ * B_SLOT + 0 * 256) / 16, 112, !(FIRST)>(acc, (a)[0], (a)[1], (a)[2], (a)[3], blo); \
      wgmma_rs56<(sl_ * B_SLOT + 1 * 256) / 16, 112, 1>(acc, (a)[4], (a)[5], (a)[6], (a)[7], blo); \
      wgmma_rs56<(sl_ * B_SLOT + 2 * 256) / 16, 112, 1>(acc, (a)[8], (a)[9], (a)[10], (a)[11], blo); \
      wgmma_rs56<(sl_ * B_SLOT + 3 * 256) / 16, 112, 1>(acc, (a)[12], (a)[13], (a)[14], (a)[15], blo); \
      wgmma_rs56<(sl_ * B_SLOT + 4 * 256) / 16, 112, 1>(acc, (a)[16], (a)[17], (a)[18], (a)[19], blo); \
      wgmma_rs56<(sl_ * B_SLOT + 5 * 256) / 16, 112, 1>(acc, (a)[20], (a)[21], (a)[22], (a)[23], blo); \
      wgmma_rs56<(sl_ * B_SLOT + 6 * 256) / 16, 112, 1>(acc, (a)[24], (a)[25], (a)[26], (a)[27], blo); \
      wg_commit(); } while (0)
    auto rel = [&](int i) { release((28 + i) % B_NSLOT); };
    auto tg = [&](uint32_t v) { return (v & 0xFFFEFFFFu) | tag; };
    auto send = [&](float (&acc)[28], int cc) {
      reg_fence(acc);
      const uint32_t a = out_addr(cc, wg) + wq * 1792;
#pragma unroll
      for (int q = 0; q < 3; q++)
        sts128(a + q * 512 + lane * 16, pack_bf16(acc[8 * q], acc[8 * q + 1]), pack_bf16(acc[8 * q + 2], acc[8 * q + 3]),
               pack_bf16(acc[8 * q + 4], acc[8 * q + 5]), tg(pack_bf16(acc[8 * q + 6], acc[8 * q + 7])));
      sts64(a + 1536 + lane * 8, pack_bf16(acc[24], acc[25]), tg(pack_bf16(acc[26], acc[27])));
      asm volatile("fence.proxy.async.shared::cta;" ::: "memory");
      mbar_arrive(bar_out + 8 * (cc * 2 + wg));
    };
    auto load_hh = [&](uint32_t (&d)[28], int q) {
      mbar_wait(bar_hh + 8 * (2 * q + wg), 0);
      const uint32_t a = sb + a_slot(2 * q + wg, cg) + t128 * 16;
#pragma unroll
      for (int i = 0; i < 7; i++) {
        const uint4 v = lds128(a + i * 2048);
        d[4 * i] = v.x; d[4 * i + 1] = v.y; d[4 * i + 2] = v.z; d[4 * i + 3] = v.w;
      }
    };
    ISSUE(accA, 0, hh, true);
    send_hh(1);
    ISSUE(accA, 1, hh + 28, false);
    load_hh(ph0, 0);
    wg_wait<1>(); rel(0);
    ISSUE(accA, 2, ph0, false);      wg_wait<1>(); rel(1);
    ISSUE(accB, 3, hh, true);        wg_wait<1>(); rel(2);
    ISSUE(accB, 4, hh + 28, false);  wg_wait<1>(); rel(3);
    ISSUE(accB, 5, ph0, false);
    if (tid == 0) TR(1, 11);
    load_hh(ph1, 1);
    wg_wait<1>(); rel(4);
    ISSUE(accA, 6, ph1, false);      wg_wait<1>(); rel(5);
    ISSUE(accB, 7, ph1, false);      wg_wait<1>(); rel(6);
    ISSUE(accC, 8, hh, true);        send(accA, 0); wg_wait<1>(); rel(7);
    if (tid == 0) TR(1, 13);
    ISSUE(accC, 9, hh + 28, false);  send(accB, 1); wg_wait<1>(); rel(8);
    ISSUE(accC, 10, ph0, false);
    ISSUE(accC, 11, ph1, false);
    const int row = rt * 128 + wg * 64 + wq * 16 + g;
    uint32_t r20, r21;
    asm volatile("ld.relaxed.gpu.global.u32 %0, [%1];" : "=r"(r20) : "l"(g_stat2 + row) : "memory");
    asm volatile("ld.relaxed.gpu.global.u32 %0, [%1];" : "=r"(r21) : "l"(g_stat2 + row + 8) : "memory");
    ISSUE(accB, 12, hh, true);
    wg_wait<1>();
    send(accC, 2);
    if (tid == 0) TR(1, 16);
    ISSUE(accB, 13, hh + 28, false);
    ISSUE(accB, 14, ph0, false);
    ISSUE(accB, 15, ph1, false);
    if (tid == 0) TR(1, 7);
    uint32_t hres[16];
#pragma unroll
    for (int i = 0; i < 4; i++) {
      int qq = lane >> 3, r = lane & 7, kg = 7 * cg + 2 * i + (qq >> 1), c = 2 * wq + (qq & 1);
      if (kg > 55) kg = 55;
      asm volatile("ldmatrix.sync.aligned.m8n8.x4.trans.shared.b16 {%0,%1,%2,%3}, [%4];"
                   : "=r"(hres[4 * i]), "=r"(hres[4 * i + 1]), "=r"(hres[4 * i + 2]), "=r"(hres[4 * i + 3])
                   : "r"(sb + B_SA + kg * 2048 + wg * 1024 + r * 128 + ((c ^ r) << 4)) : "memory");
    }
    {
      int it = 0;
      while ((((r20 ^ ep) | (r21 ^ ep)) & 1u) && ++it < 400000) {
        asm volatile("ld.relaxed.gpu.global.u32 %0, [%1];" : "=r"(r20) : "l"(g_stat2 + row) : "memory");
        asm volatile("ld.relaxed.gpu.global.u32 %0, [%1];" : "=r"(r21) : "l"(g_stat2 + row + 8) : "memory");
      }
    }
    wg_wait<0>();
    reg_fence(accB);
    if (tid == 0) TR(1, 9);
#pragma unroll 1
    for (int q = 0; q < 3; q++) {
      mbar_wait(bar_in + 8 * (2 * q + wg), 0);
      add_in(accB, q, warp);
      if (tid == 0 && q == 1) TR(1, 12);
    }
    uint32_t* o0 = (uint32_t*)(out + (size_t)row * DM + 56 * cg + 2 * t);
    uint32_t* o1 = o0 + 8 * DM / 2;
#pragma unroll
    for (int i = 0; i < 7; i++) {
      o0[4 * i] = hadd2_bf(hres[2 * i], pack_bf16(accB[4 * i] * __uint_as_float(r20), accB[4 * i + 1] * __uint_as_float(r20)));
      o1[4 * i] = hadd2_bf(hres[2 * i + 1], pack_bf16(accB[4 * i + 2] * __uint_as_float(r21), accB[4 * i + 3] * __uint_as_float(r21)));
    }
    if (tid == 0) TR(1, 10);
    if (tid == 128) TR(1, 15);
  }
}

extern "C" void kernel_launch(void* const* d_in, const int* in_sizes, int n_in, void* d_out, int out_size) {
  const __nv_bfloat16* x = (const __nv_bfloat16*)d_in[0];
  const __nv_bfloat16 *are = (const __nv_bfloat16*)d_in[1], *aim = (const __nv_bfloat16*)d_in[2], *bre = (const __nv_bfloat16*)d_in[3],
                      *bim = (const __nv_bfloat16*)d_in[4], *cre = (const __nv_bfloat16*)d_in[5], *cim = (const __nv_bfloat16*)d_in[6],
                      *logdt = (const __nv_bfloat16*)d_in[7], *dskip = (const __nv_bfloat16*)d_in[8];
  const __nv_bfloat16 *wg = (const __nv_bfloat16*)d_in[10], *wu = (const __nv_bfloat16*)d_in[11], *wd = (const __nv_bfloat16*)d_in[12];

  static bool init = false;
  if (!init) {
    init = true;
    cudaFuncSetAttribute(k_ffn, cudaFuncAttributeMaxDynamicSharedMemorySize, B_SMEM);
    cudaFuncSetAttribute(k_front, cudaFuncAttributeMaxDynamicSharedMemorySize, A_SMEM);
  }
  cudaStream_t st = cudaStreamPerThread;
  k_front<<<128, 512, A_SMEM, st>>>(
      x, (const uint32_t*)are, (const uint32_t*)aim, (const uint32_t*)bre, (const uint32_t*)bim, (const uint32_t*)cre, (const uint32_t*)cim,
      (const unsigned short*)logdt, (const unsigned short*)dskip, (const uint4*)wg, (const uint4*)wu, (const uint4*)wd);
  cudaLaunchConfig_t cfg = {};
  cfg.gridDim = dim3(128); cfg.blockDim = dim3(384); cfg.dynamicSmemBytes = B_SMEM; cfg.stream = st;
  cudaLaunchAttribute at[1];
  at[0].id = cudaLaunchAttributeProgrammaticStreamSerialization; at[0].val.programmaticStreamSerializationAllowed = 1;
  cfg.attrs = at; cfg.numAttrs = 1;
  cudaLaunchKernelEx(&cfg, k_ffn, (__nv_bfloat16*)d_out);
}
```

```cpp
#include <cuda_runtime.h>
#include <cuda_bf16.h>
#include <stdint.h>

constexpr int LSEQ = 2048, DM = 448;

__device__ uint4    g_himg[16 * 114688 / 16];
__device__ uint4    g_cimg[8 * 2 * 224];
__device__ uint32_t g_stat2[LSEQ];
__device__ uint4    g_part[128 * 3 * 896];
__device__ uint4    g_wimg[8 * 602112 / 16];
__device__ uint4    g_ux[DM * 128 * 4];
__device__ unsigned g_cnt1;
__device__ uint32_t g_flag[128 * 8];

#define TR(k, i) do {} while (0)
__device__ __forceinline__ uint32_t s2u(const void* p) { return (uint32_t)__cvta_generic_to_shared(p); }
__device__ __forceinline__ void mbar_init(uint32_t b, int c) { asm volatile("mbarrier.init.shared::cta.b64 [%0], %1;" ::"r"(b), "r"(c)); }
__device__ __forceinline__ void mbar_expect(uint32_t b, int bytes) { asm volatile("mbarrier.arrive.expect_tx.shared::cta.b64 _, [%0], %1;" ::"r"(b), "r"(bytes) : "memory"); }
__device__ __forceinline__ void mbar_arrive(uint32_t b) { asm volatile("mbarrier.arrive.shared::cta.b64 _, [%0];" ::"r"(b) : "memory"); }
__device__ __forceinline__ void mbar_wait(uint32_t b, int ph) {
  asm volatile("{\n.reg .pred p;\n.reg .b32 n;\nmov.b32 n, 0;\nLW:\nmbarrier.try_wait.parity.shared::cta.b64 p, [%0], %1;\n@p bra LD;\n"
               "add.u32 n, n, 1;\nsetp.lt.u32 p, n, 4000000;\n@p bra LW;\ntrap;\nLD:\n}" ::"r"(b), "r"(ph) : "memory");
}
__device__ __forceinline__ bool mbar_test(uint32_t b, int ph) {
  uint32_t ok;
  asm volatile("{\n.reg .pred p;\nmbarrier.test_wait.parity.shared::cta.b64 p, [%1], %2;\nselp.u32 %0, 1, 0, p;\n}" : "=r"(ok) : "r"(b), "r"(ph) : "memory");
  return ok;
}
__device__ __forceinline__ void wg_fence() { asm volatile("wgmma.fence.sync.aligned;" ::: "memory"); }
__device__ __forceinline__ void wg_commit() { asm volatile("wgmma.commit_group.sync.aligned;" ::: "memory"); }
template <int N> __device__ __forceinline__ void wg_wait() { asm volatile("wgmma.wait_group.sync.aligned %0;" ::"n"(N) : "memory"); }
template <int N> __device__ __forceinline__ void reg_fence(float (&a)[N]) {
#pragma unroll
  for (int i = 0; i < N; i++) asm volatile("" : "+f"(a[i])::"memory");
}
__device__ __forceinline__ uint32_t pack_bf16(float lo, float hi) {
  uint32_t r; asm("cvt.rn.bf16x2.f32 %0, %1, %2;" : "=r"(r) : "f"(hi), "f"(lo)); return r;
}
__device__ __forceinline__ float bf_lo(uint32_t v) { return __uint_as_float(v << 16); }
__device__ __forceinline__ float bf_hi(uint32_t v) { return __uint_as_float(v & 0xFFFF0000u); }
__device__ __forceinline__ float rbf(float x) { return __bfloat162float(__float2bfloat16_rn(x)); }
__device__ __forceinline__ uint32_t hmul2_bf(uint32_t a, uint32_t b) { uint32_t r; asm("mul.rn.bf16x2 %0, %1, %2;" : "=r"(r) : "r"(a), "r"(b)); return r; }
__device__ __forceinline__ uint32_t hadd2_bf(uint32_t a, uint32_t b) { uint32_t r; asm("add.rn.bf16x2 %0, %1, %2;" : "=r"(r) : "r"(a), "r"(b)); return r; }
__device__ __forceinline__ void bulk_ld(uint32_t dst, const void* src, int bytes, uint32_t bar) {
  asm volatile("cp.async.bulk.shared::cluster.global.mbarrier::complete_tx::bytes [%0], [%1], %2, [%3];"
               ::"r"(dst), "l"(src), "r"(bytes), "r"(bar) : "memory");
}

__device__ __forceinline__ void bulk_ld_mc(uint32_t dst, const void* src, int bytes, uint32_t bar) {
  asm volatile("cp.async.bulk.shared::cluster.global.mbarrier::complete_tx::bytes.multicast::cluster [%0], [%1], %2, [%3], %4;"
               ::"r"(dst), "l"(src), "r"(bytes), "r"(bar), "h"((uint16_t)3) : "memory");
}
template <int AOFF, uint32_t AHI, int BOFF, uint32_t BHI, int ACC>
__device__ __forceinline__ void wgmma_ss224(float (&d)[112], uint32_t alo, uint32_t blo) {
  asm volatile("{\n.reg .pred p;\n.reg .b64 ad, bd;\nsetp.ne.b32 p, %118, 0;\n"
    "mov.b64 ad, {%112, %115};\nadd.s64 ad, ad, %114;\nmov.b64 bd, {%113, %117};\nadd.s64 bd, bd, %116;\n"
    "wgmma.mma_async.sync.aligned.m64n224k16.f32.bf16.bf16 {%0,%1,%2,%3,%4,%5,%6,%7,%8,%9,%10,%11,%12,%13,%14,%15,%16,%17,%18,%19,%20,%21,%22,%23,%24,%25,%26,%27,%28,%29,%30,%31,%32,%33,%34,%35,%36,%37,%38,%39,%40,%41,%42,%43,%44,%45,%46,%47,%48,%49,%50,%51,%52,%53,%54,%55,%56,%57,%58,%59,%60,%61,%62,%63,%64,%65,%66,%67,%68,%69,%70,%71,%72,%73,%74,%75,%76,%77,%78,%79,%80,%81,%82,%83,%84,%85,%86,%87,%88,%89,%90,%91,%92,%93,%94,%95,%96,%97,%98,%99,%100,%101,%102,%103,%104,%105,%106,%107,%108,%109,%110,%111}, ad, bd, p, 1, 1, 1, 1;\n}\n"
    : "+f"(d[0]),"+f"(d[1]),"+f"(d[2]),"+f"(d[3]),"+f"(d[4]),"+f"(d[5]),"+f"(d[6]),"+f"(d[7]),"+f"(d[8]),"+f"(d[9]),"+f"(d[10]),"+f"(d[11]),"+f"(d[12]),"+f"(d[13]),"+f"(d[14]),"+f"(d[15]),"+f"(d[16]),"+f"(d[17]),"+f"(d[18]),"+f"(d[19]),"+f"(d[20]),"+f"(d[21]),"+f"(d[22]),"+f"(d[23]),"+f"(d[24]),"+f"(d[25]),"+f"(d[26]),"+f"(d[27]),"+f"(d[28]),"+f"(d[29]),"+f"(d[30]),"+f"(d[31]),"+f"(d[32]),"+f"(d[33]),"+f"(d[34]),"+f"(d[35]),"+f"(d[36]),"+f"(d[37]),"+f"(d[38]),"+f"(d[39]),"+f"(d[40]),"+f"(d[41]),"+f"(d[42]),"+f"(d[43]),"+f"(d[44]),"+f"(d[45]),"+f"(d[46]),"+f"(d[47]),"+f"(d[48]),"+f"(d[49]),"+f"(d[50]),"+f"(d[51]),"+f"(d[52]),"+f"(d[53]),"+f"(d[54]),"+f"(d[55]),"+f"(d[56]),"+f"(d[57]),"+f"(d[58]),"+f"(d[59]),"+f"(d[60]),"+f"(d[61]),"+f"(d[62]),"+f"(d[63]),"+f"(d[64]),"+f"(d[65]),"+f"(d[66]),"+f"(d[67]),"+f"(d[68]),"+f"(d[69]),"+f"(d[70]),"+f"(d[71]),"+f"(d[72]),"+f"(d[73]),"+f"(d[74]),"+f"(d[75]),"+f"(d[76]),"+f"(d[77]),"+f"(d[78]),"+f"(d[79]),"+f"(d[80]),"+f"(d[81]),"+f"(d[82]),"+f"(d[83]),"+f"(d[84]),"+f"(d[85]),"+f"(d[86]),"+f"(d[87]),"+f"(d[88]),"+f"(d[89]),"+f"(d[90]),"+f"(d[91]),"+f"(d[92]),"+f"(d[93]),"+f"(d[94]),"+f"(d[95]),"+f"(d[96]),"+f"(d[97]),"+f"(d[98]),"+f"(d[99]),"+f"(d[100]),"+f"(d[101]),"+f"(d[102]),"+f"(d[103]),"+f"(d[104]),"+f"(d[105]),"+f"(d[106]),"+f"(d[107]),"+f"(d[108]),"+f"(d[109]),"+f"(d[110]),"+f"(d[111])
    : "r"(alo), "r"(blo), "n"(AOFF), "n"(AHI), "n"(BOFF), "n"(BHI), "n"(ACC));
}
template <int AOFF, uint32_t AHI, int BOFF, uint32_t BHI, int ACC>
__device__ __forceinline__ void wgmma_ss232(float (&d)[116], uint32_t alo, uint32_t blo) {
  asm volatile("{\n.reg .pred p;\n.reg .b64 ad, bd;\nsetp.ne.b32 p, %122, 0;\n"
    "mov.b64 ad, {%116, %119};\nadd.s64 ad, ad, %118;\nmov.b64 bd, {%117, %121};\nadd.s64 bd, bd, %120;\n"
    "wgmma.mma_async.sync.aligned.m64n232k16.f32.bf16.bf16 {%0,%1,%2,%3,%4,%5,%6,%7,%8,%9,%10,%11,%12,%13,%14,%15,%16,%17,%18,%19,%20,%21,%22,%23,%24,%25,%26,%27,%28,%29,%30,%31,%32,%33,%34,%35,%36,%37,%38,%39,%40,%41,%42,%43,%44,%45,%46,%47,%48,%49,%50,%51,%52,%53,%54,%55,%56,%57,%58,%59,%60,%61,%62,%63,%64,%65,%66,%67,%68,%69,%70,%71,%72,%73,%74,%75,%76,%77,%78,%79,%80,%81,%82,%83,%84,%85,%86,%87,%88,%89,%90,%91,%92,%93,%94,%95,%96,%97,%98,%99,%100,%101,%102,%103,%104,%105,%106,%107,%108,%109,%110,%111,%112,%113,%114,%115}, ad, bd, p, 1, 1, 1, 1;\n}\n"
    : "+f"(d[0]),"+f"(d[1]),"+f"(d[2]),"+f"(d[3]),"+f"(d[4]),"+f"(d[5]),"+f"(d[6]),"+f"(d[7]),"+f"(d[8]),"+f"(d[9]),"+f"(d[10]),"+f"(d[11]),"+f"(d[12]),"+f"(d[13]),"+f"(d[14]),"+f"(d[15]),"+f"(d[16]),"+f"(d[17]),"+f"(d[18]),"+f"(d[19]),"+f"(d[20]),"+f"(d[21]),"+f"(d[22]),"+f"(d[23]),"+f"(d[24]),"+f"(d[25]),"+f"(d[26]),"+f"(d[27]),"+f"(d[28]),"+f"(d[29]),"+f"(d[30]),"+f"(d[31]),"+f"(d[32]),"+f"(d[33]),"+f"(d[34]),"+f"(d[35]),"+f"(d[36]),"+f"(d[37]),"+f"(d[38]),"+f"(d[39]),"+f"(d[40]),"+f"(d[41]),"+f"(d[42]),"+f"(d[43]),"+f"(d[44]),"+f"(d[45]),"+f"(d[46]),"+f"(d[47]),"+f"(d[48]),"+f"(d[49]),"+f"(d[50]),"+f"(d[51]),"+f"(d[52]),"+f"(d[53]),"+f"(d[54]),"+f"(d[55]),"+f"(d[56]),"+f"(d[57]),"+f"(d[58]),"+f"(d[59]),"+f"(d[60]),"+f"(d[61]),"+f"(d[62]),"+f"(d[63]),"+f"(d[64]),"+f"(d[65]),"+f"(d[66]),"+f"(d[67]),"+f"(d[68]),"+f"(d[69]),"+f"(d[70]),"+f"(d[71]),"+f"(d[72]),"+f"(d[73]),"+f"(d[74]),"+f"(d[75]),"+f"(d[76]),"+f"(d[77]),"+f"(d[78]),"+f"(d[79]),"+f"(d[80]),"+f"(d[81]),"+f"(d[82]),"+f"(d[83]),"+f"(d[84]),"+f"(d[85]),"+f"(d[86]),"+f"(d[87]),"+f"(d[88]),"+f"(d[89]),"+f"(d[90]),"+f"(d[91]),"+f"(d[92]),"+f"(d[93]),"+f"(d[94]),"+f"(d[95]),"+f"(d[96]),"+f"(d[97]),"+f"(d[98]),"+f"(d[99]),"+f"(d[100]),"+f"(d[101]),"+f"(d[102]),"+f"(d[103]),"+f"(d[104]),"+f"(d[105]),"+f"(d[106]),"+f"(d[107]),"+f"(d[108]),"+f"(d[109]),"+f"(d[110]),"+f"(d[111]),"+f"(d[112]),"+f"(d[113]),"+f"(d[114]),"+f"(d[115])
    : "r"(alo), "r"(blo), "n"(AOFF), "n"(AHI), "n"(BOFF), "n"(BHI), "n"(ACC));
}
template <int OFF, uint32_t BHI, int ACC>
__device__ __forceinline__ void wgmma_rs224(float (&d)[112], uint32_t a0, uint32_t a1, uint32_t a2, uint32_t a3, uint32_t blo) {
  asm volatile("{\n.reg .pred p;\n.reg .b64 bd;\nsetp.ne.b32 p, %119, 0;\nmov.b64 bd, {%116, %118};\nadd.s64 bd, bd, %117;\n"
    "wgmma.mma_async.sync.aligned.m64n224k16.f32.bf16.bf16 {%0,%1,%2,%3,%4,%5,%6,%7,%8,%9,%10,%11,%12,%13,%14,%15,%16,%17,%18,%19,%20,%21,%22,%23,%24,%25,%26,%27,%28,%29,%30,%31,%32,%33,%34,%35,%36,%37,%38,%39,%40,%41,%42,%43,%44,%45,%46,%47,%48,%49,%50,%51,%52,%53,%54,%55,%56,%57,%58,%59,%60,%61,%62,%63,%64,%65,%66,%67,%68,%69,%70,%71,%72,%73,%74,%75,%76,%77,%78,%79,%80,%81,%82,%83,%84,%85,%86,%87,%88,%89,%90,%91,%92,%93,%94,%95,%96,%97,%98,%99,%100,%101,%102,%103,%104,%105,%106,%107,%108,%109,%110,%111}, {%112,%113,%114,%115}, bd, p, 1, 1, 1;\n}\n"
    : "+f"(d[0]),"+f"(d[1]),"+f"(d[2]),"+f"(d[3]),"+f"(d[4]),"+f"(d[5]),"+f"(d[6]),"+f"(d[7]),"+f"(d[8]),"+f"(d[9]),"+f"(d[10]),"+f"(d[11]),"+f"(d[12]),"+f"(d[13]),"+f"(d[14]),"+f"(d[15]),"+f"(d[16]),"+f"(d[17]),"+f"(d[18]),"+f"(d[19]),"+f"(d[20]),"+f"(d[21]),"+f"(d[22]),"+f"(d[23]),"+f"(d[24]),"+f"(d[25]),"+f"(d[26]),"+f"(d[27]),"+f"(d[28]),"+f"(d[29]),"+f"(d[30]),"+f"(d[31]),"+f"(d[32]),"+f"(d[33]),"+f"(d[34]),"+f"(d[35]),"+f"(d[36]),"+f"(d[37]),"+f"(d[38]),"+f"(d[39]),"+f"(d[40]),"+f"(d[41]),"+f"(d[42]),"+f"(d[43]),"+f"(d[44]),"+f"(d[45]),"+f"(d[46]),"+f"(d[47]),"+f"(d[48]),"+f"(d[49]),"+f"(d[50]),"+f"(d[51]),"+f"(d[52]),"+f"(d[53]),"+f"(d[54]),"+f"(d[55]),"+f"(d[56]),"+f"(d[57]),"+f"(d[58]),"+f"(d[59]),"+f"(d[60]),"+f"(d[61]),"+f"(d[62]),"+f"(d[63]),"+f"(d[64]),"+f"(d[65]),"+f"(d[66]),"+f"(d[67]),"+f"(d[68]),"+f"(d[69]),"+f"(d[70]),"+f"(d[71]),"+f"(d[72]),"+f"(d[73]),"+f"(d[74]),"+f"(d[75]),"+f"(d[76]),"+f"(d[77]),"+f"(d[78]),"+f"(d[79]),"+f"(d[80]),"+f"(d[81]),"+f"(d[82]),"+f"(d[83]),"+f"(d[84]),"+f"(d[85]),"+f"(d[86]),"+f"(d[87]),"+f"(d[88]),"+f"(d[89]),"+f"(d[90]),"+f"(d[91]),"+f"(d[92]),"+f"(d[93]),"+f"(d[94]),"+f"(d[95]),"+f"(d[96]),"+f"(d[97]),"+f"(d[98]),"+f"(d[99]),"+f"(d[100]),"+f"(d[101]),"+f"(d[102]),"+f"(d[103]),"+f"(d[104]),"+f"(d[105]),"+f"(d[106]),"+f"(d[107]),"+f"(d[108]),"+f"(d[109]),"+f"(d[110]),"+f"(d[111])
    : "r"(a0), "r"(a1), "r"(a2), "r"(a3), "r"(blo), "n"(OFF), "n"(BHI), "n"(ACC));
}
template <int OFF, uint32_t BHI, int ACC>
__device__ __forceinline__ void wgmma_rs56(float (&d)[28], uint32_t a0, uint32_t a1, uint32_t a2, uint32_t a3, uint32_t blo) {
  asm volatile("{\n.reg .pred p;\n.reg .b64 bd;\nsetp.ne.b32 p, %35, 0;\nmov.b64 bd, {%32, %34};\nadd.s64 bd, bd, %33;\n"
    "wgmma.mma_async.sync.aligned.m64n56k16.f32.bf16.bf16 {%0,%1,%2,%3,%4,%5,%6,%7,%8,%9,%10,%11,%12,%13,%14,%15,%16,%17,%18,%19,%20,%21,%22,%23,%24,%25,%26,%27}, {%28,%29,%30,%31}, bd, p, 1, 1, 1;\n}\n"
    : "+f"(d[0]),"+f"(d[1]),"+f"(d[2]),"+f"(d[3]),"+f"(d[4]),"+f"(d[5]),"+f"(d[6]),"+f"(d[7]),"+f"(d[8]),"+f"(d[9]),"+f"(d[10]),"+f"(d[11]),"+f"(d[12]),"+f"(d[13]),"+f"(d[14]),"+f"(d[15]),"+f"(d[16]),"+f"(d[17]),"+f"(d[18]),"+f"(d[19]),"+f"(d[20]),"+f"(d[21]),"+f"(d[22]),"+f"(d[23]),"+f"(d[24]),"+f"(d[25]),"+f"(d[26]),"+f"(d[27])
    : "r"(a0), "r"(a1), "r"(a2), "r"(a3), "r"(blo), "n"(OFF), "n"(BHI), "n"(ACC));
}

__device__ __forceinline__ void st128(uint4* p, uint32_t a, uint32_t b, uint32_t c, uint32_t d) {
  asm volatile("{\n.reg .b128 v;\n.reg .b64 lo, hi;\nmov.b64 lo, {%1, %2};\nmov.b64 hi, {%3, %4};\nmov.b128 v, {lo, hi};\n"
               "st.relaxed.gpu.global.b128 [%0], v;\n}" ::"l"(p), "r"(a), "r"(b), "r"(c), "r"(d) : "memory");
}
__device__ __forceinline__ void ld128(const uint4* p, uint32_t* r) {
  asm volatile("{\n.reg .b128 v;\n.reg .b64 lo, hi;\nld.relaxed.gpu.global.b128 v, [%4];\nmov.b128 {lo, hi}, v;\n"
               "mov.b64 {%0, %1}, lo;\nmov.b64 {%2, %3}, hi;\n}" : "=r"(r[0]), "=r"(r[1]), "=r"(r[2]), "=r"(r[3]) : "l"(p) : "memory");
}

template <int OFF, uint32_t BHI, int ACC>
__device__ __forceinline__ void wgmma_rs32(float (&d)[16], uint32_t a0, uint32_t a1, uint32_t a2, uint32_t a3, uint32_t blo) {
  asm volatile("{\n.reg .pred p;\n.reg .b64 bd;\nsetp.ne.b32 p, %23, 0;\nmov.b64 bd, {%20, %22};\nadd.s64 bd, bd, %21;\n"
    "wgmma.mma_async.sync.aligned.m64n32k16.f32.bf16.bf16 {%0,%1,%2,%3,%4,%5,%6,%7,%8,%9,%10,%11,%12,%13,%14,%15}, {%16,%17,%18,%19}, bd, p, 1, 1, 0;\n}\n"
    : "+f"(d[0]),"+f"(d[1]),"+f"(d[2]),"+f"(d[3]),"+f"(d[4]),"+f"(d[5]),"+f"(d[6]),"+f"(d[7]),"+f"(d[8]),"+f"(d[9]),"+f"(d[10]),"+f"(d[11]),"+f"(d[12]),"+f"(d[13]),"+f"(d[14]),"+f"(d[15])
    : "r"(a0), "r"(a1), "r"(a2), "r"(a3), "r"(blo), "n"(OFF), "n"(BHI), "n"(ACC));
}
template <int OFF, uint32_t BHI, int ACC>
__device__ __forceinline__ void wgmma_rs24(float (&d)[12], uint32_t a0, uint32_t a1, uint32_t a2, uint32_t a3, uint32_t blo) {
  asm volatile("{\n.reg .pred p;\n.reg .b64 bd;\nsetp.ne.b32 p, %19, 0;\nmov.b64 bd, {%16, %18};\nadd.s64 bd, bd, %17;\n"
    "wgmma.mma_async.sync.aligned.m64n24k16.f32.bf16.bf16 {%0,%1,%2,%3,%4,%5,%6,%7,%8,%9,%10,%11}, {%12,%13,%14,%15}, bd, p, 1, 1, 1;\n}\n"
    : "+f"(d[0]),"+f"(d[1]),"+f"(d[2]),"+f"(d[3]),"+f"(d[4]),"+f"(d[5]),"+f"(d[6]),"+f"(d[7]),"+f"(d[8]),"+f"(d[9]),"+f"(d[10]),"+f"(d[11])
    : "r"(a0), "r"(a1), "r"(a2), "r"(a3), "r"(blo), "n"(OFF), "n"(BHI), "n"(ACC));
}
template <int OFF, uint32_t BHI, int ACC>
__device__ __forceinline__ void wgmma_rs16(float (&d)[8], uint32_t a0, uint32_t a1, uint32_t a2, uint32_t a3, uint32_t blo) {
  asm volatile("{\n.reg .pred p;\n.reg .b64 bd;\nsetp.ne.b32 p, %15, 0;\nmov.b64 bd, {%12, %14};\nadd.s64 bd, bd, %13;\n"
    "wgmma.mma_async.sync.aligned.m64n16k16.f32.bf16.bf16 {%0,%1,%2,%3,%4,%5,%6,%7}, {%8,%9,%10,%11}, bd, p, 1, 1, 1;\n}\n"
    : "+f"(d[0]),"+f"(d[1]),"+f"(d[2]),"+f"(d[3]),"+f"(d[4]),"+f"(d[5]),"+f"(d[6]),"+f"(d[7])
    : "r"(a0), "r"(a1), "r"(a2), "r"(a3), "r"(blo), "n"(OFF), "n"(BHI), "n"(ACC));
}

constexpr int A_R1 = 0;
constexpr int A_R2A = A_R1 + 2624, A_R2B = A_R2A + 768, A_R3A = A_R2B + 768, A_R3B = A_R3A + 528;
constexpr int A_K1024 = A_R3B + 528;
constexpr int A_W5 = A_K1024 + 16;
constexpr int A_W3 = A_W5 + 4096;
constexpr int A_W9 = A_W3 + 4112;
constexpr int A_W7 = A_W9 + 2048;
constexpr int A_V  = A_W7 + 2048;
constexpr int A_UB = A_V + 2048;
constexpr int A_STG = A_UB + 5248;
constexpr int A_Y2 = A_STG, A_Y3 = A_Y2 + 6528, A_YB = A_Y3 + 4352;
constexpr int A_REC = A_STG + 4 * 4352;
constexpr int A_CH = A_REC + 8192;
static_assert(A_W5 % 16 == 0 && A_UB % 16 == 0 && A_CH % 16 == 0 && A_YB + 4096 <= A_REC, "layout");

struct cf { float x, y; };
__device__ __forceinline__ cf cmul(cf a, cf b) { cf r; r.x = fmaf(a.x, b.x, -a.y * b.y); r.y = fmaf(a.x, b.y, a.y * b.x); return r; }
__device__ __forceinline__ cf cexp_l(float lr, float li, float l) {
  float mag; asm("ex2.approx.ftz.f32 %0, %1;" : "=f"(mag) : "f"((lr * l) * 1.4426950408889634f));
  const float th = li * l;
  const float k = (fmaf(th, 0.15915494f, 12582912.f)) - 12582912.f;
  float ph = fmaf(th, 0.15915494f, -k);
  ph = fmaf(th, 6.4206383e-9f, ph) * 6.2831853f;
  cf r; r.x = mag * __cosf(ph); r.y = mag * __sinf(ph); return r;
}
__device__ __forceinline__ void sts16(uint32_t a, uint32_t v) { asm volatile("st.shared.u16 [%0], %1;" ::"r"(a), "h"((uint16_t)v) : "memory"); }
__device__ __forceinline__ void sts32(uint32_t a, uint32_t v) { asm volatile("st.shared.u32 [%0], %1;" ::"r"(a), "r"(v) : "memory"); }
__device__ __forceinline__ void sts64(uint32_t a, uint32_t v0, uint32_t v1) { asm volatile("st.shared.v2.u32 [%0], {%1, %2};" ::"r"(a), "r"(v0), "r"(v1) : "memory"); }
__device__ __forceinline__ void sts128(uint32_t a, uint32_t v0, uint32_t v1, uint32_t v2, uint32_t v3) {
  asm volatile("st.shared.v4.u32 [%0], {%1, %2, %3, %4};" ::"r"(a), "r"(v0), "r"(v1), "r"(v2), "r"(v3) : "memory");
}
__device__ __forceinline__ uint32_t lds32(uint32_t a) { uint32_t v; asm volatile("ld.shared.u32 %0, [%1];" : "=r"(v) : "r"(a) : "memory"); return v; }
__device__ __forceinline__ uint4 lds128(uint32_t a) {
  uint4 v; asm volatile("ld.shared.v4.u32 {%0, %1, %2, %3}, [%4];" : "=r"(v.x), "=r"(v.y), "=r"(v.z), "=r"(v.w) : "r"(a) : "memory"); return v;
}
__device__ __forceinline__ void ldsm4(uint32_t* r, uint32_t a) {
  asm volatile("ldmatrix.sync.aligned.m8n8.x4.shared.b16 {%0,%1,%2,%3}, [%4];" : "=r"(r[0]), "=r"(r[1]), "=r"(r[2]), "=r"(r[3]) : "r"(a) : "memory");
}
__device__ __forceinline__ void mma16816(float* d, const uint32_t* a, uint32_t b0, uint32_t b1) {
  asm volatile("mma.sync.aligned.m16n8k16.row.col.f32.bf16.bf16.f32 {%0,%1,%2,%3}, {%4,%5,%6,%7}, {%8,%9}, {%0,%1,%2,%3};"
               : "+f"(d[0]), "+f"(d[1]), "+f"(d[2]), "+f"(d[3]) : "r"(a[0]), "r"(a[1]), "r"(a[2]), "r"(a[3]), "r"(b0), "r"(b1));
}
__device__ __forceinline__ uint32_t hsub2_bf(uint32_t a, uint32_t b) { uint32_t r; asm("sub.rn.bf16x2 %0, %1, %2;" : "=r"(r) : "r"(a), "r"(b)); return r; }
__device__ __forceinline__ void bar_sync(int id, int n) { asm volatile("bar.sync %0, %1;" ::"r"(id), "r"(n) : "memory"); }

template <int S> struct F1B { static constexpr int c = S / 4 + ((S & 3) == 3 ? 0 : 0), cc = (16 * S) / 64, ks = (64 * cc - (16 * S - 48)) / 16, off = (A_UB + 2 * ks * 656 + (9 - cc) * 16) / 16; };

template <int NS>
__device__ __forceinline__ void load_quads(uint32_t* q, uint32_t addr) {
#pragma unroll
  for (int i = 0; i < NS; i++) {
    q[4 * i] = lds32(addr + i * 64); q[4 * i + 1] = lds32(addr + i * 64 + 32);
    q[4 * i + 2] = i ? q[4 * i - 3] : lds32(addr - 32);
    q[4 * i + 3] = q[4 * i];
  }
#pragma unroll
  for (int i = 0; i < 4 * NS; i++) asm volatile("" : "+r"(q[i]));
}
template <int S0, int NS>
__device__ __forceinline__ void f1_steps(float (&acc)[16], const uint32_t* a, uint32_t blo) {
  if constexpr (NS > 0) {
    wgmma_rs32<F1B<S0>::off, 8, S0 != 0>(acc, a[0], a[1], a[2], a[3], blo);
    f1_steps<S0 + 1, NS - 1>(acc, a + 4, blo);
  }
}
template <int S0, int NS, int BASE, int FIRST>
__device__ __forceinline__ void s2_steps(float (&acc)[12], const uint32_t* a, uint32_t blo) {
  if constexpr (NS > 0) {
    wgmma_rs24<BASE / 16 + (112 - 16 * S0), 64, !(FIRST && S0 == 0)>(acc, a[0], a[1], a[2], a[3], blo);
    s2_steps<S0 + 1, NS - 1, BASE, FIRST>(acc, a + 4, blo);
  }
}
template <int S0, int NS, int BASE, int FIRST>
__device__ __forceinline__ void s3_steps(float (&acc)[8], const uint32_t* a, uint32_t blo) {
  if constexpr (NS > 0) {
    wgmma_rs16<BASE / 16 + (48 - 16 * S0), 64, !(FIRST && S0 == 0)>(acc, a[0], a[1], a[2], a[3], blo);
    s3_steps<S0 + 1, NS - 1, BASE, FIRST>(acc, a + 4, blo);
  }
}

__device__ __forceinline__ void phase_a(
        unsigned char* sm, const uint32_t bar_rec, const uint32_t ep_addr,
        const __nv_bfloat16* __restrict__ x, const uint32_t* __restrict__ are, const uint32_t* __restrict__ aim,
        const uint32_t* __restrict__ bre, const uint32_t* __restrict__ bim, const uint32_t* __restrict__ cre,
        const uint32_t* __restrict__ cim, const unsigned short* __restrict__ logdt, const unsigned short* __restrict__ dskip,
        const uint4* __restrict__ wgate, const uint4* __restrict__ wup, const uint4* __restrict__ wdown) {
  const uint32_t sb = s2u(sm);
  const int tid = threadIdx.x, wg = tid >> 7, warp = tid >> 5, lane = tid & 31, wq = warp & 3, t128 = tid & 127;
  const int blk = blockIdx.x;
  const bool conv = blk < 112;

  uint2 xr[4];
  {
    const uint2* p = (const uint2*)(x + (size_t)(blk * 16 + warp) * DM);
    xr[0] = __ldg(p + lane); xr[1] = __ldg(p + 32 + lane); xr[2] = __ldg(p + 64 + lane);
    xr[3] = lane < 16 ? __ldg(p + 96 + lane) : make_uint2(0, 0);
  }
  const int ch = conv ? blk * 4 + wg : 0;
  const uint32_t cb = sb + wg * A_CH;
  uint32_t prm[6];
  {
    const int i = ch * 128 + t128;
    prm[0] = __ldg(are + i); prm[1] = __ldg(aim + i); prm[2] = __ldg(bre + i); prm[3] = __ldg(bim + i); prm[4] = __ldg(cre + i); prm[5] = __ldg(cim + i);
  }
  const uint32_t ldt = __ldg(logdt + ch);
  uint32_t cnt0 = 0;
  if (tid == 0) cnt0 = __ldcg(&g_cnt1);
#pragma unroll
  for (int i = 0; i < 4; i++) if (i < 3 || t128 < (A_W5 + 1024) / 16 - 384) sts128(cb + (i * 128 + t128) * 16, 0, 0, 0, 0);
  if (t128 < 65) sts128(cb + (t128 < 64 ? A_W3 + t128 * 16 : A_W9), 0, 0, 0, 0);
  if (t128 < 72) sts128(cb + A_UB + (t128 / 9) * 656 + (t128 % 9) * 16, 0, 0, 0, 0);
  {
    float s = 0.f, q = 0.f;
#pragma unroll
    for (int i = 0; i < 4; i++) {
      const float a = bf_lo(xr[i].x), b = bf_hi(xr[i].x), c = bf_lo(xr[i].y), d = bf_hi(xr[i].y);
      s += (a + b) + (c + d);
      q = fmaf(a, a, q); q = fmaf(b, b, q); q = fmaf(c, c, q); q = fmaf(d, d, q);
    }
#pragma unroll
    for (int o = 16; o; o >>= 1) { s += __shfl_xor_sync(~0u, s, o); q += __shfl_xor_sync(~0u, q, o); }
    const float mean = s * (1.f / DM);
    const float var = fmaxf(fmaf(-mean, mean, q * (1.f / DM)), 0.f);
    const float rs = __frcp_rn(rbf(__fsqrt_rn(rbf(rbf(var) + 1e-5f))));
    const uint32_t mm = pack_bf16(mean, mean);
    const uint32_t tu = sb + A_REC + (warp >> 3) * A_CH + (warp & 7) * 912 + lane * 8, tx = tu + 2 * A_CH;
#pragma unroll
    for (int i = 0; i < 4; i++) {
      if (i < 3 || lane < 16) {
        const uint32_t d0 = hsub2_bf(xr[i].x, mm), d1 = hsub2_bf(xr[i].y, mm);
        sts64(tu + i * 256, pack_bf16(bf_lo(d0) * rs, bf_hi(d0) * rs), pack_bf16(bf_lo(d1) * rs, bf_hi(d1) * rs));
        sts64(tx + i * 256, xr[i].x, xr[i].y);
      }
    }
  }
  if (tid == 0) sts32(ep_addr, (cnt0 >> 7) + 1u);
  if (tid == 320) TR(0, 1);
  auto publish_rows = [&]() {
    bar_sync(5, 512);
    uint4* dst = g_ux + ((size_t)(warp * 8 + (lane >> 2)) * 128 + blk) * 4 + ((lane ^ (blk >> 1)) & 3);
#pragma unroll
    for (int i = 0; i < 4; i++) {
      if (i < 3 || warp < 8) {
        uint32_t r[4];
        asm volatile("ldmatrix.sync.aligned.m8n8.x4.trans.shared.b16 {%0,%1,%2,%3}, [%4];" : "=r"(r[0]), "=r"(r[1]), "=r"(r[2]), "=r"(r[3])
                     : "r"(sb + A_REC + (lane >> 3) * A_CH + (lane & 7) * 912 + (warp + 16 * i) * 16) : "memory");
        dst[i * 65536] = make_uint4(r[0], r[1], r[2], r[3]);
      }
    }
    if (warp != 0) asm volatile("bar.arrive 6, 512;" ::: "memory");
  };
  auto release_rows = [&]() {
    if (warp == 0) {
      bar_sync(6, 512);
      if (lane == 0) { asm volatile("red.release.gpu.global.add.u32 [%0], 1;" ::"l"(&g_cnt1) : "memory"); TR(0, 8); }
      __syncwarp();
    }
  };

  if (!conv) {
    publish_rows();
    release_rows();
    const int a = blk - 112, mat = a >> 3, j = a & 7;
    float s[8];
#pragma unroll
    for (int k = 0; k < 8; k++) s[k] = 0.f;
    if (lane < 28) {
      const uint4* src = (mat ? wup : wgate) + j * 28 + lane + (size_t)warp * 224;
#pragma unroll
      for (int hb = 0; hb < 2; hb++) {
        uint4 v[14];
#pragma unroll
        for (int r = 0; r < 14; r++) v[r] = __ldg(src + (size_t)(hb * 14 + r) * 16 * 224);
#pragma unroll
        for (int r = 0; r < 14; r++) {
          s[0] += bf_lo(v[r].x); s[1] += bf_hi(v[r].x); s[2] += bf_lo(v[r].y); s[3] += bf_hi(v[r].y);
          s[4] += bf_lo(v[r].z); s[5] += bf_hi(v[r].z); s[6] += bf_lo(v[r].w); s[7] += bf_hi(v[r].w);
        }
      }
      float4* red = (float4*)(sm + A_STG + warp * 896 + lane * 32);
      red[0] = make_float4(s[0], s[1], s[2], s[3]); red[1] = make_float4(s[4], s[5], s[6], s[7]);
    }
    bar_sync(5, 512);
    if (tid < 224) {
      float t = 0.f;
#pragma unroll
      for (int w = 0; w < 16; w++) t += *(const float*)(sm + A_STG + w * 896 + tid * 4);
      const float hi = rbf(t), mid = rbf(t - hi), lo = rbf(t - hi - mid);
      const int q = tid / 112, n = tid % 112 + 112 * mat;
      __nv_bfloat16* dst = (__nv_bfloat16*)(g_cimg + (j * 2 + q) * 224 + (n >> 3) * 8) + (n & 7);
      dst[0] = __float2bfloat16_rn(hi); dst[8] = __float2bfloat16_rn(mid); dst[16] = __float2bfloat16_rn(lo);
#pragma unroll
      for (int k = 3; k < 8; k++) dst[8 * k] = __float2bfloat16_rn(0.f);
    }
    if (tid == 320) TR(0, 10);
    return;
  }

  const int g = lane >> 2, t = lane & 3;
  const int wr = (wq + wg) & 3;
  uint4 wv[6];
  auto w_src = [&](int i) -> const uint4* {
    if (i < 4) return (blk < 56 ? wgate : wup) + (blk % 56) * 4 + (lane & 3) + (size_t)(i * 128 + warp * 8 + (lane >> 2)) * 224;
    const int it = warp + 16 * (i - 4);
    return wdown + (size_t)(blk * 16 + (it / 14) * 8 + (lane >> 2)) * 56 + (it % 14) * 4 + (lane & 3);
  };
  auto w_on = [&](int i) { return i == 3 ? warp < 8 : i == 5 ? warp < 12 : true; };
  {
    const uint32_t stg = cb + A_STG + wq * 4352;
    const float dt = rbf(expf(__uint_as_float(ldt << 16)));
    float lr[2], li[2];
    cf bq[2], b0[2], b4[2];
    uint32_t bf[48];
#pragma unroll
    for (int m = 0; m < 2; m++) {
      lr[m] = dt * (m ? bf_hi(prm[0]) : bf_lo(prm[0]));
      li[m] = dt * (m ? bf_hi(prm[1]) : bf_lo(prm[1]));
    }
    {
      cf b[2], z[2];
#pragma unroll
      for (int m = 0; m < 2; m++) {
        cf db, c;
        db.x = dt * (m ? bf_hi(prm[2]) : bf_lo(prm[2])); db.y = -dt * (m ? bf_hi(prm[3]) : bf_lo(prm[3]));
        c.x = m ? bf_hi(prm[4]) : bf_lo(prm[4]); c.y = -(m ? bf_hi(prm[5]) : bf_lo(prm[5]));
        b[m] = cmul(c, db);
        z[m] = cexp_l(lr[m], -li[m], 1.f);
        bq[m] = cexp_l(lr[m], -li[m], 256.f);
      }
#pragma unroll
      for (int i = 0; i < 8; i++) {
        sts64(stg + i * 272 + lane * 8, pack_bf16(b[0].x, b[0].y), pack_bf16(b[1].x, b[1].y));
        if (!(i & 1)) {
          cf e0 = cmul(b[0], bq[0]), e1 = cmul(b[1], bq[1]);
          sts64(stg + (8 + i / 2) * 272 + lane * 8, pack_bf16(e0.x, e0.y), pack_bf16(e1.x, e1.y));
          if (i == 0) { b0[0] = e0; b0[1] = e1; }
          if (i == 4) { b4[0] = e0; b4[1] = e1; }
        }
        if (i < 7) { b[0] = cmul(b[0], z[0]); b[1] = cmul(b[1], z[1]); }
        if (i == 1) publish_rows();
      }
#pragma unroll
      for (int i = 0; i < 7; i++) {
        b0[0] = cmul(b0[0], bq[0]); b0[1] = cmul(b0[1], bq[1]);
        sts64(stg + (i < 2 ? 12 + 2 * i : i - 2) * 272 + lane * 8, pack_bf16(b0[0].x, b0[0].y), pack_bf16(b0[1].x, b0[1].y));
        if (i < 2) {
          b4[0] = cmul(b4[0], bq[0]); b4[1] = cmul(b4[1], bq[1]);
          sts64(stg + (13 + 2 * i) * 272 + lane * 8, pack_bf16(b4[0].x, b4[0].y), pack_bf16(b4[1].x, b4[1].y));
        }
        if (i == 1) {
          __syncwarp();
#pragma unroll
          for (int n = 0; n < 2; n++)
#pragma unroll
            for (int k2 = 0; k2 < 4; k2++) ldsm4(bf + n * 16 + k2 * 4, stg + (n * 8 + (lane & 7)) * 272 + k2 * 64 + (lane >> 3) * 16);
          __syncwarp();
        }
      }
    }
    __syncwarp();
#pragma unroll
    for (int k2 = 0; k2 < 4; k2++) ldsm4(bf + 32 + k2 * 4, stg + (lane & 7) * 272 + k2 * 64 + (lane >> 3) * 16);
    release_rows();
    if (!(lane & 1)) {
#pragma unroll
      for (int i = 0; i < 6; i++) if (w_on(i)) asm volatile("prefetch.global.L2 [%0];" ::"l"(w_src(i)));
    }
    if (tid == 320) TR(0, 16);
    float c[6][4];
#pragma unroll
    for (int i = 0; i < 6; i++) { c[i][0] = 0.f; c[i][1] = 0.f; c[i][2] = 0.f; c[i][3] = 0.f; }
    cf p[2], v[2];
    p[0] = cexp_l(lr[0], li[0], 8.f); p[1] = cexp_l(lr[1], li[1], 8.f);
    v[0].x = 1.f; v[0].y = 0.f; v[1] = v[0];
#pragma unroll
    for (int mt = 0; mt < 2; mt++) {
      __syncwarp();
#pragma unroll
      for (int i = 0; i < 16; i++) {
        sts64(stg + i * 272 + lane * 8, pack_bf16(v[0].x, v[0].y), pack_bf16(v[1].x, v[1].y));
        if (mt == 0 && i == 0) { v[0] = p[0]; v[1] = p[1]; }
        else if (mt == 0 || i < 15) { v[0] = cmul(v[0], p[0]); v[1] = cmul(v[1], p[1]); }
      }
      __syncwarp();
      if (mt == 1 && tid == 160) {
        const uint32_t tgt = lds32(ep_addr) * 128u;
        uint32_t cv; int it = 0;
        do { asm volatile("ld.acquire.gpu.global.u32 %0, [%1];" : "=r"(cv) : "l"(&g_cnt1) : "memory"); } while ((int)(cv - tgt) < 0 && ++it < 200000);
        asm volatile("fence.proxy.async;" ::: "memory");
        TR(0, 9);
        mbar_expect(bar_rec, 32768);
        for (int c2 = 0; c2 < 4; c2++) bulk_ld(sb + c2 * A_CH + A_REC, g_ux + (size_t)(blk * 4 + c2) * 512, 8192, bar_rec);
      }
#pragma unroll
      for (int ks = 0; ks < 8; ks++) {
        uint32_t a[4];
        ldsm4(a, stg + (lane & 15) * 272 + ks * 32 + (lane >> 4) * 16);
#pragma unroll
        for (int n = 0; n < 3; n++) mma16816(c[n * 2 + mt], a, bf[n * 16 + ks * 2], bf[n * 16 + ks * 2 + 1]);
      }
    }
    __syncwarp();
#pragma unroll
    for (int i = 0; i < 6; i++)
      sts128(stg + i * 512 + lane * 16, __float_as_uint(c[i][0]), __float_as_uint(c[i][1]), __float_as_uint(c[i][2]), __float_as_uint(c[i][3]));
#pragma unroll
    for (int i = 0; i < 6; i++) if (w_on(i)) wv[i] = __ldg(w_src(i));
    bar_sync(1 + wg, 128);
    if (tid == 320) TR(0, 2);
#pragma unroll
    for (int rep = 0; rep < 2; rep++) {
      const int qd = rep ? 2 + wr : 3 - wr;
      if (rep == 0 || wr >= 2) {
        float s[4] = {0.f, 0.f, 0.f, 0.f};
#pragma unroll
        for (int w = 0; w < 4; w++) {
          uint4 u4 = lds128(cb + A_STG + w * 4352 + qd * 512 + lane * 16);
          s[0] += __uint_as_float(u4.x); s[1] += __uint_as_float(u4.y); s[2] += __uint_as_float(u4.z); s[3] += __uint_as_float(u4.w);
        }
#pragma unroll
        for (int hf = 0; hf < 2; hf++) {
          const int j = (qd & 1) * 16 + g + 8 * hf;
          const uint32_t pk = pack_bf16(s[2 * hf + 1], s[2 * hf]);
          const uint32_t v0 = pk >> 16, v1 = pk & 0xFFFFu, v00 = v0 * 0x10001u;
          if (rep == 1) {
            if (t < 2) {
#pragma unroll
              for (int e = 0; e < 2; e++) {
                const int lam = 128 + 32 * (2 * t + e) + j, mu = lam >> 1;
                const uint32_t val = e ? v1 : v0;
                uint32_t a = cb + ((lam & 1) ? A_R3B : A_R3A) + mu * 4;
                if (lam == 128) { a = cb + A_R2A + 128 * 4; sts32(cb + A_K1024, val << 16); }
                sts16(a, val); sts16(a + 6, val);
              }
            } else if (t == 2 && j == 0) { sts16(cb + A_R3A + 128 * 4, v0); }
          } else if (qd < 2) {
            const uint32_t a = cb + A_R1 + (62 + 8 * j + 2 * t) * 4;
            sts16(a, v0); sts32(a + 4, pk); sts16(a + 10, v1);
          } else if (t < 2) {
            const int L = 256 + 8 * j + 4 * t;
            const uint32_t a = cb + A_R1 + (62 + L) * 4;
            if (L > 256) { sts16(a - 4, v0); sts32(a, v00); } else sts16(a, v0);
            sts32(a + 4, v00); sts32(a + 8, pk); sts16(a + 14, v1);
          } else {
            const int mu = 64 + 32 * (t - 2) + j;
            if (mu == 64) {
              const uint32_t a = cb + A_R1 + (62 + 512) * 4;
              sts16(a - 4, v0); sts32(a, v00); sts32(a + 4, v00); sts32(a + 8, v00); sts16(a + 14, v0);
            } else { sts16(cb + A_R2A + mu * 4, v0); sts16(cb + A_R2A + mu * 4 + 6, v0); }
            sts16(cb + A_R2B + mu * 4, v1); sts16(cb + A_R2B + mu * 4 + 6, v1);
          }
        }
      }
    }
  }
  {
    const int ngg = (blk % 56) * 4 + (lane & 3), j = ngg / 28, q = (ngg % 28) / 14, ng = ngg % 14 + (blk < 56 ? 0 : 14);
    uint4* dst = g_wimg + (size_t)j * 37632 + q * 14 * 896 + ng * 32 + (warp >> 2) * 896 + (warp & 3) * 8 + (lane >> 2);
#pragma unroll
    for (int i = 0; i < 4; i++) if (w_on(i)) dst[i * 4 * 896] = wv[i];
#pragma unroll
    for (int i = 4; i < 6; i++) {
      const int it = warp + 16 * (i - 4), n2 = (it % 14) * 4 + (lane & 3), k = (blk % 7) * 16 + (it / 14) * 8 + (lane >> 2);
      if (w_on(i)) g_wimg[(size_t)(blk / 14) * 37632 + 25088 + ((n2 / 7) * 2 + (blk / 7) % 2) * 784 + (n2 % 7) * 112 + k] = wv[i];
    }
  }
  if (tid == 320) TR(0, 3);

  const int bk = wr * 32 + lane;
  uint32_t xt[8], ud[8];
  {
    mbar_wait(bar_rec, 0);
    if (tid == 320) TR(0, 4);
    uint4 r[4];
#pragma unroll
    for (int i = 0; i < 4; i++) r[i] = lds128(cb + A_REC + bk * 64 + ((i ^ (bk >> 1)) & 3) * 16);
    const uint32_t ua = cb + A_UB + ((2 * bk) & 7) * 656 + ((bk >> 2) + 9) * 16;
    sts128(ua, r[0].x, r[1].x, r[2].x, r[3].x);
    sts128(ua + 656, r[0].y, r[1].y, r[2].y, r[3].y);
    if (bk <= 96) {
      const bool neg = bk == 96;
      const int bp = neg ? -1 : bk;
      uint32_t h[4];
      h[0] = lds32(cb + A_REC + ((bp - 1) & 127) * 64 + ((2 ^ ((bp - 1) >> 1)) & 3) * 16 + 4);
      h[1] = lds32(cb + A_REC + ((bp - 1) & 127) * 64 + ((3 ^ ((bp - 1) >> 1)) & 3) * 16 + 4);
      h[2] = lds32(cb + A_REC + (bp + 1) * 64 + ((0 ^ ((bp + 1) >> 1)) & 3) * 16);
      h[3] = lds32(cb + A_REC + (bp + 1) * 64 + ((1 ^ ((bp + 1) >> 1)) & 3) * 16);
      if (bp <= 0) { h[0] = 0; h[1] = 0; }
      const uint32_t wd[12] = {h[0], h[1], neg ? 0 : r[0].x, neg ? 0 : r[1].x, neg ? 0 : r[2].x, neg ? 0 : r[3].x,
                               neg ? 0 : r[0].y, neg ? 0 : r[1].y, neg ? 0 : r[2].y, neg ? 0 : r[3].y, h[2], h[3]};
      float P[25];
      P[0] = 0.f;
#pragma unroll
      for (int i = 0; i < 12; i++) { P[2 * i + 1] = P[2 * i] + bf_lo(wd[i]); P[2 * i + 2] = P[2 * i + 1] + bf_hi(wd[i]); }
#define WIN(i, hw) (P[(i) + 5 + (hw)] - P[(i) + 4 - (hw)])
#define WPK(i, hw) pack_bf16(WIN(i, hw), WIN((i) + 1, hw))
      const int tp = 2 * bp;
      const uint32_t a3 = cb + A_W3 + (tp + 64) * 16 + 8, a5 = cb + A_W5 + (tp + 64) * 16;
      if (!neg) sts64(a3, WPK(0, 1), WPK(2, 1));
      if (!neg) sts128(a3 + 8, WPK(4, 1), WPK(6, 1), WPK(8, 1), WPK(10, 1));
      sts64(a3 + 24, WPK(12, 1), WPK(14, 1));
      sts128(a5, WPK(0, 2), WPK(2, 2), WPK(4, 2), WPK(6, 2));
      sts128(a5 + 16, WPK(8, 2), WPK(10, 2), WPK(12, 2), WPK(14, 2));
      if (bp < 64) {
        if (!neg) sts128(cb + A_W7 + 1024 + bp * 16, WPK(0, 3), WPK(2, 3), WPK(4, 3), WPK(6, 3));
        if (bp < 63) {
          sts128(cb + A_W7 + (bp + 1) * 16, WPK(8, 3), WPK(10, 3), WPK(12, 3), WPK(14, 3));
          sts128(cb + A_W9 + (bp + 1) * 16, WPK(0, 4), WPK(2, 4), WPK(4, 4), WPK(6, 4));
          sts128(cb + A_W9 + 1024 + (bp + 1) * 16, WPK(8, 4), WPK(10, 4), WPK(12, 4), WPK(14, 4));
        }
        if (!neg) {
#define VPK(i) pack_bf16(P[(i) + 2] - P[i], P[(i) + 3] - P[(i) + 1])
          sts128(cb + A_V + bp * 32, VPK(0), VPK(2), VPK(4), VPK(6));
          sts128(cb + A_V + bp * 32 + 16, VPK(8), VPK(10), VPK(12), VPK(14));
        }
      }
    }
  }
  asm volatile("fence.proxy.async.shared::cta;" ::: "memory");
  bar_sync(1 + wg, 128);
  if (tid == 320) TR(0, 5);

  {
    const uint32_t cbu = __shfl_sync(~0u, cb, 0);
    const uint32_t blo_k = ((cbu & 0x3FFFF) >> 4) | (41u << 16);
    const uint32_t blo_n = ((cbu & 0x3FFFF) >> 4) | (8u << 16);
    const uint32_t tb = cb + (16 * wq + g - 2 * t) * 4;
    float y1[16], y2[12], y3[8];
    const uint32_t dk16 = __ldg(dskip + ch);
    uint32_t qa[32], qb[32];
    const uint32_t t1 = tb + A_R1 + (62 - 48) * 4;
    load_quads<4>(qa, tb + A_R3A + 17 * 4); load_quads<4>(qa + 16, tb + A_R3B + 16 * 4);
    wg_fence();
    s3_steps<0, 4, A_W9, 1>(y3, qa, blo_n); s3_steps<0, 4, A_W7, 0>(y3, qa + 16, blo_n);
    wg_commit();
    load_quads<8>(qb, tb + A_R2A + 16 * 4);
    wg_fence(); s2_steps<0, 8, A_W5, 1>(y2, qb, blo_n); wg_commit();
    wg_wait<1>(); load_quads<8>(qa, tb + A_R2B + 16 * 4);
    wg_fence(); s2_steps<0, 8, A_W3, 0>(y2, qa, blo_n); wg_commit();
    wg_wait<1>(); load_quads<8>(qb, t1);
    wg_fence(); f1_steps<0, 8>(y1, qb, blo_k); wg_commit();
    wg_wait<1>(); load_quads<8>(qa, t1 + 8 * 64);
    wg_fence(); f1_steps<8, 8>(y1, qa, blo_k); wg_commit();
    reg_fence(y2); reg_fence(y3);
    if (tid == 320) TR(0, 18);
    {
      const float k1024 = __uint_as_float(lds32(cb + A_K1024));
#pragma unroll
      for (int i = 0; i < 2; i++)
#pragma unroll
        for (int hf = 0; hf < 2; hf++) {
          const int idx = 16 * (16 * wq + g + 8 * hf) + 8 * i + 2 * t;
          const uint32_t vv = lds32(cb + A_V + idx * 2);
          sts64(cb + A_Y3 + (idx + 4 * (idx >> 6)) * 4, __float_as_uint(fmaf(k1024, bf_lo(vv), y3[4 * i + 2 * hf])),
                __float_as_uint(fmaf(k1024, bf_hi(vv), y3[4 * i + 2 * hf + 1])));
        }
#pragma unroll
      for (int i = 0; i < 3; i++)
#pragma unroll
        for (int hf = 0; hf < 2; hf++) {
          const int idx = 512 * i + 8 * (16 * wq + g + 8 * hf) + 2 * t;
          sts64(cb + A_Y2 + (idx + 4 * (idx >> 6)) * 4, __float_as_uint(y2[4 * i + 2 * hf]), __float_as_uint(y2[4 * i + 2 * hf + 1]));
        }
    }
    wg_wait<1>(); load_quads<8>(qb, t1 + 16 * 64);
    wg_fence(); f1_steps<16, 8>(y1, qb, blo_k); wg_commit();
    wg_wait<1>(); load_quads<8>(qa, t1 + 24 * 64);
    wg_fence(); f1_steps<24, 8>(y1, qa, blo_k); wg_commit();
    wg_wait<1>(); load_quads<5>(qb, t1 + 32 * 64);
    wg_fence(); f1_steps<32, 5>(y1, qb, blo_k); wg_commit();
    bar_sync(1 + wg, 128);
    float ex[12];
#pragma unroll
    for (int i = 1; i < 4; i++)
#pragma unroll
      for (int k = 0; k < 4; k++) {
        const int aa = 8 * i + 2 * t + (k & 1), b = 16 * wq + g + 8 * (k >> 1);
        float e = __uint_as_float(lds32(cb + A_Y2 + ((aa - 8) * 68 + b) * 4));
        if (i >= 2) e += __uint_as_float(lds32(cb + A_Y3 + ((aa - 16) * 68 + b) * 4));
        ex[4 * (i - 1) + k] = e;
      }
    {
      const uint32_t dk = dk16 * 0x10001u;
#pragma unroll
      for (int i = 0; i < 4; i++) {
        const uint4 r = lds128(cb + A_REC + bk * 64 + ((i ^ (bk >> 1)) & 3) * 16);
        ud[i] = hmul2_bf(r.x, dk); ud[4 + i] = hmul2_bf(r.y, dk); xt[i] = r.z; xt[4 + i] = r.w;
      }
    }
    wg_wait<0>();
    reg_fence(y1);
    if (tid == 320) TR(0, 6);
#pragma unroll
    for (int i = 0; i < 12; i++) y1[4 + i] += ex[i];
#pragma unroll
    for (int i = 0; i < 2; i++) {
      const int mi = lane >> 3, aa = 8 * (2 * i + (mi >> 1)) + (lane & 7);
      asm volatile("stmatrix.sync.aligned.m8n8.x4.trans.shared.b16 [%0], {%1,%2,%3,%4};"
                   ::"r"(cb + A_YB + aa * 128 + (((2 * wq + (mi & 1)) ^ (lane & 7)) << 4)),
                     "r"(pack_bf16(y1[8 * i], y1[8 * i + 1])), "r"(pack_bf16(y1[8 * i + 2], y1[8 * i + 3])),
                     "r"(pack_bf16(y1[8 * i + 4], y1[8 * i + 5])), "r"(pack_bf16(y1[8 * i + 6], y1[8 * i + 7])) : "memory");
    }
  }
  bar_sync(1 + wg, 128);
#pragma unroll
  for (int c = 0; c < 2; c++) {
    const int tau = 2 * bk + c, r = ch & 7;
    const uint4 y = lds128(cb + A_YB + (tau >> 3) * 128 + (((tau ^ (tau >> 3)) & 7) << 4));
    g_himg[(size_t)(tau >> 4) * 7168 + (ch >> 3) * 128 + ((tau >> 3) & 1) * 64 + r * 8 + ((tau & 7) ^ r)] =
        make_uint4(hadd2_bf(xt[4 * c], hadd2_bf(y.x, ud[4 * c])), hadd2_bf(xt[4 * c + 1], hadd2_bf(y.y, ud[4 * c + 1])),
                   hadd2_bf(xt[4 * c + 2], hadd2_bf(y.z, ud[4 * c + 2])), hadd2_bf(xt[4 * c + 3], hadd2_bf(y.w, ud[4 * c + 3])));
  }
  if (tid == 320) TR(0, 7);
}

constexpr int B_SA = 0, B_RING = 114688, B_SLOT = 14848, B_NSLOT = 7;
constexpr int B_CS = B_RING + B_NSLOT * B_SLOT;
constexpr int B_RED = B_CS + 7168;
constexpr int B_BAR = B_RED + 256;
constexpr int B_SMEM = B_BAR + 1024, A_SMEM = 4 * A_CH + 64;

__device__ __forceinline__ uint32_t mapa(uint32_t a, uint32_t r) { uint32_t o; asm("mapa.shared::cluster.u32 %0, %1, %2;" : "=r"(o) : "r"(a), "r"(r)); return o; }
template <class T> __device__ __forceinline__ T* pin(T* p) { asm volatile("" : "+l"(p)); return p; }
__device__ __forceinline__ uint32_t pin(uint32_t v) { asm volatile("" : "+r"(v)); return v; }
template <int Q, int ST>
__device__ __forceinline__ void g1_stage(float (&acc)[116], uint32_t alo, uint32_t blo, uint32_t bar_full, uint32_t bar_h) {
  constexpr int s = Q * 14 + ST, sl = s % B_NSLOT;
  if (Q == 0) mbar_wait(bar_h + 8 * ST, 0);
  mbar_wait(bar_full + 8 * sl, (s / B_NSLOT) & 1);
  wg_fence();
  if (Q == 0) {
    wgmma_ss232<(2 * ST) * 256, 0x40000080u, (sl * B_SLOT) / 16, 32, ST != 0>(acc, alo, blo);
    wgmma_ss232<(2 * ST + 1) * 256, 0x40000080u, (sl * B_SLOT + 256) / 16, 32, 1>(acc, alo, blo);
  } else {
    wgmma_ss224<(2 * ST) * 256, 0x40000080u, (sl * B_SLOT) / 16, 32, ST != 0>(*(float(*)[112])acc, alo, blo);
    wgmma_ss224<(2 * ST + 1) * 256, 0x40000080u, (sl * B_SLOT + 256) / 16, 32, 1>(*(float(*)[112])acc, alo, blo);
  }
}

__global__ void __launch_bounds__(512, 1)
k_front(const __nv_bfloat16* __restrict__ x, const uint32_t* __restrict__ are, const uint32_t* __restrict__ aim,
        const uint32_t* __restrict__ bre, const uint32_t* __restrict__ bim, const uint32_t* __restrict__ cre,
        const uint32_t* __restrict__ cim, const unsigned short* __restrict__ logdt, const unsigned short* __restrict__ dskip,
        const uint4* __restrict__ wgate, const uint4* __restrict__ wup, const uint4* __restrict__ wdown) {
  extern __shared__ __align__(1024) unsigned char sm[];
  const uint32_t bar_rec = s2u(sm) + 4 * A_CH;
  if (threadIdx.x == 320) TR(0, 0);
  asm volatile("griddepcontrol.launch_dependents;");
  if (threadIdx.x == 160) { mbar_init(bar_rec, 1); asm volatile("fence.mbarrier_init.release.cluster;" ::: "memory"); }
  phase_a(sm, bar_rec, bar_rec + 8, x, are, aim, bre, bim, cre, cim, logdt, dskip, wgate, wup, wdown);
}

__global__ void __cluster_dims__(2, 1, 1) __launch_bounds__(384, 1) k_ffn(__nv_bfloat16* __restrict__ out) {
  extern __shared__ __align__(1024) unsigned char sm[];
  const uint32_t sb = s2u(sm);
  const int tid = threadIdx.x, wg = tid >> 7, warp = tid >> 5, lane = tid & 31;
  const uint32_t bar_full = sb + B_BAR, bar_empty = bar_full + 64, bar_h = bar_full + 128, bar_cs = bar_full + 240,
                 bar_g2 = bar_full + 248, bar_in = bar_full + 256, bar_hh = bar_full + 304, bar_afree = bar_full + 336, bar_out = bar_full + 352;
  if (tid == 0) {
    TR(1, 0);
    for (int i = 0; i < B_NSLOT; i++) { mbar_init(bar_full + 8 * i, 1); mbar_init(bar_empty + 8 * i, 2); }
    asm volatile("fence.mbarrier_init.release.cluster;" ::: "memory");
  } else if (tid == 32) {
    for (int i = 0; i < 14; i++) mbar_init(bar_h + 8 * i, 1);
    asm volatile("fence.mbarrier_init.release.cluster;" ::: "memory");
  } else if (tid == 64) {
    mbar_init(bar_cs, 1);
    mbar_init(bar_g2, 4);
    for (int i = 0; i < 6; i++) mbar_init(bar_in + 8 * i, 1);
    for (int i = 0; i < 4; i++) { mbar_init(bar_hh + 8 * i, 1); mbar_expect(bar_hh + 8 * i, 14336); }
    mbar_init(bar_afree, 4); mbar_init(bar_afree + 8, 2);
    for (int i = 0; i < 6; i++) mbar_init(bar_out + 8 * i, 128);
    asm volatile("fence.mbarrier_init.release.cluster;" ::: "memory");
  } else if (tid >= 128 && tid < 352) {
    sts128(sb + B_RING + ((tid - 128) >> 5) * B_SLOT + 14336 + (tid & 31) * 16, 0x3F803F80u, 0x3F803F80u, 0x3F803F80u, 0x3F803F80u);
  }
  asm volatile("fence.proxy.async.shared::cta;" ::: "memory");
  __syncthreads();
  asm volatile("barrier.cluster.arrive.relaxed.aligned;" ::: "memory");
  const int rank = blockIdx.x & 1, rt = blockIdx.x >> 3, j = blockIdx.x & 7, p = j >> 1, cg = 4 * rank + p;
  const int wq = warp & 3, t128 = tid & 127, g = lane >> 2, t = lane & 3;
  uint32_t ep, tag;
  auto load_ep = [&]() { asm volatile("ld.relaxed.gpu.global.u32 %0, [%1];" : "=r"(ep) : "l"(&g_cnt1) : "memory"); };
  auto a_slot = [&](int i, int own) { return B_SA + (i + (i >= own)) * 14336; };
  auto in_addr = [&](int q, int cw) { return sb + a_slot(4 + q, cg) + cw * 1792; };
  auto out_addr = [&](int cc, int w) { return sb + a_slot((cc & 2) + w, cg) + (cc & 1) * 7168; };
  auto in_cta = [&](int q) { return rt * 8 + ((p + 3 - q) & 3) * 2 + rank; };
  auto in_src = [&](int q, int cw) { return g_part + (size_t)(in_cta(q) * 3 + q) * 896 + cw * 112; };
  auto add_in = [&](float (&sum)[28], int q, int cw) {
    const uint32_t a = in_addr(q, cw);
    const uint4 v0 = lds128(a + lane * 16), v1 = lds128(a + 512 + lane * 16), v2 = lds128(a + 1024 + lane * 16);
    uint32_t in[14] = {v0.x, v0.y, v0.z, v0.w, v1.x, v1.y, v1.z, v1.w, v2.x, v2.y, v2.z, v2.w, 0, 0};
    asm volatile("ld.shared.v2.u32 {%0, %1}, [%2];" : "=r"(in[12]), "=r"(in[13]) : "r"(a + 1536 + lane * 8) : "memory");
    int it = 0;
    while ((((in[3] ^ tag) | (in[7] ^ tag) | (in[11] ^ tag) | (in[13] ^ tag)) & 0x10000u) && ++it < 400000) {
      const uint4* gs = pin(in_src(q, cw));
#pragma unroll
      for (int i = 0; i < 3; i++) ld128(gs + i * 32 + lane, in + 4 * i);
      asm volatile("{\n.reg .b64 v;\nld.relaxed.gpu.global.b64 v, [%2];\nmov.b64 {%0, %1}, v;\n}"
                   : "=r"(in[12]), "=r"(in[13]) : "l"((const uint2*)(gs + 96) + lane) : "memory");
    }
#pragma unroll
    for (int i = 0; i < 14; i++) { sum[2 * i] += bf_lo(in[i]); sum[2 * i + 1] += bf_hi(in[i]); }
  };
  auto w_issue = [&](int s) {
    const char* wsrc = (const char*)g_wimg + (size_t)j * 602112;
    const int slot = s % B_NSLOT;
    const uint32_t dst = sb + B_RING + slot * B_SLOT, fb = bar_full + 8 * slot;
    if (s < 28) {
      mbar_expect(fb, 14336);
      bulk_ld(dst, wsrc + s * 14336, 14336, fb);
    } else {
      const int i = s - 28;
      const int ci = i < 3 ? 0 : i < 6 ? 1 : i < 8 ? i - 6 : i < 12 ? 2 : 3;
      const int kp = i < 3 ? i : i < 6 ? i - 3 : i < 8 ? 3 : (i & 3);
      mbar_expect(fb, 12544);
      bulk_ld(dst, (const char*)g_wimg + (size_t)(j ^ (kp >> 1)) * 602112 + 401408 + ((4 * rank + ((p + 1 + ci) & 3)) * 2 + (kp & 1)) * 12544, 12544, fb);
    }
  };

  if (wg == 2) {
    asm volatile("setmaxnreg.dec.sync.aligned.u32 40;");
    asm volatile("barrier.cluster.wait.aligned;" ::: "memory");
    asm volatile("griddepcontrol.wait;" ::: "memory");
    if (warp == 8) {
      if (lane == 0) {
        TR(1, 1);
        for (int s = 0; s < 44; s++) {
          if (s >= B_NSLOT) mbar_wait(bar_empty + 8 * (s % B_NSLOT), (s / B_NSLOT - 1) & 1);
          w_issue(s);
        }
      }
    } else if (warp == 9) {
      if (lane == 0) {
        const char* hsrc = (const char*)g_himg + (size_t)rt * 114688;
        for (int i = 0; i < 14; i++) {
          mbar_expect(bar_h + 8 * i, 8192);
          bulk_ld_mc(sb + B_SA + i * 8192 + rank * 4096, hsrc + i * 8192 + rank * 4096, 4096, bar_h + 8 * i);
        }
        mbar_expect(bar_cs, 7168);
        bulk_ld(sb + B_CS, g_cimg + j * 448, 7168, bar_cs);
      }
      __syncwarp();
      load_ep(); ep >>= 7;
      const int lq = (lane >> 1) & 3, lcw = (lane & 1) * 4;
      const uint32_t* fl = g_flag + in_cta(lq) * 8 + (lane & 7);
      bool todo = lane < 6, live = false;
      int it = 0;
      while (__any_sync(~0u, todo) && ++it < 400000) {
        if (!live) { __nanosleep(400); live = mbar_test(bar_g2, 0); }
        if (todo) {
          uint32_t w;
          asm volatile("ld.relaxed.gpu.global.u32 %0, [%1];" : "=r"(w) : "l"(fl) : "memory");
          if (live && w == ep) {
            mbar_expect(bar_in + 8 * lane, 7168);
            bulk_ld(in_addr(lq, lcw), in_src(lq, lcw), 7168, bar_in + 8 * lane);
            todo = false;
            if (lane & 1) TR(1, 24 + lq);
          }
        }
      }
    } else {
      const int t64 = tid - 320;
      load_ep();
      const int r = (lane >> 1) & 7, c = (j & 3) * 2 + (lane & 1);
      const uint32_t src = sb + B_SA + (t64 >> 4) * 2048 + (j >> 2) * 1024 + r * 128 + ((c ^ r) << 4);
      float a[16];
#pragma unroll
      for (int k = 0; k < 16; k++) a[k] = 0.f;
#pragma unroll 1
      for (int i = 0; i < 14; i++) {
        mbar_wait(bar_h + 8 * i, 0);
        uint4 v = lds128(src + i * 8192);
        float e[8] = {bf_lo(v.x), bf_hi(v.x), bf_lo(v.y), bf_hi(v.y), bf_lo(v.z), bf_hi(v.z), bf_lo(v.w), bf_hi(v.w)};
#pragma unroll
        for (int k = 0; k < 8; k++) { a[2 * k] += e[k]; a[2 * k + 1] = fmaf(e[k], e[k], a[2 * k + 1]); }
        __nanosleep(160);
      }
      __syncwarp();
      if (lane == 0) { mbar_arrive(bar_g2); asm volatile("mbarrier.arrive.shared::cluster.b64 _, [%0];" ::"r"(mapa(bar_afree, rank ^ 1)) : "memory"); }
#pragma unroll
      for (int rd = 0; rd < 4; rd++) {
        const int n = 8 >> rd;
        const bool up = lane & (2 * n);
#pragma unroll
        for (int k = 0; k < 8; k++) {
          if (k < n) {
            float keep = up ? a[k + n] : a[k], give = up ? a[k] : a[k + n];
            a[k] = keep + __shfl_xor_sync(~0u, give, 2 * n);
          }
        }
      }
      float* red = (float*)(sm + B_RED);
      red[(warp & 1) * 32 + (lane & 1) * 16 + (lane >> 1)] = a[0];
      bar_sync(1, 64);
      if (t64 < 16) {
        float mean = (red[2 * t64] + red[32 + 2 * t64]) * (1.f / DM);
        float var = fmaxf(fmaf(-mean, mean, (red[2 * t64 + 1] + red[33 + 2 * t64]) * (1.f / DM)), 0.f);
        float rs = __frcp_rn(rbf(__fsqrt_rn(rbf(rbf(var) + 1e-5f))));
        asm volatile("st.relaxed.gpu.global.u32 [%0], %1;"
                     ::"l"(g_stat2 + rt * 128 + j * 16 + t64), "r"((__float_as_uint(rs * rs) & ~1u) | ((ep >> 7) & 1u)) : "memory");
      }
      if (t64 == 0) TR(1, 2);
      if (lane == 0) {
        const int w = warp & 1;
        for (int cc = 0; cc < 3; cc++) {
          mbar_wait(bar_out + 8 * (cc * 2 + w), 0);
          asm volatile("cp.async.bulk.global.shared::cta.bulk_group [%0], [%1], 7168;"
                       ::"l"(g_part + (size_t)(blockIdx.x * 3 + cc) * 896 + w * 448), "r"(out_addr(cc, w)) : "memory");
          asm volatile("cp.async.bulk.commit_group;" ::: "memory");
          asm volatile("cp.async.bulk.wait_group 0;" ::: "memory");
          asm volatile("st.relaxed.gpu.global.u32 [%0], %1;" ::"l"(g_flag + blockIdx.x * 8 + cc * 2 + w), "r"(ep >> 7) : "memory");
          if (w) TR(1, 27 + cc);
        }
      }
    }
  } else {
    asm volatile("setmaxnreg.inc.sync.aligned.u32 232;");
    asm volatile("barrier.cluster.wait.aligned;" ::: "memory");
    uint32_t hh[56];
    const bool relt = t128 == 0;
    auto release = [&](int sl) { if (relt) mbar_arrive(bar_empty + 8 * sl); };
    auto send_hh = [&](int q) {
      const uint32_t da = mapa(sb + a_slot(2 * q + wg, cg ^ 4) + t128 * 16, rank ^ 1), db = mapa(bar_hh + 8 * (2 * q + wg), rank ^ 1);
#pragma unroll
      for (int i = 0; i < 7; i++)
        asm volatile("st.async.weak.shared::cluster.mbarrier::complete_tx::bytes.v4.b32 [%0], {%1, %2, %3, %4}, [%5];"
                     ::"r"(da + i * 2048), "r"(hh[28 * q + 4 * i]), "r"(hh[28 * q + 4 * i + 1]),
                       "r"(hh[28 * q + 4 * i + 2]), "r"(hh[28 * q + 4 * i + 3]), "r"(db) : "memory");
    };
    const uint32_t alo = __shfl_sync(~0u, ((sb + B_SA + wg * 1024) & 0x3FFFF) >> 4, 0);
    const uint32_t blo = (((sb + B_RING) & 0x3FFFF) >> 4) | (8u << 16);
    const uint32_t clo = ((sb + B_CS) & 0x3FFFF) >> 4;
    uint32_t nm0, nm1;
    if (wg == 1) bar_sync(3, 256);
#define G1S(Q, ST) do { g1_stage<Q, ST>(acc, alo, blo, bar_full, bar_h); wg_commit(); \
      if (ST > 0) { wg_wait<1>(); release((Q * 14 + ST - 1) % B_NSLOT); } } while (0)
#define G1HH(Q) do { \
      _Pragma("unroll") \
      for (int i = 0; i < 28; i++) hh[28 * Q + i] = pack_bf16(acc[2 * i] * acc[56 + 2 * i], acc[2 * i + 1] * acc[57 + 2 * i]); \
    } while (0)
    {
      float acc[116];
      G1S(0, 0);
      if (tid == 0) TR(1, 3);
      G1S(0, 1);
      if (wg == 0) asm volatile("bar.arrive 3, 256;" ::: "memory");
      G1S(0, 2); G1S(0, 3); G1S(0, 4); G1S(0, 5); G1S(0, 6); G1S(0, 7); G1S(0, 8); G1S(0, 9); G1S(0, 10); G1S(0, 11); G1S(0, 12);
      G1S(0, 13);
      if (tid == 0) TR(1, 4);
      mbar_wait(bar_cs, 0);
      wg_wait<0>(); reg_fence(acc); release(13 % B_NSLOT);
      {
        const uint32_t msk = t == 0 ? 0xFFFFFFFFu : t == 1 ? 0xFFFFu : 0u;
        const float a = acc[112] * (-1.f / DM), b = acc[114] * (-1.f / DM);
        nm0 = pack_bf16(a, a) & msk; nm1 = pack_bf16(b, b) & msk;
      }
      wg_fence();
      wgmma_rs224<0, 8, 1>(*(float(*)[112])acc, nm0, nm1, 0u, 0u, clo);
      wg_commit(); wg_wait<0>(); reg_fence(acc);
      G1HH(0);
      if (tid == 0) TR(1, 5);
      G1S(1, 0); G1S(1, 1); G1S(1, 2); G1S(1, 3); G1S(1, 4); G1S(1, 5); G1S(1, 6);
      if (relt) asm volatile("mbarrier.arrive.shared::cluster.b64 _, [%0];" ::"r"(mapa(bar_afree, rank ^ 1)) : "memory");
      G1S(1, 7); G1S(1, 8); G1S(1, 9);
      if (relt) asm volatile("mbarrier.arrive.shared::cluster.b64 _, [%0];" ::"r"(mapa(bar_afree + 8, rank ^ 1)) : "memory");
      mbar_wait(bar_afree, 0);
      send_hh(0);
      G1S(1, 10); G1S(1, 11); G1S(1, 12);
      load_ep();
      g1_stage<1, 13>(acc, alo, blo, bar_full, bar_h);
      wgmma_rs224<224, 8, 1>(*(float(*)[112])acc, nm0, nm1, 0u, 0u, clo);
      wg_commit(); wg_wait<1>(); release(26 % B_NSLOT);
      wg_wait<0>(); reg_fence(acc); release(27 % B_NSLOT);
      if (t128 == 0) mbar_arrive(bar_g2);
      G1HH(1);
      if (tid == 0) TR(1, 6);
    }
    float accA[28], accB[28], accC[28];
    uint32_t ph0[28], ph1[28];
    ep = pin(ep >> 7); tag = pin((ep & 1u) << 16);
#define ISSUE(acc, I, a, FIRST) do { \
      constexpr int s_ = 28 + (I), sl_ = s_ % B_NSLOT; \
      mbar_wait(bar_full + 8 * sl_, (s_ / B_NSLOT) & 1); \
      wg_fence(); \
      wgmma_rs56<(sl_ * B_SLOT + 0 * 256) / 16, 112, !(FIRST)>(acc, (a)[0], (a)[1], (a)[2], (a)[3], blo); \
      wgmma_rs56<(sl_ * B_SLOT + 1 * 256) / 16, 112, 1>(acc, (a)[4], (a)[5], (a)[6], (a)[7], blo); \
      wgmma_rs56<(sl_ * B_SLOT + 2 * 256) / 16, 112, 1>(acc, (a)[8], (a)[9], (a)[10], (a)[11], blo); \
      wgmma_rs56<(sl_ * B_SLOT + 3 * 256) / 16, 112, 1>(acc, (a)[12], (a)[13], (a)[14], (a)[15], blo); \
      wgmma_rs56<(sl_ * B_SLOT + 4 * 256) / 16, 112, 1>(acc, (a)[16], (a)[17], (a)[18], (a)[19], blo); \
      wgmma_rs56<(sl_ * B_SLOT + 5 * 256) / 16, 112, 1>(acc, (a)[20], (a)[21], (a)[22], (a)[23], blo); \
      wgmma_rs56<(sl_ * B_SLOT + 6 * 256) / 16, 112, 1>(acc, (a)[24], (a)[25], (a)[26], (a)[27], blo); \
      wg_commit(); } while (0)
    auto rel = [&](int i) { release((28 + i) % B_NSLOT); };
    auto tg = [&](uint32_t v) { return (v & 0xFFFEFFFFu) | tag; };
    auto send = [&](float (&acc)[28], int cc) {
      reg_fence(acc);
      const uint32_t a = out_addr(cc, wg) + wq * 1792;
#pragma unroll
      for (int q = 0; q < 3; q++)
        sts128(a + q * 512 + lane * 16, pack_bf16(acc[8 * q], acc[8 * q + 1]), pack_bf16(acc[8 * q + 2], acc[8 * q + 3]),
               pack_bf16(acc[8 * q + 4], acc[8 * q + 5]), tg(pack_bf16(acc[8 * q + 6], acc[8 * q + 7])));
      sts64(a + 1536 + lane * 8, pack_bf16(acc[24], acc[25]), tg(pack_bf16(acc[26], acc[27])));
      asm volatile("fence.proxy.async.shared::cta;" ::: "memory");
      mbar_arrive(bar_out + 8 * (cc * 2 + wg));
    };
    auto load_hh = [&](uint32_t (&d)[28], int q) {
      mbar_wait(bar_hh + 8 * (2 * q + wg), 0);
      const uint32_t a = sb + a_slot(2 * q + wg, cg) + t128 * 16;
#pragma unroll
      for (int i = 0; i < 7; i++) {
        const uint4 v = lds128(a + i * 2048);
        d[4 * i] = v.x; d[4 * i + 1] = v.y; d[4 * i + 2] = v.z; d[4 * i + 3] = v.w;
      }
    };
    ISSUE(accA, 0, hh, true);
    mbar_wait(bar_afree + 8, 0);
    send_hh(1);
    ISSUE(accA, 1, hh + 28, false);
    load_hh(ph0, 0);
    wg_wait<1>(); rel(0);
    ISSUE(accA, 2, ph0, false);      wg_wait<1>(); rel(1);
    ISSUE(accB, 3, hh, true);        wg_wait<1>(); rel(2);
    ISSUE(accB, 4, hh + 28, false);  wg_wait<1>(); rel(3);
    ISSUE(accB, 5, ph0, false);
    if (tid == 0) TR(1, 11);
    load_hh(ph1, 1);
    wg_wait<1>(); rel(4);
    ISSUE(accA, 6, ph1, false);      wg_wait<1>(); rel(5);
    ISSUE(accB, 7, ph1, false);      wg_wait<1>(); rel(6);
    ISSUE(accC, 8, hh, true);        send(accA, 0); wg_wait<1>(); rel(7);
    if (tid == 0) TR(1, 13);
    ISSUE(accC, 9, hh + 28, false);  send(accB, 1); wg_wait<1>(); rel(8);
    ISSUE(accC, 10, ph0, false);
    ISSUE(accC, 11, ph1, false);
    const int row = rt * 128 + wg * 64 + wq * 16 + g;
    uint32_t r20, r21;
    asm volatile("ld.relaxed.gpu.global.u32 %0, [%1];" : "=r"(r20) : "l"(g_stat2 + row) : "memory");
    asm volatile("ld.relaxed.gpu.global.u32 %0, [%1];" : "=r"(r21) : "l"(g_stat2 + row + 8) : "memory");
    ISSUE(accB, 12, hh, true);
    wg_wait<1>();
    send(accC, 2);
    if (tid == 0) TR(1, 16);
    ISSUE(accB, 13, hh + 28, false);
    ISSUE(accB, 14, ph0, false);
    ISSUE(accB, 15, ph1, false);
    if (tid == 0) TR(1, 7);
    uint32_t hres[16];
#pragma unroll
    for (int i = 0; i < 4; i++) {
      int qq = lane >> 3, r = lane & 7, kg = 7 * cg + 2 * i + (qq >> 1), c = 2 * wq + (qq & 1);
      if (kg > 55) kg = 55;
      asm volatile("ldmatrix.sync.aligned.m8n8.x4.trans.shared.b16 {%0,%1,%2,%3}, [%4];"
                   : "=r"(hres[4 * i]), "=r"(hres[4 * i + 1]), "=r"(hres[4 * i + 2]), "=r"(hres[4 * i + 3])
                   : "r"(sb + B_SA + kg * 2048 + wg * 1024 + r * 128 + ((c ^ r) << 4)) : "memory");
    }
    {
      int it = 0;
      while ((((r20 ^ ep) | (r21 ^ ep)) & 1u) && ++it < 400000) {
        asm volatile("ld.relaxed.gpu.global.u32 %0, [%1];" : "=r"(r20) : "l"(g_stat2 + row) : "memory");
        asm volatile("ld.relaxed.gpu.global.u32 %0, [%1];" : "=r"(r21) : "l"(g_stat2 + row + 8) : "memory");
      }
    }
    wg_wait<0>();
    reg_fence(accB);
    if (tid == 0) TR(1, 9);
#pragma unroll 1
    for (int q = 0; q < 3; q++) {
      mbar_wait(bar_in + 8 * (2 * q + wg), 0);
      add_in(accB, q, warp);
      if (tid == 0 && q == 1) TR(1, 12);
    }
    uint32_t* o0 = (uint32_t*)(out + (size_t)row * DM + 56 * cg + 2 * t);
    uint32_t* o1 = o0 + 8 * DM / 2;
#pragma unroll
    for (int i = 0; i < 7; i++) {
      o0[4 * i] = hadd2_bf(hres[2 * i], pack_bf16(accB[4 * i] * __uint_as_float(r20), accB[4 * i + 1] * __uint_as_float(r20)));
      o1[4 * i] = hadd2_bf(hres[2 * i + 1], pack_bf16(accB[4 * i + 2] * __uint_as_float(r21), accB[4 * i + 3] * __uint_as_float(r21)));
    }
    if (tid == 0) TR(1, 10);
    if (tid == 128) TR(1, 15);
  }
}

extern "C" void kernel_launch(void* const* d_in, const int* in_sizes, int n_in, void* d_out, int out_size) {
  const __nv_bfloat16* x = (const __nv_bfloat16*)d_in[0];
  const __nv_bfloat16 *are = (const __nv_bfloat16*)d_in[1], *aim = (const __nv_bfloat16*)d_in[2], *bre = (const __nv_bfloat16*)d_in[3],
                      *bim = (const __nv_bfloat16*)d_in[4], *cre = (const __nv_bfloat16*)d_in[5], *cim = (const __nv_bfloat16*)d_in[6],
                      *logdt = (const __nv_bfloat16*)d_in[7], *dskip = (const __nv_bfloat16*)d_in[8];
  const __nv_bfloat16 *wg = (const __nv_bfloat16*)d_in[10], *wu = (const __nv_bfloat16*)d_in[11], *wd = (const __nv_bfloat16*)d_in[12];

  static bool init = false;
  if (!init) {
    init = true;
    cudaFuncSetAttribute(k_ffn, cudaFuncAttributeMaxDynamicSharedMemorySize, B_SMEM);
    cudaFuncSetAttribute(k_front, cudaFuncAttributeMaxDynamicSharedMemorySize, A_SMEM);
  }
  cudaStream_t st = cudaStreamPerThread;
  k_front<<<128, 512, A_SMEM, st>>>(
      x, (const uint32_t*)are, (const uint32_t*)aim, (const uint32_t*)bre, (const uint32_t*)bim, (const uint32_t*)cre, (const uint32_t*)cim,
      (const unsigned short*)logdt, (const unsigned short*)dskip, (const uint4*)wg, (const uint4*)wu, (const uint4*)wd);
  cudaLaunchConfig_t cfg = {};
  cfg.gridDim = dim3(128); cfg.blockDim = dim3(384); cfg.dynamicSmemBytes = B_SMEM; cfg.stream = st;
  cudaLaunchAttribute at[1];
  at[0].id = cudaLaunchAttributeProgrammaticStreamSerialization; at[0].val.programmaticStreamSerializationAllowed = 1;
  cfg.attrs = at; cfg.numAttrs = 1;
  cudaLaunchKernelEx(&cfg, k_ffn, (__nv_bfloat16*)d_out);
}
```

```cpp
#include <cuda_runtime.h>
#include <cuda_bf16.h>
#include <stdint.h>

constexpr int LSEQ = 2048, DM = 448;

__device__ uint4    g_himg[16 * 114688 / 16];
__device__ uint4    g_cimg[8 * 2 * 224];
__device__ uint32_t g_stat2[LSEQ];
__device__ uint4    g_part[128 * 3 * 896];
__device__ uint4    g_wimg[8 * 602112 / 16];
__device__ uint4    g_ux[DM * 128 * 4];
__device__ unsigned g_cnt1;
__device__ uint32_t g_flag[128 * 8];

#define TR(k, i) do {} while (0)
__device__ __forceinline__ uint32_t s2u(const void* p) { return (uint32_t)__cvta_generic_to_shared(p); }
__device__ __forceinline__ void mbar_init(uint32_t b, int c) { asm volatile("mbarrier.init.shared::cta.b64 [%0], %1;" ::"r"(b), "r"(c)); }
__device__ __forceinline__ void mbar_expect(uint32_t b, int bytes) { asm volatile("mbarrier.arrive.expect_tx.shared::cta.b64 _, [%0], %1;" ::"r"(b), "r"(bytes) : "memory"); }
__device__ __forceinline__ void mbar_arrive(uint32_t b) { asm volatile("mbarrier.arrive.shared::cta.b64 _, [%0];" ::"r"(b) : "memory"); }
__device__ __forceinline__ void mbar_wait(uint32_t b, int ph) {
  asm volatile("{\n.reg .pred p;\n.reg .b32 n;\nmov.b32 n, 0;\nLW:\nmbarrier.try_wait.parity.shared::cta.b64 p, [%0], %1;\n@p bra LD;\n"
               "add.u32 n, n, 1;\nsetp.lt.u32 p, n, 4000000;\n@p bra LW;\ntrap;\nLD:\n}" ::"r"(b), "r"(ph) : "memory");
}
__device__ __forceinline__ bool mbar_test(uint32_t b, int ph) {
  uint32_t ok;
  asm volatile("{\n.reg .pred p;\nmbarrier.test_wait.parity.shared::cta.b64 p, [%1], %2;\nselp.u32 %0, 1, 0, p;\n}" : "=r"(ok) : "r"(b), "r"(ph) : "memory");
  return ok;
}
__device__ __forceinline__ void wg_fence() { asm volatile("wgmma.fence.sync.aligned;" ::: "memory"); }
__device__ __forceinline__ void wg_commit() { asm volatile("wgmma.commit_group.sync.aligned;" ::: "memory"); }
template <int N> __device__ __forceinline__ void wg_wait() { asm volatile("wgmma.wait_group.sync.aligned %0;" ::"n"(N) : "memory"); }
template <int N> __device__ __forceinline__ void reg_fence(float (&a)[N]) {
#pragma unroll
  for (int i = 0; i < N; i++) asm volatile("" : "+f"(a[i])::"memory");
}
__device__ __forceinline__ uint32_t pack_bf16(float lo, float hi) {
  uint32_t r; asm("cvt.rn.bf16x2.f32 %0, %1, %2;" : "=r"(r) : "f"(hi), "f"(lo)); return r;
}
__device__ __forceinline__ float bf_lo(uint32_t v) { return __uint_as_float(v << 16); }
__device__ __forceinline__ float bf_hi(uint32_t v) { return __uint_as_float(v & 0xFFFF0000u); }
__device__ __forceinline__ float rbf(float x) { return __bfloat162float(__float2bfloat16_rn(x)); }
__device__ __forceinline__ uint32_t hmul2_bf(uint32_t a, uint32_t b) { uint32_t r; asm("mul.rn.bf16x2 %0, %1, %2;" : "=r"(r) : "r"(a), "r"(b)); return r; }
__device__ __forceinline__ uint32_t hadd2_bf(uint32_t a, uint32_t b) { uint32_t r; asm("add.rn.bf16x2 %0, %1, %2;" : "=r"(r) : "r"(a), "r"(b)); return r; }
__device__ __forceinline__ void bulk_ld(uint32_t dst, const void* src, int bytes, uint32_t bar) {
  asm volatile("cp.async.bulk.shared::cluster.global.mbarrier::complete_tx::bytes [%0], [%1], %2, [%3];"
               ::"r"(dst), "l"(src), "r"(bytes), "r"(bar) : "memory");
}

__device__ __forceinline__ void bulk_ld_mc(uint32_t dst, const void* src, int bytes, uint32_t bar) {
  asm volatile("cp.async.bulk.shared::cluster.global.mbarrier::complete_tx::bytes.multicast::cluster [%0], [%1], %2, [%3], %4;"
               ::"r"(dst), "l"(src), "r"(bytes), "r"(bar), "h"((uint16_t)3) : "memory");
}
template <int AOFF, uint32_t AHI, int BOFF, uint32_t BHI, int ACC>
__device__ __forceinline__ void wgmma_ss224(float (&d)[112], uint32_t alo, uint32_t blo) {
  asm volatile("{\n.reg .pred p;\n.reg .b64 ad, bd;\nsetp.ne.b32 p, %118, 0;\n"
    "mov.b64 ad, {%112, %115};\nadd.s64 ad, ad, %114;\nmov.b64 bd, {%113, %117};\nadd.s64 bd, bd, %116;\n"
    "wgmma.mma_async.sync.aligned.m64n224k16.f32.bf16.bf16 {%0,%1,%2,%3,%4,%5,%6,%7,%8,%9,%10,%11,%12,%13,%14,%15,%16,%17,%18,%19,%20,%21,%22,%23,%24,%25,%26,%27,%28,%29,%30,%31,%32,%33,%34,%35,%36,%37,%38,%39,%40,%41,%42,%43,%44,%45,%46,%47,%48,%49,%50,%51,%52,%53,%54,%55,%56,%57,%58,%59,%60,%61,%62,%63,%64,%65,%66,%67,%68,%69,%70,%71,%72,%73,%74,%75,%76,%77,%78,%79,%80,%81,%82,%83,%84,%85,%86,%87,%88,%89,%90,%91,%92,%93,%94,%95,%96,%97,%98,%99,%100,%101,%102,%103,%104,%105,%106,%107,%108,%109,%110,%111}, ad, bd, p, 1, 1, 1, 1;\n}\n"
    : "+f"(d[0]),"+f"(d[1]),"+f"(d[2]),"+f"(d[3]),"+f"(d[4]),"+f"(d[5]),"+f"(d[6]),"+f"(d[7]),"+f"(d[8]),"+f"(d[9]),"+f"(d[10]),"+f"(d[11]),"+f"(d[12]),"+f"(d[13]),"+f"(d[14]),"+f"(d[15]),"+f"(d[16]),"+f"(d[17]),"+f"(d[18]),"+f"(d[19]),"+f"(d[20]),"+f"(d[21]),"+f"(d[22]),"+f"(d[23]),"+f"(d[24]),"+f"(d[25]),"+f"(d[26]),"+f"(d[27]),"+f"(d[28]),"+f"(d[29]),"+f"(d[30]),"+f"(d[31]),"+f"(d[32]),"+f"(d[33]),"+f"(d[34]),"+f"(d[35]),"+f"(d[36]),"+f"(d[37]),"+f"(d[38]),"+f"(d[39]),"+f"(d[40]),"+f"(d[41]),"+f"(d[42]),"+f"(d[43]),"+f"(d[44]),"+f"(d[45]),"+f"(d[46]),"+f"(d[47]),"+f"(d[48]),"+f"(d[49]),"+f"(d[50]),"+f"(d[51]),"+f"(d[52]),"+f"(d[53]),"+f"(d[54]),"+f"(d[55]),"+f"(d[56]),"+f"(d[57]),"+f"(d[58]),"+f"(d[59]),"+f"(d[60]),"+f"(d[61]),"+f"(d[62]),"+f"(d[63]),"+f"(d[64]),"+f"(d[65]),"+f"(d[66]),"+f"(d[67]),"+f"(d[68]),"+f"(d[69]),"+f"(d[70]),"+f"(d[71]),"+f"(d[72]),"+f"(d[73]),"+f"(d[74]),"+f"(d[75]),"+f"(d[76]),"+f"(d[77]),"+f"(d[78]),"+f"(d[79]),"+f"(d[80]),"+f"(d[81]),"+f"(d[82]),"+f"(d[83]),"+f"(d[84]),"+f"(d[85]),"+f"(d[86]),"+f"(d[87]),"+f"(d[88]),"+f"(d[89]),"+f"(d[90]),"+f"(d[91]),"+f"(d[92]),"+f"(d[93]),"+f"(d[94]),"+f"(d[95]),"+f"(d[96]),"+f"(d[97]),"+f"(d[98]),"+f"(d[99]),"+f"(d[100]),"+f"(d[101]),"+f"(d[102]),"+f"(d[103]),"+f"(d[104]),"+f"(d[105]),"+f"(d[106]),"+f"(d[107]),"+f"(d[108]),"+f"(d[109]),"+f"(d[110]),"+f"(d[111])
    : "r"(alo), "r"(blo), "n"(AOFF), "n"(AHI), "n"(BOFF), "n"(BHI), "n"(ACC));
}
template <int AOFF, uint32_t AHI, int BOFF, uint32_t BHI, int ACC>
__device__ __forceinline__ void wgmma_ss232(float (&d)[116], uint32_t alo, uint32_t blo) {
  asm volatile("{\n.reg .pred p;\n.reg .b64 ad, bd;\nsetp.ne.b32 p, %122, 0;\n"
    "mov.b64 ad, {%116, %119};\nadd.s64 ad, ad, %118;\nmov.b64 bd, {%117, %121};\nadd.s64 bd, bd, %120;\n"
    "wgmma.mma_async.sync.aligned.m64n232k16.f32.bf16.bf16 {%0,%1,%2,%3,%4,%5,%6,%7,%8,%9,%10,%11,%12,%13,%14,%15,%16,%17,%18,%19,%20,%21,%22,%23,%24,%25,%26,%27,%28,%29,%30,%31,%32,%33,%34,%35,%36,%37,%38,%39,%40,%41,%42,%43,%44,%45,%46,%47,%48,%49,%50,%51,%52,%53,%54,%55,%56,%57,%58,%59,%60,%61,%62,%63,%64,%65,%66,%67,%68,%69,%70,%71,%72,%73,%74,%75,%76,%77,%78,%79,%80,%81,%82,%83,%84,%85,%86,%87,%88,%89,%90,%91,%92,%93,%94,%95,%96,%97,%98,%99,%100,%101,%102,%103,%104,%105,%106,%107,%108,%109,%110,%111,%112,%113,%114,%115}, ad, bd, p, 1, 1, 1, 1;\n}\n"
    : "+f"(d[0]),"+f"(d[1]),"+f"(d[2]),"+f"(d[3]),"+f"(d[4]),"+f"(d[5]),"+f"(d[6]),"+f"(d[7]),"+f"(d[8]),"+f"(d[9]),"+f"(d[10]),"+f"(d[11]),"+f"(d[12]),"+f"(d[13]),"+f"(d[14]),"+f"(d[15]),"+f"(d[16]),"+f"(d[17]),"+f"(d[18]),"+f"(d[19]),"+f"(d[20]),"+f"(d[21]),"+f"(d[22]),"+f"(d[23]),"+f"(d[24]),"+f"(d[25]),"+f"(d[26]),"+f"(d[27]),"+f"(d[28]),"+f"(d[29]),"+f"(d[30]),"+f"(d[31]),"+f"(d[32]),"+f"(d[33]),"+f"(d[34]),"+f"(d[35]),"+f"(d[36]),"+f"(d[37]),"+f"(d[38]),"+f"(d[39]),"+f"(d[40]),"+f"(d[41]),"+f"(d[42]),"+f"(d[43]),"+f"(d[44]),"+f"(d[45]),"+f"(d[46]),"+f"(d[47]),"+f"(d[48]),"+f"(d[49]),"+f"(d[50]),"+f"(d[51]),"+f"(d[52]),"+f"(d[53]),"+f"(d[54]),"+f"(d[55]),"+f"(d[56]),"+f"(d[57]),"+f"(d[58]),"+f"(d[59]),"+f"(d[60]),"+f"(d[61]),"+f"(d[62]),"+f"(d[63]),"+f"(d[64]),"+f"(d[65]),"+f"(d[66]),"+f"(d[67]),"+f"(d[68]),"+f"(d[69]),"+f"(d[70]),"+f"(d[71]),"+f"(d[72]),"+f"(d[73]),"+f"(d[74]),"+f"(d[75]),"+f"(d[76]),"+f"(d[77]),"+f"(d[78]),"+f"(d[79]),"+f"(d[80]),"+f"(d[81]),"+f"(d[82]),"+f"(d[83]),"+f"(d[84]),"+f"(d[85]),"+f"(d[86]),"+f"(d[87]),"+f"(d[88]),"+f"(d[89]),"+f"(d[90]),"+f"(d[91]),"+f"(d[92]),"+f"(d[93]),"+f"(d[94]),"+f"(d[95]),"+f"(d[96]),"+f"(d[97]),"+f"(d[98]),"+f"(d[99]),"+f"(d[100]),"+f"(d[101]),"+f"(d[102]),"+f"(d[103]),"+f"(d[104]),"+f"(d[105]),"+f"(d[106]),"+f"(d[107]),"+f"(d[108]),"+f"(d[109]),"+f"(d[110]),"+f"(d[111]),"+f"(d[112]),"+f"(d[113]),"+f"(d[114]),"+f"(d[115])
    : "r"(alo), "r"(blo), "n"(AOFF), "n"(AHI), "n"(BOFF), "n"(BHI), "n"(ACC));
}
template <int OFF, uint32_t BHI, int ACC>
__device__ __forceinline__ void wgmma_rs224(float (&d)[112], uint32_t a0, uint32_t a1, uint32_t a2, uint32_t a3, uint32_t blo) {
  asm volatile("{\n.reg .pred p;\n.reg .b64 bd;\nsetp.ne.b32 p, %119, 0;\nmov.b64 bd, {%116, %118};\nadd.s64 bd, bd, %117;\n"
    "wgmma.mma_async.sync.aligned.m64n224k16.f32.bf16.bf16 {%0,%1,%2,%3,%4,%5,%6,%7,%8,%9,%10,%11,%12,%13,%14,%15,%16,%17,%18,%19,%20,%21,%22,%23,%24,%25,%26,%27,%28,%29,%30,%31,%32,%33,%34,%35,%36,%37,%38,%39,%40,%41,%42,%43,%44,%45,%46,%47,%48,%49,%50,%51,%52,%53,%54,%55,%56,%57,%58,%59,%60,%61,%62,%63,%64,%65,%66,%67,%68,%69,%70,%71,%72,%73,%74,%75,%76,%77,%78,%79,%80,%81,%82,%83,%84,%85,%86,%87,%88,%89,%90,%91,%92,%93,%94,%95,%96,%97,%98,%99,%100,%101,%102,%103,%104,%105,%106,%107,%108,%109,%110,%111}, {%112,%113,%114,%115}, bd, p, 1, 1, 1;\n}\n"
    : "+f"(d[0]),"+f"(d[1]),"+f"(d[2]),"+f"(d[3]),"+f"(d[4]),"+f"(d[5]),"+f"(d[6]),"+f"(d[7]),"+f"(d[8]),"+f"(d[9]),"+f"(d[10]),"+f"(d[11]),"+f"(d[12]),"+f"(d[13]),"+f"(d[14]),"+f"(d[15]),"+f"(d[16]),"+f"(d[17]),"+f"(d[18]),"+f"(d[19]),"+f"(d[20]),"+f"(d[21]),"+f"(d[22]),"+f"(d[23]),"+f"(d[24]),"+f"(d[25]),"+f"(d[26]),"+f"(d[27]),"+f"(d[28]),"+f"(d[29]),"+f"(d[30]),"+f"(d[31]),"+f"(d[32]),"+f"(d[33]),"+f"(d[34]),"+f"(d[35]),"+f"(d[36]),"+f"(d[37]),"+f"(d[38]),"+f"(d[39]),"+f"(d[40]),"+f"(d[41]),"+f"(d[42]),"+f"(d[43]),"+f"(d[44]),"+f"(d[45]),"+f"(d[46]),"+f"(d[47]),"+f"(d[48]),"+f"(d[49]),"+f"(d[50]),"+f"(d[51]),"+f"(d[52]),"+f"(d[53]),"+f"(d[54]),"+f"(d[55]),"+f"(d[56]),"+f"(d[57]),"+f"(d[58]),"+f"(d[59]),"+f"(d[60]),"+f"(d[61]),"+f"(d[62]),"+f"(d[63]),"+f"(d[64]),"+f"(d[65]),"+f"(d[66]),"+f"(d[67]),"+f"(d[68]),"+f"(d[69]),"+f"(d[70]),"+f"(d[71]),"+f"(d[72]),"+f"(d[73]),"+f"(d[74]),"+f"(d[75]),"+f"(d[76]),"+f"(d[77]),"+f"(d[78]),"+f"(d[79]),"+f"(d[80]),"+f"(d[81]),"+f"(d[82]),"+f"(d[83]),"+f"(d[84]),"+f"(d[85]),"+f"(d[86]),"+f"(d[87]),"+f"(d[88]),"+f"(d[89]),"+f"(d[90]),"+f"(d[91]),"+f"(d[92]),"+f"(d[93]),"+f"(d[94]),"+f"(d[95]),"+f"(d[96]),"+f"(d[97]),"+f"(d[98]),"+f"(d[99]),"+f"(d[100]),"+f"(d[101]),"+f"(d[102]),"+f"(d[103]),"+f"(d[104]),"+f"(d[105]),"+f"(d[106]),"+f"(d[107]),"+f"(d[108]),"+f"(d[109]),"+f"(d[110]),"+f"(d[111])
    : "r"(a0), "r"(a1), "r"(a2), "r"(a3), "r"(blo), "n"(OFF), "n"(BHI), "n"(ACC));
}
template <int OFF, uint32_t BHI, int ACC>
__device__ __forceinline__ void wgmma_rs56(float (&d)[28], uint32_t a0, uint32_t a1, uint32_t a2, uint32_t a3, uint32_t blo) {
  asm volatile("{\n.reg .pred p;\n.reg .b64 bd;\nsetp.ne.b32 p, %35, 0;\nmov.b64 bd, {%32, %34};\nadd.s64 bd, bd, %33;\n"
    "wgmma.mma_async.sync.aligned.m64n56k16.f32.bf16.bf16 {%0,%1,%2,%3,%4,%5,%6,%7,%8,%9,%10,%11,%12,%13,%14,%15,%16,%17,%18,%19,%20,%21,%22,%23,%24,%25,%26,%27}, {%28,%29,%30,%31}, bd, p, 1, 1, 1;\n}\n"
    : "+f"(d[0]),"+f"(d[1]),"+f"(d[2]),"+f"(d[3]),"+f"(d[4]),"+f"(d[5]),"+f"(d[6]),"+f"(d[7]),"+f"(d[8]),"+f"(d[9]),"+f"(d[10]),"+f"(d[11]),"+f"(d[12]),"+f"(d[13]),"+f"(d[14]),"+f"(d[15]),"+f"(d[16]),"+f"(d[17]),"+f"(d[18]),"+f"(d[19]),"+f"(d[20]),"+f"(d[21]),"+f"(d[22]),"+f"(d[23]),"+f"(d[24]),"+f"(d[25]),"+f"(d[26]),"+f"(d[27])
    : "r"(a0), "r"(a1), "r"(a2), "r"(a3), "r"(blo), "n"(OFF), "n"(BHI), "n"(ACC));
}

__device__ __forceinline__ void st128(uint4* p, uint32_t a, uint32_t b, uint32_t c, uint32_t d) {
  asm volatile("{\n.reg .b128 v;\n.reg .b64 lo, hi;\nmov.b64 lo, {%1, %2};\nmov.b64 hi, {%3, %4};\nmov.b128 v, {lo, hi};\n"
               "st.relaxed.gpu.global.b128 [%0], v;\n}" ::"l"(p), "r"(a), "r"(b), "r"(c), "r"(d) : "memory");
}
__device__ __forceinline__ void ld128(const uint4* p, uint32_t* r) {
  asm volatile("{\n.reg .b128 v;\n.reg .b64 lo, hi;\nld.relaxed.gpu.global.b128 v, [%4];\nmov.b128 {lo, hi}, v;\n"
               "mov.b64 {%0, %1}, lo;\nmov.b64 {%2, %3}, hi;\n}" : "=r"(r[0]), "=r"(r[1]), "=r"(r[2]), "=r"(r[3]) : "l"(p) : "memory");
}

template <int OFF, uint32_t BHI, int ACC>
__device__ __forceinline__ void wgmma_rs32(float (&d)[16], uint32_t a0, uint32_t a1, uint32_t a2, uint32_t a3, uint32_t blo) {
  asm volatile("{\n.reg .pred p;\n.reg .b64 bd;\nsetp.ne.b32 p, %23, 0;\nmov.b64 bd, {%20, %22};\nadd.s64 bd, bd, %21;\n"
    "wgmma.mma_async.sync.aligned.m64n32k16.f32.bf16.bf16 {%0,%1,%2,%3,%4,%5,%6,%7,%8,%9,%10,%11,%12,%13,%14,%15}, {%16,%17,%18,%19}, bd, p, 1, 1, 0;\n}\n"
    : "+f"(d[0]),"+f"(d[1]),"+f"(d[2]),"+f"(d[3]),"+f"(d[4]),"+f"(d[5]),"+f"(d[6]),"+f"(d[7]),"+f"(d[8]),"+f"(d[9]),"+f"(d[10]),"+f"(d[11]),"+f"(d[12]),"+f"(d[13]),"+f"(d[14]),"+f"(d[15])
    : "r"(a0), "r"(a1), "r"(a2), "r"(a3), "r"(blo), "n"(OFF), "n"(BHI), "n"(ACC));
}
template <int OFF, uint32_t BHI, int ACC>
__device__ __forceinline__ void wgmma_rs24(float (&d)[12], uint32_t a0, uint32_t a1, uint32_t a2, uint32_t a3, uint32_t blo) {
  asm volatile("{\n.reg .pred p;\n.reg .b64 bd;\nsetp.ne.b32 p, %19, 0;\nmov.b64 bd, {%16, %18};\nadd.s64 bd, bd, %17;\n"
    "wgmma.mma_async.sync.aligned.m64n24k16.f32.bf16.bf16 {%0,%1,%2,%3,%4,%5,%6,%7,%8,%9,%10,%11}, {%12,%13,%14,%15}, bd, p, 1, 1, 1;\n}\n"
    : "+f"(d[0]),"+f"(d[1]),"+f"(d[2]),"+f"(d[3]),"+f"(d[4]),"+f"(d[5]),"+f"(d[6]),"+f"(d[7]),"+f"(d[8]),"+f"(d[9]),"+f"(d[10]),"+f"(d[11])
    : "r"(a0), "r"(a1), "r"(a2), "r"(a3), "r"(blo), "n"(OFF), "n"(BHI), "n"(ACC));
}
template <int OFF, uint32_t BHI, int ACC>
__device__ __forceinline__ void wgmma_rs16(float (&d)[8], uint32_t a0, uint32_t a1, uint32_t a2, uint32_t a3, uint32_t blo) {
  asm volatile("{\n.reg .pred p;\n.reg .b64 bd;\nsetp.ne.b32 p, %15, 0;\nmov.b64 bd, {%12, %14};\nadd.s64 bd, bd, %13;\n"
    "wgmma.mma_async.sync.aligned.m64n16k16.f32.bf16.bf16 {%0,%1,%2,%3,%4,%5,%6,%7}, {%8,%9,%10,%11}, bd, p, 1, 1, 1;\n}\n"
    : "+f"(d[0]),"+f"(d[1]),"+f"(d[2]),"+f"(d[3]),"+f"(d[4]),"+f"(d[5]),"+f"(d[6]),"+f"(d[7])
    : "r"(a0), "r"(a1), "r"(a2), "r"(a3), "r"(blo), "n"(OFF), "n"(BHI), "n"(ACC));
}

constexpr int A_R1 = 0;
constexpr int A_R2A = A_R1 + 2624, A_R2B = A_R2A + 768, A_R3A = A_R2B + 768, A_R3B = A_R3A + 528;
constexpr int A_K1024 = A_R3B + 528;
constexpr int A_W5 = A_K1024 + 16;
constexpr int A_W3 = A_W5 + 4096;
constexpr int A_W9 = A_W3 + 4112;
constexpr int A_W7 = A_W9 + 2048;
constexpr int A_V  = A_W7 + 2048;
constexpr int A_UB = A_V + 2048;
constexpr int A_STG = A_UB + 5248;
constexpr int A_Y2 = A_STG, A_Y3 = A_Y2 + 6528, A_YB = A_Y3 + 4352;
constexpr int A_REC = A_STG + 4 * 4352;
constexpr int A_CH = A_REC + 8192;
static_assert(A_W5 % 16 == 0 && A_UB % 16 == 0 && A_CH % 16 == 0 && A_YB + 4096 <= A_REC, "layout");

struct cf { float x, y; };
__device__ __forceinline__ cf cmul(cf a, cf b) { cf r; r.x = fmaf(a.x, b.x, -a.y * b.y); r.y = fmaf(a.x, b.y, a.y * b.x); return r; }
__device__ __forceinline__ cf cexp_l(float lr, float li, float l) {
  float mag; asm("ex2.approx.ftz.f32 %0, %1;" : "=f"(mag) : "f"((lr * l) * 1.4426950408889634f));
  const float th = li * l;
  const float k = (fmaf(th, 0.15915494f, 12582912.f)) - 12582912.f;
  float ph = fmaf(th, 0.15915494f, -k);
  ph = fmaf(th, 6.4206383e-9f, ph) * 6.2831853f;
  cf r; r.x = mag * __cosf(ph); r.y = mag * __sinf(ph); return r;
}
__device__ __forceinline__ void sts16(uint32_t a, uint32_t v) { asm volatile("st.shared.u16 [%0], %1;" ::"r"(a), "h"((uint16_t)v) : "memory"); }
__device__ __forceinline__ void sts32(uint32_t a, uint32_t v) { asm volatile("st.shared.u32 [%0], %1;" ::"r"(a), "r"(v) : "memory"); }
__device__ __forceinline__ void sts64(uint32_t a, uint32_t v0, uint32_t v1) { asm volatile("st.shared.v2.u32 [%0], {%1, %2};" ::"r"(a), "r"(v0), "r"(v1) : "memory"); }
__device__ __forceinline__ void sts128(uint32_t a, uint32_t v0, uint32_t v1, uint32_t v2, uint32_t v3) {
  asm volatile("st.shared.v4.u32 [%0], {%1, %2, %3, %4};" ::"r"(a), "r"(v0), "r"(v1), "r"(v2), "r"(v3) : "memory");
}
__device__ __forceinline__ uint32_t lds32(uint32_t a) { uint32_t v; asm volatile("ld.shared.u32 %0, [%1];" : "=r"(v) : "r"(a) : "memory"); return v; }
__device__ __forceinline__ uint4 lds128(uint32_t a) {
  uint4 v; asm volatile("ld.shared.v4.u32 {%0, %1, %2, %3}, [%4];" : "=r"(v.x), "=r"(v.y), "=r"(v.z), "=r"(v.w) : "r"(a) : "memory"); return v;
}
__device__ __forceinline__ void ldsm4(uint32_t* r, uint32_t a) {
  asm volatile("ldmatrix.sync.aligned.m8n8.x4.shared.b16 {%0,%1,%2,%3}, [%4];" : "=r"(r[0]), "=r"(r[1]), "=r"(r[2]), "=r"(r[3]) : "r"(a) : "memory");
}
__device__ __forceinline__ void mma16816(float* d, const uint32_t* a, uint32_t b0, uint32_t b1) {
  asm volatile("mma.sync.aligned.m16n8k16.row.col.f32.bf16.bf16.f32 {%0,%1,%2,%3}, {%4,%5,%6,%7}, {%8,%9}, {%0,%1,%2,%3};"
               : "+f"(d[0]), "+f"(d[1]), "+f"(d[2]), "+f"(d[3]) : "r"(a[0]), "r"(a[1]), "r"(a[2]), "r"(a[3]), "r"(b0), "r"(b1));
}
__device__ __forceinline__ uint32_t hsub2_bf(uint32_t a, uint32_t b) { uint32_t r; asm("sub.rn.bf16x2 %0, %1, %2;" : "=r"(r) : "r"(a), "r"(b)); return r; }
__device__ __forceinline__ void bar_sync(int id, int n) { asm volatile("bar.sync %0, %1;" ::"r"(id), "r"(n) : "memory"); }

template <int S> struct F1B { static constexpr int c = S / 4 + ((S & 3) == 3 ? 0 : 0), cc = (16 * S) / 64, ks = (64 * cc - (16 * S - 48)) / 16, off = (A_UB + 2 * ks * 656 + (9 - cc) * 16) / 16; };

template <int NS>
__device__ __forceinline__ void load_quads(uint32_t* q, uint32_t addr) {
#pragma unroll
  for (int i = 0; i < NS; i++) {
    q[4 * i] = lds32(addr + i * 64); q[4 * i + 1] = lds32(addr + i * 64 + 32);
    q[4 * i + 2] = i ? q[4 * i - 3] : lds32(addr - 32);
    q[4 * i + 3] = q[4 * i];
  }
#pragma unroll
  for (int i = 0; i < 4 * NS; i++) asm volatile("" : "+r"(q[i]));
}
template <int S0, int NS>
__device__ __forceinline__ void f1_steps(float (&acc)[16], const uint32_t* a, uint32_t blo) {
  if constexpr (NS > 0) {
    wgmma_rs32<F1B<S0>::off, 8, S0 != 0>(acc, a[0], a[1], a[2], a[3], blo);
    f1_steps<S0 + 1, NS - 1>(acc, a + 4, blo);
  }
}
template <int S0, int NS, int BASE, int FIRST>
__device__ __forceinline__ void s2_steps(float (&acc)[12], const uint32_t* a, uint32_t blo) {
  if constexpr (NS > 0) {
    wgmma_rs24<BASE / 16 + (112 - 16 * S0), 64, !(FIRST && S0 == 0)>(acc, a[0], a[1], a[2], a[3], blo);
    s2_steps<S0 + 1, NS - 1, BASE, FIRST>(acc, a + 4, blo);
  }
}
template <int S0, int NS, int BASE, int FIRST>
__device__ __forceinline__ void s3_steps(float (&acc)[8], const uint32_t* a, uint32_t blo) {
  if constexpr (NS > 0) {
    wgmma_rs16<BASE / 16 + (48 - 16 * S0), 64, !(FIRST && S0 == 0)>(acc, a[0], a[1], a[2], a[3], blo);
    s3_steps<S0 + 1, NS - 1, BASE, FIRST>(acc, a + 4, blo);
  }
}

__device__ __forceinline__ void phase_a(
        unsigned char* sm, const uint32_t bar_rec, const uint32_t ep_addr,
        const __nv_bfloat16* __restrict__ x, const uint32_t* __restrict__ are, const uint32_t* __restrict__ aim,
        const uint32_t* __restrict__ bre, const uint32_t* __restrict__ bim, const uint32_t* __restrict__ cre,
        const uint32_t* __restrict__ cim, const unsigned short* __restrict__ logdt, const unsigned short* __restrict__ dskip,
        const uint4* __restrict__ wgate, const uint4* __restrict__ wup, const uint4* __restrict__ wdown) {
  const uint32_t sb = s2u(sm);
  const int tid = threadIdx.x, wg = tid >> 7, warp = tid >> 5, lane = tid & 31, wq = warp & 3, t128 = tid & 127;
  const int blk = blockIdx.x;
  const bool conv = blk < 112;

  uint2 xr[4];
  {
    const uint2* p = (const uint2*)(x + (size_t)(blk * 16 + warp) * DM);
    xr[0] = __ldg(p + lane); xr[1] = __ldg(p + 32 + lane); xr[2] = __ldg(p + 64 + lane);
    xr[3] = lane < 16 ? __ldg(p + 96 + lane) : make_uint2(0, 0);
  }
  const int ch = conv ? blk * 4 + wg : 0;
  const uint32_t cb = sb + wg * A_CH;
  uint32_t prm[6];
  {
    const int i = ch * 128 + t128;
    prm[0] = __ldg(are + i); prm[1] = __ldg(aim + i); prm[2] = __ldg(bre + i); prm[3] = __ldg(bim + i); prm[4] = __ldg(cre + i); prm[5] = __ldg(cim + i);
  }
  const uint32_t ldt = __ldg(logdt + ch);
  uint32_t cnt0 = 0;
  if (tid == 0) cnt0 = __ldcg(&g_cnt1);
#pragma unroll
  for (int i = 0; i < 4; i++) if (i < 3 || t128 < (A_W5 + 1024) / 16 - 384) sts128(cb + (i * 128 + t128) * 16, 0, 0, 0, 0);
  if (t128 < 65) sts128(cb + (t128 < 64 ? A_W3 + t128 * 16 : A_W9), 0, 0, 0, 0);
  if (t128 < 72) sts128(cb + A_UB + (t128 / 9) * 656 + (t128 % 9) * 16, 0, 0, 0, 0);
  {
    float s = 0.f, q = 0.f;
#pragma unroll
    for (int i = 0; i < 4; i++) {
      const float a = bf_lo(xr[i].x), b = bf_hi(xr[i].x), c = bf_lo(xr[i].y), d = bf_hi(xr[i].y);
      s += (a + b) + (c + d);
      q = fmaf(a, a, q); q = fmaf(b, b, q); q = fmaf(c, c, q); q = fmaf(d, d, q);
    }
#pragma unroll
    for (int o = 16; o; o >>= 1) { s += __shfl_xor_sync(~0u, s, o); q += __shfl_xor_sync(~0u, q, o); }
    const float mean = s * (1.f / DM);
    const float var = fmaxf(fmaf(-mean, mean, q * (1.f / DM)), 0.f);
    const float rs = __frcp_rn(rbf(__fsqrt_rn(rbf(rbf(var) + 1e-5f))));
    const uint32_t mm = pack_bf16(mean, mean);
    const uint32_t tu = sb + A_REC + (warp >> 3) * A_CH + (warp & 7) * 912 + lane * 8, tx = tu + 2 * A_CH;
#pragma unroll
    for (int i = 0; i < 4; i++) {
      if (i < 3 || lane < 16) {
        const uint32_t d0 = hsub2_bf(xr[i].x, mm), d1 = hsub2_bf(xr[i].y, mm);
        sts64(tu + i * 256, pack_bf16(bf_lo(d0) * rs, bf_hi(d0) * rs), pack_bf16(bf_lo(d1) * rs, bf_hi(d1) * rs));
        sts64(tx + i * 256, xr[i].x, xr[i].y);
      }
    }
  }
  if (tid == 0) sts32(ep_addr, (cnt0 >> 7) + 1u);
  if (tid == 320) TR(0, 1);
  auto publish_rows = [&]() {
    bar_sync(5, 512);
    uint4* dst = g_ux + ((size_t)(warp * 8 + (lane >> 2)) * 128 + blk) * 4 + ((lane ^ (blk >> 1)) & 3);
#pragma unroll
    for (int i = 0; i < 4; i++) {
      if (i < 3 || warp < 8) {
        uint32_t r[4];
        asm volatile("ldmatrix.sync.aligned.m8n8.x4.trans.shared.b16 {%0,%1,%2,%3}, [%4];" : "=r"(r[0]), "=r"(r[1]), "=r"(r[2]), "=r"(r[3])
                     : "r"(sb + A_REC + (lane >> 3) * A_CH + (lane & 7) * 912 + (warp + 16 * i) * 16) : "memory");
        dst[i * 65536] = make_uint4(r[0], r[1], r[2], r[3]);
      }
    }
    if (warp != 0) asm volatile("bar.arrive 6, 512;" ::: "memory");
  };
  auto release_rows = [&]() {
    if (warp == 0) {
      bar_sync(6, 512);
      if (lane == 0) { asm volatile("red.release.gpu.global.add.u32 [%0], 1;" ::"l"(&g_cnt1) : "memory"); TR(0, 8); }
      __syncwarp();
    }
  };

  if (!conv) {
    publish_rows();
    release_rows();
    const int a = blk - 112, mat = a >> 3, j = a & 7;
    float s[8];
#pragma unroll
    for (int k = 0; k < 8; k++) s[k] = 0.f;
    if (lane < 28) {
      const uint4* src = (mat ? wup : wgate) + j * 28 + lane + (size_t)warp * 224;
#pragma unroll
      for (int hb = 0; hb < 2; hb++) {
        uint4 v[14];
#pragma unroll
        for (int r = 0; r < 14; r++) v[r] = __ldg(src + (size_t)(hb * 14 + r) * 16 * 224);
#pragma unroll
        for (int r = 0; r < 14; r++) {
          s[0] += bf_lo(v[r].x); s[1] += bf_hi(v[r].x); s[2] += bf_lo(v[r].y); s[3] += bf_hi(v[r].y);
          s[4] += bf_lo(v[r].z); s[5] += bf_hi(v[r].z); s[6] += bf_lo(v[r].w); s[7] += bf_hi(v[r].w);
        }
      }
      float4* red = (float4*)(sm + A_STG + warp * 896 + lane * 32);
      red[0] = make_float4(s[0], s[1], s[2], s[3]); red[1] = make_float4(s[4], s[5], s[6], s[7]);
    }
    bar_sync(5, 512);
    if (tid < 224) {
      float t = 0.f;
#pragma unroll
      for (int w = 0; w < 16; w++) t += *(const float*)(sm + A_STG + w * 896 + tid * 4);
      const float hi = rbf(t), mid = rbf(t - hi), lo = rbf(t - hi - mid);
      const int q = tid / 112, n = tid % 112 + 112 * mat;
      __nv_bfloat16* dst = (__nv_bfloat16*)(g_cimg + (j * 2 + q) * 224 + (n >> 3) * 8) + (n & 7);
      dst[0] = __float2bfloat16_rn(hi); dst[8] = __float2bfloat16_rn(mid); dst[16] = __float2bfloat16_rn(lo);
#pragma unroll
      for (int k = 3; k < 8; k++) dst[8 * k] = __float2bfloat16_rn(0.f);
    }
    if (tid == 320) TR(0, 10);
    return;
  }

  const int g = lane >> 2, t = lane & 3;
  const int wr = (wq + wg) & 3;
  uint4 wv[6];
  auto w_src = [&](int i) -> const uint4* {
    if (i < 4) return (blk < 56 ? wgate : wup) + (blk % 56) * 4 + (lane & 3) + (size_t)(i * 128 + warp * 8 + (lane >> 2)) * 224;
    const int it = warp + 16 * (i - 4);
    return wdown + (size_t)(blk * 16 + (it / 14) * 8 + (lane >> 2)) * 56 + (it % 14) * 4 + (lane & 3);
  };
  auto w_on = [&](int i) { return i == 3 ? warp < 8 : i == 5 ? warp < 12 : true; };
  {
    const uint32_t stg = cb + A_STG + wq * 4352;
    const float dt = rbf(expf(__uint_as_float(ldt << 16)));
    float lr[2], li[2];
    cf bq[2], b0[2], b4[2];
    uint32_t bf[48];
#pragma unroll
    for (int m = 0; m < 2; m++) {
      lr[m] = dt * (m ? bf_hi(prm[0]) : bf_lo(prm[0]));
      li[m] = dt * (m ? bf_hi(prm[1]) : bf_lo(prm[1]));
    }
    {
      cf b[2], z[2];
#pragma unroll
      for (int m = 0; m < 2; m++) {
        cf db, c;
        db.x = dt * (m ? bf_hi(prm[2]) : bf_lo(prm[2])); db.y = -dt * (m ? bf_hi(prm[3]) : bf_lo(prm[3]));
        c.x = m ? bf_hi(prm[4]) : bf_lo(prm[4]); c.y = -(m ? bf_hi(prm[5]) : bf_lo(prm[5]));
        b[m] = cmul(c, db);
        z[m] = cexp_l(lr[m], -li[m], 1.f);
        bq[m] = cexp_l(lr[m], -li[m], 256.f);
      }
#pragma unroll
      for (int i = 0; i < 8; i++) {
        sts64(stg + i * 272 + lane * 8, pack_bf16(b[0].x, b[0].y), pack_bf16(b[1].x, b[1].y));
        if (!(i & 1)) {
          cf e0 = cmul(b[0], bq[0]), e1 = cmul(b[1], bq[1]);
          sts64(stg + (8 + i / 2) * 272 + lane * 8, pack_bf16(e0.x, e0.y), pack_bf16(e1.x, e1.y));
          if (i == 0) { b0[0] = e0; b0[1] = e1; }
          if (i == 4) { b4[0] = e0; b4[1] = e1; }
        }
        if (i < 7) { b[0] = cmul(b[0], z[0]); b[1] = cmul(b[1], z[1]); }
        if (i == 1) publish_rows();
      }
#pragma unroll
      for (int i = 0; i < 7; i++) {
        b0[0] = cmul(b0[0], bq[0]); b0[1] = cmul(b0[1], bq[1]);
        sts64(stg + (i < 2 ? 12 + 2 * i : i - 2) * 272 + lane * 8, pack_bf16(b0[0].x, b0[0].y), pack_bf16(b0[1].x, b0[1].y));
        if (i < 2) {
          b4[0] = cmul(b4[0], bq[0]); b4[1] = cmul(b4[1], bq[1]);
          sts64(stg + (13 + 2 * i) * 272 + lane * 8, pack_bf16(b4[0].x, b4[0].y), pack_bf16(b4[1].x, b4[1].y));
        }
        if (i == 1) {
          __syncwarp();
#pragma unroll
          for (int n = 0; n < 2; n++)
#pragma unroll
            for (int k2 = 0; k2 < 4; k2++) ldsm4(bf + n * 16 + k2 * 4, stg + (n * 8 + (lane & 7)) * 272 + k2 * 64 + (lane >> 3) * 16);
          __syncwarp();
        }
      }
    }
    __syncwarp();
#pragma unroll
    for (int k2 = 0; k2 < 4; k2++) ldsm4(bf + 32 + k2 * 4, stg + (lane & 7) * 272 + k2 * 64 + (lane >> 3) * 16);
    release_rows();
    if (!(lane & 1)) {
#pragma unroll
      for (int i = 0; i < 6; i++) if (w_on(i)) asm volatile("prefetch.global.L2 [%0];" ::"l"(w_src(i)));
    }
    if (tid == 320) TR(0, 16);
    float c[6][4];
#pragma unroll
    for (int i = 0; i < 6; i++) { c[i][0] = 0.f; c[i][1] = 0.f; c[i][2] = 0.f; c[i][3] = 0.f; }
    cf p[2], v[2];
    p[0] = cexp_l(lr[0], li[0], 8.f); p[1] = cexp_l(lr[1], li[1], 8.f);
    v[0].x = 1.f; v[0].y = 0.f; v[1] = v[0];
#pragma unroll
    for (int mt = 0; mt < 2; mt++) {
      __syncwarp();
#pragma unroll
      for (int i = 0; i < 16; i++) {
        sts64(stg + i * 272 + lane * 8, pack_bf16(v[0].x, v[0].y), pack_bf16(v[1].x, v[1].y));
        if (mt == 0 && i == 0) { v[0] = p[0]; v[1] = p[1]; }
        else if (mt == 0 || i < 15) { v[0] = cmul(v[0], p[0]); v[1] = cmul(v[1], p[1]); }
      }
      __syncwarp();
      if (mt == 1 && tid == 160) {
        const uint32_t tgt = lds32(ep_addr) * 128u;
        uint32_t cv; int it = 0;
        do { asm volatile("ld.acquire.gpu.global.u32 %0, [%1];" : "=r"(cv) : "l"(&g_cnt1) : "memory"); } while ((int)(cv - tgt) < 0 && ++it < 200000);
        asm volatile("fence.proxy.async;" ::: "memory");
        TR(0, 9);
        mbar_expect(bar_rec, 32768);
        for (int c2 = 0; c2 < 4; c2++) bulk_ld(sb + c2 * A_CH + A_REC, g_ux + (size_t)(blk * 4 + c2) * 512, 8192, bar_rec);
      }
#pragma unroll
      for (int ks = 0; ks < 8; ks++) {
        uint32_t a[4];
        ldsm4(a, stg + (lane & 15) * 272 + ks * 32 + (lane >> 4) * 16);
#pragma unroll
        for (int n = 0; n < 3; n++) mma16816(c[n * 2 + mt], a, bf[n * 16 + ks * 2], bf[n * 16 + ks * 2 + 1]);
      }
    }
    __syncwarp();
#pragma unroll
    for (int i = 0; i < 6; i++)
      sts128(stg + i * 512 + lane * 16, __float_as_uint(c[i][0]), __float_as_uint(c[i][1]), __float_as_uint(c[i][2]), __float_as_uint(c[i][3]));
#pragma unroll
    for (int i = 0; i < 6; i++) if (w_on(i)) wv[i] = __ldg(w_src(i));
    bar_sync(1 + wg, 128);
    if (tid == 320) TR(0, 2);
#pragma unroll
    for (int rep = 0; rep < 2; rep++) {
      const int qd = rep ? 2 + wr : 3 - wr;
      if (rep == 0 || wr >= 2) {
        float s[4] = {0.f, 0.f, 0.f, 0.f};
#pragma unroll
        for (int w = 0; w < 4; w++) {
          uint4 u4 = lds128(cb + A_STG + w * 4352 + qd * 512 + lane * 16);
          s[0] += __uint_as_float(u4.x); s[1] += __uint_as_float(u4.y); s[2] += __uint_as_float(u4.z); s[3] += __uint_as_float(u4.w);
        }
#pragma unroll
        for (int hf = 0; hf < 2; hf++) {
          const int j = (qd & 1) * 16 + g + 8 * hf;
          const uint32_t pk = pack_bf16(s[2 * hf + 1], s[2 * hf]);
          const uint32_t v0 = pk >> 16, v1 = pk & 0xFFFFu, v00 = v0 * 0x10001u;
          if (rep == 1) {
            if (t < 2) {
#pragma unroll
              for (int e = 0; e < 2; e++) {
                const int lam = 128 + 32 * (2 * t + e) + j, mu = lam >> 1;
                const uint32_t val = e ? v1 : v0;
                uint32_t a = cb + ((lam & 1) ? A_R3B : A_R3A) + mu * 4;
                if (lam == 128) { a = cb + A_R2A + 128 * 4; sts32(cb + A_K1024, val << 16); }
                sts16(a, val); sts16(a + 6, val);
              }
            } else if (t == 2 && j == 0) { sts16(cb + A_R3A + 128 * 4, v0); }
          } else if (qd < 2) {
            const uint32_t a = cb + A_R1 + (62 + 8 * j + 2 * t) * 4;
            sts16(a, v0); sts32(a + 4, pk); sts16(a + 10, v1);
          } else if (t < 2) {
            const int L = 256 + 8 * j + 4 * t;
            const uint32_t a = cb + A_R1 + (62 + L) * 4;
            if (L > 256) { sts16(a - 4, v0); sts32(a, v00); } else sts16(a, v0);
            sts32(a + 4, v00); sts32(a + 8, pk); sts16(a + 14, v1);
          } else {
            const int mu = 64 + 32 * (t - 2) + j;
            if (mu == 64) {
              const uint32_t a = cb + A_R1 + (62 + 512) * 4;
              sts16(a - 4, v0); sts32(a, v00); sts32(a + 4, v00); sts32(a + 8, v00); sts16(a + 14, v0);
            } else { sts16(cb + A_R2A + mu * 4, v0); sts16(cb + A_R2A + mu * 4 + 6, v0); }
            sts16(cb + A_R2B + mu * 4, v1); sts16(cb + A_R2B + mu * 4 + 6, v1);
          }
        }
      }
    }
  }
  {
    const int ngg = (blk % 56) * 4 + (lane & 3), j = ngg / 28, q = (ngg % 28) / 14, ng = ngg % 14 + (blk < 56 ? 0 : 14);
    uint4* dst = g_wimg + (size_t)j * 37632 + q * 14 * 896 + ng * 32 + (warp >> 2) * 896 + (warp & 3) * 8 + (lane >> 2);
#pragma unroll
    for (int i = 0; i < 4; i++) if (w_on(i)) dst[i * 4 * 896] = wv[i];
#pragma unroll
    for (int i = 4; i < 6; i++) {
      const int it = warp + 16 * (i - 4), n2 = (it % 14) * 4 + (lane & 3), k = (blk % 7) * 16 + (it / 14) * 8 + (lane >> 2);
      if (w_on(i)) g_wimg[(size_t)(blk / 14) * 37632 + 25088 + ((n2 / 7) * 2 + (blk / 7) % 2) * 784 + (n2 % 7) * 112 + k] = wv[i];
    }
  }
  if (tid == 320) TR(0, 3);

  const int bk = wr * 32 + lane;
  uint32_t xt[8], ud[8];
  {
    mbar_wait(bar_rec, 0);
    if (tid == 320) TR(0, 4);
    uint4 r[4];
#pragma unroll
    for (int i = 0; i < 4; i++) r[i] = lds128(cb + A_REC + bk * 64 + ((i ^ (bk >> 1)) & 3) * 16);
    const uint32_t ua = cb + A_UB + ((2 * bk) & 7) * 656 + ((bk >> 2) + 9) * 16;
    sts128(ua, r[0].x, r[1].x, r[2].x, r[3].x);
    sts128(ua + 656, r[0].y, r[1].y, r[2].y, r[3].y);
    if (bk <= 96) {
      const bool neg = bk == 96;
      const int bp = neg ? -1 : bk;
      uint32_t h[4];
      h[0] = lds32(cb + A_REC + ((bp - 1) & 127) * 64 + ((2 ^ ((bp - 1) >> 1)) & 3) * 16 + 4);
      h[1] = lds32(cb + A_REC + ((bp - 1) & 127) * 64 + ((3 ^ ((bp - 1) >> 1)) & 3) * 16 + 4);
      h[2] = lds32(cb + A_REC + (bp + 1) * 64 + ((0 ^ ((bp + 1) >> 1)) & 3) * 16);
      h[3] = lds32(cb + A_REC + (bp + 1) * 64 + ((1 ^ ((bp + 1) >> 1)) & 3) * 16);
      if (bp <= 0) { h[0] = 0; h[1] = 0; }
      const uint32_t wd[12] = {h[0], h[1], neg ? 0 : r[0].x, neg ? 0 : r[1].x, neg ? 0 : r[2].x, neg ? 0 : r[3].x,
                               neg ? 0 : r[0].y, neg ? 0 : r[1].y, neg ? 0 : r[2].y, neg ? 0 : r[3].y, h[2], h[3]};
      float P[25];
      P[0] = 0.f;
#pragma unroll
      for (int i = 0; i < 12; i++) { P[2 * i + 1] = P[2 * i] + bf_lo(wd[i]); P[2 * i + 2] = P[2 * i + 1] + bf_hi(wd[i]); }
#define WIN(i, hw) (P[(i) + 5 + (hw)] - P[(i) + 4 - (hw)])
#define WPK(i, hw) pack_bf16(WIN(i, hw), WIN((i) + 1, hw))
      const int tp = 2 * bp;
      const uint32_t a3 = cb + A_W3 + (tp + 64) * 16 + 8, a5 = cb + A_W5 + (tp + 64) * 16;
      if (!neg) sts64(a3, WPK(0, 1), WPK(2, 1));
      if (!neg) sts128(a3 + 8, WPK(4, 1), WPK(6, 1), WPK(8, 1), WPK(10, 1));
      sts64(a3 + 24, WPK(12, 1), WPK(14, 1));
      sts128(a5, WPK(0, 2), WPK(2, 2), WPK(4, 2), WPK(6, 2));
      sts128(a5 + 16, WPK(8, 2), WPK(10, 2), WPK(12, 2), WPK(14, 2));
      if (bp < 64) {
        if (!neg) sts128(cb + A_W7 + 1024 + bp * 16, WPK(0, 3), WPK(2, 3), WPK(4, 3), WPK(6, 3));
        if (bp < 63) {
          sts128(cb + A_W7 + (bp + 1) * 16, WPK(8, 3), WPK(10, 3), WPK(12, 3), WPK(14, 3));
          sts128(cb + A_W9 + (bp + 1) * 16, WPK(0, 4), WPK(2, 4), WPK(4, 4), WPK(6, 4));
          sts128(cb + A_W9 + 1024 + (bp + 1) * 16, WPK(8, 4), WPK(10, 4), WPK(12, 4), WPK(14, 4));
        }
        if (!neg) {
#define VPK(i) pack_bf16(P[(i) + 2] - P[i], P[(i) + 3] - P[(i) + 1])
          sts128(cb + A_V + bp * 32, VPK(0), VPK(2), VPK(4), VPK(6));
          sts128(cb + A_V + bp * 32 + 16, VPK(8), VPK(10), VPK(12), VPK(14));
        }
      }
    }
  }
  asm volatile("fence.proxy.async.shared::cta;" ::: "memory");
  bar_sync(1 + wg, 128);
  if (tid == 320) TR(0, 5);

  {
    const uint32_t cbu = __shfl_sync(~0u, cb, 0);
    const uint32_t blo_k = ((cbu & 0x3FFFF) >> 4) | (41u << 16);
    const uint32_t blo_n = ((cbu & 0x3FFFF) >> 4) | (8u << 16);
    const uint32_t tb = cb + (16 * wq + g - 2 * t) * 4;
    float y1[16], y2[12], y3[8];
    const uint32_t dk16 = __ldg(dskip + ch);
    uint32_t qa[32], qb[32];
    const uint32_t t1 = tb + A_R1 + (62 - 48) * 4;
    load_quads<4>(qa, tb + A_R3A + 17 * 4); load_quads<4>(qa + 16, tb + A_R3B + 16 * 4);
    wg_fence();
    s3_steps<0, 4, A_W9, 1>(y3, qa, blo_n); s3_steps<0, 4, A_W7, 0>(y3, qa + 16, blo_n);
    wg_commit();
    load_quads<8>(qb, tb + A_R2A + 16 * 4);
    wg_fence(); s2_steps<0, 8, A_W5, 1>(y2, qb, blo_n); wg_commit();
    wg_wait<1>(); load_quads<8>(qa, tb + A_R2B + 16 * 4);
    wg_fence(); s2_steps<0, 8, A_W3, 0>(y2, qa, blo_n); wg_commit();
    wg_wait<1>(); load_quads<8>(qb, t1);
    wg_fence(); f1_steps<0, 8>(y1, qb, blo_k); wg_commit();
    wg_wait<1>(); load_quads<8>(qa, t1 + 8 * 64);
    wg_fence(); f1_steps<8, 8>(y1, qa, blo_k); wg_commit();
    reg_fence(y2); reg_fence(y3);
    if (tid == 320) TR(0, 18);
    {
      const float k1024 = __uint_as_float(lds32(cb + A_K1024));
#pragma unroll
      for (int i = 0; i < 2; i++)
#pragma unroll
        for (int hf = 0; hf < 2; hf++) {
          const int idx = 16 * (16 * wq + g + 8 * hf) + 8 * i + 2 * t;
          const uint32_t vv = lds32(cb + A_V + idx * 2);
          sts64(cb + A_Y3 + (idx + 4 * (idx >> 6)) * 4, __float_as_uint(fmaf(k1024, bf_lo(vv), y3[4 * i + 2 * hf])),
                __float_as_uint(fmaf(k1024, bf_hi(vv), y3[4 * i + 2 * hf + 1])));
        }
#pragma unroll
      for (int i = 0; i < 3; i++)
#pragma unroll
        for (int hf = 0; hf < 2; hf++) {
          const int idx = 512 * i + 8 * (16 * wq + g + 8 * hf) + 2 * t;
          sts64(cb + A_Y2 + (idx + 4 * (idx >> 6)) * 4, __float_as_uint(y2[4 * i + 2 * hf]), __float_as_uint(y2[4 * i + 2 * hf + 1]));
        }
    }
    wg_wait<1>(); load_quads<8>(qb, t1 + 16 * 64);
    wg_fence(); f1_steps<16, 8>(y1, qb, blo_k); wg_commit();
    wg_wait<1>(); load_quads<8>(qa, t1 + 24 * 64);
    wg_fence(); f1_steps<24, 8>(y1, qa, blo_k); wg_commit();
    wg_wait<1>(); load_quads<5>(qb, t1 + 32 * 64);
    wg_fence(); f1_steps<32, 5>(y1, qb, blo_k); wg_commit();
    bar_sync(1 + wg, 128);
    float ex[12];
#pragma unroll
    for (int i = 1; i < 4; i++)
#pragma unroll
      for (int k = 0; k < 4; k++) {
        const int aa = 8 * i + 2 * t + (k & 1), b = 16 * wq + g + 8 * (k >> 1);
        float e = __uint_as_float(lds32(cb + A_Y2 + ((aa - 8) * 68 + b) * 4));
        if (i >= 2) e += __uint_as_float(lds32(cb + A_Y3 + ((aa - 16) * 68 + b) * 4));
        ex[4 * (i - 1) + k] = e;
      }
    {
      const uint32_t dk = dk16 * 0x10001u;
#pragma unroll
      for (int i = 0; i < 4; i++) {
        const uint4 r = lds128(cb + A_REC + bk * 64 + ((i ^ (bk >> 1)) & 3) * 16);
        ud[i] = hmul2_bf(r.x, dk); ud[4 + i] = hmul2_bf(r.y, dk); xt[i] = r.z; xt[4 + i] = r.w;
      }
    }
    wg_wait<0>();
    reg_fence(y1);
    if (tid == 320) TR(0, 6);
#pragma unroll
    for (int i = 0; i < 12; i++) y1[4 + i] += ex[i];
#pragma unroll
    for (int i = 0; i < 2; i++) {
      const int mi = lane >> 3, aa = 8 * (2 * i + (mi >> 1)) + (lane & 7);
      asm volatile("stmatrix.sync.aligned.m8n8.x4.trans.shared.b16 [%0], {%1,%2,%3,%4};"
                   ::"r"(cb + A_YB + aa * 128 + (((2 * wq + (mi & 1)) ^ (lane & 7)) << 4)),
                     "r"(pack_bf16(y1[8 * i], y1[8 * i + 1])), "r"(pack_bf16(y1[8 * i + 2], y1[8 * i + 3])),
                     "r"(pack_bf16(y1[8 * i + 4], y1[8 * i + 5])), "r"(pack_bf16(y1[8 * i + 6], y1[8 * i + 7])) : "memory");
    }
  }
  bar_sync(1 + wg, 128);
#pragma unroll
  for (int c = 0; c < 2; c++) {
    const int tau = 2 * bk + c, r = ch & 7;
    const uint4 y = lds128(cb + A_YB + (tau >> 3) * 128 + (((tau ^ (tau >> 3)) & 7) << 4));
    g_himg[(size_t)(tau >> 4) * 7168 + (ch >> 3) * 128 + ((tau >> 3) & 1) * 64 + r * 8 + ((tau & 7) ^ r)] =
        make_uint4(hadd2_bf(xt[4 * c], hadd2_bf(y.x, ud[4 * c])), hadd2_bf(xt[4 * c + 1], hadd2_bf(y.y, ud[4 * c + 1])),
                   hadd2_bf(xt[4 * c + 2], hadd2_bf(y.z, ud[4 * c + 2])), hadd2_bf(xt[4 * c + 3], hadd2_bf(y.w, ud[4 * c + 3])));
  }
  if (tid == 320) TR(0, 7);
}

constexpr int B_SA = 0, B_RING = 114688, B_SLOT = 14848, B_NSLOT = 7;
constexpr int B_CS = B_RING + B_NSLOT * B_SLOT;
constexpr int B_RED = B_CS + 7168;
constexpr int B_BAR = B_RED + 256;
constexpr int B_SMEM = B_BAR + 1024, A_SMEM = 4 * A_CH + 64;

__device__ __forceinline__ uint32_t mapa(uint32_t a, uint32_t r) { uint32_t o; asm("mapa.shared::cluster.u32 %0, %1, %2;" : "=r"(o) : "r"(a), "r"(r)); return o; }
template <class T> __device__ __forceinline__ T* pin(T* p) { asm volatile("" : "+l"(p)); return p; }
__device__ __forceinline__ uint32_t pin(uint32_t v) { asm volatile("" : "+r"(v)); return v; }
template <int Q, int ST>
__device__ __forceinline__ void g1_stage(float (&acc)[116], uint32_t alo, uint32_t blo, uint32_t bar_full, uint32_t bar_h) {
  constexpr int s = Q * 14 + ST, sl = s % B_NSLOT;
  if (Q == 0) mbar_wait(bar_h + 8 * ST, 0);
  mbar_wait(bar_full + 8 * sl, (s / B_NSLOT) & 1);
  wg_fence();
  if (Q == 0) {
    wgmma_ss232<(2 * ST) * 256, 0x40000080u, (sl * B_SLOT) / 16, 32, ST != 0>(acc, alo, blo);
    wgmma_ss232<(2 * ST + 1) * 256, 0x40000080u, (sl * B_SLOT + 256) / 16, 32, 1>(acc, alo, blo);
  } else {
    wgmma_ss224<(2 * ST) * 256, 0x40000080u, (sl * B_SLOT) / 16, 32, ST != 0>(*(float(*)[112])acc, alo, blo);
    wgmma_ss224<(2 * ST + 1) * 256, 0x40000080u, (sl * B_SLOT + 256) / 16, 32, 1>(*(float(*)[112])acc, alo, blo);
  }
}

__global__ void __launch_bounds__(512, 1)
k_front(const __nv_bfloat16* __restrict__ x, const uint32_t* __restrict__ are, const uint32_t* __restrict__ aim,
        const uint32_t* __restrict__ bre, const uint32_t* __restrict__ bim, const uint32_t* __restrict__ cre,
        const uint32_t* __restrict__ cim, const unsigned short* __restrict__ logdt, const unsigned short* __restrict__ dskip,
        const uint4* __restrict__ wgate, const uint4* __restrict__ wup, const uint4* __restrict__ wdown) {
  extern __shared__ __align__(1024) unsigned char sm[];
  const uint32_t bar_rec = s2u(sm) + 4 * A_CH;
  if (threadIdx.x == 320) TR(0, 0);
  asm volatile("griddepcontrol.launch_dependents;");
  if (threadIdx.x == 160) { mbar_init(bar_rec, 1); asm volatile("fence.mbarrier_init.release.cluster;" ::: "memory"); }
  phase_a(sm, bar_rec, bar_rec + 8, x, are, aim, bre, bim, cre, cim, logdt, dskip, wgate, wup, wdown);
}

__global__ void __cluster_dims__(2, 1, 1) __launch_bounds__(384, 1) k_ffn(__nv_bfloat16* __restrict__ out) {
  extern __shared__ __align__(1024) unsigned char sm[];
  const uint32_t sb = s2u(sm);
  const int tid = threadIdx.x, wg = tid >> 7, warp = tid >> 5, lane = tid & 31;
  const uint32_t bar_full = sb + B_BAR, bar_empty = bar_full + 64, bar_h = bar_full + 128, bar_cs = bar_full + 240,
                 bar_g2 = bar_full + 248, bar_in = bar_full + 256, bar_hh = bar_full + 304, bar_afree = bar_full + 336, bar_out = bar_full + 352;
  if (tid == 0) {
    TR(1, 0);
    for (int i = 0; i < B_NSLOT; i++) { mbar_init(bar_full + 8 * i, 1); mbar_init(bar_empty + 8 * i, 2); }
    asm volatile("fence.mbarrier_init.release.cluster;" ::: "memory");
  } else if (tid == 32) {
    for (int i = 0; i < 14; i++) mbar_init(bar_h + 8 * i, 1);
    asm volatile("fence.mbarrier_init.release.cluster;" ::: "memory");
  } else if (tid == 64) {
    mbar_init(bar_cs, 1);
    mbar_init(bar_g2, 4);
    for (int i = 0; i < 6; i++) mbar_init(bar_in + 8 * i, 1);
    for (int i = 0; i < 4; i++) { mbar_init(bar_hh + 8 * i, 1); mbar_expect(bar_hh + 8 * i, 14336); }
    mbar_init(bar_afree, 4); mbar_init(bar_afree + 8, 2);
    for (int i = 0; i < 6; i++) mbar_init(bar_out + 8 * i, 128);
    asm volatile("fence.mbarrier_init.release.cluster;" ::: "memory");
  } else if (tid >= 128 && tid < 352) {
    sts128(sb + B_RING + ((tid - 128) >> 5) * B_SLOT + 14336 + (tid & 31) * 16, 0x3F803F80u, 0x3F803F80u, 0x3F803F80u, 0x3F803F80u);
  }
  asm volatile("fence.proxy.async.shared::cta;" ::: "memory");
  __syncthreads();
  asm volatile("barrier.cluster.arrive.relaxed.aligned;" ::: "memory");
  const int rank = blockIdx.x & 1, rt = blockIdx.x >> 3, j = blockIdx.x & 7, p = j >> 1, cg = 4 * rank + p;
  const int wq = warp & 3, t128 = tid & 127, g = lane >> 2, t = lane & 3;
  uint32_t ep, tag;
  auto load_ep = [&]() { asm volatile("ld.relaxed.gpu.global.u32 %0, [%1];" : "=r"(ep) : "l"(&g_cnt1) : "memory"); };
  auto a_slot = [&](int i, int own) { return B_SA + (i + (i >= own)) * 14336; };
  auto in_addr = [&](int q, int cw) { return sb + a_slot(4 + q, cg) + cw * 1792; };
  auto out_addr = [&](int cc, int w) { return sb + a_slot((cc & 2) + w, cg) + (cc & 1) * 7168; };
  auto in_cta = [&](int q) { return rt * 8 + ((p + 3 - q) & 3) * 2 + rank; };
  auto in_src = [&](int q, int cw) { return g_part + (size_t)(in_cta(q) * 3 + q) * 896 + cw * 112; };
  auto add_in = [&](float (&sum)[28], int q, int cw) {
    const uint32_t a = in_addr(q, cw);
    const uint4 v0 = lds128(a + lane * 16), v1 = lds128(a + 512 + lane * 16), v2 = lds128(a + 1024 + lane * 16);
    uint32_t in[14] = {v0.x, v0.y, v0.z, v0.w, v1.x, v1.y, v1.z, v1.w, v2.x, v2.y, v2.z, v2.w, 0, 0};
    asm volatile("ld.shared.v2.u32 {%0, %1}, [%2];" : "=r"(in[12]), "=r"(in[13]) : "r"(a + 1536 + lane * 8) : "memory");
    int it = 0;
    while ((((in[3] ^ tag) | (in[7] ^ tag) | (in[11] ^ tag) | (in[13] ^ tag)) & 0x10000u) && ++it < 400000) {
      const uint4* gs = pin(in_src(q, cw));
#pragma unroll
      for (int i = 0; i < 3; i++) ld128(gs + i * 32 + lane, in + 4 * i);
      asm volatile("{\n.reg .b64 v;\nld.relaxed.gpu.global.b64 v, [%2];\nmov.b64 {%0, %1}, v;\n}"
                   : "=r"(in[12]), "=r"(in[13]) : "l"((const uint2*)(gs + 96) + lane) : "memory");
    }
#pragma unroll
    for (int i = 0; i < 14; i++) { sum[2 * i] += bf_lo(in[i]); sum[2 * i + 1] += bf_hi(in[i]); }
  };

  if (wg == 2) {
    asm volatile("setmaxnreg.dec.sync.aligned.u32 40;");
    const int p_slot = lane % B_NSLOT;
    const uint32_t p_dst = pin(sb + B_RING + p_slot * B_SLOT), p_fb = pin(bar_full + 8 * p_slot), p_eb = pin(bar_empty + 8 * p_slot);
    const uint32_t p_ph = pin((uint32_t)(lane / B_NSLOT + 1) & 1u);
    const char* p_src1 = pin((const char*)g_wimg + (size_t)j * 602112 + lane * 14336);
    const int p_ci = lane < 3 ? 0 : lane < 6 ? 1 : lane < 8 ? lane - 6 : lane < 12 ? 2 : 3;
    const int p_kp = lane < 3 ? lane : lane < 6 ? lane - 3 : lane < 8 ? 3 : (lane & 3);
    const char* p_src2 = pin((const char*)g_wimg + (size_t)(j ^ (p_kp >> 1)) * 602112 + 401408 + ((4 * rank + ((p + 1 + p_ci) & 3)) * 2 + (p_kp & 1)) * 12544);
    asm volatile("barrier.cluster.wait.aligned;" ::: "memory");
    asm volatile("griddepcontrol.wait;" ::: "memory");
    if (warp == 8) {
      if (lane == 0) TR(1, 1);
#pragma unroll 1
      for (int s = 0; s < 28; s++) {
        if (lane == s) {
          if (s >= B_NSLOT) mbar_wait(p_eb, p_ph);
          mbar_expect(p_fb, 14336);
          bulk_ld(p_dst, p_src1, 14336, p_fb);
        }
        __syncwarp();
      }
#pragma unroll 1
      for (int s = 0; s < 16; s++) {
        if (lane == s) {
          mbar_wait(p_eb, p_ph);
          mbar_expect(p_fb, 12544);
          bulk_ld(p_dst, p_src2, 12544, p_fb);
        }
        __syncwarp();
      }
    } else if (warp == 9) {
      if (lane < 14) {
        mbar_expect(bar_h + 8 * lane, 8192);
        bulk_ld_mc(sb + B_SA + lane * 8192 + rank * 4096, (const char*)g_himg + (size_t)rt * 114688 + lane * 8192 + rank * 4096, 4096, bar_h + 8 * lane);
      } else if (lane == 14) {
        mbar_expect(bar_cs, 7168);
        bulk_ld(sb + B_CS, g_cimg + j * 448, 7168, bar_cs);
      }
      __syncwarp();
      load_ep(); ep >>= 7;
      const int lq = (lane >> 1) & 3, lcw = (lane & 1) * 4;
      const uint32_t* fl = g_flag + in_cta(lq) * 8 + (lane & 7);
      bool todo = lane < 6, live = false;
      int it = 0;
      while (__any_sync(~0u, todo) && ++it < 400000) {
        if (!live) { __nanosleep(400); live = mbar_test(bar_g2, 0); }
        if (todo) {
          uint32_t w;
          asm volatile("ld.relaxed.gpu.global.u32 %0, [%1];" : "=r"(w) : "l"(fl) : "memory");
          if (live && w == ep) {
            mbar_expect(bar_in + 8 * lane, 7168);
            bulk_ld(in_addr(lq, lcw), in_src(lq, lcw), 7168, bar_in + 8 * lane);
            todo = false;
            if (lane & 1) TR(1, 24 + lq);
          }
        }
      }
    } else {
      const int t64 = tid - 320;
      load_ep();
      const int r = (lane >> 1) & 7, c = (j & 3) * 2 + (lane & 1);
      const uint32_t src = sb + B_SA + (t64 >> 4) * 2048 + (j >> 2) * 1024 + r * 128 + ((c ^ r) << 4);
      float a[16];
#pragma unroll
      for (int k = 0; k < 16; k++) a[k] = 0.f;
#pragma unroll 1
      for (int i = 0; i < 14; i++) {
        mbar_wait(bar_h + 8 * i, 0);
        uint4 v = lds128(src + i * 8192);
        float e[8] = {bf_lo(v.x), bf_hi(v.x), bf_lo(v.y), bf_hi(v.y), bf_lo(v.z), bf_hi(v.z), bf_lo(v.w), bf_hi(v.w)};
#pragma unroll
        for (int k = 0; k < 8; k++) { a[2 * k] += e[k]; a[2 * k + 1] = fmaf(e[k], e[k], a[2 * k + 1]); }
        __nanosleep(160);
      }
      __syncwarp();
      if (lane == 0) { mbar_arrive(bar_g2); asm volatile("mbarrier.arrive.shared::cluster.b64 _, [%0];" ::"r"(mapa(bar_afree, rank ^ 1)) : "memory"); }
#pragma unroll
      for (int rd = 0; rd < 4; rd++) {
        const int n = 8 >> rd;
        const bool up = lane & (2 * n);
#pragma unroll
        for (int k = 0; k < 8; k++) {
          if (k < n) {
            float keep = up ? a[k + n] : a[k], give = up ? a[k] : a[k + n];
            a[k] = keep + __shfl_xor_sync(~0u, give, 2 * n);
          }
        }
      }
      float* red = (float*)(sm + B_RED);
      red[(warp & 1) * 32 + (lane & 1) * 16 + (lane >> 1)] = a[0];
      bar_sync(1, 64);
      if (t64 < 16) {
        float mean = (red[2 * t64] + red[32 + 2 * t64]) * (1.f / DM);
        float var = fmaxf(fmaf(-mean, mean, (red[2 * t64 + 1] + red[33 + 2 * t64]) * (1.f / DM)), 0.f);
        float rs = __frcp_rn(rbf(__fsqrt_rn(rbf(rbf(var) + 1e-5f))));
        asm volatile("st.relaxed.gpu.global.u32 [%0], %1;"
                     ::"l"(g_stat2 + rt * 128 + j * 16 + t64), "r"((__float_as_uint(rs * rs) & ~1u) | ((ep >> 7) & 1u)) : "memory");
      }
      if (t64 == 0) TR(1, 2);
      if (lane == 0) {
        const int w = warp & 1;
        for (int cc = 0; cc < 3; cc++) {
          mbar_wait(bar_out + 8 * (cc * 2 + w), 0);
          asm volatile("cp.async.bulk.global.shared::cta.bulk_group [%0], [%1], 7168;"
                       ::"l"(g_part + (size_t)(blockIdx.x * 3 + cc) * 896 + w * 448), "r"(out_addr(cc, w)) : "memory");
          asm volatile("cp.async.bulk.commit_group;" ::: "memory");
          asm volatile("cp.async.bulk.wait_group 0;" ::: "memory");
          asm volatile("st.relaxed.gpu.global.u32 [%0], %1;" ::"l"(g_flag + blockIdx.x * 8 + cc * 2 + w), "r"(ep >> 7) : "memory");
          if (w) TR(1, 27 + cc);
        }
      }
    }
  } else {
    asm volatile("setmaxnreg.inc.sync.aligned.u32 232;");
    asm volatile("barrier.cluster.wait.aligned;" ::: "memory");
    uint32_t hh[56];
    const bool relt = t128 == 0;
    auto release = [&](int sl) { if (relt) mbar_arrive(bar_empty + 8 * sl); };
    auto send_hh = [&](int q) {
      const uint32_t da = mapa(sb + a_slot(2 * q + wg, cg ^ 4) + t128 * 16, rank ^ 1), db = mapa(bar_hh + 8 * (2 * q + wg), rank ^ 1);
#pragma unroll
      for (int i = 0; i < 7; i++)
        asm volatile("st.async.weak.shared::cluster.mbarrier::complete_tx::bytes.v4.b32 [%0], {%1, %2, %3, %4}, [%5];"
                     ::"r"(da + i * 2048), "r"(hh[28 * q + 4 * i]), "r"(hh[28 * q + 4 * i + 1]),
                       "r"(hh[28 * q + 4 * i + 2]), "r"(hh[28 * q + 4 * i + 3]), "r"(db) : "memory");
    };
    const uint32_t alo = __shfl_sync(~0u, ((sb + B_SA + wg * 1024) & 0x3FFFF) >> 4, 0);
    const uint32_t blo = (((sb + B_RING) & 0x3FFFF) >> 4) | (8u << 16);
    const uint32_t clo = ((sb + B_CS) & 0x3FFFF) >> 4;
    uint32_t nm0, nm1;
    if (wg == 1) bar_sync(3, 256);
#define G1S(Q, ST) do { g1_stage<Q, ST>(acc, alo, blo, bar_full, bar_h); wg_commit(); \
      if (ST > 0) { wg_wait<1>(); release((Q * 14 + ST - 1) % B_NSLOT); } } while (0)
#define G1HH(Q) do { \
      _Pragma("unroll") \
      for (int i = 0; i < 28; i++) hh[28 * Q + i] = pack_bf16(acc[2 * i] * acc[56 + 2 * i], acc[2 * i + 1] * acc[57 + 2 * i]); \
    } while (0)
    {
      float acc[116];
      G1S(0, 0);
      if (tid == 0) TR(1, 3);
      G1S(0, 1);
      if (wg == 0) asm volatile("bar.arrive 3, 256;" ::: "memory");
      G1S(0, 2); G1S(0, 3); G1S(0, 4); G1S(0, 5); G1S(0, 6); G1S(0, 7); G1S(0, 8); G1S(0, 9); G1S(0, 10); G1S(0, 11); G1S(0, 12);
      G1S(0, 13);
      if (tid == 0) TR(1, 4);
      mbar_wait(bar_cs, 0);
      wg_wait<0>(); reg_fence(acc); release(13 % B_NSLOT);
      {
        const uint32_t msk = t == 0 ? 0xFFFFFFFFu : t == 1 ? 0xFFFFu : 0u;
        const float a = acc[112] * (-1.f / DM), b = acc[114] * (-1.f / DM);
        nm0 = pack_bf16(a, a) & msk; nm1 = pack_bf16(b, b) & msk;
      }
      wg_fence();
      wgmma_rs224<0, 8, 1>(*(float(*)[112])acc, nm0, nm1, 0u, 0u, clo);
      wg_commit(); wg_wait<0>(); reg_fence(acc);
      G1HH(0);
      if (tid == 0) TR(1, 5);
      G1S(1, 0); G1S(1, 1); G1S(1, 2); G1S(1, 3); G1S(1, 4); G1S(1, 5); G1S(1, 6);
      if (relt) asm volatile("mbarrier.arrive.shared::cluster.b64 _, [%0];" ::"r"(mapa(bar_afree, rank ^ 1)) : "memory");
      G1S(1, 7); G1S(1, 8); G1S(1, 9);
      if (relt) asm volatile("mbarrier.arrive.shared::cluster.b64 _, [%0];" ::"r"(mapa(bar_afree + 8, rank ^ 1)) : "memory");
      mbar_wait(bar_afree, 0);
      send_hh(0);
      G1S(1, 10); G1S(1, 11); G1S(1, 12);
      load_ep();
      g1_stage<1, 13>(acc, alo, blo, bar_full, bar_h);
      wgmma_rs224<224, 8, 1>(*(float(*)[112])acc, nm0, nm1, 0u, 0u, clo);
      wg_commit(); wg_wait<1>(); release(26 % B_NSLOT);
      wg_wait<0>(); reg_fence(acc); release(27 % B_NSLOT);
      if (t128 == 0) mbar_arrive(bar_g2);
      G1HH(1);
      if (tid == 0) TR(1, 6);
    }
    float accA[28], accB[28], accC[28];
    uint32_t ph0[28], ph1[28];
    ep = pin(ep >> 7); tag = pin((ep & 1u) << 16);
#define ISSUE(acc, I, a, FIRST) do { \
      constexpr int s_ = 28 + (I), sl_ = s_ % B_NSLOT; \
      mbar_wait(bar_full + 8 * sl_, (s_ / B_NSLOT) & 1); \
      wg_fence(); \
      wgmma_rs56<(sl_ * B_SLOT + 0 * 256) / 16, 112, !(FIRST)>(acc, (a)[0], (a)[1], (a)[2], (a)[3], blo); \
      wgmma_rs56<(sl_ * B_SLOT + 1 * 256) / 16, 112, 1>(acc, (a)[4], (a)[5], (a)[6], (a)[7], blo); \
      wgmma_rs56<(sl_ * B_SLOT + 2 * 256) / 16, 112, 1>(acc, (a)[8], (a)[9], (a)[10], (a)[11], blo); \
      wgmma_rs56<(sl_ * B_SLOT + 3 * 256) / 16, 112, 1>(acc, (a)[12], (a)[13], (a)[14], (a)[15], blo); \
      wgmma_rs56<(sl_ * B_SLOT + 4 * 256) / 16, 112, 1>(acc, (a)[16], (a)[17], (a)[18], (a)[19], blo); \
      wgmma_rs56<(sl_ * B_SLOT + 5 * 256) / 16, 112, 1>(acc, (a)[20], (a)[21], (a)[22], (a)[23], blo); \
      wgmma_rs56<(sl_ * B_SLOT + 6 * 256) / 16, 112, 1>(acc, (a)[24], (a)[25], (a)[26], (a)[27], blo); \
      wg_commit(); } while (0)
    auto rel = [&](int i) { release((28 + i) % B_NSLOT); };
    auto tg = [&](uint32_t v) { return (v & 0xFFFEFFFFu) | tag; };
    auto send = [&](float (&acc)[28], int cc) {
      reg_fence(acc);
      const uint32_t a = out_addr(cc, wg) + wq * 1792;
#pragma unroll
      for (int q = 0; q < 3; q++)
        sts128(a + q * 512 + lane * 16, pack_bf16(acc[8 * q], acc[8 * q + 1]), pack_bf16(acc[8 * q + 2], acc[8 * q + 3]),
               pack_bf16(acc[8 * q + 4], acc[8 * q + 5]), tg(pack_bf16(acc[8 * q + 6], acc[8 * q + 7])));
      sts64(a + 1536 + lane * 8, pack_bf16(acc[24], acc[25]), tg(pack_bf16(acc[26], acc[27])));
      asm volatile("fence.proxy.async.shared::cta;" ::: "memory");
      mbar_arrive(bar_out + 8 * (cc * 2 + wg));
    };
    auto load_hh = [&](uint32_t (&d)[28], int q) {
      mbar_wait(bar_hh + 8 * (2 * q + wg), 0);
      const uint32_t a = sb + a_slot(2 * q + wg, cg) + t128 * 16;
#pragma unroll
      for (int i = 0; i < 7; i++) {
        const uint4 v = lds128(a + i * 2048);
        d[4 * i] = v.x; d[4 * i + 1] = v.y; d[4 * i + 2] = v.z; d[4 * i + 3] = v.w;
      }
    };
    ISSUE(accA, 0, hh, true);
    mbar_wait(bar_afree + 8, 0);
    send_hh(1);
    ISSUE(accA, 1, hh + 28, false);
    load_hh(ph0, 0);
    wg_wait<1>(); rel(0);
    ISSUE(accA, 2, ph0, false);      wg_wait<1>(); rel(1);
    ISSUE(accB, 3, hh, true);        wg_wait<1>(); rel(2);
    ISSUE(accB, 4, hh + 28, false);  wg_wait<1>(); rel(3);
    ISSUE(accB, 5, ph0, false);
    if (tid == 0) TR(1, 11);
    load_hh(ph1, 1);
    wg_wait<1>(); rel(4);
    ISSUE(accA, 6, ph1, false);      wg_wait<1>(); rel(5);
    ISSUE(accB, 7, ph1, false);      wg_wait<1>(); rel(6);
    ISSUE(accC, 8, hh, true);        send(accA, 0); wg_wait<1>(); rel(7);
    if (tid == 0) TR(1, 13);
    ISSUE(accC, 9, hh + 28, false);  send(accB, 1); wg_wait<1>(); rel(8);
    ISSUE(accC, 10, ph0, false);
    ISSUE(accC, 11, ph1, false);
    const int row = rt * 128 + wg * 64 + wq * 16 + g;
    uint32_t r20, r21;
    asm volatile("ld.relaxed.gpu.global.u32 %0, [%1];" : "=r"(r20) : "l"(g_stat2 + row) : "memory");
    asm volatile("ld.relaxed.gpu.global.u32 %0, [%1];" : "=r"(r21) : "l"(g_stat2 + row + 8) : "memory");
    ISSUE(accB, 12, hh, true);
    wg_wait<1>();
    send(accC, 2);
    if (tid == 0) TR(1, 16);
    ISSUE(accB, 13, hh + 28, false);
    ISSUE(accB, 14, ph0, false);
    ISSUE(accB, 15, ph1, false);
    if (tid == 0) TR(1, 7);
    uint32_t hres[16];
#pragma unroll
    for (int i = 0; i < 4; i++) {
      int qq = lane >> 3, r = lane & 7, kg = 7 * cg + 2 * i + (qq >> 1), c = 2 * wq + (qq & 1);
      if (kg > 55) kg = 55;
      asm volatile("ldmatrix.sync.aligned.m8n8.x4.trans.shared.b16 {%0,%1,%2,%3}, [%4];"
                   : "=r"(hres[4 * i]), "=r"(hres[4 * i + 1]), "=r"(hres[4 * i + 2]), "=r"(hres[4 * i + 3])
                   : "r"(sb + B_SA + kg * 2048 + wg * 1024 + r * 128 + ((c ^ r) << 4)) : "memory");
    }
    {
      int it = 0;
      while ((((r20 ^ ep) | (r21 ^ ep)) & 1u) && ++it < 400000) {
        asm volatile("ld.relaxed.gpu.global.u32 %0, [%1];" : "=r"(r20) : "l"(g_stat2 + row) : "memory");
        asm volatile("ld.relaxed.gpu.global.u32 %0, [%1];" : "=r"(r21) : "l"(g_stat2 + row + 8) : "memory");
      }
    }
    wg_wait<0>();
    reg_fence(accB);
    if (tid == 0) TR(1, 9);
#pragma unroll 1
    for (int q = 0; q < 3; q++) {
      mbar_wait(bar_in + 8 * (2 * q + wg), 0);
      add_in(accB, q, warp);
      if (tid == 0 && q == 1) TR(1, 12);
    }
    uint32_t* o0 = (uint32_t*)(out + (size_t)row * DM + 56 * cg + 2 * t);
    uint32_t* o1 = o0 + 8 * DM / 2;
#pragma unroll
    for (int i = 0; i < 7; i++) {
      o0[4 * i] = hadd2_bf(hres[2 * i], pack_bf16(accB[4 * i] * __uint_as_float(r20), accB[4 * i + 1] * __uint_as_float(r20)));
      o1[4 * i] = hadd2_bf(hres[2 * i + 1], pack_bf16(accB[4 * i + 2] * __uint_as_float(r21), accB[4 * i + 3] * __uint_as_float(r21)));
    }
    if (tid == 0) TR(1, 10);
    if (tid == 128) TR(1, 15);
  }
}

extern "C" void kernel_launch(void* const* d_in, const int* in_sizes, int n_in, void* d_out, int out_size) {
  const __nv_bfloat16* x = (const __nv_bfloat16*)d_in[0];
  const __nv_bfloat16 *are = (const __nv_bfloat16*)d_in[1], *aim = (const __nv_bfloat16*)d_in[2], *bre = (const __nv_bfloat16*)d_in[3],
                      *bim = (const __nv_bfloat16*)d_in[4], *cre = (const __nv_bfloat16*)d_in[5], *cim = (const __nv_bfloat16*)d_in[6],
                      *logdt = (const __nv_bfloat16*)d_in[7], *dskip = (const __nv_bfloat16*)d_in[8];
  const __nv_bfloat16 *wg = (const __nv_bfloat16*)d_in[10], *wu = (const __nv_bfloat16*)d_in[11], *wd = (const __nv_bfloat16*)d_in[12];

  static bool init = false;
  if (!init) {
    init = true;
    cudaFuncSetAttribute(k_ffn, cudaFuncAttributeMaxDynamicSharedMemorySize, B_SMEM);
    cudaFuncSetAttribute(k_front, cudaFuncAttributeMaxDynamicSharedMemorySize, A_SMEM);
  }
  cudaStream_t st = cudaStreamPerThread;
  k_front<<<128, 512, A_SMEM, st>>>(
      x, (const uint32_t*)are, (const uint32_t*)aim, (const uint32_t*)bre, (const uint32_t*)bim, (const uint32_t*)cre, (const uint32_t*)cim,
      (const unsigned short*)logdt, (const unsigned short*)dskip, (const uint4*)wg, (const uint4*)wu, (const uint4*)wd);
  cudaLaunchConfig_t cfg = {};
  cfg.gridDim = dim3(128); cfg.blockDim = dim3(384); cfg.dynamicSmemBytes = B_SMEM; cfg.stream = st;
  cudaLaunchAttribute at[1];
  at[0].id = cudaLaunchAttributeProgrammaticStreamSerialization; at[0].val.programmaticStreamSerializationAllowed = 1;
  cfg.attrs = at; cfg.numAttrs = 1;
  cudaLaunchKernelEx(&cfg, k_ffn, (__nv_bfloat16*)d_out);
}
```

```cpp
#include <cuda_runtime.h>
#include <cuda_bf16.h>
#include <stdint.h>

constexpr int LSEQ = 2048, DM = 448;

__device__ uint4    g_himg[16 * 114688 / 16];
__device__ uint4    g_cimg[8 * 2 * 224];
__device__ uint32_t g_stat2[LSEQ];
__device__ uint4    g_part[128 * 3 * 896];
__device__ uint4    g_wimg[8 * 602112 / 16];
__device__ uint4    g_ux[DM * 128 * 4];
__device__ unsigned g_cnt1;
__device__ uint32_t g_flag[128 * 8];

#define TR(k, i) do {} while (0)
__device__ __forceinline__ uint32_t s2u(const void* p) { return (uint32_t)__cvta_generic_to_shared(p); }
__device__ __forceinline__ void mbar_init(uint32_t b, int c) { asm volatile("mbarrier.init.shared::cta.b64 [%0], %1;" ::"r"(b), "r"(c)); }
__device__ __forceinline__ void mbar_expect(uint32_t b, int bytes) { asm volatile("mbarrier.arrive.expect_tx.shared::cta.b64 _, [%0], %1;" ::"r"(b), "r"(bytes) : "memory"); }
__device__ __forceinline__ void mbar_arrive(uint32_t b) { asm volatile("mbarrier.arrive.shared::cta.b64 _, [%0];" ::"r"(b) : "memory"); }
__device__ __forceinline__ void mbar_wait(uint32_t b, int ph) {
  asm volatile("{\n.reg .pred p;\n.reg .b32 n;\nmov.b32 n, 0;\nLW:\nmbarrier.try_wait.parity.shared::cta.b64 p, [%0], %1;\n@p bra LD;\n"
               "add.u32 n, n, 1;\nsetp.lt.u32 p, n, 4000000;\n@p bra LW;\ntrap;\nLD:\n}" ::"r"(b), "r"(ph) : "memory");
}
__device__ __forceinline__ bool mbar_test(uint32_t b, int ph) {
  uint32_t ok;
  asm volatile("{\n.reg .pred p;\nmbarrier.test_wait.parity.shared::cta.b64 p, [%1], %2;\nselp.u32 %0, 1, 0, p;\n}" : "=r"(ok) : "r"(b), "r"(ph) : "memory");
  return ok;
}
__device__ __forceinline__ void wg_fence() { asm volatile("wgmma.fence.sync.aligned;" ::: "memory"); }
__device__ __forceinline__ void wg_commit() { asm volatile("wgmma.commit_group.sync.aligned;" ::: "memory"); }
template <int N> __device__ __forceinline__ void wg_wait() { asm volatile("wgmma.wait_group.sync.aligned %0;" ::"n"(N) : "memory"); }
template <int N> __device__ __forceinline__ void reg_fence(float (&a)[N]) {
#pragma unroll
  for (int i = 0; i < N; i++) asm volatile("" : "+f"(a[i])::"memory");
}
__device__ __forceinline__ uint32_t pack_bf16(float lo, float hi) {
  uint32_t r; asm("cvt.rn.bf16x2.f32 %0, %1, %2;" : "=r"(r) : "f"(hi), "f"(lo)); return r;
}
__device__ __forceinline__ float bf_lo(uint32_t v) { return __uint_as_float(v << 16); }
__device__ __forceinline__ float bf_hi(uint32_t v) { return __uint_as_float(v & 0xFFFF0000u); }
__device__ __forceinline__ float rbf(float x) { return __bfloat162float(__float2bfloat16_rn(x)); }
__device__ __forceinline__ uint32_t hmul2_bf(uint32_t a, uint32_t b) { uint32_t r; asm("mul.rn.bf16x2 %0, %1, %2;" : "=r"(r) : "r"(a), "r"(b)); return r; }
__device__ __forceinline__ uint32_t hadd2_bf(uint32_t a, uint32_t b) { uint32_t r; asm("add.rn.bf16x2 %0, %1, %2;" : "=r"(r) : "r"(a), "r"(b)); return r; }
__device__ __forceinline__ void bulk_ld(uint32_t dst, const void* src, int bytes, uint32_t bar) {
  asm volatile("cp.async.bulk.shared::cluster.global.mbarrier::complete_tx::bytes [%0], [%1], %2, [%3];"
               ::"r"(dst), "l"(src), "r"(bytes), "r"(bar) : "memory");
}

template <int BYTES>
__device__ __forceinline__ void bulk_ld_elect(uint32_t dst, const void* src, uint32_t bar) {
  asm volatile("{\n.reg .pred p;\nelect.sync _|p, 0xffffffff;\n"
               "@p mbarrier.arrive.expect_tx.shared::cta.b64 _, [%2], %3;\n"
               "@p cp.async.bulk.shared::cluster.global.mbarrier::complete_tx::bytes [%0], [%1], %3, [%2];\n}"
               ::"r"(dst), "l"(src), "r"(bar), "n"(BYTES) : "memory");
}
__device__ __forceinline__ void bulk_ld_mc(uint32_t dst, const void* src, int bytes, uint32_t bar) {
  asm volatile("cp.async.bulk.shared::cluster.global.mbarrier::complete_tx::bytes.multicast::cluster [%0], [%1], %2, [%3], %4;"
               ::"r"(dst), "l"(src), "r"(bytes), "r"(bar), "h"((uint16_t)3) : "memory");
}
template <int AOFF, uint32_t AHI, int BOFF, uint32_t BHI, int ACC>
__device__ __forceinline__ void wgmma_ss224(float (&d)[112], uint32_t alo, uint32_t blo) {
  asm volatile("{\n.reg .pred p;\n.reg .b64 ad, bd;\nsetp.ne.b32 p, %118, 0;\n"
    "mov.b64 ad, {%112, %115};\nadd.s64 ad, ad, %114;\nmov.b64 bd, {%113, %117};\nadd.s64 bd, bd, %116;\n"
    "wgmma.mma_async.sync.aligned.m64n224k16.f32.bf16.bf16 {%0,%1,%2,%3,%4,%5,%6,%7,%8,%9,%10,%11,%12,%13,%14,%15,%16,%17,%18,%19,%20,%21,%22,%23,%24,%25,%26,%27,%28,%29,%30,%31,%32,%33,%34,%35,%36,%37,%38,%39,%40,%41,%42,%43,%44,%45,%46,%47,%48,%49,%50,%51,%52,%53,%54,%55,%56,%57,%58,%59,%60,%61,%62,%63,%64,%65,%66,%67,%68,%69,%70,%71,%72,%73,%74,%75,%76,%77,%78,%79,%80,%81,%82,%83,%84,%85,%86,%87,%88,%89,%90,%91,%92,%93,%94,%95,%96,%97,%98,%99,%100,%101,%102,%103,%104,%105,%106,%107,%108,%109,%110,%111}, ad, bd, p, 1, 1, 1, 1;\n}\n"
    : "+f"(d[0]),"+f"(d[1]),"+f"(d[2]),"+f"(d[3]),"+f"(d[4]),"+f"(d[5]),"+f"(d[6]),"+f"(d[7]),"+f"(d[8]),"+f"(d[9]),"+f"(d[10]),"+f"(d[11]),"+f"(d[12]),"+f"(d[13]),"+f"(d[14]),"+f"(d[15]),"+f"(d[16]),"+f"(d[17]),"+f"(d[18]),"+f"(d[19]),"+f"(d[20]),"+f"(d[21]),"+f"(d[22]),"+f"(d[23]),"+f"(d[24]),"+f"(d[25]),"+f"(d[26]),"+f"(d[27]),"+f"(d[28]),"+f"(d[29]),"+f"(d[30]),"+f"(d[31]),"+f"(d[32]),"+f"(d[33]),"+f"(d[34]),"+f"(d[35]),"+f"(d[36]),"+f"(d[37]),"+f"(d[38]),"+f"(d[39]),"+f"(d[40]),"+f"(d[41]),"+f"(d[42]),"+f"(d[43]),"+f"(d[44]),"+f"(d[45]),"+f"(d[46]),"+f"(d[47]),"+f"(d[48]),"+f"(d[49]),"+f"(d[50]),"+f"(d[51]),"+f"(d[52]),"+f"(d[53]),"+f"(d[54]),"+f"(d[55]),"+f"(d[56]),"+f"(d[57]),"+f"(d[58]),"+f"(d[59]),"+f"(d[60]),"+f"(d[61]),"+f"(d[62]),"+f"(d[63]),"+f"(d[64]),"+f"(d[65]),"+f"(d[66]),"+f"(d[67]),"+f"(d[68]),"+f"(d[69]),"+f"(d[70]),"+f"(d[71]),"+f"(d[72]),"+f"(d[73]),"+f"(d[74]),"+f"(d[75]),"+f"(d[76]),"+f"(d[77]),"+f"(d[78]),"+f"(d[79]),"+f"(d[80]),"+f"(d[81]),"+f"(d[82]),"+f"(d[83]),"+f"(d[84]),"+f"(d[85]),"+f"(d[86]),"+f"(d[87]),"+f"(d[88]),"+f"(d[89]),"+f"(d[90]),"+f"(d[91]),"+f"(d[92]),"+f"(d[93]),"+f"(d[94]),"+f"(d[95]),"+f"(d[96]),"+f"(d[97]),"+f"(d[98]),"+f"(d[99]),"+f"(d[100]),"+f"(d[101]),"+f"(d[102]),"+f"(d[103]),"+f"(d[104]),"+f"(d[105]),"+f"(d[106]),"+f"(d[107]),"+f"(d[108]),"+f"(d[109]),"+f"(d[110]),"+f"(d[111])
    : "r"(alo), "r"(blo), "n"(AOFF), "n"(AHI), "n"(BOFF), "n"(BHI), "n"(ACC));
}
template <int AOFF, uint32_t AHI, int BOFF, uint32_t BHI, int ACC>
__device__ __forceinline__ void wgmma_ss232(float (&d)[116], uint32_t alo, uint32_t blo) {
  asm volatile("{\n.reg .pred p;\n.reg .b64 ad, bd;\nsetp.ne.b32 p, %122, 0;\n"
    "mov.b64 ad, {%116, %119};\nadd.s64 ad, ad, %118;\nmov.b64 bd, {%117, %121};\nadd.s64 bd, bd, %120;\n"
    "wgmma.mma_async.sync.aligned.m64n232k16.f32.bf16.bf16 {%0,%1,%2,%3,%4,%5,%6,%7,%8,%9,%10,%11,%12,%13,%14,%15,%16,%17,%18,%19,%20,%21,%22,%23,%24,%25,%26,%27,%28,%29,%30,%31,%32,%33,%34,%35,%36,%37,%38,%39,%40,%41,%42,%43,%44,%45,%46,%47,%48,%49,%50,%51,%52,%53,%54,%55,%56,%57,%58,%59,%60,%61,%62,%63,%64,%65,%66,%67,%68,%69,%70,%71,%72,%73,%74,%75,%76,%77,%78,%79,%80,%81,%82,%83,%84,%85,%86,%87,%88,%89,%90,%91,%92,%93,%94,%95,%96,%97,%98,%99,%100,%101,%102,%103,%104,%105,%106,%107,%108,%109,%110,%111,%112,%113,%114,%115}, ad, bd, p, 1, 1, 1, 1;\n}\n"
    : "+f"(d[0]),"+f"(d[1]),"+f"(d[2]),"+f"(d[3]),"+f"(d[4]),"+f"(d[5]),"+f"(d[6]),"+f"(d[7]),"+f"(d[8]),"+f"(d[9]),"+f"(d[10]),"+f"(d[11]),"+f"(d[12]),"+f"(d[13]),"+f"(d[14]),"+f"(d[15]),"+f"(d[16]),"+f"(d[17]),"+f"(d[18]),"+f"(d[19]),"+f"(d[20]),"+f"(d[21]),"+f"(d[22]),"+f"(d[23]),"+f"(d[24]),"+f"(d[25]),"+f"(d[26]),"+f"(d[27]),"+f"(d[28]),"+f"(d[29]),"+f"(d[30]),"+f"(d[31]),"+f"(d[32]),"+f"(d[33]),"+f"(d[34]),"+f"(d[35]),"+f"(d[36]),"+f"(d[37]),"+f"(d[38]),"+f"(d[39]),"+f"(d[40]),"+f"(d[41]),"+f"(d[42]),"+f"(d[43]),"+f"(d[44]),"+f"(d[45]),"+f"(d[46]),"+f"(d[47]),"+f"(d[48]),"+f"(d[49]),"+f"(d[50]),"+f"(d[51]),"+f"(d[52]),"+f"(d[53]),"+f"(d[54]),"+f"(d[55]),"+f"(d[56]),"+f"(d[57]),"+f"(d[58]),"+f"(d[59]),"+f"(d[60]),"+f"(d[61]),"+f"(d[62]),"+f"(d[63]),"+f"(d[64]),"+f"(d[65]),"+f"(d[66]),"+f"(d[67]),"+f"(d[68]),"+f"(d[69]),"+f"(d[70]),"+f"(d[71]),"+f"(d[72]),"+f"(d[73]),"+f"(d[74]),"+f"(d[75]),"+f"(d[76]),"+f"(d[77]),"+f"(d[78]),"+f"(d[79]),"+f"(d[80]),"+f"(d[81]),"+f"(d[82]),"+f"(d[83]),"+f"(d[84]),"+f"(d[85]),"+f"(d[86]),"+f"(d[87]),"+f"(d[88]),"+f"(d[89]),"+f"(d[90]),"+f"(d[91]),"+f"(d[92]),"+f"(d[93]),"+f"(d[94]),"+f"(d[95]),"+f"(d[96]),"+f"(d[97]),"+f"(d[98]),"+f"(d[99]),"+f"(d[100]),"+f"(d[101]),"+f"(d[102]),"+f"(d[103]),"+f"(d[104]),"+f"(d[105]),"+f"(d[106]),"+f"(d[107]),"+f"(d[108]),"+f"(d[109]),"+f"(d[110]),"+f"(d[111]),"+f"(d[112]),"+f"(d[113]),"+f"(d[114]),"+f"(d[115])
    : "r"(alo), "r"(blo), "n"(AOFF), "n"(AHI), "n"(BOFF), "n"(BHI), "n"(ACC));
}
template <int OFF, uint32_t BHI, int ACC>
__device__ __forceinline__ void wgmma_rs224(float (&d)[112], uint32_t a0, uint32_t a1, uint32_t a2, uint32_t a3, uint32_t blo) {
  asm volatile("{\n.reg .pred p;\n.reg .b64 bd;\nsetp.ne.b32 p, %119, 0;\nmov.b64 bd, {%116, %118};\nadd.s64 bd, bd, %117;\n"
    "wgmma.mma_async.sync.aligned.m64n224k16.f32.bf16.bf16 {%0,%1,%2,%3,%4,%5,%6,%7,%8,%9,%10,%11,%12,%13,%14,%15,%16,%17,%18,%19,%20,%21,%22,%23,%24,%25,%26,%27,%28,%29,%30,%31,%32,%33,%34,%35,%36,%37,%38,%39,%40,%41,%42,%43,%44,%45,%46,%47,%48,%49,%50,%51,%52,%53,%54,%55,%56,%57,%58,%59,%60,%61,%62,%63,%64,%65,%66,%67,%68,%69,%70,%71,%72,%73,%74,%75,%76,%77,%78,%79,%80,%81,%82,%83,%84,%85,%86,%87,%88,%89,%90,%91,%92,%93,%94,%95,%96,%97,%98,%99,%100,%101,%102,%103,%104,%105,%106,%107,%108,%109,%110,%111}, {%112,%113,%114,%115}, bd, p, 1, 1, 1;\n}\n"
    : "+f"(d[0]),"+f"(d[1]),"+f"(d[2]),"+f"(d[3]),"+f"(d[4]),"+f"(d[5]),"+f"(d[6]),"+f"(d[7]),"+f"(d[8]),"+f"(d[9]),"+f"(d[10]),"+f"(d[11]),"+f"(d[12]),"+f"(d[13]),"+f"(d[14]),"+f"(d[15]),"+f"(d[16]),"+f"(d[17]),"+f"(d[18]),"+f"(d[19]),"+f"(d[20]),"+f"(d[21]),"+f"(d[22]),"+f"(d[23]),"+f"(d[24]),"+f"(d[25]),"+f"(d[26]),"+f"(d[27]),"+f"(d[28]),"+f"(d[29]),"+f"(d[30]),"+f"(d[31]),"+f"(d[32]),"+f"(d[33]),"+f"(d[34]),"+f"(d[35]),"+f"(d[36]),"+f"(d[37]),"+f"(d[38]),"+f"(d[39]),"+f"(d[40]),"+f"(d[41]),"+f"(d[42]),"+f"(d[43]),"+f"(d[44]),"+f"(d[45]),"+f"(d[46]),"+f"(d[47]),"+f"(d[48]),"+f"(d[49]),"+f"(d[50]),"+f"(d[51]),"+f"(d[52]),"+f"(d[53]),"+f"(d[54]),"+f"(d[55]),"+f"(d[56]),"+f"(d[57]),"+f"(d[58]),"+f"(d[59]),"+f"(d[60]),"+f"(d[61]),"+f"(d[62]),"+f"(d[63]),"+f"(d[64]),"+f"(d[65]),"+f"(d[66]),"+f"(d[67]),"+f"(d[68]),"+f"(d[69]),"+f"(d[70]),"+f"(d[71]),"+f"(d[72]),"+f"(d[73]),"+f"(d[74]),"+f"(d[75]),"+f"(d[76]),"+f"(d[77]),"+f"(d[78]),"+f"(d[79]),"+f"(d[80]),"+f"(d[81]),"+f"(d[82]),"+f"(d[83]),"+f"(d[84]),"+f"(d[85]),"+f"(d[86]),"+f"(d[87]),"+f"(d[88]),"+f"(d[89]),"+f"(d[90]),"+f"(d[91]),"+f"(d[92]),"+f"(d[93]),"+f"(d[94]),"+f"(d[95]),"+f"(d[96]),"+f"(d[97]),"+f"(d[98]),"+f"(d[99]),"+f"(d[100]),"+f"(d[101]),"+f"(d[102]),"+f"(d[103]),"+f"(d[104]),"+f"(d[105]),"+f"(d[106]),"+f"(d[107]),"+f"(d[108]),"+f"(d[109]),"+f"(d[110]),"+f"(d[111])
    : "r"(a0), "r"(a1), "r"(a2), "r"(a3), "r"(blo), "n"(OFF), "n"(BHI), "n"(ACC));
}
template <int OFF, uint32_t BHI, int ACC>
__device__ __forceinline__ void wgmma_rs56(float (&d)[28], uint32_t a0, uint32_t a1, uint32_t a2, uint32_t a3, uint32_t blo) {
  asm volatile("{\n.reg .pred p;\n.reg .b64 bd;\nsetp.ne.b32 p, %35, 0;\nmov.b64 bd, {%32, %34};\nadd.s64 bd, bd, %33;\n"
    "wgmma.mma_async.sync.aligned.m64n56k16.f32.bf16.bf16 {%0,%1,%2,%3,%4,%5,%6,%7,%8,%9,%10,%11,%12,%13,%14,%15,%16,%17,%18,%19,%20,%21,%22,%23,%24,%25,%26,%27}, {%28,%29,%30,%31}, bd, p, 1, 1, 1;\n}\n"
    : "+f"(d[0]),"+f"(d[1]),"+f"(d[2]),"+f"(d[3]),"+f"(d[4]),"+f"(d[5]),"+f"(d[6]),"+f"(d[7]),"+f"(d[8]),"+f"(d[9]),"+f"(d[10]),"+f"(d[11]),"+f"(d[12]),"+f"(d[13]),"+f"(d[14]),"+f"(d[15]),"+f"(d[16]),"+f"(d[17]),"+f"(d[18]),"+f"(d[19]),"+f"(d[20]),"+f"(d[21]),"+f"(d[22]),"+f"(d[23]),"+f"(d[24]),"+f"(d[25]),"+f"(d[26]),"+f"(d[27])
    : "r"(a0), "r"(a1), "r"(a2), "r"(a3), "r"(blo), "n"(OFF), "n"(BHI), "n"(ACC));
}

__device__ __forceinline__ void st128(uint4* p, uint32_t a, uint32_t b, uint32_t c, uint32_t d) {
  asm volatile("{\n.reg .b128 v;\n.reg .b64 lo, hi;\nmov.b64 lo, {%1, %2};\nmov.b64 hi, {%3, %4};\nmov.b128 v, {lo, hi};\n"
               "st.relaxed.gpu.global.b128 [%0], v;\n}" ::"l"(p), "r"(a), "r"(b), "r"(c), "r"(d) : "memory");
}
__device__ __forceinline__ void ld128(const uint4* p, uint32_t* r) {
  asm volatile("{\n.reg .b128 v;\n.reg .b64 lo, hi;\nld.relaxed.gpu.global.b128 v, [%4];\nmov.b128 {lo, hi}, v;\n"
               "mov.b64 {%0, %1}, lo;\nmov.b64 {%2, %3}, hi;\n}" : "=r"(r[0]), "=r"(r[1]), "=r"(r[2]), "=r"(r[3]) : "l"(p) : "memory");
}

template <int OFF, uint32_t BHI, int ACC>
__device__ __forceinline__ void wgmma_rs32(float (&d)[16], uint32_t a0, uint32_t a1, uint32_t a2, uint32_t a3, uint32_t blo) {
  asm volatile("{\n.reg .pred p;\n.reg .b64 bd;\nsetp.ne.b32 p, %23, 0;\nmov.b64 bd, {%20, %22};\nadd.s64 bd, bd, %21;\n"
    "wgmma.mma_async.sync.aligned.m64n32k16.f32.bf16.bf16 {%0,%1,%2,%3,%4,%5,%6,%7,%8,%9,%10,%11,%12,%13,%14,%15}, {%16,%17,%18,%19}, bd, p, 1, 1, 0;\n}\n"
    : "+f"(d[0]),"+f"(d[1]),"+f"(d[2]),"+f"(d[3]),"+f"(d[4]),"+f"(d[5]),"+f"(d[6]),"+f"(d[7]),"+f"(d[8]),"+f"(d[9]),"+f"(d[10]),"+f"(d[11]),"+f"(d[12]),"+f"(d[13]),"+f"(d[14]),"+f"(d[15])
    : "r"(a0), "r"(a1), "r"(a2), "r"(a3), "r"(blo), "n"(OFF), "n"(BHI), "n"(ACC));
}
template <int OFF, uint32_t BHI, int ACC>
__device__ __forceinline__ void wgmma_rs24(float (&d)[12], uint32_t a0, uint32_t a1, uint32_t a2, uint32_t a3, uint32_t blo) {
  asm volatile("{\n.reg .pred p;\n.reg .b64 bd;\nsetp.ne.b32 p, %19, 0;\nmov.b64 bd, {%16, %18};\nadd.s64 bd, bd, %17;\n"
    "wgmma.mma_async.sync.aligned.m64n24k16.f32.bf16.bf16 {%0,%1,%2,%3,%4,%5,%6,%7,%8,%9,%10,%11}, {%12,%13,%14,%15}, bd, p, 1, 1, 1;\n}\n"
    : "+f"(d[0]),"+f"(d[1]),"+f"(d[2]),"+f"(d[3]),"+f"(d[4]),"+f"(d[5]),"+f"(d[6]),"+f"(d[7]),"+f"(d[8]),"+f"(d[9]),"+f"(d[10]),"+f"(d[11])
    : "r"(a0), "r"(a1), "r"(a2), "r"(a3), "r"(blo), "n"(OFF), "n"(BHI), "n"(ACC));
}
template <int OFF, uint32_t BHI, int ACC>
__device__ __forceinline__ void wgmma_rs16(float (&d)[8], uint32_t a0, uint32_t a1, uint32_t a2, uint32_t a3, uint32_t blo) {
  asm volatile("{\n.reg .pred p;\n.reg .b64 bd;\nsetp.ne.b32 p, %15, 0;\nmov.b64 bd, {%12, %14};\nadd.s64 bd, bd, %13;\n"
    "wgmma.mma_async.sync.aligned.m64n16k16.f32.bf16.bf16 {%0,%1,%2,%3,%4,%5,%6,%7}, {%8,%9,%10,%11}, bd, p, 1, 1, 1;\n}\n"
    : "+f"(d[0]),"+f"(d[1]),"+f"(d[2]),"+f"(d[3]),"+f"(d[4]),"+f"(d[5]),"+f"(d[6]),"+f"(d[7])
    : "r"(a0), "r"(a1), "r"(a2), "r"(a3), "r"(blo), "n"(OFF), "n"(BHI), "n"(ACC));
}

constexpr int A_R1 = 0;
constexpr int A_R2A = A_R1 + 2624, A_R2B = A_R2A + 768, A_R3A = A_R2B + 768, A_R3B = A_R3A + 528;
constexpr int A_K1024 = A_R3B + 528;
constexpr int A_W5 = A_K1024 + 16;
constexpr int A_W3 = A_W5 + 4096;
constexpr int A_W9 = A_W3 + 4112;
constexpr int A_W7 = A_W9 + 2048;
constexpr int A_V  = A_W7 + 2048;
constexpr int A_UB = A_V + 2048;
constexpr int A_STG = A_UB + 5248;
constexpr int A_Y2 = A_STG, A_Y3 = A_Y2 + 6528, A_YB = A_Y3 + 4352;
constexpr int A_REC = A_STG + 4 * 4352;
constexpr int A_CH = A_REC + 8192;
static_assert(A_W5 % 16 == 0 && A_UB % 16 == 0 && A_CH % 16 == 0 && A_YB + 4096 <= A_REC, "layout");

struct cf { float x, y; };
__device__ __forceinline__ cf cmul(cf a, cf b) { cf r; r.x = fmaf(a.x, b.x, -a.y * b.y); r.y = fmaf(a.x, b.y, a.y * b.x); return r; }
__device__ __forceinline__ cf cexp_l(float lr, float li, float l) {
  float mag; asm("ex2.approx.ftz.f32 %0, %1;" : "=f"(mag) : "f"((lr * l) * 1.4426950408889634f));
  const float th = li * l;
  const float k = (fmaf(th, 0.15915494f, 12582912.f)) - 12582912.f;
  float ph = fmaf(th, 0.15915494f, -k);
  ph = fmaf(th, 6.4206383e-9f, ph) * 6.2831853f;
  cf r; r.x = mag * __cosf(ph); r.y = mag * __sinf(ph); return r;
}
__device__ __forceinline__ void sts16(uint32_t a, uint32_t v) { asm volatile("st.shared.u16 [%0], %1;" ::"r"(a), "h"((uint16_t)v) : "memory"); }
__device__ __forceinline__ void sts32(uint32_t a, uint32_t v) { asm volatile("st.shared.u32 [%0], %1;" ::"r"(a), "r"(v) : "memory"); }
__device__ __forceinline__ void sts64(uint32_t a, uint32_t v0, uint32_t v1) { asm volatile("st.shared.v2.u32 [%0], {%1, %2};" ::"r"(a), "r"(v0), "r"(v1) : "memory"); }
__device__ __forceinline__ void sts128(uint32_t a, uint32_t v0, uint32_t v1, uint32_t v2, uint32_t v3) {
  asm volatile("st.shared.v4.u32 [%0], {%1, %2, %3, %4};" ::"r"(a), "r"(v0), "r"(v1), "r"(v2), "r"(v3) : "memory");
}
__device__ __forceinline__ uint32_t lds32(uint32_t a) { uint32_t v; asm volatile("ld.shared.u32 %0, [%1];" : "=r"(v) : "r"(a) : "memory"); return v; }
__device__ __forceinline__ uint4 lds128(uint32_t a) {
  uint4 v; asm volatile("ld.shared.v4.u32 {%0, %1, %2, %3}, [%4];" : "=r"(v.x), "=r"(v.y), "=r"(v.z), "=r"(v.w) : "r"(a) : "memory"); return v;
}
__device__ __forceinline__ void ldsm4(uint32_t* r, uint32_t a) {
  asm volatile("ldmatrix.sync.aligned.m8n8.x4.shared.b16 {%0,%1,%2,%3}, [%4];" : "=r"(r[0]), "=r"(r[1]), "=r"(r[2]), "=r"(r[3]) : "r"(a) : "memory");
}
__device__ __forceinline__ void mma16816(float* d, const uint32_t* a, uint32_t b0, uint32_t b1) {
  asm volatile("mma.sync.aligned.m16n8k16.row.col.f32.bf16.bf16.f32 {%0,%1,%2,%3}, {%4,%5,%6,%7}, {%8,%9}, {%0,%1,%2,%3};"
               : "+f"(d[0]), "+f"(d[1]), "+f"(d[2]), "+f"(d[3]) : "r"(a[0]), "r"(a[1]), "r"(a[2]), "r"(a[3]), "r"(b0), "r"(b1));
}
__device__ __forceinline__ uint32_t hsub2_bf(uint32_t a, uint32_t b) { uint32_t r; asm("sub.rn.bf16x2 %0, %1, %2;" : "=r"(r) : "r"(a), "r"(b)); return r; }
__device__ __forceinline__ void bar_sync(int id, int n) { asm volatile("bar.sync %0, %1;" ::"r"(id), "r"(n) : "memory"); }

template <int S> struct F1B { static constexpr int c = S / 4 + ((S & 3) == 3 ? 0 : 0), cc = (16 * S) / 64, ks = (64 * cc - (16 * S - 48)) / 16, off = (A_UB + 2 * ks * 656 + (9 - cc) * 16) / 16; };

template <int NS>
__device__ __forceinline__ void load_quads(uint32_t* q, uint32_t addr) {
#pragma unroll
  for (int i = 0; i < NS; i++) {
    q[4 * i] = lds32(addr + i * 64); q[4 * i + 1] = lds32(addr + i * 64 + 32);
    q[4 * i + 2] = i ? q[4 * i - 3] : lds32(addr - 32);
    q[4 * i + 3] = q[4 * i];
  }
#pragma unroll
  for (int i = 0; i < 4 * NS; i++) asm volatile("" : "+r"(q[i]));
}
template <int S0, int NS>
__device__ __forceinline__ void f1_steps(float (&acc)[16], const uint32_t* a, uint32_t blo) {
  if constexpr (NS > 0) {
    wgmma_rs32<F1B<S0>::off, 8, S0 != 0>(acc, a[0], a[1], a[2], a[3], blo);
    f1_steps<S0 + 1, NS - 1>(acc, a + 4, blo);
  }
}
template <int S0, int NS, int BASE, int FIRST>
__device__ __forceinline__ void s2_steps(float (&acc)[12], const uint32_t* a, uint32_t blo) {
  if constexpr (NS > 0) {
    wgmma_rs24<BASE / 16 + (112 - 16 * S0), 64, !(FIRST && S0 == 0)>(acc, a[0], a[1], a[2], a[3], blo);
    s2_steps<S0 + 1, NS - 1, BASE, FIRST>(acc, a + 4, blo);
  }
}
template <int S0, int NS, int BASE, int FIRST>
__device__ __forceinline__ void s3_steps(float (&acc)[8], const uint32_t* a, uint32_t blo) {
  if constexpr (NS > 0) {
    wgmma_rs16<BASE / 16 + (48 - 16 * S0), 64, !(FIRST && S0 == 0)>(acc, a[0], a[1], a[2], a[3], blo);
    s3_steps<S0 + 1, NS - 1, BASE, FIRST>(acc, a + 4, blo);
  }
}

__device__ __forceinline__ void phase_a(
        unsigned char* sm, const uint32_t bar_rec, const uint32_t ep_addr,
        const __nv_bfloat16* __restrict__ x, const uint32_t* __restrict__ are, const uint32_t* __restrict__ aim,
        const uint32_t* __restrict__ bre, const uint32_t* __restrict__ bim, const uint32_t* __restrict__ cre,
        const uint32_t* __restrict__ cim, const unsigned short* __restrict__ logdt, const unsigned short* __restrict__ dskip,
        const uint4* __restrict__ wgate, const uint4* __restrict__ wup, const uint4* __restrict__ wdown) {
  const uint32_t sb = s2u(sm);
  const int tid = threadIdx.x, wg = tid >> 7, warp = tid >> 5, lane = tid & 31, wq = warp & 3, t128 = tid & 127;
  const int blk = blockIdx.x;
  const bool conv = blk < 112;

  uint2 xr[4];
  {
    const uint2* p = (const uint2*)(x + (size_t)(blk * 16 + warp) * DM);
    xr[0] = __ldg(p + lane); xr[1] = __ldg(p + 32 + lane); xr[2] = __ldg(p + 64 + lane);
    xr[3] = lane < 16 ? __ldg(p + 96 + lane) : make_uint2(0, 0);
  }
  const int ch = conv ? blk * 4 + wg : 0;
  const uint32_t cb = sb + wg * A_CH;
  uint32_t prm[6];
  {
    const int i = ch * 128 + t128;
    prm[0] = __ldg(are + i); prm[1] = __ldg(aim + i); prm[2] = __ldg(bre + i); prm[3] = __ldg(bim + i); prm[4] = __ldg(cre + i); prm[5] = __ldg(cim + i);
  }
  const uint32_t ldt = __ldg(logdt + ch);
  uint32_t cnt0 = 0;
  if (tid == 0) cnt0 = __ldcg(&g_cnt1);
#pragma unroll
  for (int i = 0; i < 4; i++) if (i < 3 || t128 < (A_W5 + 1024) / 16 - 384) sts128(cb + (i * 128 + t128) * 16, 0, 0, 0, 0);
  if (t128 < 65) sts128(cb + (t128 < 64 ? A_W3 + t128 * 16 : A_W9), 0, 0, 0, 0);
  if (t128 < 72) sts128(cb + A_UB + (t128 / 9) * 656 + (t128 % 9) * 16, 0, 0, 0, 0);
  {
    float s = 0.f, q = 0.f;
#pragma unroll
    for (int i = 0; i < 4; i++) {
      const float a = bf_lo(xr[i].x), b = bf_hi(xr[i].x), c = bf_lo(xr[i].y), d = bf_hi(xr[i].y);
      s += (a + b) + (c + d);
      q = fmaf(a, a, q); q = fmaf(b, b, q); q = fmaf(c, c, q); q = fmaf(d, d, q);
    }
#pragma unroll
    for (int o = 16; o; o >>= 1) { s += __shfl_xor_sync(~0u, s, o); q += __shfl_xor_sync(~0u, q, o); }
    const float mean = s * (1.f / DM);
    const float var = fmaxf(fmaf(-mean, mean, q * (1.f / DM)), 0.f);
    const float rs = __frcp_rn(rbf(__fsqrt_rn(rbf(rbf(var) + 1e-5f))));
    const uint32_t mm = pack_bf16(mean, mean);
    const uint32_t tu = sb + A_REC + (warp >> 3) * A_CH + (warp & 7) * 912 + lane * 8, tx = tu + 2 * A_CH;
#pragma unroll
    for (int i = 0; i < 4; i++) {
      if (i < 3 || lane < 16) {
        const uint32_t d0 = hsub2_bf(xr[i].x, mm), d1 = hsub2_bf(xr[i].y, mm);
        sts64(tu + i * 256, pack_bf16(bf_lo(d0) * rs, bf_hi(d0) * rs), pack_bf16(bf_lo(d1) * rs, bf_hi(d1) * rs));
        sts64(tx + i * 256, xr[i].x, xr[i].y);
      }
    }
  }
  if (tid == 0) sts32(ep_addr, (cnt0 >> 7) + 1u);
  if (tid == 320) TR(0, 1);
  auto publish_rows = [&]() {
    bar_sync(5, 512);
    uint4* dst = g_ux + ((size_t)(warp * 8 + (lane >> 2)) * 128 + blk) * 4 + ((lane ^ (blk >> 1)) & 3);
#pragma unroll
    for (int i = 0; i < 4; i++) {
      if (i < 3 || warp < 8) {
        uint32_t r[4];
        asm volatile("ldmatrix.sync.aligned.m8n8.x4.trans.shared.b16 {%0,%1,%2,%3}, [%4];" : "=r"(r[0]), "=r"(r[1]), "=r"(r[2]), "=r"(r[3])
                     : "r"(sb + A_REC + (lane >> 3) * A_CH + (lane & 7) * 912 + (warp + 16 * i) * 16) : "memory");
        dst[i * 65536] = make_uint4(r[0], r[1], r[2], r[3]);
      }
    }
    if (warp != 0) asm volatile("bar.arrive 6, 512;" ::: "memory");
  };
  auto release_rows = [&]() {
    if (warp == 0) {
      bar_sync(6, 512);
      if (lane == 0) { asm volatile("red.release.gpu.global.add.u32 [%0], 1;" ::"l"(&g_cnt1) : "memory"); TR(0, 8); }
      __syncwarp();
    }
  };

  if (!conv) {
    publish_rows();
    release_rows();
    const int a = blk - 112, mat = a >> 3, j = a & 7;
    float s[8];
#pragma unroll
    for (int k = 0; k < 8; k++) s[k] = 0.f;
    if (lane < 28) {
      const uint4* src = (mat ? wup : wgate) + j * 28 + lane + (size_t)warp * 224;
#pragma unroll
      for (int hb = 0; hb < 2; hb++) {
        uint4 v[14];
#pragma unroll
        for (int r = 0; r < 14; r++) v[r] = __ldg(src + (size_t)(hb * 14 + r) * 16 * 224);
#pragma unroll
        for (int r = 0; r < 14; r++) {
          s[0] += bf_lo(v[r].x); s[1] += bf_hi(v[r].x); s[2] += bf_lo(v[r].y); s[3] += bf_hi(v[r].y);
          s[4] += bf_lo(v[r].z); s[5] += bf_hi(v[r].z); s[6] += bf_lo(v[r].w); s[7] += bf_hi(v[r].w);
        }
      }
      float4* red = (float4*)(sm + A_STG + warp * 896 + lane * 32);
      red[0] = make_float4(s[0], s[1], s[2], s[3]); red[1] = make_float4(s[4], s[5], s[6], s[7]);
    }
    bar_sync(5, 512);
    if (tid < 224) {
      float t = 0.f;
#pragma unroll
      for (int w = 0; w < 16; w++) t += *(const float*)(sm + A_STG + w * 896 + tid * 4);
      const float hi = rbf(t), mid = rbf(t - hi), lo = rbf(t - hi - mid);
      const int q = tid / 112, n = tid % 112 + 112 * mat;
      __nv_bfloat16* dst = (__nv_bfloat16*)(g_cimg + (j * 2 + q) * 224 + (n >> 3) * 8) + (n & 7);
      dst[0] = __float2bfloat16_rn(hi); dst[8] = __float2bfloat16_rn(mid); dst[16] = __float2bfloat16_rn(lo);
#pragma unroll
      for (int k = 3; k < 8; k++) dst[8 * k] = __float2bfloat16_rn(0.f);
    }
    if (tid == 320) TR(0, 10);
    return;
  }

  const int g = lane >> 2, t = lane & 3;
  const int wr = (wq + wg) & 3;
  uint4 wv[6];
  auto w_src = [&](int i) -> const uint4* {
    if (i < 4) return (blk < 56 ? wgate : wup) + (blk % 56) * 4 + (lane & 3) + (size_t)(i * 128 + warp * 8 + (lane >> 2)) * 224;
    const int it = warp + 16 * (i - 4);
    return wdown + (size_t)(blk * 16 + (it / 14) * 8 + (lane >> 2)) * 56 + (it % 14) * 4 + (lane & 3);
  };
  auto w_on = [&](int i) { return i == 3 ? warp < 8 : i == 5 ? warp < 12 : true; };
  {
    const uint32_t stg = cb + A_STG + wq * 4352;
    const float dt = rbf(expf(__uint_as_float(ldt << 16)));
    float lr[2], li[2];
    cf bq[2], b0[2], b4[2];
    uint32_t bf[48];
#pragma unroll
    for (int m = 0; m < 2; m++) {
      lr[m] = dt * (m ? bf_hi(prm[0]) : bf_lo(prm[0]));
      li[m] = dt * (m ? bf_hi(prm[1]) : bf_lo(prm[1]));
    }
    {
      cf b[2], z[2];
#pragma unroll
      for (int m = 0; m < 2; m++) {
        cf db, c;
        db.x = dt * (m ? bf_hi(prm[2]) : bf_lo(prm[2])); db.y = -dt * (m ? bf_hi(prm[3]) : bf_lo(prm[3]));
        c.x = m ? bf_hi(prm[4]) : bf_lo(prm[4]); c.y = -(m ? bf_hi(prm[5]) : bf_lo(prm[5]));
        b[m] = cmul(c, db);
        z[m] = cexp_l(lr[m], -li[m], 1.f);
        bq[m] = cexp_l(lr[m], -li[m], 256.f);
      }
#pragma unroll
      for (int i = 0; i < 8; i++) {
        sts64(stg + i * 272 + lane * 8, pack_bf16(b[0].x, b[0].y), pack_bf16(b[1].x, b[1].y));
        if (!(i & 1)) {
          cf e0 = cmul(b[0], bq[0]), e1 = cmul(b[1], bq[1]);
          sts64(stg + (8 + i / 2) * 272 + lane * 8, pack_bf16(e0.x, e0.y), pack_bf16(e1.x, e1.y));
          if (i == 0) { b0[0] = e0; b0[1] = e1; }
          if (i == 4) { b4[0] = e0; b4[1] = e1; }
        }
        if (i < 7) { b[0] = cmul(b[0], z[0]); b[1] = cmul(b[1], z[1]); }
        if (i == 1) publish_rows();
      }
#pragma unroll
      for (int i = 0; i < 7; i++) {
        b0[0] = cmul(b0[0], bq[0]); b0[1] = cmul(b0[1], bq[1]);
        sts64(stg + (i < 2 ? 12 + 2 * i : i - 2) * 272 + lane * 8, pack_bf16(b0[0].x, b0[0].y), pack_bf16(b0[1].x, b0[1].y));
        if (i < 2) {
          b4[0] = cmul(b4[0], bq[0]); b4[1] = cmul(b4[1], bq[1]);
          sts64(stg + (13 + 2 * i) * 272 + lane * 8, pack_bf16(b4[0].x, b4[0].y), pack_bf16(b4[1].x, b4[1].y));
        }
        if (i == 1) {
          __syncwarp();
#pragma unroll
          for (int n = 0; n < 2; n++)
#pragma unroll
            for (int k2 = 0; k2 < 4; k2++) ldsm4(bf + n * 16 + k2 * 4, stg + (n * 8 + (lane & 7)) * 272 + k2 * 64 + (lane >> 3) * 16);
          __syncwarp();
        }
      }
    }
    __syncwarp();
#pragma unroll
    for (int k2 = 0; k2 < 4; k2++) ldsm4(bf + 32 + k2 * 4, stg + (lane & 7) * 272 + k2 * 64 + (lane >> 3) * 16);
    release_rows();
    if (!(lane & 1)) {
#pragma unroll
      for (int i = 0; i < 6; i++) if (w_on(i)) asm volatile("prefetch.global.L2 [%0];" ::"l"(w_src(i)));
    }
    if (tid == 320) TR(0, 16);
    float c[6][4];
#pragma unroll
    for (int i = 0; i < 6; i++) { c[i][0] = 0.f; c[i][1] = 0.f; c[i][2] = 0.f; c[i][3] = 0.f; }
    cf p[2], v[2];
    p[0] = cexp_l(lr[0], li[0], 8.f); p[1] = cexp_l(lr[1], li[1], 8.f);
    v[0].x = 1.f; v[0].y = 0.f; v[1] = v[0];
#pragma unroll
    for (int mt = 0; mt < 2; mt++) {
      __syncwarp();
#pragma unroll
      for (int i = 0; i < 16; i++) {
        sts64(stg + i * 272 + lane * 8, pack_bf16(v[0].x, v[0].y), pack_bf16(v[1].x, v[1].y));
        if (mt == 0 && i == 0) { v[0] = p[0]; v[1] = p[1]; }
        else if (mt == 0 || i < 15) { v[0] = cmul(v[0], p[0]); v[1] = cmul(v[1], p[1]); }
      }
      __syncwarp();
      if (mt == 1 && tid == 160) {
        const uint32_t tgt = lds32(ep_addr) * 128u;
        uint32_t cv; int it = 0;
        do { asm volatile("ld.acquire.gpu.global.u32 %0, [%1];" : "=r"(cv) : "l"(&g_cnt1) : "memory"); } while ((int)(cv - tgt) < 0 && ++it < 200000);
        asm volatile("fence.proxy.async;" ::: "memory");
        TR(0, 9);
        mbar_expect(bar_rec, 32768);
        for (int c2 = 0; c2 < 4; c2++) bulk_ld(sb + c2 * A_CH + A_REC, g_ux + (size_t)(blk * 4 + c2) * 512, 8192, bar_rec);
      }
#pragma unroll
      for (int ks = 0; ks < 8; ks++) {
        uint32_t a[4];
        ldsm4(a, stg + (lane & 15) * 272 + ks * 32 + (lane >> 4) * 16);
#pragma unroll
        for (int n = 0; n < 3; n++) mma16816(c[n * 2 + mt], a, bf[n * 16 + ks * 2], bf[n * 16 + ks * 2 + 1]);
      }
    }
    __syncwarp();
#pragma unroll
    for (int i = 0; i < 6; i++)
      sts128(stg + i * 512 + lane * 16, __float_as_uint(c[i][0]), __float_as_uint(c[i][1]), __float_as_uint(c[i][2]), __float_as_uint(c[i][3]));
#pragma unroll
    for (int i = 0; i < 6; i++) if (w_on(i)) wv[i] = __ldg(w_src(i));
    bar_sync(1 + wg, 128);
    if (tid == 320) TR(0, 2);
#pragma unroll
    for (int rep = 0; rep < 2; rep++) {
      const int qd = rep ? 2 + wr : 3 - wr;
      if (rep == 0 || wr >= 2) {
        float s[4] = {0.f, 0.f, 0.f, 0.f};
#pragma unroll
        for (int w = 0; w < 4; w++) {
          uint4 u4 = lds128(cb + A_STG + w * 4352 + qd * 512 + lane * 16);
          s[0] += __uint_as_float(u4.x); s[1] += __uint_as_float(u4.y); s[2] += __uint_as_float(u4.z); s[3] += __uint_as_float(u4.w);
        }
#pragma unroll
        for (int hf = 0; hf < 2; hf++) {
          const int j = (qd & 1) * 16 + g + 8 * hf;
          const uint32_t pk = pack_bf16(s[2 * hf + 1], s[2 * hf]);
          const uint32_t v0 = pk >> 16, v1 = pk & 0xFFFFu, v00 = v0 * 0x10001u;
          if (rep == 1) {
            if (t < 2) {
#pragma unroll
              for (int e = 0; e < 2; e++) {
                const int lam = 128 + 32 * (2 * t + e) + j, mu = lam >> 1;
                const uint32_t val = e ? v1 : v0;
                uint32_t a = cb + ((lam & 1) ? A_R3B : A_R3A) + mu * 4;
                if (lam == 128) { a = cb + A_R2A + 128 * 4; sts32(cb + A_K1024, val << 16); }
                sts16(a, val); sts16(a + 6, val);
              }
            } else if (t == 2 && j == 0) { sts16(cb + A_R3A + 128 * 4, v0); }
          } else if (qd < 2) {
            const uint32_t a = cb + A_R1 + (62 + 8 * j + 2 * t) * 4;
            sts16(a, v0); sts32(a + 4, pk); sts16(a + 10, v1);
          } else if (t < 2) {
            const int L = 256 + 8 * j + 4 * t;
            const uint32_t a = cb + A_R1 + (62 + L) * 4;
            if (L > 256) { sts16(a - 4, v0); sts32(a, v00); } else sts16(a, v0);
            sts32(a + 4, v00); sts32(a + 8, pk); sts16(a + 14, v1);
          } else {
            const int mu = 64 + 32 * (t - 2) + j;
            if (mu == 64) {
              const uint32_t a = cb + A_R1 + (62 + 512) * 4;
              sts16(a - 4, v0); sts32(a, v00); sts32(a + 4, v00); sts32(a + 8, v00); sts16(a + 14, v0);
            } else { sts16(cb + A_R2A + mu * 4, v0); sts16(cb + A_R2A + mu * 4 + 6, v0); }
            sts16(cb + A_R2B + mu * 4, v1); sts16(cb + A_R2B + mu * 4 + 6, v1);
          }
        }
      }
    }
  }
  {
    const int ngg = (blk % 56) * 4 + (lane & 3), j = ngg / 28, q = (ngg % 28) / 14, ng = ngg % 14 + (blk < 56 ? 0 : 14);
    uint4* dst = g_wimg + (size_t)j * 37632 + q * 14 * 896 + ng * 32 + (warp >> 2) * 896 + (warp & 3) * 8 + (lane >> 2);
#pragma unroll
    for (int i = 0; i < 4; i++) if (w_on(i)) dst[i * 4 * 896] = wv[i];
#pragma unroll
    for (int i = 4; i < 6; i++) {
      const int it = warp + 16 * (i - 4), n2 = (it % 14) * 4 + (lane & 3), k = (blk % 7) * 16 + (it / 14) * 8 + (lane >> 2);
      if (w_on(i)) g_wimg[(size_t)(blk / 14) * 37632 + 25088 + ((n2 / 7) * 2 + (blk / 7) % 2) * 784 + (n2 % 7) * 112 + k] = wv[i];
    }
  }
  if (tid == 320) TR(0, 3);

  const int bk = wr * 32 + lane;
  uint32_t xt[8], ud[8];
  {
    mbar_wait(bar_rec, 0);
    if (tid == 320) TR(0, 4);
    uint4 r[4];
#pragma unroll
    for (int i = 0; i < 4; i++) r[i] = lds128(cb + A_REC + bk * 64 + ((i ^ (bk >> 1)) & 3) * 16);
    const uint32_t ua = cb + A_UB + ((2 * bk) & 7) * 656 + ((bk >> 2) + 9) * 16;
    sts128(ua, r[0].x, r[1].x, r[2].x, r[3].x);
    sts128(ua + 656, r[0].y, r[1].y, r[2].y, r[3].y);
    if (bk <= 96) {
      const bool neg = bk == 96;
      const int bp = neg ? -1 : bk;
      uint32_t h[4];
      h[0] = lds32(cb + A_REC + ((bp - 1) & 127) * 64 + ((2 ^ ((bp - 1) >> 1)) & 3) * 16 + 4);
      h[1] = lds32(cb + A_REC + ((bp - 1) & 127) * 64 + ((3 ^ ((bp - 1) >> 1)) & 3) * 16 + 4);
      h[2] = lds32(cb + A_REC + (bp + 1) * 64 + ((0 ^ ((bp + 1) >> 1)) & 3) * 16);
      h[3] = lds32(cb + A_REC + (bp + 1) * 64 + ((1 ^ ((bp + 1) >> 1)) & 3) * 16);
      if (bp <= 0) { h[0] = 0; h[1] = 0; }
      const uint32_t wd[12] = {h[0], h[1], neg ? 0 : r[0].x, neg ? 0 : r[1].x, neg ? 0 : r[2].x, neg ? 0 : r[3].x,
                               neg ? 0 : r[0].y, neg ? 0 : r[1].y, neg ? 0 : r[2].y, neg ? 0 : r[3].y, h[2], h[3]};
      float P[25];
      P[0] = 0.f;
#pragma unroll
      for (int i = 0; i < 12; i++) { P[2 * i + 1] = P[2 * i] + bf_lo(wd[i]); P[2 * i + 2] = P[2 * i + 1] + bf_hi(wd[i]); }
#define WIN(i, hw) (P[(i) + 5 + (hw)] - P[(i) + 4 - (hw)])
#define WPK(i, hw) pack_bf16(WIN(i, hw), WIN((i) + 1, hw))
      const int tp = 2 * bp;
      const uint32_t a3 = cb + A_W3 + (tp + 64) * 16 + 8, a5 = cb + A_W5 + (tp + 64) * 16;
      if (!neg) sts64(a3, WPK(0, 1), WPK(2, 1));
      if (!neg) sts128(a3 + 8, WPK(4, 1), WPK(6, 1), WPK(8, 1), WPK(10, 1));
      sts64(a3 + 24, WPK(12, 1), WPK(14, 1));
      sts128(a5, WPK(0, 2), WPK(2, 2), WPK(4, 2), WPK(6, 2));
      sts128(a5 + 16, WPK(8, 2), WPK(10, 2), WPK(12, 2), WPK(14, 2));
      if (bp < 64) {
        if (!neg) sts128(cb + A_W7 + 1024 + bp * 16, WPK(0, 3), WPK(2, 3), WPK(4, 3), WPK(6, 3));
        if (bp < 63) {
          sts128(cb + A_W7 + (bp + 1) * 16, WPK(8, 3), WPK(10, 3), WPK(12, 3), WPK(14, 3));
          sts128(cb + A_W9 + (bp + 1) * 16, WPK(0, 4), WPK(2, 4), WPK(4, 4), WPK(6, 4));
          sts128(cb + A_W9 + 1024 + (bp + 1) * 16, WPK(8, 4), WPK(10, 4), WPK(12, 4), WPK(14, 4));
        }
        if (!neg) {
#define VPK(i) pack_bf16(P[(i) + 2] - P[i], P[(i) + 3] - P[(i) + 1])
          sts128(cb + A_V + bp * 32, VPK(0), VPK(2), VPK(4), VPK(6));
          sts128(cb + A_V + bp * 32 + 16, VPK(8), VPK(10), VPK(12), VPK(14));
        }
      }
    }
  }
  asm volatile("fence.proxy.async.shared::cta;" ::: "memory");
  bar_sync(1 + wg, 128);
  if (tid == 320) TR(0, 5);

  {
    const uint32_t cbu = __shfl_sync(~0u, cb, 0);
    const uint32_t blo_k = ((cbu & 0x3FFFF) >> 4) | (41u << 16);
    const uint32_t blo_n = ((cbu & 0x3FFFF) >> 4) | (8u << 16);
    const uint32_t tb = cb + (16 * wq + g - 2 * t) * 4;
    float y1[16], y2[12], y3[8];
    const uint32_t dk16 = __ldg(dskip + ch);
    uint32_t qa[32], qb[32];
    const uint32_t t1 = tb + A_R1 + (62 - 48) * 4;
    load_quads<4>(qa, tb + A_R3A + 17 * 4); load_quads<4>(qa + 16, tb + A_R3B + 16 * 4);
    wg_fence();
    s3_steps<0, 4, A_W9, 1>(y3, qa, blo_n); s3_steps<0, 4, A_W7, 0>(y3, qa + 16, blo_n);
    wg_commit();
    load_quads<8>(qb, tb + A_R2A + 16 * 4);
    wg_fence(); s2_steps<0, 8, A_W5, 1>(y2, qb, blo_n); wg_commit();
    wg_wait<1>(); load_quads<8>(qa, tb + A_R2B + 16 * 4);
    wg_fence(); s2_steps<0, 8, A_W3, 0>(y2, qa, blo_n); wg_commit();
    wg_wait<1>(); load_quads<8>(qb, t1);
    wg_fence(); f1_steps<0, 8>(y1, qb, blo_k); wg_commit();
    wg_wait<1>(); load_quads<8>(qa, t1 + 8 * 64);
    wg_fence(); f1_steps<8, 8>(y1, qa, blo_k); wg_commit();
    reg_fence(y2); reg_fence(y3);
    if (tid == 320) TR(0, 18);
    {
      const float k1024 = __uint_as_float(lds32(cb + A_K1024));
#pragma unroll
      for (int i = 0; i < 2; i++)
#pragma unroll
        for (int hf = 0; hf < 2; hf++) {
          const int idx = 16 * (16 * wq + g + 8 * hf) + 8 * i + 2 * t;
          const uint32_t vv = lds32(cb + A_V + idx * 2);
          sts64(cb + A_Y3 + (idx + 4 * (idx >> 6)) * 4, __float_as_uint(fmaf(k1024, bf_lo(vv), y3[4 * i + 2 * hf])),
                __float_as_uint(fmaf(k1024, bf_hi(vv), y3[4 * i + 2 * hf + 1])));
        }
#pragma unroll
      for (int i = 0; i < 3; i++)
#pragma unroll
        for (int hf = 0; hf < 2; hf++) {
          const int idx = 512 * i + 8 * (16 * wq + g + 8 * hf) + 2 * t;
          sts64(cb + A_Y2 + (idx + 4 * (idx >> 6)) * 4, __float_as_uint(y2[4 * i + 2 * hf]), __float_as_uint(y2[4 * i + 2 * hf + 1]));
        }
    }
    wg_wait<1>(); load_quads<8>(qb, t1 + 16 * 64);
    wg_fence(); f1_steps<16, 8>(y1, qb, blo_k); wg_commit();
    wg_wait<1>(); load_quads<8>(qa, t1 + 24 * 64);
    wg_fence(); f1_steps<24, 8>(y1, qa, blo_k); wg_commit();
    wg_wait<1>(); load_quads<5>(qb, t1 + 32 * 64);
    wg_fence(); f1_steps<32, 5>(y1, qb, blo_k); wg_commit();
    bar_sync(1 + wg, 128);
    float ex[12];
#pragma unroll
    for (int i = 1; i < 4; i++)
#pragma unroll
      for (int k = 0; k < 4; k++) {
        const int aa = 8 * i + 2 * t + (k & 1), b = 16 * wq + g + 8 * (k >> 1);
        float e = __uint_as_float(lds32(cb + A_Y2 + ((aa - 8) * 68 + b) * 4));
        if (i >= 2) e += __uint_as_float(lds32(cb + A_Y3 + ((aa - 16) * 68 + b) * 4));
        ex[4 * (i - 1) + k] = e;
      }
    {
      const uint32_t dk = dk16 * 0x10001u;
#pragma unroll
      for (int i = 0; i < 4; i++) {
        const uint4 r = lds128(cb + A_REC + bk * 64 + ((i ^ (bk >> 1)) & 3) * 16);
        ud[i] = hmul2_bf(r.x, dk); ud[4 + i] = hmul2_bf(r.y, dk); xt[i] = r.z; xt[4 + i] = r.w;
      }
    }
    wg_wait<0>();
    reg_fence(y1);
    if (tid == 320) TR(0, 6);
#pragma unroll
    for (int i = 0; i < 12; i++) y1[4 + i] += ex[i];
#pragma unroll
    for (int i = 0; i < 2; i++) {
      const int mi = lane >> 3, aa = 8 * (2 * i + (mi >> 1)) + (lane & 7);
      asm volatile("stmatrix.sync.aligned.m8n8.x4.trans.shared.b16 [%0], {%1,%2,%3,%4};"
                   ::"r"(cb + A_YB + aa * 128 + (((2 * wq + (mi & 1)) ^ (lane & 7)) << 4)),
                     "r"(pack_bf16(y1[8 * i], y1[8 * i + 1])), "r"(pack_bf16(y1[8 * i + 2], y1[8 * i + 3])),
                     "r"(pack_bf16(y1[8 * i + 4], y1[8 * i + 5])), "r"(pack_bf16(y1[8 * i + 6], y1[8 * i + 7])) : "memory");
    }
  }
  bar_sync(1 + wg, 128);
#pragma unroll
  for (int c = 0; c < 2; c++) {
    const int tau = 2 * bk + c, r = ch & 7;
    const uint4 y = lds128(cb + A_YB + (tau >> 3) * 128 + (((tau ^ (tau >> 3)) & 7) << 4));
    g_himg[(size_t)(tau >> 4) * 7168 + (ch >> 3) * 128 + ((tau >> 3) & 1) * 64 + r * 8 + ((tau & 7) ^ r)] =
        make_uint4(hadd2_bf(xt[4 * c], hadd2_bf(y.x, ud[4 * c])), hadd2_bf(xt[4 * c + 1], hadd2_bf(y.y, ud[4 * c + 1])),
                   hadd2_bf(xt[4 * c + 2], hadd2_bf(y.z, ud[4 * c + 2])), hadd2_bf(xt[4 * c + 3], hadd2_bf(y.w, ud[4 * c + 3])));
  }
  if (tid == 320) TR(0, 7);
}

constexpr int B_SA = 0, B_RING = 114688, B_SLOT = 14848, B_NSLOT = 7;
constexpr int B_CS = B_RING + B_NSLOT * B_SLOT;
constexpr int B_RED = B_CS + 7168;
constexpr int B_BAR = B_RED + 256;
constexpr int B_SMEM = B_BAR + 1024, A_SMEM = 4 * A_CH + 64;

__device__ __forceinline__ uint32_t mapa(uint32_t a, uint32_t r) { uint32_t o; asm("mapa.shared::cluster.u32 %0, %1, %2;" : "=r"(o) : "r"(a), "r"(r)); return o; }
template <class T> __device__ __forceinline__ T* pin(T* p) { asm volatile("" : "+l"(p)); return p; }
__device__ __forceinline__ uint32_t pin(uint32_t v) { asm volatile("" : "+r"(v)); return v; }
template <int Q, int ST>
__device__ __forceinline__ void g1_stage(float (&acc)[116], uint32_t alo, uint32_t blo, uint32_t bar_full, uint32_t bar_h) {
  constexpr int s = Q * 14 + ST, sl = s % B_NSLOT;
  if (Q == 0) mbar_wait(bar_h + 8 * ST, 0);
  mbar_wait(bar_full + 8 * sl, (s / B_NSLOT) & 1);
  wg_fence();
  if (Q == 0) {
    wgmma_ss232<(2 * ST) * 256, 0x40000080u, (sl * B_SLOT) / 16, 32, ST != 0>(acc, alo, blo);
    wgmma_ss232<(2 * ST + 1) * 256, 0x40000080u, (sl * B_SLOT + 256) / 16, 32, 1>(acc, alo, blo);
  } else {
    wgmma_ss224<(2 * ST) * 256, 0x40000080u, (sl * B_SLOT) / 16, 32, ST != 0>(*(float(*)[112])acc, alo, blo);
    wgmma_ss224<(2 * ST + 1) * 256, 0x40000080u, (sl * B_SLOT + 256) / 16, 32, 1>(*(float(*)[112])acc, alo, blo);
  }
}

__global__ void __launch_bounds__(512, 1)
k_front(const __nv_bfloat16* __restrict__ x, const uint32_t* __restrict__ are, const uint32_t* __restrict__ aim,
        const uint32_t* __restrict__ bre, const uint32_t* __restrict__ bim, const uint32_t* __restrict__ cre,
        const uint32_t* __restrict__ cim, const unsigned short* __restrict__ logdt, const unsigned short* __restrict__ dskip,
        const uint4* __restrict__ wgate, const uint4* __restrict__ wup, const uint4* __restrict__ wdown) {
  extern __shared__ __align__(1024) unsigned char sm[];
  const uint32_t bar_rec = s2u(sm) + 4 * A_CH;
  if (threadIdx.x == 320) TR(0, 0);
  asm volatile("griddepcontrol.launch_dependents;");
  if (threadIdx.x == 160) { mbar_init(bar_rec, 1); asm volatile("fence.mbarrier_init.release.cluster;" ::: "memory"); }
  phase_a(sm, bar_rec, bar_rec + 8, x, are, aim, bre, bim, cre, cim, logdt, dskip, wgate, wup, wdown);
}

__global__ void __cluster_dims__(2, 1, 1) __launch_bounds__(384, 1) k_ffn(__nv_bfloat16* __restrict__ out) {
  extern __shared__ __align__(1024) unsigned char sm[];
  const uint32_t sb = s2u(sm);
  const int tid = threadIdx.x, warp = __shfl_sync(~0u, tid >> 5, 0), wg = warp >> 2, lane = tid & 31;
  const uint32_t bar_full = sb + B_BAR, bar_empty = bar_full + 64, bar_h = bar_full + 128, bar_cs = bar_full + 240,
                 bar_g2 = bar_full + 248, bar_in = bar_full + 256, bar_hh = bar_full + 304, bar_afree = bar_full + 336, bar_out = bar_full + 352;
  if (tid == 0) {
    TR(1, 0);
    for (int i = 0; i < B_NSLOT; i++) { mbar_init(bar_full + 8 * i, 1); mbar_init(bar_empty + 8 * i, 2); }
    asm volatile("fence.mbarrier_init.release.cluster;" ::: "memory");
  } else if (tid == 32) {
    for (int i = 0; i < 14; i++) mbar_init(bar_h + 8 * i, 1);
    asm volatile("fence.mbarrier_init.release.cluster;" ::: "memory");
  } else if (tid == 64) {
    mbar_init(bar_cs, 1);
    mbar_init(bar_g2, 4);
    for (int i = 0; i < 6; i++) mbar_init(bar_in + 8 * i, 1);
    for (int i = 0; i < 4; i++) { mbar_init(bar_hh + 8 * i, 1); mbar_expect(bar_hh + 8 * i, 14336); }
    mbar_init(bar_afree, 4); mbar_init(bar_afree + 8, 2);
    for (int i = 0; i < 6; i++) mbar_init(bar_out + 8 * i, 128);
    asm volatile("fence.mbarrier_init.release.cluster;" ::: "memory");
  } else if (tid >= 128 && tid < 352) {
    sts128(sb + B_RING + ((tid - 128) >> 5) * B_SLOT + 14336 + (tid & 31) * 16, 0x3F803F80u, 0x3F803F80u, 0x3F803F80u, 0x3F803F80u);
  }
  asm volatile("fence.proxy.async.shared::cta;" ::: "memory");
  __syncthreads();
  asm volatile("barrier.cluster.arrive.relaxed.aligned;" ::: "memory");
  const int rank = blockIdx.x & 1, rt = blockIdx.x >> 3, j = blockIdx.x & 7, p = j >> 1, cg = 4 * rank + p;
  const int wq = warp & 3, t128 = tid & 127, g = lane >> 2, t = lane & 3;
  uint32_t ep, tag;
  auto load_ep = [&]() { asm volatile("ld.relaxed.gpu.global.u32 %0, [%1];" : "=r"(ep) : "l"(&g_cnt1) : "memory"); };
  auto a_slot = [&](int i, int own) { return B_SA + (i + (i >= own)) * 14336; };
  auto in_addr = [&](int q, int cw) { return sb + a_slot(4 + q, cg) + cw * 1792; };
  auto out_addr = [&](int cc, int w) { return sb + a_slot((cc & 2) + w, cg) + (cc & 1) * 7168; };
  auto in_cta = [&](int q) { return rt * 8 + ((p + 3 - q) & 3) * 2 + rank; };
  auto in_src = [&](int q, int cw) { return g_part + (size_t)(in_cta(q) * 3 + q) * 896 + cw * 112; };
  auto add_in = [&](float (&sum)[28], int q, int cw) {
    const uint32_t a = in_addr(q, cw);
    const uint4 v0 = lds128(a + lane * 16), v1 = lds128(a + 512 + lane * 16), v2 = lds128(a + 1024 + lane * 16);
    uint32_t in[14] = {v0.x, v0.y, v0.z, v0.w, v1.x, v1.y, v1.z, v1.w, v2.x, v2.y, v2.z, v2.w, 0, 0};
    asm volatile("ld.shared.v2.u32 {%0, %1}, [%2];" : "=r"(in[12]), "=r"(in[13]) : "r"(a + 1536 + lane * 8) : "memory");
    int it = 0;
    while ((((in[3] ^ tag) | (in[7] ^ tag) | (in[11] ^ tag) | (in[13] ^ tag)) & 0x10000u) && ++it < 400000) {
      const uint4* gs = pin(in_src(q, cw));
#pragma unroll
      for (int i = 0; i < 3; i++) ld128(gs + i * 32 + lane, in + 4 * i);
      asm volatile("{\n.reg .b64 v;\nld.relaxed.gpu.global.b64 v, [%2];\nmov.b64 {%0, %1}, v;\n}"
                   : "=r"(in[12]), "=r"(in[13]) : "l"((const uint2*)(gs + 96) + lane) : "memory");
    }
#pragma unroll
    for (int i = 0; i < 14; i++) { sum[2 * i] += bf_lo(in[i]); sum[2 * i + 1] += bf_hi(in[i]); }
  };

  if (wg == 2) {
    asm volatile("setmaxnreg.dec.sync.aligned.u32 40;");
    asm volatile("barrier.cluster.wait.aligned;" ::: "memory");
    asm volatile("griddepcontrol.wait;" ::: "memory");
    if (warp == 8) {
      if (lane == 0) TR(1, 1);
      const char* wsrc = (const char*)g_wimg + (size_t)j * 602112;
#pragma unroll
      for (int s = 0; s < 28; s++) {
        if (s >= B_NSLOT) mbar_wait(bar_empty + 8 * (s % B_NSLOT), (s / B_NSLOT + 1) & 1);
        bulk_ld_elect<14336>(sb + B_RING + (s % B_NSLOT) * B_SLOT, wsrc + s * 14336, bar_full + 8 * (s % B_NSLOT));
      }
      const char* dsrc[2] = {wsrc + 401408 + rank * 100352, (const char*)g_wimg + (size_t)(j ^ 1) * 602112 + 401408 + rank * 100352};
#pragma unroll
      for (int i = 0; i < 16; i++) {
        const int ci = i < 3 ? 0 : i < 6 ? 1 : i < 8 ? i - 6 : i < 12 ? 2 : 3;
        const int kp = i < 3 ? i : i < 6 ? i - 3 : i < 8 ? 3 : (i & 3);
        mbar_wait(bar_empty + 8 * (i % B_NSLOT), (i / B_NSLOT + 1) & 1);
        bulk_ld_elect<12544>(sb + B_RING + (i % B_NSLOT) * B_SLOT, dsrc[kp >> 1] + ((p + 1 + ci) & 3) * 25088 + (kp & 1) * 12544, bar_full + 8 * (i % B_NSLOT));
      }
    } else if (warp == 9) {
      if (lane < 14) {
        mbar_expect(bar_h + 8 * lane, 8192);
        bulk_ld_mc(sb + B_SA + lane * 8192 + rank * 4096, (const char*)g_himg + (size_t)rt * 114688 + lane * 8192 + rank * 4096, 4096, bar_h + 8 * lane);
      } else if (lane == 14) {
        mbar_expect(bar_cs, 7168);
        bulk_ld(sb + B_CS, g_cimg + j * 448, 7168, bar_cs);
      }
      __syncwarp();
      load_ep(); ep >>= 7;
      const int lq = (lane >> 1) & 3, lcw = (lane & 1) * 4;
      const uint32_t* fl = g_flag + in_cta(lq) * 8 + (lane & 7);
      bool todo = lane < 6, live = false;
      int it = 0;
      while (__any_sync(~0u, todo) && ++it < 400000) {
        if (!live) { __nanosleep(400); live = mbar_test(bar_g2, 0); }
        if (todo) {
          uint32_t w;
          asm volatile("ld.relaxed.gpu.global.u32 %0, [%1];" : "=r"(w) : "l"(fl) : "memory");
          if (live && w == ep) {
            mbar_expect(bar_in + 8 * lane, 7168);
            bulk_ld(in_addr(lq, lcw), in_src(lq, lcw), 7168, bar_in + 8 * lane);
            todo = false;
            if (lane & 1) TR(1, 24 + lq);
          }
        }
      }
    } else {
      const int t64 = tid - 320;
      load_ep();
      const int r = (lane >> 1) & 7, c = (j & 3) * 2 + (lane & 1);
      const uint32_t src = sb + B_SA + (t64 >> 4) * 2048 + (j >> 2) * 1024 + r * 128 + ((c ^ r) << 4);
      float a[16];
#pragma unroll
      for (int k = 0; k < 16; k++) a[k] = 0.f;
#pragma unroll 1
      for (int i = 0; i < 14; i++) {
        mbar_wait(bar_h + 8 * i, 0);
        uint4 v = lds128(src + i * 8192);
        float e[8] = {bf_lo(v.x), bf_hi(v.x), bf_lo(v.y), bf_hi(v.y), bf_lo(v.z), bf_hi(v.z), bf_lo(v.w), bf_hi(v.w)};
#pragma unroll
        for (int k = 0; k < 8; k++) { a[2 * k] += e[k]; a[2 * k + 1] = fmaf(e[k], e[k], a[2 * k + 1]); }
        __nanosleep(160);
      }
      __syncwarp();
      if (lane == 0) { mbar_arrive(bar_g2); asm volatile("mbarrier.arrive.shared::cluster.b64 _, [%0];" ::"r"(mapa(bar_afree, rank ^ 1)) : "memory"); }
#pragma unroll
      for (int rd = 0; rd < 4; rd++) {
        const int n = 8 >> rd;
        const bool up = lane & (2 * n);
#pragma unroll
        for (int k = 0; k < 8; k++) {
          if (k < n) {
            float keep = up ? a[k + n] : a[k], give = up ? a[k] : a[k + n];
            a[k] = keep + __shfl_xor_sync(~0u, give, 2 * n);
          }
        }
      }
      float* red = (float*)(sm + B_RED);
      red[(warp & 1) * 32 + (lane & 1) * 16 + (lane >> 1)] = a[0];
      bar_sync(1, 64);
      if (t64 < 16) {
        float mean = (red[2 * t64] + red[32 + 2 * t64]) * (1.f / DM);
        float var = fmaxf(fmaf(-mean, mean, (red[2 * t64 + 1] + red[33 + 2 * t64]) * (1.f / DM)), 0.f);
        float rs = __frcp_rn(rbf(__fsqrt_rn(rbf(rbf(var) + 1e-5f))));
        asm volatile("st.relaxed.gpu.global.u32 [%0], %1;"
                     ::"l"(g_stat2 + rt * 128 + j * 16 + t64), "r"((__float_as_uint(rs * rs) & ~1u) | ((ep >> 7) & 1u)) : "memory");
      }
      if (t64 == 0) TR(1, 2);
      if (lane == 0) {
        const int w = warp & 1;
        for (int cc = 0; cc < 3; cc++) {
          mbar_wait(bar_out + 8 * (cc * 2 + w), 0);
          asm volatile("cp.async.bulk.global.shared::cta.bulk_group [%0], [%1], 7168;"
                       ::"l"(g_part + (size_t)(blockIdx.x * 3 + cc) * 896 + w * 448), "r"(out_addr(cc, w)) : "memory");
          asm volatile("cp.async.bulk.commit_group;" ::: "memory");
          asm volatile("cp.async.bulk.wait_group 0;" ::: "memory");
          asm volatile("st.relaxed.gpu.global.u32 [%0], %1;" ::"l"(g_flag + blockIdx.x * 8 + cc * 2 + w), "r"(ep >> 7) : "memory");
          if (w) TR(1, 27 + cc);
        }
      }
    }
  } else {
    asm volatile("setmaxnreg.inc.sync.aligned.u32 232;");
    asm volatile("barrier.cluster.wait.aligned;" ::: "memory");
    uint32_t hh[56];
    const bool relt = t128 == 0;
    auto release = [&](int sl) { if (relt) mbar_arrive(bar_empty + 8 * sl); };
    auto send_hh = [&](int q) {
      const uint32_t da = mapa(sb + a_slot(2 * q + wg, cg ^ 4) + t128 * 16, rank ^ 1), db = mapa(bar_hh + 8 * (2 * q + wg), rank ^ 1);
#pragma unroll
      for (int i = 0; i < 7; i++)
        asm volatile("st.async.weak.shared::cluster.mbarrier::complete_tx::bytes.v4.b32 [%0], {%1, %2, %3, %4}, [%5];"
                     ::"r"(da + i * 2048), "r"(hh[28 * q + 4 * i]), "r"(hh[28 * q + 4 * i + 1]),
                       "r"(hh[28 * q + 4 * i + 2]), "r"(hh[28 * q + 4 * i + 3]), "r"(db) : "memory");
    };
    const uint32_t alo = ((sb + B_SA + wg * 1024) & 0x3FFFF) >> 4;
    const uint32_t blo = (((sb + B_RING) & 0x3FFFF) >> 4) | (8u << 16);
    const uint32_t clo = ((sb + B_CS) & 0x3FFFF) >> 4;
    uint32_t nm0, nm1;
    if (wg == 1) bar_sync(3, 256);
#define G1S(Q, ST) do { g1_stage<Q, ST>(acc, alo, blo, bar_full, bar_h); wg_commit(); \
      if (ST > 0) { wg_wait<1>(); release((Q * 14 + ST - 1) % B_NSLOT); } } while (0)
#define G1HH(Q) do { \
      _Pragma("unroll") \
      for (int i = 0; i < 28; i++) hh[28 * Q + i] = pack_bf16(acc[2 * i] * acc[56 + 2 * i], acc[2 * i + 1] * acc[57 + 2 * i]); \
    } while (0)
    {
      float acc[116];
      G1S(0, 0);
      if (tid == 0) TR(1, 3);
      G1S(0, 1);
      if (wg == 0) asm volatile("bar.arrive 3, 256;" ::: "memory");
      G1S(0, 2); G1S(0, 3); G1S(0, 4); G1S(0, 5); G1S(0, 6); G1S(0, 7); G1S(0, 8); G1S(0, 9); G1S(0, 10); G1S(0, 11); G1S(0, 12);
      G1S(0, 13);
      if (tid == 0) TR(1, 4);
      mbar_wait(bar_cs, 0);
      wg_wait<0>(); reg_fence(acc); release(13 % B_NSLOT);
      {
        const uint32_t msk = t == 0 ? 0xFFFFFFFFu : t == 1 ? 0xFFFFu : 0u;
        const float a = acc[112] * (-1.f / DM), b = acc[114] * (-1.f / DM);
        nm0 = pack_bf16(a, a) & msk; nm1 = pack_bf16(b, b) & msk;
      }
      wg_fence();
      wgmma_rs224<0, 8, 1>(*(float(*)[112])acc, nm0, nm1, 0u, 0u, clo);
      wg_commit(); wg_wait<0>(); reg_fence(acc);
      G1HH(0);
      if (tid == 0) TR(1, 5);
      G1S(1, 0); G1S(1, 1); G1S(1, 2); G1S(1, 3); G1S(1, 4); G1S(1, 5); G1S(1, 6);
      if (relt) asm volatile("mbarrier.arrive.shared::cluster.b64 _, [%0];" ::"r"(mapa(bar_afree, rank ^ 1)) : "memory");
      G1S(1, 7); G1S(1, 8); G1S(1, 9);
      if (relt) asm volatile("mbarrier.arrive.shared::cluster.b64 _, [%0];" ::"r"(mapa(bar_afree + 8, rank ^ 1)) : "memory");
      mbar_wait(bar_afree, 0);
      send_hh(0);
      G1S(1, 10); G1S(1, 11); G1S(1, 12);
      load_ep();
      g1_stage<1, 13>(acc, alo, blo, bar_full, bar_h);
      wgmma_rs224<224, 8, 1>(*(float(*)[112])acc, nm0, nm1, 0u, 0u, clo);
      wg_commit(); wg_wait<1>(); release(26 % B_NSLOT);
      wg_wait<0>(); reg_fence(acc); release(27 % B_NSLOT);
      if (t128 == 0) mbar_arrive(bar_g2);
      G1HH(1);
      if (tid == 0) TR(1, 6);
    }
    float accA[28], accB[28], accC[28];
    uint32_t ph0[28], ph1[28];
    ep = pin(ep >> 7); tag = pin((ep & 1u) << 16);
#define ISSUE(acc, I, a, FIRST) do { \
      constexpr int s_ = 28 + (I), sl_ = s_ % B_NSLOT; \
      mbar_wait(bar_full + 8 * sl_, (s_ / B_NSLOT) & 1); \
      wg_fence(); \
      wgmma_rs56<(sl_ * B_SLOT + 0 * 256) / 16, 112, !(FIRST)>(acc, (a)[0], (a)[1], (a)[2], (a)[3], blo); \
      wgmma_rs56<(sl_ * B_SLOT + 1 * 256) / 16, 112, 1>(acc, (a)[4], (a)[5], (a)[6], (a)[7], blo); \
      wgmma_rs56<(sl_ * B_SLOT + 2 * 256) / 16, 112, 1>(acc, (a)[8], (a)[9], (a)[10], (a)[11], blo); \
      wgmma_rs56<(sl_ * B_SLOT + 3 * 256) / 16, 112, 1>(acc, (a)[12], (a)[13], (a)[14], (a)[15], blo); \
      wgmma_rs56<(sl_ * B_SLOT + 4 * 256) / 16, 112, 1>(acc, (a)[16], (a)[17], (a)[18], (a)[19], blo); \
      wgmma_rs56<(sl_ * B_SLOT + 5 * 256) / 16, 112, 1>(acc, (a)[20], (a)[21], (a)[22], (a)[23], blo); \
      wgmma_rs56<(sl_ * B_SLOT + 6 * 256) / 16, 112, 1>(acc, (a)[24], (a)[25], (a)[26], (a)[27], blo); \
      wg_commit(); } while (0)
    auto rel = [&](int i) { release((28 + i) % B_NSLOT); };
    auto tg = [&](uint32_t v) { return (v & 0xFFFEFFFFu) | tag; };
    auto send = [&](float (&acc)[28], int cc) {
      reg_fence(acc);
      const uint32_t a = out_addr(cc, wg) + wq * 1792;
#pragma unroll
      for (int q = 0; q < 3; q++)
        sts128(a + q * 512 + lane * 16, pack_bf16(acc[8 * q], acc[8 * q + 1]), pack_bf16(acc[8 * q + 2], acc[8 * q + 3]),
               pack_bf16(acc[8 * q + 4], acc[8 * q + 5]), tg(pack_bf16(acc[8 * q + 6], acc[8 * q + 7])));
      sts64(a + 1536 + lane * 8, pack_bf16(acc[24], acc[25]), tg(pack_bf16(acc[26], acc[27])));
      asm volatile("fence.proxy.async.shared::cta;" ::: "memory");
      mbar_arrive(bar_out + 8 * (cc * 2 + wg));
    };
    auto load_hh = [&](uint32_t (&d)[28], int q) {
      mbar_wait(bar_hh + 8 * (2 * q + wg), 0);
      const uint32_t a = sb + a_slot(2 * q + wg, cg) + t128 * 16;
#pragma unroll
      for (int i = 0; i < 7; i++) {
        const uint4 v = lds128(a + i * 2048);
        d[4 * i] = v.x; d[4 * i + 1] = v.y; d[4 * i + 2] = v.z; d[4 * i + 3] = v.w;
      }
    };
    ISSUE(accA, 0, hh, true);
    mbar_wait(bar_afree + 8, 0);
    send_hh(1);
    ISSUE(accA, 1, hh + 28, false);
    load_hh(ph0, 0);
    wg_wait<1>(); rel(0);
    ISSUE(accA, 2, ph0, false);      wg_wait<1>(); rel(1);
    ISSUE(accB, 3, hh, true);        wg_wait<1>(); rel(2);
    ISSUE(accB, 4, hh + 28, false);  wg_wait<1>(); rel(3);
    ISSUE(accB, 5, ph0, false);
    if (tid == 0) TR(1, 11);
    load_hh(ph1, 1);
    wg_wait<1>(); rel(4);
    ISSUE(accA, 6, ph1, false);      wg_wait<1>(); rel(5);
    ISSUE(accB, 7, ph1, false);      wg_wait<1>(); rel(6);
    ISSUE(accC, 8, hh, true);        send(accA, 0); wg_wait<1>(); rel(7);
    if (tid == 0) TR(1, 13);
    ISSUE(accC, 9, hh + 28, false);  send(accB, 1); wg_wait<1>(); rel(8);
    ISSUE(accC, 10, ph0, false);
    ISSUE(accC, 11, ph1, false);
    const int row = rt * 128 + wg * 64 + wq * 16 + g;
    uint32_t r20, r21;
    asm volatile("ld.relaxed.gpu.global.u32 %0, [%1];" : "=r"(r20) : "l"(g_stat2 + row) : "memory");
    asm volatile("ld.relaxed.gpu.global.u32 %0, [%1];" : "=r"(r21) : "l"(g_stat2 + row + 8) : "memory");
    ISSUE(accB, 12, hh, true);
    wg_wait<1>();
    send(accC, 2);
    if (tid == 0) TR(1, 16);
    ISSUE(accB, 13, hh + 28, false);
    ISSUE(accB, 14, ph0, false);
    ISSUE(accB, 15, ph1, false);
    if (tid == 0) TR(1, 7);
    uint32_t hres[16];
#pragma unroll
    for (int i = 0; i < 4; i++) {
      int qq = lane >> 3, r = lane & 7, kg = 7 * cg + 2 * i + (qq >> 1), c = 2 * wq + (qq & 1);
      if (kg > 55) kg = 55;
      asm volatile("ldmatrix.sync.aligned.m8n8.x4.trans.shared.b16 {%0,%1,%2,%3}, [%4];"
                   : "=r"(hres[4 * i]), "=r"(hres[4 * i + 1]), "=r"(hres[4 * i + 2]), "=r"(hres[4 * i + 3])
                   : "r"(sb + B_SA + kg * 2048 + wg * 1024 + r * 128 + ((c ^ r) << 4)) : "memory");
    }
    {
      int it = 0;
      while ((((r20 ^ ep) | (r21 ^ ep)) & 1u) && ++it < 400000) {
        asm volatile("ld.relaxed.gpu.global.u32 %0, [%1];" : "=r"(r20) : "l"(g_stat2 + row) : "memory");
        asm volatile("ld.relaxed.gpu.global.u32 %0, [%1];" : "=r"(r21) : "l"(g_stat2 + row + 8) : "memory");
      }
    }
    wg_wait<0>();
    reg_fence(accB);
    if (tid == 0) TR(1, 9);
#pragma unroll 1
    for (int q = 0; q < 3; q++) {
      mbar_wait(bar_in + 8 * (2 * q + wg), 0);
      add_in(accB, q, warp);
      if (tid == 0 && q == 1) TR(1, 12);
    }
    uint32_t* o0 = (uint32_t*)(out + (size_t)row * DM + 56 * cg + 2 * t);
    uint32_t* o1 = o0 + 8 * DM / 2;
#pragma unroll
    for (int i = 0; i < 7; i++) {
      o0[4 * i] = hadd2_bf(hres[2 * i], pack_bf16(accB[4 * i] * __uint_as_float(r20), accB[4 * i + 1] * __uint_as_float(r20)));
      o1[4 * i] = hadd2_bf(hres[2 * i + 1], pack_bf16(accB[4 * i + 2] * __uint_as_float(r21), accB[4 * i + 3] * __uint_as_float(r21)));
    }
    if (tid == 0) TR(1, 10);
    if (tid == 128) TR(1, 15);
  }
}

extern "C" void kernel_launch(void* const* d_in, const int* in_sizes, int n_in, void* d_out, int out_size) {
  const __nv_bfloat16* x = (const __nv_bfloat16*)d_in[0];
  const __nv_bfloat16 *are = (const __nv_bfloat16*)d_in[1], *aim = (const __nv_bfloat16*)d_in[2], *bre = (const __nv_bfloat16*)d_in[3],
                      *bim = (const __nv_bfloat16*)d_in[4], *cre = (const __nv_bfloat16*)d_in[5], *cim = (const __nv_bfloat16*)d_in[6],
                      *logdt = (const __nv_bfloat16*)d_in[7], *dskip = (const __nv_bfloat16*)d_in[8];
  const __nv_bfloat16 *wg = (const __nv_bfloat16*)d_in[10], *wu = (const __nv_bfloat16*)d_in[11], *wd = (const __nv_bfloat16*)d_in[12];

  static bool init = false;
  if (!init) {
    init = true;
    cudaFuncSetAttribute(k_ffn, cudaFuncAttributeMaxDynamicSharedMemorySize, B_SMEM);
    cudaFuncSetAttribute(k_front, cudaFuncAttributeMaxDynamicSharedMemorySize, A_SMEM);
  }
  cudaStream_t st = cudaStreamPerThread;
  k_front<<<128, 512, A_SMEM, st>>>(
      x, (const uint32_t*)are, (const uint32_t*)aim, (const uint32_t*)bre, (const uint32_t*)bim, (const uint32_t*)cre, (const uint32_t*)cim,
      (const unsigned short*)logdt, (const unsigned short*)dskip, (const uint4*)wg, (const uint4*)wu, (const uint4*)wd);
  cudaLaunchConfig_t cfg = {};
  cfg.gridDim = dim3(128); cfg.blockDim = dim3(384); cfg.dynamicSmemBytes = B_SMEM; cfg.stream = st;
  cudaLaunchAttribute at[1];
  at[0].id = cudaLaunchAttributeProgrammaticStreamSerialization; at[0].val.programmaticStreamSerializationAllowed = 1;
  cfg.attrs = at; cfg.numAttrs = 1;
  cudaLaunchKernelEx(&cfg, k_ffn, (__nv_bfloat16*)d_out);
}
```

```cpp
#include <cuda_runtime.h>
#include <cuda_bf16.h>
#include <stdint.h>

constexpr int LSEQ = 2048, DM = 448;

__device__ uint4    g_himg[16 * 114688 / 16];
__device__ uint4    g_cimg[8 * 2 * 224];
__device__ uint32_t g_stat2[LSEQ];
__device__ uint4    g_part[128 * 3 * 896];
__device__ uint4    g_wimg[8 * 602112 / 16];
__device__ uint4    g_ux[DM * 128 * 4];
__device__ unsigned g_cnt1;
__device__ uint32_t g_flag[128 * 8];

#define TR(k, i) do {} while (0)
__device__ __forceinline__ uint32_t s2u(const void* p) { return (uint32_t)__cvta_generic_to_shared(p); }
__device__ __forceinline__ void mbar_init(uint32_t b, int c) { asm volatile("mbarrier.init.shared::cta.b64 [%0], %1;" ::"r"(b), "r"(c)); }
__device__ __forceinline__ void mbar_expect(uint32_t b, int bytes) { asm volatile("mbarrier.arrive.expect_tx.shared::cta.b64 _, [%0], %1;" ::"r"(b), "r"(bytes) : "memory"); }
__device__ __forceinline__ void mbar_arrive(uint32_t b) { asm volatile("mbarrier.arrive.shared::cta.b64 _, [%0];" ::"r"(b) : "memory"); }
__device__ __forceinline__ void mbar_wait(uint32_t b, int ph) {
  asm volatile("{\n.reg .pred p;\n.reg .b32 n;\nmov.b32 n, 0;\nLW:\nmbarrier.try_wait.parity.shared::cta.b64 p, [%0], %1;\n@p bra LD;\n"
               "add.u32 n, n, 1;\nsetp.lt.u32 p, n, 4000000;\n@p bra LW;\ntrap;\nLD:\n}" ::"r"(b), "r"(ph) : "memory");
}
__device__ __forceinline__ bool mbar_test(uint32_t b, int ph) {
  uint32_t ok;
  asm volatile("{\n.reg .pred p;\nmbarrier.test_wait.parity.shared::cta.b64 p, [%1], %2;\nselp.u32 %0, 1, 0, p;\n}" : "=r"(ok) : "r"(b), "r"(ph) : "memory");
  return ok;
}
__device__ __forceinline__ void wg_fence() { asm volatile("wgmma.fence.sync.aligned;" ::: "memory"); }
__device__ __forceinline__ void wg_commit() { asm volatile("wgmma.commit_group.sync.aligned;" ::: "memory"); }
template <int N> __device__ __forceinline__ void wg_wait() { asm volatile("wgmma.wait_group.sync.aligned %0;" ::"n"(N) : "memory"); }
template <int N> __device__ __forceinline__ void reg_fence(float (&a)[N]) {
#pragma unroll
  for (int i = 0; i < N; i++) asm volatile("" : "+f"(a[i])::"memory");
}
__device__ __forceinline__ uint32_t pack_bf16(float lo, float hi) {
  uint32_t r; asm("cvt.rn.bf16x2.f32 %0, %1, %2;" : "=r"(r) : "f"(hi), "f"(lo)); return r;
}
__device__ __forceinline__ float bf_lo(uint32_t v) { return __uint_as_float(v << 16); }
__device__ __forceinline__ float bf_hi(uint32_t v) { return __uint_as_float(v & 0xFFFF0000u); }
__device__ __forceinline__ float rbf(float x) { return __bfloat162float(__float2bfloat16_rn(x)); }
__device__ __forceinline__ uint32_t hmul2_bf(uint32_t a, uint32_t b) { uint32_t r; asm("mul.rn.bf16x2 %0, %1, %2;" : "=r"(r) : "r"(a), "r"(b)); return r; }
__device__ __forceinline__ uint32_t hadd2_bf(uint32_t a, uint32_t b) { uint32_t r; asm("add.rn.bf16x2 %0, %1, %2;" : "=r"(r) : "r"(a), "r"(b)); return r; }
__device__ __forceinline__ void bulk_ld(uint32_t dst, const void* src, int bytes, uint32_t bar) {
  asm volatile("cp.async.bulk.shared::cluster.global.mbarrier::complete_tx::bytes [%0], [%1], %2, [%3];"
               ::"r"(dst), "l"(src), "r"(bytes), "r"(bar) : "memory");
}

template <int BYTES>
__device__ __forceinline__ void bulk_ld_elect(uint32_t dst, const void* src, uint32_t bar) {
  asm volatile("{\n.reg .pred p;\nelect.sync _|p, 0xffffffff;\n"
               "@p mbarrier.arrive.expect_tx.shared::cta.b64 _, [%2], %3;\n"
               "@p cp.async.bulk.shared::cluster.global.mbarrier::complete_tx::bytes [%0], [%1], %3, [%2];\n}"
               ::"r"(dst), "l"(src), "r"(bar), "n"(BYTES) : "memory");
}
template <int BYTES>
__device__ __forceinline__ void bulk_ld_mc_elect(uint32_t dst, const void* src, uint32_t bar) {
  asm volatile("{\n.reg .pred p;\nelect.sync _|p, 0xffffffff;\n"
               "@p mbarrier.arrive.expect_tx.shared::cta.b64 _, [%2], %3;\n"
               "@p cp.async.bulk.shared::cluster.global.mbarrier::complete_tx::bytes.multicast::cluster [%0], [%1], %4, [%2], %5;\n}"
               ::"r"(dst), "l"(src), "r"(bar), "n"(2 * BYTES), "n"(BYTES), "h"((uint16_t)3) : "memory");
}
template <int AOFF, uint32_t AHI, int BOFF, uint32_t BHI, int ACC>
__device__ __forceinline__ void wgmma_ss224(float (&d)[112], uint32_t alo, uint32_t blo) {
  asm volatile("{\n.reg .pred p;\n.reg .b64 ad, bd;\nsetp.ne.b32 p, %118, 0;\n"
    "mov.b64 ad, {%112, %115};\nadd.s64 ad, ad, %114;\nmov.b64 bd, {%113, %117};\nadd.s64 bd, bd, %116;\n"
    "wgmma.mma_async.sync.aligned.m64n224k16.f32.bf16.bf16 {%0,%1,%2,%3,%4,%5,%6,%7,%8,%9,%10,%11,%12,%13,%14,%15,%16,%17,%18,%19,%20,%21,%22,%23,%24,%25,%26,%27,%28,%29,%30,%31,%32,%33,%34,%35,%36,%37,%38,%39,%40,%41,%42,%43,%44,%45,%46,%47,%48,%49,%50,%51,%52,%53,%54,%55,%56,%57,%58,%59,%60,%61,%62,%63,%64,%65,%66,%67,%68,%69,%70,%71,%72,%73,%74,%75,%76,%77,%78,%79,%80,%81,%82,%83,%84,%85,%86,%87,%88,%89,%90,%91,%92,%93,%94,%95,%96,%97,%98,%99,%100,%101,%102,%103,%104,%105,%106,%107,%108,%109,%110,%111}, ad, bd, p, 1, 1, 1, 1;\n}\n"
    : "+f"(d[0]),"+f"(d[1]),"+f"(d[2]),"+f"(d[3]),"+f"(d[4]),"+f"(d[5]),"+f"(d[6]),"+f"(d[7]),"+f"(d[8]),"+f"(d[9]),"+f"(d[10]),"+f"(d[11]),"+f"(d[12]),"+f"(d[13]),"+f"(d[14]),"+f"(d[15]),"+f"(d[16]),"+f"(d[17]),"+f"(d[18]),"+f"(d[19]),"+f"(d[20]),"+f"(d[21]),"+f"(d[22]),"+f"(d[23]),"+f"(d[24]),"+f"(d[25]),"+f"(d[26]),"+f"(d[27]),"+f"(d[28]),"+f"(d[29]),"+f"(d[30]),"+f"(d[31]),"+f"(d[32]),"+f"(d[33]),"+f"(d[34]),"+f"(d[35]),"+f"(d[36]),"+f"(d[37]),"+f"(d[38]),"+f"(d[39]),"+f"(d[40]),"+f"(d[41]),"+f"(d[42]),"+f"(d[43]),"+f"(d[44]),"+f"(d[45]),"+f"(d[46]),"+f"(d[47]),"+f"(d[48]),"+f"(d[49]),"+f"(d[50]),"+f"(d[51]),"+f"(d[52]),"+f"(d[53]),"+f"(d[54]),"+f"(d[55]),"+f"(d[56]),"+f"(d[57]),"+f"(d[58]),"+f"(d[59]),"+f"(d[60]),"+f"(d[61]),"+f"(d[62]),"+f"(d[63]),"+f"(d[64]),"+f"(d[65]),"+f"(d[66]),"+f"(d[67]),"+f"(d[68]),"+f"(d[69]),"+f"(d[70]),"+f"(d[71]),"+f"(d[72]),"+f"(d[73]),"+f"(d[74]),"+f"(d[75]),"+f"(d[76]),"+f"(d[77]),"+f"(d[78]),"+f"(d[79]),"+f"(d[80]),"+f"(d[81]),"+f"(d[82]),"+f"(d[83]),"+f"(d[84]),"+f"(d[85]),"+f"(d[86]),"+f"(d[87]),"+f"(d[88]),"+f"(d[89]),"+f"(d[90]),"+f"(d[91]),"+f"(d[92]),"+f"(d[93]),"+f"(d[94]),"+f"(d[95]),"+f"(d[96]),"+f"(d[97]),"+f"(d[98]),"+f"(d[99]),"+f"(d[100]),"+f"(d[101]),"+f"(d[102]),"+f"(d[103]),"+f"(d[104]),"+f"(d[105]),"+f"(d[106]),"+f"(d[107]),"+f"(d[108]),"+f"(d[109]),"+f"(d[110]),"+f"(d[111])
    : "r"(alo), "r"(blo), "n"(AOFF), "n"(AHI), "n"(BOFF), "n"(BHI), "n"(ACC));
}
template <int AOFF, uint32_t AHI, int BOFF, uint32_t BHI, int ACC>
__device__ __forceinline__ void wgmma_ss232(float (&d)[116], uint32_t alo, uint32_t blo) {
  asm volatile("{\n.reg .pred p;\n.reg .b64 ad, bd;\nsetp.ne.b32 p, %122, 0;\n"
    "mov.b64 ad, {%116, %119};\nadd.s64 ad, ad, %118;\nmov.b64 bd, {%117, %121};\nadd.s64 bd, bd, %120;\n"
    "wgmma.mma_async.sync.aligned.m64n232k16.f32.bf16.bf16 {%0,%1,%2,%3,%4,%5,%6,%7,%8,%9,%10,%11,%12,%13,%14,%15,%16,%17,%18,%19,%20,%21,%22,%23,%24,%25,%26,%27,%28,%29,%30,%31,%32,%33,%34,%35,%36,%37,%38,%39,%40,%41,%42,%43,%44,%45,%46,%47,%48,%49,%50,%51,%52,%53,%54,%55,%56,%57,%58,%59,%60,%61,%62,%63,%64,%65,%66,%67,%68,%69,%70,%71,%72,%73,%74,%75,%76,%77,%78,%79,%80,%81,%82,%83,%84,%85,%86,%87,%88,%89,%90,%91,%92,%93,%94,%95,%96,%97,%98,%99,%100,%101,%102,%103,%104,%105,%106,%107,%108,%109,%110,%111,%112,%113,%114,%115}, ad, bd, p, 1, 1, 1, 1;\n}\n"
    : "+f"(d[0]),"+f"(d[1]),"+f"(d[2]),"+f"(d[3]),"+f"(d[4]),"+f"(d[5]),"+f"(d[6]),"+f"(d[7]),"+f"(d[8]),"+f"(d[9]),"+f"(d[10]),"+f"(d[11]),"+f"(d[12]),"+f"(d[13]),"+f"(d[14]),"+f"(d[15]),"+f"(d[16]),"+f"(d[17]),"+f"(d[18]),"+f"(d[19]),"+f"(d[20]),"+f"(d[21]),"+f"(d[22]),"+f"(d[23]),"+f"(d[24]),"+f"(d[25]),"+f"(d[26]),"+f"(d[27]),"+f"(d[28]),"+f"(d[29]),"+f"(d[30]),"+f"(d[31]),"+f"(d[32]),"+f"(d[33]),"+f"(d[34]),"+f"(d[35]),"+f"(d[36]),"+f"(d[37]),"+f"(d[38]),"+f"(d[39]),"+f"(d[40]),"+f"(d[41]),"+f"(d[42]),"+f"(d[43]),"+f"(d[44]),"+f"(d[45]),"+f"(d[46]),"+f"(d[47]),"+f"(d[48]),"+f"(d[49]),"+f"(d[50]),"+f"(d[51]),"+f"(d[52]),"+f"(d[53]),"+f"(d[54]),"+f"(d[55]),"+f"(d[56]),"+f"(d[57]),"+f"(d[58]),"+f"(d[59]),"+f"(d[60]),"+f"(d[61]),"+f"(d[62]),"+f"(d[63]),"+f"(d[64]),"+f"(d[65]),"+f"(d[66]),"+f"(d[67]),"+f"(d[68]),"+f"(d[69]),"+f"(d[70]),"+f"(d[71]),"+f"(d[72]),"+f"(d[73]),"+f"(d[74]),"+f"(d[75]),"+f"(d[76]),"+f"(d[77]),"+f"(d[78]),"+f"(d[79]),"+f"(d[80]),"+f"(d[81]),"+f"(d[82]),"+f"(d[83]),"+f"(d[84]),"+f"(d[85]),"+f"(d[86]),"+f"(d[87]),"+f"(d[88]),"+f"(d[89]),"+f"(d[90]),"+f"(d[91]),"+f"(d[92]),"+f"(d[93]),"+f"(d[94]),"+f"(d[95]),"+f"(d[96]),"+f"(d[97]),"+f"(d[98]),"+f"(d[99]),"+f"(d[100]),"+f"(d[101]),"+f"(d[102]),"+f"(d[103]),"+f"(d[104]),"+f"(d[105]),"+f"(d[106]),"+f"(d[107]),"+f"(d[108]),"+f"(d[109]),"+f"(d[110]),"+f"(d[111]),"+f"(d[112]),"+f"(d[113]),"+f"(d[114]),"+f"(d[115])
    : "r"(alo), "r"(blo), "n"(AOFF), "n"(AHI), "n"(BOFF), "n"(BHI), "n"(ACC));
}
template <int OFF, uint32_t BHI, int ACC>
__device__ __forceinline__ void wgmma_rs224(float (&d)[112], uint32_t a0, uint32_t a1, uint32_t a2, uint32_t a3, uint32_t blo) {
  asm volatile("{\n.reg .pred p;\n.reg .b64 bd;\nsetp.ne.b32 p, %119, 0;\nmov.b64 bd, {%116, %118};\nadd.s64 bd, bd, %117;\n"
    "wgmma.mma_async.sync.aligned.m64n224k16.f32.bf16.bf16 {%0,%1,%2,%3,%4,%5,%6,%7,%8,%9,%10,%11,%12,%13,%14,%15,%16,%17,%18,%19,%20,%21,%22,%23,%24,%25,%26,%27,%28,%29,%30,%31,%32,%33,%34,%35,%36,%37,%38,%39,%40,%41,%42,%43,%44,%45,%46,%47,%48,%49,%50,%51,%52,%53,%54,%55,%56,%57,%58,%59,%60,%61,%62,%63,%64,%65,%66,%67,%68,%69,%70,%71,%72,%73,%74,%75,%76,%77,%78,%79,%80,%81,%82,%83,%84,%85,%86,%87,%88,%89,%90,%91,%92,%93,%94,%95,%96,%97,%98,%99,%100,%101,%102,%103,%104,%105,%106,%107,%108,%109,%110,%111}, {%112,%113,%114,%115}, bd, p, 1, 1, 1;\n}\n"
    : "+f"(d[0]),"+f"(d[1]),"+f"(d[2]),"+f"(d[3]),"+f"(d[4]),"+f"(d[5]),"+f"(d[6]),"+f"(d[7]),"+f"(d[8]),"+f"(d[9]),"+f"(d[10]),"+f"(d[11]),"+f"(d[12]),"+f"(d[13]),"+f"(d[14]),"+f"(d[15]),"+f"(d[16]),"+f"(d[17]),"+f"(d[18]),"+f"(d[19]),"+f"(d[20]),"+f"(d[21]),"+f"(d[22]),"+f"(d[23]),"+f"(d[24]),"+f"(d[25]),"+f"(d[26]),"+f"(d[27]),"+f"(d[28]),"+f"(d[29]),"+f"(d[30]),"+f"(d[31]),"+f"(d[32]),"+f"(d[33]),"+f"(d[34]),"+f"(d[35]),"+f"(d[36]),"+f"(d[37]),"+f"(d[38]),"+f"(d[39]),"+f"(d[40]),"+f"(d[41]),"+f"(d[42]),"+f"(d[43]),"+f"(d[44]),"+f"(d[45]),"+f"(d[46]),"+f"(d[47]),"+f"(d[48]),"+f"(d[49]),"+f"(d[50]),"+f"(d[51]),"+f"(d[52]),"+f"(d[53]),"+f"(d[54]),"+f"(d[55]),"+f"(d[56]),"+f"(d[57]),"+f"(d[58]),"+f"(d[59]),"+f"(d[60]),"+f"(d[61]),"+f"(d[62]),"+f"(d[63]),"+f"(d[64]),"+f"(d[65]),"+f"(d[66]),"+f"(d[67]),"+f"(d[68]),"+f"(d[69]),"+f"(d[70]),"+f"(d[71]),"+f"(d[72]),"+f"(d[73]),"+f"(d[74]),"+f"(d[75]),"+f"(d[76]),"+f"(d[77]),"+f"(d[78]),"+f"(d[79]),"+f"(d[80]),"+f"(d[81]),"+f"(d[82]),"+f"(d[83]),"+f"(d[84]),"+f"(d[85]),"+f"(d[86]),"+f"(d[87]),"+f"(d[88]),"+f"(d[89]),"+f"(d[90]),"+f"(d[91]),"+f"(d[92]),"+f"(d[93]),"+f"(d[94]),"+f"(d[95]),"+f"(d[96]),"+f"(d[97]),"+f"(d[98]),"+f"(d[99]),"+f"(d[100]),"+f"(d[101]),"+f"(d[102]),"+f"(d[103]),"+f"(d[104]),"+f"(d[105]),"+f"(d[106]),"+f"(d[107]),"+f"(d[108]),"+f"(d[109]),"+f"(d[110]),"+f"(d[111])
    : "r"(a0), "r"(a1), "r"(a2), "r"(a3), "r"(blo), "n"(OFF), "n"(BHI), "n"(ACC));
}
template <int OFF, uint32_t BHI, int ACC>
__device__ __forceinline__ void wgmma_rs56(float (&d)[28], uint32_t a0, uint32_t a1, uint32_t a2, uint32_t a3, uint32_t blo) {
  asm volatile("{\n.reg .pred p;\n.reg .b64 bd;\nsetp.ne.b32 p, %35, 0;\nmov.b64 bd, {%32, %34};\nadd.s64 bd, bd, %33;\n"
    "wgmma.mma_async.sync.aligned.m64n56k16.f32.bf16.bf16 {%0,%1,%2,%3,%4,%5,%6,%7,%8,%9,%10,%11,%12,%13,%14,%15,%16,%17,%18,%19,%20,%21,%22,%23,%24,%25,%26,%27}, {%28,%29,%30,%31}, bd, p, 1, 1, 1;\n}\n"
    : "+f"(d[0]),"+f"(d[1]),"+f"(d[2]),"+f"(d[3]),"+f"(d[4]),"+f"(d[5]),"+f"(d[6]),"+f"(d[7]),"+f"(d[8]),"+f"(d[9]),"+f"(d[10]),"+f"(d[11]),"+f"(d[12]),"+f"(d[13]),"+f"(d[14]),"+f"(d[15]),"+f"(d[16]),"+f"(d[17]),"+f"(d[18]),"+f"(d[19]),"+f"(d[20]),"+f"(d[21]),"+f"(d[22]),"+f"(d[23]),"+f"(d[24]),"+f"(d[25]),"+f"(d[26]),"+f"(d[27])
    : "r"(a0), "r"(a1), "r"(a2), "r"(a3), "r"(blo), "n"(OFF), "n"(BHI), "n"(ACC));
}

__device__ __forceinline__ void st128(uint4* p, uint32_t a, uint32_t b, uint32_t c, uint32_t d) {
  asm volatile("{\n.reg .b128 v;\n.reg .b64 lo, hi;\nmov.b64 lo, {%1, %2};\nmov.b64 hi, {%3, %4};\nmov.b128 v, {lo, hi};\n"
               "st.relaxed.gpu.global.b128 [%0], v;\n}" ::"l"(p), "r"(a), "r"(b), "r"(c), "r"(d) : "memory");
}
__device__ __forceinline__ void ld128(const uint4* p, uint32_t* r) {
  asm volatile("{\n.reg .b128 v;\n.reg .b64 lo, hi;\nld.relaxed.gpu.global.b128 v, [%4];\nmov.b128 {lo, hi}, v;\n"
               "mov.b64 {%0, %1}, lo;\nmov.b64 {%2, %3}, hi;\n}" : "=r"(r[0]), "=r"(r[1]), "=r"(r[2]), "=r"(r[3]) : "l"(p) : "memory");
}

template <int OFF, uint32_t BHI, int ACC>
__device__ __forceinline__ void wgmma_rs32(float (&d)[16], uint32_t a0, uint32_t a1, uint32_t a2, uint32_t a3, uint32_t blo) {
  asm volatile("{\n.reg .pred p;\n.reg .b64 bd;\nsetp.ne.b32 p, %23, 0;\nmov.b64 bd, {%20, %22};\nadd.s64 bd, bd, %21;\n"
    "wgmma.mma_async.sync.aligned.m64n32k16.f32.bf16.bf16 {%0,%1,%2,%3,%4,%5,%6,%7,%8,%9,%10,%11,%12,%13,%14,%15}, {%16,%17,%18,%19}, bd, p, 1, 1, 0;\n}\n"
    : "+f"(d[0]),"+f"(d[1]),"+f"(d[2]),"+f"(d[3]),"+f"(d[4]),"+f"(d[5]),"+f"(d[6]),"+f"(d[7]),"+f"(d[8]),"+f"(d[9]),"+f"(d[10]),"+f"(d[11]),"+f"(d[12]),"+f"(d[13]),"+f"(d[14]),"+f"(d[15])
    : "r"(a0), "r"(a1), "r"(a2), "r"(a3), "r"(blo), "n"(OFF), "n"(BHI), "n"(ACC));
}
template <int OFF, uint32_t BHI, int ACC>
__device__ __forceinline__ void wgmma_rs24(float (&d)[12], uint32_t a0, uint32_t a1, uint32_t a2, uint32_t a3, uint32_t blo) {
  asm volatile("{\n.reg .pred p;\n.reg .b64 bd;\nsetp.ne.b32 p, %19, 0;\nmov.b64 bd, {%16, %18};\nadd.s64 bd, bd, %17;\n"
    "wgmma.mma_async.sync.aligned.m64n24k16.f32.bf16.bf16 {%0,%1,%2,%3,%4,%5,%6,%7,%8,%9,%10,%11}, {%12,%13,%14,%15}, bd, p, 1, 1, 1;\n}\n"
    : "+f"(d[0]),"+f"(d[1]),"+f"(d[2]),"+f"(d[3]),"+f"(d[4]),"+f"(d[5]),"+f"(d[6]),"+f"(d[7]),"+f"(d[8]),"+f"(d[9]),"+f"(d[10]),"+f"(d[11])
    : "r"(a0), "r"(a1), "r"(a2), "r"(a3), "r"(blo), "n"(OFF), "n"(BHI), "n"(ACC));
}
template <int OFF, uint32_t BHI, int ACC>
__device__ __forceinline__ void wgmma_rs16(float (&d)[8], uint32_t a0, uint32_t a1, uint32_t a2, uint32_t a3, uint32_t blo) {
  asm volatile("{\n.reg .pred p;\n.reg .b64 bd;\nsetp.ne.b32 p, %15, 0;\nmov.b64 bd, {%12, %14};\nadd.s64 bd, bd, %13;\n"
    "wgmma.mma_async.sync.aligned.m64n16k16.f32.bf16.bf16 {%0,%1,%2,%3,%4,%5,%6,%7}, {%8,%9,%10,%11}, bd, p, 1, 1, 1;\n}\n"
    : "+f"(d[0]),"+f"(d[1]),"+f"(d[2]),"+f"(d[3]),"+f"(d[4]),"+f"(d[5]),"+f"(d[6]),"+f"(d[7])
    : "r"(a0), "r"(a1), "r"(a2), "r"(a3), "r"(blo), "n"(OFF), "n"(BHI), "n"(ACC));
}

constexpr int A_R1 = 0;
constexpr int A_R2A = A_R1 + 2624, A_R2B = A_R2A + 768, A_R3A = A_R2B + 768, A_R3B = A_R3A + 528;
constexpr int A_K1024 = A_R3B + 528;
constexpr int A_W5 = A_K1024 + 16;
constexpr int A_W3 = A_W5 + 4096;
constexpr int A_W9 = A_W3 + 4112;
constexpr int A_W7 = A_W9 + 2048;
constexpr int A_V  = A_W7 + 2048;
constexpr int A_UB = A_V + 2048;
constexpr int A_STG = A_UB + 5248;
constexpr int A_Y2 = A_STG, A_Y3 = A_Y2 + 6528, A_YB = A_Y3 + 4352;
constexpr int A_REC = A_STG + 4 * 4352;
constexpr int A_CH = A_REC + 8192;
static_assert(A_W5 % 16 == 0 && A_UB % 16 == 0 && A_CH % 16 == 0 && A_YB + 4096 <= A_REC, "layout");

struct cf { float x, y; };
__device__ __forceinline__ cf cmul(cf a, cf b) { cf r; r.x = fmaf(a.x, b.x, -a.y * b.y); r.y = fmaf(a.x, b.y, a.y * b.x); return r; }
__device__ __forceinline__ cf cexp_l(float lr, float li, float l) {
  float mag; asm("ex2.approx.ftz.f32 %0, %1;" : "=f"(mag) : "f"((lr * l) * 1.4426950408889634f));
  const float th = li * l;
  const float k = (fmaf(th, 0.15915494f, 12582912.f)) - 12582912.f;
  float ph = fmaf(th, 0.15915494f, -k);
  ph = fmaf(th, 6.4206383e-9f, ph) * 6.2831853f;
  cf r; r.x = mag * __cosf(ph); r.y = mag * __sinf(ph); return r;
}
__device__ __forceinline__ void sts16(uint32_t a, uint32_t v) { asm volatile("st.shared.u16 [%0], %1;" ::"r"(a), "h"((uint16_t)v) : "memory"); }
__device__ __forceinline__ void sts32(uint32_t a, uint32_t v) { asm volatile("st.shared.u32 [%0], %1;" ::"r"(a), "r"(v) : "memory"); }
__device__ __forceinline__ void sts64(uint32_t a, uint32_t v0, uint32_t v1) { asm volatile("st.shared.v2.u32 [%0], {%1, %2};" ::"r"(a), "r"(v0), "r"(v1) : "memory"); }
__device__ __forceinline__ void sts128(uint32_t a, uint32_t v0, uint32_t v1, uint32_t v2, uint32_t v3) {
  asm volatile("st.shared.v4.u32 [%0], {%1, %2, %3, %4};" ::"r"(a), "r"(v0), "r"(v1), "r"(v2), "r"(v3) : "memory");
}
__device__ __forceinline__ uint32_t lds32(uint32_t a) { uint32_t v; asm volatile("ld.shared.u32 %0, [%1];" : "=r"(v) : "r"(a) : "memory"); return v; }
__device__ __forceinline__ uint4 lds128(uint32_t a) {
  uint4 v; asm volatile("ld.shared.v4.u32 {%0, %1, %2, %3}, [%4];" : "=r"(v.x), "=r"(v.y), "=r"(v.z), "=r"(v.w) : "r"(a) : "memory"); return v;
}
__device__ __forceinline__ void ldsm4(uint32_t* r, uint32_t a) {
  asm volatile("ldmatrix.sync.aligned.m8n8.x4.shared.b16 {%0,%1,%2,%3}, [%4];" : "=r"(r[0]), "=r"(r[1]), "=r"(r[2]), "=r"(r[3]) : "r"(a) : "memory");
}
__device__ __forceinline__ void mma16816(float* d, const uint32_t* a, uint32_t b0, uint32_t b1) {
  asm volatile("mma.sync.aligned.m16n8k16.row.col.f32.bf16.bf16.f32 {%0,%1,%2,%3}, {%4,%5,%6,%7}, {%8,%9}, {%0,%1,%2,%3};"
               : "+f"(d[0]), "+f"(d[1]), "+f"(d[2]), "+f"(d[3]) : "r"(a[0]), "r"(a[1]), "r"(a[2]), "r"(a[3]), "r"(b0), "r"(b1));
}
__device__ __forceinline__ uint32_t hsub2_bf(uint32_t a, uint32_t b) { uint32_t r; asm("sub.rn.bf16x2 %0, %1, %2;" : "=r"(r) : "r"(a), "r"(b)); return r; }
__device__ __forceinline__ void bar_sync(int id, int n) { asm volatile("bar.sync %0, %1;" ::"r"(id), "r"(n) : "memory"); }

template <int S> struct F1B { static constexpr int c = S / 4 + ((S & 3) == 3 ? 0 : 0), cc = (16 * S) / 64, ks = (64 * cc - (16 * S - 48)) / 16, off = (A_UB + 2 * ks * 656 + (9 - cc) * 16) / 16; };

template <int NS>
__device__ __forceinline__ void load_quads(uint32_t* q, uint32_t addr) {
#pragma unroll
  for (int i = 0; i < NS; i++) {
    q[4 * i] = lds32(addr + i * 64); q[4 * i + 1] = lds32(addr + i * 64 + 32);
    q[4 * i + 2] = i ? q[4 * i - 3] : lds32(addr - 32);
    q[4 * i + 3] = q[4 * i];
  }
#pragma unroll
  for (int i = 0; i < 4 * NS; i++) asm volatile("" : "+r"(q[i]));
}
template <int S0, int NS>
__device__ __forceinline__ void f1_steps(float (&acc)[16], const uint32_t* a, uint32_t blo) {
  if constexpr (NS > 0) {
    wgmma_rs32<F1B<S0>::off, 8, S0 != 0>(acc, a[0], a[1], a[2], a[3], blo);
    f1_steps<S0 + 1, NS - 1>(acc, a + 4, blo);
  }
}
template <int S0, int NS, int BASE, int FIRST>
__device__ __forceinline__ void s2_steps(float (&acc)[12], const uint32_t* a, uint32_t blo) {
  if constexpr (NS > 0) {
    wgmma_rs24<BASE / 16 + (112 - 16 * S0), 64, !(FIRST && S0 == 0)>(acc, a[0], a[1], a[2], a[3], blo);
    s2_steps<S0 + 1, NS - 1, BASE, FIRST>(acc, a + 4, blo);
  }
}
template <int S0, int NS, int BASE, int FIRST>
__device__ __forceinline__ void s3_steps(float (&acc)[8], const uint32_t* a, uint32_t blo) {
  if constexpr (NS > 0) {
    wgmma_rs16<BASE / 16 + (48 - 16 * S0), 64, !(FIRST && S0 == 0)>(acc, a[0], a[1], a[2], a[3], blo);
    s3_steps<S0 + 1, NS - 1, BASE, FIRST>(acc, a + 4, blo);
  }
}

__device__ __forceinline__ void phase_a(
        unsigned char* sm, const uint32_t bar_rec, const uint32_t ep_addr,
        const __nv_bfloat16* __restrict__ x, const uint32_t* __restrict__ are, const uint32_t* __restrict__ aim,
        const uint32_t* __restrict__ bre, const uint32_t* __restrict__ bim, const uint32_t* __restrict__ cre,
        const uint32_t* __restrict__ cim, const unsigned short* __restrict__ logdt, const unsigned short* __restrict__ dskip,
        const uint4* __restrict__ wgate, const uint4* __restrict__ wup, const uint4* __restrict__ wdown) {
  const uint32_t sb = s2u(sm);
  const int tid = threadIdx.x, wg = tid >> 7, warp = tid >> 5, lane = tid & 31, wq = warp & 3, t128 = tid & 127;
  const int blk = blockIdx.x;
  const bool conv = blk < 112;

  uint2 xr[4];
  {
    const uint2* p = (const uint2*)(x + (size_t)(blk * 16 + warp) * DM);
    xr[0] = __ldg(p + lane); xr[1] = __ldg(p + 32 + lane); xr[2] = __ldg(p + 64 + lane);
    xr[3] = lane < 16 ? __ldg(p + 96 + lane) : make_uint2(0, 0);
  }
  const int ch = conv ? blk * 4 + wg : 0;
  const uint32_t cb = sb + wg * A_CH;
  uint32_t prm[6];
  {
    const int i = ch * 128 + t128;
    prm[0] = __ldg(are + i); prm[1] = __ldg(aim + i); prm[2] = __ldg(bre + i); prm[3] = __ldg(bim + i); prm[4] = __ldg(cre + i); prm[5] = __ldg(cim + i);
  }
  const uint32_t ldt = __ldg(logdt + ch);
  uint32_t cnt0 = 0;
  if (tid == 0) cnt0 = __ldcg(&g_cnt1);
#pragma unroll
  for (int i = 0; i < 4; i++) if (i < 3 || t128 < (A_W5 + 1024) / 16 - 384) sts128(cb + (i * 128 + t128) * 16, 0, 0, 0, 0);
  if (t128 < 65) sts128(cb + (t128 < 64 ? A_W3 + t128 * 16 : A_W9), 0, 0, 0, 0);
  if (t128 < 72) sts128(cb + A_UB + (t128 / 9) * 656 + (t128 % 9) * 16, 0, 0, 0, 0);
  {
    float s = 0.f, q = 0.f;
#pragma unroll
    for (int i = 0; i < 4; i++) {
      const float a = bf_lo(xr[i].x), b = bf_hi(xr[i].x), c = bf_lo(xr[i].y), d = bf_hi(xr[i].y);
      s += (a + b) + (c + d);
      q = fmaf(a, a, q); q = fmaf(b, b, q); q = fmaf(c, c, q); q = fmaf(d, d, q);
    }
#pragma unroll
    for (int o = 16; o; o >>= 1) { s += __shfl_xor_sync(~0u, s, o); q += __shfl_xor_sync(~0u, q, o); }
    const float mean = s * (1.f / DM);
    const float var = fmaxf(fmaf(-mean, mean, q * (1.f / DM)), 0.f);
    const float rs = __frcp_rn(rbf(__fsqrt_rn(rbf(rbf(var) + 1e-5f))));
    const uint32_t mm = pack_bf16(mean, mean);
    const uint32_t tu = sb + A_REC + (warp >> 3) * A_CH + (warp & 7) * 912 + lane * 8, tx = tu + 2 * A_CH;
#pragma unroll
    for (int i = 0; i < 4; i++) {
      if (i < 3 || lane < 16) {
        const uint32_t d0 = hsub2_bf(xr[i].x, mm), d1 = hsub2_bf(xr[i].y, mm);
        sts64(tu + i * 256, pack_bf16(bf_lo(d0) * rs, bf_hi(d0) * rs), pack_bf16(bf_lo(d1) * rs, bf_hi(d1) * rs));
        sts64(tx + i * 256, xr[i].x, xr[i].y);
      }
    }
  }
  if (tid == 0) sts32(ep_addr, (cnt0 >> 7) + 1u);
  if (tid == 320) TR(0, 1);
  auto publish_rows = [&]() {
    bar_sync(5, 512);
    uint4* dst = g_ux + ((size_t)(warp * 8 + (lane >> 2)) * 128 + blk) * 4 + ((lane ^ (blk >> 1)) & 3);
#pragma unroll
    for (int i = 0; i < 4; i++) {
      if (i < 3 || warp < 8) {
        uint32_t r[4];
        asm volatile("ldmatrix.sync.aligned.m8n8.x4.trans.shared.b16 {%0,%1,%2,%3}, [%4];" : "=r"(r[0]), "=r"(r[1]), "=r"(r[2]), "=r"(r[3])
                     : "r"(sb + A_REC + (lane >> 3) * A_CH + (lane & 7) * 912 + (warp + 16 * i) * 16) : "memory");
        dst[i * 65536] = make_uint4(r[0], r[1], r[2], r[3]);
      }
    }
    if (warp != 0) asm volatile("bar.arrive 6, 512;" ::: "memory");
  };
  auto release_rows = [&]() {
    if (warp == 0) {
      bar_sync(6, 512);
      if (lane == 0) { asm volatile("red.release.gpu.global.add.u32 [%0], 1;" ::"l"(&g_cnt1) : "memory"); TR(0, 8); }
      __syncwarp();
    }
  };

  if (!conv) {
    publish_rows();
    release_rows();
    const int a = blk - 112, mat = a >> 3, j = a & 7;
    float s[8];
#pragma unroll
    for (int k = 0; k < 8; k++) s[k] = 0.f;
    if (lane < 28) {
      const uint4* src = (mat ? wup : wgate) + j * 28 + lane + (size_t)warp * 224;
#pragma unroll
      for (int hb = 0; hb < 2; hb++) {
        uint4 v[14];
#pragma unroll
        for (int r = 0; r < 14; r++) v[r] = __ldg(src + (size_t)(hb * 14 + r) * 16 * 224);
#pragma unroll
        for (int r = 0; r < 14; r++) {
          s[0] += bf_lo(v[r].x); s[1] += bf_hi(v[r].x); s[2] += bf_lo(v[r].y); s[3] += bf_hi(v[r].y);
          s[4] += bf_lo(v[r].z); s[5] += bf_hi(v[r].z); s[6] += bf_lo(v[r].w); s[7] += bf_hi(v[r].w);
        }
      }
      float4* red = (float4*)(sm + A_STG + warp * 896 + lane * 32);
      red[0] = make_float4(s[0], s[1], s[2], s[3]); red[1] = make_float4(s[4], s[5], s[6], s[7]);
    }
    bar_sync(5, 512);
    if (tid < 224) {
      float t = 0.f;
#pragma unroll
      for (int w = 0; w < 16; w++) t += *(const float*)(sm + A_STG + w * 896 + tid * 4);
      const float hi = rbf(t), mid = rbf(t - hi), lo = rbf(t - hi - mid);
      const int q = tid / 112, n = tid % 112 + 112 * mat;
      __nv_bfloat16* dst = (__nv_bfloat16*)(g_cimg + (j * 2 + q) * 224 + (n >> 3) * 8) + (n & 7);
      dst[0] = __float2bfloat16_rn(hi); dst[8] = __float2bfloat16_rn(mid); dst[16] = __float2bfloat16_rn(lo);
#pragma unroll
      for (int k = 3; k < 8; k++) dst[8 * k] = __float2bfloat16_rn(0.f);
    }
    if (tid == 320) TR(0, 10);
    return;
  }

  const int g = lane >> 2, t = lane & 3;
  const int wr = (wq + wg) & 3;
  uint4 wv[6];
  auto w_src = [&](int i) -> const uint4* {
    if (i < 4) return (blk < 56 ? wgate : wup) + (blk % 56) * 4 + (lane & 3) + (size_t)(i * 128 + warp * 8 + (lane >> 2)) * 224;
    const int it = warp + 16 * (i - 4);
    return wdown + (size_t)(blk * 16 + (it / 14) * 8 + (lane >> 2)) * 56 + (it % 14) * 4 + (lane & 3);
  };
  auto w_on = [&](int i) { return i == 3 ? warp < 8 : i == 5 ? warp < 12 : true; };
  {
    const uint32_t stg = cb + A_STG + wq * 4352;
    const float dt = rbf(expf(__uint_as_float(ldt << 16)));
    float lr[2], li[2];
    cf bq[2], b0[2], b4[2];
    uint32_t bf[48];
#pragma unroll
    for (int m = 0; m < 2; m++) {
      lr[m] = dt * (m ? bf_hi(prm[0]) : bf_lo(prm[0]));
      li[m] = dt * (m ? bf_hi(prm[1]) : bf_lo(prm[1]));
    }
    {
      cf b[2], z[2];
#pragma unroll
      for (int m = 0; m < 2; m++) {
        cf db, c;
        db.x = dt * (m ? bf_hi(prm[2]) : bf_lo(prm[2])); db.y = -dt * (m ? bf_hi(prm[3]) : bf_lo(prm[3]));
        c.x = m ? bf_hi(prm[4]) : bf_lo(prm[4]); c.y = -(m ? bf_hi(prm[5]) : bf_lo(prm[5]));
        b[m] = cmul(c, db);
        z[m] = cexp_l(lr[m], -li[m], 1.f);
        bq[m] = cexp_l(lr[m], -li[m], 256.f);
      }
#pragma unroll
      for (int i = 0; i < 8; i++) {
        sts64(stg + i * 272 + lane * 8, pack_bf16(b[0].x, b[0].y), pack_bf16(b[1].x, b[1].y));
        if (!(i & 1)) {
          cf e0 = cmul(b[0], bq[0]), e1 = cmul(b[1], bq[1]);
          sts64(stg + (8 + i / 2) * 272 + lane * 8, pack_bf16(e0.x, e0.y), pack_bf16(e1.x, e1.y));
          if (i == 0) { b0[0] = e0; b0[1] = e1; }
          if (i == 4) { b4[0] = e0; b4[1] = e1; }
        }
        if (i < 7) { b[0] = cmul(b[0], z[0]); b[1] = cmul(b[1], z[1]); }
        if (i == 1) publish_rows();
      }
#pragma unroll
      for (int i = 0; i < 7; i++) {
        b0[0] = cmul(b0[0], bq[0]); b0[1] = cmul(b0[1], bq[1]);
        sts64(stg + (i < 2 ? 12 + 2 * i : i - 2) * 272 + lane * 8, pack_bf16(b0[0].x, b0[0].y), pack_bf16(b0[1].x, b0[1].y));
        if (i < 2) {
          b4[0] = cmul(b4[0], bq[0]); b4[1] = cmul(b4[1], bq[1]);
          sts64(stg + (13 + 2 * i) * 272 + lane * 8, pack_bf16(b4[0].x, b4[0].y), pack_bf16(b4[1].x, b4[1].y));
        }
        if (i == 1) {
          __syncwarp();
#pragma unroll
          for (int n = 0; n < 2; n++)
#pragma unroll
            for (int k2 = 0; k2 < 4; k2++) ldsm4(bf + n * 16 + k2 * 4, stg + (n * 8 + (lane & 7)) * 272 + k2 * 64 + (lane >> 3) * 16);
          __syncwarp();
        }
      }
    }
    __syncwarp();
#pragma unroll
    for (int k2 = 0; k2 < 4; k2++) ldsm4(bf + 32 + k2 * 4, stg + (lane & 7) * 272 + k2 * 64 + (lane >> 3) * 16);
    release_rows();
    if (!(lane & 1)) {
#pragma unroll
      for (int i = 0; i < 6; i++) if (w_on(i)) asm volatile("prefetch.global.L2 [%0];" ::"l"(w_src(i)));
    }
    if (tid == 320) TR(0, 16);
    float c[6][4];
#pragma unroll
    for (int i = 0; i < 6; i++) { c[i][0] = 0.f; c[i][1] = 0.f; c[i][2] = 0.f; c[i][3] = 0.f; }
    cf p[2], v[2];
    p[0] = cexp_l(lr[0], li[0], 8.f); p[1] = cexp_l(lr[1], li[1], 8.f);
    v[0].x = 1.f; v[0].y = 0.f; v[1] = v[0];
#pragma unroll
    for (int mt = 0; mt < 2; mt++) {
      __syncwarp();
#pragma unroll
      for (int i = 0; i < 16; i++) {
        sts64(stg + i * 272 + lane * 8, pack_bf16(v[0].x, v[0].y), pack_bf16(v[1].x, v[1].y));
        if (mt == 0 && i == 0) { v[0] = p[0]; v[1] = p[1]; }
        else if (mt == 0 || i < 15) { v[0] = cmul(v[0], p[0]); v[1] = cmul(v[1], p[1]); }
      }
      __syncwarp();
      if (mt == 1 && tid == 160) {
        const uint32_t tgt = lds32(ep_addr) * 128u;
        uint32_t cv; int it = 0;
        do { asm volatile("ld.acquire.gpu.global.u32 %0, [%1];" : "=r"(cv) : "l"(&g_cnt1) : "memory"); } while ((int)(cv - tgt) < 0 && ++it < 200000);
        asm volatile("fence.proxy.async;" ::: "memory");
        TR(0, 9);
        mbar_expect(bar_rec, 32768);
        for (int c2 = 0; c2 < 4; c2++) bulk_ld(sb + c2 * A_CH + A_REC, g_ux + (size_t)(blk * 4 + c2) * 512, 8192, bar_rec);
      }
#pragma unroll
      for (int ks = 0; ks < 8; ks++) {
        uint32_t a[4];
        ldsm4(a, stg + (lane & 15) * 272 + ks * 32 + (lane >> 4) * 16);
#pragma unroll
        for (int n = 0; n < 3; n++) mma16816(c[n * 2 + mt], a, bf[n * 16 + ks * 2], bf[n * 16 + ks * 2 + 1]);
      }
    }
    __syncwarp();
#pragma unroll
    for (int i = 0; i < 6; i++)
      sts128(stg + i * 512 + lane * 16, __float_as_uint(c[i][0]), __float_as_uint(c[i][1]), __float_as_uint(c[i][2]), __float_as_uint(c[i][3]));
#pragma unroll
    for (int i = 0; i < 6; i++) if (w_on(i)) wv[i] = __ldg(w_src(i));
    bar_sync(1 + wg, 128);
    if (tid == 320) TR(0, 2);
#pragma unroll
    for (int rep = 0; rep < 2; rep++) {
      const int qd = rep ? 2 + wr : 3 - wr;
      if (rep == 0 || wr >= 2) {
        float s[4] = {0.f, 0.f, 0.f, 0.f};
#pragma unroll
        for (int w = 0; w < 4; w++) {
          uint4 u4 = lds128(cb + A_STG + w * 4352 + qd * 512 + lane * 16);
          s[0] += __uint_as_float(u4.x); s[1] += __uint_as_float(u4.y); s[2] += __uint_as_float(u4.z); s[3] += __uint_as_float(u4.w);
        }
#pragma unroll
        for (int hf = 0; hf < 2; hf++) {
          const int j = (qd & 1) * 16 + g + 8 * hf;
          const uint32_t pk = pack_bf16(s[2 * hf + 1], s[2 * hf]);
          const uint32_t v0 = pk >> 16, v1 = pk & 0xFFFFu, v00 = v0 * 0x10001u;
          if (rep == 1) {
            if (t < 2) {
#pragma unroll
              for (int e = 0; e < 2; e++) {
                const int lam = 128 + 32 * (2 * t + e) + j, mu = lam >> 1;
                const uint32_t val = e ? v1 : v0;
                uint32_t a = cb + ((lam & 1) ? A_R3B : A_R3A) + mu * 4;
                if (lam == 128) { a = cb + A_R2A + 128 * 4; sts32(cb + A_K1024, val << 16); }
                sts16(a, val); sts16(a + 6, val);
              }
            } else if (t == 2 && j == 0) { sts16(cb + A_R3A + 128 * 4, v0); }
          } else if (qd < 2) {
            const uint32_t a = cb + A_R1 + (62 + 8 * j + 2 * t) * 4;
            sts16(a, v0); sts32(a + 4, pk); sts16(a + 10, v1);
          } else if (t < 2) {
            const int L = 256 + 8 * j + 4 * t;
            const uint32_t a = cb + A_R1 + (62 + L) * 4;
            if (L > 256) { sts16(a - 4, v0); sts32(a, v00); } else sts16(a, v0);
            sts32(a + 4, v00); sts32(a + 8, pk); sts16(a + 14, v1);
          } else {
            const int mu = 64 + 32 * (t - 2) + j;
            if (mu == 64) {
              const uint32_t a = cb + A_R1 + (62 + 512) * 4;
              sts16(a - 4, v0); sts32(a, v00); sts32(a + 4, v00); sts32(a + 8, v00); sts16(a + 14, v0);
            } else { sts16(cb + A_R2A + mu * 4, v0); sts16(cb + A_R2A + mu * 4 + 6, v0); }
            sts16(cb + A_R2B + mu * 4, v1); sts16(cb + A_R2B + mu * 4 + 6, v1);
          }
        }
      }
    }
  }
  {
    const int ngg = (blk % 56) * 4 + (lane & 3), j = ngg / 28, q = (ngg % 28) / 14, ng = ngg % 14 + (blk < 56 ? 0 : 14);
    uint4* dst = g_wimg + (size_t)j * 37632 + q * 14 * 896 + ng * 32 + (warp >> 2) * 896 + (warp & 3) * 8 + (lane >> 2);
#pragma unroll
    for (int i = 0; i < 4; i++) if (w_on(i)) dst[i * 4 * 896] = wv[i];
#pragma unroll
    for (int i = 4; i < 6; i++) {
      const int it = warp + 16 * (i - 4), n2 = (it % 14) * 4 + (lane & 3), k = (blk % 7) * 16 + (it / 14) * 8 + (lane >> 2);
      if (w_on(i)) g_wimg[(size_t)(blk / 14) * 37632 + 25088 + ((n2 / 7) * 2 + (blk / 7) % 2) * 784 + (n2 % 7) * 112 + k] = wv[i];
    }
  }
  if (tid == 320) TR(0, 3);

  const int bk = wr * 32 + lane;
  uint32_t xt[8], ud[8];
  {
    mbar_wait(bar_rec, 0);
    if (tid == 320) TR(0, 4);
    uint4 r[4];
#pragma unroll
    for (int i = 0; i < 4; i++) r[i] = lds128(cb + A_REC + bk * 64 + ((i ^ (bk >> 1)) & 3) * 16);
    const uint32_t ua = cb + A_UB + ((2 * bk) & 7) * 656 + ((bk >> 2) + 9) * 16;
    sts128(ua, r[0].x, r[1].x, r[2].x, r[3].x);
    sts128(ua + 656, r[0].y, r[1].y, r[2].y, r[3].y);
    if (bk <= 96) {
      const bool neg = bk == 96;
      const int bp = neg ? -1 : bk;
      uint32_t h[4];
      h[0] = lds32(cb + A_REC + ((bp - 1) & 127) * 64 + ((2 ^ ((bp - 1) >> 1)) & 3) * 16 + 4);
      h[1] = lds32(cb + A_REC + ((bp - 1) & 127) * 64 + ((3 ^ ((bp - 1) >> 1)) & 3) * 16 + 4);
      h[2] = lds32(cb + A_REC + (bp + 1) * 64 + ((0 ^ ((bp + 1) >> 1)) & 3) * 16);
      h[3] = lds32(cb + A_REC + (bp + 1) * 64 + ((1 ^ ((bp + 1) >> 1)) & 3) * 16);
      if (bp <= 0) { h[0] = 0; h[1] = 0; }
      const uint32_t wd[12] = {h[0], h[1], neg ? 0 : r[0].x, neg ? 0 : r[1].x, neg ? 0 : r[2].x, neg ? 0 : r[3].x,
                               neg ? 0 : r[0].y, neg ? 0 : r[1].y, neg ? 0 : r[2].y, neg ? 0 : r[3].y, h[2], h[3]};
      float P[25];
      P[0] = 0.f;
#pragma unroll
      for (int i = 0; i < 12; i++) { P[2 * i + 1] = P[2 * i] + bf_lo(wd[i]); P[2 * i + 2] = P[2 * i + 1] + bf_hi(wd[i]); }
#define WIN(i, hw) (P[(i) + 5 + (hw)] - P[(i) + 4 - (hw)])
#define WPK(i, hw) pack_bf16(WIN(i, hw), WIN((i) + 1, hw))
      const int tp = 2 * bp;
      const uint32_t a3 = cb + A_W3 + (tp + 64) * 16 + 8, a5 = cb + A_W5 + (tp + 64) * 16;
      if (!neg) sts64(a3, WPK(0, 1), WPK(2, 1));
      if (!neg) sts128(a3 + 8, WPK(4, 1), WPK(6, 1), WPK(8, 1), WPK(10, 1));
      sts64(a3 + 24, WPK(12, 1), WPK(14, 1));
      sts128(a5, WPK(0, 2), WPK(2, 2), WPK(4, 2), WPK(6, 2));
      sts128(a5 + 16, WPK(8, 2), WPK(10, 2), WPK(12, 2), WPK(14, 2));
      if (bp < 64) {
        if (!neg) sts128(cb + A_W7 + 1024 + bp * 16, WPK(0, 3), WPK(2, 3), WPK(4, 3), WPK(6, 3));
        if (bp < 63) {
          sts128(cb + A_W7 + (bp + 1) * 16, WPK(8, 3), WPK(10, 3), WPK(12, 3), WPK(14, 3));
          sts128(cb + A_W9 + (bp + 1) * 16, WPK(0, 4), WPK(2, 4), WPK(4, 4), WPK(6, 4));
          sts128(cb + A_W9 + 1024 + (bp + 1) * 16, WPK(8, 4), WPK(10, 4), WPK(12, 4), WPK(14, 4));
        }
        if (!neg) {
#define VPK(i) pack_bf16(P[(i) + 2] - P[i], P[(i) + 3] - P[(i) + 1])
          sts128(cb + A_V + bp * 32, VPK(0), VPK(2), VPK(4), VPK(6));
          sts128(cb + A_V + bp * 32 + 16, VPK(8), VPK(10), VPK(12), VPK(14));
        }
      }
    }
  }
  asm volatile("fence.proxy.async.shared::cta;" ::: "memory");
  bar_sync(1 + wg, 128);
  if (tid == 320) TR(0, 5);

  {
    const uint32_t cbu = __shfl_sync(~0u, cb, 0);
    const uint32_t blo_k = ((cbu & 0x3FFFF) >> 4) | (41u << 16);
    const uint32_t blo_n = ((cbu & 0x3FFFF) >> 4) | (8u << 16);
    const uint32_t tb = cb + (16 * wq + g - 2 * t) * 4;
    float y1[16], y2[12], y3[8];
    const uint32_t dk16 = __ldg(dskip + ch);
    uint32_t qa[32], qb[32];
    const uint32_t t1 = tb + A_R1 + (62 - 48) * 4;
    load_quads<4>(qa, tb + A_R3A + 17 * 4); load_quads<4>(qa + 16, tb + A_R3B + 16 * 4);
    wg_fence();
    s3_steps<0, 4, A_W9, 1>(y3, qa, blo_n); s3_steps<0, 4, A_W7, 0>(y3, qa + 16, blo_n);
    wg_commit();
    load_quads<8>(qb, tb + A_R2A + 16 * 4);
    wg_fence(); s2_steps<0, 8, A_W5, 1>(y2, qb, blo_n); wg_commit();
    wg_wait<1>(); load_quads<8>(qa, tb + A_R2B + 16 * 4);
    wg_fence(); s2_steps<0, 8, A_W3, 0>(y2, qa, blo_n); wg_commit();
    wg_wait<1>(); load_quads<8>(qb, t1);
    wg_fence(); f1_steps<0, 8>(y1, qb, blo_k); wg_commit();
    wg_wait<1>(); load_quads<8>(qa, t1 + 8 * 64);
    wg_fence(); f1_steps<8, 8>(y1, qa, blo_k); wg_commit();
    reg_fence(y2); reg_fence(y3);
    if (tid == 320) TR(0, 18);
    {
      const float k1024 = __uint_as_float(lds32(cb + A_K1024));
#pragma unroll
      for (int i = 0; i < 2; i++)
#pragma unroll
        for (int hf = 0; hf < 2; hf++) {
          const int idx = 16 * (16 * wq + g + 8 * hf) + 8 * i + 2 * t;
          const uint32_t vv = lds32(cb + A_V + idx * 2);
          sts64(cb + A_Y3 + (idx + 4 * (idx >> 6)) * 4, __float_as_uint(fmaf(k1024, bf_lo(vv), y3[4 * i + 2 * hf])),
                __float_as_uint(fmaf(k1024, bf_hi(vv), y3[4 * i + 2 * hf + 1])));
        }
#pragma unroll
      for (int i = 0; i < 3; i++)
#pragma unroll
        for (int hf = 0; hf < 2; hf++) {
          const int idx = 512 * i + 8 * (16 * wq + g + 8 * hf) + 2 * t;
          sts64(cb + A_Y2 + (idx + 4 * (idx >> 6)) * 4, __float_as_uint(y2[4 * i + 2 * hf]), __float_as_uint(y2[4 * i + 2 * hf + 1]));
        }
    }
    wg_wait<1>(); load_quads<8>(qb, t1 + 16 * 64);
    wg_fence(); f1_steps<16, 8>(y1, qb, blo_k); wg_commit();
    wg_wait<1>(); load_quads<8>(qa, t1 + 24 * 64);
    wg_fence(); f1_steps<24, 8>(y1, qa, blo_k); wg_commit();
    wg_wait<1>(); load_quads<5>(qb, t1 + 32 * 64);
    wg_fence(); f1_steps<32, 5>(y1, qb, blo_k); wg_commit();
    bar_sync(1 + wg, 128);
    float ex[12];
#pragma unroll
    for (int i = 1; i < 4; i++)
#pragma unroll
      for (int k = 0; k < 4; k++) {
        const int aa = 8 * i + 2 * t + (k & 1), b = 16 * wq + g + 8 * (k >> 1);
        float e = __uint_as_float(lds32(cb + A_Y2 + ((aa - 8) * 68 + b) * 4));
        if (i >= 2) e += __uint_as_float(lds32(cb + A_Y3 + ((aa - 16) * 68 + b) * 4));
        ex[4 * (i - 1) + k] = e;
      }
    {
      const uint32_t dk = dk16 * 0x10001u;
#pragma unroll
      for (int i = 0; i < 4; i++) {
        const uint4 r = lds128(cb + A_REC + bk * 64 + ((i ^ (bk >> 1)) & 3) * 16);
        ud[i] = hmul2_bf(r.x, dk); ud[4 + i] = hmul2_bf(r.y, dk); xt[i] = r.z; xt[4 + i] = r.w;
      }
    }
    wg_wait<0>();
    reg_fence(y1);
    if (tid == 320) TR(0, 6);
#pragma unroll
    for (int i = 0; i < 12; i++) y1[4 + i] += ex[i];
#pragma unroll
    for (int i = 0; i < 2; i++) {
      const int mi = lane >> 3, aa = 8 * (2 * i + (mi >> 1)) + (lane & 7);
      asm volatile("stmatrix.sync.aligned.m8n8.x4.trans.shared.b16 [%0], {%1,%2,%3,%4};"
                   ::"r"(cb + A_YB + aa * 128 + (((2 * wq + (mi & 1)) ^ (lane & 7)) << 4)),
                     "r"(pack_bf16(y1[8 * i], y1[8 * i + 1])), "r"(pack_bf16(y1[8 * i + 2], y1[8 * i + 3])),
                     "r"(pack_bf16(y1[8 * i + 4], y1[8 * i + 5])), "r"(pack_bf16(y1[8 * i + 6], y1[8 * i + 7])) : "memory");
    }
  }
  bar_sync(1 + wg, 128);
#pragma unroll
  for (int c = 0; c < 2; c++) {
    const int tau = 2 * bk + c, r = ch & 7;
    const uint4 y = lds128(cb + A_YB + (tau >> 3) * 128 + (((tau ^ (tau >> 3)) & 7) << 4));
    g_himg[(size_t)(tau >> 4) * 7168 + (ch >> 3) * 128 + ((tau >> 3) & 1) * 64 + r * 8 + ((tau & 7) ^ r)] =
        make_uint4(hadd2_bf(xt[4 * c], hadd2_bf(y.x, ud[4 * c])), hadd2_bf(xt[4 * c + 1], hadd2_bf(y.y, ud[4 * c + 1])),
                   hadd2_bf(xt[4 * c + 2], hadd2_bf(y.z, ud[4 * c + 2])), hadd2_bf(xt[4 * c + 3], hadd2_bf(y.w, ud[4 * c + 3])));
  }
  if (tid == 320) TR(0, 7);
}

constexpr int B_SA = 0, B_RING = 114688, B_SLOT = 14848, B_NSLOT = 7;
constexpr int B_CS = B_RING + B_NSLOT * B_SLOT;
constexpr int B_RED = B_CS + 7168;
constexpr int B_BAR = B_RED + 256;
constexpr int B_SMEM = B_BAR + 1024, A_SMEM = 4 * A_CH + 64;

__device__ __forceinline__ uint32_t mapa(uint32_t a, uint32_t r) { uint32_t o; asm("mapa.shared::cluster.u32 %0, %1, %2;" : "=r"(o) : "r"(a), "r"(r)); return o; }
template <class T> __device__ __forceinline__ T* pin(T* p) { asm volatile("" : "+l"(p)); return p; }
__device__ __forceinline__ uint32_t pin(uint32_t v) { asm volatile("" : "+r"(v)); return v; }
template <int Q, int ST>
__device__ __forceinline__ void g1_stage(float (&acc)[116], uint32_t alo, uint32_t blo, uint32_t bar_full, uint32_t bar_h) {
  constexpr int s = Q * 14 + ST, sl = s % B_NSLOT;
  if (Q == 0) mbar_wait(bar_h + 8 * ST, 0);
  mbar_wait(bar_full + 8 * sl, (s / B_NSLOT) & 1);
  wg_fence();
  if (Q == 0) {
    wgmma_ss232<(2 * ST) * 256, 0x40000080u, (sl * B_SLOT) / 16, 32, ST != 0>(acc, alo, blo);
    wgmma_ss232<(2 * ST + 1) * 256, 0x40000080u, (sl * B_SLOT + 256) / 16, 32, 1>(acc, alo, blo);
  } else {
    wgmma_ss224<(2 * ST) * 256, 0x40000080u, (sl * B_SLOT) / 16, 32, ST != 0>(*(float(*)[112])acc, alo, blo);
    wgmma_ss224<(2 * ST + 1) * 256, 0x40000080u, (sl * B_SLOT + 256) / 16, 32, 1>(*(float(*)[112])acc, alo, blo);
  }
}

__global__ void __launch_bounds__(512, 1)
k_front(const __nv_bfloat16* __restrict__ x, const uint32_t* __restrict__ are, const uint32_t* __restrict__ aim,
        const uint32_t* __restrict__ bre, const uint32_t* __restrict__ bim, const uint32_t* __restrict__ cre,
        const uint32_t* __restrict__ cim, const unsigned short* __restrict__ logdt, const unsigned short* __restrict__ dskip,
        const uint4* __restrict__ wgate, const uint4* __restrict__ wup, const uint4* __restrict__ wdown) {
  extern __shared__ __align__(1024) unsigned char sm[];
  const uint32_t bar_rec = s2u(sm) + 4 * A_CH;
  if (threadIdx.x == 320) TR(0, 0);
  asm volatile("griddepcontrol.launch_dependents;");
  if (threadIdx.x == 160) { mbar_init(bar_rec, 1); asm volatile("fence.mbarrier_init.release.cluster;" ::: "memory"); }
  phase_a(sm, bar_rec, bar_rec + 8, x, are, aim, bre, bim, cre, cim, logdt, dskip, wgate, wup, wdown);
}

__global__ void __cluster_dims__(2, 1, 1) __launch_bounds__(384, 1) k_ffn(__nv_bfloat16* __restrict__ out) {
  extern __shared__ __align__(1024) unsigned char sm[];
  const uint32_t sb = s2u(sm);
  const int tid = threadIdx.x, warp = __shfl_sync(~0u, tid >> 5, 0), wg = warp >> 2, lane = tid & 31;
  const uint32_t bar_full = sb + B_BAR, bar_empty = bar_full + 64, bar_h = bar_full + 128, bar_cs = bar_full + 240,
                 bar_g2 = bar_full + 248, bar_in = bar_full + 256, bar_hh = bar_full + 304, bar_afree = bar_full + 336, bar_out = bar_full + 352;
  if (tid == 0) {
    TR(1, 0);
    for (int i = 0; i < B_NSLOT; i++) { mbar_init(bar_full + 8 * i, 1); mbar_init(bar_empty + 8 * i, 2); }
    asm volatile("fence.mbarrier_init.release.cluster;" ::: "memory");
  } else if (tid == 32) {
    for (int i = 0; i < 14; i++) mbar_init(bar_h + 8 * i, 1);
    asm volatile("fence.mbarrier_init.release.cluster;" ::: "memory");
  } else if (tid == 64) {
    mbar_init(bar_cs, 1);
    mbar_init(bar_g2, 4);
    for (int i = 0; i < 6; i++) mbar_init(bar_in + 8 * i, 1);
    for (int i = 0; i < 4; i++) { mbar_init(bar_hh + 8 * i, 1); mbar_expect(bar_hh + 8 * i, 14336); }
    mbar_init(bar_afree, 4); mbar_init(bar_afree + 8, 2);
    for (int i = 0; i < 6; i++) mbar_init(bar_out + 8 * i, 128);
    asm volatile("fence.mbarrier_init.release.cluster;" ::: "memory");
  } else if (tid >= 128 && tid < 352) {
    sts128(sb + B_RING + ((tid - 128) >> 5) * B_SLOT + 14336 + (tid & 31) * 16, 0x3F803F80u, 0x3F803F80u, 0x3F803F80u, 0x3F803F80u);
  }
  asm volatile("fence.proxy.async.shared::cta;" ::: "memory");
  __syncthreads();
  asm volatile("barrier.cluster.arrive.relaxed.aligned;" ::: "memory");
  const int rank = blockIdx.x & 1, rt = blockIdx.x >> 3, j = blockIdx.x & 7, p = j >> 1, cg = 4 * rank + p;
  const int wq = warp & 3, t128 = tid & 127, g = lane >> 2, t = lane & 3;
  uint32_t ep, tag;
  auto load_ep = [&]() { asm volatile("ld.relaxed.gpu.global.u32 %0, [%1];" : "=r"(ep) : "l"(&g_cnt1) : "memory"); };
  auto a_slot = [&](int i, int own) { return B_SA + (i + (i >= own)) * 14336; };
  auto in_addr = [&](int q, int cw) { return sb + a_slot(4 + q, cg) + cw * 1792; };
  auto out_addr = [&](int cc, int w) { return sb + a_slot((cc & 2) + w, cg) + (cc & 1) * 7168; };
  auto in_cta = [&](int q) { return rt * 8 + ((p + 3 - q) & 3) * 2 + rank; };
  auto in_src = [&](int q, int cw) { return g_part + (size_t)(in_cta(q) * 3 + q) * 896 + cw * 112; };
  auto add_in = [&](float (&sum)[28], int q, int cw) {
    const uint32_t a = in_addr(q, cw);
    const uint4 v0 = lds128(a + lane * 16), v1 = lds128(a + 512 + lane * 16), v2 = lds128(a + 1024 + lane * 16);
    uint32_t in[14] = {v0.x, v0.y, v0.z, v0.w, v1.x, v1.y, v1.z, v1.w, v2.x, v2.y, v2.z, v2.w, 0, 0};
    asm volatile("ld.shared.v2.u32 {%0, %1}, [%2];" : "=r"(in[12]), "=r"(in[13]) : "r"(a + 1536 + lane * 8) : "memory");
    int it = 0;
    while ((((in[3] ^ tag) | (in[7] ^ tag) | (in[11] ^ tag) | (in[13] ^ tag)) & 0x10000u) && ++it < 400000) {
      const uint4* gs = pin(in_src(q, cw));
#pragma unroll
      for (int i = 0; i < 3; i++) ld128(gs + i * 32 + lane, in + 4 * i);
      asm volatile("{\n.reg .b64 v;\nld.relaxed.gpu.global.b64 v, [%2];\nmov.b64 {%0, %1}, v;\n}"
                   : "=r"(in[12]), "=r"(in[13]) : "l"((const uint2*)(gs + 96) + lane) : "memory");
    }
#pragma unroll
    for (int i = 0; i < 14; i++) { sum[2 * i] += bf_lo(in[i]); sum[2 * i + 1] += bf_hi(in[i]); }
  };

  if (wg == 2) {
    asm volatile("setmaxnreg.dec.sync.aligned.u32 40;");
    asm volatile("barrier.cluster.wait.aligned;" ::: "memory");
    asm volatile("griddepcontrol.wait;" ::: "memory");
    if (warp == 8) {
      if (lane == 0) TR(1, 1);
      const char* wsrc = (const char*)g_wimg + (size_t)j * 602112;
      const char* hsrc = (const char*)g_himg + (size_t)rt * 114688 + rank * 4096;
#pragma unroll
      for (int s = 0; s < 28; s++) {
        if (s < B_NSLOT) bulk_ld_mc_elect<4096>(sb + B_SA + s * 8192 + rank * 4096, hsrc + s * 8192, bar_h + 8 * s);
        if (s == B_NSLOT) {
#pragma unroll
          for (int i = 7; i < 14; i++) bulk_ld_mc_elect<4096>(sb + B_SA + i * 8192 + rank * 4096, hsrc + i * 8192, bar_h + 8 * i);
          bulk_ld_elect<7168>(sb + B_CS, g_cimg + j * 448, bar_cs);
        }
        if (s >= B_NSLOT) mbar_wait(bar_empty + 8 * (s % B_NSLOT), (s / B_NSLOT + 1) & 1);
        bulk_ld_elect<14336>(sb + B_RING + (s % B_NSLOT) * B_SLOT, wsrc + s * 14336, bar_full + 8 * (s % B_NSLOT));
      }
      const char* dsrc[2] = {wsrc + 401408 + rank * 100352, (const char*)g_wimg + (size_t)(j ^ 1) * 602112 + 401408 + rank * 100352};
#pragma unroll
      for (int i = 0; i < 16; i++) {
        const int ci = i < 3 ? 0 : i < 6 ? 1 : i < 8 ? i - 6 : i < 12 ? 2 : 3;
        const int kp = i < 3 ? i : i < 6 ? i - 3 : i < 8 ? 3 : (i & 3);
        mbar_wait(bar_empty + 8 * (i % B_NSLOT), (i / B_NSLOT + 1) & 1);
        bulk_ld_elect<12544>(sb + B_RING + (i % B_NSLOT) * B_SLOT, dsrc[kp >> 1] + ((p + 1 + ci) & 3) * 25088 + (kp & 1) * 12544, bar_full + 8 * (i % B_NSLOT));
      }
    } else if (warp == 9) {
      load_ep(); ep >>= 7;
      const int lq = (lane >> 1) & 3, lcw = (lane & 1) * 4;
      const uint32_t* fl = g_flag + in_cta(lq) * 8 + (lane & 7);
      bool todo = lane < 6, live = false;
      int it = 0;
      while (__any_sync(~0u, todo) && ++it < 400000) {
        if (!live) { __nanosleep(400); live = mbar_test(bar_g2, 0); }
        if (todo) {
          uint32_t w;
          asm volatile("ld.relaxed.gpu.global.u32 %0, [%1];" : "=r"(w) : "l"(fl) : "memory");
          if (live && w == ep) {
            mbar_expect(bar_in + 8 * lane, 7168);
            bulk_ld(in_addr(lq, lcw), in_src(lq, lcw), 7168, bar_in + 8 * lane);
            todo = false;
            if (lane & 1) TR(1, 24 + lq);
          }
        }
      }
    } else {
      const int t64 = tid - 320;
      load_ep();
      const int r = (lane >> 1) & 7, c = (j & 3) * 2 + (lane & 1);
      const uint32_t src = sb + B_SA + (t64 >> 4) * 2048 + (j >> 2) * 1024 + r * 128 + ((c ^ r) << 4);
      float a[16];
#pragma unroll
      for (int k = 0; k < 16; k++) a[k] = 0.f;
#pragma unroll 1
      for (int i = 0; i < 14; i++) {
        mbar_wait(bar_h + 8 * i, 0);
        uint4 v = lds128(src + i * 8192);
        float e[8] = {bf_lo(v.x), bf_hi(v.x), bf_lo(v.y), bf_hi(v.y), bf_lo(v.z), bf_hi(v.z), bf_lo(v.w), bf_hi(v.w)};
#pragma unroll
        for (int k = 0; k < 8; k++) { a[2 * k] += e[k]; a[2 * k + 1] = fmaf(e[k], e[k], a[2 * k + 1]); }
        __nanosleep(160);
      }
      __syncwarp();
      if (lane == 0) { mbar_arrive(bar_g2); asm volatile("mbarrier.arrive.shared::cluster.b64 _, [%0];" ::"r"(mapa(bar_afree, rank ^ 1)) : "memory"); }
#pragma unroll
      for (int rd = 0; rd < 4; rd++) {
        const int n = 8 >> rd;
        const bool up = lane & (2 * n);
#pragma unroll
        for (int k = 0; k < 8; k++) {
          if (k < n) {
            float keep = up ? a[k + n] : a[k], give = up ? a[k] : a[k + n];
            a[k] = keep + __shfl_xor_sync(~0u, give, 2 * n);
          }
        }
      }
      float* red = (float*)(sm + B_RED);
      red[(warp & 1) * 32 + (lane & 1) * 16 + (lane >> 1)] = a[0];
      bar_sync(1, 64);
      if (t64 < 16) {
        float mean = (red[2 * t64] + red[32 + 2 * t64]) * (1.f / DM);
        float var = fmaxf(fmaf(-mean, mean, (red[2 * t64 + 1] + red[33 + 2 * t64]) * (1.f / DM)), 0.f);
        float rs = __frcp_rn(rbf(__fsqrt_rn(rbf(rbf(var) + 1e-5f))));
        asm volatile("st.relaxed.gpu.global.u32 [%0], %1;"
                     ::"l"(g_stat2 + rt * 128 + j * 16 + t64), "r"((__float_as_uint(rs * rs) & ~1u) | ((ep >> 7) & 1u)) : "memory");
      }
      if (t64 == 0) TR(1, 2);
      if (lane == 0) {
        const int w = warp & 1;
        for (int cc = 0; cc < 3; cc++) {
          mbar_wait(bar_out + 8 * (cc * 2 + w), 0);
          asm volatile("cp.async.bulk.global.shared::cta.bulk_group [%0], [%1], 7168;"
                       ::"l"(g_part + (size_t)(blockIdx.x * 3 + cc) * 896 + w * 448), "r"(out_addr(cc, w)) : "memory");
          asm volatile("cp.async.bulk.commit_group;" ::: "memory");
          asm volatile("cp.async.bulk.wait_group 0;" ::: "memory");
          asm volatile("st.relaxed.gpu.global.u32 [%0], %1;" ::"l"(g_flag + blockIdx.x * 8 + cc * 2 + w), "r"(ep >> 7) : "memory");
          if (w) TR(1, 27 + cc);
        }
      }
    }
  } else {
    asm volatile("setmaxnreg.inc.sync.aligned.u32 232;");
    asm volatile("barrier.cluster.wait.aligned;" ::: "memory");
    uint32_t hh[56];
    const bool relt = t128 == 0;
    auto release = [&](int sl) { if (relt) mbar_arrive(bar_empty + 8 * sl); };
    auto send_hh = [&](int q) {
      const uint32_t da = mapa(sb + a_slot(2 * q + wg, cg ^ 4) + t128 * 16, rank ^ 1), db = mapa(bar_hh + 8 * (2 * q + wg), rank ^ 1);
#pragma unroll
      for (int i = 0; i < 7; i++)
        asm volatile("st.async.weak.shared::cluster.mbarrier::complete_tx::bytes.v4.b32 [%0], {%1, %2, %3, %4}, [%5];"
                     ::"r"(da + i * 2048), "r"(hh[28 * q + 4 * i]), "r"(hh[28 * q + 4 * i + 1]),
                       "r"(hh[28 * q + 4 * i + 2]), "r"(hh[28 * q + 4 * i + 3]), "r"(db) : "memory");
    };
    uint32_t alo = ((sb + B_SA + wg * 1024) & 0x3FFFF) >> 4;
    uint32_t blo = (((sb + B_RING) & 0x3FFFF) >> 4) | (8u << 16);
    const uint32_t clo = ((sb + B_CS) & 0x3FFFF) >> 4;
    uint32_t nm0, nm1;
    if (wg == 1) bar_sync(3, 256);
#define G1S(Q, ST) do { if (ST % 7 == 0) { alo = pin(alo); blo = pin(blo); }   \
      g1_stage<Q, ST>(acc, alo, blo, bar_full, bar_h); wg_commit(); \
      if (ST > 0) { wg_wait<1>(); release((Q * 14 + ST - 1) % B_NSLOT); } } while (0)
#define G1HH(Q) do { \
      _Pragma("unroll") \
      for (int i = 0; i < 28; i++) hh[28 * Q + i] = pack_bf16(acc[2 * i] * acc[56 + 2 * i], acc[2 * i + 1] * acc[57 + 2 * i]); \
    } while (0)
    {
      float acc[116];
      G1S(0, 0);
      if (tid == 0) TR(1, 3);
      G1S(0, 1);
      if (wg == 0) asm volatile("bar.arrive 3, 256;" ::: "memory");
      G1S(0, 2); G1S(0, 3); G1S(0, 4); G1S(0, 5); G1S(0, 6); G1S(0, 7); G1S(0, 8); G1S(0, 9); G1S(0, 10); G1S(0, 11); G1S(0, 12);
      G1S(0, 13);
      if (tid == 0) TR(1, 4);
      mbar_wait(bar_cs, 0);
      wg_wait<0>(); reg_fence(acc); release(13 % B_NSLOT);
      {
        const uint32_t msk = t == 0 ? 0xFFFFFFFFu : t == 1 ? 0xFFFFu : 0u;
        const float a = acc[112] * (-1.f / DM), b = acc[114] * (-1.f / DM);
        nm0 = pack_bf16(a, a) & msk; nm1 = pack_bf16(b, b) & msk;
      }
      wg_fence();
      wgmma_rs224<0, 8, 1>(*(float(*)[112])acc, nm0, nm1, 0u, 0u, clo);
      wg_commit(); wg_wait<0>(); reg_fence(acc);
      G1HH(0);
      if (tid == 0) TR(1, 5);
      G1S(1, 0); G1S(1, 1); G1S(1, 2); G1S(1, 3); G1S(1, 4); G1S(1, 5); G1S(1, 6);
      if (relt) asm volatile("mbarrier.arrive.shared::cluster.b64 _, [%0];" ::"r"(mapa(bar_afree, rank ^ 1)) : "memory");
      G1S(1, 7); G1S(1, 8); G1S(1, 9);
      if (relt) asm volatile("mbarrier.arrive.shared::cluster.b64 _, [%0];" ::"r"(mapa(bar_afree + 8, rank ^ 1)) : "memory");
      mbar_wait(bar_afree, 0);
      send_hh(0);
      G1S(1, 10); G1S(1, 11); G1S(1, 12);
      load_ep();
      g1_stage<1, 13>(acc, alo, blo, bar_full, bar_h);
      wgmma_rs224<224, 8, 1>(*(float(*)[112])acc, nm0, nm1, 0u, 0u, clo);
      wg_commit(); wg_wait<1>(); release(26 % B_NSLOT);
      wg_wait<0>(); reg_fence(acc); release(27 % B_NSLOT);
      if (t128 == 0) mbar_arrive(bar_g2);
      G1HH(1);
      if (tid == 0) TR(1, 6);
    }
    float accA[28], accB[28];
    uint32_t ph0[28], ph1[28];
    ep = pin(ep >> 7); tag = pin((ep & 1u) << 16);
#define ISSUE(acc, I, a, FIRST) do { \
      constexpr int s_ = 28 + (I), sl_ = s_ % B_NSLOT; \
      if (sl_ == 0) blo = pin(blo); \
      mbar_wait(bar_full + 8 * sl_, (s_ / B_NSLOT) & 1); \
      wg_fence(); \
      wgmma_rs56<(sl_ * B_SLOT + 0 * 256) / 16, 112, !(FIRST)>(acc, (a)[0], (a)[1], (a)[2], (a)[3], blo); \
      wgmma_rs56<(sl_ * B_SLOT + 1 * 256) / 16, 112, 1>(acc, (a)[4], (a)[5], (a)[6], (a)[7], blo); \
      wgmma_rs56<(sl_ * B_SLOT + 2 * 256) / 16, 112, 1>(acc, (a)[8], (a)[9], (a)[10], (a)[11], blo); \
      wgmma_rs56<(sl_ * B_SLOT + 3 * 256) / 16, 112, 1>(acc, (a)[12], (a)[13], (a)[14], (a)[15], blo); \
      wgmma_rs56<(sl_ * B_SLOT + 4 * 256) / 16, 112, 1>(acc, (a)[16], (a)[17], (a)[18], (a)[19], blo); \
      wgmma_rs56<(sl_ * B_SLOT + 5 * 256) / 16, 112, 1>(acc, (a)[20], (a)[21], (a)[22], (a)[23], blo); \
      wgmma_rs56<(sl_ * B_SLOT + 6 * 256) / 16, 112, 1>(acc, (a)[24], (a)[25], (a)[26], (a)[27], blo); \
      wg_commit(); } while (0)
    auto rel = [&](int i) { release((28 + i) % B_NSLOT); };
    auto tg = [&](uint32_t v) { return (v & 0xFFFEFFFFu) | tag; };
    auto send = [&](float (&acc)[28], int cc) {
      reg_fence(acc);
      const uint32_t a = out_addr(cc, wg) + wq * 1792;
#pragma unroll
      for (int q = 0; q < 3; q++)
        sts128(a + q * 512 + lane * 16, pack_bf16(acc[8 * q], acc[8 * q + 1]), pack_bf16(acc[8 * q + 2], acc[8 * q + 3]),
               pack_bf16(acc[8 * q + 4], acc[8 * q + 5]), tg(pack_bf16(acc[8 * q + 6], acc[8 * q + 7])));
      sts64(a + 1536 + lane * 8, pack_bf16(acc[24], acc[25]), tg(pack_bf16(acc[26], acc[27])));
      asm volatile("fence.proxy.async.shared::cta;" ::: "memory");
      mbar_arrive(bar_out + 8 * (cc * 2 + wg));
    };
    auto load_hh = [&](uint32_t (&d)[28], int q) {
      mbar_wait(bar_hh + 8 * (2 * q + wg), 0);
      const uint32_t a = sb + a_slot(2 * q + wg, cg) + t128 * 16;
#pragma unroll
      for (int i = 0; i < 7; i++) {
        const uint4 v = lds128(a + i * 2048);
        d[4 * i] = v.x; d[4 * i + 1] = v.y; d[4 * i + 2] = v.z; d[4 * i + 3] = v.w;
      }
    };
    ISSUE(accA, 0, hh, true);
    mbar_wait(bar_afree + 8, 0);
    send_hh(1);
    ISSUE(accA, 1, hh + 28, false);
    load_hh(ph0, 0);
    wg_wait<1>(); rel(0);
    ISSUE(accA, 2, ph0, false);      wg_wait<1>(); rel(1);
    ISSUE(accB, 3, hh, true);        wg_wait<1>(); rel(2);
    ISSUE(accB, 4, hh + 28, false);  wg_wait<1>(); rel(3);
    ISSUE(accB, 5, ph0, false);
    if (tid == 0) TR(1, 11);
    load_hh(ph1, 1);
    wg_wait<1>(); rel(4);
    ISSUE(accA, 6, ph1, false);      wg_wait<1>(); rel(5);
    ISSUE(accB, 7, ph1, false);      wg_wait<1>(); rel(6); send(accA, 0);
    ISSUE(accA, 8, hh, true);        wg_wait<1>(); rel(7); send(accB, 1);
    if (tid == 0) TR(1, 13);
    ISSUE(accA, 9, hh + 28, false);  wg_wait<1>(); rel(8);
    ISSUE(accA, 10, ph0, false);
    ISSUE(accA, 11, ph1, false);
    const int row = rt * 128 + wg * 64 + wq * 16 + g;
    uint32_t r20, r21;
    asm volatile("ld.relaxed.gpu.global.u32 %0, [%1];" : "=r"(r20) : "l"(g_stat2 + row) : "memory");
    asm volatile("ld.relaxed.gpu.global.u32 %0, [%1];" : "=r"(r21) : "l"(g_stat2 + row + 8) : "memory");
    ISSUE(accB, 12, hh, true);
    wg_wait<1>();
    send(accA, 2);
    if (tid == 0) TR(1, 16);
    ISSUE(accB, 13, hh + 28, false);
    ISSUE(accB, 14, ph0, false);
    ISSUE(accB, 15, ph1, false);
    if (tid == 0) TR(1, 7);
    uint32_t hres[16];
#pragma unroll
    for (int i = 0; i < 4; i++) {
      int qq = lane >> 3, r = lane & 7, kg = 7 * cg + 2 * i + (qq >> 1), c = 2 * wq + (qq & 1);
      if (kg > 55) kg = 55;
      asm volatile("ldmatrix.sync.aligned.m8n8.x4.trans.shared.b16 {%0,%1,%2,%3}, [%4];"
                   : "=r"(hres[4 * i]), "=r"(hres[4 * i + 1]), "=r"(hres[4 * i + 2]), "=r"(hres[4 * i + 3])
                   : "r"(sb + B_SA + kg * 2048 + wg * 1024 + r * 128 + ((c ^ r) << 4)) : "memory");
    }
    {
      int it = 0;
      while ((((r20 ^ ep) | (r21 ^ ep)) & 1u) && ++it < 400000) {
        asm volatile("ld.relaxed.gpu.global.u32 %0, [%1];" : "=r"(r20) : "l"(g_stat2 + row) : "memory");
        asm volatile("ld.relaxed.gpu.global.u32 %0, [%1];" : "=r"(r21) : "l"(g_stat2 + row + 8) : "memory");
      }
    }
    wg_wait<0>();
    reg_fence(accB);
    if (tid == 0) TR(1, 9);
#pragma unroll 1
    for (int q = 0; q < 3; q++) {
      mbar_wait(bar_in + 8 * (2 * q + wg), 0);
      add_in(accB, q, warp);
      if (tid == 0 && q == 1) TR(1, 12);
    }
    uint32_t* o0 = (uint32_t*)(out + (size_t)row * DM + 56 * cg + 2 * t);
    uint32_t* o1 = o0 + 8 * DM / 2;
#pragma unroll
    for (int i = 0; i < 7; i++) {
      o0[4 * i] = hadd2_bf(hres[2 * i], pack_bf16(accB[4 * i] * __uint_as_float(r20), accB[4 * i + 1] * __uint_as_float(r20)));
      o1[4 * i] = hadd2_bf(hres[2 * i + 1], pack_bf16(accB[4 * i + 2] * __uint_as_float(r21), accB[4 * i + 3] * __uint_as_float(r21)));
    }
    if (tid == 0) TR(1, 10);
    if (tid == 128) TR(1, 15);
  }
}

extern "C" void kernel_launch(void* const* d_in, const int* in_sizes, int n_in, void* d_out, int out_size) {
  const __nv_bfloat16* x = (const __nv_bfloat16*)d_in[0];
  const __nv_bfloat16 *are = (const __nv_bfloat16*)d_in[1], *aim = (const __nv_bfloat16*)d_in[2], *bre = (const __nv_bfloat16*)d_in[3],
                      *bim = (const __nv_bfloat16*)d_in[4], *cre = (const __nv_bfloat16*)d_in[5], *cim = (const __nv_bfloat16*)d_in[6],
                      *logdt = (const __nv_bfloat16*)d_in[7], *dskip = (const __nv_bfloat16*)d_in[8];
  const __nv_bfloat16 *wg = (const __nv_bfloat16*)d_in[10], *wu = (const __nv_bfloat16*)d_in[11], *wd = (const __nv_bfloat16*)d_in[12];

  static bool init = false;
  if (!init) {
    init = true;
    cudaFuncSetAttribute(k_ffn, cudaFuncAttributeMaxDynamicSharedMemorySize, B_SMEM);
    cudaFuncSetAttribute(k_front, cudaFuncAttributeMaxDynamicSharedMemorySize, A_SMEM);
  }
  cudaStream_t st = cudaStreamPerThread;
  k_front<<<128, 512, A_SMEM, st>>>(
      x, (const uint32_t*)are, (const uint32_t*)aim, (const uint32_t*)bre, (const uint32_t*)bim, (const uint32_t*)cre, (const uint32_t*)cim,
      (const unsigned short*)logdt, (const unsigned short*)dskip, (const uint4*)wg, (const uint4*)wu, (const uint4*)wd);
  cudaLaunchConfig_t cfg = {};
  cfg.gridDim = dim3(128); cfg.blockDim = dim3(384); cfg.dynamicSmemBytes = B_SMEM; cfg.stream = st;
  cudaLaunchAttribute at[1];
  at[0].id = cudaLaunchAttributeProgrammaticStreamSerialization; at[0].val.programmaticStreamSerializationAllowed = 1;
  cfg.attrs = at; cfg.numAttrs = 1;
  cudaLaunchKernelEx(&cfg, k_ffn, (__nv_bfloat16*)d_out);
}
```

```cpp
#include <cuda_runtime.h>
#include <cuda_bf16.h>
#include <stdint.h>

constexpr int LSEQ = 2048, DM = 448;

__device__ uint4    g_himg[16 * 114688 / 16];
__device__ uint4    g_cimg[8 * 2 * 224];
__device__ uint32_t g_stat2[LSEQ];
__device__ uint4    g_part[128 * 3 * 896];
__device__ uint4    g_wimg[8 * 602112 / 16];
__device__ uint4    g_ux[DM * 128 * 4];
__device__ unsigned g_cnt1;
__device__ uint32_t g_flag[128 * 32];

#define TR(k, i) do {} while (0)
__device__ __forceinline__ uint32_t s2u(const void* p) { return (uint32_t)__cvta_generic_to_shared(p); }
__device__ __forceinline__ void mbar_init(uint32_t b, int c) { asm volatile("mbarrier.init.shared::cta.b64 [%0], %1;" ::"r"(b), "r"(c)); }
__device__ __forceinline__ void mbar_expect(uint32_t b, int bytes) { asm volatile("mbarrier.arrive.expect_tx.shared::cta.b64 _, [%0], %1;" ::"r"(b), "r"(bytes) : "memory"); }
__device__ __forceinline__ void mbar_arrive(uint32_t b) { asm volatile("mbarrier.arrive.shared::cta.b64 _, [%0];" ::"r"(b) : "memory"); }
__device__ __forceinline__ void mbar_wait(uint32_t b, int ph) {
  asm volatile("{\n.reg .pred p;\n.reg .b32 n;\nmov.b32 n, 0;\nLW:\nmbarrier.try_wait.parity.shared::cta.b64 p, [%0], %1;\n@p bra LD;\n"
               "add.u32 n, n, 1;\nsetp.lt.u32 p, n, 4000000;\n@p bra LW;\ntrap;\nLD:\n}" ::"r"(b), "r"(ph) : "memory");
}
__device__ __forceinline__ bool mbar_test(uint32_t b, int ph) {
  uint32_t ok;
  asm volatile("{\n.reg .pred p;\nmbarrier.test_wait.parity.shared::cta.b64 p, [%1], %2;\nselp.u32 %0, 1, 0, p;\n}" : "=r"(ok) : "r"(b), "r"(ph) : "memory");
  return ok;
}
__device__ __forceinline__ void wg_fence() { asm volatile("wgmma.fence.sync.aligned;" ::: "memory"); }
__device__ __forceinline__ void wg_commit() { asm volatile("wgmma.commit_group.sync.aligned;" ::: "memory"); }
template <int N> __device__ __forceinline__ void wg_wait() { asm volatile("wgmma.wait_group.sync.aligned %0;" ::"n"(N) : "memory"); }
template <int N> __device__ __forceinline__ void reg_fence(float (&a)[N]) {
#pragma unroll
  for (int i = 0; i < N; i++) asm volatile("" : "+f"(a[i])::"memory");
}
__device__ __forceinline__ uint32_t pack_bf16(float lo, float hi) {
  uint32_t r; asm("cvt.rn.bf16x2.f32 %0, %1, %2;" : "=r"(r) : "f"(hi), "f"(lo)); return r;
}
__device__ __forceinline__ float bf_lo(uint32_t v) { return __uint_as_float(v << 16); }
__device__ __forceinline__ float bf_hi(uint32_t v) { return __uint_as_float(v & 0xFFFF0000u); }
__device__ __forceinline__ float rbf(float x) { return __bfloat162float(__float2bfloat16_rn(x)); }
__device__ __forceinline__ uint32_t hmul2_bf(uint32_t a, uint32_t b) { uint32_t r; asm("mul.rn.bf16x2 %0, %1, %2;" : "=r"(r) : "r"(a), "r"(b)); return r; }
__device__ __forceinline__ uint32_t hadd2_bf(uint32_t a, uint32_t b) { uint32_t r; asm("add.rn.bf16x2 %0, %1, %2;" : "=r"(r) : "r"(a), "r"(b)); return r; }
__device__ __forceinline__ void bulk_ld(uint32_t dst, const void* src, int bytes, uint32_t bar) {
  asm volatile("cp.async.bulk.shared::cluster.global.mbarrier::complete_tx::bytes [%0], [%1], %2, [%3];"
               ::"r"(dst), "l"(src), "r"(bytes), "r"(bar) : "memory");
}

template <int BYTES>
__device__ __forceinline__ void bulk_ld_elect(uint32_t dst, const void* src, uint32_t bar) {
  asm volatile("{\n.reg .pred p;\nelect.sync _|p, 0xffffffff;\n"
               "@p mbarrier.arrive.expect_tx.shared::cta.b64 _, [%2], %3;\n"
               "@p cp.async.bulk.shared::cluster.global.mbarrier::complete_tx::bytes [%0], [%1], %3, [%2];\n}"
               ::"r"(dst), "l"(src), "r"(bar), "n"(BYTES) : "memory");
}
template <int BYTES>
__device__ __forceinline__ void bulk_ld_mc_elect(uint32_t dst, const void* src, uint32_t bar) {
  asm volatile("{\n.reg .pred p;\nelect.sync _|p, 0xffffffff;\n"
               "@p mbarrier.arrive.expect_tx.shared::cta.b64 _, [%2], %3;\n"
               "@p cp.async.bulk.shared::cluster.global.mbarrier::complete_tx::bytes.multicast::cluster [%0], [%1], %4, [%2], %5;\n}"
               ::"r"(dst), "l"(src), "r"(bar), "n"(2 * BYTES), "n"(BYTES), "h"((uint16_t)3) : "memory");
}
template <int AOFF, uint32_t AHI, int BOFF, uint32_t BHI, int ACC>
__device__ __forceinline__ void wgmma_ss224(float (&d)[112], uint32_t alo, uint32_t blo) {
  asm volatile("{\n.reg .pred p;\n.reg .b64 ad, bd;\nsetp.ne.b32 p, %118, 0;\n"
    "mov.b64 ad, {%112, %115};\nadd.s64 ad, ad, %114;\nmov.b64 bd, {%113, %117};\nadd.s64 bd, bd, %116;\n"
    "wgmma.mma_async.sync.aligned.m64n224k16.f32.bf16.bf16 {%0,%1,%2,%3,%4,%5,%6,%7,%8,%9,%10,%11,%12,%13,%14,%15,%16,%17,%18,%19,%20,%21,%22,%23,%24,%25,%26,%27,%28,%29,%30,%31,%32,%33,%34,%35,%36,%37,%38,%39,%40,%41,%42,%43,%44,%45,%46,%47,%48,%49,%50,%51,%52,%53,%54,%55,%56,%57,%58,%59,%60,%61,%62,%63,%64,%65,%66,%67,%68,%69,%70,%71,%72,%73,%74,%75,%76,%77,%78,%79,%80,%81,%82,%83,%84,%85,%86,%87,%88,%89,%90,%91,%92,%93,%94,%95,%96,%97,%98,%99,%100,%101,%102,%103,%104,%105,%106,%107,%108,%109,%110,%111}, ad, bd, p, 1, 1, 1, 1;\n}\n"
    : "+f"(d[0]),"+f"(d[1]),"+f"(d[2]),"+f"(d[3]),"+f"(d[4]),"+f"(d[5]),"+f"(d[6]),"+f"(d[7]),"+f"(d[8]),"+f"(d[9]),"+f"(d[10]),"+f"(d[11]),"+f"(d[12]),"+f"(d[13]),"+f"(d[14]),"+f"(d[15]),"+f"(d[16]),"+f"(d[17]),"+f"(d[18]),"+f"(d[19]),"+f"(d[20]),"+f"(d[21]),"+f"(d[22]),"+f"(d[23]),"+f"(d[24]),"+f"(d[25]),"+f"(d[26]),"+f"(d[27]),"+f"(d[28]),"+f"(d[29]),"+f"(d[30]),"+f"(d[31]),"+f"(d[32]),"+f"(d[33]),"+f"(d[34]),"+f"(d[35]),"+f"(d[36]),"+f"(d[37]),"+f"(d[38]),"+f"(d[39]),"+f"(d[40]),"+f"(d[41]),"+f"(d[42]),"+f"(d[43]),"+f"(d[44]),"+f"(d[45]),"+f"(d[46]),"+f"(d[47]),"+f"(d[48]),"+f"(d[49]),"+f"(d[50]),"+f"(d[51]),"+f"(d[52]),"+f"(d[53]),"+f"(d[54]),"+f"(d[55]),"+f"(d[56]),"+f"(d[57]),"+f"(d[58]),"+f"(d[59]),"+f"(d[60]),"+f"(d[61]),"+f"(d[62]),"+f"(d[63]),"+f"(d[64]),"+f"(d[65]),"+f"(d[66]),"+f"(d[67]),"+f"(d[68]),"+f"(d[69]),"+f"(d[70]),"+f"(d[71]),"+f"(d[72]),"+f"(d[73]),"+f"(d[74]),"+f"(d[75]),"+f"(d[76]),"+f"(d[77]),"+f"(d[78]),"+f"(d[79]),"+f"(d[80]),"+f"(d[81]),"+f"(d[82]),"+f"(d[83]),"+f"(d[84]),"+f"(d[85]),"+f"(d[86]),"+f"(d[87]),"+f"(d[88]),"+f"(d[89]),"+f"(d[90]),"+f"(d[91]),"+f"(d[92]),"+f"(d[93]),"+f"(d[94]),"+f"(d[95]),"+f"(d[96]),"+f"(d[97]),"+f"(d[98]),"+f"(d[99]),"+f"(d[100]),"+f"(d[101]),"+f"(d[102]),"+f"(d[103]),"+f"(d[104]),"+f"(d[105]),"+f"(d[106]),"+f"(d[107]),"+f"(d[108]),"+f"(d[109]),"+f"(d[110]),"+f"(d[111])
    : "r"(alo), "r"(blo), "n"(AOFF), "n"(AHI), "n"(BOFF), "n"(BHI), "n"(ACC));
}
template <int AOFF, uint32_t AHI, int BOFF, uint32_t BHI, int ACC>
__device__ __forceinline__ void wgmma_ss232(float (&d)[116], uint32_t alo, uint32_t blo) {
  asm volatile("{\n.reg .pred p;\n.reg .b64 ad, bd;\nsetp.ne.b32 p, %122, 0;\n"
    "mov.b64 ad, {%116, %119};\nadd.s64 ad, ad, %118;\nmov.b64 bd, {%117, %121};\nadd.s64 bd, bd, %120;\n"
    "wgmma.mma_async.sync.aligned.m64n232k16.f32.bf16.bf16 {%0,%1,%2,%3,%4,%5,%6,%7,%8,%9,%10,%11,%12,%13,%14,%15,%16,%17,%18,%19,%20,%21,%22,%23,%24,%25,%26,%27,%28,%29,%30,%31,%32,%33,%34,%35,%36,%37,%38,%39,%40,%41,%42,%43,%44,%45,%46,%47,%48,%49,%50,%51,%52,%53,%54,%55,%56,%57,%58,%59,%60,%61,%62,%63,%64,%65,%66,%67,%68,%69,%70,%71,%72,%73,%74,%75,%76,%77,%78,%79,%80,%81,%82,%83,%84,%85,%86,%87,%88,%89,%90,%91,%92,%93,%94,%95,%96,%97,%98,%99,%100,%101,%102,%103,%104,%105,%106,%107,%108,%109,%110,%111,%112,%113,%114,%115}, ad, bd, p, 1, 1, 1, 1;\n}\n"
    : "+f"(d[0]),"+f"(d[1]),"+f"(d[2]),"+f"(d[3]),"+f"(d[4]),"+f"(d[5]),"+f"(d[6]),"+f"(d[7]),"+f"(d[8]),"+f"(d[9]),"+f"(d[10]),"+f"(d[11]),"+f"(d[12]),"+f"(d[13]),"+f"(d[14]),"+f"(d[15]),"+f"(d[16]),"+f"(d[17]),"+f"(d[18]),"+f"(d[19]),"+f"(d[20]),"+f"(d[21]),"+f"(d[22]),"+f"(d[23]),"+f"(d[24]),"+f"(d[25]),"+f"(d[26]),"+f"(d[27]),"+f"(d[28]),"+f"(d[29]),"+f"(d[30]),"+f"(d[31]),"+f"(d[32]),"+f"(d[33]),"+f"(d[34]),"+f"(d[35]),"+f"(d[36]),"+f"(d[37]),"+f"(d[38]),"+f"(d[39]),"+f"(d[40]),"+f"(d[41]),"+f"(d[42]),"+f"(d[43]),"+f"(d[44]),"+f"(d[45]),"+f"(d[46]),"+f"(d[47]),"+f"(d[48]),"+f"(d[49]),"+f"(d[50]),"+f"(d[51]),"+f"(d[52]),"+f"(d[53]),"+f"(d[54]),"+f"(d[55]),"+f"(d[56]),"+f"(d[57]),"+f"(d[58]),"+f"(d[59]),"+f"(d[60]),"+f"(d[61]),"+f"(d[62]),"+f"(d[63]),"+f"(d[64]),"+f"(d[65]),"+f"(d[66]),"+f"(d[67]),"+f"(d[68]),"+f"(d[69]),"+f"(d[70]),"+f"(d[71]),"+f"(d[72]),"+f"(d[73]),"+f"(d[74]),"+f"(d[75]),"+f"(d[76]),"+f"(d[77]),"+f"(d[78]),"+f"(d[79]),"+f"(d[80]),"+f"(d[81]),"+f"(d[82]),"+f"(d[83]),"+f"(d[84]),"+f"(d[85]),"+f"(d[86]),"+f"(d[87]),"+f"(d[88]),"+f"(d[89]),"+f"(d[90]),"+f"(d[91]),"+f"(d[92]),"+f"(d[93]),"+f"(d[94]),"+f"(d[95]),"+f"(d[96]),"+f"(d[97]),"+f"(d[98]),"+f"(d[99]),"+f"(d[100]),"+f"(d[101]),"+f"(d[102]),"+f"(d[103]),"+f"(d[104]),"+f"(d[105]),"+f"(d[106]),"+f"(d[107]),"+f"(d[108]),"+f"(d[109]),"+f"(d[110]),"+f"(d[111]),"+f"(d[112]),"+f"(d[113]),"+f"(d[114]),"+f"(d[115])
    : "r"(alo), "r"(blo), "n"(AOFF), "n"(AHI), "n"(BOFF), "n"(BHI), "n"(ACC));
}
template <int OFF, uint32_t BHI, int ACC>
__device__ __forceinline__ void wgmma_rs224(float (&d)[112], uint32_t a0, uint32_t a1, uint32_t a2, uint32_t a3, uint32_t blo) {
  asm volatile("{\n.reg .pred p;\n.reg .b64 bd;\nsetp.ne.b32 p, %119, 0;\nmov.b64 bd, {%116, %118};\nadd.s64 bd, bd, %117;\n"
    "wgmma.mma_async.sync.aligned.m64n224k16.f32.bf16.bf16 {%0,%1,%2,%3,%4,%5,%6,%7,%8,%9,%10,%11,%12,%13,%14,%15,%16,%17,%18,%19,%20,%21,%22,%23,%24,%25,%26,%27,%28,%29,%30,%31,%32,%33,%34,%35,%36,%37,%38,%39,%40,%41,%42,%43,%44,%45,%46,%47,%48,%49,%50,%51,%52,%53,%54,%55,%56,%57,%58,%59,%60,%61,%62,%63,%64,%65,%66,%67,%68,%69,%70,%71,%72,%73,%74,%75,%76,%77,%78,%79,%80,%81,%82,%83,%84,%85,%86,%87,%88,%89,%90,%91,%92,%93,%94,%95,%96,%97,%98,%99,%100,%101,%102,%103,%104,%105,%106,%107,%108,%109,%110,%111}, {%112,%113,%114,%115}, bd, p, 1, 1, 1;\n}\n"
    : "+f"(d[0]),"+f"(d[1]),"+f"(d[2]),"+f"(d[3]),"+f"(d[4]),"+f"(d[5]),"+f"(d[6]),"+f"(d[7]),"+f"(d[8]),"+f"(d[9]),"+f"(d[10]),"+f"(d[11]),"+f"(d[12]),"+f"(d[13]),"+f"(d[14]),"+f"(d[15]),"+f"(d[16]),"+f"(d[17]),"+f"(d[18]),"+f"(d[19]),"+f"(d[20]),"+f"(d[21]),"+f"(d[22]),"+f"(d[23]),"+f"(d[24]),"+f"(d[25]),"+f"(d[26]),"+f"(d[27]),"+f"(d[28]),"+f"(d[29]),"+f"(d[30]),"+f"(d[31]),"+f"(d[32]),"+f"(d[33]),"+f"(d[34]),"+f"(d[35]),"+f"(d[36]),"+f"(d[37]),"+f"(d[38]),"+f"(d[39]),"+f"(d[40]),"+f"(d[41]),"+f"(d[42]),"+f"(d[43]),"+f"(d[44]),"+f"(d[45]),"+f"(d[46]),"+f"(d[47]),"+f"(d[48]),"+f"(d[49]),"+f"(d[50]),"+f"(d[51]),"+f"(d[52]),"+f"(d[53]),"+f"(d[54]),"+f"(d[55]),"+f"(d[56]),"+f"(d[57]),"+f"(d[58]),"+f"(d[59]),"+f"(d[60]),"+f"(d[61]),"+f"(d[62]),"+f"(d[63]),"+f"(d[64]),"+f"(d[65]),"+f"(d[66]),"+f"(d[67]),"+f"(d[68]),"+f"(d[69]),"+f"(d[70]),"+f"(d[71]),"+f"(d[72]),"+f"(d[73]),"+f"(d[74]),"+f"(d[75]),"+f"(d[76]),"+f"(d[77]),"+f"(d[78]),"+f"(d[79]),"+f"(d[80]),"+f"(d[81]),"+f"(d[82]),"+f"(d[83]),"+f"(d[84]),"+f"(d[85]),"+f"(d[86]),"+f"(d[87]),"+f"(d[88]),"+f"(d[89]),"+f"(d[90]),"+f"(d[91]),"+f"(d[92]),"+f"(d[93]),"+f"(d[94]),"+f"(d[95]),"+f"(d[96]),"+f"(d[97]),"+f"(d[98]),"+f"(d[99]),"+f"(d[100]),"+f"(d[101]),"+f"(d[102]),"+f"(d[103]),"+f"(d[104]),"+f"(d[105]),"+f"(d[106]),"+f"(d[107]),"+f"(d[108]),"+f"(d[109]),"+f"(d[110]),"+f"(d[111])
    : "r"(a0), "r"(a1), "r"(a2), "r"(a3), "r"(blo), "n"(OFF), "n"(BHI), "n"(ACC));
}
template <int OFF, uint32_t BHI, int ACC>
__device__ __forceinline__ void wgmma_rs56(float (&d)[28], uint32_t a0, uint32_t a1, uint32_t a2, uint32_t a3, uint32_t blo) {
  asm volatile("{\n.reg .pred p;\n.reg .b64 bd;\nsetp.ne.b32 p, %35, 0;\nmov.b64 bd, {%32, %34};\nadd.s64 bd, bd, %33;\n"
    "wgmma.mma_async.sync.aligned.m64n56k16.f32.bf16.bf16 {%0,%1,%2,%3,%4,%5,%6,%7,%8,%9,%10,%11,%12,%13,%14,%15,%16,%17,%18,%19,%20,%21,%22,%23,%24,%25,%26,%27}, {%28,%29,%30,%31}, bd, p, 1, 1, 1;\n}\n"
    : "+f"(d[0]),"+f"(d[1]),"+f"(d[2]),"+f"(d[3]),"+f"(d[4]),"+f"(d[5]),"+f"(d[6]),"+f"(d[7]),"+f"(d[8]),"+f"(d[9]),"+f"(d[10]),"+f"(d[11]),"+f"(d[12]),"+f"(d[13]),"+f"(d[14]),"+f"(d[15]),"+f"(d[16]),"+f"(d[17]),"+f"(d[18]),"+f"(d[19]),"+f"(d[20]),"+f"(d[21]),"+f"(d[22]),"+f"(d[23]),"+f"(d[24]),"+f"(d[25]),"+f"(d[26]),"+f"(d[27])
    : "r"(a0), "r"(a1), "r"(a2), "r"(a3), "r"(blo), "n"(OFF), "n"(BHI), "n"(ACC));
}

__device__ __forceinline__ void st128(uint4* p, uint32_t a, uint32_t b, uint32_t c, uint32_t d) {
  asm volatile("{\n.reg .b128 v;\n.reg .b64 lo, hi;\nmov.b64 lo, {%1, %2};\nmov.b64 hi, {%3, %4};\nmov.b128 v, {lo, hi};\n"
               "st.relaxed.gpu.global.b128 [%0], v;\n}" ::"l"(p), "r"(a), "r"(b), "r"(c), "r"(d) : "memory");
}
__device__ __forceinline__ void ld128(const uint4* p, uint32_t* r) {
  asm volatile("{\n.reg .b128 v;\n.reg .b64 lo, hi;\nld.relaxed.gpu.global.b128 v, [%4];\nmov.b128 {lo, hi}, v;\n"
               "mov.b64 {%0, %1}, lo;\nmov.b64 {%2, %3}, hi;\n}" : "=r"(r[0]), "=r"(r[1]), "=r"(r[2]), "=r"(r[3]) : "l"(p) : "memory");
}

template <int OFF, uint32_t BHI, int ACC>
__device__ __forceinline__ void wgmma_rs32(float (&d)[16], uint32_t a0, uint32_t a1, uint32_t a2, uint32_t a3, uint32_t blo) {
  asm volatile("{\n.reg .pred p;\n.reg .b64 bd;\nsetp.ne.b32 p, %23, 0;\nmov.b64 bd, {%20, %22};\nadd.s64 bd, bd, %21;\n"
    "wgmma.mma_async.sync.aligned.m64n32k16.f32.bf16.bf16 {%0,%1,%2,%3,%4,%5,%6,%7,%8,%9,%10,%11,%12,%13,%14,%15}, {%16,%17,%18,%19}, bd, p, 1, 1, 0;\n}\n"
    : "+f"(d[0]),"+f"(d[1]),"+f"(d[2]),"+f"(d[3]),"+f"(d[4]),"+f"(d[5]),"+f"(d[6]),"+f"(d[7]),"+f"(d[8]),"+f"(d[9]),"+f"(d[10]),"+f"(d[11]),"+f"(d[12]),"+f"(d[13]),"+f"(d[14]),"+f"(d[15])
    : "r"(a0), "r"(a1), "r"(a2), "r"(a3), "r"(blo), "n"(OFF), "n"(BHI), "n"(ACC));
}
template <int OFF, uint32_t BHI, int ACC>
__device__ __forceinline__ void wgmma_rs24(float (&d)[12], uint32_t a0, uint32_t a1, uint32_t a2, uint32_t a3, uint32_t blo) {
  asm volatile("{\n.reg .pred p;\n.reg .b64 bd;\nsetp.ne.b32 p, %19, 0;\nmov.b64 bd, {%16, %18};\nadd.s64 bd, bd, %17;\n"
    "wgmma.mma_async.sync.aligned.m64n24k16.f32.bf16.bf16 {%0,%1,%2,%3,%4,%5,%6,%7,%8,%9,%10,%11}, {%12,%13,%14,%15}, bd, p, 1, 1, 1;\n}\n"
    : "+f"(d[0]),"+f"(d[1]),"+f"(d[2]),"+f"(d[3]),"+f"(d[4]),"+f"(d[5]),"+f"(d[6]),"+f"(d[7]),"+f"(d[8]),"+f"(d[9]),"+f"(d[10]),"+f"(d[11])
    : "r"(a0), "r"(a1), "r"(a2), "r"(a3), "r"(blo), "n"(OFF), "n"(BHI), "n"(ACC));
}
template <int OFF, uint32_t BHI, int ACC>
__device__ __forceinline__ void wgmma_rs16(float (&d)[8], uint32_t a0, uint32_t a1, uint32_t a2, uint32_t a3, uint32_t blo) {
  asm volatile("{\n.reg .pred p;\n.reg .b64 bd;\nsetp.ne.b32 p, %15, 0;\nmov.b64 bd, {%12, %14};\nadd.s64 bd, bd, %13;\n"
    "wgmma.mma_async.sync.aligned.m64n16k16.f32.bf16.bf16 {%0,%1,%2,%3,%4,%5,%6,%7}, {%8,%9,%10,%11}, bd, p, 1, 1, 1;\n}\n"
    : "+f"(d[0]),"+f"(d[1]),"+f"(d[2]),"+f"(d[3]),"+f"(d[4]),"+f"(d[5]),"+f"(d[6]),"+f"(d[7])
    : "r"(a0), "r"(a1), "r"(a2), "r"(a3), "r"(blo), "n"(OFF), "n"(BHI), "n"(ACC));
}

constexpr int A_R1 = 0;
constexpr int A_R2A = A_R1 + 2624, A_R2B = A_R2A + 768, A_R3A = A_R2B + 768, A_R3B = A_R3A + 528;
constexpr int A_K1024 = A_R3B + 528;
constexpr int A_W5 = A_K1024 + 16;
constexpr int A_W3 = A_W5 + 4096;
constexpr int A_W9 = A_W3 + 4112;
constexpr int A_W7 = A_W9 + 2048;
constexpr int A_V  = A_W7 + 2048;
constexpr int A_UB = A_V + 2048;
constexpr int A_STG = A_UB + 5248;
constexpr int A_Y2 = A_STG, A_Y3 = A_Y2 + 6528, A_YB = A_Y3 + 4352;
constexpr int A_REC = A_STG + 4 * 4352;
constexpr int A_CH = A_REC + 8192;
static_assert(A_W5 % 16 == 0 && A_UB % 16 == 0 && A_CH % 16 == 0 && A_YB + 4096 <= A_REC, "layout");

struct cf { float x, y; };
__device__ __forceinline__ cf cmul(cf a, cf b) { cf r; r.x = fmaf(a.x, b.x, -a.y * b.y); r.y = fmaf(a.x, b.y, a.y * b.x); return r; }
__device__ __forceinline__ cf cexp_l(float lr, float li, float l) {
  float mag; asm("ex2.approx.ftz.f32 %0, %1;" : "=f"(mag) : "f"((lr * l) * 1.4426950408889634f));
  const float th = li * l;
  const float k = (fmaf(th, 0.15915494f, 12582912.f)) - 12582912.f;
  float ph = fmaf(th, 0.15915494f, -k);
  ph = fmaf(th, 6.4206383e-9f, ph) * 6.2831853f;
  cf r; r.x = mag * __cosf(ph); r.y = mag * __sinf(ph); return r;
}
__device__ __forceinline__ void sts16(uint32_t a, uint32_t v) { asm volatile("st.shared.u16 [%0], %1;" ::"r"(a), "h"((uint16_t)v) : "memory"); }
__device__ __forceinline__ void sts32(uint32_t a, uint32_t v) { asm volatile("st.shared.u32 [%0], %1;" ::"r"(a), "r"(v) : "memory"); }
__device__ __forceinline__ void sts64(uint32_t a, uint32_t v0, uint32_t v1) { asm volatile("st.shared.v2.u32 [%0], {%1, %2};" ::"r"(a), "r"(v0), "r"(v1) : "memory"); }
__device__ __forceinline__ void sts128(uint32_t a, uint32_t v0, uint32_t v1, uint32_t v2, uint32_t v3) {
  asm volatile("st.shared.v4.u32 [%0], {%1, %2, %3, %4};" ::"r"(a), "r"(v0), "r"(v1), "r"(v2), "r"(v3) : "memory");
}
__device__ __forceinline__ uint32_t lds32(uint32_t a) { uint32_t v; asm volatile("ld.shared.u32 %0, [%1];" : "=r"(v) : "r"(a) : "memory"); return v; }
__device__ __forceinline__ uint4 lds128(uint32_t a) {
  uint4 v; asm volatile("ld.shared.v4.u32 {%0, %1, %2, %3}, [%4];" : "=r"(v.x), "=r"(v.y), "=r"(v.z), "=r"(v.w) : "r"(a) : "memory"); return v;
}
__device__ __forceinline__ void ldsm4(uint32_t* r, uint32_t a) {
  asm volatile("ldmatrix.sync.aligned.m8n8.x4.shared.b16 {%0,%1,%2,%3}, [%4];" : "=r"(r[0]), "=r"(r[1]), "=r"(r[2]), "=r"(r[3]) : "r"(a) : "memory");
}
__device__ __forceinline__ void mma16816(float* d, const uint32_t* a, uint32_t b0, uint32_t b1) {
  asm volatile("mma.sync.aligned.m16n8k16.row.col.f32.bf16.bf16.f32 {%0,%1,%2,%3}, {%4,%5,%6,%7}, {%8,%9}, {%0,%1,%2,%3};"
               : "+f"(d[0]), "+f"(d[1]), "+f"(d[2]), "+f"(d[3]) : "r"(a[0]), "r"(a[1]), "r"(a[2]), "r"(a[3]), "r"(b0), "r"(b1));
}
__device__ __forceinline__ uint32_t hsub2_bf(uint32_t a, uint32_t b) { uint32_t r; asm("sub.rn.bf16x2 %0, %1, %2;" : "=r"(r) : "r"(a), "r"(b)); return r; }
__device__ __forceinline__ void bar_sync(int id, int n) { asm volatile("bar.sync %0, %1;" ::"r"(id), "r"(n) : "memory"); }

template <int S> struct F1B { static constexpr int c = S / 4 + ((S & 3) == 3 ? 0 : 0), cc = (16 * S) / 64, ks = (64 * cc - (16 * S - 48)) / 16, off = (A_UB + 2 * ks * 656 + (9 - cc) * 16) / 16; };

template <int NS>
__device__ __forceinline__ void load_quads(uint32_t* q, uint32_t addr) {
#pragma unroll
  for (int i = 0; i < NS; i++) {
    q[4 * i] = lds32(addr + i * 64); q[4 * i + 1] = lds32(addr + i * 64 + 32);
    q[4 * i + 2] = i ? q[4 * i - 3] : lds32(addr - 32);
    q[4 * i + 3] = q[4 * i];
  }
#pragma unroll
  for (int i = 0; i < 4 * NS; i++) asm volatile("" : "+r"(q[i]));
}
template <int S0, int NS>
__device__ __forceinline__ void f1_steps(float (&acc)[16], const uint32_t* a, uint32_t blo) {
  if constexpr (NS > 0) {
    wgmma_rs32<F1B<S0>::off, 8, S0 != 0>(acc, a[0], a[1], a[2], a[3], blo);
    f1_steps<S0 + 1, NS - 1>(acc, a + 4, blo);
  }
}
template <int S0, int NS, int BASE, int FIRST>
__device__ __forceinline__ void s2_steps(float (&acc)[12], const uint32_t* a, uint32_t blo) {
  if constexpr (NS > 0) {
    wgmma_rs24<BASE / 16 + (112 - 16 * S0), 64, !(FIRST && S0 == 0)>(acc, a[0], a[1], a[2], a[3], blo);
    s2_steps<S0 + 1, NS - 1, BASE, FIRST>(acc, a + 4, blo);
  }
}
template <int S0, int NS, int BASE, int FIRST>
__device__ __forceinline__ void s3_steps(float (&acc)[8], const uint32_t* a, uint32_t blo) {
  if constexpr (NS > 0) {
    wgmma_rs16<BASE / 16 + (48 - 16 * S0), 64, !(FIRST && S0 == 0)>(acc, a[0], a[1], a[2], a[3], blo);
    s3_steps<S0 + 1, NS - 1, BASE, FIRST>(acc, a + 4, blo);
  }
}

__device__ __forceinline__ void phase_a(
        unsigned char* sm, const uint32_t bar_rec, const uint32_t ep_addr,
        const __nv_bfloat16* __restrict__ x, const uint32_t* __restrict__ are, const uint32_t* __restrict__ aim,
        const uint32_t* __restrict__ bre, const uint32_t* __restrict__ bim, const uint32_t* __restrict__ cre,
        const uint32_t* __restrict__ cim, const unsigned short* __restrict__ logdt, const unsigned short* __restrict__ dskip,
        const uint4* __restrict__ wgate, const uint4* __restrict__ wup, const uint4* __restrict__ wdown) {
  const uint32_t sb = s2u(sm);
  const int tid = threadIdx.x, wg = tid >> 7, warp = tid >> 5, lane = tid & 31, wq = warp & 3, t128 = tid & 127;
  const int blk = blockIdx.x;
  const bool conv = blk < 112;

  uint2 xr[4];
  {
    const uint2* p = (const uint2*)(x + (size_t)(blk * 16 + warp) * DM);
    xr[0] = __ldg(p + lane); xr[1] = __ldg(p + 32 + lane); xr[2] = __ldg(p + 64 + lane);
    xr[3] = lane < 16 ? __ldg(p + 96 + lane) : make_uint2(0, 0);
  }
  const int ch = conv ? blk * 4 + wg : 0;
  const uint32_t cb = sb + wg * A_CH;
  uint32_t prm[6];
  {
    const int i = ch * 128 + t128;
    prm[0] = __ldg(are + i); prm[1] = __ldg(aim + i); prm[2] = __ldg(bre + i); prm[3] = __ldg(bim + i); prm[4] = __ldg(cre + i); prm[5] = __ldg(cim + i);
  }
  const uint32_t ldt = __ldg(logdt + ch);
  uint32_t cnt0 = 0;
  if (tid == 0) cnt0 = __ldcg(&g_cnt1);
#pragma unroll
  for (int i = 0; i < 4; i++) if (i < 3 || t128 < (A_W5 + 1024) / 16 - 384) sts128(cb + (i * 128 + t128) * 16, 0, 0, 0, 0);
  if (t128 < 65) sts128(cb + (t128 < 64 ? A_W3 + t128 * 16 : A_W9), 0, 0, 0, 0);
  if (t128 < 72) sts128(cb + A_UB + (t128 / 9) * 656 + (t128 % 9) * 16, 0, 0, 0, 0);
  {
    float s = 0.f, q = 0.f;
#pragma unroll
    for (int i = 0; i < 4; i++) {
      const float a = bf_lo(xr[i].x), b = bf_hi(xr[i].x), c = bf_lo(xr[i].y), d = bf_hi(xr[i].y);
      s += (a + b) + (c + d);
      q = fmaf(a, a, q); q = fmaf(b, b, q); q = fmaf(c, c, q); q = fmaf(d, d, q);
    }
#pragma unroll
    for (int o = 16; o; o >>= 1) { s += __shfl_xor_sync(~0u, s, o); q += __shfl_xor_sync(~0u, q, o); }
    const float mean = s * (1.f / DM);
    const float var = fmaxf(fmaf(-mean, mean, q * (1.f / DM)), 0.f);
    const float rs = __frcp_rn(rbf(__fsqrt_rn(rbf(rbf(var) + 1e-5f))));
    const uint32_t mm = pack_bf16(mean, mean);
    const uint32_t tu = sb + A_REC + (warp >> 3) * A_CH + (warp & 7) * 912 + lane * 8, tx = tu + 2 * A_CH;
#pragma unroll
    for (int i = 0; i < 4; i++) {
      if (i < 3 || lane < 16) {
        const uint32_t d0 = hsub2_bf(xr[i].x, mm), d1 = hsub2_bf(xr[i].y, mm);
        sts64(tu + i * 256, pack_bf16(bf_lo(d0) * rs, bf_hi(d0) * rs), pack_bf16(bf_lo(d1) * rs, bf_hi(d1) * rs));
        sts64(tx + i * 256, xr[i].x, xr[i].y);
      }
    }
  }
  if (tid == 0) sts32(ep_addr, (cnt0 >> 7) + 1u);
  if (tid == 320) TR(0, 1);
  auto publish_rows = [&]() {
    bar_sync(5, 512);
    uint4* dst = g_ux + ((size_t)(warp * 8 + (lane >> 2)) * 128 + blk) * 4 + ((lane ^ (blk >> 1)) & 3);
#pragma unroll
    for (int i = 0; i < 4; i++) {
      if (i < 3 || warp < 8) {
        uint32_t r[4];
        asm volatile("ldmatrix.sync.aligned.m8n8.x4.trans.shared.b16 {%0,%1,%2,%3}, [%4];" : "=r"(r[0]), "=r"(r[1]), "=r"(r[2]), "=r"(r[3])
                     : "r"(sb + A_REC + (lane >> 3) * A_CH + (lane & 7) * 912 + (warp + 16 * i) * 16) : "memory");
        dst[i * 65536] = make_uint4(r[0], r[1], r[2], r[3]);
      }
    }
    if (warp != 0) asm volatile("bar.arrive 6, 512;" ::: "memory");
  };
  auto release_rows = [&]() {
    if (warp == 0) {
      bar_sync(6, 512);
      if (lane == 0) { asm volatile("red.release.gpu.global.add.u32 [%0], 1;" ::"l"(&g_cnt1) : "memory"); TR(0, 8); }
      __syncwarp();
    }
  };

  if (!conv) {
    publish_rows();
    release_rows();
    const int a = blk - 112, mat = a >> 3, j = a & 7;
    float s[8];
#pragma unroll
    for (int k = 0; k < 8; k++) s[k] = 0.f;
    if (lane < 28) {
      const uint4* src = (mat ? wup : wgate) + j * 28 + lane + (size_t)warp * 224;
#pragma unroll
      for (int hb = 0; hb < 2; hb++) {
        uint4 v[14];
#pragma unroll
        for (int r = 0; r < 14; r++) v[r] = __ldg(src + (size_t)(hb * 14 + r) * 16 * 224);
#pragma unroll
        for (int r = 0; r < 14; r++) {
          s[0] += bf_lo(v[r].x); s[1] += bf_hi(v[r].x); s[2] += bf_lo(v[r].y); s[3] += bf_hi(v[r].y);
          s[4] += bf_lo(v[r].z); s[5] += bf_hi(v[r].z); s[6] += bf_lo(v[r].w); s[7] += bf_hi(v[r].w);
        }
      }
      float4* red = (float4*)(sm + A_STG + warp * 896 + lane * 32);
      red[0] = make_float4(s[0], s[1], s[2], s[3]); red[1] = make_float4(s[4], s[5], s[6], s[7]);
    }
    bar_sync(5, 512);
    if (tid < 224) {
      float t = 0.f;
#pragma unroll
      for (int w = 0; w < 16; w++) t += *(const float*)(sm + A_STG + w * 896 + tid * 4);
      const float hi = rbf(t), mid = rbf(t - hi), lo = rbf(t - hi - mid);
      const int q = tid / 112, n = tid % 112 + 112 * mat;
      __nv_bfloat16* dst = (__nv_bfloat16*)(g_cimg + (j * 2 + q) * 224 + (n >> 3) * 8) + (n & 7);
      dst[0] = __float2bfloat16_rn(hi); dst[8] = __float2bfloat16_rn(mid); dst[16] = __float2bfloat16_rn(lo);
#pragma unroll
      for (int k = 3; k < 8; k++) dst[8 * k] = __float2bfloat16_rn(0.f);
    }
    if (tid == 320) TR(0, 10);
    return;
  }

  const int g = lane >> 2, t = lane & 3;
  const int wr = (wq + wg) & 3;
  uint4 wv[6];
  auto w_src = [&](int i) -> const uint4* {
    if (i < 4) return (blk < 56 ? wgate : wup) + (blk % 56) * 4 + (lane & 3) + (size_t)(i * 128 + warp * 8 + (lane >> 2)) * 224;
    const int it = warp + 16 * (i - 4);
    return wdown + (size_t)(blk * 16 + (it / 14) * 8 + (lane >> 2)) * 56 + (it % 14) * 4 + (lane & 3);
  };
  auto w_on = [&](int i) { return i == 3 ? warp < 8 : i == 5 ? warp < 12 : true; };
  {
    const uint32_t stg = cb + A_STG + wq * 4352;
    const float dt = rbf(expf(__uint_as_float(ldt << 16)));
    float lr[2], li[2];
    cf bq[2], b0[2], b4[2];
    uint32_t bf[48];
#pragma unroll
    for (int m = 0; m < 2; m++) {
      lr[m] = dt * (m ? bf_hi(prm[0]) : bf_lo(prm[0]));
      li[m] = dt * (m ? bf_hi(prm[1]) : bf_lo(prm[1]));
    }
    {
      cf b[2], z[2];
#pragma unroll
      for (int m = 0; m < 2; m++) {
        cf db, c;
        db.x = dt * (m ? bf_hi(prm[2]) : bf_lo(prm[2])); db.y = -dt * (m ? bf_hi(prm[3]) : bf_lo(prm[3]));
        c.x = m ? bf_hi(prm[4]) : bf_lo(prm[4]); c.y = -(m ? bf_hi(prm[5]) : bf_lo(prm[5]));
        b[m] = cmul(c, db);
        z[m] = cexp_l(lr[m], -li[m], 1.f);
        bq[m] = cexp_l(lr[m], -li[m], 256.f);
      }
#pragma unroll
      for (int i = 0; i < 8; i++) {
        sts64(stg + i * 272 + lane * 8, pack_bf16(b[0].x, b[0].y), pack_bf16(b[1].x, b[1].y));
        if (!(i & 1)) {
          cf e0 = cmul(b[0], bq[0]), e1 = cmul(b[1], bq[1]);
          sts64(stg + (8 + i / 2) * 272 + lane * 8, pack_bf16(e0.x, e0.y), pack_bf16(e1.x, e1.y));
          if (i == 0) { b0[0] = e0; b0[1] = e1; }
          if (i == 4) { b4[0] = e0; b4[1] = e1; }
        }
        if (i < 7) { b[0] = cmul(b[0], z[0]); b[1] = cmul(b[1], z[1]); }
        if (i == 1) publish_rows();
      }
#pragma unroll
      for (int i = 0; i < 7; i++) {
        b0[0] = cmul(b0[0], bq[0]); b0[1] = cmul(b0[1], bq[1]);
        sts64(stg + (i < 2 ? 12 + 2 * i : i - 2) * 272 + lane * 8, pack_bf16(b0[0].x, b0[0].y), pack_bf16(b0[1].x, b0[1].y));
        if (i < 2) {
          b4[0] = cmul(b4[0], bq[0]); b4[1] = cmul(b4[1], bq[1]);
          sts64(stg + (13 + 2 * i) * 272 + lane * 8, pack_bf16(b4[0].x, b4[0].y), pack_bf16(b4[1].x, b4[1].y));
        }
        if (i == 1) {
          __syncwarp();
#pragma unroll
          for (int n = 0; n < 2; n++)
#pragma unroll
            for (int k2 = 0; k2 < 4; k2++) ldsm4(bf + n * 16 + k2 * 4, stg + (n * 8 + (lane & 7)) * 272 + k2 * 64 + (lane >> 3) * 16);
          __syncwarp();
        }
      }
    }
    __syncwarp();
#pragma unroll
    for (int k2 = 0; k2 < 4; k2++) ldsm4(bf + 32 + k2 * 4, stg + (lane & 7) * 272 + k2 * 64 + (lane >> 3) * 16);
    release_rows();
    if (!(lane & 1)) {
#pragma unroll
      for (int i = 0; i < 6; i++) if (w_on(i)) asm volatile("prefetch.global.L2 [%0];" ::"l"(w_src(i)));
    }
    if (tid == 320) TR(0, 16);
    float c[6][4];
#pragma unroll
    for (int i = 0; i < 6; i++) { c[i][0] = 0.f; c[i][1] = 0.f; c[i][2] = 0.f; c[i][3] = 0.f; }
    cf p[2], v[2];
    p[0] = cexp_l(lr[0], li[0], 8.f); p[1] = cexp_l(lr[1], li[1], 8.f);
    v[0].x = 1.f; v[0].y = 0.f; v[1] = v[0];
#pragma unroll
    for (int mt = 0; mt < 2; mt++) {
      __syncwarp();
#pragma unroll
      for (int i = 0; i < 16; i++) {
        sts64(stg + i * 272 + lane * 8, pack_bf16(v[0].x, v[0].y), pack_bf16(v[1].x, v[1].y));
        if (mt == 0 && i == 0) { v[0] = p[0]; v[1] = p[1]; }
        else if (mt == 0 || i < 15) { v[0] = cmul(v[0], p[0]); v[1] = cmul(v[1], p[1]); }
      }
      __syncwarp();
      if (mt == 1 && tid == 160) {
        const uint32_t tgt = lds32(ep_addr) * 128u;
        uint32_t cv; int it = 0;
        do { asm volatile("ld.acquire.gpu.global.u32 %0, [%1];" : "=r"(cv) : "l"(&g_cnt1) : "memory"); } while ((int)(cv - tgt) < 0 && ++it < 200000);
        asm volatile("fence.proxy.async;" ::: "memory");
        TR(0, 9);
        mbar_expect(bar_rec, 32768);
        for (int c2 = 0; c2 < 4; c2++) bulk_ld(sb + c2 * A_CH + A_REC, g_ux + (size_t)(blk * 4 + c2) * 512, 8192, bar_rec);
      }
#pragma unroll
      for (int ks = 0; ks < 8; ks++) {
        uint32_t a[4];
        ldsm4(a, stg + (lane & 15) * 272 + ks * 32 + (lane >> 4) * 16);
#pragma unroll
        for (int n = 0; n < 3; n++) mma16816(c[n * 2 + mt], a, bf[n * 16 + ks * 2], bf[n * 16 + ks * 2 + 1]);
      }
    }
    __syncwarp();
#pragma unroll
    for (int i = 0; i < 6; i++)
      sts128(stg + i * 512 + lane * 16, __float_as_uint(c[i][0]), __float_as_uint(c[i][1]), __float_as_uint(c[i][2]), __float_as_uint(c[i][3]));
#pragma unroll
    for (int i = 0; i < 6; i++) if (w_on(i)) wv[i] = __ldg(w_src(i));
    bar_sync(1 + wg, 128);
    if (tid == 320) TR(0, 2);
#pragma unroll
    for (int rep = 0; rep < 2; rep++) {
      const int qd = rep ? 2 + wr : 3 - wr;
      if (rep == 0 || wr >= 2) {
        float s[4] = {0.f, 0.f, 0.f, 0.f};
#pragma unroll
        for (int w = 0; w < 4; w++) {
          uint4 u4 = lds128(cb + A_STG + w * 4352 + qd * 512 + lane * 16);
          s[0] += __uint_as_float(u4.x); s[1] += __uint_as_float(u4.y); s[2] += __uint_as_float(u4.z); s[3] += __uint_as_float(u4.w);
        }
#pragma unroll
        for (int hf = 0; hf < 2; hf++) {
          const int j = (qd & 1) * 16 + g + 8 * hf;
          const uint32_t pk = pack_bf16(s[2 * hf + 1], s[2 * hf]);
          const uint32_t v0 = pk >> 16, v1 = pk & 0xFFFFu, v00 = v0 * 0x10001u;
          if (rep == 1) {
            if (t < 2) {
#pragma unroll
              for (int e = 0; e < 2; e++) {
                const int lam = 128 + 32 * (2 * t + e) + j, mu = lam >> 1;
                const uint32_t val = e ? v1 : v0;
                uint32_t a = cb + ((lam & 1) ? A_R3B : A_R3A) + mu * 4;
                if (lam == 128) { a = cb + A_R2A + 128 * 4; sts32(cb + A_K1024, val << 16); }
                sts16(a, val); sts16(a + 6, val);
              }
            } else if (t == 2 && j == 0) { sts16(cb + A_R3A + 128 * 4, v0); }
          } else if (qd < 2) {
            const uint32_t a = cb + A_R1 + (62 + 8 * j + 2 * t) * 4;
            sts16(a, v0); sts32(a + 4, pk); sts16(a + 10, v1);
          } else if (t < 2) {
            const int L = 256 + 8 * j + 4 * t;
            const uint32_t a = cb + A_R1 + (62 + L) * 4;
            if (L > 256) { sts16(a - 4, v0); sts32(a, v00); } else sts16(a, v0);
            sts32(a + 4, v00); sts32(a + 8, pk); sts16(a + 14, v1);
          } else {
            const int mu = 64 + 32 * (t - 2) + j;
            if (mu == 64) {
              const uint32_t a = cb + A_R1 + (62 + 512) * 4;
              sts16(a - 4, v0); sts32(a, v00); sts32(a + 4, v00); sts32(a + 8, v00); sts16(a + 14, v0);
            } else { sts16(cb + A_R2A + mu * 4, v0); sts16(cb + A_R2A + mu * 4 + 6, v0); }
            sts16(cb + A_R2B + mu * 4, v1); sts16(cb + A_R2B + mu * 4 + 6, v1);
          }
        }
      }
    }
  }
  {
    const int ngg = (blk % 56) * 4 + (lane & 3), j = ngg / 28, q = (ngg % 28) / 14, ng = ngg % 14 + (blk < 56 ? 0 : 14);
    uint4* dst = g_wimg + (size_t)j * 37632 + q * 14 * 896 + ng * 32 + (warp >> 2) * 896 + (warp & 3) * 8 + (lane >> 2);
#pragma unroll
    for (int i = 0; i < 4; i++) if (w_on(i)) dst[i * 4 * 896] = wv[i];
#pragma unroll
    for (int i = 4; i < 6; i++) {
      const int it = warp + 16 * (i - 4), n2 = (it % 14) * 4 + (lane & 3), k = (blk % 7) * 16 + (it / 14) * 8 + (lane >> 2);
      if (w_on(i)) g_wimg[(size_t)(blk / 14) * 37632 + 25088 + ((n2 / 7) * 2 + (blk / 7) % 2) * 784 + (n2 % 7) * 112 + k] = wv[i];
    }
  }
  if (tid == 320) TR(0, 3);

  const int bk = wr * 32 + lane;
  uint32_t xt[8], ud[8];
  {
    mbar_wait(bar_rec, 0);
    if (tid == 320) TR(0, 4);
    uint4 r[4];
#pragma unroll
    for (int i = 0; i < 4; i++) r[i] = lds128(cb + A_REC + bk * 64 + ((i ^ (bk >> 1)) & 3) * 16);
    const uint32_t ua = cb + A_UB + ((2 * bk) & 7) * 656 + ((bk >> 2) + 9) * 16;
    sts128(ua, r[0].x, r[1].x, r[2].x, r[3].x);
    sts128(ua + 656, r[0].y, r[1].y, r[2].y, r[3].y);
    if (bk <= 96) {
      const bool neg = bk == 96;
      const int bp = neg ? -1 : bk;
      uint32_t h[4];
      h[0] = lds32(cb + A_REC + ((bp - 1) & 127) * 64 + ((2 ^ ((bp - 1) >> 1)) & 3) * 16 + 4);
      h[1] = lds32(cb + A_REC + ((bp - 1) & 127) * 64 + ((3 ^ ((bp - 1) >> 1)) & 3) * 16 + 4);
      h[2] = lds32(cb + A_REC + (bp + 1) * 64 + ((0 ^ ((bp + 1) >> 1)) & 3) * 16);
      h[3] = lds32(cb + A_REC + (bp + 1) * 64 + ((1 ^ ((bp + 1) >> 1)) & 3) * 16);
      if (bp <= 0) { h[0] = 0; h[1] = 0; }
      const uint32_t wd[12] = {h[0], h[1], neg ? 0 : r[0].x, neg ? 0 : r[1].x, neg ? 0 : r[2].x, neg ? 0 : r[3].x,
                               neg ? 0 : r[0].y, neg ? 0 : r[1].y, neg ? 0 : r[2].y, neg ? 0 : r[3].y, h[2], h[3]};
      float P[25];
      P[0] = 0.f;
#pragma unroll
      for (int i = 0; i < 12; i++) { P[2 * i + 1] = P[2 * i] + bf_lo(wd[i]); P[2 * i + 2] = P[2 * i + 1] + bf_hi(wd[i]); }
#define WIN(i, hw) (P[(i) + 5 + (hw)] - P[(i) + 4 - (hw)])
#define WPK(i, hw) pack_bf16(WIN(i, hw), WIN((i) + 1, hw))
      const int tp = 2 * bp;
      const uint32_t a3 = cb + A_W3 + (tp + 64) * 16 + 8, a5 = cb + A_W5 + (tp + 64) * 16;
      if (!neg) sts64(a3, WPK(0, 1), WPK(2, 1));
      if (!neg) sts128(a3 + 8, WPK(4, 1), WPK(6, 1), WPK(8, 1), WPK(10, 1));
      sts64(a3 + 24, WPK(12, 1), WPK(14, 1));
      sts128(a5, WPK(0, 2), WPK(2, 2), WPK(4, 2), WPK(6, 2));
      sts128(a5 + 16, WPK(8, 2), WPK(10, 2), WPK(12, 2), WPK(14, 2));
      if (bp < 64) {
        if (!neg) sts128(cb + A_W7 + 1024 + bp * 16, WPK(0, 3), WPK(2, 3), WPK(4, 3), WPK(6, 3));
        if (bp < 63) {
          sts128(cb + A_W7 + (bp + 1) * 16, WPK(8, 3), WPK(10, 3), WPK(12, 3), WPK(14, 3));
          sts128(cb + A_W9 + (bp + 1) * 16, WPK(0, 4), WPK(2, 4), WPK(4, 4), WPK(6, 4));
          sts128(cb + A_W9 + 1024 + (bp + 1) * 16, WPK(8, 4), WPK(10, 4), WPK(12, 4), WPK(14, 4));
        }
        if (!neg) {
#define VPK(i) pack_bf16(P[(i) + 2] - P[i], P[(i) + 3] - P[(i) + 1])
          sts128(cb + A_V + bp * 32, VPK(0), VPK(2), VPK(4), VPK(6));
          sts128(cb + A_V + bp * 32 + 16, VPK(8), VPK(10), VPK(12), VPK(14));
        }
      }
    }
  }
  asm volatile("fence.proxy.async.shared::cta;" ::: "memory");
  bar_sync(1 + wg, 128);
  if (tid == 320) TR(0, 5);

  {
    const uint32_t cbu = __shfl_sync(~0u, cb, 0);
    const uint32_t blo_k = ((cbu & 0x3FFFF) >> 4) | (41u << 16);
    const uint32_t blo_n = ((cbu & 0x3FFFF) >> 4) | (8u << 16);
    const uint32_t tb = cb + (16 * wq + g - 2 * t) * 4;
    float y1[16], y2[12], y3[8];
    const uint32_t dk16 = __ldg(dskip + ch);
    uint32_t qa[32], qb[32];
    const uint32_t t1 = tb + A_R1 + (62 - 48) * 4;
    load_quads<4>(qa, tb + A_R3A + 17 * 4); load_quads<4>(qa + 16, tb + A_R3B + 16 * 4);
    wg_fence();
    s3_steps<0, 4, A_W9, 1>(y3, qa, blo_n); s3_steps<0, 4, A_W7, 0>(y3, qa + 16, blo_n);
    wg_commit();
    load_quads<8>(qb, tb + A_R2A + 16 * 4);
    wg_fence(); s2_steps<0, 8, A_W5, 1>(y2, qb, blo_n); wg_commit();
    wg_wait<1>(); load_quads<8>(qa, tb + A_R2B + 16 * 4);
    wg_fence(); s2_steps<0, 8, A_W3, 0>(y2, qa, blo_n); wg_commit();
    wg_wait<1>(); load_quads<8>(qb, t1);
    wg_fence(); f1_steps<0, 8>(y1, qb, blo_k); wg_commit();
    wg_wait<1>(); load_quads<8>(qa, t1 + 8 * 64);
    wg_fence(); f1_steps<8, 8>(y1, qa, blo_k); wg_commit();
    reg_fence(y2); reg_fence(y3);
    if (tid == 320) TR(0, 18);
    {
      const float k1024 = __uint_as_float(lds32(cb + A_K1024));
#pragma unroll
      for (int i = 0; i < 2; i++)
#pragma unroll
        for (int hf = 0; hf < 2; hf++) {
          const int idx = 16 * (16 * wq + g + 8 * hf) + 8 * i + 2 * t;
          const uint32_t vv = lds32(cb + A_V + idx * 2);
          sts64(cb + A_Y3 + (idx + 4 * (idx >> 6)) * 4, __float_as_uint(fmaf(k1024, bf_lo(vv), y3[4 * i + 2 * hf])),
                __float_as_uint(fmaf(k1024, bf_hi(vv), y3[4 * i + 2 * hf + 1])));
        }
#pragma unroll
      for (int i = 0; i < 3; i++)
#pragma unroll
        for (int hf = 0; hf < 2; hf++) {
          const int idx = 512 * i + 8 * (16 * wq + g + 8 * hf) + 2 * t;
          sts64(cb + A_Y2 + (idx + 4 * (idx >> 6)) * 4, __float_as_uint(y2[4 * i + 2 * hf]), __float_as_uint(y2[4 * i + 2 * hf + 1]));
        }
    }
    wg_wait<1>(); load_quads<8>(qb, t1 + 16 * 64);
    wg_fence(); f1_steps<16, 8>(y1, qb, blo_k); wg_commit();
    wg_wait<1>(); load_quads<8>(qa, t1 + 24 * 64);
    wg_fence(); f1_steps<24, 8>(y1, qa, blo_k); wg_commit();
    wg_wait<1>(); load_quads<5>(qb, t1 + 32 * 64);
    wg_fence(); f1_steps<32, 5>(y1, qb, blo_k); wg_commit();
    bar_sync(1 + wg, 128);
    float ex[12];
#pragma unroll
    for (int i = 1; i < 4; i++)
#pragma unroll
      for (int k = 0; k < 4; k++) {
        const int aa = 8 * i + 2 * t + (k & 1), b = 16 * wq + g + 8 * (k >> 1);
        float e = __uint_as_float(lds32(cb + A_Y2 + ((aa - 8) * 68 + b) * 4));
        if (i >= 2) e += __uint_as_float(lds32(cb + A_Y3 + ((aa - 16) * 68 + b) * 4));
        ex[4 * (i - 1) + k] = e;
      }
    {
      const uint32_t dk = dk16 * 0x10001u;
#pragma unroll
      for (int i = 0; i < 4; i++) {
        const uint4 r = lds128(cb + A_REC + bk * 64 + ((i ^ (bk >> 1)) & 3) * 16);
        ud[i] = hmul2_bf(r.x, dk); ud[4 + i] = hmul2_bf(r.y, dk); xt[i] = r.z; xt[4 + i] = r.w;
      }
    }
    wg_wait<0>();
    reg_fence(y1);
    if (tid == 320) TR(0, 6);
#pragma unroll
    for (int i = 0; i < 12; i++) y1[4 + i] += ex[i];
#pragma unroll
    for (int i = 0; i < 2; i++) {
      const int mi = lane >> 3, aa = 8 * (2 * i + (mi >> 1)) + (lane & 7);
      asm volatile("stmatrix.sync.aligned.m8n8.x4.trans.shared.b16 [%0], {%1,%2,%3,%4};"
                   ::"r"(cb + A_YB + aa * 128 + (((2 * wq + (mi & 1)) ^ (lane & 7)) << 4)),
                     "r"(pack_bf16(y1[8 * i], y1[8 * i + 1])), "r"(pack_bf16(y1[8 * i + 2], y1[8 * i + 3])),
                     "r"(pack_bf16(y1[8 * i + 4], y1[8 * i + 5])), "r"(pack_bf16(y1[8 * i + 6], y1[8 * i + 7])) : "memory");
    }
  }
  bar_sync(1 + wg, 128);
#pragma unroll
  for (int c = 0; c < 2; c++) {
    const int tau = 2 * bk + c, r = ch & 7;
    const uint4 y = lds128(cb + A_YB + (tau >> 3) * 128 + (((tau ^ (tau >> 3)) & 7) << 4));
    g_himg[(size_t)(tau >> 4) * 7168 + (ch >> 3) * 128 + ((tau >> 3) & 1) * 64 + r * 8 + ((tau & 7) ^ r)] =
        make_uint4(hadd2_bf(xt[4 * c], hadd2_bf(y.x, ud[4 * c])), hadd2_bf(xt[4 * c + 1], hadd2_bf(y.y, ud[4 * c + 1])),
                   hadd2_bf(xt[4 * c + 2], hadd2_bf(y.z, ud[4 * c + 2])), hadd2_bf(xt[4 * c + 3], hadd2_bf(y.w, ud[4 * c + 3])));
  }
  if (tid == 320) TR(0, 7);
}

constexpr int B_SA = 0, B_RING = 114688, B_SLOT = 14848, B_NSLOT = 7;
constexpr int B_CS = B_RING + B_NSLOT * B_SLOT;
constexpr int B_RED = B_CS + 7168;
constexpr int B_BAR = B_RED + 256;
constexpr int B_SMEM = B_BAR + 1024, A_SMEM = 4 * A_CH + 64;

__device__ __forceinline__ uint32_t mapa(uint32_t a, uint32_t r) { uint32_t o; asm("mapa.shared::cluster.u32 %0, %1, %2;" : "=r"(o) : "r"(a), "r"(r)); return o; }
template <class T> __device__ __forceinline__ T* pin(T* p) { asm volatile("" : "+l"(p)); return p; }
__device__ __forceinline__ uint32_t pin(uint32_t v) { asm volatile("" : "+r"(v)); return v; }
template <int Q, int ST>
__device__ __forceinline__ void g1_stage(float (&acc)[116], uint32_t alo, uint32_t blo, uint32_t bar_full, uint32_t bar_h) {
  constexpr int s = Q * 14 + ST, sl = s % B_NSLOT;
  if (Q == 0) mbar_wait(bar_h + 8 * ST, 0);
  mbar_wait(bar_full + 8 * sl, (s / B_NSLOT) & 1);
  wg_fence();
  if (Q == 0) {
    wgmma_ss232<(2 * ST) * 256, 0x40000080u, (sl * B_SLOT) / 16, 32, ST != 0>(acc, alo, blo);
    wgmma_ss232<(2 * ST + 1) * 256, 0x40000080u, (sl * B_SLOT + 256) / 16, 32, 1>(acc, alo, blo);
  } else {
    wgmma_ss224<(2 * ST) * 256, 0x40000080u, (sl * B_SLOT) / 16, 32, ST != 0>(*(float(*)[112])acc, alo, blo);
    wgmma_ss224<(2 * ST + 1) * 256, 0x40000080u, (sl * B_SLOT + 256) / 16, 32, 1>(*(float(*)[112])acc, alo, blo);
  }
}

__global__ void __launch_bounds__(512, 1)
k_front(const __nv_bfloat16* __restrict__ x, const uint32_t* __restrict__ are, const uint32_t* __restrict__ aim,
        const uint32_t* __restrict__ bre, const uint32_t* __restrict__ bim, const uint32_t* __restrict__ cre,
        const uint32_t* __restrict__ cim, const unsigned short* __restrict__ logdt, const unsigned short* __restrict__ dskip,
        const uint4* __restrict__ wgate, const uint4* __restrict__ wup, const uint4* __restrict__ wdown) {
  extern __shared__ __align__(1024) unsigned char sm[];
  const uint32_t bar_rec = s2u(sm) + 4 * A_CH;
  if (threadIdx.x == 320) TR(0, 0);
  asm volatile("griddepcontrol.launch_dependents;");
  if (threadIdx.x == 160) { mbar_init(bar_rec, 1); asm volatile("fence.mbarrier_init.release.cluster;" ::: "memory"); }
  phase_a(sm, bar_rec, bar_rec + 8, x, are, aim, bre, bim, cre, cim, logdt, dskip, wgate, wup, wdown);
}

__global__ void __cluster_dims__(2, 1, 1) __launch_bounds__(384, 1) k_ffn(__nv_bfloat16* __restrict__ out) {
  extern __shared__ __align__(1024) unsigned char sm[];
  const uint32_t sb = s2u(sm);
  const int tid = threadIdx.x, warp = __shfl_sync(~0u, tid >> 5, 0), wg = warp >> 2, lane = tid & 31;
  const uint32_t bar_full = sb + B_BAR, bar_empty = bar_full + 64, bar_h = bar_full + 128, bar_cs = bar_full + 240,
                 bar_g2 = bar_full + 248, bar_in = bar_full + 256, bar_hh = bar_full + 304, bar_afree = bar_full + 336, bar_out = bar_full + 352;
  if (tid == 0) {
    TR(1, 0);
    for (int i = 0; i < B_NSLOT; i++) { mbar_init(bar_full + 8 * i, 1); mbar_init(bar_empty + 8 * i, 2); }
    asm volatile("fence.mbarrier_init.release.cluster;" ::: "memory");
  } else if (tid == 32) {
    for (int i = 0; i < 14; i++) mbar_init(bar_h + 8 * i, 1);
    asm volatile("fence.mbarrier_init.release.cluster;" ::: "memory");
  } else if (tid == 64) {
    mbar_init(bar_cs, 1);
    mbar_init(bar_g2, 4);
    for (int i = 0; i < 6; i++) mbar_init(bar_in + 8 * i, 1);
    for (int i = 0; i < 4; i++) { mbar_init(bar_hh + 8 * i, 1); mbar_expect(bar_hh + 8 * i, 14336); }
    mbar_init(bar_afree, 4); mbar_init(bar_afree + 8, 2);
    for (int i = 0; i < 6; i++) mbar_init(bar_out + 8 * i, 128);
    asm volatile("fence.mbarrier_init.release.cluster;" ::: "memory");
  } else if (tid >= 128 && tid < 352) {
    sts128(sb + B_RING + ((tid - 128) >> 5) * B_SLOT + 14336 + (tid & 31) * 16, 0x3F803F80u, 0x3F803F80u, 0x3F803F80u, 0x3F803F80u);
  }
  asm volatile("fence.proxy.async.shared::cta;" ::: "memory");
  __syncthreads();
  asm volatile("barrier.cluster.arrive.relaxed.aligned;" ::: "memory");
  const int rank = blockIdx.x & 1, rt = blockIdx.x >> 3, j = blockIdx.x & 7, p = j >> 1, cg = 4 * rank + p;
  const int wq = warp & 3, t128 = tid & 127, g = lane >> 2, t = lane & 3;
  uint32_t ep, tag;
  auto load_ep = [&]() { asm volatile("ld.relaxed.gpu.global.u32 %0, [%1];" : "=r"(ep) : "l"(&g_cnt1) : "memory"); };
  auto a_slot = [&](int i, int own) { return B_SA + (i + (i >= own)) * 14336; };
  auto in_addr = [&](int q, int cw) { return sb + a_slot(4 + q, cg) + cw * 1792; };
  auto out_addr = [&](int cc, int w) { return sb + a_slot((cc & 2) + w, cg) + (cc & 1) * 7168; };
  auto in_cta = [&](int q) { return rt * 8 + ((p + 3 - q) & 3) * 2 + rank; };
  auto in_src = [&](int q, int cw) { return g_part + (size_t)(in_cta(q) * 3 + q) * 896 + cw * 112; };
  auto in_bad = [&](uint32_t (&in)[14]) { return ((in[3] ^ tag) | (in[7] ^ tag) | (in[11] ^ tag) | (in[13] ^ tag)) & 0x10000u; };
  auto in_poll = [&](uint32_t (&in)[14], const uint4* gs) {
    int it = 0;
    do {
#pragma unroll
      for (int i = 0; i < 3; i++) ld128(gs + i * 32, in + 4 * i);
      asm volatile("{\n.reg .b64 v;\nld.relaxed.gpu.global.b64 v, [%2];\nmov.b64 {%0, %1}, v;\n}"
                   : "=r"(in[12]), "=r"(in[13]) : "l"((const uint2*)(gs + 96) - lane) : "memory");
    } while (in_bad(in) && ++it < 400000);
  };
  auto in_smem = [&](uint32_t (&in)[14], int q, int cw) {
    const uint32_t a = in_addr(q, cw);
    const uint4 v0 = lds128(a + lane * 16), v1 = lds128(a + 512 + lane * 16), v2 = lds128(a + 1024 + lane * 16);
    in[0] = v0.x; in[1] = v0.y; in[2] = v0.z; in[3] = v0.w; in[4] = v1.x; in[5] = v1.y; in[6] = v1.z; in[7] = v1.w;
    in[8] = v2.x; in[9] = v2.y; in[10] = v2.z; in[11] = v2.w;
    asm volatile("ld.shared.v2.u32 {%0, %1}, [%2];" : "=r"(in[12]), "=r"(in[13]) : "r"(a + 1536 + lane * 8) : "memory");
    if (in_bad(in)) in_poll(in, pin(in_src(q, cw) + lane));
  };

  if (wg == 2) {
    asm volatile("setmaxnreg.dec.sync.aligned.u32 40;");
    asm volatile("barrier.cluster.wait.aligned;" ::: "memory");
    asm volatile("griddepcontrol.wait;" ::: "memory");
    if (warp == 8) {
      if (lane == 0) TR(1, 1);
      const char* wsrc = (const char*)g_wimg + (size_t)j * 602112;
      const char* hsrc = (const char*)g_himg + (size_t)rt * 114688 + rank * 4096;
#pragma unroll
      for (int s = 0; s < 28; s++) {
        if (s < B_NSLOT) bulk_ld_mc_elect<4096>(sb + B_SA + s * 8192 + rank * 4096, hsrc + s * 8192, bar_h + 8 * s);
        if (s == B_NSLOT) {
#pragma unroll
          for (int i = 7; i < 14; i++) bulk_ld_mc_elect<4096>(sb + B_SA + i * 8192 + rank * 4096, hsrc + i * 8192, bar_h + 8 * i);
          bulk_ld_elect<7168>(sb + B_CS, g_cimg + j * 448, bar_cs);
        }
        if (s >= B_NSLOT) mbar_wait(bar_empty + 8 * (s % B_NSLOT), (s / B_NSLOT + 1) & 1);
        bulk_ld_elect<14336>(sb + B_RING + (s % B_NSLOT) * B_SLOT, wsrc + s * 14336, bar_full + 8 * (s % B_NSLOT));
      }
      const char* dsrc[2] = {wsrc + 401408 + rank * 100352, (const char*)g_wimg + (size_t)(j ^ 1) * 602112 + 401408 + rank * 100352};
#pragma unroll
      for (int i = 0; i < 16; i++) {
        const int ci = i < 3 ? 0 : i < 6 ? 1 : i < 8 ? i - 6 : i < 12 ? 2 : 3;
        const int kp = i < 3 ? i : i < 6 ? i - 3 : i < 8 ? 3 : (i & 3);
        mbar_wait(bar_empty + 8 * (i % B_NSLOT), (i / B_NSLOT + 1) & 1);
        bulk_ld_elect<12544>(sb + B_RING + (i % B_NSLOT) * B_SLOT, dsrc[kp >> 1] + ((p + 1 + ci) & 3) * 25088 + (kp & 1) * 12544, bar_full + 8 * (i % B_NSLOT));
      }
    } else if (warp == 9) {
      load_ep(); ep >>= 7;
      const uint32_t* fl = g_flag + blockIdx.x * 32 + (lane & 7);
      uint32_t todo = 0xF;
      bool live = false;
      int it = 0;
      while (todo && ++it < 400000) {
        if (!live) { __nanosleep(400); live = __all_sync(~0u, mbar_test(bar_g2, 0)); }
        uint32_t w;
        asm volatile("ld.relaxed.gpu.global.u32 %0, [%1];" : "=r"(w) : "l"(fl) : "memory");
        const uint32_t rdy = live ? __ballot_sync(~0u, w == ep) & todo : 0u;
        if (rdy) {
#pragma unroll
          for (int u = 0; u < 4; u++)
            if ((rdy >> u) & 1) {
              bulk_ld_elect<7168>(in_addr(u >> 1, (u & 1) * 4), in_src(u >> 1, (u & 1) * 4), bar_in + 8 * u);
              if ((u & 1) && lane == 0) TR(1, 24 + (u >> 1));
            }
          todo &= ~rdy;
        }
      }
    } else {
      const int t64 = tid - 320;
      load_ep();
      const int r = (lane >> 1) & 7, c = (j & 3) * 2 + (lane & 1);
      const uint32_t src = sb + B_SA + (t64 >> 4) * 2048 + (j >> 2) * 1024 + r * 128 + ((c ^ r) << 4);
      float a[16];
#pragma unroll
      for (int k = 0; k < 16; k++) a[k] = 0.f;
#pragma unroll 1
      for (int i = 0; i < 14; i++) {
        mbar_wait(bar_h + 8 * i, 0);
        uint4 v = lds128(src + i * 8192);
        float e[8] = {bf_lo(v.x), bf_hi(v.x), bf_lo(v.y), bf_hi(v.y), bf_lo(v.z), bf_hi(v.z), bf_lo(v.w), bf_hi(v.w)};
#pragma unroll
        for (int k = 0; k < 8; k++) { a[2 * k] += e[k]; a[2 * k + 1] = fmaf(e[k], e[k], a[2 * k + 1]); }
        __nanosleep(160);
      }
      __syncwarp();
      if (lane == 0) { mbar_arrive(bar_g2); asm volatile("mbarrier.arrive.shared::cluster.b64 _, [%0];" ::"r"(mapa(bar_afree, rank ^ 1)) : "memory"); }
#pragma unroll
      for (int rd = 0; rd < 4; rd++) {
        const int n = 8 >> rd;
        const bool up = lane & (2 * n);
#pragma unroll
        for (int k = 0; k < 8; k++) {
          if (k < n) {
            float keep = up ? a[k + n] : a[k], give = up ? a[k] : a[k + n];
            a[k] = keep + __shfl_xor_sync(~0u, give, 2 * n);
          }
        }
      }
      float* red = (float*)(sm + B_RED);
      red[(warp & 1) * 32 + (lane & 1) * 16 + (lane >> 1)] = a[0];
      bar_sync(1, 64);
      if (t64 < 16) {
        float mean = (red[2 * t64] + red[32 + 2 * t64]) * (1.f / DM);
        float var = fmaxf(fmaf(-mean, mean, (red[2 * t64 + 1] + red[33 + 2 * t64]) * (1.f / DM)), 0.f);
        float rs = __frcp_rn(rbf(__fsqrt_rn(rbf(rbf(var) + 1e-5f))));
        asm volatile("st.relaxed.gpu.global.u32 [%0], %1;"
                     ::"l"(g_stat2 + rt * 128 + j * 16 + t64), "r"((__float_as_uint(rs * rs) & ~1u) | ((ep >> 7) & 1u)) : "memory");
      }
      if (t64 == 0) TR(1, 2);
      if (lane == 0) {
        const int w = warp & 1;
        for (int cc = 0; cc < 2; cc++) {
          mbar_wait(bar_out + 8 * (cc * 2 + w), 0);
          asm volatile("cp.async.bulk.global.shared::cta.bulk_group [%0], [%1], 7168;"
                       ::"l"(g_part + (size_t)(blockIdx.x * 3 + cc) * 896 + w * 448), "r"(out_addr(cc, w)) : "memory");
          asm volatile("cp.async.bulk.commit_group;" ::: "memory");
          asm volatile("cp.async.bulk.wait_group 0;" ::: "memory");
          asm volatile("st.relaxed.gpu.global.u32 [%0], %1;" ::"l"(g_flag + (rt * 8 + ((p + 1 + cc) & 3) * 2 + rank) * 32 + cc * 2 + w), "r"(ep >> 7) : "memory");
          if (w) TR(1, 27 + cc);
        }
      }
    }
  } else {
    asm volatile("setmaxnreg.inc.sync.aligned.u32 232;");
    asm volatile("barrier.cluster.wait.aligned;" ::: "memory");
    uint32_t hh[56];
    const bool relt = t128 == 0;
    auto release = [&](int sl) { if (relt) mbar_arrive(bar_empty + 8 * sl); };
    auto send_hh = [&](int q) {
      const uint32_t da = mapa(sb + a_slot(2 * q + wg, cg ^ 4) + t128 * 16, rank ^ 1), db = mapa(bar_hh + 8 * (2 * q + wg), rank ^ 1);
#pragma unroll
      for (int i = 0; i < 7; i++)
        asm volatile("st.async.weak.shared::cluster.mbarrier::complete_tx::bytes.v4.b32 [%0], {%1, %2, %3, %4}, [%5];"
                     ::"r"(da + i * 2048), "r"(hh[28 * q + 4 * i]), "r"(hh[28 * q + 4 * i + 1]),
                       "r"(hh[28 * q + 4 * i + 2]), "r"(hh[28 * q + 4 * i + 3]), "r"(db) : "memory");
    };
    uint32_t alo = ((sb + B_SA + wg * 1024) & 0x3FFFF) >> 4;
    uint32_t blo = (((sb + B_RING) & 0x3FFFF) >> 4) | (8u << 16);
    const uint32_t clo = ((sb + B_CS) & 0x3FFFF) >> 4;
    uint32_t nm0, nm1;
    if (wg == 1) bar_sync(3, 256);
#define G1S(Q, ST) do { if (ST % 7 == 0) { alo = pin(alo); blo = pin(blo); }   \
      g1_stage<Q, ST>(acc, alo, blo, bar_full, bar_h); wg_commit(); \
      if (ST > 0) { wg_wait<1>(); release((Q * 14 + ST - 1) % B_NSLOT); } } while (0)
#define G1HH(Q) do { \
      _Pragma("unroll") \
      for (int i = 0; i < 28; i++) hh[28 * Q + i] = pack_bf16(acc[2 * i] * acc[56 + 2 * i], acc[2 * i + 1] * acc[57 + 2 * i]); \
    } while (0)
    {
      float acc[116];
      G1S(0, 0);
      if (tid == 0) TR(1, 3);
      G1S(0, 1);
      if (wg == 0) asm volatile("bar.arrive 3, 256;" ::: "memory");
      G1S(0, 2); G1S(0, 3); G1S(0, 4); G1S(0, 5); G1S(0, 6); G1S(0, 7); G1S(0, 8); G1S(0, 9); G1S(0, 10); G1S(0, 11); G1S(0, 12);
      G1S(0, 13);
      if (tid == 0) TR(1, 4);
      mbar_wait(bar_cs, 0);
      wg_wait<0>(); reg_fence(acc); release(13 % B_NSLOT);
      {
        const uint32_t msk = t == 0 ? 0xFFFFFFFFu : t == 1 ? 0xFFFFu : 0u;
        const float a = acc[112] * (-1.f / DM), b = acc[114] * (-1.f / DM);
        nm0 = pack_bf16(a, a) & msk; nm1 = pack_bf16(b, b) & msk;
      }
      wg_fence();
      wgmma_rs224<0, 8, 1>(*(float(*)[112])acc, nm0, nm1, 0u, 0u, clo);
      wg_commit(); wg_wait<0>(); reg_fence(acc);
      G1HH(0);
      if (tid == 0) TR(1, 5);
      G1S(1, 0); G1S(1, 1); G1S(1, 2); G1S(1, 3); G1S(1, 4); G1S(1, 5); G1S(1, 6);
      if (relt) asm volatile("mbarrier.arrive.shared::cluster.b64 _, [%0];" ::"r"(mapa(bar_afree, rank ^ 1)) : "memory");
      G1S(1, 7); G1S(1, 8); G1S(1, 9);
      if (relt) asm volatile("mbarrier.arrive.shared::cluster.b64 _, [%0];" ::"r"(mapa(bar_afree + 8, rank ^ 1)) : "memory");
      mbar_wait(bar_afree, 0);
      send_hh(0);
      G1S(1, 10); G1S(1, 11); G1S(1, 12);
      load_ep();
      g1_stage<1, 13>(acc, alo, blo, bar_full, bar_h);
      wgmma_rs224<224, 8, 1>(*(float(*)[112])acc, nm0, nm1, 0u, 0u, clo);
      wg_commit(); wg_wait<1>(); release(26 % B_NSLOT);
      wg_wait<0>(); reg_fence(acc); release(27 % B_NSLOT);
      if (t128 == 0) mbar_arrive(bar_g2);
      G1HH(1);
      if (tid == 0) TR(1, 6);
    }
    float accA[28], accB[28];
    uint32_t ph0[28], ph1[28];
    ep = pin(ep >> 7); tag = pin((ep & 1u) << 16);
#define ISSUE(acc, I, a, FIRST) do { \
      constexpr int s_ = 28 + (I), sl_ = s_ % B_NSLOT; \
      if (sl_ == 0) blo = pin(blo); \
      mbar_wait(bar_full + 8 * sl_, (s_ / B_NSLOT) & 1); \
      wg_fence(); \
      wgmma_rs56<(sl_ * B_SLOT + 0 * 256) / 16, 112, !(FIRST)>(acc, (a)[0], (a)[1], (a)[2], (a)[3], blo); \
      wgmma_rs56<(sl_ * B_SLOT + 1 * 256) / 16, 112, 1>(acc, (a)[4], (a)[5], (a)[6], (a)[7], blo); \
      wgmma_rs56<(sl_ * B_SLOT + 2 * 256) / 16, 112, 1>(acc, (a)[8], (a)[9], (a)[10], (a)[11], blo); \
      wgmma_rs56<(sl_ * B_SLOT + 3 * 256) / 16, 112, 1>(acc, (a)[12], (a)[13], (a)[14], (a)[15], blo); \
      wgmma_rs56<(sl_ * B_SLOT + 4 * 256) / 16, 112, 1>(acc, (a)[16], (a)[17], (a)[18], (a)[19], blo); \
      wgmma_rs56<(sl_ * B_SLOT + 5 * 256) / 16, 112, 1>(acc, (a)[20], (a)[21], (a)[22], (a)[23], blo); \
      wgmma_rs56<(sl_ * B_SLOT + 6 * 256) / 16, 112, 1>(acc, (a)[24], (a)[25], (a)[26], (a)[27], blo); \
      wg_commit(); } while (0)
    auto rel = [&](int i) { release((28 + i) % B_NSLOT); };
    auto tg = [&](uint32_t v) { return (v & 0xFFFEFFFFu) | tag; };
    auto send = [&](float (&acc)[28], int cc) {
      reg_fence(acc);
      const uint32_t a = out_addr(cc, wg) + wq * 1792;
#pragma unroll
      for (int q = 0; q < 3; q++)
        sts128(a + q * 512 + lane * 16, pack_bf16(acc[8 * q], acc[8 * q + 1]), pack_bf16(acc[8 * q + 2], acc[8 * q + 3]),
               pack_bf16(acc[8 * q + 4], acc[8 * q + 5]), tg(pack_bf16(acc[8 * q + 6], acc[8 * q + 7])));
      sts64(a + 1536 + lane * 8, pack_bf16(acc[24], acc[25]), tg(pack_bf16(acc[26], acc[27])));
      asm volatile("fence.proxy.async.shared::cta;" ::: "memory");
      mbar_arrive(bar_out + 8 * (cc * 2 + wg));
    };
    auto load_hh = [&](uint32_t (&d)[28], int q) {
      mbar_wait(bar_hh + 8 * (2 * q + wg), 0);
      const uint32_t a = sb + a_slot(2 * q + wg, cg) + t128 * 16;
#pragma unroll
      for (int i = 0; i < 7; i++) {
        const uint4 v = lds128(a + i * 2048);
        d[4 * i] = v.x; d[4 * i + 1] = v.y; d[4 * i + 2] = v.z; d[4 * i + 3] = v.w;
      }
    };
    ISSUE(accA, 0, hh, true);
    mbar_wait(bar_afree + 8, 0);
    send_hh(1);
    ISSUE(accA, 1, hh + 28, false);
    load_hh(ph0, 0);
    wg_wait<1>(); rel(0);
    ISSUE(accA, 2, ph0, false);      wg_wait<1>(); rel(1);
    ISSUE(accB, 3, hh, true);        wg_wait<1>(); rel(2);
    ISSUE(accB, 4, hh + 28, false);  wg_wait<1>(); rel(3);
    ISSUE(accB, 5, ph0, false);
    if (tid == 0) TR(1, 11);
    load_hh(ph1, 1);
    wg_wait<1>(); rel(4);
    ISSUE(accA, 6, ph1, false);      wg_wait<1>(); rel(5);
    ISSUE(accB, 7, ph1, false);      wg_wait<1>(); rel(6); send(accA, 0);
    ISSUE(accA, 8, hh, true);        wg_wait<1>(); rel(7); send(accB, 1);
    if (tid == 0) TR(1, 13);
    ISSUE(accA, 9, hh + 28, false);  wg_wait<1>(); rel(8);
    ISSUE(accA, 10, ph0, false);
    ISSUE(accA, 11, ph1, false);
    const int row = rt * 128 + wg * 64 + wq * 16 + g;
    uint32_t r20, r21;
    asm volatile("ld.relaxed.gpu.global.u32 %0, [%1];" : "=r"(r20) : "l"(g_stat2 + row) : "memory");
    asm volatile("ld.relaxed.gpu.global.u32 %0, [%1];" : "=r"(r21) : "l"(g_stat2 + row + 8) : "memory");
    ISSUE(accB, 12, hh, true);
    wg_wait<1>();
    {
      reg_fence(accA);
      uint4* pd = g_part + (size_t)(blockIdx.x * 3 + 2) * 896 + warp * 112 + lane;
#pragma unroll
      for (int q = 0; q < 3; q++)
        st128(pd + q * 32, pack_bf16(accA[8 * q], accA[8 * q + 1]), pack_bf16(accA[8 * q + 2], accA[8 * q + 3]),
              pack_bf16(accA[8 * q + 4], accA[8 * q + 5]), tg(pack_bf16(accA[8 * q + 6], accA[8 * q + 7])));
      asm volatile("{\n.reg .b64 v;\nmov.b64 v, {%1, %2};\nst.relaxed.gpu.global.b64 [%0], v;\n}"
                   ::"l"((uint2*)(pd + 96) - lane), "r"(pack_bf16(accA[24], accA[25])), "r"(tg(pack_bf16(accA[26], accA[27]))) : "memory");
    }
    if (tid == 0) TR(1, 16);
    ISSUE(accB, 13, hh + 28, false);
    ISSUE(accB, 14, ph0, false);
    ISSUE(accB, 15, ph1, false);
    if (tid == 0) TR(1, 7);
    uint32_t hres[16];
#pragma unroll
    for (int i = 0; i < 4; i++) {
      int qq = lane >> 3, r = lane & 7, kg = 7 * cg + 2 * i + (qq >> 1), c = 2 * wq + (qq & 1);
      if (kg > 55) kg = 55;
      asm volatile("ldmatrix.sync.aligned.m8n8.x4.trans.shared.b16 {%0,%1,%2,%3}, [%4];"
                   : "=r"(hres[4 * i]), "=r"(hres[4 * i + 1]), "=r"(hres[4 * i + 2]), "=r"(hres[4 * i + 3])
                   : "r"(sb + B_SA + kg * 2048 + wg * 1024 + r * 128 + ((c ^ r) << 4)) : "memory");
    }
    {
      int it = 0;
      while ((((r20 ^ ep) | (r21 ^ ep)) & 1u) && ++it < 400000) {
        asm volatile("ld.relaxed.gpu.global.u32 %0, [%1];" : "=r"(r20) : "l"(g_stat2 + row) : "memory");
        asm volatile("ld.relaxed.gpu.global.u32 %0, [%1];" : "=r"(r21) : "l"(g_stat2 + row + 8) : "memory");
      }
    }
    uint32_t in0[14], in1[14];
    const uint4* last_src = pin(in_src(2, warp) + lane);
    mbar_wait(bar_in + 8 * wg, 0);
    in_smem(in0, 0, warp);
    mbar_wait(bar_in + 8 * (2 + wg), 0);
    in_smem(in1, 1, warp);
#pragma unroll
    for (int i = 0; i < 14; i++) { accA[2 * i] = bf_lo(in0[i]) + bf_lo(in1[i]); accA[2 * i + 1] = bf_hi(in0[i]) + bf_hi(in1[i]); }
    if (tid == 0) TR(1, 12);
    wg_wait<0>();
    reg_fence(accB);
    if (tid == 0) TR(1, 9);
    in_poll(in0, last_src);
#pragma unroll
    for (int i = 0; i < 14; i++) { accB[2 * i] += accA[2 * i] + bf_lo(in0[i]); accB[2 * i + 1] += accA[2 * i + 1] + bf_hi(in0[i]); }
    uint32_t* o0 = (uint32_t*)(out + (size_t)row * DM + 56 * cg + 2 * t);
    uint32_t* o1 = o0 + 8 * DM / 2;
#pragma unroll
    for (int i = 0; i < 7; i++) {
      o0[4 * i] = hadd2_bf(hres[2 * i], pack_bf16(accB[4 * i] * __uint_as_float(r20), accB[4 * i + 1] * __uint_as_float(r20)));
      o1[4 * i] = hadd2_bf(hres[2 * i + 1], pack_bf16(accB[4 * i + 2] * __uint_as_float(r21), accB[4 * i + 3] * __uint_as_float(r21)));
    }
    if (tid == 0) TR(1, 10);
    if (tid == 128) TR(1, 15);
  }
}

extern "C" void kernel_launch(void* const* d_in, const int* in_sizes, int n_in, void* d_out, int out_size) {
  const __nv_bfloat16* x = (const __nv_bfloat16*)d_in[0];
  const __nv_bfloat16 *are = (const __nv_bfloat16*)d_in[1], *aim = (const __nv_bfloat16*)d_in[2], *bre = (const __nv_bfloat16*)d_in[3],
                      *bim = (const __nv_bfloat16*)d_in[4], *cre = (const __nv_bfloat16*)d_in[5], *cim = (const __nv_bfloat16*)d_in[6],
                      *logdt = (const __nv_bfloat16*)d_in[7], *dskip = (const __nv_bfloat16*)d_in[8];
  const __nv_bfloat16 *wg = (const __nv_bfloat16*)d_in[10], *wu = (const __nv_bfloat16*)d_in[11], *wd = (const __nv_bfloat16*)d_in[12];

  static bool init = false;
  if (!init) {
    init = true;
    cudaFuncSetAttribute(k_ffn, cudaFuncAttributeMaxDynamicSharedMemorySize, B_SMEM);
    cudaFuncSetAttribute(k_front, cudaFuncAttributeMaxDynamicSharedMemorySize, A_SMEM);
  }
  cudaStream_t st = cudaStreamPerThread;
  k_front<<<128, 512, A_SMEM, st>>>(
      x, (const uint32_t*)are, (const uint32_t*)aim, (const uint32_t*)bre, (const uint32_t*)bim, (const uint32_t*)cre, (const uint32_t*)cim,
      (const unsigned short*)logdt, (const unsigned short*)dskip, (const uint4*)wg, (const uint4*)wu, (const uint4*)wd);
  cudaLaunchConfig_t cfg = {};
  cfg.gridDim = dim3(128); cfg.blockDim = dim3(384); cfg.dynamicSmemBytes = B_SMEM; cfg.stream = st;
  cudaLaunchAttribute at[1];
  at[0].id = cudaLaunchAttributeProgrammaticStreamSerialization; at[0].val.programmaticStreamSerializationAllowed = 1;
  cfg.attrs = at; cfg.numAttrs = 1;
  cudaLaunchKernelEx(&cfg, k_ffn, (__nv_bfloat16*)d_out);
}
```

```cpp
#include <cuda_runtime.h>
#include <cuda_bf16.h>
#include <stdint.h>

constexpr int LSEQ = 2048, DM = 448;

__device__ uint4    g_himg[16 * 114688 / 16];
__device__ uint4    g_cimg[8 * 2 * 224];
__device__ uint32_t g_stat2[LSEQ];
__device__ uint4    g_part[128 * 3 * 896];
__device__ uint4    g_wimg[8 * 602112 / 16];
__device__ uint4    g_ux[DM * 128 * 4];
__device__ unsigned g_cnt1;

#define TR(k, i) do {} while (0)
__device__ __forceinline__ uint32_t s2u(const void* p) { return (uint32_t)__cvta_generic_to_shared(p); }
__device__ __forceinline__ void mbar_init(uint32_t b, int c) { asm volatile("mbarrier.init.shared::cta.b64 [%0], %1;" ::"r"(b), "r"(c)); }
__device__ __forceinline__ void mbar_expect(uint32_t b, int bytes) { asm volatile("mbarrier.arrive.expect_tx.shared::cta.b64 _, [%0], %1;" ::"r"(b), "r"(bytes) : "memory"); }
__device__ __forceinline__ void mbar_arrive(uint32_t b) { asm volatile("mbarrier.arrive.shared::cta.b64 _, [%0];" ::"r"(b) : "memory"); }
__device__ __forceinline__ void mbar_wait(uint32_t b, int ph) {
  asm volatile("{\n.reg .pred p;\n.reg .b32 n;\nmov.b32 n, 0;\nLW:\nmbarrier.try_wait.parity.shared::cta.b64 p, [%0], %1;\n@p bra LD;\n"
               "add.u32 n, n, 1;\nsetp.lt.u32 p, n, 4000000;\n@p bra LW;\ntrap;\nLD:\n}" ::"r"(b), "r"(ph) : "memory");
}
__device__ __forceinline__ bool mbar_test(uint32_t b, int ph) {
  uint32_t ok;
  asm volatile("{\n.reg .pred p;\nmbarrier.test_wait.parity.shared::cta.b64 p, [%1], %2;\nselp.u32 %0, 1, 0, p;\n}" : "=r"(ok) : "r"(b), "r"(ph) : "memory");
  return ok;
}
__device__ __forceinline__ void wg_fence() { asm volatile("wgmma.fence.sync.aligned;" ::: "memory"); }
__device__ __forceinline__ void wg_commit() { asm volatile("wgmma.commit_group.sync.aligned;" ::: "memory"); }
template <int N> __device__ __forceinline__ void wg_wait() { asm volatile("wgmma.wait_group.sync.aligned %0;" ::"n"(N) : "memory"); }
template <int N> __device__ __forceinline__ void reg_fence(float (&a)[N]) {
#pragma unroll
  for (int i = 0; i < N; i++) asm volatile("" : "+f"(a[i])::"memory");
}
__device__ __forceinline__ uint32_t pack_bf16(float lo, float hi) {
  uint32_t r; asm("cvt.rn.bf16x2.f32 %0, %1, %2;" : "=r"(r) : "f"(hi), "f"(lo)); return r;
}
__device__ __forceinline__ float bf_lo(uint32_t v) { return __uint_as_float(v << 16); }
__device__ __forceinline__ float bf_hi(uint32_t v) { return __uint_as_float(v & 0xFFFF0000u); }
__device__ __forceinline__ float rbf(float x) { return __bfloat162float(__float2bfloat16_rn(x)); }
__device__ __forceinline__ uint32_t hmul2_bf(uint32_t a, uint32_t b) { uint32_t r; asm("mul.rn.bf16x2 %0, %1, %2;" : "=r"(r) : "r"(a), "r"(b)); return r; }
__device__ __forceinline__ uint32_t hadd2_bf(uint32_t a, uint32_t b) { uint32_t r; asm("add.rn.bf16x2 %0, %1, %2;" : "=r"(r) : "r"(a), "r"(b)); return r; }
__device__ __forceinline__ void bulk_ld(uint32_t dst, const void* src, int bytes, uint32_t bar) {
  asm volatile("cp.async.bulk.shared::cluster.global.mbarrier::complete_tx::bytes [%0], [%1], %2, [%3];"
               ::"r"(dst), "l"(src), "r"(bytes), "r"(bar) : "memory");
}

template <int BYTES>
__device__ __forceinline__ void bulk_ld_elect(uint32_t dst, const void* src, uint32_t bar) {
  asm volatile("{\n.reg .pred p;\nelect.sync _|p, 0xffffffff;\n"
               "@p mbarrier.arrive.expect_tx.shared::cta.b64 _, [%2], %3;\n"
               "@p cp.async.bulk.shared::cluster.global.mbarrier::complete_tx::bytes [%0], [%1], %3, [%2];\n}"
               ::"r"(dst), "l"(src), "r"(bar), "n"(BYTES) : "memory");
}
template <int BYTES>
__device__ __forceinline__ void bulk_ld_mc_elect(uint32_t dst, const void* src, uint32_t bar) {
  asm volatile("{\n.reg .pred p;\nelect.sync _|p, 0xffffffff;\n"
               "@p mbarrier.arrive.expect_tx.shared::cta.b64 _, [%2], %3;\n"
               "@p cp.async.bulk.shared::cluster.global.mbarrier::complete_tx::bytes.multicast::cluster [%0], [%1], %4, [%2], %5;\n}"
               ::"r"(dst), "l"(src), "r"(bar), "n"(2 * BYTES), "n"(BYTES), "h"((uint16_t)3) : "memory");
}
template <int AOFF, uint32_t AHI, int BOFF, uint32_t BHI, int ACC>
__device__ __forceinline__ void wgmma_ss224(float (&d)[112], uint32_t alo, uint32_t blo) {
  asm volatile("{\n.reg .pred p;\n.reg .b64 ad, bd;\nsetp.ne.b32 p, %118, 0;\n"
    "mov.b64 ad, {%112, %115};\nadd.s64 ad, ad, %114;\nmov.b64 bd, {%113, %117};\nadd.s64 bd, bd, %116;\n"
    "wgmma.mma_async.sync.aligned.m64n224k16.f32.bf16.bf16 {%0,%1,%2,%3,%4,%5,%6,%7,%8,%9,%10,%11,%12,%13,%14,%15,%16,%17,%18,%19,%20,%21,%22,%23,%24,%25,%26,%27,%28,%29,%30,%31,%32,%33,%34,%35,%36,%37,%38,%39,%40,%41,%42,%43,%44,%45,%46,%47,%48,%49,%50,%51,%52,%53,%54,%55,%56,%57,%58,%59,%60,%61,%62,%63,%64,%65,%66,%67,%68,%69,%70,%71,%72,%73,%74,%75,%76,%77,%78,%79,%80,%81,%82,%83,%84,%85,%86,%87,%88,%89,%90,%91,%92,%93,%94,%95,%96,%97,%98,%99,%100,%101,%102,%103,%104,%105,%106,%107,%108,%109,%110,%111}, ad, bd, p, 1, 1, 1, 1;\n}\n"
    : "+f"(d[0]),"+f"(d[1]),"+f"(d[2]),"+f"(d[3]),"+f"(d[4]),"+f"(d[5]),"+f"(d[6]),"+f"(d[7]),"+f"(d[8]),"+f"(d[9]),"+f"(d[10]),"+f"(d[11]),"+f"(d[12]),"+f"(d[13]),"+f"(d[14]),"+f"(d[15]),"+f"(d[16]),"+f"(d[17]),"+f"(d[18]),"+f"(d[19]),"+f"(d[20]),"+f"(d[21]),"+f"(d[22]),"+f"(d[23]),"+f"(d[24]),"+f"(d[25]),"+f"(d[26]),"+f"(d[27]),"+f"(d[28]),"+f"(d[29]),"+f"(d[30]),"+f"(d[31]),"+f"(d[32]),"+f"(d[33]),"+f"(d[34]),"+f"(d[35]),"+f"(d[36]),"+f"(d[37]),"+f"(d[38]),"+f"(d[39]),"+f"(d[40]),"+f"(d[41]),"+f"(d[42]),"+f"(d[43]),"+f"(d[44]),"+f"(d[45]),"+f"(d[46]),"+f"(d[47]),"+f"(d[48]),"+f"(d[49]),"+f"(d[50]),"+f"(d[51]),"+f"(d[52]),"+f"(d[53]),"+f"(d[54]),"+f"(d[55]),"+f"(d[56]),"+f"(d[57]),"+f"(d[58]),"+f"(d[59]),"+f"(d[60]),"+f"(d[61]),"+f"(d[62]),"+f"(d[63]),"+f"(d[64]),"+f"(d[65]),"+f"(d[66]),"+f"(d[67]),"+f"(d[68]),"+f"(d[69]),"+f"(d[70]),"+f"(d[71]),"+f"(d[72]),"+f"(d[73]),"+f"(d[74]),"+f"(d[75]),"+f"(d[76]),"+f"(d[77]),"+f"(d[78]),"+f"(d[79]),"+f"(d[80]),"+f"(d[81]),"+f"(d[82]),"+f"(d[83]),"+f"(d[84]),"+f"(d[85]),"+f"(d[86]),"+f"(d[87]),"+f"(d[88]),"+f"(d[89]),"+f"(d[90]),"+f"(d[91]),"+f"(d[92]),"+f"(d[93]),"+f"(d[94]),"+f"(d[95]),"+f"(d[96]),"+f"(d[97]),"+f"(d[98]),"+f"(d[99]),"+f"(d[100]),"+f"(d[101]),"+f"(d[102]),"+f"(d[103]),"+f"(d[104]),"+f"(d[105]),"+f"(d[106]),"+f"(d[107]),"+f"(d[108]),"+f"(d[109]),"+f"(d[110]),"+f"(d[111])
    : "r"(alo), "r"(blo), "n"(AOFF), "n"(AHI), "n"(BOFF), "n"(BHI), "n"(ACC));
}
template <int AOFF, uint32_t AHI, int BOFF, uint32_t BHI, int ACC>
__device__ __forceinline__ void wgmma_ss232(float (&d)[116], uint32_t alo, uint32_t blo) {
  asm volatile("{\n.reg .pred p;\n.reg .b64 ad, bd;\nsetp.ne.b32 p, %122, 0;\n"
    "mov.b64 ad, {%116, %119};\nadd.s64 ad, ad, %118;\nmov.b64 bd, {%117, %121};\nadd.s64 bd, bd, %120;\n"
    "wgmma.mma_async.sync.aligned.m64n232k16.f32.bf16.bf16 {%0,%1,%2,%3,%4,%5,%6,%7,%8,%9,%10,%11,%12,%13,%14,%15,%16,%17,%18,%19,%20,%21,%22,%23,%24,%25,%26,%27,%28,%29,%30,%31,%32,%33,%34,%35,%36,%37,%38,%39,%40,%41,%42,%43,%44,%45,%46,%47,%48,%49,%50,%51,%52,%53,%54,%55,%56,%57,%58,%59,%60,%61,%62,%63,%64,%65,%66,%67,%68,%69,%70,%71,%72,%73,%74,%75,%76,%77,%78,%79,%80,%81,%82,%83,%84,%85,%86,%87,%88,%89,%90,%91,%92,%93,%94,%95,%96,%97,%98,%99,%100,%101,%102,%103,%104,%105,%106,%107,%108,%109,%110,%111,%112,%113,%114,%115}, ad, bd, p, 1, 1, 1, 1;\n}\n"
    : "+f"(d[0]),"+f"(d[1]),"+f"(d[2]),"+f"(d[3]),"+f"(d[4]),"+f"(d[5]),"+f"(d[6]),"+f"(d[7]),"+f"(d[8]),"+f"(d[9]),"+f"(d[10]),"+f"(d[11]),"+f"(d[12]),"+f"(d[13]),"+f"(d[14]),"+f"(d[15]),"+f"(d[16]),"+f"(d[17]),"+f"(d[18]),"+f"(d[19]),"+f"(d[20]),"+f"(d[21]),"+f"(d[22]),"+f"(d[23]),"+f"(d[24]),"+f"(d[25]),"+f"(d[26]),"+f"(d[27]),"+f"(d[28]),"+f"(d[29]),"+f"(d[30]),"+f"(d[31]),"+f"(d[32]),"+f"(d[33]),"+f"(d[34]),"+f"(d[35]),"+f"(d[36]),"+f"(d[37]),"+f"(d[38]),"+f"(d[39]),"+f"(d[40]),"+f"(d[41]),"+f"(d[42]),"+f"(d[43]),"+f"(d[44]),"+f"(d[45]),"+f"(d[46]),"+f"(d[47]),"+f"(d[48]),"+f"(d[49]),"+f"(d[50]),"+f"(d[51]),"+f"(d[52]),"+f"(d[53]),"+f"(d[54]),"+f"(d[55]),"+f"(d[56]),"+f"(d[57]),"+f"(d[58]),"+f"(d[59]),"+f"(d[60]),"+f"(d[61]),"+f"(d[62]),"+f"(d[63]),"+f"(d[64]),"+f"(d[65]),"+f"(d[66]),"+f"(d[67]),"+f"(d[68]),"+f"(d[69]),"+f"(d[70]),"+f"(d[71]),"+f"(d[72]),"+f"(d[73]),"+f"(d[74]),"+f"(d[75]),"+f"(d[76]),"+f"(d[77]),"+f"(d[78]),"+f"(d[79]),"+f"(d[80]),"+f"(d[81]),"+f"(d[82]),"+f"(d[83]),"+f"(d[84]),"+f"(d[85]),"+f"(d[86]),"+f"(d[87]),"+f"(d[88]),"+f"(d[89]),"+f"(d[90]),"+f"(d[91]),"+f"(d[92]),"+f"(d[93]),"+f"(d[94]),"+f"(d[95]),"+f"(d[96]),"+f"(d[97]),"+f"(d[98]),"+f"(d[99]),"+f"(d[100]),"+f"(d[101]),"+f"(d[102]),"+f"(d[103]),"+f"(d[104]),"+f"(d[105]),"+f"(d[106]),"+f"(d[107]),"+f"(d[108]),"+f"(d[109]),"+f"(d[110]),"+f"(d[111]),"+f"(d[112]),"+f"(d[113]),"+f"(d[114]),"+f"(d[115])
    : "r"(alo), "r"(blo), "n"(AOFF), "n"(AHI), "n"(BOFF), "n"(BHI), "n"(ACC));
}
template <int OFF, uint32_t BHI, int ACC>
__device__ __forceinline__ void wgmma_rs224(float (&d)[112], uint32_t a0, uint32_t a1, uint32_t a2, uint32_t a3, uint32_t blo) {
  asm volatile("{\n.reg .pred p;\n.reg .b64 bd;\nsetp.ne.b32 p, %119, 0;\nmov.b64 bd, {%116, %118};\nadd.s64 bd, bd, %117;\n"
    "wgmma.mma_async.sync.aligned.m64n224k16.f32.bf16.bf16 {%0,%1,%2,%3,%4,%5,%6,%7,%8,%9,%10,%11,%12,%13,%14,%15,%16,%17,%18,%19,%20,%21,%22,%23,%24,%25,%26,%27,%28,%29,%30,%31,%32,%33,%34,%35,%36,%37,%38,%39,%40,%41,%42,%43,%44,%45,%46,%47,%48,%49,%50,%51,%52,%53,%54,%55,%56,%57,%58,%59,%60,%61,%62,%63,%64,%65,%66,%67,%68,%69,%70,%71,%72,%73,%74,%75,%76,%77,%78,%79,%80,%81,%82,%83,%84,%85,%86,%87,%88,%89,%90,%91,%92,%93,%94,%95,%96,%97,%98,%99,%100,%101,%102,%103,%104,%105,%106,%107,%108,%109,%110,%111}, {%112,%113,%114,%115}, bd, p, 1, 1, 1;\n}\n"
    : "+f"(d[0]),"+f"(d[1]),"+f"(d[2]),"+f"(d[3]),"+f"(d[4]),"+f"(d[5]),"+f"(d[6]),"+f"(d[7]),"+f"(d[8]),"+f"(d[9]),"+f"(d[10]),"+f"(d[11]),"+f"(d[12]),"+f"(d[13]),"+f"(d[14]),"+f"(d[15]),"+f"(d[16]),"+f"(d[17]),"+f"(d[18]),"+f"(d[19]),"+f"(d[20]),"+f"(d[21]),"+f"(d[22]),"+f"(d[23]),"+f"(d[24]),"+f"(d[25]),"+f"(d[26]),"+f"(d[27]),"+f"(d[28]),"+f"(d[29]),"+f"(d[30]),"+f"(d[31]),"+f"(d[32]),"+f"(d[33]),"+f"(d[34]),"+f"(d[35]),"+f"(d[36]),"+f"(d[37]),"+f"(d[38]),"+f"(d[39]),"+f"(d[40]),"+f"(d[41]),"+f"(d[42]),"+f"(d[43]),"+f"(d[44]),"+f"(d[45]),"+f"(d[46]),"+f"(d[47]),"+f"(d[48]),"+f"(d[49]),"+f"(d[50]),"+f"(d[51]),"+f"(d[52]),"+f"(d[53]),"+f"(d[54]),"+f"(d[55]),"+f"(d[56]),"+f"(d[57]),"+f"(d[58]),"+f"(d[59]),"+f"(d[60]),"+f"(d[61]),"+f"(d[62]),"+f"(d[63]),"+f"(d[64]),"+f"(d[65]),"+f"(d[66]),"+f"(d[67]),"+f"(d[68]),"+f"(d[69]),"+f"(d[70]),"+f"(d[71]),"+f"(d[72]),"+f"(d[73]),"+f"(d[74]),"+f"(d[75]),"+f"(d[76]),"+f"(d[77]),"+f"(d[78]),"+f"(d[79]),"+f"(d[80]),"+f"(d[81]),"+f"(d[82]),"+f"(d[83]),"+f"(d[84]),"+f"(d[85]),"+f"(d[86]),"+f"(d[87]),"+f"(d[88]),"+f"(d[89]),"+f"(d[90]),"+f"(d[91]),"+f"(d[92]),"+f"(d[93]),"+f"(d[94]),"+f"(d[95]),"+f"(d[96]),"+f"(d[97]),"+f"(d[98]),"+f"(d[99]),"+f"(d[100]),"+f"(d[101]),"+f"(d[102]),"+f"(d[103]),"+f"(d[104]),"+f"(d[105]),"+f"(d[106]),"+f"(d[107]),"+f"(d[108]),"+f"(d[109]),"+f"(d[110]),"+f"(d[111])
    : "r"(a0), "r"(a1), "r"(a2), "r"(a3), "r"(blo), "n"(OFF), "n"(BHI), "n"(ACC));
}
template <int OFF, uint32_t BHI, int ACC>
__device__ __forceinline__ void wgmma_rs56(float (&d)[28], uint32_t a0, uint32_t a1, uint32_t a2, uint32_t a3, uint32_t blo) {
  asm volatile("{\n.reg .pred p;\n.reg .b64 bd;\nsetp.ne.b32 p, %35, 0;\nmov.b64 bd, {%32, %34};\nadd.s64 bd, bd, %33;\n"
    "wgmma.mma_async.sync.aligned.m64n56k16.f32.bf16.bf16 {%0,%1,%2,%3,%4,%5,%6,%7,%8,%9,%10,%11,%12,%13,%14,%15,%16,%17,%18,%19,%20,%21,%22,%23,%24,%25,%26,%27}, {%28,%29,%30,%31}, bd, p, 1, 1, 1;\n}\n"
    : "+f"(d[0]),"+f"(d[1]),"+f"(d[2]),"+f"(d[3]),"+f"(d[4]),"+f"(d[5]),"+f"(d[6]),"+f"(d[7]),"+f"(d[8]),"+f"(d[9]),"+f"(d[10]),"+f"(d[11]),"+f"(d[12]),"+f"(d[13]),"+f"(d[14]),"+f"(d[15]),"+f"(d[16]),"+f"(d[17]),"+f"(d[18]),"+f"(d[19]),"+f"(d[20]),"+f"(d[21]),"+f"(d[22]),"+f"(d[23]),"+f"(d[24]),"+f"(d[25]),"+f"(d[26]),"+f"(d[27])
    : "r"(a0), "r"(a1), "r"(a2), "r"(a3), "r"(blo), "n"(OFF), "n"(BHI), "n"(ACC));
}

__device__ __forceinline__ void st128(uint4* p, uint32_t a, uint32_t b, uint32_t c, uint32_t d) {
  asm volatile("{\n.reg .b128 v;\n.reg .b64 lo, hi;\nmov.b64 lo, {%1, %2};\nmov.b64 hi, {%3, %4};\nmov.b128 v, {lo, hi};\n"
               "st.relaxed.gpu.global.b128 [%0], v;\n}" ::"l"(p), "r"(a), "r"(b), "r"(c), "r"(d) : "memory");
}
__device__ __forceinline__ void ld128(const uint4* p, uint32_t* r) {
  asm volatile("{\n.reg .b128 v;\n.reg .b64 lo, hi;\nld.relaxed.gpu.global.b128 v, [%4];\nmov.b128 {lo, hi}, v;\n"
               "mov.b64 {%0, %1}, lo;\nmov.b64 {%2, %3}, hi;\n}" : "=r"(r[0]), "=r"(r[1]), "=r"(r[2]), "=r"(r[3]) : "l"(p) : "memory");
}

template <int OFF, uint32_t BHI, int ACC>
__device__ __forceinline__ void wgmma_rs32(float (&d)[16], uint32_t a0, uint32_t a1, uint32_t a2, uint32_t a3, uint32_t blo) {
  asm volatile("{\n.reg .pred p;\n.reg .b64 bd;\nsetp.ne.b32 p, %23, 0;\nmov.b64 bd, {%20, %22};\nadd.s64 bd, bd, %21;\n"
    "wgmma.mma_async.sync.aligned.m64n32k16.f32.bf16.bf16 {%0,%1,%2,%3,%4,%5,%6,%7,%8,%9,%10,%11,%12,%13,%14,%15}, {%16,%17,%18,%19}, bd, p, 1, 1, 0;\n}\n"
    : "+f"(d[0]),"+f"(d[1]),"+f"(d[2]),"+f"(d[3]),"+f"(d[4]),"+f"(d[5]),"+f"(d[6]),"+f"(d[7]),"+f"(d[8]),"+f"(d[9]),"+f"(d[10]),"+f"(d[11]),"+f"(d[12]),"+f"(d[13]),"+f"(d[14]),"+f"(d[15])
    : "r"(a0), "r"(a1), "r"(a2), "r"(a3), "r"(blo), "n"(OFF), "n"(BHI), "n"(ACC));
}
template <int OFF, uint32_t BHI, int ACC>
__device__ __forceinline__ void wgmma_rs24(float (&d)[12], uint32_t a0, uint32_t a1, uint32_t a2, uint32_t a3, uint32_t blo) {
  asm volatile("{\n.reg .pred p;\n.reg .b64 bd;\nsetp.ne.b32 p, %19, 0;\nmov.b64 bd, {%16, %18};\nadd.s64 bd, bd, %17;\n"
    "wgmma.mma_async.sync.aligned.m64n24k16.f32.bf16.bf16 {%0,%1,%2,%3,%4,%5,%6,%7,%8,%9,%10,%11}, {%12,%13,%14,%15}, bd, p, 1, 1, 1;\n}\n"
    : "+f"(d[0]),"+f"(d[1]),"+f"(d[2]),"+f"(d[3]),"+f"(d[4]),"+f"(d[5]),"+f"(d[6]),"+f"(d[7]),"+f"(d[8]),"+f"(d[9]),"+f"(d[10]),"+f"(d[11])
    : "r"(a0), "r"(a1), "r"(a2), "r"(a3), "r"(blo), "n"(OFF), "n"(BHI), "n"(ACC));
}
template <int OFF, uint32_t BHI, int ACC>
__device__ __forceinline__ void wgmma_rs16(float (&d)[8], uint32_t a0, uint32_t a1, uint32_t a2, uint32_t a3, uint32_t blo) {
  asm volatile("{\n.reg .pred p;\n.reg .b64 bd;\nsetp.ne.b32 p, %15, 0;\nmov.b64 bd, {%12, %14};\nadd.s64 bd, bd, %13;\n"
    "wgmma.mma_async.sync.aligned.m64n16k16.f32.bf16.bf16 {%0,%1,%2,%3,%4,%5,%6,%7}, {%8,%9,%10,%11}, bd, p, 1, 1, 1;\n}\n"
    : "+f"(d[0]),"+f"(d[1]),"+f"(d[2]),"+f"(d[3]),"+f"(d[4]),"+f"(d[5]),"+f"(d[6]),"+f"(d[7])
    : "r"(a0), "r"(a1), "r"(a2), "r"(a3), "r"(blo), "n"(OFF), "n"(BHI), "n"(ACC));
}

constexpr int A_R1 = 0;
constexpr int A_R2A = A_R1 + 2624, A_R2B = A_R2A + 768, A_R3A = A_R2B + 768, A_R3B = A_R3A + 528;
constexpr int A_K1024 = A_R3B + 528;
constexpr int A_W5 = A_K1024 + 16;
constexpr int A_W3 = A_W5 + 4096;
constexpr int A_W9 = A_W3 + 4112;
constexpr int A_W7 = A_W9 + 2048;
constexpr int A_V  = A_W7 + 2048;
constexpr int A_UB = A_V + 2048;
constexpr int A_STG = A_UB + 5248;
constexpr int A_Y2 = A_STG, A_Y3 = A_Y2 + 6528, A_YB = A_Y3 + 4352;
constexpr int A_REC = A_STG + 4 * 4352;
constexpr int A_CH = A_REC + 8192;
static_assert(A_W5 % 16 == 0 && A_UB % 16 == 0 && A_CH % 16 == 0 && A_YB + 4096 <= A_REC, "layout");

struct cf { float x, y; };
__device__ __forceinline__ cf cmul(cf a, cf b) { cf r; r.x = fmaf(a.x, b.x, -a.y * b.y); r.y = fmaf(a.x, b.y, a.y * b.x); return r; }
__device__ __forceinline__ cf cexp_l(float lr, float li, float l) {
  float mag; asm("ex2.approx.ftz.f32 %0, %1;" : "=f"(mag) : "f"((lr * l) * 1.4426950408889634f));
  const float th = li * l;
  const float k = (fmaf(th, 0.15915494f, 12582912.f)) - 12582912.f;
  float ph = fmaf(th, 0.15915494f, -k);
  ph = fmaf(th, 6.4206383e-9f, ph) * 6.2831853f;
  cf r; r.x = mag * __cosf(ph); r.y = mag * __sinf(ph); return r;
}
__device__ __forceinline__ void sts16(uint32_t a, uint32_t v) { asm volatile("st.shared.u16 [%0], %1;" ::"r"(a), "h"((uint16_t)v) : "memory"); }
__device__ __forceinline__ void sts32(uint32_t a, uint32_t v) { asm volatile("st.shared.u32 [%0], %1;" ::"r"(a), "r"(v) : "memory"); }
__device__ __forceinline__ void sts64(uint32_t a, uint32_t v0, uint32_t v1) { asm volatile("st.shared.v2.u32 [%0], {%1, %2};" ::"r"(a), "r"(v0), "r"(v1) : "memory"); }
__device__ __forceinline__ void sts128(uint32_t a, uint32_t v0, uint32_t v1, uint32_t v2, uint32_t v3) {
  asm volatile("st.shared.v4.u32 [%0], {%1, %2, %3, %4};" ::"r"(a), "r"(v0), "r"(v1), "r"(v2), "r"(v3) : "memory");
}
__device__ __forceinline__ uint32_t lds32(uint32_t a) { uint32_t v; asm volatile("ld.shared.u32 %0, [%1];" : "=r"(v) : "r"(a) : "memory"); return v; }
__device__ __forceinline__ uint4 lds128(uint32_t a) {
  uint4 v; asm volatile("ld.shared.v4.u32 {%0, %1, %2, %3}, [%4];" : "=r"(v.x), "=r"(v.y), "=r"(v.z), "=r"(v.w) : "r"(a) : "memory"); return v;
}
__device__ __forceinline__ void ldsm4(uint32_t* r, uint32_t a) {
  asm volatile("ldmatrix.sync.aligned.m8n8.x4.shared.b16 {%0,%1,%2,%3}, [%4];" : "=r"(r[0]), "=r"(r[1]), "=r"(r[2]), "=r"(r[3]) : "r"(a) : "memory");
}
__device__ __forceinline__ void mma16816(float* d, const uint32_t* a, uint32_t b0, uint32_t b1) {
  asm volatile("mma.sync.aligned.m16n8k16.row.col.f32.bf16.bf16.f32 {%0,%1,%2,%3}, {%4,%5,%6,%7}, {%8,%9}, {%0,%1,%2,%3};"
               : "+f"(d[0]), "+f"(d[1]), "+f"(d[2]), "+f"(d[3]) : "r"(a[0]), "r"(a[1]), "r"(a[2]), "r"(a[3]), "r"(b0), "r"(b1));
}
__device__ __forceinline__ uint32_t hsub2_bf(uint32_t a, uint32_t b) { uint32_t r; asm("sub.rn.bf16x2 %0, %1, %2;" : "=r"(r) : "r"(a), "r"(b)); return r; }
__device__ __forceinline__ void bar_sync(int id, int n) { asm volatile("bar.sync %0, %1;" ::"r"(id), "r"(n) : "memory"); }

template <int S> struct F1B { static constexpr int c = S / 4 + ((S & 3) == 3 ? 0 : 0), cc = (16 * S) / 64, ks = (64 * cc - (16 * S - 48)) / 16, off = (A_UB + 2 * ks * 656 + (9 - cc) * 16) / 16; };

template <int NS>
__device__ __forceinline__ void load_quads(uint32_t* q, uint32_t addr) {
#pragma unroll
  for (int i = 0; i < NS; i++) {
    q[4 * i] = lds32(addr + i * 64); q[4 * i + 1] = lds32(addr + i * 64 + 32);
    q[4 * i + 2] = i ? q[4 * i - 3] : lds32(addr - 32);
    q[4 * i + 3] = q[4 * i];
  }
#pragma unroll
  for (int i = 0; i < 4 * NS; i++) asm volatile("" : "+r"(q[i]));
}
template <int S0, int NS>
__device__ __forceinline__ void f1_steps(float (&acc)[16], const uint32_t* a, uint32_t blo) {
  if constexpr (NS > 0) {
    wgmma_rs32<F1B<S0>::off, 8, S0 != 0>(acc, a[0], a[1], a[2], a[3], blo);
    f1_steps<S0 + 1, NS - 1>(acc, a + 4, blo);
  }
}
template <int S0, int NS, int BASE, int FIRST>
__device__ __forceinline__ void s2_steps(float (&acc)[12], const uint32_t* a, uint32_t blo) {
  if constexpr (NS > 0) {
    wgmma_rs24<BASE / 16 + (112 - 16 * S0), 64, !(FIRST && S0 == 0)>(acc, a[0], a[1], a[2], a[3], blo);
    s2_steps<S0 + 1, NS - 1, BASE, FIRST>(acc, a + 4, blo);
  }
}
template <int S0, int NS, int BASE, int FIRST>
__device__ __forceinline__ void s3_steps(float (&acc)[8], const uint32_t* a, uint32_t blo) {
  if constexpr (NS > 0) {
    wgmma_rs16<BASE / 16 + (48 - 16 * S0), 64, !(FIRST && S0 == 0)>(acc, a[0], a[1], a[2], a[3], blo);
    s3_steps<S0 + 1, NS - 1, BASE, FIRST>(acc, a + 4, blo);
  }
}

__device__ __forceinline__ void phase_a(
        unsigned char* sm, const uint32_t bar_rec, const uint32_t ep_addr,
        const __nv_bfloat16* __restrict__ x, const uint32_t* __restrict__ are, const uint32_t* __restrict__ aim,
        const uint32_t* __restrict__ bre, const uint32_t* __restrict__ bim, const uint32_t* __restrict__ cre,
        const uint32_t* __restrict__ cim, const unsigned short* __restrict__ logdt, const unsigned short* __restrict__ dskip,
        const uint4* __restrict__ wgate, const uint4* __restrict__ wup, const uint4* __restrict__ wdown) {
  const uint32_t sb = s2u(sm);
  const int tid = threadIdx.x, wg = tid >> 7, warp = tid >> 5, lane = tid & 31, wq = warp & 3, t128 = tid & 127;
  const int blk = blockIdx.x;
  const bool conv = blk < 112;

  uint2 xr[4];
  {
    const uint2* p = (const uint2*)(x + (size_t)(blk * 16 + warp) * DM);
    xr[0] = __ldg(p + lane); xr[1] = __ldg(p + 32 + lane); xr[2] = __ldg(p + 64 + lane);
    xr[3] = lane < 16 ? __ldg(p + 96 + lane) : make_uint2(0, 0);
  }
  const int ch = conv ? blk * 4 + wg : 0;
  const uint32_t cb = sb + wg * A_CH;
  uint32_t prm[6];
  {
    const int i = ch * 128 + t128;
    prm[0] = __ldg(are + i); prm[1] = __ldg(aim + i); prm[2] = __ldg(bre + i); prm[3] = __ldg(bim + i); prm[4] = __ldg(cre + i); prm[5] = __ldg(cim + i);
  }
  const uint32_t ldt = __ldg(logdt + ch);
  uint32_t cnt0 = 0;
  if (tid == 0) cnt0 = __ldcg(&g_cnt1);
#pragma unroll
  for (int i = 0; i < 4; i++) if (i < 3 || t128 < (A_W5 + 1024) / 16 - 384) sts128(cb + (i * 128 + t128) * 16, 0, 0, 0, 0);
  if (t128 < 65) sts128(cb + (t128 < 64 ? A_W3 + t128 * 16 : A_W9), 0, 0, 0, 0);
  if (t128 < 72) sts128(cb + A_UB + (t128 / 9) * 656 + (t128 % 9) * 16, 0, 0, 0, 0);
  {
    float s = 0.f, q = 0.f;
#pragma unroll
    for (int i = 0; i < 4; i++) {
      const float a = bf_lo(xr[i].x), b = bf_hi(xr[i].x), c = bf_lo(xr[i].y), d = bf_hi(xr[i].y);
      s += (a + b) + (c + d);
      q = fmaf(a, a, q); q = fmaf(b, b, q); q = fmaf(c, c, q); q = fmaf(d, d, q);
    }
#pragma unroll
    for (int o = 16; o; o >>= 1) { s += __shfl_xor_sync(~0u, s, o); q += __shfl_xor_sync(~0u, q, o); }
    const float mean = s * (1.f / DM);
    const float var = fmaxf(fmaf(-mean, mean, q * (1.f / DM)), 0.f);
    const float rs = __frcp_rn(rbf(__fsqrt_rn(rbf(rbf(var) + 1e-5f))));
    const uint32_t mm = pack_bf16(mean, mean);
    const uint32_t tu = sb + A_REC + (warp >> 3) * A_CH + (warp & 7) * 912 + lane * 8, tx = tu + 2 * A_CH;
#pragma unroll
    for (int i = 0; i < 4; i++) {
      if (i < 3 || lane < 16) {
        const uint32_t d0 = hsub2_bf(xr[i].x, mm), d1 = hsub2_bf(xr[i].y, mm);
        sts64(tu + i * 256, pack_bf16(bf_lo(d0) * rs, bf_hi(d0) * rs), pack_bf16(bf_lo(d1) * rs, bf_hi(d1) * rs));
        sts64(tx + i * 256, xr[i].x, xr[i].y);
      }
    }
  }
  if (tid == 0) sts32(ep_addr, (cnt0 >> 7) + 1u);
  if (tid == 320) TR(0, 1);
  auto publish_rows = [&]() {
    bar_sync(5, 512);
    uint4* dst = g_ux + ((size_t)(warp * 8 + (lane >> 2)) * 128 + blk) * 4 + ((lane ^ (blk >> 1)) & 3);
#pragma unroll
    for (int i = 0; i < 4; i++) {
      if (i < 3 || warp < 8) {
        uint32_t r[4];
        asm volatile("ldmatrix.sync.aligned.m8n8.x4.trans.shared.b16 {%0,%1,%2,%3}, [%4];" : "=r"(r[0]), "=r"(r[1]), "=r"(r[2]), "=r"(r[3])
                     : "r"(sb + A_REC + (lane >> 3) * A_CH + (lane & 7) * 912 + (warp + 16 * i) * 16) : "memory");
        dst[i * 65536] = make_uint4(r[0], r[1], r[2], r[3]);
      }
    }
    if (warp != 0) asm volatile("bar.arrive 6, 512;" ::: "memory");
  };
  auto release_rows = [&]() {
    if (warp == 0) {
      bar_sync(6, 512);
      if (lane == 0) { asm volatile("red.release.gpu.global.add.u32 [%0], 1;" ::"l"(&g_cnt1) : "memory"); TR(0, 8); }
      __syncwarp();
    }
  };

  if (!conv) {
    publish_rows();
    release_rows();
    const int a = blk - 112, mat = a >> 3, j = a & 7;
    float s[8];
#pragma unroll
    for (int k = 0; k < 8; k++) s[k] = 0.f;
    if (lane < 28) {
      const uint4* src = (mat ? wup : wgate) + j * 28 + lane + (size_t)warp * 224;
#pragma unroll
      for (int hb = 0; hb < 2; hb++) {
        uint4 v[14];
#pragma unroll
        for (int r = 0; r < 14; r++) v[r] = __ldg(src + (size_t)(hb * 14 + r) * 16 * 224);
#pragma unroll
        for (int r = 0; r < 14; r++) {
          s[0] += bf_lo(v[r].x); s[1] += bf_hi(v[r].x); s[2] += bf_lo(v[r].y); s[3] += bf_hi(v[r].y);
          s[4] += bf_lo(v[r].z); s[5] += bf_hi(v[r].z); s[6] += bf_lo(v[r].w); s[7] += bf_hi(v[r].w);
        }
      }
      float4* red = (float4*)(sm + A_STG + warp * 896 + lane * 32);
      red[0] = make_float4(s[0], s[1], s[2], s[3]); red[1] = make_float4(s[4], s[5], s[6], s[7]);
    }
    bar_sync(5, 512);
    if (tid < 224) {
      float t = 0.f;
#pragma unroll
      for (int w = 0; w < 16; w++) t += *(const float*)(sm + A_STG + w * 896 + tid * 4);
      const float hi = rbf(t), mid = rbf(t - hi), lo = rbf(t - hi - mid);
      const int q = tid / 112, n = tid % 112 + 112 * mat;
      __nv_bfloat16* dst = (__nv_bfloat16*)(g_cimg + (j * 2 + q) * 224 + (n >> 3) * 8) + (n & 7);
      dst[0] = __float2bfloat16_rn(hi); dst[8] = __float2bfloat16_rn(mid); dst[16] = __float2bfloat16_rn(lo);
#pragma unroll
      for (int k = 3; k < 8; k++) dst[8 * k] = __float2bfloat16_rn(0.f);
    }
    if (tid == 320) TR(0, 10);
    return;
  }

  const int g = lane >> 2, t = lane & 3;
  const int wr = (wq + wg) & 3;
  uint4 wv[6];
  auto w_src = [&](int i) -> const uint4* {
    if (i < 4) return (blk < 56 ? wgate : wup) + (blk % 56) * 4 + (lane & 3) + (size_t)(i * 128 + warp * 8 + (lane >> 2)) * 224;
    const int it = warp + 16 * (i - 4);
    return wdown + (size_t)(blk * 16 + (it / 14) * 8 + (lane >> 2)) * 56 + (it % 14) * 4 + (lane & 3);
  };
  auto w_on = [&](int i) { return i == 3 ? warp < 8 : i == 5 ? warp < 12 : true; };
  {
    const uint32_t stg = cb + A_STG + wq * 4352;
    const float dt = rbf(expf(__uint_as_float(ldt << 16)));
    float lr[2], li[2];
    cf bq[2], b0[2], b4[2];
    uint32_t bf[48];
#pragma unroll
    for (int m = 0; m < 2; m++) {
      lr[m] = dt * (m ? bf_hi(prm[0]) : bf_lo(prm[0]));
      li[m] = dt * (m ? bf_hi(prm[1]) : bf_lo(prm[1]));
    }
    {
      cf b[2], z[2];
#pragma unroll
      for (int m = 0; m < 2; m++) {
        cf db, c;
        db.x = dt * (m ? bf_hi(prm[2]) : bf_lo(prm[2])); db.y = -dt * (m ? bf_hi(prm[3]) : bf_lo(prm[3]));
        c.x = m ? bf_hi(prm[4]) : bf_lo(prm[4]); c.y = -(m ? bf_hi(prm[5]) : bf_lo(prm[5]));
        b[m] = cmul(c, db);
        z[m] = cexp_l(lr[m], -li[m], 1.f);
        bq[m] = cexp_l(lr[m], -li[m], 256.f);
      }
#pragma unroll
      for (int i = 0; i < 8; i++) {
        sts64(stg + i * 272 + lane * 8, pack_bf16(b[0].x, b[0].y), pack_bf16(b[1].x, b[1].y));
        if (!(i & 1)) {
          cf e0 = cmul(b[0], bq[0]), e1 = cmul(b[1], bq[1]);
          sts64(stg + (8 + i / 2) * 272 + lane * 8, pack_bf16(e0.x, e0.y), pack_bf16(e1.x, e1.y));
          if (i == 0) { b0[0] = e0; b0[1] = e1; }
          if (i == 4) { b4[0] = e0; b4[1] = e1; }
        }
        if (i < 7) { b[0] = cmul(b[0], z[0]); b[1] = cmul(b[1], z[1]); }
        if (i == 1) publish_rows();
      }
#pragma unroll
      for (int i = 0; i < 7; i++) {
        b0[0] = cmul(b0[0], bq[0]); b0[1] = cmul(b0[1], bq[1]);
        sts64(stg + (i < 2 ? 12 + 2 * i : i - 2) * 272 + lane * 8, pack_bf16(b0[0].x, b0[0].y), pack_bf16(b0[1].x, b0[1].y));
        if (i < 2) {
          b4[0] = cmul(b4[0], bq[0]); b4[1] = cmul(b4[1], bq[1]);
          sts64(stg + (13 + 2 * i) * 272 + lane * 8, pack_bf16(b4[0].x, b4[0].y), pack_bf16(b4[1].x, b4[1].y));
        }
        if (i == 1) {
          __syncwarp();
#pragma unroll
          for (int n = 0; n < 2; n++)
#pragma unroll
            for (int k2 = 0; k2 < 4; k2++) ldsm4(bf + n * 16 + k2 * 4, stg + (n * 8 + (lane & 7)) * 272 + k2 * 64 + (lane >> 3) * 16);
          __syncwarp();
        }
      }
    }
    __syncwarp();
#pragma unroll
    for (int k2 = 0; k2 < 4; k2++) ldsm4(bf + 32 + k2 * 4, stg + (lane & 7) * 272 + k2 * 64 + (lane >> 3) * 16);
    release_rows();
    if (!(lane & 1)) {
#pragma unroll
      for (int i = 0; i < 6; i++) if (w_on(i)) asm volatile("prefetch.global.L2 [%0];" ::"l"(w_src(i)));
    }
    if (tid == 320) TR(0, 16);
    float c[6][4];
#pragma unroll
    for (int i = 0; i < 6; i++) { c[i][0] = 0.f; c[i][1] = 0.f; c[i][2] = 0.f; c[i][3] = 0.f; }
    cf p[2], v[2];
    p[0] = cexp_l(lr[0], li[0], 8.f); p[1] = cexp_l(lr[1], li[1], 8.f);
    v[0].x = 1.f; v[0].y = 0.f; v[1] = v[0];
#pragma unroll
    for (int mt = 0; mt < 2; mt++) {
      __syncwarp();
#pragma unroll
      for (int i = 0; i < 16; i++) {
        sts64(stg + i * 272 + lane * 8, pack_bf16(v[0].x, v[0].y), pack_bf16(v[1].x, v[1].y));
        if (mt == 0 && i == 0) { v[0] = p[0]; v[1] = p[1]; }
        else if (mt == 0 || i < 15) { v[0] = cmul(v[0], p[0]); v[1] = cmul(v[1], p[1]); }
      }
      __syncwarp();
      if (mt == 1 && tid == 160) {
        const uint32_t tgt = lds32(ep_addr) * 128u;
        uint32_t cv; int it = 0;
        do { asm volatile("ld.acquire.gpu.global.u32 %0, [%1];" : "=r"(cv) : "l"(&g_cnt1) : "memory"); } while ((int)(cv - tgt) < 0 && ++it < 200000);
        asm volatile("fence.proxy.async;" ::: "memory");
        TR(0, 9);
        mbar_expect(bar_rec, 32768);
        for (int c2 = 0; c2 < 4; c2++) bulk_ld(sb + c2 * A_CH + A_REC, g_ux + (size_t)(blk * 4 + c2) * 512, 8192, bar_rec);
      }
#pragma unroll
      for (int ks = 0; ks < 8; ks++) {
        uint32_t a[4];
        ldsm4(a, stg + (lane & 15) * 272 + ks * 32 + (lane >> 4) * 16);
#pragma unroll
        for (int n = 0; n < 3; n++) mma16816(c[n * 2 + mt], a, bf[n * 16 + ks * 2], bf[n * 16 + ks * 2 + 1]);
      }
    }
    __syncwarp();
#pragma unroll
    for (int i = 0; i < 6; i++)
      sts128(stg + i * 512 + lane * 16, __float_as_uint(c[i][0]), __float_as_uint(c[i][1]), __float_as_uint(c[i][2]), __float_as_uint(c[i][3]));
#pragma unroll
    for (int i = 0; i < 6; i++) if (w_on(i)) wv[i] = __ldg(w_src(i));
    bar_sync(1 + wg, 128);
    if (tid == 320) TR(0, 2);
#pragma unroll
    for (int rep = 0; rep < 2; rep++) {
      const int qd = rep ? 2 + wr : 3 - wr;
      if (rep == 0 || wr >= 2) {
        float s[4] = {0.f, 0.f, 0.f, 0.f};
#pragma unroll
        for (int w = 0; w < 4; w++) {
          uint4 u4 = lds128(cb + A_STG + w * 4352 + qd * 512 + lane * 16);
          s[0] += __uint_as_float(u4.x); s[1] += __uint_as_float(u4.y); s[2] += __uint_as_float(u4.z); s[3] += __uint_as_float(u4.w);
        }
#pragma unroll
        for (int hf = 0; hf < 2; hf++) {
          const int j = (qd & 1) * 16 + g + 8 * hf;
          const uint32_t pk = pack_bf16(s[2 * hf + 1], s[2 * hf]);
          const uint32_t v0 = pk >> 16, v1 = pk & 0xFFFFu, v00 = v0 * 0x10001u;
          if (rep == 1) {
            if (t < 2) {
#pragma unroll
              for (int e = 0; e < 2; e++) {
                const int lam = 128 + 32 * (2 * t + e) + j, mu = lam >> 1;
                const uint32_t val = e ? v1 : v0;
                uint32_t a = cb + ((lam & 1) ? A_R3B : A_R3A) + mu * 4;
                if (lam == 128) { a = cb + A_R2A + 128 * 4; sts32(cb + A_K1024, val << 16); }
                sts16(a, val); sts16(a + 6, val);
              }
            } else if (t == 2 && j == 0) { sts16(cb + A_R3A + 128 * 4, v0); }
          } else if (qd < 2) {
            const uint32_t a = cb + A_R1 + (62 + 8 * j + 2 * t) * 4;
            sts16(a, v0); sts32(a + 4, pk); sts16(a + 10, v1);
          } else if (t < 2) {
            const int L = 256 + 8 * j + 4 * t;
            const uint32_t a = cb + A_R1 + (62 + L) * 4;
            if (L > 256) { sts16(a - 4, v0); sts32(a, v00); } else sts16(a, v0);
            sts32(a + 4, v00); sts32(a + 8, pk); sts16(a + 14, v1);
          } else {
            const int mu = 64 + 32 * (t - 2) + j;
            if (mu == 64) {
              const uint32_t a = cb + A_R1 + (62 + 512) * 4;
              sts16(a - 4, v0); sts32(a, v00); sts32(a + 4, v00); sts32(a + 8, v00); sts16(a + 14, v0);
            } else { sts16(cb + A_R2A + mu * 4, v0); sts16(cb + A_R2A + mu * 4 + 6, v0); }
            sts16(cb + A_R2B + mu * 4, v1); sts16(cb + A_R2B + mu * 4 + 6, v1);
          }
        }
      }
    }
  }
  {
    const int ngg = (blk % 56) * 4 + (lane & 3), j = ngg / 28, q = (ngg % 28) / 14, ng = ngg % 14 + (blk < 56 ? 0 : 14);
    uint4* dst = g_wimg + (size_t)j * 37632 + q * 14 * 896 + ng * 32 + (warp >> 2) * 896 + (warp & 3) * 8 + (lane >> 2);
#pragma unroll
    for (int i = 0; i < 4; i++) if (w_on(i)) dst[i * 4 * 896] = wv[i];
#pragma unroll
    for (int i = 4; i < 6; i++) {
      const int it = warp + 16 * (i - 4), n2 = (it % 14) * 4 + (lane & 3), k = (blk % 7) * 16 + (it / 14) * 8 + (lane >> 2);
      if (w_on(i)) g_wimg[(size_t)(blk / 14) * 37632 + 25088 + ((n2 / 7) * 2 + (blk / 7) % 2) * 784 + (n2 % 7) * 112 + k] = wv[i];
    }
  }
  if (tid == 320) TR(0, 3);

  const int bk = wr * 32 + lane;
  uint32_t xt[8], ud[8];
  {
    mbar_wait(bar_rec, 0);
    if (tid == 320) TR(0, 4);
    uint4 r[4];
#pragma unroll
    for (int i = 0; i < 4; i++) r[i] = lds128(cb + A_REC + bk * 64 + ((i ^ (bk >> 1)) & 3) * 16);
    const uint32_t ua = cb + A_UB + ((2 * bk) & 7) * 656 + ((bk >> 2) + 9) * 16;
    sts128(ua, r[0].x, r[1].x, r[2].x, r[3].x);
    sts128(ua + 656, r[0].y, r[1].y, r[2].y, r[3].y);
    if (bk <= 96) {
      const bool neg = bk == 96;
      const int bp = neg ? -1 : bk;
      uint32_t h[4];
      h[0] = lds32(cb + A_REC + ((bp - 1) & 127) * 64 + ((2 ^ ((bp - 1) >> 1)) & 3) * 16 + 4);
      h[1] = lds32(cb + A_REC + ((bp - 1) & 127) * 64 + ((3 ^ ((bp - 1) >> 1)) & 3) * 16 + 4);
      h[2] = lds32(cb + A_REC + (bp + 1) * 64 + ((0 ^ ((bp + 1) >> 1)) & 3) * 16);
      h[3] = lds32(cb + A_REC + (bp + 1) * 64 + ((1 ^ ((bp + 1) >> 1)) & 3) * 16);
      if (bp <= 0) { h[0] = 0; h[1] = 0; }
      const uint32_t wd[12] = {h[0], h[1], neg ? 0 : r[0].x, neg ? 0 : r[1].x, neg ? 0 : r[2].x, neg ? 0 : r[3].x,
                               neg ? 0 : r[0].y, neg ? 0 : r[1].y, neg ? 0 : r[2].y, neg ? 0 : r[3].y, h[2], h[3]};
      float P[25];
      P[0] = 0.f;
#pragma unroll
      for (int i = 0; i < 12; i++) { P[2 * i + 1] = P[2 * i] + bf_lo(wd[i]); P[2 * i + 2] = P[2 * i + 1] + bf_hi(wd[i]); }
#define WIN(i, hw) (P[(i) + 5 + (hw)] - P[(i) + 4 - (hw)])
#define WPK(i, hw) pack_bf16(WIN(i, hw), WIN((i) + 1, hw))
      const int tp = 2 * bp;
      const uint32_t a3 = cb + A_W3 + (tp + 64) * 16 + 8, a5 = cb + A_W5 + (tp + 64) * 16;
      if (!neg) sts64(a3, WPK(0, 1), WPK(2, 1));
      if (!neg) sts128(a3 + 8, WPK(4, 1), WPK(6, 1), WPK(8, 1), WPK(10, 1));
      sts64(a3 + 24, WPK(12, 1), WPK(14, 1));
      sts128(a5, WPK(0, 2), WPK(2, 2), WPK(4, 2), WPK(6, 2));
      sts128(a5 + 16, WPK(8, 2), WPK(10, 2), WPK(12, 2), WPK(14, 2));
      if (bp < 64) {
        if (!neg) sts128(cb + A_W7 + 1024 + bp * 16, WPK(0, 3), WPK(2, 3), WPK(4, 3), WPK(6, 3));
        if (bp < 63) {
          sts128(cb + A_W7 + (bp + 1) * 16, WPK(8, 3), WPK(10, 3), WPK(12, 3), WPK(14, 3));
          sts128(cb + A_W9 + (bp + 1) * 16, WPK(0, 4), WPK(2, 4), WPK(4, 4), WPK(6, 4));
          sts128(cb + A_W9 + 1024 + (bp + 1) * 16, WPK(8, 4), WPK(10, 4), WPK(12, 4), WPK(14, 4));
        }
        if (!neg) {
#define VPK(i) pack_bf16(P[(i) + 2] - P[i], P[(i) + 3] - P[(i) + 1])
          sts128(cb + A_V + bp * 32, VPK(0), VPK(2), VPK(4), VPK(6));
          sts128(cb + A_V + bp * 32 + 16, VPK(8), VPK(10), VPK(12), VPK(14));
        }
      }
    }
  }
  asm volatile("fence.proxy.async.shared::cta;" ::: "memory");
  bar_sync(1 + wg, 128);
  if (tid == 320) TR(0, 5);

  {
    const uint32_t cbu = __shfl_sync(~0u, cb, 0);
    const uint32_t blo_k = ((cbu & 0x3FFFF) >> 4) | (41u << 16);
    const uint32_t blo_n = ((cbu & 0x3FFFF) >> 4) | (8u << 16);
    const uint32_t tb = cb + (16 * wq + g - 2 * t) * 4;
    float y1[16], y2[12], y3[8];
    const uint32_t dk16 = __ldg(dskip + ch);
    uint32_t qa[32], qb[32];
    const uint32_t t1 = tb + A_R1 + (62 - 48) * 4;
    load_quads<4>(qa, tb + A_R3A + 17 * 4); load_quads<4>(qa + 16, tb + A_R3B + 16 * 4);
    wg_fence();
    s3_steps<0, 4, A_W9, 1>(y3, qa, blo_n); s3_steps<0, 4, A_W7, 0>(y3, qa + 16, blo_n);
    wg_commit();
    load_quads<8>(qb, tb + A_R2A + 16 * 4);
    wg_fence(); s2_steps<0, 8, A_W5, 1>(y2, qb, blo_n); wg_commit();
    wg_wait<1>(); load_quads<8>(qa, tb + A_R2B + 16 * 4);
    wg_fence(); s2_steps<0, 8, A_W3, 0>(y2, qa, blo_n); wg_commit();
    wg_wait<1>(); load_quads<8>(qb, t1);
    wg_fence(); f1_steps<0, 8>(y1, qb, blo_k); wg_commit();
    wg_wait<1>(); load_quads<8>(qa, t1 + 8 * 64);
    wg_fence(); f1_steps<8, 8>(y1, qa, blo_k); wg_commit();
    reg_fence(y2); reg_fence(y3);
    if (tid == 320) TR(0, 18);
    {
      const float k1024 = __uint_as_float(lds32(cb + A_K1024));
#pragma unroll
      for (int i = 0; i < 2; i++)
#pragma unroll
        for (int hf = 0; hf < 2; hf++) {
          const int idx = 16 * (16 * wq + g + 8 * hf) + 8 * i + 2 * t;
          const uint32_t vv = lds32(cb + A_V + idx * 2);
          sts64(cb + A_Y3 + (idx + 4 * (idx >> 6)) * 4, __float_as_uint(fmaf(k1024, bf_lo(vv), y3[4 * i + 2 * hf])),
                __float_as_uint(fmaf(k1024, bf_hi(vv), y3[4 * i + 2 * hf + 1])));
        }
#pragma unroll
      for (int i = 0; i < 3; i++)
#pragma unroll
        for (int hf = 0; hf < 2; hf++) {
          const int idx = 512 * i + 8 * (16 * wq + g + 8 * hf) + 2 * t;
          sts64(cb + A_Y2 + (idx + 4 * (idx >> 6)) * 4, __float_as_uint(y2[4 * i + 2 * hf]), __float_as_uint(y2[4 * i + 2 * hf + 1]));
        }
    }
    wg_wait<1>(); load_quads<8>(qb, t1 + 16 * 64);
    wg_fence(); f1_steps<16, 8>(y1, qb, blo_k); wg_commit();
    wg_wait<1>(); load_quads<8>(qa, t1 + 24 * 64);
    wg_fence(); f1_steps<24, 8>(y1, qa, blo_k); wg_commit();
    wg_wait<1>(); load_quads<5>(qb, t1 + 32 * 64);
    wg_fence(); f1_steps<32, 5>(y1, qb, blo_k); wg_commit();
    bar_sync(1 + wg, 128);
    float ex[12];
#pragma unroll
    for (int i = 1; i < 4; i++)
#pragma unroll
      for (int k = 0; k < 4; k++) {
        const int aa = 8 * i + 2 * t + (k & 1), b = 16 * wq + g + 8 * (k >> 1);
        float e = __uint_as_float(lds32(cb + A_Y2 + ((aa - 8) * 68 + b) * 4));
        if (i >= 2) e += __uint_as_float(lds32(cb + A_Y3 + ((aa - 16) * 68 + b) * 4));
        ex[4 * (i - 1) + k] = e;
      }
    {
      const uint32_t dk = dk16 * 0x10001u;
#pragma unroll
      for (int i = 0; i < 4; i++) {
        const uint4 r = lds128(cb + A_REC + bk * 64 + ((i ^ (bk >> 1)) & 3) * 16);
        ud[i] = hmul2_bf(r.x, dk); ud[4 + i] = hmul2_bf(r.y, dk); xt[i] = r.z; xt[4 + i] = r.w;
      }
    }
    wg_wait<0>();
    reg_fence(y1);
    if (tid == 320) TR(0, 6);
#pragma unroll
    for (int i = 0; i < 12; i++) y1[4 + i] += ex[i];
#pragma unroll
    for (int i = 0; i < 2; i++) {
      const int mi = lane >> 3, aa = 8 * (2 * i + (mi >> 1)) + (lane & 7);
      asm volatile("stmatrix.sync.aligned.m8n8.x4.trans.shared.b16 [%0], {%1,%2,%3,%4};"
                   ::"r"(cb + A_YB + aa * 128 + (((2 * wq + (mi & 1)) ^ (lane & 7)) << 4)),
                     "r"(pack_bf16(y1[8 * i], y1[8 * i + 1])), "r"(pack_bf16(y1[8 * i + 2], y1[8 * i + 3])),
                     "r"(pack_bf16(y1[8 * i + 4], y1[8 * i + 5])), "r"(pack_bf16(y1[8 * i + 6], y1[8 * i + 7])) : "memory");
    }
  }
  bar_sync(1 + wg, 128);
#pragma unroll
  for (int c = 0; c < 2; c++) {
    const int tau = 2 * bk + c, r = ch & 7;
    const uint4 y = lds128(cb + A_YB + (tau >> 3) * 128 + (((tau ^ (tau >> 3)) & 7) << 4));
    g_himg[(size_t)(tau >> 4) * 7168 + (ch >> 3) * 128 + ((tau >> 3) & 1) * 64 + r * 8 + ((tau & 7) ^ r)] =
        make_uint4(hadd2_bf(xt[4 * c], hadd2_bf(y.x, ud[4 * c])), hadd2_bf(xt[4 * c + 1], hadd2_bf(y.y, ud[4 * c + 1])),
                   hadd2_bf(xt[4 * c + 2], hadd2_bf(y.z, ud[4 * c + 2])), hadd2_bf(xt[4 * c + 3], hadd2_bf(y.w, ud[4 * c + 3])));
  }
  if (tid == 320) TR(0, 7);
}

constexpr int B_SA = 0, B_RING = 114688, B_SLOT = 14848, B_NSLOT = 7;
constexpr int B_CS = B_RING + B_NSLOT * B_SLOT;
constexpr int B_RED = B_CS + 7168;
constexpr int B_BAR = B_RED + 256;
constexpr int B_SMEM = B_BAR + 1024, A_SMEM = 4 * A_CH + 64;

__device__ __forceinline__ uint32_t mapa(uint32_t a, uint32_t r) { uint32_t o; asm("mapa.shared::cluster.u32 %0, %1, %2;" : "=r"(o) : "r"(a), "r"(r)); return o; }
template <class T> __device__ __forceinline__ T* pin(T* p) { asm volatile("" : "+l"(p)); return p; }
__device__ __forceinline__ uint32_t pin(uint32_t v) { asm volatile("" : "+r"(v)); return v; }
template <int Q, int ST>
__device__ __forceinline__ void g1_stage(float (&acc)[116], uint32_t alo, uint32_t blo, uint32_t bar_full, uint32_t bar_h) {
  constexpr int s = Q * 14 + ST, sl = s % B_NSLOT;
  if (Q == 0) mbar_wait(bar_h + 8 * ST, 0);
  mbar_wait(bar_full + 8 * sl, (s / B_NSLOT) & 1);
  wg_fence();
  if (Q == 0) {
    wgmma_ss232<(2 * ST) * 256, 0x40000080u, (sl * B_SLOT) / 16, 32, ST != 0>(acc, alo, blo);
    wgmma_ss232<(2 * ST + 1) * 256, 0x40000080u, (sl * B_SLOT + 256) / 16, 32, 1>(acc, alo, blo);
  } else {
    wgmma_ss224<(2 * ST) * 256, 0x40000080u, (sl * B_SLOT) / 16, 32, ST != 0>(*(float(*)[112])acc, alo, blo);
    wgmma_ss224<(2 * ST + 1) * 256, 0x40000080u, (sl * B_SLOT + 256) / 16, 32, 1>(*(float(*)[112])acc, alo, blo);
  }
}

__global__ void __launch_bounds__(512, 1)
k_front(const __nv_bfloat16* __restrict__ x, const uint32_t* __restrict__ are, const uint32_t* __restrict__ aim,
        const uint32_t* __restrict__ bre, const uint32_t* __restrict__ bim, const uint32_t* __restrict__ cre,
        const uint32_t* __restrict__ cim, const unsigned short* __restrict__ logdt, const unsigned short* __restrict__ dskip,
        const uint4* __restrict__ wgate, const uint4* __restrict__ wup, const uint4* __restrict__ wdown) {
  extern __shared__ __align__(1024) unsigned char sm[];
  const uint32_t bar_rec = s2u(sm) + 4 * A_CH;
  if (threadIdx.x == 320) TR(0, 0);
  asm volatile("griddepcontrol.launch_dependents;");
  if (threadIdx.x == 160) { mbar_init(bar_rec, 1); asm volatile("fence.mbarrier_init.release.cluster;" ::: "memory"); }
  phase_a(sm, bar_rec, bar_rec + 8, x, are, aim, bre, bim, cre, cim, logdt, dskip, wgate, wup, wdown);
}

__global__ void __cluster_dims__(2, 1, 1) __launch_bounds__(384, 1) k_ffn(__nv_bfloat16* __restrict__ out) {
  extern __shared__ __align__(1024) unsigned char sm[];
  const uint32_t sb = s2u(sm);
  const int tid = threadIdx.x, warp = __shfl_sync(~0u, tid >> 5, 0), wg = warp >> 2, lane = tid & 31;
  const uint32_t bar_full = sb + B_BAR, bar_empty = bar_full + 64, bar_h = bar_full + 128, bar_cs = bar_full + 240,
                 bar_hh = bar_full + 304, bar_afree = bar_full + 336, bar_out = bar_full + 352;
  if (tid == 0) {
    TR(1, 0);
    for (int i = 0; i < B_NSLOT; i++) { mbar_init(bar_full + 8 * i, 1); mbar_init(bar_empty + 8 * i, 2); }
    asm volatile("fence.mbarrier_init.release.cluster;" ::: "memory");
  } else if (tid == 32) {
    for (int i = 0; i < 14; i++) mbar_init(bar_h + 8 * i, 1);
    asm volatile("fence.mbarrier_init.release.cluster;" ::: "memory");
  } else if (tid == 64) {
    mbar_init(bar_cs, 1);
    for (int i = 0; i < 4; i++) { mbar_init(bar_hh + 8 * i, 1); mbar_expect(bar_hh + 8 * i, 14336); }
    mbar_init(bar_afree, 4); mbar_init(bar_afree + 8, 2);
    for (int i = 0; i < 6; i++) mbar_init(bar_out + 8 * i, 128);
    asm volatile("fence.mbarrier_init.release.cluster;" ::: "memory");
  } else if (tid >= 128 && tid < 352) {
    sts128(sb + B_RING + ((tid - 128) >> 5) * B_SLOT + 14336 + (tid & 31) * 16, 0x3F803F80u, 0x3F803F80u, 0x3F803F80u, 0x3F803F80u);
  }
  asm volatile("fence.proxy.async.shared::cta;" ::: "memory");
  __syncthreads();
  asm volatile("barrier.cluster.arrive.relaxed.aligned;" ::: "memory");
  const int rank = blockIdx.x & 1, rt = blockIdx.x >> 3, j = blockIdx.x & 7, p = j >> 1, cg = 4 * rank + p;
  const int wq = warp & 3, t128 = tid & 127, g = lane >> 2, t = lane & 3;
  uint32_t ep, tag;
  auto load_ep = [&]() { asm volatile("ld.relaxed.gpu.global.u32 %0, [%1];" : "=r"(ep) : "l"(&g_cnt1) : "memory"); };
  auto a_slot = [&](int i, int own) { return B_SA + (i + (i >= own)) * 14336; };
  auto out_addr = [&](int cc, int w) { return sb + a_slot((cc & 2) + w, cg) + (cc & 1) * 7168; };
  auto in_cta = [&](int q) { return rt * 8 + ((p + 3 - q) & 3) * 2 + rank; };
  auto in_src = [&](int q, int cw) { return g_part + (size_t)(in_cta(q) * 3 + q) * 896 + cw * 112; };
  auto in_bad = [&](uint32_t (&in)[14]) { return ((in[3] ^ tag) | (in[7] ^ tag) | (in[11] ^ tag) | (in[13] ^ tag)) & 0x10000u; };
  auto in_load = [&](uint32_t (&in)[14], const uint4* gs) {
#pragma unroll
    for (int i = 0; i < 3; i++) ld128(gs + i * 32, in + 4 * i);
    asm volatile("{\n.reg .b64 v;\nld.relaxed.gpu.global.b64 v, [%2];\nmov.b64 {%0, %1}, v;\n}"
                 : "=r"(in[12]), "=r"(in[13]) : "l"((const uint2*)(gs + 96) - lane) : "memory");
  };
  auto in_check = [&](uint32_t (&in)[14], int q, int cw) {
    int it = 0;
    while (in_bad(in) && ++it < 400000) in_load(in, pin(in_src(q, cw) + lane));
  };

  if (wg == 2) {
    asm volatile("setmaxnreg.dec.sync.aligned.u32 40;");
    asm volatile("barrier.cluster.wait.aligned;" ::: "memory");
    asm volatile("griddepcontrol.wait;" ::: "memory");
    if (warp == 8) {
      if (lane == 0) TR(1, 1);
      const char* wsrc = (const char*)g_wimg + (size_t)j * 602112;
      const char* hsrc = (const char*)g_himg + (size_t)rt * 114688 + rank * 4096;
#pragma unroll
      for (int s = 0; s < 28; s++) {
        if (s < B_NSLOT) bulk_ld_mc_elect<4096>(sb + B_SA + s * 8192 + rank * 4096, hsrc + s * 8192, bar_h + 8 * s);
        if (s == B_NSLOT) {
#pragma unroll
          for (int i = 7; i < 14; i++) bulk_ld_mc_elect<4096>(sb + B_SA + i * 8192 + rank * 4096, hsrc + i * 8192, bar_h + 8 * i);
          bulk_ld_elect<7168>(sb + B_CS, g_cimg + j * 448, bar_cs);
        }
        if (s >= B_NSLOT) mbar_wait(bar_empty + 8 * (s % B_NSLOT), (s / B_NSLOT + 1) & 1);
        bulk_ld_elect<14336>(sb + B_RING + (s % B_NSLOT) * B_SLOT, wsrc + s * 14336, bar_full + 8 * (s % B_NSLOT));
      }
      const char* dsrc[2] = {wsrc + 401408 + rank * 100352, (const char*)g_wimg + (size_t)(j ^ 1) * 602112 + 401408 + rank * 100352};
#pragma unroll
      for (int i = 0; i < 16; i++) {
        const int ci = i < 3 ? 0 : i < 6 ? 1 : i < 8 ? i - 6 : i < 12 ? 2 : 3;
        const int kp = i < 3 ? i : i < 6 ? i - 3 : i < 8 ? 3 : (i & 3);
        mbar_wait(bar_empty + 8 * (i % B_NSLOT), (i / B_NSLOT + 1) & 1);
        bulk_ld_elect<12544>(sb + B_RING + (i % B_NSLOT) * B_SLOT, dsrc[kp >> 1] + ((p + 1 + ci) & 3) * 25088 + (kp & 1) * 12544, bar_full + 8 * (i % B_NSLOT));
      }
    } else if (warp >= 10) {
      const int t64 = tid - 320;
      load_ep();
      const int r = (lane >> 1) & 7, c = (j & 3) * 2 + (lane & 1);
      const uint32_t src = sb + B_SA + (t64 >> 4) * 2048 + (j >> 2) * 1024 + r * 128 + ((c ^ r) << 4);
      float a[16];
#pragma unroll
      for (int k = 0; k < 16; k++) a[k] = 0.f;
#pragma unroll 1
      for (int i = 0; i < 14; i++) {
        mbar_wait(bar_h + 8 * i, 0);
        uint4 v = lds128(src + i * 8192);
        float e[8] = {bf_lo(v.x), bf_hi(v.x), bf_lo(v.y), bf_hi(v.y), bf_lo(v.z), bf_hi(v.z), bf_lo(v.w), bf_hi(v.w)};
#pragma unroll
        for (int k = 0; k < 8; k++) { a[2 * k] += e[k]; a[2 * k + 1] = fmaf(e[k], e[k], a[2 * k + 1]); }
        __nanosleep(160);
      }
      __syncwarp();
      if (lane == 0) { asm volatile("mbarrier.arrive.shared::cluster.b64 _, [%0];" ::"r"(mapa(bar_afree, rank ^ 1)) : "memory"); }
#pragma unroll
      for (int rd = 0; rd < 4; rd++) {
        const int n = 8 >> rd;
        const bool up = lane & (2 * n);
#pragma unroll
        for (int k = 0; k < 8; k++) {
          if (k < n) {
            float keep = up ? a[k + n] : a[k], give = up ? a[k] : a[k + n];
            a[k] = keep + __shfl_xor_sync(~0u, give, 2 * n);
          }
        }
      }
      float* red = (float*)(sm + B_RED);
      red[(warp & 1) * 32 + (lane & 1) * 16 + (lane >> 1)] = a[0];
      bar_sync(1, 64);
      if (t64 < 16) {
        float mean = (red[2 * t64] + red[32 + 2 * t64]) * (1.f / DM);
        float var = fmaxf(fmaf(-mean, mean, (red[2 * t64 + 1] + red[33 + 2 * t64]) * (1.f / DM)), 0.f);
        float rs = __frcp_rn(rbf(__fsqrt_rn(rbf(rbf(var) + 1e-5f))));
        asm volatile("st.relaxed.gpu.global.u32 [%0], %1;"
                     ::"l"(g_stat2 + rt * 128 + j * 16 + t64), "r"((__float_as_uint(rs * rs) & ~1u) | ((ep >> 7) & 1u)) : "memory");
      }
      if (t64 == 0) TR(1, 2);
      if (lane == 0) {
        const int w = warp & 1;
        for (int cc = 0; cc < 2; cc++) {
          mbar_wait(bar_out + 8 * (cc * 2 + w), 0);
          asm volatile("cp.async.bulk.global.shared::cta.bulk_group [%0], [%1], 7168;"
                       ::"l"(g_part + (size_t)(blockIdx.x * 3 + cc) * 896 + w * 448), "r"(out_addr(cc, w)) : "memory");
          if (w) TR(1, 27 + cc);
        }
        asm volatile("cp.async.bulk.commit_group;" ::: "memory");
        asm volatile("cp.async.bulk.wait_group 0;" ::: "memory");
      }
    }
  } else {
    asm volatile("setmaxnreg.inc.sync.aligned.u32 232;");
    asm volatile("barrier.cluster.wait.aligned;" ::: "memory");
    uint32_t hh[56];
    const bool relt = t128 == 0;
    auto release = [&](int sl) { if (relt) mbar_arrive(bar_empty + 8 * sl); };
    auto send_hh = [&](int q) {
      const uint32_t da = mapa(sb + a_slot(2 * q + wg, cg ^ 4) + t128 * 16, rank ^ 1), db = mapa(bar_hh + 8 * (2 * q + wg), rank ^ 1);
#pragma unroll
      for (int i = 0; i < 7; i++)
        asm volatile("st.async.weak.shared::cluster.mbarrier::complete_tx::bytes.v4.b32 [%0], {%1, %2, %3, %4}, [%5];"
                     ::"r"(da + i * 2048), "r"(hh[28 * q + 4 * i]), "r"(hh[28 * q + 4 * i + 1]),
                       "r"(hh[28 * q + 4 * i + 2]), "r"(hh[28 * q + 4 * i + 3]), "r"(db) : "memory");
    };
    uint32_t alo = ((sb + B_SA + wg * 1024) & 0x3FFFF) >> 4;
    uint32_t blo = (((sb + B_RING) & 0x3FFFF) >> 4) | (8u << 16);
    const uint32_t clo = ((sb + B_CS) & 0x3FFFF) >> 4;
    uint32_t nm0, nm1;
    if (wg == 1) bar_sync(3, 256);
#define G1S(Q, ST) do { if (ST % 7 == 0) { alo = pin(alo); blo = pin(blo); }   \
      g1_stage<Q, ST>(acc, alo, blo, bar_full, bar_h); wg_commit(); \
      if (ST > 0) { wg_wait<1>(); release((Q * 14 + ST - 1) % B_NSLOT); } } while (0)
#define G1HH(Q) do { \
      _Pragma("unroll") \
      for (int i = 0; i < 28; i++) hh[28 * Q + i] = pack_bf16(acc[2 * i] * acc[56 + 2 * i], acc[2 * i + 1] * acc[57 + 2 * i]); \
    } while (0)
    {
      float acc[116];
      G1S(0, 0);
      if (tid == 0) TR(1, 3);
      G1S(0, 1);
      if (wg == 0) asm volatile("bar.arrive 3, 256;" ::: "memory");
      G1S(0, 2); G1S(0, 3); G1S(0, 4); G1S(0, 5); G1S(0, 6); G1S(0, 7); G1S(0, 8); G1S(0, 9); G1S(0, 10); G1S(0, 11); G1S(0, 12);
      G1S(0, 13);
      if (tid == 0) TR(1, 4);
      mbar_wait(bar_cs, 0);
      wg_wait<0>(); reg_fence(acc); release(13 % B_NSLOT);
      {
        const uint32_t msk = t == 0 ? 0xFFFFFFFFu : t == 1 ? 0xFFFFu : 0u;
        const float a = acc[112] * (-1.f / DM), b = acc[114] * (-1.f / DM);
        nm0 = pack_bf16(a, a) & msk; nm1 = pack_bf16(b, b) & msk;
      }
      wg_fence();
      wgmma_rs224<0, 8, 1>(*(float(*)[112])acc, nm0, nm1, 0u, 0u, clo);
      wg_commit(); wg_wait<0>(); reg_fence(acc);
      G1HH(0);
      if (tid == 0) TR(1, 5);
      G1S(1, 0); G1S(1, 1); G1S(1, 2); G1S(1, 3); G1S(1, 4); G1S(1, 5); G1S(1, 6);
      if (relt) asm volatile("mbarrier.arrive.shared::cluster.b64 _, [%0];" ::"r"(mapa(bar_afree, rank ^ 1)) : "memory");
      G1S(1, 7); G1S(1, 8); G1S(1, 9);
      if (relt) asm volatile("mbarrier.arrive.shared::cluster.b64 _, [%0];" ::"r"(mapa(bar_afree + 8, rank ^ 1)) : "memory");
      mbar_wait(bar_afree, 0);
      send_hh(0);
      G1S(1, 10); G1S(1, 11); G1S(1, 12);
      load_ep();
      g1_stage<1, 13>(acc, alo, blo, bar_full, bar_h);
      wgmma_rs224<224, 8, 1>(*(float(*)[112])acc, nm0, nm1, 0u, 0u, clo);
      wg_commit(); wg_wait<1>(); release(26 % B_NSLOT);
      wg_wait<0>(); reg_fence(acc); release(27 % B_NSLOT);
      G1HH(1);
      if (tid == 0) TR(1, 6);
    }
    float accA[28], accB[28];
    uint32_t ph0[28], ph1[28];
    ep = pin(ep >> 7); tag = pin((ep & 1u) << 16);
#define ISSUE(acc, I, a, FIRST) do { \
      constexpr int s_ = 28 + (I), sl_ = s_ % B_NSLOT; \
      if (sl_ == 0) blo = pin(blo); \
      mbar_wait(bar_full + 8 * sl_, (s_ / B_NSLOT) & 1); \
      wg_fence(); \
      wgmma_rs56<(sl_ * B_SLOT + 0 * 256) / 16, 112, !(FIRST)>(acc, (a)[0], (a)[1], (a)[2], (a)[3], blo); \
      wgmma_rs56<(sl_ * B_SLOT + 1 * 256) / 16, 112, 1>(acc, (a)[4], (a)[5], (a)[6], (a)[7], blo); \
      wgmma_rs56<(sl_ * B_SLOT + 2 * 256) / 16, 112, 1>(acc, (a)[8], (a)[9], (a)[10], (a)[11], blo); \
      wgmma_rs56<(sl_ * B_SLOT + 3 * 256) / 16, 112, 1>(acc, (a)[12], (a)[13], (a)[14], (a)[15], blo); \
      wgmma_rs56<(sl_ * B_SLOT + 4 * 256) / 16, 112, 1>(acc, (a)[16], (a)[17], (a)[18], (a)[19], blo); \
      wgmma_rs56<(sl_ * B_SLOT + 5 * 256) / 16, 112, 1>(acc, (a)[20], (a)[21], (a)[22], (a)[23], blo); \
      wgmma_rs56<(sl_ * B_SLOT + 6 * 256) / 16, 112, 1>(acc, (a)[24], (a)[25], (a)[26], (a)[27], blo); \
      wg_commit(); } while (0)
    auto rel = [&](int i) { release((28 + i) % B_NSLOT); };
    auto tg = [&](uint32_t v) { return (v & 0xFFFEFFFFu) | tag; };
    auto send = [&](float (&acc)[28], int cc) {
      reg_fence(acc);
      const uint32_t a = out_addr(cc, wg) + wq * 1792;
#pragma unroll
      for (int q = 0; q < 3; q++)
        sts128(a + q * 512 + lane * 16, pack_bf16(acc[8 * q], acc[8 * q + 1]), pack_bf16(acc[8 * q + 2], acc[8 * q + 3]),
               pack_bf16(acc[8 * q + 4], acc[8 * q + 5]), tg(pack_bf16(acc[8 * q + 6], acc[8 * q + 7])));
      sts64(a + 1536 + lane * 8, pack_bf16(acc[24], acc[25]), tg(pack_bf16(acc[26], acc[27])));
      asm volatile("fence.proxy.async.shared::cta;" ::: "memory");
      mbar_arrive(bar_out + 8 * (cc * 2 + wg));
    };
    auto load_hh = [&](uint32_t (&d)[28], int q) {
      mbar_wait(bar_hh + 8 * (2 * q + wg), 0);
      const uint32_t a = sb + a_slot(2 * q + wg, cg) + t128 * 16;
#pragma unroll
      for (int i = 0; i < 7; i++) {
        const uint4 v = lds128(a + i * 2048);
        d[4 * i] = v.x; d[4 * i + 1] = v.y; d[4 * i + 2] = v.z; d[4 * i + 3] = v.w;
      }
    };
    ISSUE(accA, 0, hh, true);
    mbar_wait(bar_afree + 8, 0);
    send_hh(1);
    ISSUE(accA, 1, hh + 28, false);
    load_hh(ph0, 0);
    wg_wait<1>(); rel(0);
    ISSUE(accA, 2, ph0, false);      wg_wait<1>(); rel(1);
    ISSUE(accB, 3, hh, true);        wg_wait<1>(); rel(2);
    ISSUE(accB, 4, hh + 28, false);  wg_wait<1>(); rel(3);
    ISSUE(accB, 5, ph0, false);
    if (tid == 0) TR(1, 11);
    load_hh(ph1, 1);
    wg_wait<1>(); rel(4);
    ISSUE(accA, 6, ph1, false);      wg_wait<1>(); rel(5);
    ISSUE(accB, 7, ph1, false);      wg_wait<1>(); rel(6); send(accA, 0);
    ISSUE(accA, 8, hh, true);        wg_wait<1>(); rel(7); send(accB, 1);
    if (tid == 0) TR(1, 13);
    ISSUE(accA, 9, hh + 28, false);  wg_wait<1>(); rel(8);
    ISSUE(accA, 10, ph0, false);
    ISSUE(accA, 11, ph1, false);
    const int row = rt * 128 + wg * 64 + wq * 16 + g;
    uint32_t r20, r21;
    asm volatile("ld.relaxed.gpu.global.u32 %0, [%1];" : "=r"(r20) : "l"(g_stat2 + row) : "memory");
    asm volatile("ld.relaxed.gpu.global.u32 %0, [%1];" : "=r"(r21) : "l"(g_stat2 + row + 8) : "memory");
    ISSUE(accB, 12, hh, true);
    wg_wait<1>();
    {
      reg_fence(accA);
      uint4* pd = g_part + (size_t)(blockIdx.x * 3 + 2) * 896 + warp * 112 + lane;
#pragma unroll
      for (int q = 0; q < 3; q++)
        st128(pd + q * 32, pack_bf16(accA[8 * q], accA[8 * q + 1]), pack_bf16(accA[8 * q + 2], accA[8 * q + 3]),
              pack_bf16(accA[8 * q + 4], accA[8 * q + 5]), tg(pack_bf16(accA[8 * q + 6], accA[8 * q + 7])));
      asm volatile("{\n.reg .b64 v;\nmov.b64 v, {%1, %2};\nst.relaxed.gpu.global.b64 [%0], v;\n}"
                   ::"l"((uint2*)(pd + 96) - lane), "r"(pack_bf16(accA[24], accA[25])), "r"(tg(pack_bf16(accA[26], accA[27]))) : "memory");
    }
    if (tid == 0) TR(1, 16);
    ISSUE(accB, 13, hh + 28, false);
    ISSUE(accB, 14, ph0, false);
    uint32_t in0[14], in1[14], in2[14];
    in_load(in0, in_src(0, warp) + lane);
    in_load(in1, in_src(1, warp) + lane);
    ISSUE(accB, 15, ph1, false);
    if (tid == 0) TR(1, 7);
    {
      int it = 0;
      while ((((r20 ^ ep) | (r21 ^ ep)) & 1u) && ++it < 400000) {
        asm volatile("ld.relaxed.gpu.global.u32 %0, [%1];" : "=r"(r20) : "l"(g_stat2 + row) : "memory");
        asm volatile("ld.relaxed.gpu.global.u32 %0, [%1];" : "=r"(r21) : "l"(g_stat2 + row + 8) : "memory");
      }
    }
    wg_wait<1>();
    in_load(in2, in_src(2, warp) + lane);
    in_check(in0, 0, warp); in_check(in1, 1, warp);
#pragma unroll
    for (int i = 0; i < 14; i++) { accA[2 * i] = bf_lo(in0[i]) + bf_lo(in1[i]); accA[2 * i + 1] = bf_hi(in0[i]) + bf_hi(in1[i]); }
    if (tid == 0) TR(1, 12);
    wg_wait<0>();
    reg_fence(accB);
    uint32_t hres[16];
#pragma unroll
    for (int i = 0; i < 4; i++) {
      int qq = lane >> 3, r = lane & 7, kg = 7 * cg + 2 * i + (qq >> 1), c = 2 * wq + (qq & 1);
      if (kg > 55) kg = 55;
      asm volatile("ldmatrix.sync.aligned.m8n8.x4.trans.shared.b16 {%0,%1,%2,%3}, [%4];"
                   : "=r"(hres[4 * i]), "=r"(hres[4 * i + 1]), "=r"(hres[4 * i + 2]), "=r"(hres[4 * i + 3])
                   : "r"(sb + B_SA + kg * 2048 + wg * 1024 + r * 128 + ((c ^ r) << 4)) : "memory");
    }
#pragma unroll
    for (int i = 0; i < 28; i++) accB[i] += accA[i];
    if (tid == 0) TR(1, 9);
    in_check(in2, 2, warp);
#pragma unroll
    for (int i = 0; i < 14; i++) { accB[2 * i] += bf_lo(in2[i]); accB[2 * i + 1] += bf_hi(in2[i]); }
    uint32_t* o0 = (uint32_t*)(out + (size_t)row * DM + 56 * cg + 2 * t);
    uint32_t* o1 = o0 + 8 * DM / 2;
#pragma unroll
    for (int i = 0; i < 7; i++) {
      o0[4 * i] = hadd2_bf(hres[2 * i], pack_bf16(accB[4 * i] * __uint_as_float(r20), accB[4 * i + 1] * __uint_as_float(r20)));
      o1[4 * i] = hadd2_bf(hres[2 * i + 1], pack_bf16(accB[4 * i + 2] * __uint_as_float(r21), accB[4 * i + 3] * __uint_as_float(r21)));
    }
    if (tid == 0) TR(1, 10);
    if (tid == 128) TR(1, 15);
  }
}

extern "C" void kernel_launch(void* const* d_in, const int* in_sizes, int n_in, void* d_out, int out_size) {
  const __nv_bfloat16* x = (const __nv_bfloat16*)d_in[0];
  const __nv_bfloat16 *are = (const __nv_bfloat16*)d_in[1], *aim = (const __nv_bfloat16*)d_in[2], *bre = (const __nv_bfloat16*)d_in[3],
                      *bim = (const __nv_bfloat16*)d_in[4], *cre = (const __nv_bfloat16*)d_in[5], *cim = (const __nv_bfloat16*)d_in[6],
                      *logdt = (const __nv_bfloat16*)d_in[7], *dskip = (const __nv_bfloat16*)d_in[8];
  const __nv_bfloat16 *wg = (const __nv_bfloat16*)d_in[10], *wu = (const __nv_bfloat16*)d_in[11], *wd = (const __nv_bfloat16*)d_in[12];

  static bool init = false;
  if (!init) {
    init = true;
    cudaFuncSetAttribute(k_ffn, cudaFuncAttributeMaxDynamicSharedMemorySize, B_SMEM);
    cudaFuncSetAttribute(k_front, cudaFuncAttributeMaxDynamicSharedMemorySize, A_SMEM);
  }
  cudaStream_t st = cudaStreamPerThread;
  k_front<<<128, 512, A_SMEM, st>>>(
      x, (const uint32_t*)are, (const uint32_t*)aim, (const uint32_t*)bre, (const uint32_t*)bim, (const uint32_t*)cre, (const uint32_t*)cim,
      (const unsigned short*)logdt, (const unsigned short*)dskip, (const uint4*)wg, (const uint4*)wu, (const uint4*)wd);
  cudaLaunchConfig_t cfg = {};
  cfg.gridDim = dim3(128); cfg.blockDim = dim3(384); cfg.dynamicSmemBytes = B_SMEM; cfg.stream = st;
  cudaLaunchAttribute at[1];
  at[0].id = cudaLaunchAttributeProgrammaticStreamSerialization; at[0].val.programmaticStreamSerializationAllowed = 1;
  cfg.attrs = at; cfg.numAttrs = 1;
  cudaLaunchKernelEx(&cfg, k_ffn, (__nv_bfloat16*)d_out);
}
```

```cpp
#include <cuda_runtime.h>
#include <cuda_bf16.h>
#include <cuda_fp16.h>
#include <stdint.h>

constexpr int LSEQ = 2048, DM = 448;

__device__ uint4    g_himg[16 * 114688 / 16];
__device__ uint4    g_cimg[8 * 2 * 224];
__device__ uint32_t g_stat2[LSEQ];
__device__ uint4    g_part[128 * 3 * 896];
__device__ uint4    g_wimg[8 * 602112 / 16];
__device__ uint4    g_ux[DM * 128 * 4];
__device__ unsigned g_cnt1;

#define TR(k, i) do {} while (0)
__device__ __forceinline__ uint32_t s2u(const void* p) { return (uint32_t)__cvta_generic_to_shared(p); }
__device__ __forceinline__ void mbar_init(uint32_t b, int c) { asm volatile("mbarrier.init.shared::cta.b64 [%0], %1;" ::"r"(b), "r"(c)); }
__device__ __forceinline__ void mbar_expect(uint32_t b, int bytes) { asm volatile("mbarrier.arrive.expect_tx.shared::cta.b64 _, [%0], %1;" ::"r"(b), "r"(bytes) : "memory"); }
__device__ __forceinline__ void mbar_arrive(uint32_t b) { asm volatile("mbarrier.arrive.shared::cta.b64 _, [%0];" ::"r"(b) : "memory"); }
__device__ __forceinline__ void mbar_wait(uint32_t b, int ph) {
  asm volatile("{\n.reg .pred p;\n.reg .b32 n;\nmov.b32 n, 0;\nLW:\nmbarrier.try_wait.parity.shared::cta.b64 p, [%0], %1;\n@p bra LD;\n"
               "add.u32 n, n, 1;\nsetp.lt.u32 p, n, 4000000;\n@p bra LW;\ntrap;\nLD:\n}" ::"r"(b), "r"(ph) : "memory");
}
__device__ __forceinline__ bool mbar_test(uint32_t b, int ph) {
  uint32_t ok;
  asm volatile("{\n.reg .pred p;\nmbarrier.test_wait.parity.shared::cta.b64 p, [%1], %2;\nselp.u32 %0, 1, 0, p;\n}" : "=r"(ok) : "r"(b), "r"(ph) : "memory");
  return ok;
}
__device__ __forceinline__ void wg_fence() { asm volatile("wgmma.fence.sync.aligned;" ::: "memory"); }
__device__ __forceinline__ void wg_commit() { asm volatile("wgmma.commit_group.sync.aligned;" ::: "memory"); }
template <int N> __device__ __forceinline__ void wg_wait() { asm volatile("wgmma.wait_group.sync.aligned %0;" ::"n"(N) : "memory"); }
template <int N> __device__ __forceinline__ void reg_fence(float (&a)[N]) {
#pragma unroll
  for (int i = 0; i < N; i++) asm volatile("" : "+f"(a[i])::"memory");
}
__device__ __forceinline__ uint32_t pack_bf16(float lo, float hi) {
  uint32_t r; asm("cvt.rn.bf16x2.f32 %0, %1, %2;" : "=r"(r) : "f"(hi), "f"(lo)); return r;
}
__device__ __forceinline__ float bf_lo(uint32_t v) { return __uint_as_float(v << 16); }
__device__ __forceinline__ float bf_hi(uint32_t v) { return __uint_as_float(v & 0xFFFF0000u); }
__device__ __forceinline__ float rbf(float x) { return __bfloat162float(__float2bfloat16_rn(x)); }
__device__ __forceinline__ uint32_t hmul2_bf(uint32_t a, uint32_t b) { uint32_t r; asm("mul.rn.bf16x2 %0, %1, %2;" : "=r"(r) : "r"(a), "r"(b)); return r; }
__device__ __forceinline__ uint32_t hadd2_bf(uint32_t a, uint32_t b) { uint32_t r; asm("add.rn.bf16x2 %0, %1, %2;" : "=r"(r) : "r"(a), "r"(b)); return r; }
__device__ __forceinline__ void bulk_ld(uint32_t dst, const void* src, int bytes, uint32_t bar) {
  asm volatile("cp.async.bulk.shared::cluster.global.mbarrier::complete_tx::bytes [%0], [%1], %2, [%3];"
               ::"r"(dst), "l"(src), "r"(bytes), "r"(bar) : "memory");
}

template <int BYTES>
__device__ __forceinline__ void bulk_ld_elect(uint32_t dst, const void* src, uint32_t bar) {
  asm volatile("{\n.reg .pred p;\nelect.sync _|p, 0xffffffff;\n"
               "@p mbarrier.arrive.expect_tx.shared::cta.b64 _, [%2], %3;\n"
               "@p cp.async.bulk.shared::cluster.global.mbarrier::complete_tx::bytes [%0], [%1], %3, [%2];\n}"
               ::"r"(dst), "l"(src), "r"(bar), "n"(BYTES) : "memory");
}
template <int BYTES>
__device__ __forceinline__ void bulk_ld_mc_elect(uint32_t dst, const void* src, uint32_t bar) {
  asm volatile("{\n.reg .pred p;\nelect.sync _|p, 0xffffffff;\n"
               "@p mbarrier.arrive.expect_tx.shared::cta.b64 _, [%2], %3;\n"
               "@p cp.async.bulk.shared::cluster.global.mbarrier::complete_tx::bytes.multicast::cluster [%0], [%1], %4, [%2], %5;\n}"
               ::"r"(dst), "l"(src), "r"(bar), "n"(2 * BYTES), "n"(BYTES), "h"((uint16_t)3) : "memory");
}
template <int AOFF, uint32_t AHI, int BOFF, uint32_t BHI, int ACC>
__device__ __forceinline__ void wgmma_ss224(float (&d)[112], uint32_t alo, uint32_t blo) {
  asm volatile("{\n.reg .pred p;\n.reg .b64 ad, bd;\nsetp.ne.b32 p, %118, 0;\n"
    "mov.b64 ad, {%112, %115};\nadd.s64 ad, ad, %114;\nmov.b64 bd, {%113, %117};\nadd.s64 bd, bd, %116;\n"
    "wgmma.mma_async.sync.aligned.m64n224k16.f32.bf16.bf16 {%0,%1,%2,%3,%4,%5,%6,%7,%8,%9,%10,%11,%12,%13,%14,%15,%16,%17,%18,%19,%20,%21,%22,%23,%24,%25,%26,%27,%28,%29,%30,%31,%32,%33,%34,%35,%36,%37,%38,%39,%40,%41,%42,%43,%44,%45,%46,%47,%48,%49,%50,%51,%52,%53,%54,%55,%56,%57,%58,%59,%60,%61,%62,%63,%64,%65,%66,%67,%68,%69,%70,%71,%72,%73,%74,%75,%76,%77,%78,%79,%80,%81,%82,%83,%84,%85,%86,%87,%88,%89,%90,%91,%92,%93,%94,%95,%96,%97,%98,%99,%100,%101,%102,%103,%104,%105,%106,%107,%108,%109,%110,%111}, ad, bd, p, 1, 1, 1, 1;\n}\n"
    : "+f"(d[0]),"+f"(d[1]),"+f"(d[2]),"+f"(d[3]),"+f"(d[4]),"+f"(d[5]),"+f"(d[6]),"+f"(d[7]),"+f"(d[8]),"+f"(d[9]),"+f"(d[10]),"+f"(d[11]),"+f"(d[12]),"+f"(d[13]),"+f"(d[14]),"+f"(d[15]),"+f"(d[16]),"+f"(d[17]),"+f"(d[18]),"+f"(d[19]),"+f"(d[20]),"+f"(d[21]),"+f"(d[22]),"+f"(d[23]),"+f"(d[24]),"+f"(d[25]),"+f"(d[26]),"+f"(d[27]),"+f"(d[28]),"+f"(d[29]),"+f"(d[30]),"+f"(d[31]),"+f"(d[32]),"+f"(d[33]),"+f"(d[34]),"+f"(d[35]),"+f"(d[36]),"+f"(d[37]),"+f"(d[38]),"+f"(d[39]),"+f"(d[40]),"+f"(d[41]),"+f"(d[42]),"+f"(d[43]),"+f"(d[44]),"+f"(d[45]),"+f"(d[46]),"+f"(d[47]),"+f"(d[48]),"+f"(d[49]),"+f"(d[50]),"+f"(d[51]),"+f"(d[52]),"+f"(d[53]),"+f"(d[54]),"+f"(d[55]),"+f"(d[56]),"+f"(d[57]),"+f"(d[58]),"+f"(d[59]),"+f"(d[60]),"+f"(d[61]),"+f"(d[62]),"+f"(d[63]),"+f"(d[64]),"+f"(d[65]),"+f"(d[66]),"+f"(d[67]),"+f"(d[68]),"+f"(d[69]),"+f"(d[70]),"+f"(d[71]),"+f"(d[72]),"+f"(d[73]),"+f"(d[74]),"+f"(d[75]),"+f"(d[76]),"+f"(d[77]),"+f"(d[78]),"+f"(d[79]),"+f"(d[80]),"+f"(d[81]),"+f"(d[82]),"+f"(d[83]),"+f"(d[84]),"+f"(d[85]),"+f"(d[86]),"+f"(d[87]),"+f"(d[88]),"+f"(d[89]),"+f"(d[90]),"+f"(d[91]),"+f"(d[92]),"+f"(d[93]),"+f"(d[94]),"+f"(d[95]),"+f"(d[96]),"+f"(d[97]),"+f"(d[98]),"+f"(d[99]),"+f"(d[100]),"+f"(d[101]),"+f"(d[102]),"+f"(d[103]),"+f"(d[104]),"+f"(d[105]),"+f"(d[106]),"+f"(d[107]),"+f"(d[108]),"+f"(d[109]),"+f"(d[110]),"+f"(d[111])
    : "r"(alo), "r"(blo), "n"(AOFF), "n"(AHI), "n"(BOFF), "n"(BHI), "n"(ACC));
}
template <int AOFF, uint32_t AHI, int BOFF, uint32_t BHI, int ACC>
__device__ __forceinline__ void wgmma_ss232(float (&d)[116], uint32_t alo, uint32_t blo) {
  asm volatile("{\n.reg .pred p;\n.reg .b64 ad, bd;\nsetp.ne.b32 p, %122, 0;\n"
    "mov.b64 ad, {%116, %119};\nadd.s64 ad, ad, %118;\nmov.b64 bd, {%117, %121};\nadd.s64 bd, bd, %120;\n"
    "wgmma.mma_async.sync.aligned.m64n232k16.f32.bf16.bf16 {%0,%1,%2,%3,%4,%5,%6,%7,%8,%9,%10,%11,%12,%13,%14,%15,%16,%17,%18,%19,%20,%21,%22,%23,%24,%25,%26,%27,%28,%29,%30,%31,%32,%33,%34,%35,%36,%37,%38,%39,%40,%41,%42,%43,%44,%45,%46,%47,%48,%49,%50,%51,%52,%53,%54,%55,%56,%57,%58,%59,%60,%61,%62,%63,%64,%65,%66,%67,%68,%69,%70,%71,%72,%73,%74,%75,%76,%77,%78,%79,%80,%81,%82,%83,%84,%85,%86,%87,%88,%89,%90,%91,%92,%93,%94,%95,%96,%97,%98,%99,%100,%101,%102,%103,%104,%105,%106,%107,%108,%109,%110,%111,%112,%113,%114,%115}, ad, bd, p, 1, 1, 1, 1;\n}\n"
    : "+f"(d[0]),"+f"(d[1]),"+f"(d[2]),"+f"(d[3]),"+f"(d[4]),"+f"(d[5]),"+f"(d[6]),"+f"(d[7]),"+f"(d[8]),"+f"(d[9]),"+f"(d[10]),"+f"(d[11]),"+f"(d[12]),"+f"(d[13]),"+f"(d[14]),"+f"(d[15]),"+f"(d[16]),"+f"(d[17]),"+f"(d[18]),"+f"(d[19]),"+f"(d[20]),"+f"(d[21]),"+f"(d[22]),"+f"(d[23]),"+f"(d[24]),"+f"(d[25]),"+f"(d[26]),"+f"(d[27]),"+f"(d[28]),"+f"(d[29]),"+f"(d[30]),"+f"(d[31]),"+f"(d[32]),"+f"(d[33]),"+f"(d[34]),"+f"(d[35]),"+f"(d[36]),"+f"(d[37]),"+f"(d[38]),"+f"(d[39]),"+f"(d[40]),"+f"(d[41]),"+f"(d[42]),"+f"(d[43]),"+f"(d[44]),"+f"(d[45]),"+f"(d[46]),"+f"(d[47]),"+f"(d[48]),"+f"(d[49]),"+f"(d[50]),"+f"(d[51]),"+f"(d[52]),"+f"(d[53]),"+f"(d[54]),"+f"(d[55]),"+f"(d[56]),"+f"(d[57]),"+f"(d[58]),"+f"(d[59]),"+f"(d[60]),"+f"(d[61]),"+f"(d[62]),"+f"(d[63]),"+f"(d[64]),"+f"(d[65]),"+f"(d[66]),"+f"(d[67]),"+f"(d[68]),"+f"(d[69]),"+f"(d[70]),"+f"(d[71]),"+f"(d[72]),"+f"(d[73]),"+f"(d[74]),"+f"(d[75]),"+f"(d[76]),"+f"(d[77]),"+f"(d[78]),"+f"(d[79]),"+f"(d[80]),"+f"(d[81]),"+f"(d[82]),"+f"(d[83]),"+f"(d[84]),"+f"(d[85]),"+f"(d[86]),"+f"(d[87]),"+f"(d[88]),"+f"(d[89]),"+f"(d[90]),"+f"(d[91]),"+f"(d[92]),"+f"(d[93]),"+f"(d[94]),"+f"(d[95]),"+f"(d[96]),"+f"(d[97]),"+f"(d[98]),"+f"(d[99]),"+f"(d[100]),"+f"(d[101]),"+f"(d[102]),"+f"(d[103]),"+f"(d[104]),"+f"(d[105]),"+f"(d[106]),"+f"(d[107]),"+f"(d[108]),"+f"(d[109]),"+f"(d[110]),"+f"(d[111]),"+f"(d[112]),"+f"(d[113]),"+f"(d[114]),"+f"(d[115])
    : "r"(alo), "r"(blo), "n"(AOFF), "n"(AHI), "n"(BOFF), "n"(BHI), "n"(ACC));
}
template <int OFF, uint32_t BHI, int ACC>
__device__ __forceinline__ void wgmma_rs224(float (&d)[112], uint32_t a0, uint32_t a1, uint32_t a2, uint32_t a3, uint32_t blo) {
  asm volatile("{\n.reg .pred p;\n.reg .b64 bd;\nsetp.ne.b32 p, %119, 0;\nmov.b64 bd, {%116, %118};\nadd.s64 bd, bd, %117;\n"
    "wgmma.mma_async.sync.aligned.m64n224k16.f32.bf16.bf16 {%0,%1,%2,%3,%4,%5,%6,%7,%8,%9,%10,%11,%12,%13,%14,%15,%16,%17,%18,%19,%20,%21,%22,%23,%24,%25,%26,%27,%28,%29,%30,%31,%32,%33,%34,%35,%36,%37,%38,%39,%40,%41,%42,%43,%44,%45,%46,%47,%48,%49,%50,%51,%52,%53,%54,%55,%56,%57,%58,%59,%60,%61,%62,%63,%64,%65,%66,%67,%68,%69,%70,%71,%72,%73,%74,%75,%76,%77,%78,%79,%80,%81,%82,%83,%84,%85,%86,%87,%88,%89,%90,%91,%92,%93,%94,%95,%96,%97,%98,%99,%100,%101,%102,%103,%104,%105,%106,%107,%108,%109,%110,%111}, {%112,%113,%114,%115}, bd, p, 1, 1, 1;\n}\n"
    : "+f"(d[0]),"+f"(d[1]),"+f"(d[2]),"+f"(d[3]),"+f"(d[4]),"+f"(d[5]),"+f"(d[6]),"+f"(d[7]),"+f"(d[8]),"+f"(d[9]),"+f"(d[10]),"+f"(d[11]),"+f"(d[12]),"+f"(d[13]),"+f"(d[14]),"+f"(d[15]),"+f"(d[16]),"+f"(d[17]),"+f"(d[18]),"+f"(d[19]),"+f"(d[20]),"+f"(d[21]),"+f"(d[22]),"+f"(d[23]),"+f"(d[24]),"+f"(d[25]),"+f"(d[26]),"+f"(d[27]),"+f"(d[28]),"+f"(d[29]),"+f"(d[30]),"+f"(d[31]),"+f"(d[32]),"+f"(d[33]),"+f"(d[34]),"+f"(d[35]),"+f"(d[36]),"+f"(d[37]),"+f"(d[38]),"+f"(d[39]),"+f"(d[40]),"+f"(d[41]),"+f"(d[42]),"+f"(d[43]),"+f"(d[44]),"+f"(d[45]),"+f"(d[46]),"+f"(d[47]),"+f"(d[48]),"+f"(d[49]),"+f"(d[50]),"+f"(d[51]),"+f"(d[52]),"+f"(d[53]),"+f"(d[54]),"+f"(d[55]),"+f"(d[56]),"+f"(d[57]),"+f"(d[58]),"+f"(d[59]),"+f"(d[60]),"+f"(d[61]),"+f"(d[62]),"+f"(d[63]),"+f"(d[64]),"+f"(d[65]),"+f"(d[66]),"+f"(d[67]),"+f"(d[68]),"+f"(d[69]),"+f"(d[70]),"+f"(d[71]),"+f"(d[72]),"+f"(d[73]),"+f"(d[74]),"+f"(d[75]),"+f"(d[76]),"+f"(d[77]),"+f"(d[78]),"+f"(d[79]),"+f"(d[80]),"+f"(d[81]),"+f"(d[82]),"+f"(d[83]),"+f"(d[84]),"+f"(d[85]),"+f"(d[86]),"+f"(d[87]),"+f"(d[88]),"+f"(d[89]),"+f"(d[90]),"+f"(d[91]),"+f"(d[92]),"+f"(d[93]),"+f"(d[94]),"+f"(d[95]),"+f"(d[96]),"+f"(d[97]),"+f"(d[98]),"+f"(d[99]),"+f"(d[100]),"+f"(d[101]),"+f"(d[102]),"+f"(d[103]),"+f"(d[104]),"+f"(d[105]),"+f"(d[106]),"+f"(d[107]),"+f"(d[108]),"+f"(d[109]),"+f"(d[110]),"+f"(d[111])
    : "r"(a0), "r"(a1), "r"(a2), "r"(a3), "r"(blo), "n"(OFF), "n"(BHI), "n"(ACC));
}
template <int OFF, uint32_t BHI, int ACC>
__device__ __forceinline__ void wgmma_rs56(float (&d)[28], uint32_t a0, uint32_t a1, uint32_t a2, uint32_t a3, uint32_t blo) {
  asm volatile("{\n.reg .pred p;\n.reg .b64 bd;\nsetp.ne.b32 p, %35, 0;\nmov.b64 bd, {%32, %34};\nadd.s64 bd, bd, %33;\n"
    "wgmma.mma_async.sync.aligned.m64n56k16.f32.bf16.bf16 {%0,%1,%2,%3,%4,%5,%6,%7,%8,%9,%10,%11,%12,%13,%14,%15,%16,%17,%18,%19,%20,%21,%22,%23,%24,%25,%26,%27}, {%28,%29,%30,%31}, bd, p, 1, 1, 1;\n}\n"
    : "+f"(d[0]),"+f"(d[1]),"+f"(d[2]),"+f"(d[3]),"+f"(d[4]),"+f"(d[5]),"+f"(d[6]),"+f"(d[7]),"+f"(d[8]),"+f"(d[9]),"+f"(d[10]),"+f"(d[11]),"+f"(d[12]),"+f"(d[13]),"+f"(d[14]),"+f"(d[15]),"+f"(d[16]),"+f"(d[17]),"+f"(d[18]),"+f"(d[19]),"+f"(d[20]),"+f"(d[21]),"+f"(d[22]),"+f"(d[23]),"+f"(d[24]),"+f"(d[25]),"+f"(d[26]),"+f"(d[27])
    : "r"(a0), "r"(a1), "r"(a2), "r"(a3), "r"(blo), "n"(OFF), "n"(BHI), "n"(ACC));
}

__device__ __forceinline__ void st128(uint4* p, uint32_t a, uint32_t b, uint32_t c, uint32_t d) {
  asm volatile("{\n.reg .b128 v;\n.reg .b64 lo, hi;\nmov.b64 lo, {%1, %2};\nmov.b64 hi, {%3, %4};\nmov.b128 v, {lo, hi};\n"
               "st.relaxed.gpu.global.b128 [%0], v;\n}" ::"l"(p), "r"(a), "r"(b), "r"(c), "r"(d) : "memory");
}
__device__ __forceinline__ void ld128(const uint4* p, uint32_t* r) {
  asm volatile("{\n.reg .b128 v;\n.reg .b64 lo, hi;\nld.relaxed.gpu.global.b128 v, [%4];\nmov.b128 {lo, hi}, v;\n"
               "mov.b64 {%0, %1}, lo;\nmov.b64 {%2, %3}, hi;\n}" : "=r"(r[0]), "=r"(r[1]), "=r"(r[2]), "=r"(r[3]) : "l"(p) : "memory");
}

template <int OFF, uint32_t BHI, int ACC>
__device__ __forceinline__ void wgmma_rs32(float (&d)[16], uint32_t a0, uint32_t a1, uint32_t a2, uint32_t a3, uint32_t blo) {
  asm volatile("{\n.reg .pred p;\n.reg .b64 bd;\nsetp.ne.b32 p, %23, 0;\nmov.b64 bd, {%20, %22};\nadd.s64 bd, bd, %21;\n"
    "wgmma.mma_async.sync.aligned.m64n32k16.f32.bf16.bf16 {%0,%1,%2,%3,%4,%5,%6,%7,%8,%9,%10,%11,%12,%13,%14,%15}, {%16,%17,%18,%19}, bd, p, 1, 1, 0;\n}\n"
    : "+f"(d[0]),"+f"(d[1]),"+f"(d[2]),"+f"(d[3]),"+f"(d[4]),"+f"(d[5]),"+f"(d[6]),"+f"(d[7]),"+f"(d[8]),"+f"(d[9]),"+f"(d[10]),"+f"(d[11]),"+f"(d[12]),"+f"(d[13]),"+f"(d[14]),"+f"(d[15])
    : "r"(a0), "r"(a1), "r"(a2), "r"(a3), "r"(blo), "n"(OFF), "n"(BHI), "n"(ACC));
}
template <int OFF, uint32_t BHI, int ACC>
__device__ __forceinline__ void wgmma_rs24(float (&d)[12], uint32_t a0, uint32_t a1, uint32_t a2, uint32_t a3, uint32_t blo) {
  asm volatile("{\n.reg .pred p;\n.reg .b64 bd;\nsetp.ne.b32 p, %19, 0;\nmov.b64 bd, {%16, %18};\nadd.s64 bd, bd, %17;\n"
    "wgmma.mma_async.sync.aligned.m64n24k16.f32.bf16.bf16 {%0,%1,%2,%3,%4,%5,%6,%7,%8,%9,%10,%11}, {%12,%13,%14,%15}, bd, p, 1, 1, 1;\n}\n"
    : "+f"(d[0]),"+f"(d[1]),"+f"(d[2]),"+f"(d[3]),"+f"(d[4]),"+f"(d[5]),"+f"(d[6]),"+f"(d[7]),"+f"(d[8]),"+f"(d[9]),"+f"(d[10]),"+f"(d[11])
    : "r"(a0), "r"(a1), "r"(a2), "r"(a3), "r"(blo), "n"(OFF), "n"(BHI), "n"(ACC));
}
template <int OFF, uint32_t BHI, int ACC>
__device__ __forceinline__ void wgmma_rs16(float (&d)[8], uint32_t a0, uint32_t a1, uint32_t a2, uint32_t a3, uint32_t blo) {
  asm volatile("{\n.reg .pred p;\n.reg .b64 bd;\nsetp.ne.b32 p, %15, 0;\nmov.b64 bd, {%12, %14};\nadd.s64 bd, bd, %13;\n"
    "wgmma.mma_async.sync.aligned.m64n16k16.f32.bf16.bf16 {%0,%1,%2,%3,%4,%5,%6,%7}, {%8,%9,%10,%11}, bd, p, 1, 1, 1;\n}\n"
    : "+f"(d[0]),"+f"(d[1]),"+f"(d[2]),"+f"(d[3]),"+f"(d[4]),"+f"(d[5]),"+f"(d[6]),"+f"(d[7])
    : "r"(a0), "r"(a1), "r"(a2), "r"(a3), "r"(blo), "n"(OFF), "n"(BHI), "n"(ACC));
}

constexpr int A_R1 = 0;
constexpr int A_R2A = A_R1 + 2624, A_R2B = A_R2A + 768, A_R3A = A_R2B + 768, A_R3B = A_R3A + 528;
constexpr int A_K1024 = A_R3B + 528;
constexpr int A_W5 = A_K1024 + 16;
constexpr int A_W3 = A_W5 + 4096;
constexpr int A_W9 = A_W3 + 4112;
constexpr int A_W7 = A_W9 + 2080;
constexpr int A_V  = A_W7 + 2080 + 32;
constexpr int A_SCL = A_V + 2048;
constexpr int A_UB = A_SCL + 16;
constexpr int A_STG = A_UB + 5248;
constexpr int A_Y2 = A_STG, A_Y3 = A_Y2 + 6528, A_YB = A_Y3 + 4352;
constexpr int A_REC = A_STG + 4 * 4352;
constexpr int A_CH = A_REC + 8192;
static_assert(A_W5 % 16 == 0 && A_UB % 16 == 0 && A_CH % 16 == 0 && A_YB + 4096 <= A_REC, "layout");

struct cf { float x, y; };
__device__ __forceinline__ cf cmul(cf a, cf b) { cf r; r.x = fmaf(a.x, b.x, -a.y * b.y); r.y = fmaf(a.x, b.y, a.y * b.x); return r; }
__device__ __forceinline__ cf cexp_l(float lr, float li, float l) {
  float mag; asm("ex2.approx.ftz.f32 %0, %1;" : "=f"(mag) : "f"((lr * l) * 1.4426950408889634f));
  const float th = li * l;
  const float k = (fmaf(th, 0.15915494f, 12582912.f)) - 12582912.f;
  float ph = fmaf(th, 0.15915494f, -k);
  ph = fmaf(th, 6.4206383e-9f, ph) * 6.2831853f;
  cf r; r.x = mag * __cosf(ph); r.y = mag * __sinf(ph); return r;
}
__device__ __forceinline__ void sts16(uint32_t a, uint32_t v) { asm volatile("st.shared.u16 [%0], %1;" ::"r"(a), "h"((uint16_t)v) : "memory"); }
__device__ __forceinline__ void sts32(uint32_t a, uint32_t v) { asm volatile("st.shared.u32 [%0], %1;" ::"r"(a), "r"(v) : "memory"); }
__device__ __forceinline__ void sts64(uint32_t a, uint32_t v0, uint32_t v1) { asm volatile("st.shared.v2.u32 [%0], {%1, %2};" ::"r"(a), "r"(v0), "r"(v1) : "memory"); }
__device__ __forceinline__ void sts128(uint32_t a, uint32_t v0, uint32_t v1, uint32_t v2, uint32_t v3) {
  asm volatile("st.shared.v4.u32 [%0], {%1, %2, %3, %4};" ::"r"(a), "r"(v0), "r"(v1), "r"(v2), "r"(v3) : "memory");
}
__device__ __forceinline__ uint32_t lds32(uint32_t a) { uint32_t v; asm volatile("ld.shared.u32 %0, [%1];" : "=r"(v) : "r"(a) : "memory"); return v; }
__device__ __forceinline__ uint4 lds128(uint32_t a) {
  uint4 v; asm volatile("ld.shared.v4.u32 {%0, %1, %2, %3}, [%4];" : "=r"(v.x), "=r"(v.y), "=r"(v.z), "=r"(v.w) : "r"(a) : "memory"); return v;
}
__device__ __forceinline__ void ldsm4(uint32_t* r, uint32_t a) {
  asm volatile("ldmatrix.sync.aligned.m8n8.x4.shared.b16 {%0,%1,%2,%3}, [%4];" : "=r"(r[0]), "=r"(r[1]), "=r"(r[2]), "=r"(r[3]) : "r"(a) : "memory");
}
__device__ __forceinline__ void mma16816(float* d, uint32_t a0, uint32_t a1, uint32_t a2, uint32_t a3, uint32_t b0, uint32_t b1) {
  asm volatile("mma.sync.aligned.m16n8k16.row.col.f32.f16.f16.f32 {%0,%1,%2,%3}, {%4,%5,%6,%7}, {%8,%9}, {%0,%1,%2,%3};"
               : "+f"(d[0]), "+f"(d[1]), "+f"(d[2]), "+f"(d[3]) : "r"(a0), "r"(a1), "r"(a2), "r"(a3), "r"(b0), "r"(b1));
}
__device__ __forceinline__ uint32_t pack_h(float lo, float hi) { uint32_t r; asm("cvt.rn.f16x2.f32 %0, %1, %2;" : "=r"(r) : "f"(hi), "f"(lo)); return r; }
__device__ __forceinline__ uint32_t pack_h(cf v) { return pack_h(v.x, v.y); }
__device__ __forceinline__ uint32_t hcmul(uint32_t x, uint32_t r0, uint32_t r1) {
  const __half2 hx = *(__half2*)&x;
  const __half2 y = __hfma2(__high2half2(hx), *(__half2*)&r1, __hmul2(__low2half2(hx), *(__half2*)&r0));
  return *(const uint32_t*)&y;
}
__device__ __forceinline__ float ln_rstd(float var) {
  float sd, rs;
  asm("sqrt.approx.f32 %0, %1;" : "=f"(sd) : "f"(rbf(rbf(var) + 1e-5f)));
  asm("rcp.approx.f32 %0, %1;" : "=f"(rs) : "f"(rbf(sd)));
  return rs;
}
__device__ __forceinline__ uint32_t hsub2_bf(uint32_t a, uint32_t b) { uint32_t r; asm("sub.rn.bf16x2 %0, %1, %2;" : "=r"(r) : "r"(a), "r"(b)); return r; }
__device__ __forceinline__ void bar_sync(int id, int n) { asm volatile("bar.sync %0, %1;" ::"r"(id), "r"(n) : "memory"); }

template <int S> struct F1B { static constexpr int c = S / 4 + ((S & 3) == 3 ? 0 : 0), cc = (16 * S) / 64, ks = (64 * cc - (16 * S - 48)) / 16, off = (A_UB + 2 * ks * 656 + (9 - cc) * 16) / 16; };

template <int NS>
__device__ __forceinline__ void load_quads(uint32_t* q, uint32_t addr) {
#pragma unroll
  for (int i = 0; i < NS; i++) {
    q[4 * i] = lds32(addr + i * 64); q[4 * i + 1] = lds32(addr + i * 64 + 32);
    q[4 * i + 2] = i ? q[4 * i - 3] : lds32(addr - 32);
    q[4 * i + 3] = q[4 * i];
  }
#pragma unroll
  for (int i = 0; i < 4 * NS; i++) asm volatile("" : "+r"(q[i]));
}
template <int S0, int NS>
__device__ __forceinline__ void f1_steps(float (&acc)[16], const uint32_t* a, uint32_t blo) {
  if constexpr (NS > 0) {
    wgmma_rs32<F1B<S0>::off, 8, S0 != 0>(acc, a[0], a[1], a[2], a[3], blo);
    f1_steps<S0 + 1, NS - 1>(acc, a + 4, blo);
  }
}
template <int S0, int NS, int BASE, int FIRST>
__device__ __forceinline__ void s2_steps(float (&acc)[12], const uint32_t* a, uint32_t blo) {
  if constexpr (NS > 0) {
    wgmma_rs24<BASE / 16 + (112 - 16 * S0), 64, !(FIRST && S0 == 0)>(acc, a[0], a[1], a[2], a[3], blo);
    s2_steps<S0 + 1, NS - 1, BASE, FIRST>(acc, a + 4, blo);
  }
}
template <int S0, int NS, int BASE, int FIRST>
__device__ __forceinline__ void s3_steps(float (&acc)[8], const uint32_t* a, uint32_t blo) {
  if constexpr (NS > 0) {
    wgmma_rs16<BASE / 16 + (48 - 16 * S0), 65, !(FIRST && S0 == 0)>(acc, a[0], a[1], a[2], a[3], blo);
    s3_steps<S0 + 1, NS - 1, BASE, FIRST>(acc, a + 4, blo);
  }
}

__device__ __forceinline__ void phase_a(
        unsigned char* sm, const uint32_t bar_rec, const uint32_t ep_addr,
        const __nv_bfloat16* __restrict__ x, const uint32_t* __restrict__ are, const uint32_t* __restrict__ aim,
        const uint32_t* __restrict__ bre, const uint32_t* __restrict__ bim, const uint32_t* __restrict__ cre,
        const uint32_t* __restrict__ cim, const unsigned short* __restrict__ logdt, const unsigned short* __restrict__ dskip,
        const uint4* __restrict__ wgate, const uint4* __restrict__ wup, const uint4* __restrict__ wdown) {
  const uint32_t sb = s2u(sm);
  const int tid = threadIdx.x, warp = __shfl_sync(~0u, tid >> 5, 0), wg = warp >> 2, lane = tid & 31, wq = warp & 3, t128 = tid & 127;
  const int blk = blockIdx.x;
  const bool conv = blk < 112;

  uint2 xr[4];
  {
    const uint2* p = (const uint2*)(x + (size_t)(blk * 16 + warp) * DM);
    xr[0] = __ldg(p + lane); xr[1] = __ldg(p + 32 + lane); xr[2] = __ldg(p + 64 + lane);
    xr[3] = lane < 16 ? __ldg(p + 96 + lane) : make_uint2(0, 0);
  }
  const int ch = conv ? blk * 4 + wg : 0;
  const uint32_t cb = sb + wg * A_CH;
  uint32_t prm[6];
  {
    const int i = ch * 128 + t128;
    prm[0] = __ldg(are + i); prm[1] = __ldg(aim + i); prm[2] = __ldg(bre + i); prm[3] = __ldg(bim + i); prm[4] = __ldg(cre + i); prm[5] = __ldg(cim + i);
  }
  const uint32_t ldt = __ldg(logdt + ch);
  uint32_t cnt0 = 0;
  if (tid == 0) cnt0 = __ldcg(&g_cnt1);
#pragma unroll
  for (int i = 0; i < 4; i++) if (i < 3 || t128 < (A_W5 + 1024) / 16 - 384) sts128(cb + (i * 128 + t128) * 16, 0, 0, 0, 0);
  if (t128 < 64) sts128(cb + A_W3 + t128 * 16, 0, 0, 0, 0);
  if (t128 < 72) sts128(cb + A_UB + (t128 / 9) * 656 + (t128 % 9) * 16, 0, 0, 0, 0);
  {
    float s = 0.f, q = 0.f;
#pragma unroll
    for (int i = 0; i < 4; i++) {
      const float a = bf_lo(xr[i].x), b = bf_hi(xr[i].x), c = bf_lo(xr[i].y), d = bf_hi(xr[i].y);
      s += (a + b) + (c + d);
      q = fmaf(a, a, q); q = fmaf(b, b, q); q = fmaf(c, c, q); q = fmaf(d, d, q);
    }
#pragma unroll
    for (int o = 16; o; o >>= 1) { s += __shfl_xor_sync(~0u, s, o); q += __shfl_xor_sync(~0u, q, o); }
    const float mean = s * (1.f / DM);
    const float var = fmaxf(fmaf(-mean, mean, q * (1.f / DM)), 0.f);
    const float rs = ln_rstd(var);
    const uint32_t mm = pack_bf16(mean, mean);
    const uint32_t tu = sb + A_REC + (warp >> 3) * A_CH + (warp & 7) * 912 + lane * 8, tx = tu + 2 * A_CH;
#pragma unroll
    for (int i = 0; i < 4; i++) {
      if (i < 3 || lane < 16) {
        const uint32_t d0 = hsub2_bf(xr[i].x, mm), d1 = hsub2_bf(xr[i].y, mm);
        sts64(tu + i * 256, pack_bf16(bf_lo(d0) * rs, bf_hi(d0) * rs), pack_bf16(bf_lo(d1) * rs, bf_hi(d1) * rs));
        sts64(tx + i * 256, xr[i].x, xr[i].y);
      }
    }
  }
  if (tid == 0) sts32(ep_addr, (cnt0 >> 7) + 1u);
  if (tid == 320) TR(0, 1);
  auto publish_rows = [&]() {
    bar_sync(5, 512);
    uint4* dst = g_ux + ((size_t)(warp * 8 + (lane >> 2)) * 128 + blk) * 4 + ((lane ^ (blk >> 1)) & 3);
#pragma unroll
    for (int i = 0; i < 4; i++) {
      if (i < 3 || warp < 8) {
        uint32_t r[4];
        asm volatile("ldmatrix.sync.aligned.m8n8.x4.trans.shared.b16 {%0,%1,%2,%3}, [%4];" : "=r"(r[0]), "=r"(r[1]), "=r"(r[2]), "=r"(r[3])
                     : "r"(sb + A_REC + (lane >> 3) * A_CH + (lane & 7) * 912 + (warp + 16 * i) * 16) : "memory");
        dst[i * 65536] = make_uint4(r[0], r[1], r[2], r[3]);
      }
    }
    if (warp != 0) asm volatile("bar.arrive 6, 512;" ::: "memory");
  };
  auto release_rows = [&]() {
    if (warp == 0) {
      bar_sync(6, 512);
      if (lane == 0) { asm volatile("red.release.gpu.global.add.u32 [%0], 1;" ::"l"(&g_cnt1) : "memory"); TR(0, 8); }
      __syncwarp();
    }
  };

  if (!conv) {
    publish_rows();
    release_rows();
    const int a = blk - 112, mat = a >> 3, j = a & 7;
    float s[8];
#pragma unroll
    for (int k = 0; k < 8; k++) s[k] = 0.f;
    if (lane < 28) {
      const uint4* src = (mat ? wup : wgate) + j * 28 + lane + (size_t)warp * 224;
#pragma unroll
      for (int hb = 0; hb < 2; hb++) {
        uint4 v[14];
#pragma unroll
        for (int r = 0; r < 14; r++) v[r] = __ldg(src + (size_t)(hb * 14 + r) * 16 * 224);
#pragma unroll
        for (int r = 0; r < 14; r++) {
          s[0] += bf_lo(v[r].x); s[1] += bf_hi(v[r].x); s[2] += bf_lo(v[r].y); s[3] += bf_hi(v[r].y);
          s[4] += bf_lo(v[r].z); s[5] += bf_hi(v[r].z); s[6] += bf_lo(v[r].w); s[7] += bf_hi(v[r].w);
        }
      }
      float4* red = (float4*)(sm + A_STG + warp * 896 + lane * 32);
      red[0] = make_float4(s[0], s[1], s[2], s[3]); red[1] = make_float4(s[4], s[5], s[6], s[7]);
    }
    bar_sync(5, 512);
    if (tid < 224) {
      float t = 0.f;
#pragma unroll
      for (int w = 0; w < 16; w++) t += *(const float*)(sm + A_STG + w * 896 + tid * 4);
      const float hi = rbf(t), mid = rbf(t - hi), lo = rbf(t - hi - mid);
      const int q = tid / 112, n = tid % 112 + 112 * mat;
      __nv_bfloat16* dst = (__nv_bfloat16*)(g_cimg + (j * 2 + q) * 224 + (n >> 3) * 8) + (n & 7);
      dst[0] = __float2bfloat16_rn(hi); dst[8] = __float2bfloat16_rn(mid); dst[16] = __float2bfloat16_rn(lo);
#pragma unroll
      for (int k = 3; k < 8; k++) dst[8 * k] = __float2bfloat16_rn(0.f);
    }
    if (tid == 320) TR(0, 10);
    return;
  }

  const int g = lane >> 2, t = lane & 3;
  const int wr = (wq + wg) & 3;
  const int bk = wr * 32 + lane;
  const int wu2 = ch >> 1, wjq = wu2 / 14, wst = wu2 % 14;
  const uint4* wsrc1 = ((ch & 1) ? wup : wgate) + (size_t)(wst * 32 + wq * 8 + g) * 224 + wjq * 14 + t;
  const uint4* wsrc2 = wdown + (size_t)(wu2 * 8 + g) * 56 + ((ch & 1) * 4 + wq) * 7 + t;
  uint4 wv[6];
  {
    const uint32_t stg = cb + A_STG + wq * 4352, sw = stg + lane * 8;
    const float dt = rbf(expf(__uint_as_float(ldt << 16)));
    float lr[2], li[2];
    cf bq[2], b0[2], b4[2];
    uint32_t bf[48];
#pragma unroll
    for (int m = 0; m < 2; m++) {
      lr[m] = dt * (m ? bf_hi(prm[0]) : bf_lo(prm[0]));
      li[m] = dt * (m ? bf_hi(prm[1]) : bf_lo(prm[1]));
    }
    {
      cf b[2], z[2];
#pragma unroll
      for (int m = 0; m < 2; m++) {
        cf db, c;
        db.x = dt * (m ? bf_hi(prm[2]) : bf_lo(prm[2])); db.y = -dt * (m ? bf_hi(prm[3]) : bf_lo(prm[3]));
        c.x = m ? bf_hi(prm[4]) : bf_lo(prm[4]); c.y = -(m ? bf_hi(prm[5]) : bf_lo(prm[5]));
        b[m] = cmul(c, db);
        z[m] = cexp_l(lr[m], -li[m], 1.f);
        bq[m] = cexp_l(lr[m], -li[m], 256.f);
      }
      {
        const float mx = fmaxf(fmaxf(fabsf(b[0].x), fabsf(b[0].y)), fmaxf(fabsf(b[1].x), fabsf(b[1].y)));
        const uint32_t e = max(__reduce_max_sync(~0u, __float_as_uint(mx)) >> 23, 14u);
        const float sc = __uint_as_float((267u - e) << 23);
        b[0].x *= sc; b[0].y *= sc; b[1].x *= sc; b[1].y *= sc;
        if (lane == 0) sts32(cb + A_SCL + wq * 4, (e - 13u) << 23);
      }
#pragma unroll
      for (int i = 0; i < 8; i++) {
        sts64(sw + i * 272, pack_h(b[0]), pack_h(b[1]));
        if (!(i & 1)) {
          cf e0 = cmul(b[0], bq[0]), e1 = cmul(b[1], bq[1]);
          sts64(sw + (8 + i / 2) * 272, pack_h(e0), pack_h(e1));
          if (i == 0) { b0[0] = e0; b0[1] = e1; }
          if (i == 4) { b4[0] = e0; b4[1] = e1; }
        }
        if (i < 7) { b[0] = cmul(b[0], z[0]); b[1] = cmul(b[1], z[1]); }
        if (i == 1) publish_rows();
      }
#pragma unroll
      for (int i = 0; i < 7; i++) {
        b0[0] = cmul(b0[0], bq[0]); b0[1] = cmul(b0[1], bq[1]);
        sts64(sw + (i < 2 ? 12 + 2 * i : i - 2) * 272, pack_h(b0[0]), pack_h(b0[1]));
        if (i < 2) {
          b4[0] = cmul(b4[0], bq[0]); b4[1] = cmul(b4[1], bq[1]);
          sts64(sw + (13 + 2 * i) * 272, pack_h(b4[0]), pack_h(b4[1]));
        }
        if (i == 1) {
          __syncwarp();
#pragma unroll
          for (int n = 0; n < 2; n++)
#pragma unroll
            for (int k2 = 0; k2 < 4; k2++) ldsm4(bf + n * 16 + k2 * 4, stg + (n * 8 + (lane & 7)) * 272 + k2 * 64 + (lane >> 3) * 16);
          __syncwarp();
          release_rows();
        }
      }
    }
    if (!(lane & 1)) {
#pragma unroll
      for (int i = 0; i < 4; i++) if (i < 3 || t < 2) asm volatile("prefetch.global.L2 [%0];" ::"l"(wsrc1 + 4 * i));
#pragma unroll
      for (int i = 0; i < 2; i++) asm volatile("prefetch.global.L2 [%0];" ::"l"(wsrc2 + 4 * i));
    }
    {
      const cf p0 = cexp_l(lr[0], li[0], 8.f), p1 = cexp_l(lr[1], li[1], 8.f);
      cf v0 = p0, v1 = p1;
      sts64(sw + 8 * 272, 0x3C00u, 0x3C00u);
#pragma unroll
      for (int i = 1; i < 8; i++) {
        sts64(sw + (8 + i) * 272, pack_h(v0), pack_h(v1));
        v0 = cmul(v0, p0); v1 = cmul(v1, p1);
      }
      sts64(sw + 5 * 272, pack_h(v0), pack_h(v1));
      sts64(sw + 6 * 272, pack_h(-v0.y, v0.x), pack_h(-v1.y, v1.x));
    }
    __syncwarp();
    if (tid == 320) TR(0, 16);
#pragma unroll
    for (int k2 = 0; k2 < 4; k2++) ldsm4(bf + 32 + k2 * 4, stg + (lane & 7) * 272 + k2 * 64 + (lane >> 3) * 16);
    uint32_t cv = 0;
    if (tid == 160) asm volatile("ld.relaxed.gpu.global.u32 %0, [%1];" : "=r"(cv) : "l"(&g_cnt1) : "memory");
    float c[6][4];
#pragma unroll
    for (int i = 0; i < 6; i++) { c[i][0] = 0.f; c[i][1] = 0.f; c[i][2] = 0.f; c[i][3] = 0.f; }
#pragma unroll
    for (int k2 = 0; k2 < 4; k2++) {
      uint32_t a[4];
      ldsm4(a, stg + (8 + (lane & 7)) * 272 + k2 * 64 + (lane >> 3) * 16);
#pragma unroll
      for (int kk = 0; kk < 2; kk++) {
        const int ks = 2 * k2 + kk;
        uint32_t r[4];
        ldsm4(r, stg + (5 + (lane >> 4)) * 272 + ks * 32 + ((lane >> 3) & 1) * 16);
        const uint32_t x0 = a[2 * kk], y0 = a[2 * kk + 1];
        const uint32_t x1 = hcmul(x0, r[0], r[2]), y1 = hcmul(y0, r[1], r[3]);
        const uint32_t x2 = hcmul(x1, r[0], r[2]), y2 = hcmul(y1, r[1], r[3]);
        const uint32_t x3 = hcmul(x2, r[0], r[2]), y3 = hcmul(y2, r[1], r[3]);
#pragma unroll
        for (int n = 0; n < 3; n++) {
          mma16816(c[n * 2], x0, x1, y0, y1, bf[n * 16 + ks * 2], bf[n * 16 + ks * 2 + 1]);
          mma16816(c[n * 2 + 1], x2, x3, y2, y3, bf[n * 16 + ks * 2], bf[n * 16 + ks * 2 + 1]);
        }
      }
      if (k2 == 1 && warp == 5) {
        if (lane == 0) {
          const uint32_t tgt = lds32(ep_addr) * 128u;
          int it = 0;
          while ((int)(cv - tgt) < 0 && ++it < 400000) asm volatile("ld.relaxed.gpu.global.u32 %0, [%1];" : "=r"(cv) : "l"(&g_cnt1) : "memory");
          asm volatile("fence.acquire.gpu;" ::: "memory");
          asm volatile("fence.proxy.async.global;" ::: "memory");
          TR(0, 9);
        }
        __syncwarp();
#pragma unroll
        for (int c2 = 0; c2 < 4; c2++) bulk_ld_elect<8192>(sb + c2 * A_CH + A_REC, g_ux + (size_t)(blk * 4 + c2) * 512, bar_rec);
      }
    }
    __syncwarp();
#pragma unroll
    for (int i = 0; i < 6; i++)
      sts128(stg + i * 512 + lane * 16, __float_as_uint(c[i][0]), __float_as_uint(c[i][1]), __float_as_uint(c[i][2]), __float_as_uint(c[i][3]));
#pragma unroll
    for (int i = 0; i < 4; i++) if (i < 3 || t < 2) wv[i] = __ldg(wsrc1 + 4 * i);
#pragma unroll
    for (int i = 0; i < 2; i++) if (i < 1 || t < 3) wv[4 + i] = __ldg(wsrc2 + 4 * i);
  }
  if (tid == 320) TR(0, 2);

  uint32_t xt[8], ud[8];
  {
    mbar_wait(bar_rec, 0);
    if (tid == 320) TR(0, 4);
    uint4 r[4];
#pragma unroll
    for (int i = 0; i < 4; i++) r[i] = lds128(cb + A_REC + bk * 64 + ((i ^ (bk >> 1)) & 3) * 16);
    const uint32_t ua = cb + A_UB + ((2 * bk) & 7) * 656 + ((bk >> 2) + 9) * 16;
    sts128(ua, r[0].x, r[1].x, r[2].x, r[3].x);
    sts128(ua + 656, r[0].y, r[1].y, r[2].y, r[3].y);
    if (bk <= 96) {
      const bool neg = bk == 96;
      const int bp = neg ? -1 : bk;
      uint32_t h[4];
      h[0] = lds32(cb + A_REC + ((bp - 1) & 127) * 64 + ((2 ^ ((bp - 1) >> 1)) & 3) * 16 + 4);
      h[1] = lds32(cb + A_REC + ((bp - 1) & 127) * 64 + ((3 ^ ((bp - 1) >> 1)) & 3) * 16 + 4);
      h[2] = lds32(cb + A_REC + (bp + 1) * 64 + ((0 ^ ((bp + 1) >> 1)) & 3) * 16);
      h[3] = lds32(cb + A_REC + (bp + 1) * 64 + ((1 ^ ((bp + 1) >> 1)) & 3) * 16);
      if (bp <= 0) { h[0] = 0; h[1] = 0; }
      const uint32_t wd[12] = {h[0], h[1], neg ? 0 : r[0].x, neg ? 0 : r[1].x, neg ? 0 : r[2].x, neg ? 0 : r[3].x,
                               neg ? 0 : r[0].y, neg ? 0 : r[1].y, neg ? 0 : r[2].y, neg ? 0 : r[3].y, h[2], h[3]};
      float P[25];
      P[0] = 0.f;
#pragma unroll
      for (int i = 0; i < 12; i++) { P[2 * i + 1] = P[2 * i] + bf_lo(wd[i]); P[2 * i + 2] = P[2 * i + 1] + bf_hi(wd[i]); }
#define WIN(i, hw) (P[(i) + 5 + (hw)] - P[(i) + 4 - (hw)])
#define WPK(i, hw) pack_bf16(WIN(i, hw), WIN((i) + 1, hw))
      const int tp = 2 * bp;
      const uint32_t a3 = cb + A_W3 + (tp + 64) * 16 + 8, a5 = cb + A_W5 + (tp + 64) * 16;
      sts64(a3, WPK(0, 1), WPK(2, 1));
      sts128(a3 + 8, WPK(4, 1), WPK(6, 1), WPK(8, 1), WPK(10, 1));
      sts64(a3 + 24, WPK(12, 1), WPK(14, 1));
      sts128(a5, WPK(0, 2), WPK(2, 2), WPK(4, 2), WPK(6, 2));
      sts128(a5 + 16, WPK(8, 2), WPK(10, 2), WPK(12, 2), WPK(14, 2));
      if (bp < 64) {
        sts128(cb + A_W7 + 1040 + bp * 16, WPK(0, 3), WPK(2, 3), WPK(4, 3), WPK(6, 3));
        sts128(cb + A_W7 + (bp + 1) * 16, WPK(8, 3), WPK(10, 3), WPK(12, 3), WPK(14, 3));
        sts128(cb + A_W9 + (bp + 1) * 16, WPK(0, 4), WPK(2, 4), WPK(4, 4), WPK(6, 4));
        sts128(cb + A_W9 + 1040 + (bp + 1) * 16, WPK(8, 4), WPK(10, 4), WPK(12, 4), WPK(14, 4));
#define VPK(i) pack_bf16(P[(i) + 2] - P[i], P[(i) + 3] - P[(i) + 1])
        sts128(cb + A_V + bp * 32, VPK(0), VPK(2), VPK(4), VPK(6));
        sts128(cb + A_V + bp * 32 + 16, VPK(8), VPK(10), VPK(12), VPK(14));
      }
    }
  }
  asm volatile("fence.proxy.async.shared::cta;" ::: "memory");
  {
    uint4* d1 = g_wimg + (size_t)(wjq >> 1) * 37632 + ((wjq & 1) * 14 + wst) * 896 + ((ch & 1) * 14 + t) * 32 + wq * 8 + g;
#pragma unroll
    for (int i = 0; i < 4; i++) if (i < 3 || t < 2) d1[i * 128] = wv[i];
    uint4* d2 = g_wimg + (size_t)(wjq >> 1) * 37632 + 25088 + (((ch & 1) * 4 + wq) * 2 + (wjq & 1)) * 784 + t * 112 + wst * 8 + g;
#pragma unroll
    for (int i = 0; i < 2; i++) if (i < 1 || t < 3) d2[i * 448] = wv[4 + i];
  }
  bar_sync(1 + wg, 128);
  if (tid == 320) TR(0, 3);
  {
    const uint4 sc = lds128(cb + A_SCL);
    const float scl[4] = {__uint_as_float(sc.x), __uint_as_float(sc.y), __uint_as_float(sc.z), __uint_as_float(sc.w)};
#pragma unroll
    for (int rep = 0; rep < 2; rep++) {
      const int qd = rep ? 2 + wr : 3 - wr;
      if (rep == 0 || wr >= 2) {
        float s[4] = {0.f, 0.f, 0.f, 0.f};
#pragma unroll
        for (int w = 0; w < 4; w++) {
          uint4 u4 = lds128(cb + A_STG + w * 4352 + qd * 512 + lane * 16);
          s[0] = fmaf(__uint_as_float(u4.x), scl[w], s[0]); s[1] = fmaf(__uint_as_float(u4.y), scl[w], s[1]);
          s[2] = fmaf(__uint_as_float(u4.z), scl[w], s[2]); s[3] = fmaf(__uint_as_float(u4.w), scl[w], s[3]);
        }
#pragma unroll
        for (int hf = 0; hf < 2; hf++) {
          const int j = (qd & 1) * 16 + g + 8 * hf;
          const uint32_t pk = pack_bf16(s[2 * hf + 1], s[2 * hf]);
          const uint32_t v0 = pk >> 16, v1 = pk & 0xFFFFu, v00 = v0 * 0x10001u;
          if (rep == 1) {
            if (t < 2) {
#pragma unroll
              for (int e = 0; e < 2; e++) {
                const int lam = 128 + 32 * (2 * t + e) + j, mu = lam >> 1;
                const uint32_t val = e ? v1 : v0;
                uint32_t a = cb + ((lam & 1) ? A_R3B : A_R3A) + mu * 4;
                if (lam == 128) { a = cb + A_R2A + 128 * 4; sts32(cb + A_K1024, val << 16); }
                sts16(a, val); sts16(a + 6, val);
              }
            } else if (t == 2 && j == 0) { sts16(cb + A_R3A + 128 * 4, v0); }
          } else if (qd < 2) {
            const uint32_t a = cb + A_R1 + (62 + 8 * j + 2 * t) * 4;
            sts16(a, v0); sts32(a + 4, pk); sts16(a + 10, v1);
          } else if (t < 2) {
            const int L = 256 + 8 * j + 4 * t;
            const uint32_t a = cb + A_R1 + (62 + L) * 4;
            if (L > 256) { sts16(a - 4, v0); sts32(a, v00); } else sts16(a, v0);
            sts32(a + 4, v00); sts32(a + 8, pk); sts16(a + 14, v1);
          } else {
            const int mu = 64 + 32 * (t - 2) + j;
            if (mu == 64) {
              const uint32_t a = cb + A_R1 + (62 + 512) * 4;
              sts16(a - 4, v0); sts32(a, v00); sts32(a + 4, v00); sts32(a + 8, v00); sts16(a + 14, v0);
            } else { sts16(cb + A_R2A + mu * 4, v0); sts16(cb + A_R2A + mu * 4 + 6, v0); }
            sts16(cb + A_R2B + mu * 4, v1); sts16(cb + A_R2B + mu * 4 + 6, v1);
          }
        }
      }
    }
  }
  bar_sync(1 + wg, 128);
  if (tid == 320) TR(0, 5);

  {
    const uint32_t cbu = cb;
    const uint32_t blo_k = ((cbu & 0x3FFFF) >> 4) | (41u << 16);
    const uint32_t blo_n = ((cbu & 0x3FFFF) >> 4) | (8u << 16);
    const uint32_t tb = cb + (16 * wq + g - 2 * t) * 4;
    float y1[16], y2[12], y3[8];
    const uint32_t dk16 = __ldg(dskip + ch);
    uint32_t qa[32], qb[32];
    const uint32_t t1 = tb + A_R1 + (62 - 48) * 4;
    load_quads<4>(qa, tb + A_R3A + 17 * 4); load_quads<4>(qa + 16, tb + A_R3B + 16 * 4);
    wg_fence();
    s3_steps<0, 4, A_W9, 1>(y3, qa, blo_n); s3_steps<0, 4, A_W7, 0>(y3, qa + 16, blo_n);
    wg_commit();
    load_quads<8>(qb, tb + A_R2A + 16 * 4);
    wg_fence(); s2_steps<0, 8, A_W5, 1>(y2, qb, blo_n); wg_commit();
    wg_wait<1>(); load_quads<8>(qa, tb + A_R2B + 16 * 4);
    wg_fence(); s2_steps<0, 8, A_W3, 0>(y2, qa, blo_n); wg_commit();
    wg_wait<1>(); load_quads<8>(qb, t1);
    wg_fence(); f1_steps<0, 8>(y1, qb, blo_k); wg_commit();
    wg_wait<1>(); load_quads<8>(qa, t1 + 8 * 64);
    wg_fence(); f1_steps<8, 8>(y1, qa, blo_k); wg_commit();
    reg_fence(y2); reg_fence(y3);
    if (tid == 320) TR(0, 18);
    {
      const float k1024 = __uint_as_float(lds32(cb + A_K1024));
#pragma unroll
      for (int i = 0; i < 2; i++)
#pragma unroll
        for (int hf = 0; hf < 2; hf++) {
          const int idx = 16 * (16 * wq + g + 8 * hf) + 8 * i + 2 * t;
          const uint32_t vv = lds32(cb + A_V + idx * 2);
          sts64(cb + A_Y3 + (idx + 4 * (idx >> 6)) * 4, __float_as_uint(fmaf(k1024, bf_lo(vv), y3[4 * i + 2 * hf])),
                __float_as_uint(fmaf(k1024, bf_hi(vv), y3[4 * i + 2 * hf + 1])));
        }
#pragma unroll
      for (int i = 0; i < 3; i++)
#pragma unroll
        for (int hf = 0; hf < 2; hf++) {
          const int idx = 512 * i + 8 * (16 * wq + g + 8 * hf) + 2 * t;
          sts64(cb + A_Y2 + (idx + 4 * (idx >> 6)) * 4, __float_as_uint(y2[4 * i + 2 * hf]), __float_as_uint(y2[4 * i + 2 * hf + 1]));
        }
    }
    wg_wait<1>(); load_quads<8>(qb, t1 + 16 * 64);
    wg_fence(); f1_steps<16, 8>(y1, qb, blo_k); wg_commit();
    wg_wait<1>(); load_quads<8>(qa, t1 + 24 * 64);
    wg_fence(); f1_steps<24, 8>(y1, qa, blo_k); wg_commit();
    wg_wait<1>(); load_quads<5>(qb, t1 + 32 * 64);
    wg_fence(); f1_steps<32, 5>(y1, qb, blo_k); wg_commit();
    bar_sync(1 + wg, 128);
    float ex[12];
#pragma unroll
    for (int i = 1; i < 4; i++)
#pragma unroll
      for (int k = 0; k < 4; k++) {
        const int aa = 8 * i + 2 * t + (k & 1), b = 16 * wq + g + 8 * (k >> 1);
        float e = __uint_as_float(lds32(cb + A_Y2 + ((aa - 8) * 68 + b) * 4));
        if (i >= 2) e += __uint_as_float(lds32(cb + A_Y3 + ((aa - 16) * 68 + b) * 4));
        ex[4 * (i - 1) + k] = e;
      }
    {
      const uint32_t dk = dk16 * 0x10001u;
#pragma unroll
      for (int i = 0; i < 4; i++) {
        const uint4 r = lds128(cb + A_REC + bk * 64 + ((i ^ (bk >> 1)) & 3) * 16);
        ud[i] = hmul2_bf(r.x, dk); ud[4 + i] = hmul2_bf(r.y, dk); xt[i] = r.z; xt[4 + i] = r.w;
      }
    }
    wg_wait<0>();
    reg_fence(y1);
    if (tid == 320) TR(0, 6);
#pragma unroll
    for (int i = 0; i < 12; i++) y1[4 + i] += ex[i];
#pragma unroll
    for (int i = 0; i < 2; i++) {
      const int mi = lane >> 3, aa = 8 * (2 * i + (mi >> 1)) + (lane & 7);
      asm volatile("stmatrix.sync.aligned.m8n8.x4.trans.shared.b16 [%0], {%1,%2,%3,%4};"
                   ::"r"(cb + A_YB + aa * 128 + (((2 * wq + (mi & 1)) ^ (lane & 7)) << 4)),
                     "r"(pack_bf16(y1[8 * i], y1[8 * i + 1])), "r"(pack_bf16(y1[8 * i + 2], y1[8 * i + 3])),
                     "r"(pack_bf16(y1[8 * i + 4], y1[8 * i + 5])), "r"(pack_bf16(y1[8 * i + 6], y1[8 * i + 7])) : "memory");
    }
  }
  bar_sync(1 + wg, 128);
#pragma unroll
  for (int c = 0; c < 2; c++) {
    const int tau = 2 * bk + c, r = ch & 7;
    const uint4 y = lds128(cb + A_YB + (tau >> 3) * 128 + (((tau ^ (tau >> 3)) & 7) << 4));
    g_himg[(size_t)(tau >> 4) * 7168 + (ch >> 3) * 128 + ((tau >> 3) & 1) * 64 + r * 8 + ((tau & 7) ^ r)] =
        make_uint4(hadd2_bf(xt[4 * c], hadd2_bf(y.x, ud[4 * c])), hadd2_bf(xt[4 * c + 1], hadd2_bf(y.y, ud[4 * c + 1])),
                   hadd2_bf(xt[4 * c + 2], hadd2_bf(y.z, ud[4 * c + 2])), hadd2_bf(xt[4 * c + 3], hadd2_bf(y.w, ud[4 * c + 3])));
  }
  if (tid == 320) TR(0, 7);
}

constexpr int B_SA = 0, B_RING = 114688, B_SLOT = 14848, B_NSLOT = 7;
constexpr int B_CS = B_RING + B_NSLOT * B_SLOT;
constexpr int B_RED = B_CS + 7168;
constexpr int B_BAR = B_RED + 256;
constexpr int B_SMEM = B_BAR + 1024, A_SMEM = 4 * A_CH + 64;

__device__ __forceinline__ uint32_t mapa(uint32_t a, uint32_t r) { uint32_t o; asm("mapa.shared::cluster.u32 %0, %1, %2;" : "=r"(o) : "r"(a), "r"(r)); return o; }
template <class T> __device__ __forceinline__ T* pin(T* p) { asm volatile("" : "+l"(p)); return p; }
__device__ __forceinline__ uint32_t pin(uint32_t v) { asm volatile("" : "+r"(v)); return v; }
template <int Q, int ST>
__device__ __forceinline__ void g1_stage(float (&acc)[116], uint32_t alo, uint32_t blo, uint32_t bar_full, uint32_t bar_h) {
  constexpr int s = Q * 14 + ST, sl = s % B_NSLOT;
  if (Q == 0) mbar_wait(bar_h + 8 * ST, 0);
  mbar_wait(bar_full + 8 * sl, (s / B_NSLOT) & 1);
  wg_fence();
  if (Q == 0) {
    wgmma_ss232<(2 * ST) * 256, 0x40000080u, (sl * B_SLOT) / 16, 32, ST != 0>(acc, alo, blo);
    wgmma_ss232<(2 * ST + 1) * 256, 0x40000080u, (sl * B_SLOT + 256) / 16, 32, 1>(acc, alo, blo);
  } else {
    wgmma_ss224<(2 * ST) * 256, 0x40000080u, (sl * B_SLOT) / 16, 32, ST != 0>(*(float(*)[112])acc, alo, blo);
    wgmma_ss224<(2 * ST + 1) * 256, 0x40000080u, (sl * B_SLOT + 256) / 16, 32, 1>(*(float(*)[112])acc, alo, blo);
  }
}

__global__ void __launch_bounds__(512, 1)
k_front(const __nv_bfloat16* __restrict__ x, const uint32_t* __restrict__ are, const uint32_t* __restrict__ aim,
        const uint32_t* __restrict__ bre, const uint32_t* __restrict__ bim, const uint32_t* __restrict__ cre,
        const uint32_t* __restrict__ cim, const unsigned short* __restrict__ logdt, const unsigned short* __restrict__ dskip,
        const uint4* __restrict__ wgate, const uint4* __restrict__ wup, const uint4* __restrict__ wdown) {
  extern __shared__ __align__(1024) unsigned char sm[];
  const uint32_t bar_rec = s2u(sm) + 4 * A_CH;
  if (threadIdx.x == 320) TR(0, 0);
  asm volatile("griddepcontrol.launch_dependents;");
  if (threadIdx.x == 160) { mbar_init(bar_rec, 4); asm volatile("fence.mbarrier_init.release.cluster;" ::: "memory"); }
  phase_a(sm, bar_rec, bar_rec + 8, x, are, aim, bre, bim, cre, cim, logdt, dskip, wgate, wup, wdown);
}

__global__ void __cluster_dims__(2, 1, 1) __launch_bounds__(384, 1) k_ffn(__nv_bfloat16* __restrict__ out) {
  extern __shared__ __align__(1024) unsigned char sm[];
  const uint32_t sb = s2u(sm);
  const int tid = threadIdx.x, warp = __shfl_sync(~0u, tid >> 5, 0), wg = warp >> 2, lane = tid & 31;
  const uint32_t bar_full = sb + B_BAR, bar_empty = bar_full + 64, bar_h = bar_full + 128, bar_cs = bar_full + 240,
                 bar_hh = bar_full + 304, bar_afree = bar_full + 336, bar_out = bar_full + 352;
  if (tid == 0) {
    TR(1, 0);
    for (int i = 0; i < B_NSLOT; i++) { mbar_init(bar_full + 8 * i, 1); mbar_init(bar_empty + 8 * i, 2); }
    asm volatile("fence.mbarrier_init.release.cluster;" ::: "memory");
  } else if (tid == 32) {
    for (int i = 0; i < 14; i++) mbar_init(bar_h + 8 * i, 1);
    asm volatile("fence.mbarrier_init.release.cluster;" ::: "memory");
  } else if (tid == 64) {
    mbar_init(bar_cs, 1);
    for (int i = 0; i < 4; i++) { mbar_init(bar_hh + 8 * i, 1); mbar_expect(bar_hh + 8 * i, 14336); }
    mbar_init(bar_afree, 4); mbar_init(bar_afree + 8, 2);
    for (int i = 0; i < 6; i++) mbar_init(bar_out + 8 * i, 128);
    asm volatile("fence.mbarrier_init.release.cluster;" ::: "memory");
  } else if (tid >= 128 && tid < 352) {
    sts128(sb + B_RING + ((tid - 128) >> 5) * B_SLOT + 14336 + (tid & 31) * 16, 0x3F803F80u, 0x3F803F80u, 0x3F803F80u, 0x3F803F80u);
  }
  asm volatile("fence.proxy.async.shared::cta;" ::: "memory");
  __syncthreads();
  asm volatile("barrier.cluster.arrive.relaxed.aligned;" ::: "memory");
  const int rank = blockIdx.x & 1, rt = blockIdx.x >> 3, j = blockIdx.x & 7, p = j >> 1, cg = 4 * rank + p;
  const int wq = warp & 3, t128 = tid & 127, g = lane >> 2, t = lane & 3;
  uint32_t ep, tag;
  auto load_ep = [&]() { asm volatile("ld.relaxed.gpu.global.u32 %0, [%1];" : "=r"(ep) : "l"(&g_cnt1) : "memory"); };
  auto a_slot = [&](int i, int own) { return B_SA + (i + (i >= own)) * 14336; };
  auto out_addr = [&](int cc, int w) { return sb + a_slot((cc & 2) + w, cg) + (cc & 1) * 7168; };
  auto in_cta = [&](int q) { return rt * 8 + ((p + 3 - q) & 3) * 2 + rank; };
  auto in_src = [&](int q, int cw) { return g_part + (size_t)(in_cta(q) * 3 + q) * 896 + cw * 112; };
  auto in_bad = [&](uint32_t (&in)[14]) { return ((in[3] ^ tag) | (in[7] ^ tag) | (in[11] ^ tag) | (in[13] ^ tag)) & 0x10000u; };
  auto in_load = [&](uint32_t (&in)[14], const uint4* gs) {
#pragma unroll
    for (int i = 0; i < 3; i++) ld128(gs + i * 32, in + 4 * i);
    asm volatile("{\n.reg .b64 v;\nld.relaxed.gpu.global.b64 v, [%2];\nmov.b64 {%0, %1}, v;\n}"
                 : "=r"(in[12]), "=r"(in[13]) : "l"((const uint2*)(gs + 96) - lane) : "memory");
  };
  auto in_check = [&](uint32_t (&in)[14], int q, int cw) {
    int it = 0;
    while (in_bad(in) && ++it < 400000) in_load(in, pin(in_src(q, cw) + lane));
  };

  if (wg == 2) {
    asm volatile("setmaxnreg.dec.sync.aligned.u32 40;");
    asm volatile("barrier.cluster.wait.aligned;" ::: "memory");
    asm volatile("griddepcontrol.wait;" ::: "memory");
    if (warp == 8) {
      if (lane == 0) TR(1, 1);
      const char* wsrc = (const char*)g_wimg + (size_t)j * 602112;
      const char* hsrc = (const char*)g_himg + (size_t)rt * 114688 + rank * 4096;
#pragma unroll
      for (int s = 0; s < 28; s++) {
        if (s < B_NSLOT) bulk_ld_mc_elect<4096>(sb + B_SA + s * 8192 + rank * 4096, hsrc + s * 8192, bar_h + 8 * s);
        if (s == B_NSLOT) {
#pragma unroll
          for (int i = 7; i < 14; i++) bulk_ld_mc_elect<4096>(sb + B_SA + i * 8192 + rank * 4096, hsrc + i * 8192, bar_h + 8 * i);
          bulk_ld_elect<7168>(sb + B_CS, g_cimg + j * 448, bar_cs);
        }
        if (s >= B_NSLOT) mbar_wait(bar_empty + 8 * (s % B_NSLOT), (s / B_NSLOT + 1) & 1);
        bulk_ld_elect<14336>(sb + B_RING + (s % B_NSLOT) * B_SLOT, wsrc + s * 14336, bar_full + 8 * (s % B_NSLOT));
      }
      const char* dsrc[2] = {wsrc + 401408 + rank * 100352, (const char*)g_wimg + (size_t)(j ^ 1) * 602112 + 401408 + rank * 100352};
#pragma unroll
      for (int i = 0; i < 16; i++) {
        const int ci = i < 3 ? 0 : i < 6 ? 1 : i < 8 ? i - 6 : i < 12 ? 2 : 3;
        const int kp = i < 3 ? i : i < 6 ? i - 3 : i < 8 ? 3 : (i & 3);
        mbar_wait(bar_empty + 8 * (i % B_NSLOT), (i / B_NSLOT + 1) & 1);
        bulk_ld_elect<12544>(sb + B_RING + (i % B_NSLOT) * B_SLOT, dsrc[kp >> 1] + ((p + 1 + ci) & 3) * 25088 + (kp & 1) * 12544, bar_full + 8 * (i % B_NSLOT));
      }
    } else if (warp >= 10) {
      const int t64 = tid - 320;
      load_ep();
      const int r = (lane >> 1) & 7, c = (j & 3) * 2 + (lane & 1);
      const uint32_t src = sb + B_SA + (t64 >> 4) * 2048 + (j >> 2) * 1024 + r * 128 + ((c ^ r) << 4);
      float a[16];
#pragma unroll
      for (int k = 0; k < 16; k++) a[k] = 0.f;
#pragma unroll 1
      for (int i = 0; i < 14; i++) {
        mbar_wait(bar_h + 8 * i, 0);
        uint4 v = lds128(src + i * 8192);
        float e[8] = {bf_lo(v.x), bf_hi(v.x), bf_lo(v.y), bf_hi(v.y), bf_lo(v.z), bf_hi(v.z), bf_lo(v.w), bf_hi(v.w)};
#pragma unroll
        for (int k = 0; k < 8; k++) { a[2 * k] += e[k]; a[2 * k + 1] = fmaf(e[k], e[k], a[2 * k + 1]); }
        __nanosleep(160);
      }
      __syncwarp();
      if (lane == 0) { asm volatile("mbarrier.arrive.shared::cluster.b64 _, [%0];" ::"r"(mapa(bar_afree, rank ^ 1)) : "memory"); }
#pragma unroll
      for (int rd = 0; rd < 4; rd++) {
        const int n = 8 >> rd;
        const bool up = lane & (2 * n);
#pragma unroll
        for (int k = 0; k < 8; k++) {
          if (k < n) {
            float keep = up ? a[k + n] : a[k], give = up ? a[k] : a[k + n];
            a[k] = keep + __shfl_xor_sync(~0u, give, 2 * n);
          }
        }
      }
      float* red = (float*)(sm + B_RED);
      red[(warp & 1) * 32 + (lane & 1) * 16 + (lane >> 1)] = a[0];
      bar_sync(1, 64);
      if (t64 < 16) {
        float mean = (red[2 * t64] + red[32 + 2 * t64]) * (1.f / DM);
        float var = fmaxf(fmaf(-mean, mean, (red[2 * t64 + 1] + red[33 + 2 * t64]) * (1.f / DM)), 0.f);
        float rs = ln_rstd(var);
        asm volatile("st.relaxed.gpu.global.u32 [%0], %1;"
                     ::"l"(g_stat2 + rt * 128 + j * 16 + t64), "r"((__float_as_uint(rs * rs) & ~1u) | ((ep >> 7) & 1u)) : "memory");
      }
      if (t64 == 0) TR(1, 2);
      if (lane == 0) {
        const int w = warp & 1;
        for (int cc = 0; cc < 2; cc++) {
          mbar_wait(bar_out + 8 * (cc * 2 + w), 0);
          asm volatile("cp.async.bulk.global.shared::cta.bulk_group [%0], [%1], 7168;"
                       ::"l"(g_part + (size_t)(blockIdx.x * 3 + cc) * 896 + w * 448), "r"(out_addr(cc, w)) : "memory");
          if (w) TR(1, 27 + cc);
        }
        asm volatile("cp.async.bulk.commit_group;" ::: "memory");
        asm volatile("cp.async.bulk.wait_group 0;" ::: "memory");
      }
    }
  } else {
    asm volatile("setmaxnreg.inc.sync.aligned.u32 232;");
    asm volatile("barrier.cluster.wait.aligned;" ::: "memory");
    uint32_t hh[56];
    const bool relt = t128 == 0;
    auto release = [&](int sl) { if (relt) mbar_arrive(bar_empty + 8 * sl); };
    auto send_hh = [&](int q) {
      const uint32_t da = mapa(sb + a_slot(2 * q + wg, cg ^ 4) + t128 * 16, rank ^ 1), db = mapa(bar_hh + 8 * (2 * q + wg), rank ^ 1);
#pragma unroll
      for (int i = 0; i < 7; i++)
        asm volatile("st.async.weak.shared::cluster.mbarrier::complete_tx::bytes.v4.b32 [%0], {%1, %2, %3, %4}, [%5];"
                     ::"r"(da + i * 2048), "r"(hh[28 * q + 4 * i]), "r"(hh[28 * q + 4 * i + 1]),
                       "r"(hh[28 * q + 4 * i + 2]), "r"(hh[28 * q + 4 * i + 3]), "r"(db) : "memory");
    };
    uint32_t alo = ((sb + B_SA + wg * 1024) & 0x3FFFF) >> 4;
    uint32_t blo = (((sb + B_RING) & 0x3FFFF) >> 4) | (8u << 16);
    const uint32_t clo = ((sb + B_CS) & 0x3FFFF) >> 4;
    uint32_t nm0, nm1;
    if (wg == 1) bar_sync(3, 256);
#define G1S(Q, ST) do { if (ST % 7 == 0) { alo = pin(alo); blo = pin(blo); }   \
      g1_stage<Q, ST>(acc, alo, blo, bar_full, bar_h); wg_commit(); \
      if (ST > 0) { wg_wait<1>(); release((Q * 14 + ST - 1) % B_NSLOT); } } while (0)
#define G1HH(Q) do { \
      _Pragma("unroll") \
      for (int i = 0; i < 28; i++) hh[28 * Q + i] = pack_bf16(acc[2 * i] * acc[56 + 2 * i], acc[2 * i + 1] * acc[57 + 2 * i]); \
    } while (0)
    {
      float acc[116];
      G1S(0, 0);
      if (tid == 0) TR(1, 3);
      G1S(0, 1);
      if (wg == 0) asm volatile("bar.arrive 3, 256;" ::: "memory");
      G1S(0, 2); G1S(0, 3); G1S(0, 4); G1S(0, 5); G1S(0, 6); G1S(0, 7); G1S(0, 8); G1S(0, 9); G1S(0, 10); G1S(0, 11); G1S(0, 12);
      G1S(0, 13);
      if (tid == 0) TR(1, 4);
      mbar_wait(bar_cs, 0);
      wg_wait<0>(); reg_fence(acc); release(13 % B_NSLOT);
      {
        const uint32_t msk = t == 0 ? 0xFFFFFFFFu : t == 1 ? 0xFFFFu : 0u;
        const float a = acc[112] * (-1.f / DM), b = acc[114] * (-1.f / DM);
        nm0 = pack_bf16(a, a) & msk; nm1 = pack_bf16(b, b) & msk;
      }
      wg_fence();
      wgmma_rs224<0, 8, 1>(*(float(*)[112])acc, nm0, nm1, 0u, 0u, clo);
      wg_commit(); wg_wait<0>(); reg_fence(acc);
      G1HH(0);
      if (tid == 0) TR(1, 5);
      G1S(1, 0); G1S(1, 1); G1S(1, 2); G1S(1, 3); G1S(1, 4); G1S(1, 5); G1S(1, 6);
      if (relt) asm volatile("mbarrier.arrive.shared::cluster.b64 _, [%0];" ::"r"(mapa(bar_afree, rank ^ 1)) : "memory");
      G1S(1, 7); G1S(1, 8); G1S(1, 9);
      if (relt) asm volatile("mbarrier.arrive.shared::cluster.b64 _, [%0];" ::"r"(mapa(bar_afree + 8, rank ^ 1)) : "memory");
      mbar_wait(bar_afree, 0);
      send_hh(0);
      G1S(1, 10); G1S(1, 11); G1S(1, 12);
      load_ep();
      g1_stage<1, 13>(acc, alo, blo, bar_full, bar_h);
      wgmma_rs224<224, 8, 1>(*(float(*)[112])acc, nm0, nm1, 0u, 0u, clo);
      wg_commit(); wg_wait<1>(); release(26 % B_NSLOT);
      wg_wait<0>(); reg_fence(acc); release(27 % B_NSLOT);
      G1HH(1);
      if (tid == 0) TR(1, 6);
    }
    float accA[28], accB[28];
    uint32_t ph0[28], ph1[28];
    ep = pin(ep >> 7); tag = pin((ep & 1u) << 16);
#define ISSUE(acc, I, a, FIRST) do { \
      constexpr int s_ = 28 + (I), sl_ = s_ % B_NSLOT; \
      if (sl_ == 0) blo = pin(blo); \
      mbar_wait(bar_full + 8 * sl_, (s_ / B_NSLOT) & 1); \
      wg_fence(); \
      wgmma_rs56<(sl_ * B_SLOT + 0 * 256) / 16, 112, !(FIRST)>(acc, (a)[0], (a)[1], (a)[2], (a)[3], blo); \
      wgmma_rs56<(sl_ * B_SLOT + 1 * 256) / 16, 112, 1>(acc, (a)[4], (a)[5], (a)[6], (a)[7], blo); \
      wgmma_rs56<(sl_ * B_SLOT + 2 * 256) / 16, 112, 1>(acc, (a)[8], (a)[9], (a)[10], (a)[11], blo); \
      wgmma_rs56<(sl_ * B_SLOT + 3 * 256) / 16, 112, 1>(acc, (a)[12], (a)[13], (a)[14], (a)[15], blo); \
      wgmma_rs56<(sl_ * B_SLOT + 4 * 256) / 16, 112, 1>(acc, (a)[16], (a)[17], (a)[18], (a)[19], blo); \
      wgmma_rs56<(sl_ * B_SLOT + 5 * 256) / 16, 112, 1>(acc, (a)[20], (a)[21], (a)[22], (a)[23], blo); \
      wgmma_rs56<(sl_ * B_SLOT + 6 * 256) / 16, 112, 1>(acc, (a)[24], (a)[25], (a)[26], (a)[27], blo); \
      wg_commit(); } while (0)
    auto rel = [&](int i) { release((28 + i) % B_NSLOT); };
    auto tg = [&](uint32_t v) { return (v & 0xFFFEFFFFu) | tag; };
    auto send = [&](float (&acc)[28], int cc) {
      reg_fence(acc);
      const uint32_t a = out_addr(cc, wg) + wq * 1792;
#pragma unroll
      for (int q = 0; q < 3; q++)
        sts128(a + q * 512 + lane * 16, pack_bf16(acc[8 * q], acc[8 * q + 1]), pack_bf16(acc[8 * q + 2], acc[8 * q + 3]),
               pack_bf16(acc[8 * q + 4], acc[8 * q + 5]), tg(pack_bf16(acc[8 * q + 6], acc[8 * q + 7])));
      sts64(a + 1536 + lane * 8, pack_bf16(acc[24], acc[25]), tg(pack_bf16(acc[26], acc[27])));
      asm volatile("fence.proxy.async.shared::cta;" ::: "memory");
      mbar_arrive(bar_out + 8 * (cc * 2 + wg));
    };
    auto load_hh = [&](uint32_t (&d)[28], int q) {
      mbar_wait(bar_hh + 8 * (2 * q + wg), 0);
      const uint32_t a = sb + a_slot(2 * q + wg, cg) + t128 * 16;
#pragma unroll
      for (int i = 0; i < 7; i++) {
        const uint4 v = lds128(a + i * 2048);
        d[4 * i] = v.x; d[4 * i + 1] = v.y; d[4 * i + 2] = v.z; d[4 * i + 3] = v.w;
      }
    };
    ISSUE(accA, 0, hh, true);
    mbar_wait(bar_afree + 8, 0);
    send_hh(1);
    ISSUE(accA, 1, hh + 28, false);
    load_hh(ph0, 0);
    wg_wait<1>(); rel(0);
    ISSUE(accA, 2, ph0, false);      wg_wait<1>(); rel(1);
    ISSUE(accB, 3, hh, true);        wg_wait<1>(); rel(2);
    ISSUE(accB, 4, hh + 28, false);  wg_wait<1>(); rel(3);
    ISSUE(accB, 5, ph0, false);
    if (tid == 0) TR(1, 11);
    load_hh(ph1, 1);
    wg_wait<1>(); rel(4);
    ISSUE(accA, 6, ph1, false);      wg_wait<1>(); rel(5);
    ISSUE(accB, 7, ph1, false);      wg_wait<1>(); rel(6); send(accA, 0);
    ISSUE(accA, 8, hh, true);        wg_wait<1>(); rel(7); send(accB, 1);
    if (tid == 0) TR(1, 13);
    ISSUE(accA, 9, hh + 28, false);  wg_wait<1>(); rel(8);
    ISSUE(accA, 10, ph0, false);
    ISSUE(accA, 11, ph1, false);
    const int row = rt * 128 + wg * 64 + wq * 16 + g;
    uint32_t r20, r21;
    asm volatile("ld.relaxed.gpu.global.u32 %0, [%1];" : "=r"(r20) : "l"(g_stat2 + row) : "memory");
    asm volatile("ld.relaxed.gpu.global.u32 %0, [%1];" : "=r"(r21) : "l"(g_stat2 + row + 8) : "memory");
    ISSUE(accB, 12, hh, true);
    wg_wait<1>();
    {
      reg_fence(accA);
      uint4* pd = g_part + (size_t)(blockIdx.x * 3 + 2) * 896 + warp * 112 + lane;
#pragma unroll
      for (int q = 0; q < 3; q++)
        st128(pd + q * 32, pack_bf16(accA[8 * q], accA[8 * q + 1]), pack_bf16(accA[8 * q + 2], accA[8 * q + 3]),
              pack_bf16(accA[8 * q + 4], accA[8 * q + 5]), tg(pack_bf16(accA[8 * q + 6], accA[8 * q + 7])));
      asm volatile("{\n.reg .b64 v;\nmov.b64 v, {%1, %2};\nst.relaxed.gpu.global.b64 [%0], v;\n}"
                   ::"l"((uint2*)(pd + 96) - lane), "r"(pack_bf16(accA[24], accA[25])), "r"(tg(pack_bf16(accA[26], accA[27]))) : "memory");
    }
    if (tid == 0) TR(1, 16);
    ISSUE(accB, 13, hh + 28, false);
    ISSUE(accB, 14, ph0, false);
    uint32_t in0[14], in1[14], in2[14];
    in_load(in0, in_src(0, warp) + lane);
    in_load(in1, in_src(1, warp) + lane);
    ISSUE(accB, 15, ph1, false);
    if (tid == 0) TR(1, 7);
    {
      int it = 0;
      while ((((r20 ^ ep) | (r21 ^ ep)) & 1u) && ++it < 400000) {
        asm volatile("ld.relaxed.gpu.global.u32 %0, [%1];" : "=r"(r20) : "l"(g_stat2 + row) : "memory");
        asm volatile("ld.relaxed.gpu.global.u32 %0, [%1];" : "=r"(r21) : "l"(g_stat2 + row + 8) : "memory");
      }
    }
    wg_wait<1>();
    in_load(in2, in_src(2, warp) + lane);
    in_check(in0, 0, warp); in_check(in1, 1, warp);
#pragma unroll
    for (int i = 0; i < 14; i++) { accA[2 * i] = bf_lo(in0[i]) + bf_lo(in1[i]); accA[2 * i + 1] = bf_hi(in0[i]) + bf_hi(in1[i]); }
    if (tid == 0) TR(1, 12);
    wg_wait<0>();
    reg_fence(accB);
    uint32_t hres[16];
#pragma unroll
    for (int i = 0; i < 4; i++) {
      int qq = lane >> 3, r = lane & 7, kg = 7 * cg + 2 * i + (qq >> 1), c = 2 * wq + (qq & 1);
      if (kg > 55) kg = 55;
      asm volatile("ldmatrix.sync.aligned.m8n8.x4.trans.shared.b16 {%0,%1,%2,%3}, [%4];"
                   : "=r"(hres[4 * i]), "=r"(hres[4 * i + 1]), "=r"(hres[4 * i + 2]), "=r"(hres[4 * i + 3])
                   : "r"(sb + B_SA + kg * 2048 + wg * 1024 + r * 128 + ((c ^ r) << 4)) : "memory");
    }
#pragma unroll
    for (int i = 0; i < 28; i++) accB[i] += accA[i];
    if (tid == 0) TR(1, 9);
    in_check(in2, 2, warp);
#pragma unroll
    for (int i = 0; i < 14; i++) { accB[2 * i] += bf_lo(in2[i]); accB[2 * i + 1] += bf_hi(in2[i]); }
    uint32_t* o0 = (uint32_t*)(out + (size_t)row * DM + 56 * cg + 2 * t);
    uint32_t* o1 = o0 + 8 * DM / 2;
#pragma unroll
    for (int i = 0; i < 7; i++) {
      o0[4 * i] = hadd2_bf(hres[2 * i], pack_bf16(accB[4 * i] * __uint_as_float(r20), accB[4 * i + 1] * __uint_as_float(r20)));
      o1[4 * i] = hadd2_bf(hres[2 * i + 1], pack_bf16(accB[4 * i + 2] * __uint_as_float(r21), accB[4 * i + 3] * __uint_as_float(r21)));
    }
    if (tid == 0) TR(1, 10);
    if (tid == 128) TR(1, 15);
  }
}

extern "C" void kernel_launch(void* const* d_in, const int* in_sizes, int n_in, void* d_out, int out_size) {
  const __nv_bfloat16* x = (const __nv_bfloat16*)d_in[0];
  const __nv_bfloat16 *are = (const __nv_bfloat16*)d_in[1], *aim = (const __nv_bfloat16*)d_in[2], *bre = (const __nv_bfloat16*)d_in[3],
                      *bim = (const __nv_bfloat16*)d_in[4], *cre = (const __nv_bfloat16*)d_in[5], *cim = (const __nv_bfloat16*)d_in[6],
                      *logdt = (const __nv_bfloat16*)d_in[7], *dskip = (const __nv_bfloat16*)d_in[8];
  const __nv_bfloat16 *wg = (const __nv_bfloat16*)d_in[10], *wu = (const __nv_bfloat16*)d_in[11], *wd = (const __nv_bfloat16*)d_in[12];

  static bool init = false;
  if (!init) {
    init = true;
    cudaFuncSetAttribute(k_ffn, cudaFuncAttributeMaxDynamicSharedMemorySize, B_SMEM);
    cudaFuncSetAttribute(k_front, cudaFuncAttributeMaxDynamicSharedMemorySize, A_SMEM);
  }
  cudaStream_t st = cudaStreamPerThread;
  k_front<<<128, 512, A_SMEM, st>>>(
      x, (const uint32_t*)are, (const uint32_t*)aim, (const uint32_t*)bre, (const uint32_t*)bim, (const uint32_t*)cre, (const uint32_t*)cim,
      (const unsigned short*)logdt, (const unsigned short*)dskip, (const uint4*)wg, (const uint4*)wu, (const uint4*)wd);
  cudaLaunchConfig_t cfg = {};
  cfg.gridDim = dim3(128); cfg.blockDim = dim3(384); cfg.dynamicSmemBytes = B_SMEM; cfg.stream = st;
  cudaLaunchAttribute at[1];
  at[0].id = cudaLaunchAttributeProgrammaticStreamSerialization; at[0].val.programmaticStreamSerializationAllowed = 1;
  cfg.attrs = at; cfg.numAttrs = 1;
  cudaLaunchKernelEx(&cfg, k_ffn, (__nv_bfloat16*)d_out);
}
```

```cpp
#include <cuda_runtime.h>
#include <cuda_bf16.h>
#include <cuda_fp16.h>
#include <stdint.h>

constexpr int LSEQ = 2048, DM = 448;

__device__ uint4    g_himg[16 * 114688 / 16];
__device__ uint4    g_cimg[8 * 2 * 224];
__device__ uint32_t g_stat2[LSEQ];
__device__ uint4    g_part[128 * 3 * 896];
__device__ uint4    g_wimg[8 * 602112 / 16];
__device__ uint4    g_ux[DM * 128 * 4];
__device__ unsigned g_cnt1;

#define TR(k, i) do {} while (0)
__device__ __forceinline__ uint32_t s2u(const void* p) { return (uint32_t)__cvta_generic_to_shared(p); }
__device__ __forceinline__ void mbar_init(uint32_t b, int c) { asm volatile("mbarrier.init.shared::cta.b64 [%0], %1;" ::"r"(b), "r"(c)); }
__device__ __forceinline__ void mbar_expect(uint32_t b, int bytes) { asm volatile("mbarrier.arrive.expect_tx.shared::cta.b64 _, [%0], %1;" ::"r"(b), "r"(bytes) : "memory"); }
__device__ __forceinline__ void mbar_arrive(uint32_t b) { asm volatile("mbarrier.arrive.shared::cta.b64 _, [%0];" ::"r"(b) : "memory"); }
__device__ __forceinline__ void mbar_wait(uint32_t b, int ph) {
  asm volatile("{\n.reg .pred p;\n.reg .b32 n;\nmov.b32 n, 0;\nLW:\nmbarrier.try_wait.parity.shared::cta.b64 p, [%0], %1;\n@p bra LD;\n"
               "add.u32 n, n, 1;\nsetp.lt.u32 p, n, 4000000;\n@p bra LW;\ntrap;\nLD:\n}" ::"r"(b), "r"(ph) : "memory");
}
__device__ __forceinline__ bool mbar_test(uint32_t b, int ph) {
  uint32_t ok;
  asm volatile("{\n.reg .pred p;\nmbarrier.test_wait.parity.shared::cta.b64 p, [%1], %2;\nselp.u32 %0, 1, 0, p;\n}" : "=r"(ok) : "r"(b), "r"(ph) : "memory");
  return ok;
}
__device__ __forceinline__ void wg_fence() { asm volatile("wgmma.fence.sync.aligned;" ::: "memory"); }
__device__ __forceinline__ void wg_commit() { asm volatile("wgmma.commit_group.sync.aligned;" ::: "memory"); }
template <int N> __device__ __forceinline__ void wg_wait() { asm volatile("wgmma.wait_group.sync.aligned %0;" ::"n"(N) : "memory"); }
template <int N> __device__ __forceinline__ void reg_fence(float (&a)[N]) {
#pragma unroll
  for (int i = 0; i < N; i++) asm volatile("" : "+f"(a[i])::"memory");
}
__device__ __forceinline__ uint32_t pack_bf16(float lo, float hi) {
  uint32_t r; asm("cvt.rn.bf16x2.f32 %0, %1, %2;" : "=r"(r) : "f"(hi), "f"(lo)); return r;
}
__device__ __forceinline__ float bf_lo(uint32_t v) { return __uint_as_float(v << 16); }
__device__ __forceinline__ float bf_hi(uint32_t v) { return __uint_as_float(v & 0xFFFF0000u); }
__device__ __forceinline__ float rbf(float x) { return __bfloat162float(__float2bfloat16_rn(x)); }
__device__ __forceinline__ uint32_t hmul2_bf(uint32_t a, uint32_t b) { uint32_t r; asm("mul.rn.bf16x2 %0, %1, %2;" : "=r"(r) : "r"(a), "r"(b)); return r; }
__device__ __forceinline__ uint32_t hadd2_bf(uint32_t a, uint32_t b) { uint32_t r; asm("add.rn.bf16x2 %0, %1, %2;" : "=r"(r) : "r"(a), "r"(b)); return r; }
__device__ __forceinline__ void bulk_ld(uint32_t dst, const void* src, int bytes, uint32_t bar) {
  asm volatile("cp.async.bulk.shared::cluster.global.mbarrier::complete_tx::bytes [%0], [%1], %2, [%3];"
               ::"r"(dst), "l"(src), "r"(bytes), "r"(bar) : "memory");
}

template <int BYTES>
__device__ __forceinline__ void bulk_ld_elect(uint32_t dst, const void* src, uint32_t bar) {
  asm volatile("{\n.reg .pred p;\nelect.sync _|p, 0xffffffff;\n"
               "@p mbarrier.arrive.expect_tx.shared::cta.b64 _, [%2], %3;\n"
               "@p cp.async.bulk.shared::cluster.global.mbarrier::complete_tx::bytes [%0], [%1], %3, [%2];\n}"
               ::"r"(dst), "l"(src), "r"(bar), "n"(BYTES) : "memory");
}
template <int BYTES>
__device__ __forceinline__ void bulk_ld_mc_elect(uint32_t dst, const void* src, uint32_t bar) {
  asm volatile("{\n.reg .pred p;\nelect.sync _|p, 0xffffffff;\n"
               "@p mbarrier.arrive.expect_tx.shared::cta.b64 _, [%2], %3;\n"
               "@p cp.async.bulk.shared::cluster.global.mbarrier::complete_tx::bytes.multicast::cluster [%0], [%1], %4, [%2], %5;\n}"
               ::"r"(dst), "l"(src), "r"(bar), "n"(2 * BYTES), "n"(BYTES), "h"((uint16_t)3) : "memory");
}
template <int AOFF, uint32_t AHI, int BOFF, uint32_t BHI, int ACC>
__device__ __forceinline__ void wgmma_ss224(float (&d)[112], uint32_t alo, uint32_t blo) {
  asm volatile("{\n.reg .pred p;\n.reg .b64 ad, bd;\nsetp.ne.b32 p, %118, 0;\n"
    "mov.b64 ad, {%112, %115};\nadd.s64 ad, ad, %114;\nmov.b64 bd, {%113, %117};\nadd.s64 bd, bd, %116;\n"
    "wgmma.mma_async.sync.aligned.m64n224k16.f32.bf16.bf16 {%0,%1,%2,%3,%4,%5,%6,%7,%8,%9,%10,%11,%12,%13,%14,%15,%16,%17,%18,%19,%20,%21,%22,%23,%24,%25,%26,%27,%28,%29,%30,%31,%32,%33,%34,%35,%36,%37,%38,%39,%40,%41,%42,%43,%44,%45,%46,%47,%48,%49,%50,%51,%52,%53,%54,%55,%56,%57,%58,%59,%60,%61,%62,%63,%64,%65,%66,%67,%68,%69,%70,%71,%72,%73,%74,%75,%76,%77,%78,%79,%80,%81,%82,%83,%84,%85,%86,%87,%88,%89,%90,%91,%92,%93,%94,%95,%96,%97,%98,%99,%100,%101,%102,%103,%104,%105,%106,%107,%108,%109,%110,%111}, ad, bd, p, 1, 1, 1, 1;\n}\n"
    : "+f"(d[0]),"+f"(d[1]),"+f"(d[2]),"+f"(d[3]),"+f"(d[4]),"+f"(d[5]),"+f"(d[6]),"+f"(d[7]),"+f"(d[8]),"+f"(d[9]),"+f"(d[10]),"+f"(d[11]),"+f"(d[12]),"+f"(d[13]),"+f"(d[14]),"+f"(d[15]),"+f"(d[16]),"+f"(d[17]),"+f"(d[18]),"+f"(d[19]),"+f"(d[20]),"+f"(d[21]),"+f"(d[22]),"+f"(d[23]),"+f"(d[24]),"+f"(d[25]),"+f"(d[26]),"+f"(d[27]),"+f"(d[28]),"+f"(d[29]),"+f"(d[30]),"+f"(d[31]),"+f"(d[32]),"+f"(d[33]),"+f"(d[34]),"+f"(d[35]),"+f"(d[36]),"+f"(d[37]),"+f"(d[38]),"+f"(d[39]),"+f"(d[40]),"+f"(d[41]),"+f"(d[42]),"+f"(d[43]),"+f"(d[44]),"+f"(d[45]),"+f"(d[46]),"+f"(d[47]),"+f"(d[48]),"+f"(d[49]),"+f"(d[50]),"+f"(d[51]),"+f"(d[52]),"+f"(d[53]),"+f"(d[54]),"+f"(d[55]),"+f"(d[56]),"+f"(d[57]),"+f"(d[58]),"+f"(d[59]),"+f"(d[60]),"+f"(d[61]),"+f"(d[62]),"+f"(d[63]),"+f"(d[64]),"+f"(d[65]),"+f"(d[66]),"+f"(d[67]),"+f"(d[68]),"+f"(d[69]),"+f"(d[70]),"+f"(d[71]),"+f"(d[72]),"+f"(d[73]),"+f"(d[74]),"+f"(d[75]),"+f"(d[76]),"+f"(d[77]),"+f"(d[78]),"+f"(d[79]),"+f"(d[80]),"+f"(d[81]),"+f"(d[82]),"+f"(d[83]),"+f"(d[84]),"+f"(d[85]),"+f"(d[86]),"+f"(d[87]),"+f"(d[88]),"+f"(d[89]),"+f"(d[90]),"+f"(d[91]),"+f"(d[92]),"+f"(d[93]),"+f"(d[94]),"+f"(d[95]),"+f"(d[96]),"+f"(d[97]),"+f"(d[98]),"+f"(d[99]),"+f"(d[100]),"+f"(d[101]),"+f"(d[102]),"+f"(d[103]),"+f"(d[104]),"+f"(d[105]),"+f"(d[106]),"+f"(d[107]),"+f"(d[108]),"+f"(d[109]),"+f"(d[110]),"+f"(d[111])
    : "r"(alo), "r"(blo), "n"(AOFF), "n"(AHI), "n"(BOFF), "n"(BHI), "n"(ACC));
}
template <int AOFF, uint32_t AHI, int BOFF, uint32_t BHI, int ACC>
__device__ __forceinline__ void wgmma_ss232(float (&d)[116], uint32_t alo, uint32_t blo) {
  asm volatile("{\n.reg .pred p;\n.reg .b64 ad, bd;\nsetp.ne.b32 p, %122, 0;\n"
    "mov.b64 ad, {%116, %119};\nadd.s64 ad, ad, %118;\nmov.b64 bd, {%117, %121};\nadd.s64 bd, bd, %120;\n"
    "wgmma.mma_async.sync.aligned.m64n232k16.f32.bf16.bf16 {%0,%1,%2,%3,%4,%5,%6,%7,%8,%9,%10,%11,%12,%13,%14,%15,%16,%17,%18,%19,%20,%21,%22,%23,%24,%25,%26,%27,%28,%29,%30,%31,%32,%33,%34,%35,%36,%37,%38,%39,%40,%41,%42,%43,%44,%45,%46,%47,%48,%49,%50,%51,%52,%53,%54,%55,%56,%57,%58,%59,%60,%61,%62,%63,%64,%65,%66,%67,%68,%69,%70,%71,%72,%73,%74,%75,%76,%77,%78,%79,%80,%81,%82,%83,%84,%85,%86,%87,%88,%89,%90,%91,%92,%93,%94,%95,%96,%97,%98,%99,%100,%101,%102,%103,%104,%105,%106,%107,%108,%109,%110,%111,%112,%113,%114,%115}, ad, bd, p, 1, 1, 1, 1;\n}\n"
    : "+f"(d[0]),"+f"(d[1]),"+f"(d[2]),"+f"(d[3]),"+f"(d[4]),"+f"(d[5]),"+f"(d[6]),"+f"(d[7]),"+f"(d[8]),"+f"(d[9]),"+f"(d[10]),"+f"(d[11]),"+f"(d[12]),"+f"(d[13]),"+f"(d[14]),"+f"(d[15]),"+f"(d[16]),"+f"(d[17]),"+f"(d[18]),"+f"(d[19]),"+f"(d[20]),"+f"(d[21]),"+f"(d[22]),"+f"(d[23]),"+f"(d[24]),"+f"(d[25]),"+f"(d[26]),"+f"(d[27]),"+f"(d[28]),"+f"(d[29]),"+f"(d[30]),"+f"(d[31]),"+f"(d[32]),"+f"(d[33]),"+f"(d[34]),"+f"(d[35]),"+f"(d[36]),"+f"(d[37]),"+f"(d[38]),"+f"(d[39]),"+f"(d[40]),"+f"(d[41]),"+f"(d[42]),"+f"(d[43]),"+f"(d[44]),"+f"(d[45]),"+f"(d[46]),"+f"(d[47]),"+f"(d[48]),"+f"(d[49]),"+f"(d[50]),"+f"(d[51]),"+f"(d[52]),"+f"(d[53]),"+f"(d[54]),"+f"(d[55]),"+f"(d[56]),"+f"(d[57]),"+f"(d[58]),"+f"(d[59]),"+f"(d[60]),"+f"(d[61]),"+f"(d[62]),"+f"(d[63]),"+f"(d[64]),"+f"(d[65]),"+f"(d[66]),"+f"(d[67]),"+f"(d[68]),"+f"(d[69]),"+f"(d[70]),"+f"(d[71]),"+f"(d[72]),"+f"(d[73]),"+f"(d[74]),"+f"(d[75]),"+f"(d[76]),"+f"(d[77]),"+f"(d[78]),"+f"(d[79]),"+f"(d[80]),"+f"(d[81]),"+f"(d[82]),"+f"(d[83]),"+f"(d[84]),"+f"(d[85]),"+f"(d[86]),"+f"(d[87]),"+f"(d[88]),"+f"(d[89]),"+f"(d[90]),"+f"(d[91]),"+f"(d[92]),"+f"(d[93]),"+f"(d[94]),"+f"(d[95]),"+f"(d[96]),"+f"(d[97]),"+f"(d[98]),"+f"(d[99]),"+f"(d[100]),"+f"(d[101]),"+f"(d[102]),"+f"(d[103]),"+f"(d[104]),"+f"(d[105]),"+f"(d[106]),"+f"(d[107]),"+f"(d[108]),"+f"(d[109]),"+f"(d[110]),"+f"(d[111]),"+f"(d[112]),"+f"(d[113]),"+f"(d[114]),"+f"(d[115])
    : "r"(alo), "r"(blo), "n"(AOFF), "n"(AHI), "n"(BOFF), "n"(BHI), "n"(ACC));
}
template <int OFF, uint32_t BHI, int ACC>
__device__ __forceinline__ void wgmma_rs224(float (&d)[112], uint32_t a0, uint32_t a1, uint32_t a2, uint32_t a3, uint32_t blo) {
  asm volatile("{\n.reg .pred p;\n.reg .b64 bd;\nsetp.ne.b32 p, %119, 0;\nmov.b64 bd, {%116, %118};\nadd.s64 bd, bd, %117;\n"
    "wgmma.mma_async.sync.aligned.m64n224k16.f32.bf16.bf16 {%0,%1,%2,%3,%4,%5,%6,%7,%8,%9,%10,%11,%12,%13,%14,%15,%16,%17,%18,%19,%20,%21,%22,%23,%24,%25,%26,%27,%28,%29,%30,%31,%32,%33,%34,%35,%36,%37,%38,%39,%40,%41,%42,%43,%44,%45,%46,%47,%48,%49,%50,%51,%52,%53,%54,%55,%56,%57,%58,%59,%60,%61,%62,%63,%64,%65,%66,%67,%68,%69,%70,%71,%72,%73,%74,%75,%76,%77,%78,%79,%80,%81,%82,%83,%84,%85,%86,%87,%88,%89,%90,%91,%92,%93,%94,%95,%96,%97,%98,%99,%100,%101,%102,%103,%104,%105,%106,%107,%108,%109,%110,%111}, {%112,%113,%114,%115}, bd, p, 1, 1, 1;\n}\n"
    : "+f"(d[0]),"+f"(d[1]),"+f"(d[2]),"+f"(d[3]),"+f"(d[4]),"+f"(d[5]),"+f"(d[6]),"+f"(d[7]),"+f"(d[8]),"+f"(d[9]),"+f"(d[10]),"+f"(d[11]),"+f"(d[12]),"+f"(d[13]),"+f"(d[14]),"+f"(d[15]),"+f"(d[16]),"+f"(d[17]),"+f"(d[18]),"+f"(d[19]),"+f"(d[20]),"+f"(d[21]),"+f"(d[22]),"+f"(d[23]),"+f"(d[24]),"+f"(d[25]),"+f"(d[26]),"+f"(d[27]),"+f"(d[28]),"+f"(d[29]),"+f"(d[30]),"+f"(d[31]),"+f"(d[32]),"+f"(d[33]),"+f"(d[34]),"+f"(d[35]),"+f"(d[36]),"+f"(d[37]),"+f"(d[38]),"+f"(d[39]),"+f"(d[40]),"+f"(d[41]),"+f"(d[42]),"+f"(d[43]),"+f"(d[44]),"+f"(d[45]),"+f"(d[46]),"+f"(d[47]),"+f"(d[48]),"+f"(d[49]),"+f"(d[50]),"+f"(d[51]),"+f"(d[52]),"+f"(d[53]),"+f"(d[54]),"+f"(d[55]),"+f"(d[56]),"+f"(d[57]),"+f"(d[58]),"+f"(d[59]),"+f"(d[60]),"+f"(d[61]),"+f"(d[62]),"+f"(d[63]),"+f"(d[64]),"+f"(d[65]),"+f"(d[66]),"+f"(d[67]),"+f"(d[68]),"+f"(d[69]),"+f"(d[70]),"+f"(d[71]),"+f"(d[72]),"+f"(d[73]),"+f"(d[74]),"+f"(d[75]),"+f"(d[76]),"+f"(d[77]),"+f"(d[78]),"+f"(d[79]),"+f"(d[80]),"+f"(d[81]),"+f"(d[82]),"+f"(d[83]),"+f"(d[84]),"+f"(d[85]),"+f"(d[86]),"+f"(d[87]),"+f"(d[88]),"+f"(d[89]),"+f"(d[90]),"+f"(d[91]),"+f"(d[92]),"+f"(d[93]),"+f"(d[94]),"+f"(d[95]),"+f"(d[96]),"+f"(d[97]),"+f"(d[98]),"+f"(d[99]),"+f"(d[100]),"+f"(d[101]),"+f"(d[102]),"+f"(d[103]),"+f"(d[104]),"+f"(d[105]),"+f"(d[106]),"+f"(d[107]),"+f"(d[108]),"+f"(d[109]),"+f"(d[110]),"+f"(d[111])
    : "r"(a0), "r"(a1), "r"(a2), "r"(a3), "r"(blo), "n"(OFF), "n"(BHI), "n"(ACC));
}
template <int OFF, uint32_t BHI, int ACC>
__device__ __forceinline__ void wgmma_rs56(float (&d)[28], uint32_t a0, uint32_t a1, uint32_t a2, uint32_t a3, uint32_t blo) {
  asm volatile("{\n.reg .pred p;\n.reg .b64 bd;\nsetp.ne.b32 p, %35, 0;\nmov.b64 bd, {%32, %34};\nadd.s64 bd, bd, %33;\n"
    "wgmma.mma_async.sync.aligned.m64n56k16.f32.bf16.bf16 {%0,%1,%2,%3,%4,%5,%6,%7,%8,%9,%10,%11,%12,%13,%14,%15,%16,%17,%18,%19,%20,%21,%22,%23,%24,%25,%26,%27}, {%28,%29,%30,%31}, bd, p, 1, 1, 1;\n}\n"
    : "+f"(d[0]),"+f"(d[1]),"+f"(d[2]),"+f"(d[3]),"+f"(d[4]),"+f"(d[5]),"+f"(d[6]),"+f"(d[7]),"+f"(d[8]),"+f"(d[9]),"+f"(d[10]),"+f"(d[11]),"+f"(d[12]),"+f"(d[13]),"+f"(d[14]),"+f"(d[15]),"+f"(d[16]),"+f"(d[17]),"+f"(d[18]),"+f"(d[19]),"+f"(d[20]),"+f"(d[21]),"+f"(d[22]),"+f"(d[23]),"+f"(d[24]),"+f"(d[25]),"+f"(d[26]),"+f"(d[27])
    : "r"(a0), "r"(a1), "r"(a2), "r"(a3), "r"(blo), "n"(OFF), "n"(BHI), "n"(ACC));
}

__device__ __forceinline__ void st128(uint4* p, uint32_t a, uint32_t b, uint32_t c, uint32_t d) {
  asm volatile("{\n.reg .b128 v;\n.reg .b64 lo, hi;\nmov.b64 lo, {%1, %2};\nmov.b64 hi, {%3, %4};\nmov.b128 v, {lo, hi};\n"
               "st.relaxed.gpu.global.b128 [%0], v;\n}" ::"l"(p), "r"(a), "r"(b), "r"(c), "r"(d) : "memory");
}
__device__ __forceinline__ void ld128(const uint4* p, uint32_t* r) {
  asm volatile("{\n.reg .b128 v;\n.reg .b64 lo, hi;\nld.relaxed.gpu.global.b128 v, [%4];\nmov.b128 {lo, hi}, v;\n"
               "mov.b64 {%0, %1}, lo;\nmov.b64 {%2, %3}, hi;\n}" : "=r"(r[0]), "=r"(r[1]), "=r"(r[2]), "=r"(r[3]) : "l"(p) : "memory");
}

template <int OFF, uint32_t BHI, int ACC>
__device__ __forceinline__ void wgmma_rs32(float (&d)[16], uint32_t a0, uint32_t a1, uint32_t a2, uint32_t a3, uint32_t blo) {
  asm volatile("{\n.reg .pred p;\n.reg .b64 bd;\nsetp.ne.b32 p, %23, 0;\nmov.b64 bd, {%20, %22};\nadd.s64 bd, bd, %21;\n"
    "wgmma.mma_async.sync.aligned.m64n32k16.f32.bf16.bf16 {%0,%1,%2,%3,%4,%5,%6,%7,%8,%9,%10,%11,%12,%13,%14,%15}, {%16,%17,%18,%19}, bd, p, 1, 1, 0;\n}\n"
    : "+f"(d[0]),"+f"(d[1]),"+f"(d[2]),"+f"(d[3]),"+f"(d[4]),"+f"(d[5]),"+f"(d[6]),"+f"(d[7]),"+f"(d[8]),"+f"(d[9]),"+f"(d[10]),"+f"(d[11]),"+f"(d[12]),"+f"(d[13]),"+f"(d[14]),"+f"(d[15])
    : "r"(a0), "r"(a1), "r"(a2), "r"(a3), "r"(blo), "n"(OFF), "n"(BHI), "n"(ACC));
}
template <int OFF, uint32_t BHI, int ACC>
__device__ __forceinline__ void wgmma_rs24(float (&d)[12], uint32_t a0, uint32_t a1, uint32_t a2, uint32_t a3, uint32_t blo) {
  asm volatile("{\n.reg .pred p;\n.reg .b64 bd;\nsetp.ne.b32 p, %19, 0;\nmov.b64 bd, {%16, %18};\nadd.s64 bd, bd, %17;\n"
    "wgmma.mma_async.sync.aligned.m64n24k16.f32.bf16.bf16 {%0,%1,%2,%3,%4,%5,%6,%7,%8,%9,%10,%11}, {%12,%13,%14,%15}, bd, p, 1, 1, 1;\n}\n"
    : "+f"(d[0]),"+f"(d[1]),"+f"(d[2]),"+f"(d[3]),"+f"(d[4]),"+f"(d[5]),"+f"(d[6]),"+f"(d[7]),"+f"(d[8]),"+f"(d[9]),"+f"(d[10]),"+f"(d[11])
    : "r"(a0), "r"(a1), "r"(a2), "r"(a3), "r"(blo), "n"(OFF), "n"(BHI), "n"(ACC));
}
template <int OFF, uint32_t BHI, int ACC>
__device__ __forceinline__ void wgmma_rs16(float (&d)[8], uint32_t a0, uint32_t a1, uint32_t a2, uint32_t a3, uint32_t blo) {
  asm volatile("{\n.reg .pred p;\n.reg .b64 bd;\nsetp.ne.b32 p, %15, 0;\nmov.b64 bd, {%12, %14};\nadd.s64 bd, bd, %13;\n"
    "wgmma.mma_async.sync.aligned.m64n16k16.f32.bf16.bf16 {%0,%1,%2,%3,%4,%5,%6,%7}, {%8,%9,%10,%11}, bd, p, 1, 1, 1;\n}\n"
    : "+f"(d[0]),"+f"(d[1]),"+f"(d[2]),"+f"(d[3]),"+f"(d[4]),"+f"(d[5]),"+f"(d[6]),"+f"(d[7])
    : "r"(a0), "r"(a1), "r"(a2), "r"(a3), "r"(blo), "n"(OFF), "n"(BHI), "n"(ACC));
}

constexpr int A_R1 = 0;
constexpr int A_R2A = A_R1 + 2624, A_R2B = A_R2A + 768, A_R3A = A_R2B + 768, A_R3B = A_R3A + 528;
constexpr int A_K1024 = A_R3B + 528;
constexpr int A_W5 = A_K1024 + 16;
constexpr int A_W3 = A_W5 + 4096;
constexpr int A_W9 = A_W3 + 4112;
constexpr int A_W7 = A_W9 + 2080;
constexpr int A_V  = A_W7 + 2080 + 32;
constexpr int A_SCL = A_V + 2048;
constexpr int A_UB = A_SCL + 16;
constexpr int A_STG = A_UB + 5248;
constexpr int A_Y2 = A_STG, A_Y3 = A_Y2 + 6528, A_YB = A_Y3 + 4352;
constexpr int A_REC = A_STG + 4 * 4352;
constexpr int A_CH = A_REC + 8192;
static_assert(A_W5 % 16 == 0 && A_UB % 16 == 0 && A_CH % 16 == 0 && A_YB + 4096 <= A_REC, "layout");

struct cf { float x, y; };
__device__ __forceinline__ cf cmul(cf a, cf b) { cf r; r.x = fmaf(a.x, b.x, -a.y * b.y); r.y = fmaf(a.x, b.y, a.y * b.x); return r; }
__device__ __forceinline__ cf cexp_l(float lr, float li, float l) {
  float mag; asm("ex2.approx.ftz.f32 %0, %1;" : "=f"(mag) : "f"((lr * l) * 1.4426950408889634f));
  const float th = li * l;
  const float k = (fmaf(th, 0.15915494f, 12582912.f)) - 12582912.f;
  float ph = fmaf(th, 0.15915494f, -k);
  ph = fmaf(th, 6.4206383e-9f, ph) * 6.2831853f;
  cf r; r.x = mag * __cosf(ph); r.y = mag * __sinf(ph); return r;
}
__device__ __forceinline__ void sts16(uint32_t a, uint32_t v) { asm volatile("st.shared.u16 [%0], %1;" ::"r"(a), "h"((uint16_t)v) : "memory"); }
__device__ __forceinline__ void sts32(uint32_t a, uint32_t v) { asm volatile("st.shared.u32 [%0], %1;" ::"r"(a), "r"(v) : "memory"); }
__device__ __forceinline__ void sts64(uint32_t a, uint32_t v0, uint32_t v1) { asm volatile("st.shared.v2.u32 [%0], {%1, %2};" ::"r"(a), "r"(v0), "r"(v1) : "memory"); }
__device__ __forceinline__ void sts128(uint32_t a, uint32_t v0, uint32_t v1, uint32_t v2, uint32_t v3) {
  asm volatile("st.shared.v4.u32 [%0], {%1, %2, %3, %4};" ::"r"(a), "r"(v0), "r"(v1), "r"(v2), "r"(v3) : "memory");
}
__device__ __forceinline__ uint32_t lds32(uint32_t a) { uint32_t v; asm volatile("ld.shared.u32 %0, [%1];" : "=r"(v) : "r"(a) : "memory"); return v; }
__device__ __forceinline__ uint4 lds128(uint32_t a) {
  uint4 v; asm volatile("ld.shared.v4.u32 {%0, %1, %2, %3}, [%4];" : "=r"(v.x), "=r"(v.y), "=r"(v.z), "=r"(v.w) : "r"(a) : "memory"); return v;
}
__device__ __forceinline__ void ldsm4(uint32_t* r, uint32_t a) {
  asm volatile("ldmatrix.sync.aligned.m8n8.x4.shared.b16 {%0,%1,%2,%3}, [%4];" : "=r"(r[0]), "=r"(r[1]), "=r"(r[2]), "=r"(r[3]) : "r"(a) : "memory");
}
__device__ __forceinline__ void mma16816(float* d, uint32_t a0, uint32_t a1, uint32_t a2, uint32_t a3, uint32_t b0, uint32_t b1) {
  asm volatile("mma.sync.aligned.m16n8k16.row.col.f32.f16.f16.f32 {%0,%1,%2,%3}, {%4,%5,%6,%7}, {%8,%9}, {%0,%1,%2,%3};"
               : "+f"(d[0]), "+f"(d[1]), "+f"(d[2]), "+f"(d[3]) : "r"(a0), "r"(a1), "r"(a2), "r"(a3), "r"(b0), "r"(b1));
}
__device__ __forceinline__ uint32_t pack_h(float lo, float hi) { uint32_t r; asm("cvt.rn.f16x2.f32 %0, %1, %2;" : "=r"(r) : "f"(hi), "f"(lo)); return r; }
__device__ __forceinline__ uint32_t pack_h(cf v) { return pack_h(v.x, v.y); }
__device__ __forceinline__ uint32_t hcmul(uint32_t x, uint32_t r0, uint32_t r1) {
  const __half2 hx = *(__half2*)&x;
  const __half2 y = __hfma2(__high2half2(hx), *(__half2*)&r1, __hmul2(__low2half2(hx), *(__half2*)&r0));
  return *(const uint32_t*)&y;
}
__device__ __forceinline__ float ln_rstd(float var) {
  float sd, rs;
  asm("sqrt.approx.f32 %0, %1;" : "=f"(sd) : "f"(rbf(rbf(var) + 1e-5f)));
  asm("rcp.approx.f32 %0, %1;" : "=f"(rs) : "f"(rbf(sd)));
  return rs;
}
__device__ __forceinline__ uint32_t hsub2_bf(uint32_t a, uint32_t b) { uint32_t r; asm("sub.rn.bf16x2 %0, %1, %2;" : "=r"(r) : "r"(a), "r"(b)); return r; }
__device__ __forceinline__ void bar_sync(int id, int n) { asm volatile("bar.sync %0, %1;" ::"r"(id), "r"(n) : "memory"); }

template <int S> struct F1B { static constexpr int c = S / 4 + ((S & 3) == 3 ? 0 : 0), cc = (16 * S) / 64, ks = (64 * cc - (16 * S - 48)) / 16, off = (A_UB + 2 * ks * 656 + (9 - cc) * 16) / 16; };

template <int NS>
__device__ __forceinline__ void load_quads(uint32_t* q, uint32_t addr) {
#pragma unroll
  for (int i = 0; i < NS; i++) {
    q[4 * i] = lds32(addr + i * 64); q[4 * i + 1] = lds32(addr + i * 64 + 32);
    q[4 * i + 2] = i ? q[4 * i - 3] : lds32(addr - 32);
    q[4 * i + 3] = q[4 * i];
  }
#pragma unroll
  for (int i = 0; i < 4 * NS; i++) asm volatile("" : "+r"(q[i]));
}
template <int S0, int NS>
__device__ __forceinline__ void f1_steps(float (&acc)[16], const uint32_t* a, uint32_t blo) {
  if constexpr (NS > 0) {
    wgmma_rs32<F1B<S0>::off, 8, S0 != 0>(acc, a[0], a[1], a[2], a[3], blo);
    f1_steps<S0 + 1, NS - 1>(acc, a + 4, blo);
  }
}
template <int S0, int NS, int BASE, int FIRST>
__device__ __forceinline__ void s2_steps(float (&acc)[12], const uint32_t* a, uint32_t blo) {
  if constexpr (NS > 0) {
    wgmma_rs24<BASE / 16 + (112 - 16 * S0), 64, !(FIRST && S0 == 0)>(acc, a[0], a[1], a[2], a[3], blo);
    s2_steps<S0 + 1, NS - 1, BASE, FIRST>(acc, a + 4, blo);
  }
}
template <int S0, int NS, int BASE, int FIRST>
__device__ __forceinline__ void s3_steps(float (&acc)[8], const uint32_t* a, uint32_t blo) {
  if constexpr (NS > 0) {
    wgmma_rs16<BASE / 16 + (48 - 16 * S0), 65, !(FIRST && S0 == 0)>(acc, a[0], a[1], a[2], a[3], blo);
    s3_steps<S0 + 1, NS - 1, BASE, FIRST>(acc, a + 4, blo);
  }
}

__device__ __forceinline__ void phase_a(
        unsigned char* sm, const uint32_t bar_rec, const uint32_t ep_addr,
        const __nv_bfloat16* __restrict__ x, const uint32_t* __restrict__ are, const uint32_t* __restrict__ aim,
        const uint32_t* __restrict__ bre, const uint32_t* __restrict__ bim, const uint32_t* __restrict__ cre,
        const uint32_t* __restrict__ cim, const unsigned short* __restrict__ logdt, const unsigned short* __restrict__ dskip,
        const uint4* __restrict__ wgate, const uint4* __restrict__ wup, const uint4* __restrict__ wdown) {
  const uint32_t sb = s2u(sm);
  const int tid = threadIdx.x, warp = __shfl_sync(~0u, tid >> 5, 0), wg = warp >> 2, lane = tid & 31, wq = warp & 3, t128 = tid & 127;
  const int blk = blockIdx.x;
  const bool conv = blk < 112;

  uint2 xr[4];
  {
    const uint2* p = (const uint2*)(x + (size_t)(blk * 16 + warp) * DM);
    xr[0] = __ldg(p + lane); xr[1] = __ldg(p + 32 + lane); xr[2] = __ldg(p + 64 + lane);
    xr[3] = lane < 16 ? __ldg(p + 96 + lane) : make_uint2(0, 0);
  }
  const int ch = conv ? blk * 4 + wg : 0;
  const uint32_t cb = sb + wg * A_CH;
  uint32_t prm[6];
  {
    const int i = ch * 128 + t128;
    prm[0] = __ldg(are + i); prm[1] = __ldg(aim + i); prm[2] = __ldg(bre + i); prm[3] = __ldg(bim + i); prm[4] = __ldg(cre + i); prm[5] = __ldg(cim + i);
  }
  const uint32_t ldt = __ldg(logdt + ch);
  uint32_t cnt0 = 0;
  if (tid == 0) cnt0 = __ldcg(&g_cnt1);
#pragma unroll
  for (int i = 0; i < 4; i++) if (i < 3 || t128 < (A_W5 + 1024) / 16 - 384) sts128(cb + (i * 128 + t128) * 16, 0, 0, 0, 0);
  if (t128 < 64) sts128(cb + A_W3 + t128 * 16, 0, 0, 0, 0);
  if (t128 < 72) sts128(cb + A_UB + (t128 / 9) * 656 + (t128 % 9) * 16, 0, 0, 0, 0);
  {
    float s = 0.f, q = 0.f;
#pragma unroll
    for (int i = 0; i < 4; i++) {
      const float a = bf_lo(xr[i].x), b = bf_hi(xr[i].x), c = bf_lo(xr[i].y), d = bf_hi(xr[i].y);
      s += (a + b) + (c + d);
      q = fmaf(a, a, q); q = fmaf(b, b, q); q = fmaf(c, c, q); q = fmaf(d, d, q);
    }
#pragma unroll
    for (int o = 16; o; o >>= 1) { s += __shfl_xor_sync(~0u, s, o); q += __shfl_xor_sync(~0u, q, o); }
    const float mean = s * (1.f / DM);
    const float var = fmaxf(fmaf(-mean, mean, q * (1.f / DM)), 0.f);
    const float rs = ln_rstd(var);
    const uint32_t mm = pack_bf16(mean, mean);
    const uint32_t tu = sb + A_REC + (warp >> 3) * A_CH + (warp & 7) * 912 + lane * 8, tx = tu + 2 * A_CH;
#pragma unroll
    for (int i = 0; i < 4; i++) {
      if (i < 3 || lane < 16) {
        const uint32_t d0 = hsub2_bf(xr[i].x, mm), d1 = hsub2_bf(xr[i].y, mm);
        sts64(tu + i * 256, pack_bf16(bf_lo(d0) * rs, bf_hi(d0) * rs), pack_bf16(bf_lo(d1) * rs, bf_hi(d1) * rs));
        sts64(tx + i * 256, xr[i].x, xr[i].y);
      }
    }
  }
  if (tid == 0) sts32(ep_addr, (cnt0 >> 7) + 1u);
  if (tid == 320) TR(0, 1);
  auto publish_rows = [&]() {
    bar_sync(5, 512);
    uint4* dst = g_ux + ((size_t)(warp * 8 + (lane >> 2)) * 128 + blk) * 4 + ((lane ^ (blk >> 1)) & 3);
#pragma unroll
    for (int i = 0; i < 4; i++) {
      if (i < 3 || warp < 8) {
        uint32_t r[4];
        asm volatile("ldmatrix.sync.aligned.m8n8.x4.trans.shared.b16 {%0,%1,%2,%3}, [%4];" : "=r"(r[0]), "=r"(r[1]), "=r"(r[2]), "=r"(r[3])
                     : "r"(sb + A_REC + (lane >> 3) * A_CH + (lane & 7) * 912 + (warp + 16 * i) * 16) : "memory");
        dst[i * 65536] = make_uint4(r[0], r[1], r[2], r[3]);
      }
    }
    if (warp != 0) asm volatile("bar.arrive 6, 512;" ::: "memory");
  };
  auto release_rows = [&]() {
    if (warp == 0) {
      bar_sync(6, 512);
      if (lane == 0) { asm volatile("red.release.gpu.global.add.u32 [%0], 1;" ::"l"(&g_cnt1) : "memory"); TR(0, 8); }
      __syncwarp();
    }
  };

  if (!conv) {
    publish_rows();
    release_rows();
    const int a = blk - 112, mat = a >> 3, j = a & 7;
    float s[8];
#pragma unroll
    for (int k = 0; k < 8; k++) s[k] = 0.f;
    if (lane < 28) {
      const uint4* src = (mat ? wup : wgate) + j * 28 + lane + (size_t)warp * 224;
#pragma unroll
      for (int hb = 0; hb < 2; hb++) {
        uint4 v[14];
#pragma unroll
        for (int r = 0; r < 14; r++) v[r] = __ldg(src + (size_t)(hb * 14 + r) * 16 * 224);
#pragma unroll
        for (int r = 0; r < 14; r++) {
          s[0] += bf_lo(v[r].x); s[1] += bf_hi(v[r].x); s[2] += bf_lo(v[r].y); s[3] += bf_hi(v[r].y);
          s[4] += bf_lo(v[r].z); s[5] += bf_hi(v[r].z); s[6] += bf_lo(v[r].w); s[7] += bf_hi(v[r].w);
        }
      }
      float4* red = (float4*)(sm + A_STG + warp * 896 + lane * 32);
      red[0] = make_float4(s[0], s[1], s[2], s[3]); red[1] = make_float4(s[4], s[5], s[6], s[7]);
    }
    bar_sync(5, 512);
    if (tid < 224) {
      float t = 0.f;
#pragma unroll
      for (int w = 0; w < 16; w++) t += *(const float*)(sm + A_STG + w * 896 + tid * 4);
      const float hi = rbf(t), mid = rbf(t - hi), lo = rbf(t - hi - mid);
      const int q = tid / 112, n = tid % 112 + 112 * mat;
      __nv_bfloat16* dst = (__nv_bfloat16*)(g_cimg + (j * 2 + q) * 224 + (n >> 3) * 8) + (n & 7);
      dst[0] = __float2bfloat16_rn(hi); dst[8] = __float2bfloat16_rn(mid); dst[16] = __float2bfloat16_rn(lo);
#pragma unroll
      for (int k = 3; k < 8; k++) dst[8 * k] = __float2bfloat16_rn(0.f);
    }
    if (tid == 320) TR(0, 10);
    return;
  }

  const int g = lane >> 2, t = lane & 3;
  const int wr = (wq + wg) & 3;
  const int bk = wr * 32 + lane;
  const int wu2 = ch >> 1, wjq = wu2 / 14, wst = wu2 % 14;
  const uint4* wsrc1 = ((ch & 1) ? wup : wgate) + (size_t)(wst * 32 + wq * 8 + g) * 224 + wjq * 14 + t;
  const uint4* wsrc2 = wdown + (size_t)(wu2 * 8 + g) * 56 + ((ch & 1) * 4 + wq) * 7 + t;
  uint4 wv[6];
  {
    const uint32_t stg = cb + A_STG + wq * 4352, sw = stg + lane * 8;
    const float dt = rbf(expf(__uint_as_float(ldt << 16)));
    float lr[2], li[2];
    cf bq[2], b0[2], b4[2];
    uint32_t bf[48];
#pragma unroll
    for (int m = 0; m < 2; m++) {
      lr[m] = dt * (m ? bf_hi(prm[0]) : bf_lo(prm[0]));
      li[m] = dt * (m ? bf_hi(prm[1]) : bf_lo(prm[1]));
    }
    {
      cf b[2], z[2];
#pragma unroll
      for (int m = 0; m < 2; m++) {
        cf db, c;
        db.x = dt * (m ? bf_hi(prm[2]) : bf_lo(prm[2])); db.y = -dt * (m ? bf_hi(prm[3]) : bf_lo(prm[3]));
        c.x = m ? bf_hi(prm[4]) : bf_lo(prm[4]); c.y = -(m ? bf_hi(prm[5]) : bf_lo(prm[5]));
        b[m] = cmul(c, db);
        z[m] = cexp_l(lr[m], -li[m], 1.f);
        bq[m] = cexp_l(lr[m], -li[m], 256.f);
      }
      {
        const float mx = fmaxf(fmaxf(fabsf(b[0].x), fabsf(b[0].y)), fmaxf(fabsf(b[1].x), fabsf(b[1].y)));
        const uint32_t e = max(__reduce_max_sync(~0u, __float_as_uint(mx)) >> 23, 14u);
        const float sc = __uint_as_float((267u - e) << 23);
        b[0].x *= sc; b[0].y *= sc; b[1].x *= sc; b[1].y *= sc;
        if (lane == 0) sts32(cb + A_SCL + wq * 4, (e - 13u) << 23);
      }
#pragma unroll
      for (int i = 0; i < 8; i++) {
        sts64(sw + i * 272, pack_h(b[0]), pack_h(b[1]));
        if (!(i & 1)) {
          cf e0 = cmul(b[0], bq[0]), e1 = cmul(b[1], bq[1]);
          sts64(sw + (8 + i / 2) * 272, pack_h(e0), pack_h(e1));
          if (i == 0) { b0[0] = e0; b0[1] = e1; }
          if (i == 4) { b4[0] = e0; b4[1] = e1; }
        }
        if (i < 7) { b[0] = cmul(b[0], z[0]); b[1] = cmul(b[1], z[1]); }
        if (i == 1) publish_rows();
      }
#pragma unroll
      for (int i = 0; i < 7; i++) {
        b0[0] = cmul(b0[0], bq[0]); b0[1] = cmul(b0[1], bq[1]);
        sts64(sw + (i < 2 ? 12 + 2 * i : i - 2) * 272, pack_h(b0[0]), pack_h(b0[1]));
        if (i < 2) {
          b4[0] = cmul(b4[0], bq[0]); b4[1] = cmul(b4[1], bq[1]);
          sts64(sw + (13 + 2 * i) * 272, pack_h(b4[0]), pack_h(b4[1]));
        }
        if (i == 1) {
          __syncwarp();
#pragma unroll
          for (int n = 0; n < 2; n++)
#pragma unroll
            for (int k2 = 0; k2 < 4; k2++) ldsm4(bf + n * 16 + k2 * 4, stg + (n * 8 + (lane & 7)) * 272 + k2 * 64 + (lane >> 3) * 16);
          __syncwarp();
          release_rows();
        }
      }
    }
    if (!(lane & 1)) {
#pragma unroll
      for (int i = 0; i < 4; i++) if (i < 3 || t < 2) asm volatile("prefetch.global.L2 [%0];" ::"l"(wsrc1 + 4 * i));
#pragma unroll
      for (int i = 0; i < 2; i++) asm volatile("prefetch.global.L2 [%0];" ::"l"(wsrc2 + 4 * i));
    }
    {
      const cf p0 = cexp_l(lr[0], li[0], 8.f), p1 = cexp_l(lr[1], li[1], 8.f);
      cf v0 = p0, v1 = p1;
      sts64(sw + 8 * 272, 0x3C00u, 0x3C00u);
#pragma unroll
      for (int i = 1; i < 8; i++) {
        sts64(sw + (8 + i) * 272, pack_h(v0), pack_h(v1));
        v0 = cmul(v0, p0); v1 = cmul(v1, p1);
      }
      const uint32_t ra = stg + 5 * 272 + (lane >> 2) * 64 + (lane & 1) * 32 + (lane & 2) * 4;
      sts64(ra, pack_h(v0), pack_h(-v0.y, v0.x));
      sts64(ra + 16, pack_h(v1), pack_h(-v1.y, v1.x));
    }
    __syncwarp();
    if (tid == 320) TR(0, 16);
#pragma unroll
    for (int k2 = 0; k2 < 4; k2++) ldsm4(bf + 32 + k2 * 4, stg + (lane & 7) * 272 + k2 * 64 + (lane >> 3) * 16);
    uint32_t cv = 0;
    if (tid == 160) asm volatile("ld.relaxed.gpu.global.u32 %0, [%1];" : "=r"(cv) : "l"(&g_cnt1) : "memory");
    float c[6][4];
#pragma unroll
    for (int i = 0; i < 6; i++) { c[i][0] = 0.f; c[i][1] = 0.f; c[i][2] = 0.f; c[i][3] = 0.f; }
#pragma unroll
    for (int k2 = 0; k2 < 4; k2++) {
      uint32_t a[4];
      ldsm4(a, stg + (8 + (lane & 7)) * 272 + k2 * 64 + (lane >> 3) * 16);
#pragma unroll
      for (int kk = 0; kk < 2; kk++) {
        const int ks = 2 * k2 + kk;
        const uint4 r4 = lds128(stg + 5 * 272 + ks * 64 + t * 16);
        const uint32_t r[4] = {r4.x, r4.z, r4.y, r4.w};
        const uint32_t x0 = a[2 * kk], y0 = a[2 * kk + 1];
        const uint32_t x1 = hcmul(x0, r[0], r[2]), y1 = hcmul(y0, r[1], r[3]);
        const uint32_t x2 = hcmul(x1, r[0], r[2]), y2 = hcmul(y1, r[1], r[3]);
        const uint32_t x3 = hcmul(x2, r[0], r[2]), y3 = hcmul(y2, r[1], r[3]);
#pragma unroll
        for (int n = 0; n < 3; n++) {
          mma16816(c[n * 2], x0, x1, y0, y1, bf[n * 16 + ks * 2], bf[n * 16 + ks * 2 + 1]);
          mma16816(c[n * 2 + 1], x2, x3, y2, y3, bf[n * 16 + ks * 2], bf[n * 16 + ks * 2 + 1]);
        }
      }
      if (k2 == 1 && warp == 5) {
        if (lane == 0) {
          const uint32_t tgt = lds32(ep_addr) * 128u;
          int it = 0;
          while ((int)(cv - tgt) < 0 && ++it < 400000) asm volatile("ld.relaxed.gpu.global.u32 %0, [%1];" : "=r"(cv) : "l"(&g_cnt1) : "memory");
          asm volatile("fence.acquire.gpu;" ::: "memory");
          asm volatile("fence.proxy.async.global;" ::: "memory");
          TR(0, 9);
        }
        __syncwarp();
#pragma unroll
        for (int c2 = 0; c2 < 4; c2++) bulk_ld_elect<8192>(sb + c2 * A_CH + A_REC, g_ux + (size_t)(blk * 4 + c2) * 512, bar_rec);
      }
    }
    __syncwarp();
#pragma unroll
    for (int i = 0; i < 6; i++)
      sts128(stg + i * 512 + lane * 16, __float_as_uint(c[i][0]), __float_as_uint(c[i][1]), __float_as_uint(c[i][2]), __float_as_uint(c[i][3]));
#pragma unroll
    for (int i = 0; i < 4; i++) if (i < 3 || t < 2) wv[i] = __ldg(wsrc1 + 4 * i);
#pragma unroll
    for (int i = 0; i < 2; i++) if (i < 1 || t < 3) wv[4 + i] = __ldg(wsrc2 + 4 * i);
  }
  if (tid == 320) TR(0, 2);

  uint32_t xt[8], ud[8];
  {
    mbar_wait(bar_rec, 0);
    if (tid == 320) TR(0, 4);
    uint4 r[4];
#pragma unroll
    for (int i = 0; i < 4; i++) r[i] = lds128(cb + A_REC + bk * 64 + ((i ^ (bk >> 1)) & 3) * 16);
    const uint32_t ua = cb + A_UB + ((2 * bk) & 7) * 656 + ((bk >> 2) + 9) * 16;
    sts128(ua, r[0].x, r[1].x, r[2].x, r[3].x);
    sts128(ua + 656, r[0].y, r[1].y, r[2].y, r[3].y);
    if (bk <= 96) {
      const bool neg = bk == 96;
      const int bp = neg ? -1 : bk;
      uint32_t h[4];
      h[0] = lds32(cb + A_REC + ((bp - 1) & 127) * 64 + ((2 ^ ((bp - 1) >> 1)) & 3) * 16 + 4);
      h[1] = lds32(cb + A_REC + ((bp - 1) & 127) * 64 + ((3 ^ ((bp - 1) >> 1)) & 3) * 16 + 4);
      h[2] = lds32(cb + A_REC + (bp + 1) * 64 + ((0 ^ ((bp + 1) >> 1)) & 3) * 16);
      h[3] = lds32(cb + A_REC + (bp + 1) * 64 + ((1 ^ ((bp + 1) >> 1)) & 3) * 16);
      if (bp <= 0) { h[0] = 0; h[1] = 0; }
      const uint32_t wd[12] = {h[0], h[1], neg ? 0 : r[0].x, neg ? 0 : r[1].x, neg ? 0 : r[2].x, neg ? 0 : r[3].x,
                               neg ? 0 : r[0].y, neg ? 0 : r[1].y, neg ? 0 : r[2].y, neg ? 0 : r[3].y, h[2], h[3]};
      float P[25];
      P[0] = 0.f;
#pragma unroll
      for (int i = 0; i < 12; i++) { P[2 * i + 1] = P[2 * i] + bf_lo(wd[i]); P[2 * i + 2] = P[2 * i + 1] + bf_hi(wd[i]); }
#define WIN(i, hw) (P[(i) + 5 + (hw)] - P[(i) + 4 - (hw)])
#define WPK(i, hw) pack_bf16(WIN(i, hw), WIN((i) + 1, hw))
      const int tp = 2 * bp;
      const uint32_t a3 = cb + A_W3 + (tp + 64) * 16 + 8, a5 = cb + A_W5 + (tp + 64) * 16;
      sts64(a3, WPK(0, 1), WPK(2, 1));
      sts128(a3 + 8, WPK(4, 1), WPK(6, 1), WPK(8, 1), WPK(10, 1));
      sts64(a3 + 24, WPK(12, 1), WPK(14, 1));
      sts128(a5, WPK(0, 2), WPK(2, 2), WPK(4, 2), WPK(6, 2));
      sts128(a5 + 16, WPK(8, 2), WPK(10, 2), WPK(12, 2), WPK(14, 2));
      if (bp < 64) {
        sts128(cb + A_W7 + 1040 + bp * 16, WPK(0, 3), WPK(2, 3), WPK(4, 3), WPK(6, 3));
        sts128(cb + A_W7 + (bp + 1) * 16, WPK(8, 3), WPK(10, 3), WPK(12, 3), WPK(14, 3));
        sts128(cb + A_W9 + (bp + 1) * 16, WPK(0, 4), WPK(2, 4), WPK(4, 4), WPK(6, 4));
        sts128(cb + A_W9 + 1040 + (bp + 1) * 16, WPK(8, 4), WPK(10, 4), WPK(12, 4), WPK(14, 4));
#define VPK(i) pack_bf16(P[(i) + 2] - P[i], P[(i) + 3] - P[(i) + 1])
        sts128(cb + A_V + bp * 32, VPK(0), VPK(2), VPK(4), VPK(6));
        sts128(cb + A_V + bp * 32 + 16, VPK(8), VPK(10), VPK(12), VPK(14));
      }
    }
  }
  asm volatile("fence.proxy.async.shared::cta;" ::: "memory");
  {
    uint4* d1 = g_wimg + (size_t)(wjq >> 1) * 37632 + ((wjq & 1) * 14 + wst) * 896 + ((ch & 1) * 14 + t) * 32 + wq * 8 + g;
#pragma unroll
    for (int i = 0; i < 4; i++) if (i < 3 || t < 2) d1[i * 128] = wv[i];
    uint4* d2 = g_wimg + (size_t)(wjq >> 1) * 37632 + 25088 + (((ch & 1) * 4 + wq) * 2 + (wjq & 1)) * 784 + t * 112 + wst * 8 + g;
#pragma unroll
    for (int i = 0; i < 2; i++) if (i < 1 || t < 3) d2[i * 448] = wv[4 + i];
  }
  bar_sync(1 + wg, 128);
  if (tid == 320) TR(0, 3);
  {
    const uint4 sc = lds128(cb + A_SCL);
    const float scl[4] = {__uint_as_float(sc.x), __uint_as_float(sc.y), __uint_as_float(sc.z), __uint_as_float(sc.w)};
#pragma unroll
    for (int rep = 0; rep < 2; rep++) {
      const int qd = rep ? 2 + wr : 3 - wr;
      if (rep == 0 || wr >= 2) {
        float s[4] = {0.f, 0.f, 0.f, 0.f};
#pragma unroll
        for (int w = 0; w < 4; w++) {
          uint4 u4 = lds128(cb + A_STG + w * 4352 + qd * 512 + lane * 16);
          s[0] = fmaf(__uint_as_float(u4.x), scl[w], s[0]); s[1] = fmaf(__uint_as_float(u4.y), scl[w], s[1]);
          s[2] = fmaf(__uint_as_float(u4.z), scl[w], s[2]); s[3] = fmaf(__uint_as_float(u4.w), scl[w], s[3]);
        }
#pragma unroll
        for (int hf = 0; hf < 2; hf++) {
          const int j = (qd & 1) * 16 + g + 8 * hf;
          const uint32_t pk = pack_bf16(s[2 * hf + 1], s[2 * hf]);
          const uint32_t v0 = pk >> 16, v1 = pk & 0xFFFFu, v00 = v0 * 0x10001u;
          if (rep == 1) {
            if (t < 2) {
#pragma unroll
              for (int e = 0; e < 2; e++) {
                const int lam = 128 + 32 * (2 * t + e) + j, mu = lam >> 1;
                const uint32_t val = e ? v1 : v0;
                uint32_t a = cb + ((lam & 1) ? A_R3B : A_R3A) + mu * 4;
                if (lam == 128) { a = cb + A_R2A + 128 * 4; sts32(cb + A_K1024, val << 16); }
                sts16(a, val); sts16(a + 6, val);
              }
            } else if (t == 2 && j == 0) { sts16(cb + A_R3A + 128 * 4, v0); }
          } else if (qd < 2) {
            const uint32_t a = cb + A_R1 + (62 + 8 * j + 2 * t) * 4;
            sts16(a, v0); sts32(a + 4, pk); sts16(a + 10, v1);
          } else if (t < 2) {
            const int L = 256 + 8 * j + 4 * t;
            const uint32_t a = cb + A_R1 + (62 + L) * 4;
            if (L > 256) { sts16(a - 4, v0); sts32(a, v00); } else sts16(a, v0);
            sts32(a + 4, v00); sts32(a + 8, pk); sts16(a + 14, v1);
          } else {
            const int mu = 64 + 32 * (t - 2) + j;
            if (mu == 64) {
              const uint32_t a = cb + A_R1 + (62 + 512) * 4;
              sts16(a - 4, v0); sts32(a, v00); sts32(a + 4, v00); sts32(a + 8, v00); sts16(a + 14, v0);
            } else { sts16(cb + A_R2A + mu * 4, v0); sts16(cb + A_R2A + mu * 4 + 6, v0); }
            sts16(cb + A_R2B + mu * 4, v1); sts16(cb + A_R2B + mu * 4 + 6, v1);
          }
        }
      }
    }
  }
  bar_sync(1 + wg, 128);
  if (tid == 320) TR(0, 5);

  {
    const uint32_t cbu = cb;
    const uint32_t blo_k = ((cbu & 0x3FFFF) >> 4) | (41u << 16);
    const uint32_t blo_n = ((cbu & 0x3FFFF) >> 4) | (8u << 16);
    const uint32_t tb = cb + (16 * wq + g - 2 * t) * 4;
    float y1[16], y2[12], y3[8];
    const uint32_t dk16 = __ldg(dskip + ch);
    uint32_t qa[32], qb[32];
    const uint32_t t1 = tb + A_R1 + (62 - 48) * 4;
    load_quads<4>(qa, tb + A_R3A + 17 * 4); load_quads<4>(qa + 16, tb + A_R3B + 16 * 4);
    wg_fence();
    s3_steps<0, 4, A_W9, 1>(y3, qa, blo_n); s3_steps<0, 4, A_W7, 0>(y3, qa + 16, blo_n);
    wg_commit();
    load_quads<8>(qb, tb + A_R2A + 16 * 4);
    wg_fence(); s2_steps<0, 8, A_W5, 1>(y2, qb, blo_n); wg_commit();
    wg_wait<1>(); load_quads<8>(qa, tb + A_R2B + 16 * 4);
    wg_fence(); s2_steps<0, 8, A_W3, 0>(y2, qa, blo_n); wg_commit();
    wg_wait<1>(); load_quads<8>(qb, t1);
    wg_fence(); f1_steps<0, 8>(y1, qb, blo_k); wg_commit();
    wg_wait<1>(); load_quads<8>(qa, t1 + 8 * 64);
    wg_fence(); f1_steps<8, 8>(y1, qa, blo_k); wg_commit();
    reg_fence(y2); reg_fence(y3);
    if (tid == 320) TR(0, 18);
    {
      const float k1024 = __uint_as_float(lds32(cb + A_K1024));
#pragma unroll
      for (int i = 0; i < 2; i++)
#pragma unroll
        for (int hf = 0; hf < 2; hf++) {
          const int idx = 16 * (16 * wq + g + 8 * hf) + 8 * i + 2 * t;
          const uint32_t vv = lds32(cb + A_V + idx * 2);
          sts64(cb + A_Y3 + (idx + 4 * (idx >> 6)) * 4, __float_as_uint(fmaf(k1024, bf_lo(vv), y3[4 * i + 2 * hf])),
                __float_as_uint(fmaf(k1024, bf_hi(vv), y3[4 * i + 2 * hf + 1])));
        }
#pragma unroll
      for (int i = 0; i < 3; i++)
#pragma unroll
        for (int hf = 0; hf < 2; hf++) {
          const int idx = 512 * i + 8 * (16 * wq + g + 8 * hf) + 2 * t;
          sts64(cb + A_Y2 + (idx + 4 * (idx >> 6)) * 4, __float_as_uint(y2[4 * i + 2 * hf]), __float_as_uint(y2[4 * i + 2 * hf + 1]));
        }
    }
    wg_wait<1>(); load_quads<8>(qb, t1 + 16 * 64);
    wg_fence(); f1_steps<16, 8>(y1, qb, blo_k); wg_commit();
    wg_wait<1>(); load_quads<8>(qa, t1 + 24 * 64);
    wg_fence(); f1_steps<24, 8>(y1, qa, blo_k); wg_commit();
    wg_wait<1>(); load_quads<5>(qb, t1 + 32 * 64);
    wg_fence(); f1_steps<32, 5>(y1, qb, blo_k); wg_commit();
    bar_sync(1 + wg, 128);
    float ex[12];
#pragma unroll
    for (int i = 1; i < 4; i++)
#pragma unroll
      for (int k = 0; k < 4; k++) {
        const int aa = 8 * i + 2 * t + (k & 1), b = 16 * wq + g + 8 * (k >> 1);
        float e = __uint_as_float(lds32(cb + A_Y2 + ((aa - 8) * 68 + b) * 4));
        if (i >= 2) e += __uint_as_float(lds32(cb + A_Y3 + ((aa - 16) * 68 + b) * 4));
        ex[4 * (i - 1) + k] = e;
      }
    {
      const uint32_t dk = dk16 * 0x10001u;
#pragma unroll
      for (int i = 0; i < 4; i++) {
        const uint4 r = lds128(cb + A_REC + bk * 64 + ((i ^ (bk >> 1)) & 3) * 16);
        ud[i] = hmul2_bf(r.x, dk); ud[4 + i] = hmul2_bf(r.y, dk); xt[i] = r.z; xt[4 + i] = r.w;
      }
    }
    wg_wait<0>();
    reg_fence(y1);
    if (tid == 320) TR(0, 6);
#pragma unroll
    for (int i = 0; i < 12; i++) y1[4 + i] += ex[i];
#pragma unroll
    for (int i = 0; i < 2; i++) {
      const int mi = lane >> 3, aa = 8 * (2 * i + (mi >> 1)) + (lane & 7);
      asm volatile("stmatrix.sync.aligned.m8n8.x4.trans.shared.b16 [%0], {%1,%2,%3,%4};"
                   ::"r"(cb + A_YB + aa * 128 + (((2 * wq + (mi & 1)) ^ (lane & 7)) << 4)),
                     "r"(pack_bf16(y1[8 * i], y1[8 * i + 1])), "r"(pack_bf16(y1[8 * i + 2], y1[8 * i + 3])),
                     "r"(pack_bf16(y1[8 * i + 4], y1[8 * i + 5])), "r"(pack_bf16(y1[8 * i + 6], y1[8 * i + 7])) : "memory");
    }
  }
  bar_sync(1 + wg, 128);
#pragma unroll
  for (int c = 0; c < 2; c++) {
    const int tau = 2 * bk + c, r = ch & 7;
    const uint4 y = lds128(cb + A_YB + (tau >> 3) * 128 + (((tau ^ (tau >> 3)) & 7) << 4));
    g_himg[(size_t)(tau >> 4) * 7168 + (ch >> 3) * 128 + ((tau >> 3) & 1) * 64 + r * 8 + ((tau & 7) ^ r)] =
        make_uint4(hadd2_bf(xt[4 * c], hadd2_bf(y.x, ud[4 * c])), hadd2_bf(xt[4 * c + 1], hadd2_bf(y.y, ud[4 * c + 1])),
                   hadd2_bf(xt[4 * c + 2], hadd2_bf(y.z, ud[4 * c + 2])), hadd2_bf(xt[4 * c + 3], hadd2_bf(y.w, ud[4 * c + 3])));
  }
  if (tid == 320) TR(0, 7);
}

constexpr int B_SA = 0, B_RING = 114688, B_SLOT = 14848, B_NSLOT = 7;
constexpr int B_CS = B_RING + B_NSLOT * B_SLOT;
constexpr int B_RED = B_CS + 7168;
constexpr int B_BAR = B_RED + 256;
constexpr int B_SMEM = B_BAR + 1024, A_SMEM = 4 * A_CH + 64;

__device__ __forceinline__ uint32_t mapa(uint32_t a, uint32_t r) { uint32_t o; asm("mapa.shared::cluster.u32 %0, %1, %2;" : "=r"(o) : "r"(a), "r"(r)); return o; }
template <class T> __device__ __forceinline__ T* pin(T* p) { asm volatile("" : "+l"(p)); return p; }
__device__ __forceinline__ uint32_t pin(uint32_t v) { asm volatile("" : "+r"(v)); return v; }
template <int Q, int ST>
__device__ __forceinline__ void g1_stage(float (&acc)[116], uint32_t alo, uint32_t blo, uint32_t bar_full, uint32_t bar_h) {
  constexpr int s = Q * 14 + ST, sl = s % B_NSLOT;
  if (Q == 0) mbar_wait(bar_h + 8 * ST, 0);
  mbar_wait(bar_full + 8 * sl, (s / B_NSLOT) & 1);
  wg_fence();
  if (Q == 0) {
    wgmma_ss232<(2 * ST) * 256, 0x40000080u, (sl * B_SLOT) / 16, 32, ST != 0>(acc, alo, blo);
    wgmma_ss232<(2 * ST + 1) * 256, 0x40000080u, (sl * B_SLOT + 256) / 16, 32, 1>(acc, alo, blo);
  } else {
    wgmma_ss224<(2 * ST) * 256, 0x40000080u, (sl * B_SLOT) / 16, 32, ST != 0>(*(float(*)[112])acc, alo, blo);
    wgmma_ss224<(2 * ST + 1) * 256, 0x40000080u, (sl * B_SLOT + 256) / 16, 32, 1>(*(float(*)[112])acc, alo, blo);
  }
}

__global__ void __launch_bounds__(512, 1)
k_front(const __nv_bfloat16* __restrict__ x, const uint32_t* __restrict__ are, const uint32_t* __restrict__ aim,
        const uint32_t* __restrict__ bre, const uint32_t* __restrict__ bim, const uint32_t* __restrict__ cre,
        const uint32_t* __restrict__ cim, const unsigned short* __restrict__ logdt, const unsigned short* __restrict__ dskip,
        const uint4* __restrict__ wgate, const uint4* __restrict__ wup, const uint4* __restrict__ wdown) {
  extern __shared__ __align__(1024) unsigned char sm[];
  const uint32_t bar_rec = s2u(sm) + 4 * A_CH;
  if (threadIdx.x == 320) TR(0, 0);
  asm volatile("griddepcontrol.launch_dependents;");
  if (threadIdx.x == 160) { mbar_init(bar_rec, 4); asm volatile("fence.mbarrier_init.release.cluster;" ::: "memory"); }
  phase_a(sm, bar_rec, bar_rec + 8, x, are, aim, bre, bim, cre, cim, logdt, dskip, wgate, wup, wdown);
}

__global__ void __cluster_dims__(2, 1, 1) __launch_bounds__(384, 1) k_ffn(__nv_bfloat16* __restrict__ out) {
  extern __shared__ __align__(1024) unsigned char sm[];
  const uint32_t sb = s2u(sm);
  const int tid = threadIdx.x, warp = __shfl_sync(~0u, tid >> 5, 0), wg = warp >> 2, lane = tid & 31;
  const uint32_t bar_full = sb + B_BAR, bar_empty = bar_full + 64, bar_h = bar_full + 128, bar_cs = bar_full + 240,
                 bar_hh = bar_full + 304, bar_afree = bar_full + 336, bar_out = bar_full + 352;
  if (tid == 0) {
    TR(1, 0);
    for (int i = 0; i < B_NSLOT; i++) { mbar_init(bar_full + 8 * i, 1); mbar_init(bar_empty + 8 * i, 2); }
    asm volatile("fence.mbarrier_init.release.cluster;" ::: "memory");
  } else if (tid == 32) {
    for (int i = 0; i < 14; i++) mbar_init(bar_h + 8 * i, 1);
    asm volatile("fence.mbarrier_init.release.cluster;" ::: "memory");
  } else if (tid == 64) {
    mbar_init(bar_cs, 1);
    for (int i = 0; i < 4; i++) { mbar_init(bar_hh + 8 * i, 1); mbar_expect(bar_hh + 8 * i, 14336); }
    mbar_init(bar_afree, 4); mbar_init(bar_afree + 8, 2);
    for (int i = 0; i < 6; i++) mbar_init(bar_out + 8 * i, 128);
    asm volatile("fence.mbarrier_init.release.cluster;" ::: "memory");
  } else if (tid >= 128 && tid < 352) {
    sts128(sb + B_RING + ((tid - 128) >> 5) * B_SLOT + 14336 + (tid & 31) * 16, 0x3F803F80u, 0x3F803F80u, 0x3F803F80u, 0x3F803F80u);
  }
  asm volatile("fence.proxy.async.shared::cta;" ::: "memory");
  __syncthreads();
  asm volatile("barrier.cluster.arrive.relaxed.aligned;" ::: "memory");
  const int rank = blockIdx.x & 1, rt = blockIdx.x >> 3, j = blockIdx.x & 7, p = j >> 1, cg = 4 * rank + p;
  const int wq = warp & 3, t128 = tid & 127, g = lane >> 2, t = lane & 3;
  uint32_t ep, tag;
  auto load_ep = [&]() { asm volatile("ld.relaxed.gpu.global.u32 %0, [%1];" : "=r"(ep) : "l"(&g_cnt1) : "memory"); };
  auto a_slot = [&](int i, int own) { return B_SA + (i + (i >= own)) * 14336; };
  auto out_addr = [&](int cc, int w) { return sb + a_slot((cc & 2) + w, cg) + (cc & 1) * 7168; };
  auto in_cta = [&](int q) { return rt * 8 + ((p + 3 - q) & 3) * 2 + rank; };
  auto in_src = [&](int q, int cw) { return g_part + (size_t)(in_cta(q) * 3 + q) * 896 + cw * 112; };
  auto in_bad = [&](uint32_t (&in)[14]) { return ((in[3] ^ tag) | (in[7] ^ tag) | (in[11] ^ tag) | (in[13] ^ tag)) & 0x10000u; };
  auto in_load = [&](uint32_t (&in)[14], const uint4* gs) {
#pragma unroll
    for (int i = 0; i < 3; i++) ld128(gs + i * 32, in + 4 * i);
    asm volatile("{\n.reg .b64 v;\nld.relaxed.gpu.global.b64 v, [%2];\nmov.b64 {%0, %1}, v;\n}"
                 : "=r"(in[12]), "=r"(in[13]) : "l"((const uint2*)(gs + 96) - lane) : "memory");
  };
  auto in_check = [&](uint32_t (&in)[14], int q, int cw) {
    int it = 0;
    while (in_bad(in) && ++it < 400000) in_load(in, pin(in_src(q, cw) + lane));
  };

  if (wg == 2) {
    asm volatile("setmaxnreg.dec.sync.aligned.u32 40;");
    asm volatile("barrier.cluster.wait.aligned;" ::: "memory");
    asm volatile("griddepcontrol.wait;" ::: "memory");
    if (warp == 8) {
      if (lane == 0) TR(1, 1);
      const char* wsrc = (const char*)g_wimg + (size_t)j * 602112;
      const char* hsrc = (const char*)g_himg + (size_t)rt * 114688 + rank * 4096;
#pragma unroll
      for (int s = 0; s < 28; s++) {
        if (s < B_NSLOT) bulk_ld_mc_elect<4096>(sb + B_SA + s * 8192 + rank * 4096, hsrc + s * 8192, bar_h + 8 * s);
        if (s == B_NSLOT) {
#pragma unroll
          for (int i = 7; i < 14; i++) bulk_ld_mc_elect<4096>(sb + B_SA + i * 8192 + rank * 4096, hsrc + i * 8192, bar_h + 8 * i);
          bulk_ld_elect<7168>(sb + B_CS, g_cimg + j * 448, bar_cs);
        }
        if (s >= B_NSLOT) mbar_wait(bar_empty + 8 * (s % B_NSLOT), (s / B_NSLOT + 1) & 1);
        bulk_ld_elect<14336>(sb + B_RING + (s % B_NSLOT) * B_SLOT, wsrc + s * 14336, bar_full + 8 * (s % B_NSLOT));
      }
      const char* dsrc[2] = {wsrc + 401408 + rank * 100352, (const char*)g_wimg + (size_t)(j ^ 1) * 602112 + 401408 + rank * 100352};
#pragma unroll
      for (int i = 0; i < 16; i++) {
        const int ci = i < 3 ? 0 : i < 6 ? 1 : i < 8 ? i - 6 : i < 12 ? 2 : 3;
        const int kp = i < 3 ? i : i < 6 ? i - 3 : i < 8 ? 3 : (i & 3);
        mbar_wait(bar_empty + 8 * (i % B_NSLOT), (i / B_NSLOT + 1) & 1);
        bulk_ld_elect<12544>(sb + B_RING + (i % B_NSLOT) * B_SLOT, dsrc[kp >> 1] + ((p + 1 + ci) & 3) * 25088 + (kp & 1) * 12544, bar_full + 8 * (i % B_NSLOT));
      }
    } else if (warp >= 10) {
      const int t64 = tid - 320;
      load_ep();
      const int r = (lane >> 1) & 7, c = (j & 3) * 2 + (lane & 1);
      const uint32_t src = sb + B_SA + (t64 >> 4) * 2048 + (j >> 2) * 1024 + r * 128 + ((c ^ r) << 4);
      float a[16];
#pragma unroll
      for (int k = 0; k < 16; k++) a[k] = 0.f;
#pragma unroll 1
      for (int i = 0; i < 14; i++) {
        mbar_wait(bar_h + 8 * i, 0);
        uint4 v = lds128(src + i * 8192);
        float e[8] = {bf_lo(v.x), bf_hi(v.x), bf_lo(v.y), bf_hi(v.y), bf_lo(v.z), bf_hi(v.z), bf_lo(v.w), bf_hi(v.w)};
#pragma unroll
        for (int k = 0; k < 8; k++) { a[2 * k] += e[k]; a[2 * k + 1] = fmaf(e[k], e[k], a[2 * k + 1]); }
        __nanosleep(160);
      }
      __syncwarp();
      if (lane == 0) { asm volatile("mbarrier.arrive.shared::cluster.b64 _, [%0];" ::"r"(mapa(bar_afree, rank ^ 1)) : "memory"); }
#pragma unroll
      for (int rd = 0; rd < 4; rd++) {
        const int n = 8 >> rd;
        const bool up = lane & (2 * n);
#pragma unroll
        for (int k = 0; k < 8; k++) {
          if (k < n) {
            float keep = up ? a[k + n] : a[k], give = up ? a[k] : a[k + n];
            a[k] = keep + __shfl_xor_sync(~0u, give, 2 * n);
          }
        }
      }
      float* red = (float*)(sm + B_RED);
      red[(warp & 1) * 32 + (lane & 1) * 16 + (lane >> 1)] = a[0];
      bar_sync(1, 64);
      if (t64 < 16) {
        float mean = (red[2 * t64] + red[32 + 2 * t64]) * (1.f / DM);
        float var = fmaxf(fmaf(-mean, mean, (red[2 * t64 + 1] + red[33 + 2 * t64]) * (1.f / DM)), 0.f);
        float rs = ln_rstd(var);
        asm volatile("st.relaxed.gpu.global.u32 [%0], %1;"
                     ::"l"(g_stat2 + rt * 128 + j * 16 + t64), "r"((__float_as_uint(rs * rs) & ~1u) | ((ep >> 7) & 1u)) : "memory");
      }
      if (t64 == 0) TR(1, 2);
      if (lane == 0) {
        const int w = warp & 1;
        for (int cc = 0; cc < 2; cc++) {
          mbar_wait(bar_out + 8 * (cc * 2 + w), 0);
          asm volatile("cp.async.bulk.global.shared::cta.bulk_group [%0], [%1], 7168;"
                       ::"l"(g_part + (size_t)(blockIdx.x * 3 + cc) * 896 + w * 448), "r"(out_addr(cc, w)) : "memory");
          if (w) TR(1, 27 + cc);
        }
        asm volatile("cp.async.bulk.commit_group;" ::: "memory");
        asm volatile("cp.async.bulk.wait_group 0;" ::: "memory");
      }
    }
  } else {
    asm volatile("setmaxnreg.inc.sync.aligned.u32 232;");
    asm volatile("barrier.cluster.wait.aligned;" ::: "memory");
    uint32_t hh[56];
    const bool relt = t128 == 0;
    auto release = [&](int sl) { if (relt) mbar_arrive(bar_empty + 8 * sl); };
    auto send_hh = [&](int q) {
      const uint32_t da = mapa(sb + a_slot(2 * q + wg, cg ^ 4) + t128 * 16, rank ^ 1), db = mapa(bar_hh + 8 * (2 * q + wg), rank ^ 1);
#pragma unroll
      for (int i = 0; i < 7; i++)
        asm volatile("st.async.weak.shared::cluster.mbarrier::complete_tx::bytes.v4.b32 [%0], {%1, %2, %3, %4}, [%5];"
                     ::"r"(da + i * 2048), "r"(hh[28 * q + 4 * i]), "r"(hh[28 * q + 4 * i + 1]),
                       "r"(hh[28 * q + 4 * i + 2]), "r"(hh[28 * q + 4 * i + 3]), "r"(db) : "memory");
    };
    uint32_t alo = ((sb + B_SA + wg * 1024) & 0x3FFFF) >> 4;
    uint32_t blo = (((sb + B_RING) & 0x3FFFF) >> 4) | (8u << 16);
    const uint32_t clo = ((sb + B_CS) & 0x3FFFF) >> 4;
    uint32_t nm0, nm1;
    if (wg == 1) bar_sync(3, 256);
#define G1S(Q, ST) do { if (ST % 7 == 0) { alo = pin(alo); blo = pin(blo); }   \
      g1_stage<Q, ST>(acc, alo, blo, bar_full, bar_h); wg_commit(); \
      if (ST > 0) { wg_wait<1>(); release((Q * 14 + ST - 1) % B_NSLOT); } } while (0)
#define G1HH(Q) do { \
      _Pragma("unroll") \
      for (int i = 0; i < 28; i++) hh[28 * Q + i] = pack_bf16(acc[2 * i] * acc[56 + 2 * i], acc[2 * i + 1] * acc[57 + 2 * i]); \
    } while (0)
    {
      float acc[116];
      G1S(0, 0);
      if (tid == 0) TR(1, 3);
      G1S(0, 1);
      if (wg == 0) asm volatile("bar.arrive 3, 256;" ::: "memory");
      G1S(0, 2); G1S(0, 3); G1S(0, 4); G1S(0, 5); G1S(0, 6); G1S(0, 7); G1S(0, 8); G1S(0, 9); G1S(0, 10); G1S(0, 11); G1S(0, 12);
      G1S(0, 13);
      if (tid == 0) TR(1, 4);
      mbar_wait(bar_cs, 0);
      wg_wait<0>(); reg_fence(acc); release(13 % B_NSLOT);
      {
        const uint32_t msk = t == 0 ? 0xFFFFFFFFu : t == 1 ? 0xFFFFu : 0u;
        const float a = acc[112] * (-1.f / DM), b = acc[114] * (-1.f / DM);
        nm0 = pack_bf16(a, a) & msk; nm1 = pack_bf16(b, b) & msk;
      }
      wg_fence();
      wgmma_rs224<0, 8, 1>(*(float(*)[112])acc, nm0, nm1, 0u, 0u, clo);
      wg_commit(); wg_wait<0>(); reg_fence(acc);
      G1HH(0);
      if (tid == 0) TR(1, 5);
      G1S(1, 0); G1S(1, 1); G1S(1, 2); G1S(1, 3); G1S(1, 4); G1S(1, 5); G1S(1, 6);
      if (relt) asm volatile("mbarrier.arrive.shared::cluster.b64 _, [%0];" ::"r"(mapa(bar_afree, rank ^ 1)) : "memory");
      G1S(1, 7); G1S(1, 8); G1S(1, 9);
      if (relt) asm volatile("mbarrier.arrive.shared::cluster.b64 _, [%0];" ::"r"(mapa(bar_afree + 8, rank ^ 1)) : "memory");
      mbar_wait(bar_afree, 0);
      send_hh(0);
      G1S(1, 10); G1S(1, 11); G1S(1, 12);
      load_ep();
      g1_stage<1, 13>(acc, alo, blo, bar_full, bar_h);
      wgmma_rs224<224, 8, 1>(*(float(*)[112])acc, nm0, nm1, 0u, 0u, clo);
      wg_commit(); wg_wait<1>(); release(26 % B_NSLOT);
      wg_wait<0>(); reg_fence(acc); release(27 % B_NSLOT);
      G1HH(1);
      if (tid == 0) TR(1, 6);
    }
    float accA[28], accB[28];
    uint32_t ph0[28], ph1[28];
    ep = pin(ep >> 7); tag = pin((ep & 1u) << 16);
#define ISSUE(acc, I, a, FIRST) do { \
      constexpr int s_ = 28 + (I), sl_ = s_ % B_NSLOT; \
      if (sl_ == 0) blo = pin(blo); \
      mbar_wait(bar_full + 8 * sl_, (s_ / B_NSLOT) & 1); \
      wg_fence(); \
      wgmma_rs56<(sl_ * B_SLOT + 0 * 256) / 16, 112, !(FIRST)>(acc, (a)[0], (a)[1], (a)[2], (a)[3], blo); \
      wgmma_rs56<(sl_ * B_SLOT + 1 * 256) / 16, 112, 1>(acc, (a)[4], (a)[5], (a)[6], (a)[7], blo); \
      wgmma_rs56<(sl_ * B_SLOT + 2 * 256) / 16, 112, 1>(acc, (a)[8], (a)[9], (a)[10], (a)[11], blo); \
      wgmma_rs56<(sl_ * B_SLOT + 3 * 256) / 16, 112, 1>(acc, (a)[12], (a)[13], (a)[14], (a)[15], blo); \
      wgmma_rs56<(sl_ * B_SLOT + 4 * 256) / 16, 112, 1>(acc, (a)[16], (a)[17], (a)[18], (a)[19], blo); \
      wgmma_rs56<(sl_ * B_SLOT + 5 * 256) / 16, 112, 1>(acc, (a)[20], (a)[21], (a)[22], (a)[23], blo); \
      wgmma_rs56<(sl_ * B_SLOT + 6 * 256) / 16, 112, 1>(acc, (a)[24], (a)[25], (a)[26], (a)[27], blo); \
      wg_commit(); } while (0)
    auto rel = [&](int i) { release((28 + i) % B_NSLOT); };
    auto tg = [&](uint32_t v) { return (v & 0xFFFEFFFFu) | tag; };
    auto send = [&](float (&acc)[28], int cc) {
      reg_fence(acc);
      const uint32_t a = out_addr(cc, wg) + wq * 1792;
#pragma unroll
      for (int q = 0; q < 3; q++)
        sts128(a + q * 512 + lane * 16, pack_bf16(acc[8 * q], acc[8 * q + 1]), pack_bf16(acc[8 * q + 2], acc[8 * q + 3]),
               pack_bf16(acc[8 * q + 4], acc[8 * q + 5]), tg(pack_bf16(acc[8 * q + 6], acc[8 * q + 7])));
      sts64(a + 1536 + lane * 8, pack_bf16(acc[24], acc[25]), tg(pack_bf16(acc[26], acc[27])));
      asm volatile("fence.proxy.async.shared::cta;" ::: "memory");
      mbar_arrive(bar_out + 8 * (cc * 2 + wg));
    };
    auto load_hh = [&](uint32_t (&d)[28], int q) {
      mbar_wait(bar_hh + 8 * (2 * q + wg), 0);
      const uint32_t a = sb + a_slot(2 * q + wg, cg) + t128 * 16;
#pragma unroll
      for (int i = 0; i < 7; i++) {
        const uint4 v = lds128(a + i * 2048);
        d[4 * i] = v.x; d[4 * i + 1] = v.y; d[4 * i + 2] = v.z; d[4 * i + 3] = v.w;
      }
    };
    ISSUE(accA, 0, hh, true);
    mbar_wait(bar_afree + 8, 0);
    send_hh(1);
    ISSUE(accA, 1, hh + 28, false);
    load_hh(ph0, 0);
    wg_wait<1>(); rel(0);
    ISSUE(accA, 2, ph0, false);      wg_wait<1>(); rel(1);
    ISSUE(accB, 3, hh, true);        wg_wait<1>(); rel(2);
    ISSUE(accB, 4, hh + 28, false);  wg_wait<1>(); rel(3);
    ISSUE(accB, 5, ph0, false);
    if (tid == 0) TR(1, 11);
    load_hh(ph1, 1);
    wg_wait<1>(); rel(4);
    ISSUE(accA, 6, ph1, false);      wg_wait<1>(); rel(5);
    ISSUE(accB, 7, ph1, false);      wg_wait<1>(); rel(6); send(accA, 0);
    ISSUE(accA, 8, hh, true);        wg_wait<1>(); rel(7); send(accB, 1);
    if (tid == 0) TR(1, 13);
    ISSUE(accA, 9, hh + 28, false);  wg_wait<1>(); rel(8);
    ISSUE(accA, 10, ph0, false);
    ISSUE(accA, 11, ph1, false);
    const int row = rt * 128 + wg * 64 + wq * 16 + g;
    uint32_t r20, r21;
    asm volatile("ld.relaxed.gpu.global.u32 %0, [%1];" : "=r"(r20) : "l"(g_stat2 + row) : "memory");
    asm volatile("ld.relaxed.gpu.global.u32 %0, [%1];" : "=r"(r21) : "l"(g_stat2 + row + 8) : "memory");
    ISSUE(accB, 12, hh, true);
    wg_wait<1>();
    {
      reg_fence(accA);
      uint4* pd = g_part + (size_t)(blockIdx.x * 3 + 2) * 896 + warp * 112 + lane;
#pragma unroll
      for (int q = 0; q < 3; q++)
        st128(pd + q * 32, pack_bf16(accA[8 * q], accA[8 * q + 1]), pack_bf16(accA[8 * q + 2], accA[8 * q + 3]),
              pack_bf16(accA[8 * q + 4], accA[8 * q + 5]), tg(pack_bf16(accA[8 * q + 6], accA[8 * q + 7])));
      asm volatile("{\n.reg .b64 v;\nmov.b64 v, {%1, %2};\nst.relaxed.gpu.global.b64 [%0], v;\n}"
                   ::"l"((uint2*)(pd + 96) - lane), "r"(pack_bf16(accA[24], accA[25])), "r"(tg(pack_bf16(accA[26], accA[27]))) : "memory");
    }
    if (tid == 0) TR(1, 16);
    ISSUE(accB, 13, hh + 28, false);
    ISSUE(accB, 14, ph0, false);
    uint32_t in0[14], in1[14], in2[14];
    in_load(in0, in_src(0, warp) + lane);
    in_load(in1, in_src(1, warp) + lane);
    ISSUE(accB, 15, ph1, false);
    if (tid == 0) TR(1, 7);
    {
      int it = 0;
      while ((((r20 ^ ep) | (r21 ^ ep)) & 1u) && ++it < 400000) {
        asm volatile("ld.relaxed.gpu.global.u32 %0, [%1];" : "=r"(r20) : "l"(g_stat2 + row) : "memory");
        asm volatile("ld.relaxed.gpu.global.u32 %0, [%1];" : "=r"(r21) : "l"(g_stat2 + row + 8) : "memory");
      }
    }
    wg_wait<1>();
    in_load(in2, in_src(2, warp) + lane);
    in_check(in0, 0, warp); in_check(in1, 1, warp);
#pragma unroll
    for (int i = 0; i < 14; i++) { accA[2 * i] = bf_lo(in0[i]) + bf_lo(in1[i]); accA[2 * i + 1] = bf_hi(in0[i]) + bf_hi(in1[i]); }
    if (tid == 0) TR(1, 12);
    wg_wait<0>();
    reg_fence(accB);
    uint32_t hres[16];
#pragma unroll
    for (int i = 0; i < 4; i++) {
      int qq = lane >> 3, r = lane & 7, kg = 7 * cg + 2 * i + (qq >> 1), c = 2 * wq + (qq & 1);
      if (kg > 55) kg = 55;
      asm volatile("ldmatrix.sync.aligned.m8n8.x4.trans.shared.b16 {%0,%1,%2,%3}, [%4];"
                   : "=r"(hres[4 * i]), "=r"(hres[4 * i + 1]), "=r"(hres[4 * i + 2]), "=r"(hres[4 * i + 3])
                   : "r"(sb + B_SA + kg * 2048 + wg * 1024 + r * 128 + ((c ^ r) << 4)) : "memory");
    }
#pragma unroll
    for (int i = 0; i < 28; i++) accB[i] += accA[i];
    if (tid == 0) TR(1, 9);
    in_check(in2, 2, warp);
#pragma unroll
    for (int i = 0; i < 14; i++) { accB[2 * i] += bf_lo(in2[i]); accB[2 * i + 1] += bf_hi(in2[i]); }
    uint32_t* o0 = (uint32_t*)(out + (size_t)row * DM + 56 * cg + 2 * t);
    uint32_t* o1 = o0 + 8 * DM / 2;
#pragma unroll
    for (int i = 0; i < 7; i++) {
      o0[4 * i] = hadd2_bf(hres[2 * i], pack_bf16(accB[4 * i] * __uint_as_float(r20), accB[4 * i + 1] * __uint_as_float(r20)));
      o1[4 * i] = hadd2_bf(hres[2 * i + 1], pack_bf16(accB[4 * i + 2] * __uint_as_float(r21), accB[4 * i + 3] * __uint_as_float(r21)));
    }
    if (tid == 0) TR(1, 10);
    if (tid == 128) TR(1, 15);
  }
}

extern "C" void kernel_launch(void* const* d_in, const int* in_sizes, int n_in, void* d_out, int out_size) {
  const __nv_bfloat16* x = (const __nv_bfloat16*)d_in[0];
  const __nv_bfloat16 *are = (const __nv_bfloat16*)d_in[1], *aim = (const __nv_bfloat16*)d_in[2], *bre = (const __nv_bfloat16*)d_in[3],
                      *bim = (const __nv_bfloat16*)d_in[4], *cre = (const __nv_bfloat16*)d_in[5], *cim = (const __nv_bfloat16*)d_in[6],
                      *logdt = (const __nv_bfloat16*)d_in[7], *dskip = (const __nv_bfloat16*)d_in[8];
  const __nv_bfloat16 *wg = (const __nv_bfloat16*)d_in[10], *wu = (const __nv_bfloat16*)d_in[11], *wd = (const __nv_bfloat16*)d_in[12];

  static bool init = false;
  if (!init) {
    init = true;
    cudaFuncSetAttribute(k_ffn, cudaFuncAttributeMaxDynamicSharedMemorySize, B_SMEM);
    cudaFuncSetAttribute(k_front, cudaFuncAttributeMaxDynamicSharedMemorySize, A_SMEM);
  }
  cudaStream_t st = cudaStreamPerThread;
  k_front<<<128, 512, A_SMEM, st>>>(
      x, (const uint32_t*)are, (const uint32_t*)aim, (const uint32_t*)bre, (const uint32_t*)bim, (const uint32_t*)cre, (const uint32_t*)cim,
      (const unsigned short*)logdt, (const unsigned short*)dskip, (const uint4*)wg, (const uint4*)wu, (const uint4*)wd);
  cudaLaunchConfig_t cfg = {};
  cfg.gridDim = dim3(128); cfg.blockDim = dim3(384); cfg.dynamicSmemBytes = B_SMEM; cfg.stream = st;
  cudaLaunchAttribute at[1];
  at[0].id = cudaLaunchAttributeProgrammaticStreamSerialization; at[0].val.programmaticStreamSerializationAllowed = 1;
  cfg.attrs = at; cfg.numAttrs = 1;
  cudaLaunchKernelEx(&cfg, k_ffn, (__nv_bfloat16*)d_out);
}
```

```cpp
#include <cuda_runtime.h>
#include <cuda_bf16.h>
#include <cuda_fp16.h>
#include <stdint.h>

constexpr int LSEQ = 2048, DM = 448;

__device__ uint4    g_himg[16 * 114688 / 16];
__device__ uint4    g_cimg[8 * 2 * 224];
__device__ uint32_t g_stat2[LSEQ];
__device__ uint4    g_part[128 * 3 * 896];
__device__ uint4    g_wimg[8 * 602112 / 16];
__device__ uint4    g_ux[DM * 128 * 4];
__device__ unsigned g_cnt1;

#define TR(k, i) do {} while (0)
__device__ __forceinline__ uint32_t s2u(const void* p) { return (uint32_t)__cvta_generic_to_shared(p); }
__device__ __forceinline__ void mbar_init(uint32_t b, int c) { asm volatile("mbarrier.init.shared::cta.b64 [%0], %1;" ::"r"(b), "r"(c)); }
__device__ __forceinline__ void mbar_expect(uint32_t b, int bytes) { asm volatile("mbarrier.arrive.expect_tx.shared::cta.b64 _, [%0], %1;" ::"r"(b), "r"(bytes) : "memory"); }
__device__ __forceinline__ void mbar_arrive(uint32_t b) { asm volatile("mbarrier.arrive.shared::cta.b64 _, [%0];" ::"r"(b) : "memory"); }
__device__ __forceinline__ void mbar_wait(uint32_t b, int ph) {
  asm volatile("{\n.reg .pred p;\n.reg .b32 n;\nmov.b32 n, 0;\nLW:\nmbarrier.try_wait.parity.shared::cta.b64 p, [%0], %1;\n@p bra LD;\n"
               "add.u32 n, n, 1;\nsetp.lt.u32 p, n, 4000000;\n@p bra LW;\ntrap;\nLD:\n}" ::"r"(b), "r"(ph) : "memory");
}
__device__ __forceinline__ bool mbar_test(uint32_t b, int ph) {
  uint32_t ok;
  asm volatile("{\n.reg .pred p;\nmbarrier.test_wait.parity.shared::cta.b64 p, [%1], %2;\nselp.u32 %0, 1, 0, p;\n}" : "=r"(ok) : "r"(b), "r"(ph) : "memory");
  return ok;
}
__device__ __forceinline__ void wg_fence() { asm volatile("wgmma.fence.sync.aligned;" ::: "memory"); }
__device__ __forceinline__ void wg_commit() { asm volatile("wgmma.commit_group.sync.aligned;" ::: "memory"); }
template <int N> __device__ __forceinline__ void wg_wait() { asm volatile("wgmma.wait_group.sync.aligned %0;" ::"n"(N) : "memory"); }
template <int N> __device__ __forceinline__ void reg_fence(float (&a)[N]) {
#pragma unroll
  for (int i = 0; i < N; i++) asm volatile("" : "+f"(a[i])::"memory");
}
__device__ __forceinline__ uint32_t pack_bf16(float lo, float hi) {
  uint32_t r; asm("cvt.rn.bf16x2.f32 %0, %1, %2;" : "=r"(r) : "f"(hi), "f"(lo)); return r;
}
__device__ __forceinline__ float bf_lo(uint32_t v) { return __uint_as_float(v << 16); }
__device__ __forceinline__ float bf_hi(uint32_t v) { return __uint_as_float(v & 0xFFFF0000u); }
__device__ __forceinline__ float rbf(float x) { return __bfloat162float(__float2bfloat16_rn(x)); }
__device__ __forceinline__ uint32_t hmul2_bf(uint32_t a, uint32_t b) { uint32_t r; asm("mul.rn.bf16x2 %0, %1, %2;" : "=r"(r) : "r"(a), "r"(b)); return r; }
__device__ __forceinline__ uint32_t hadd2_bf(uint32_t a, uint32_t b) { uint32_t r; asm("add.rn.bf16x2 %0, %1, %2;" : "=r"(r) : "r"(a), "r"(b)); return r; }
__device__ __forceinline__ void bulk_ld(uint32_t dst, const void* src, int bytes, uint32_t bar) {
  asm volatile("cp.async.bulk.shared::cluster.global.mbarrier::complete_tx::bytes [%0], [%1], %2, [%3];"
               ::"r"(dst), "l"(src), "r"(bytes), "r"(bar) : "memory");
}

template <int BYTES>
__device__ __forceinline__ void bulk_ld_elect(uint32_t dst, const void* src, uint32_t bar) {
  asm volatile("{\n.reg .pred p;\nelect.sync _|p, 0xffffffff;\n"
               "@p mbarrier.arrive.expect_tx.shared::cta.b64 _, [%2], %3;\n"
               "@p cp.async.bulk.shared::cluster.global.mbarrier::complete_tx::bytes [%0], [%1], %3, [%2];\n}"
               ::"r"(dst), "l"(src), "r"(bar), "n"(BYTES) : "memory");
}
template <int BYTES>
__device__ __forceinline__ void bulk_ld_mc_elect(uint32_t dst, const void* src, uint32_t bar) {
  asm volatile("{\n.reg .pred p;\nelect.sync _|p, 0xffffffff;\n"
               "@p mbarrier.arrive.expect_tx.shared::cta.b64 _, [%2], %3;\n"
               "@p cp.async.bulk.shared::cluster.global.mbarrier::complete_tx::bytes.multicast::cluster [%0], [%1], %4, [%2], %5;\n}"
               ::"r"(dst), "l"(src), "r"(bar), "n"(2 * BYTES), "n"(BYTES), "h"((uint16_t)3) : "memory");
}
template <int AOFF, uint32_t AHI, int BOFF, uint32_t BHI, int ACC>
__device__ __forceinline__ void wgmma_ss224(float (&d)[112], uint32_t alo, uint32_t blo) {
  asm volatile("{\n.reg .pred p;\n.reg .b64 ad, bd;\nsetp.ne.b32 p, %118, 0;\n"
    "mov.b64 ad, {%112, %115};\nadd.s64 ad, ad, %114;\nmov.b64 bd, {%113, %117};\nadd.s64 bd, bd, %116;\n"
    "wgmma.mma_async.sync.aligned.m64n224k16.f32.bf16.bf16 {%0,%1,%2,%3,%4,%5,%6,%7,%8,%9,%10,%11,%12,%13,%14,%15,%16,%17,%18,%19,%20,%21,%22,%23,%24,%25,%26,%27,%28,%29,%30,%31,%32,%33,%34,%35,%36,%37,%38,%39,%40,%41,%42,%43,%44,%45,%46,%47,%48,%49,%50,%51,%52,%53,%54,%55,%56,%57,%58,%59,%60,%61,%62,%63,%64,%65,%66,%67,%68,%69,%70,%71,%72,%73,%74,%75,%76,%77,%78,%79,%80,%81,%82,%83,%84,%85,%86,%87,%88,%89,%90,%91,%92,%93,%94,%95,%96,%97,%98,%99,%100,%101,%102,%103,%104,%105,%106,%107,%108,%109,%110,%111}, ad, bd, p, 1, 1, 1, 1;\n}\n"
    : "+f"(d[0]),"+f"(d[1]),"+f"(d[2]),"+f"(d[3]),"+f"(d[4]),"+f"(d[5]),"+f"(d[6]),"+f"(d[7]),"+f"(d[8]),"+f"(d[9]),"+f"(d[10]),"+f"(d[11]),"+f"(d[12]),"+f"(d[13]),"+f"(d[14]),"+f"(d[15]),"+f"(d[16]),"+f"(d[17]),"+f"(d[18]),"+f"(d[19]),"+f"(d[20]),"+f"(d[21]),"+f"(d[22]),"+f"(d[23]),"+f"(d[24]),"+f"(d[25]),"+f"(d[26]),"+f"(d[27]),"+f"(d[28]),"+f"(d[29]),"+f"(d[30]),"+f"(d[31]),"+f"(d[32]),"+f"(d[33]),"+f"(d[34]),"+f"(d[35]),"+f"(d[36]),"+f"(d[37]),"+f"(d[38]),"+f"(d[39]),"+f"(d[40]),"+f"(d[41]),"+f"(d[42]),"+f"(d[43]),"+f"(d[44]),"+f"(d[45]),"+f"(d[46]),"+f"(d[47]),"+f"(d[48]),"+f"(d[49]),"+f"(d[50]),"+f"(d[51]),"+f"(d[52]),"+f"(d[53]),"+f"(d[54]),"+f"(d[55]),"+f"(d[56]),"+f"(d[57]),"+f"(d[58]),"+f"(d[59]),"+f"(d[60]),"+f"(d[61]),"+f"(d[62]),"+f"(d[63]),"+f"(d[64]),"+f"(d[65]),"+f"(d[66]),"+f"(d[67]),"+f"(d[68]),"+f"(d[69]),"+f"(d[70]),"+f"(d[71]),"+f"(d[72]),"+f"(d[73]),"+f"(d[74]),"+f"(d[75]),"+f"(d[76]),"+f"(d[77]),"+f"(d[78]),"+f"(d[79]),"+f"(d[80]),"+f"(d[81]),"+f"(d[82]),"+f"(d[83]),"+f"(d[84]),"+f"(d[85]),"+f"(d[86]),"+f"(d[87]),"+f"(d[88]),"+f"(d[89]),"+f"(d[90]),"+f"(d[91]),"+f"(d[92]),"+f"(d[93]),"+f"(d[94]),"+f"(d[95]),"+f"(d[96]),"+f"(d[97]),"+f"(d[98]),"+f"(d[99]),"+f"(d[100]),"+f"(d[101]),"+f"(d[102]),"+f"(d[103]),"+f"(d[104]),"+f"(d[105]),"+f"(d[106]),"+f"(d[107]),"+f"(d[108]),"+f"(d[109]),"+f"(d[110]),"+f"(d[111])
    : "r"(alo), "r"(blo), "n"(AOFF), "n"(AHI), "n"(BOFF), "n"(BHI), "n"(ACC));
}
template <int AOFF, uint32_t AHI, int BOFF, uint32_t BHI, int ACC>
__device__ __forceinline__ void wgmma_ss232(float (&d)[116], uint32_t alo, uint32_t blo) {
  asm volatile("{\n.reg .pred p;\n.reg .b64 ad, bd;\nsetp.ne.b32 p, %122, 0;\n"
    "mov.b64 ad, {%116, %119};\nadd.s64 ad, ad, %118;\nmov.b64 bd, {%117, %121};\nadd.s64 bd, bd, %120;\n"
    "wgmma.mma_async.sync.aligned.m64n232k16.f32.bf16.bf16 {%0,%1,%2,%3,%4,%5,%6,%7,%8,%9,%10,%11,%12,%13,%14,%15,%16,%17,%18,%19,%20,%21,%22,%23,%24,%25,%26,%27,%28,%29,%30,%31,%32,%33,%34,%35,%36,%37,%38,%39,%40,%41,%42,%43,%44,%45,%46,%47,%48,%49,%50,%51,%52,%53,%54,%55,%56,%57,%58,%59,%60,%61,%62,%63,%64,%65,%66,%67,%68,%69,%70,%71,%72,%73,%74,%75,%76,%77,%78,%79,%80,%81,%82,%83,%84,%85,%86,%87,%88,%89,%90,%91,%92,%93,%94,%95,%96,%97,%98,%99,%100,%101,%102,%103,%104,%105,%106,%107,%108,%109,%110,%111,%112,%113,%114,%115}, ad, bd, p, 1, 1, 1, 1;\n}\n"
    : "+f"(d[0]),"+f"(d[1]),"+f"(d[2]),"+f"(d[3]),"+f"(d[4]),"+f"(d[5]),"+f"(d[6]),"+f"(d[7]),"+f"(d[8]),"+f"(d[9]),"+f"(d[10]),"+f"(d[11]),"+f"(d[12]),"+f"(d[13]),"+f"(d[14]),"+f"(d[15]),"+f"(d[16]),"+f"(d[17]),"+f"(d[18]),"+f"(d[19]),"+f"(d[20]),"+f"(d[21]),"+f"(d[22]),"+f"(d[23]),"+f"(d[24]),"+f"(d[25]),"+f"(d[26]),"+f"(d[27]),"+f"(d[28]),"+f"(d[29]),"+f"(d[30]),"+f"(d[31]),"+f"(d[32]),"+f"(d[33]),"+f"(d[34]),"+f"(d[35]),"+f"(d[36]),"+f"(d[37]),"+f"(d[38]),"+f"(d[39]),"+f"(d[40]),"+f"(d[41]),"+f"(d[42]),"+f"(d[43]),"+f"(d[44]),"+f"(d[45]),"+f"(d[46]),"+f"(d[47]),"+f"(d[48]),"+f"(d[49]),"+f"(d[50]),"+f"(d[51]),"+f"(d[52]),"+f"(d[53]),"+f"(d[54]),"+f"(d[55]),"+f"(d[56]),"+f"(d[57]),"+f"(d[58]),"+f"(d[59]),"+f"(d[60]),"+f"(d[61]),"+f"(d[62]),"+f"(d[63]),"+f"(d[64]),"+f"(d[65]),"+f"(d[66]),"+f"(d[67]),"+f"(d[68]),"+f"(d[69]),"+f"(d[70]),"+f"(d[71]),"+f"(d[72]),"+f"(d[73]),"+f"(d[74]),"+f"(d[75]),"+f"(d[76]),"+f"(d[77]),"+f"(d[78]),"+f"(d[79]),"+f"(d[80]),"+f"(d[81]),"+f"(d[82]),"+f"(d[83]),"+f"(d[84]),"+f"(d[85]),"+f"(d[86]),"+f"(d[87]),"+f"(d[88]),"+f"(d[89]),"+f"(d[90]),"+f"(d[91]),"+f"(d[92]),"+f"(d[93]),"+f"(d[94]),"+f"(d[95]),"+f"(d[96]),"+f"(d[97]),"+f"(d[98]),"+f"(d[99]),"+f"(d[100]),"+f"(d[101]),"+f"(d[102]),"+f"(d[103]),"+f"(d[104]),"+f"(d[105]),"+f"(d[106]),"+f"(d[107]),"+f"(d[108]),"+f"(d[109]),"+f"(d[110]),"+f"(d[111]),"+f"(d[112]),"+f"(d[113]),"+f"(d[114]),"+f"(d[115])
    : "r"(alo), "r"(blo), "n"(AOFF), "n"(AHI), "n"(BOFF), "n"(BHI), "n"(ACC));
}
template <int OFF, uint32_t BHI, int ACC>
__device__ __forceinline__ void wgmma_rs224(float (&d)[112], uint32_t a0, uint32_t a1, uint32_t a2, uint32_t a3, uint32_t blo) {
  asm volatile("{\n.reg .pred p;\n.reg .b64 bd;\nsetp.ne.b32 p, %119, 0;\nmov.b64 bd, {%116, %118};\nadd.s64 bd, bd, %117;\n"
    "wgmma.mma_async.sync.aligned.m64n224k16.f32.bf16.bf16 {%0,%1,%2,%3,%4,%5,%6,%7,%8,%9,%10,%11,%12,%13,%14,%15,%16,%17,%18,%19,%20,%21,%22,%23,%24,%25,%26,%27,%28,%29,%30,%31,%32,%33,%34,%35,%36,%37,%38,%39,%40,%41,%42,%43,%44,%45,%46,%47,%48,%49,%50,%51,%52,%53,%54,%55,%56,%57,%58,%59,%60,%61,%62,%63,%64,%65,%66,%67,%68,%69,%70,%71,%72,%73,%74,%75,%76,%77,%78,%79,%80,%81,%82,%83,%84,%85,%86,%87,%88,%89,%90,%91,%92,%93,%94,%95,%96,%97,%98,%99,%100,%101,%102,%103,%104,%105,%106,%107,%108,%109,%110,%111}, {%112,%113,%114,%115}, bd, p, 1, 1, 1;\n}\n"
    : "+f"(d[0]),"+f"(d[1]),"+f"(d[2]),"+f"(d[3]),"+f"(d[4]),"+f"(d[5]),"+f"(d[6]),"+f"(d[7]),"+f"(d[8]),"+f"(d[9]),"+f"(d[10]),"+f"(d[11]),"+f"(d[12]),"+f"(d[13]),"+f"(d[14]),"+f"(d[15]),"+f"(d[16]),"+f"(d[17]),"+f"(d[18]),"+f"(d[19]),"+f"(d[20]),"+f"(d[21]),"+f"(d[22]),"+f"(d[23]),"+f"(d[24]),"+f"(d[25]),"+f"(d[26]),"+f"(d[27]),"+f"(d[28]),"+f"(d[29]),"+f"(d[30]),"+f"(d[31]),"+f"(d[32]),"+f"(d[33]),"+f"(d[34]),"+f"(d[35]),"+f"(d[36]),"+f"(d[37]),"+f"(d[38]),"+f"(d[39]),"+f"(d[40]),"+f"(d[41]),"+f"(d[42]),"+f"(d[43]),"+f"(d[44]),"+f"(d[45]),"+f"(d[46]),"+f"(d[47]),"+f"(d[48]),"+f"(d[49]),"+f"(d[50]),"+f"(d[51]),"+f"(d[52]),"+f"(d[53]),"+f"(d[54]),"+f"(d[55]),"+f"(d[56]),"+f"(d[57]),"+f"(d[58]),"+f"(d[59]),"+f"(d[60]),"+f"(d[61]),"+f"(d[62]),"+f"(d[63]),"+f"(d[64]),"+f"(d[65]),"+f"(d[66]),"+f"(d[67]),"+f"(d[68]),"+f"(d[69]),"+f"(d[70]),"+f"(d[71]),"+f"(d[72]),"+f"(d[73]),"+f"(d[74]),"+f"(d[75]),"+f"(d[76]),"+f"(d[77]),"+f"(d[78]),"+f"(d[79]),"+f"(d[80]),"+f"(d[81]),"+f"(d[82]),"+f"(d[83]),"+f"(d[84]),"+f"(d[85]),"+f"(d[86]),"+f"(d[87]),"+f"(d[88]),"+f"(d[89]),"+f"(d[90]),"+f"(d[91]),"+f"(d[92]),"+f"(d[93]),"+f"(d[94]),"+f"(d[95]),"+f"(d[96]),"+f"(d[97]),"+f"(d[98]),"+f"(d[99]),"+f"(d[100]),"+f"(d[101]),"+f"(d[102]),"+f"(d[103]),"+f"(d[104]),"+f"(d[105]),"+f"(d[106]),"+f"(d[107]),"+f"(d[108]),"+f"(d[109]),"+f"(d[110]),"+f"(d[111])
    : "r"(a0), "r"(a1), "r"(a2), "r"(a3), "r"(blo), "n"(OFF), "n"(BHI), "n"(ACC));
}
template <int OFF, uint32_t BHI, int ACC>
__device__ __forceinline__ void wgmma_rs56(float (&d)[28], uint32_t a0, uint32_t a1, uint32_t a2, uint32_t a3, uint32_t blo) {
  asm volatile("{\n.reg .pred p;\n.reg .b64 bd;\nsetp.ne.b32 p, %35, 0;\nmov.b64 bd, {%32, %34};\nadd.s64 bd, bd, %33;\n"
    "wgmma.mma_async.sync.aligned.m64n56k16.f32.bf16.bf16 {%0,%1,%2,%3,%4,%5,%6,%7,%8,%9,%10,%11,%12,%13,%14,%15,%16,%17,%18,%19,%20,%21,%22,%23,%24,%25,%26,%27}, {%28,%29,%30,%31}, bd, p, 1, 1, 1;\n}\n"
    : "+f"(d[0]),"+f"(d[1]),"+f"(d[2]),"+f"(d[3]),"+f"(d[4]),"+f"(d[5]),"+f"(d[6]),"+f"(d[7]),"+f"(d[8]),"+f"(d[9]),"+f"(d[10]),"+f"(d[11]),"+f"(d[12]),"+f"(d[13]),"+f"(d[14]),"+f"(d[15]),"+f"(d[16]),"+f"(d[17]),"+f"(d[18]),"+f"(d[19]),"+f"(d[20]),"+f"(d[21]),"+f"(d[22]),"+f"(d[23]),"+f"(d[24]),"+f"(d[25]),"+f"(d[26]),"+f"(d[27])
    : "r"(a0), "r"(a1), "r"(a2), "r"(a3), "r"(blo), "n"(OFF), "n"(BHI), "n"(ACC));
}

__device__ __forceinline__ void st128(uint4* p, uint32_t a, uint32_t b, uint32_t c, uint32_t d) {
  asm volatile("{\n.reg .b128 v;\n.reg .b64 lo, hi;\nmov.b64 lo, {%1, %2};\nmov.b64 hi, {%3, %4};\nmov.b128 v, {lo, hi};\n"
               "st.relaxed.gpu.global.b128 [%0], v;\n}" ::"l"(p), "r"(a), "r"(b), "r"(c), "r"(d) : "memory");
}
__device__ __forceinline__ void ld128(const uint4* p, uint32_t* r) {
  asm volatile("{\n.reg .b128 v;\n.reg .b64 lo, hi;\nld.relaxed.gpu.global.b128 v, [%4];\nmov.b128 {lo, hi}, v;\n"
               "mov.b64 {%0, %1}, lo;\nmov.b64 {%2, %3}, hi;\n}" : "=r"(r[0]), "=r"(r[1]), "=r"(r[2]), "=r"(r[3]) : "l"(p) : "memory");
}

template <int OFF, uint32_t BHI, int ACC>
__device__ __forceinline__ void wgmma_rs32(float (&d)[16], uint32_t a0, uint32_t a1, uint32_t a2, uint32_t a3, uint32_t blo) {
  asm volatile("{\n.reg .pred p;\n.reg .b64 bd;\nsetp.ne.b32 p, %23, 0;\nmov.b64 bd, {%20, %22};\nadd.s64 bd, bd, %21;\n"
    "wgmma.mma_async.sync.aligned.m64n32k16.f32.bf16.bf16 {%0,%1,%2,%3,%4,%5,%6,%7,%8,%9,%10,%11,%12,%13,%14,%15}, {%16,%17,%18,%19}, bd, p, 1, 1, 0;\n}\n"
    : "+f"(d[0]),"+f"(d[1]),"+f"(d[2]),"+f"(d[3]),"+f"(d[4]),"+f"(d[5]),"+f"(d[6]),"+f"(d[7]),"+f"(d[8]),"+f"(d[9]),"+f"(d[10]),"+f"(d[11]),"+f"(d[12]),"+f"(d[13]),"+f"(d[14]),"+f"(d[15])
    : "r"(a0), "r"(a1), "r"(a2), "r"(a3), "r"(blo), "n"(OFF), "n"(BHI), "n"(ACC));
}
template <int OFF, uint32_t BHI, int ACC>
__device__ __forceinline__ void wgmma_rs24(float (&d)[12], uint32_t a0, uint32_t a1, uint32_t a2, uint32_t a3, uint32_t blo) {
  asm volatile("{\n.reg .pred p;\n.reg .b64 bd;\nsetp.ne.b32 p, %19, 0;\nmov.b64 bd, {%16, %18};\nadd.s64 bd, bd, %17;\n"
    "wgmma.mma_async.sync.aligned.m64n24k16.f32.bf16.bf16 {%0,%1,%2,%3,%4,%5,%6,%7,%8,%9,%10,%11}, {%12,%13,%14,%15}, bd, p, 1, 1, 1;\n}\n"
    : "+f"(d[0]),"+f"(d[1]),"+f"(d[2]),"+f"(d[3]),"+f"(d[4]),"+f"(d[5]),"+f"(d[6]),"+f"(d[7]),"+f"(d[8]),"+f"(d[9]),"+f"(d[10]),"+f"(d[11])
    : "r"(a0), "r"(a1), "r"(a2), "r"(a3), "r"(blo), "n"(OFF), "n"(BHI), "n"(ACC));
}
template <int OFF, uint32_t BHI, int ACC>
__device__ __forceinline__ void wgmma_rs16(float (&d)[8], uint32_t a0, uint32_t a1, uint32_t a2, uint32_t a3, uint32_t blo) {
  asm volatile("{\n.reg .pred p;\n.reg .b64 bd;\nsetp.ne.b32 p, %15, 0;\nmov.b64 bd, {%12, %14};\nadd.s64 bd, bd, %13;\n"
    "wgmma.mma_async.sync.aligned.m64n16k16.f32.bf16.bf16 {%0,%1,%2,%3,%4,%5,%6,%7}, {%8,%9,%10,%11}, bd, p, 1, 1, 1;\n}\n"
    : "+f"(d[0]),"+f"(d[1]),"+f"(d[2]),"+f"(d[3]),"+f"(d[4]),"+f"(d[5]),"+f"(d[6]),"+f"(d[7])
    : "r"(a0), "r"(a1), "r"(a2), "r"(a3), "r"(blo), "n"(OFF), "n"(BHI), "n"(ACC));
}

constexpr int A_R1 = 0;
constexpr int A_R2A = A_R1 + 2624, A_R2B = A_R2A + 768, A_R3A = A_R2B + 768, A_R3B = A_R3A + 528;
constexpr int A_K1024 = A_R3B + 528;
constexpr int A_W5 = A_K1024 + 16;
constexpr int A_W3 = A_W5 + 4096;
constexpr int A_W9 = A_W3 + 4112;
constexpr int A_W7 = A_W9 + 2080;
constexpr int A_V  = A_W7 + 2080 + 32;
constexpr int A_SCL = A_V + 2048;
constexpr int A_UB = A_SCL + 16;
constexpr int A_STG = A_UB + 5248;
constexpr int A_Y2 = A_STG, A_Y3 = A_Y2 + 6528, A_YB = A_Y3 + 4352;
constexpr int A_REC = A_STG + 4 * 4352;
constexpr int A_CH = A_REC + 8192;
static_assert(A_W5 % 16 == 0 && A_UB % 16 == 0 && A_CH % 16 == 0 && A_YB + 4096 <= A_REC, "layout");

struct cf { float x, y; };
__device__ __forceinline__ cf cmul(cf a, cf b) { cf r; r.x = fmaf(a.x, b.x, -a.y * b.y); r.y = fmaf(a.x, b.y, a.y * b.x); return r; }
__device__ __forceinline__ cf cexp_l(float lr, float li, float l) {
  float mag; asm("ex2.approx.ftz.f32 %0, %1;" : "=f"(mag) : "f"((lr * l) * 1.4426950408889634f));
  const float th = li * l;
  const float k = (fmaf(th, 0.15915494f, 12582912.f)) - 12582912.f;
  float ph = fmaf(th, 0.15915494f, -k);
  ph = fmaf(th, 6.4206383e-9f, ph) * 6.2831853f;
  cf r; r.x = mag * __cosf(ph); r.y = mag * __sinf(ph); return r;
}
__device__ __forceinline__ void sts16(uint32_t a, uint32_t v) { asm volatile("st.shared.u16 [%0], %1;" ::"r"(a), "h"((uint16_t)v) : "memory"); }
__device__ __forceinline__ void sts32(uint32_t a, uint32_t v) { asm volatile("st.shared.u32 [%0], %1;" ::"r"(a), "r"(v) : "memory"); }
__device__ __forceinline__ void sts64(uint32_t a, uint32_t v0, uint32_t v1) { asm volatile("st.shared.v2.u32 [%0], {%1, %2};" ::"r"(a), "r"(v0), "r"(v1) : "memory"); }
__device__ __forceinline__ void sts128(uint32_t a, uint32_t v0, uint32_t v1, uint32_t v2, uint32_t v3) {
  asm volatile("st.shared.v4.u32 [%0], {%1, %2, %3, %4};" ::"r"(a), "r"(v0), "r"(v1), "r"(v2), "r"(v3) : "memory");
}
__device__ __forceinline__ uint32_t lds32(uint32_t a) { uint32_t v; asm volatile("ld.shared.u32 %0, [%1];" : "=r"(v) : "r"(a) : "memory"); return v; }
__device__ __forceinline__ uint4 lds128(uint32_t a) {
  uint4 v; asm volatile("ld.shared.v4.u32 {%0, %1, %2, %3}, [%4];" : "=r"(v.x), "=r"(v.y), "=r"(v.z), "=r"(v.w) : "r"(a) : "memory"); return v;
}
__device__ __forceinline__ void ldsm4(uint32_t* r, uint32_t a) {
  asm volatile("ldmatrix.sync.aligned.m8n8.x4.shared.b16 {%0,%1,%2,%3}, [%4];" : "=r"(r[0]), "=r"(r[1]), "=r"(r[2]), "=r"(r[3]) : "r"(a) : "memory");
}
__device__ __forceinline__ void mma16816(float* d, uint32_t a0, uint32_t a1, uint32_t a2, uint32_t a3, uint32_t b0, uint32_t b1) {
  asm volatile("mma.sync.aligned.m16n8k16.row.col.f32.f16.f16.f32 {%0,%1,%2,%3}, {%4,%5,%6,%7}, {%8,%9}, {%0,%1,%2,%3};"
               : "+f"(d[0]), "+f"(d[1]), "+f"(d[2]), "+f"(d[3]) : "r"(a0), "r"(a1), "r"(a2), "r"(a3), "r"(b0), "r"(b1));
}
__device__ __forceinline__ uint32_t pack_h(float lo, float hi) { uint32_t r; asm("cvt.rn.f16x2.f32 %0, %1, %2;" : "=r"(r) : "f"(hi), "f"(lo)); return r; }
__device__ __forceinline__ uint32_t pack_h(cf v) { return pack_h(v.x, v.y); }
__device__ __forceinline__ uint32_t hcmul(uint32_t x, uint32_t r0, uint32_t r1) {
  const __half2 hx = *(__half2*)&x;
  const __half2 y = __hfma2(__high2half2(hx), *(__half2*)&r1, __hmul2(__low2half2(hx), *(__half2*)&r0));
  return *(const uint32_t*)&y;
}
__device__ __forceinline__ float ln_rstd(float var) {
  float sd, rs;
  asm("sqrt.approx.f32 %0, %1;" : "=f"(sd) : "f"(rbf(rbf(var) + 1e-5f)));
  asm("rcp.approx.f32 %0, %1;" : "=f"(rs) : "f"(rbf(sd)));
  return rs;
}
__device__ __forceinline__ uint32_t hsub2_bf(uint32_t a, uint32_t b) { uint32_t r; asm("sub.rn.bf16x2 %0, %1, %2;" : "=r"(r) : "r"(a), "r"(b)); return r; }
__device__ __forceinline__ void bar_sync(int id, int n) { asm volatile("bar.sync %0, %1;" ::"r"(id), "r"(n) : "memory"); }

template <int S> struct F1B { static constexpr int c = S / 4 + ((S & 3) == 3 ? 0 : 0), cc = (16 * S) / 64, ks = (64 * cc - (16 * S - 48)) / 16, off = (A_UB + 2 * ks * 656 + (9 - cc) * 16) / 16; };

template <int NS>
__device__ __forceinline__ void load_quads(uint32_t* q, uint32_t addr) {
#pragma unroll
  for (int i = 0; i < NS; i++) {
    q[4 * i] = lds32(addr + i * 64); q[4 * i + 1] = lds32(addr + i * 64 + 32);
    q[4 * i + 2] = i ? q[4 * i - 3] : lds32(addr - 32);
    q[4 * i + 3] = q[4 * i];
  }
#pragma unroll
  for (int i = 0; i < 4 * NS; i++) asm volatile("" : "+r"(q[i]));
}
template <int S0, int NS>
__device__ __forceinline__ void f1_steps(float (&acc)[16], const uint32_t* a, uint32_t blo) {
  if constexpr (NS > 0) {
    wgmma_rs32<F1B<S0>::off, 8, S0 != 0>(acc, a[0], a[1], a[2], a[3], blo);
    f1_steps<S0 + 1, NS - 1>(acc, a + 4, blo);
  }
}
template <int S0, int NS, int BASE, int FIRST>
__device__ __forceinline__ void s2_steps(float (&acc)[12], const uint32_t* a, uint32_t blo) {
  if constexpr (NS > 0) {
    wgmma_rs24<BASE / 16 + (112 - 16 * S0), 64, !(FIRST && S0 == 0)>(acc, a[0], a[1], a[2], a[3], blo);
    s2_steps<S0 + 1, NS - 1, BASE, FIRST>(acc, a + 4, blo);
  }
}
template <int S0, int NS, int BASE, int FIRST>
__device__ __forceinline__ void s3_steps(float (&acc)[8], const uint32_t* a, uint32_t blo) {
  if constexpr (NS > 0) {
    wgmma_rs16<BASE / 16 + (48 - 16 * S0), 65, !(FIRST && S0 == 0)>(acc, a[0], a[1], a[2], a[3], blo);
    s3_steps<S0 + 1, NS - 1, BASE, FIRST>(acc, a + 4, blo);
  }
}

__device__ __forceinline__ void phase_a(
        unsigned char* sm, const uint32_t bar_rec, const uint32_t ep_addr,
        const __nv_bfloat16* __restrict__ x, const uint32_t* __restrict__ are, const uint32_t* __restrict__ aim,
        const uint32_t* __restrict__ bre, const uint32_t* __restrict__ bim, const uint32_t* __restrict__ cre,
        const uint32_t* __restrict__ cim, const unsigned short* __restrict__ logdt, const unsigned short* __restrict__ dskip,
        const uint4* __restrict__ wgate, const uint4* __restrict__ wup, const uint4* __restrict__ wdown) {
  const uint32_t sb = s2u(sm);
  const int tid = threadIdx.x, warp = __shfl_sync(~0u, tid >> 5, 0), wg = warp >> 2, lane = tid & 31, wq = warp & 3, t128 = tid & 127;
  const int blk = blockIdx.x;
  const bool conv = blk < 112;

  uint2 xr[4];
  {
    const uint2* p = (const uint2*)(x + (size_t)(blk * 16 + warp) * DM);
    xr[0] = __ldg(p + lane); xr[1] = __ldg(p + 32 + lane); xr[2] = __ldg(p + 64 + lane);
    xr[3] = lane < 16 ? __ldg(p + 96 + lane) : make_uint2(0, 0);
  }
  const int ch = conv ? blk * 4 + wg : 0;
  const uint32_t cb = sb + wg * A_CH;
  uint32_t prm[6];
  {
    const int i = ch * 128 + t128;
    prm[0] = __ldg(are + i); prm[1] = __ldg(aim + i); prm[2] = __ldg(bre + i); prm[3] = __ldg(bim + i); prm[4] = __ldg(cre + i); prm[5] = __ldg(cim + i);
  }
  const uint32_t ldt = __ldg(logdt + ch);
  uint32_t cnt0 = 0;
  if (tid == 0) cnt0 = __ldcg(&g_cnt1);
  const int g = lane >> 2, t = lane & 3;
  const int wu2 = ch >> 1, wjq = wu2 / 14, wst = wu2 % 14;
  const uint32_t wstg = cb + A_W5 + wq * 2944;
  if (conv) {
    const uint4* s1 = ((ch & 1) ? wup : wgate) + (size_t)(wst * 32 + g) * 224 + wjq * 14 + wq * 4 + t;
    const uint4* s2 = wdown + (size_t)(wu2 * 8 + g) * 56 + ((ch & 1) * 4 + wq) * 7 + t;
    if (wq < 3 || t < 2) {
#pragma unroll
      for (int i = 0; i < 4; i++)
        asm volatile("cp.async.cg.shared.global [%0], [%1], 16;" ::"r"(wstg + t * 512 + i * 128 + g * 16), "l"(s1 + i * 8 * 224) : "memory");
    }
    asm volatile("cp.async.cg.shared.global [%0], [%1], 16;" ::"r"(wstg + 2048 + t * 128 + g * 16), "l"(s2) : "memory");
    if (t < 3) asm volatile("cp.async.cg.shared.global [%0], [%1], 16;" ::"r"(wstg + 2560 + t * 128 + g * 16), "l"(s2 + 4) : "memory");
  }
#pragma unroll
  for (int i = 0; i < 3; i++) if (i < 2 || t128 < A_W5 / 16 - 256) sts128(cb + (i * 128 + t128) * 16, 0, 0, 0, 0);
  {
    float s = 0.f, q = 0.f;
#pragma unroll
    for (int i = 0; i < 4; i++) {
      const float a = bf_lo(xr[i].x), b = bf_hi(xr[i].x), c = bf_lo(xr[i].y), d = bf_hi(xr[i].y);
      s += (a + b) + (c + d);
      q = fmaf(a, a, q); q = fmaf(b, b, q); q = fmaf(c, c, q); q = fmaf(d, d, q);
    }
#pragma unroll
    for (int o = 16; o; o >>= 1) { s += __shfl_xor_sync(~0u, s, o); q += __shfl_xor_sync(~0u, q, o); }
    const float mean = s * (1.f / DM);
    const float var = fmaxf(fmaf(-mean, mean, q * (1.f / DM)), 0.f);
    const float rs = ln_rstd(var);
    const uint32_t mm = pack_bf16(mean, mean);
    const uint32_t tu = sb + A_REC + (warp >> 3) * A_CH + (warp & 7) * 912 + lane * 8, tx = tu + 2 * A_CH;
#pragma unroll
    for (int i = 0; i < 4; i++) {
      if (i < 3 || lane < 16) {
        const uint32_t d0 = hsub2_bf(xr[i].x, mm), d1 = hsub2_bf(xr[i].y, mm);
        sts64(tu + i * 256, pack_bf16(bf_lo(d0) * rs, bf_hi(d0) * rs), pack_bf16(bf_lo(d1) * rs, bf_hi(d1) * rs));
        sts64(tx + i * 256, xr[i].x, xr[i].y);
      }
    }
  }
  if (tid == 0) sts32(ep_addr, (cnt0 >> 7) + 1u);
  if (tid == 320) TR(0, 1);
  auto publish_rows = [&]() {
    bar_sync(5, 512);
    uint4* dst = g_ux + ((size_t)(warp * 8 + (lane >> 2)) * 128 + blk) * 4 + ((lane ^ (blk >> 1)) & 3);
#pragma unroll
    for (int i = 0; i < 4; i++) {
      if (i < 3 || warp < 8) {
        uint32_t r[4];
        asm volatile("ldmatrix.sync.aligned.m8n8.x4.trans.shared.b16 {%0,%1,%2,%3}, [%4];" : "=r"(r[0]), "=r"(r[1]), "=r"(r[2]), "=r"(r[3])
                     : "r"(sb + A_REC + (lane >> 3) * A_CH + (lane & 7) * 912 + (warp + 16 * i) * 16) : "memory");
        dst[i * 65536] = make_uint4(r[0], r[1], r[2], r[3]);
      }
    }
    if (warp != 0) asm volatile("bar.arrive 6, 512;" ::: "memory");
  };
  auto release_rows = [&]() {
    if (warp == 0) {
      bar_sync(6, 512);
      if (lane == 0) { asm volatile("red.release.gpu.global.add.u32 [%0], 1;" ::"l"(&g_cnt1) : "memory"); TR(0, 8); }
      __syncwarp();
    }
  };

  if (!conv) {
    publish_rows();
    release_rows();
    const int a = blk - 112, mat = a >> 3, j = a & 7;
    float s[8];
#pragma unroll
    for (int k = 0; k < 8; k++) s[k] = 0.f;
    if (lane < 28) {
      const uint4* src = (mat ? wup : wgate) + j * 28 + lane + (size_t)warp * 224;
#pragma unroll
      for (int hb = 0; hb < 2; hb++) {
        uint4 v[14];
#pragma unroll
        for (int r = 0; r < 14; r++) v[r] = __ldg(src + (size_t)(hb * 14 + r) * 16 * 224);
#pragma unroll
        for (int r = 0; r < 14; r++) {
          s[0] += bf_lo(v[r].x); s[1] += bf_hi(v[r].x); s[2] += bf_lo(v[r].y); s[3] += bf_hi(v[r].y);
          s[4] += bf_lo(v[r].z); s[5] += bf_hi(v[r].z); s[6] += bf_lo(v[r].w); s[7] += bf_hi(v[r].w);
        }
      }
      float4* red = (float4*)(sm + A_STG + warp * 896 + lane * 32);
      red[0] = make_float4(s[0], s[1], s[2], s[3]); red[1] = make_float4(s[4], s[5], s[6], s[7]);
    }
    bar_sync(5, 512);
    if (tid < 224) {
      float t = 0.f;
#pragma unroll
      for (int w = 0; w < 16; w++) t += *(const float*)(sm + A_STG + w * 896 + tid * 4);
      const float hi = rbf(t), mid = rbf(t - hi), lo = rbf(t - hi - mid);
      const int q = tid / 112, n = tid % 112 + 112 * mat;
      __nv_bfloat16* dst = (__nv_bfloat16*)(g_cimg + (j * 2 + q) * 224 + (n >> 3) * 8) + (n & 7);
      dst[0] = __float2bfloat16_rn(hi); dst[8] = __float2bfloat16_rn(mid); dst[16] = __float2bfloat16_rn(lo);
#pragma unroll
      for (int k = 3; k < 8; k++) dst[8 * k] = __float2bfloat16_rn(0.f);
    }
    if (tid == 320) TR(0, 10);
    return;
  }

  const int wr = (wq + wg) & 3;
  const int bk = wr * 32 + lane;
  {
    const uint32_t stg = cb + A_STG + wq * 4352, sw = stg + lane * 8;
    const float dt = rbf(expf(__uint_as_float(ldt << 16)));
    float lr[2], li[2];
    cf bq[2], b0[2], b4[2];
    uint32_t bf[48];
#pragma unroll
    for (int m = 0; m < 2; m++) {
      lr[m] = dt * (m ? bf_hi(prm[0]) : bf_lo(prm[0]));
      li[m] = dt * (m ? bf_hi(prm[1]) : bf_lo(prm[1]));
    }
    {
      cf b[2], z[2];
#pragma unroll
      for (int m = 0; m < 2; m++) {
        cf db, c;
        db.x = dt * (m ? bf_hi(prm[2]) : bf_lo(prm[2])); db.y = -dt * (m ? bf_hi(prm[3]) : bf_lo(prm[3]));
        c.x = m ? bf_hi(prm[4]) : bf_lo(prm[4]); c.y = -(m ? bf_hi(prm[5]) : bf_lo(prm[5]));
        b[m] = cmul(c, db);
        z[m] = cexp_l(lr[m], -li[m], 1.f);
        bq[m] = cexp_l(lr[m], -li[m], 256.f);
      }
      publish_rows();
      {
        const float mx = fmaxf(fmaxf(fabsf(b[0].x), fabsf(b[0].y)), fmaxf(fabsf(b[1].x), fabsf(b[1].y)));
        const uint32_t e = max(__reduce_max_sync(~0u, __float_as_uint(mx)) >> 23, 14u);
        const float sc = __uint_as_float((267u - e) << 23);
        b[0].x *= sc; b[0].y *= sc; b[1].x *= sc; b[1].y *= sc;
        if (lane == 0) sts32(cb + A_SCL + wq * 4, (e - 13u) << 23);
      }
#pragma unroll
      for (int i = 0; i < 8; i++) {
        sts64(sw + i * 272, pack_h(b[0]), pack_h(b[1]));
        if (!(i & 1)) {
          cf e0 = cmul(b[0], bq[0]), e1 = cmul(b[1], bq[1]);
          sts64(sw + (8 + i / 2) * 272, pack_h(e0), pack_h(e1));
          if (i == 0) { b0[0] = e0; b0[1] = e1; }
          if (i == 4) { b4[0] = e0; b4[1] = e1; }
        }
        if (i < 7) { b[0] = cmul(b[0], z[0]); b[1] = cmul(b[1], z[1]); }
        if (i == 5) release_rows();
      }
#pragma unroll
      for (int i = 0; i < 7; i++) {
        b0[0] = cmul(b0[0], bq[0]); b0[1] = cmul(b0[1], bq[1]);
        sts64(sw + (i < 2 ? 12 + 2 * i : i - 2) * 272, pack_h(b0[0]), pack_h(b0[1]));
        if (i < 2) {
          b4[0] = cmul(b4[0], bq[0]); b4[1] = cmul(b4[1], bq[1]);
          sts64(sw + (13 + 2 * i) * 272, pack_h(b4[0]), pack_h(b4[1]));
        }
        if (i == 1) {
          __syncwarp();
#pragma unroll
          for (int n = 0; n < 2; n++)
#pragma unroll
            for (int k2 = 0; k2 < 4; k2++) ldsm4(bf + n * 16 + k2 * 4, stg + (n * 8 + (lane & 7)) * 272 + k2 * 64 + (lane >> 3) * 16);
          __syncwarp();
        }
      }
    }
    uint32_t cv = 0;
    if (tid == 160) asm volatile("ld.relaxed.gpu.global.u32 %0, [%1];" : "=r"(cv) : "l"(&g_cnt1) : "memory");
    {
      const cf p0 = cexp_l(lr[0], li[0], 8.f), p1 = cexp_l(lr[1], li[1], 8.f);
      cf v0 = p0, v1 = p1;
      sts64(sw + 8 * 272, 0x3C00u, 0x3C00u);
#pragma unroll
      for (int i = 1; i < 8; i++) {
        sts64(sw + (8 + i) * 272, pack_h(v0), pack_h(v1));
        v0 = cmul(v0, p0); v1 = cmul(v1, p1);
      }
      const uint32_t ra = stg + 5 * 272 + (lane >> 2) * 64 + (lane & 1) * 32 + (lane & 2) * 4;
      sts64(ra, pack_h(v0), pack_h(-v0.y, v0.x));
      sts64(ra + 16, pack_h(v1), pack_h(-v1.y, v1.x));
    }
    asm volatile("cp.async.wait_all;" ::: "memory");
    asm volatile("fence.proxy.async.shared::cta;" ::: "memory");
    __syncwarp();
    if (lane == 0) {
      uint4* img = g_wimg + (size_t)(wjq >> 1) * 37632;
      asm volatile("cp.async.bulk.global.shared::cta.bulk_group [%0], [%1], %2;"
                   ::"l"(img + ((wjq & 1) * 14 + wst) * 896 + ((ch & 1) * 14 + wq * 4) * 32), "r"(wstg), "r"(wq < 3 ? 2048 : 1024) : "memory");
      asm volatile("cp.async.bulk.global.shared::cta.bulk_group [%0], [%1], 896;"
                   ::"l"(img + 25088 + (((ch & 1) * 4 + wq) * 2 + (wjq & 1)) * 784 + wst * 56), "r"(wstg + 2048) : "memory");
      asm volatile("cp.async.bulk.commit_group;" ::: "memory");
    }
    if (tid == 320) TR(0, 16);
#pragma unroll
    for (int k2 = 0; k2 < 4; k2++) ldsm4(bf + 32 + k2 * 4, stg + (lane & 7) * 272 + k2 * 64 + (lane >> 3) * 16);
    float c[6][4];
#pragma unroll
    for (int i = 0; i < 6; i++) { c[i][0] = 0.f; c[i][1] = 0.f; c[i][2] = 0.f; c[i][3] = 0.f; }
#pragma unroll
    for (int k2 = 0; k2 < 4; k2++) {
      uint32_t a[4];
      ldsm4(a, stg + (8 + (lane & 7)) * 272 + k2 * 64 + (lane >> 3) * 16);
#pragma unroll
      for (int kk = 0; kk < 2; kk++) {
        const int ks = 2 * k2 + kk;
        const uint4 r4 = lds128(stg + 5 * 272 + ks * 64 + t * 16);
        const uint32_t r[4] = {r4.x, r4.z, r4.y, r4.w};
        const uint32_t x0 = a[2 * kk], y0 = a[2 * kk + 1];
        const uint32_t x1 = hcmul(x0, r[0], r[2]), y1 = hcmul(y0, r[1], r[3]);
        const uint32_t x2 = hcmul(x1, r[0], r[2]), y2 = hcmul(y1, r[1], r[3]);
        const uint32_t x3 = hcmul(x2, r[0], r[2]), y3 = hcmul(y2, r[1], r[3]);
#pragma unroll
        for (int n = 0; n < 3; n++) {
          mma16816(c[n * 2], x0, x1, y0, y1, bf[n * 16 + ks * 2], bf[n * 16 + ks * 2 + 1]);
          mma16816(c[n * 2 + 1], x2, x3, y2, y3, bf[n * 16 + ks * 2], bf[n * 16 + ks * 2 + 1]);
        }
      }
      if (k2 == 0 && warp == 5) {
        if (lane == 0) {
          const uint32_t tgt = lds32(ep_addr) * 128u;
          int it = 0;
          while ((int)(cv - tgt) < 0 && ++it < 400000) asm volatile("ld.relaxed.gpu.global.u32 %0, [%1];" : "=r"(cv) : "l"(&g_cnt1) : "memory");
          asm volatile("fence.acquire.gpu;" ::: "memory");
          asm volatile("fence.proxy.async.global;" ::: "memory");
          TR(0, 9);
        }
        __syncwarp();
#pragma unroll
        for (int c2 = 0; c2 < 4; c2++) bulk_ld_elect<8192>(sb + c2 * A_CH + A_REC, g_ux + (size_t)(blk * 4 + c2) * 512, bar_rec);
      }
    }
    __syncwarp();
#pragma unroll
    for (int i = 0; i < 6; i++)
      sts128(stg + i * 512 + lane * 16, __float_as_uint(c[i][0]), __float_as_uint(c[i][1]), __float_as_uint(c[i][2]), __float_as_uint(c[i][3]));
    if (lane == 0) {
      asm volatile("cp.async.bulk.wait_group.read 0;" ::: "memory");
      mbar_arrive(bar_rec);
    }
  }
  if (tid == 320) TR(0, 2);

  uint32_t xt[8], ud[8];
  {
    mbar_wait(bar_rec, 0);
    if (tid == 320) TR(0, 4);
    uint4 r[4];
#pragma unroll
    for (int i = 0; i < 4; i++) r[i] = lds128(cb + A_REC + bk * 64 + ((i ^ (bk >> 1)) & 3) * 16);
    const uint32_t ua = cb + A_UB + ((2 * bk) & 7) * 656 + ((bk >> 2) + 9) * 16;
    sts128(ua, r[0].x, r[1].x, r[2].x, r[3].x);
    sts128(ua + 656, r[0].y, r[1].y, r[2].y, r[3].y);
    if (wr == 3) {
      if (lane < 31) {
        sts128(cb + A_W5 + lane * 32, 0, 0, 0, 0); sts128(cb + A_W5 + lane * 32 + 16, 0, 0, 0, 0);
        sts128(cb + A_W3 + lane * 32, 0, 0, 0, 0); sts128(cb + A_W3 + lane * 32 + 16, 0, 0, 0, 0);
      } else sts64(cb + A_W3 + 992, 0, 0);
      if (lane < 24) {
#pragma unroll
        for (int i = 0; i < 3; i++) sts128(cb + A_UB + (lane / 3) * 656 + ((lane % 3) * 3 + i) * 16, 0, 0, 0, 0);
      }
    }
    if (bk <= 96) {
      const bool neg = bk == 96;
      const int bp = neg ? -1 : bk;
      uint32_t h[4];
      h[0] = lds32(cb + A_REC + ((bp - 1) & 127) * 64 + ((2 ^ ((bp - 1) >> 1)) & 3) * 16 + 4);
      h[1] = lds32(cb + A_REC + ((bp - 1) & 127) * 64 + ((3 ^ ((bp - 1) >> 1)) & 3) * 16 + 4);
      h[2] = lds32(cb + A_REC + (bp + 1) * 64 + ((0 ^ ((bp + 1) >> 1)) & 3) * 16);
      h[3] = lds32(cb + A_REC + (bp + 1) * 64 + ((1 ^ ((bp + 1) >> 1)) & 3) * 16);
      if (bp <= 0) { h[0] = 0; h[1] = 0; }
      const uint32_t wd[12] = {h[0], h[1], neg ? 0 : r[0].x, neg ? 0 : r[1].x, neg ? 0 : r[2].x, neg ? 0 : r[3].x,
                               neg ? 0 : r[0].y, neg ? 0 : r[1].y, neg ? 0 : r[2].y, neg ? 0 : r[3].y, h[2], h[3]};
      float P[25];
      P[0] = 0.f;
#pragma unroll
      for (int i = 0; i < 12; i++) { P[2 * i + 1] = P[2 * i] + bf_lo(wd[i]); P[2 * i + 2] = P[2 * i + 1] + bf_hi(wd[i]); }
#define WIN(i, hw) (P[(i) + 5 + (hw)] - P[(i) + 4 - (hw)])
#define WPK(i, hw) pack_bf16(WIN(i, hw), WIN((i) + 1, hw))
      const int tp = 2 * bp;
      const uint32_t a3 = cb + A_W3 + (tp + 64) * 16 + 8, a5 = cb + A_W5 + (tp + 64) * 16;
      sts64(a3, WPK(0, 1), WPK(2, 1));
      sts128(a3 + 8, WPK(4, 1), WPK(6, 1), WPK(8, 1), WPK(10, 1));
      sts64(a3 + 24, WPK(12, 1), WPK(14, 1));
      sts128(a5, WPK(0, 2), WPK(2, 2), WPK(4, 2), WPK(6, 2));
      sts128(a5 + 16, WPK(8, 2), WPK(10, 2), WPK(12, 2), WPK(14, 2));
      if (bp < 64) {
        sts128(cb + A_W7 + 1040 + bp * 16, WPK(0, 3), WPK(2, 3), WPK(4, 3), WPK(6, 3));
        sts128(cb + A_W7 + (bp + 1) * 16, WPK(8, 3), WPK(10, 3), WPK(12, 3), WPK(14, 3));
        sts128(cb + A_W9 + (bp + 1) * 16, WPK(0, 4), WPK(2, 4), WPK(4, 4), WPK(6, 4));
        sts128(cb + A_W9 + 1040 + (bp + 1) * 16, WPK(8, 4), WPK(10, 4), WPK(12, 4), WPK(14, 4));
#define VPK(i) pack_bf16(P[(i) + 2] - P[i], P[(i) + 3] - P[(i) + 1])
        sts128(cb + A_V + bp * 32, VPK(0), VPK(2), VPK(4), VPK(6));
        sts128(cb + A_V + bp * 32 + 16, VPK(8), VPK(10), VPK(12), VPK(14));
      }
    }
  }
  asm volatile("fence.proxy.async.shared::cta;" ::: "memory");
  bar_sync(1 + wg, 128);
  if (tid == 320) TR(0, 3);
  {
    const uint4 sc = lds128(cb + A_SCL);
    const float scl[4] = {__uint_as_float(sc.x), __uint_as_float(sc.y), __uint_as_float(sc.z), __uint_as_float(sc.w)};
#pragma unroll
    for (int rep = 0; rep < 2; rep++) {
      const int qd = rep ? 2 + wr : 3 - wr;
      if (rep == 0 || wr >= 2) {
        float s[4] = {0.f, 0.f, 0.f, 0.f};
#pragma unroll
        for (int w = 0; w < 4; w++) {
          uint4 u4 = lds128(cb + A_STG + w * 4352 + qd * 512 + lane * 16);
          s[0] = fmaf(__uint_as_float(u4.x), scl[w], s[0]); s[1] = fmaf(__uint_as_float(u4.y), scl[w], s[1]);
          s[2] = fmaf(__uint_as_float(u4.z), scl[w], s[2]); s[3] = fmaf(__uint_as_float(u4.w), scl[w], s[3]);
        }
#pragma unroll
        for (int hf = 0; hf < 2; hf++) {
          const int j = (qd & 1) * 16 + g + 8 * hf;
          const uint32_t pk = pack_bf16(s[2 * hf + 1], s[2 * hf]);
          const uint32_t v0 = pk >> 16, v1 = pk & 0xFFFFu, v00 = v0 * 0x10001u;
          if (rep == 1) {
            if (t < 2) {
#pragma unroll
              for (int e = 0; e < 2; e++) {
                const int lam = 128 + 32 * (2 * t + e) + j, mu = lam >> 1;
                const uint32_t val = e ? v1 : v0;
                uint32_t a = cb + ((lam & 1) ? A_R3B : A_R3A) + mu * 4;
                if (lam == 128) { a = cb + A_R2A + 128 * 4; sts32(cb + A_K1024, val << 16); }
                sts16(a, val); sts16(a + 6, val);
              }
            } else if (t == 2 && j == 0) { sts16(cb + A_R3A + 128 * 4, v0); }
          } else if (qd < 2) {
            const uint32_t a = cb + A_R1 + (62 + 8 * j + 2 * t) * 4;
            sts16(a, v0); sts32(a + 4, pk); sts16(a + 10, v1);
          } else if (t < 2) {
            const int L = 256 + 8 * j + 4 * t;
            const uint32_t a = cb + A_R1 + (62 + L) * 4;
            if (L > 256) { sts16(a - 4, v0); sts32(a, v00); } else sts16(a, v0);
            sts32(a + 4, v00); sts32(a + 8, pk); sts16(a + 14, v1);
          } else {
            const int mu = 64 + 32 * (t - 2) + j;
            if (mu == 64) {
              const uint32_t a = cb + A_R1 + (62 + 512) * 4;
              sts16(a - 4, v0); sts32(a, v00); sts32(a + 4, v00); sts32(a + 8, v00); sts16(a + 14, v0);
            } else { sts16(cb + A_R2A + mu * 4, v0); sts16(cb + A_R2A + mu * 4 + 6, v0); }
            sts16(cb + A_R2B + mu * 4, v1); sts16(cb + A_R2B + mu * 4 + 6, v1);
          }
        }
      }
    }
  }
  bar_sync(1 + wg, 128);
  if (tid == 320) TR(0, 5);

  {
    const uint32_t cbu = cb;
    const uint32_t blo_k = ((cbu & 0x3FFFF) >> 4) | (41u << 16);
    const uint32_t blo_n = ((cbu & 0x3FFFF) >> 4) | (8u << 16);
    const uint32_t tb = cb + (16 * wq + g - 2 * t) * 4;
    float y1[16], y2[12], y3[8];
    const uint32_t dk16 = __ldg(dskip + ch);
    uint32_t qa[32], qb[32];
    const uint32_t t1 = tb + A_R1 + (62 - 48) * 4;
    load_quads<4>(qa, tb + A_R3A + 17 * 4); load_quads<4>(qa + 16, tb + A_R3B + 16 * 4);
    wg_fence();
    s3_steps<0, 4, A_W9, 1>(y3, qa, blo_n); s3_steps<0, 4, A_W7, 0>(y3, qa + 16, blo_n);
    wg_commit();
    load_quads<8>(qb, tb + A_R2A + 16 * 4);
    wg_fence(); s2_steps<0, 8, A_W5, 1>(y2, qb, blo_n); wg_commit();
    wg_wait<1>(); load_quads<8>(qa, tb + A_R2B + 16 * 4);
    wg_fence(); s2_steps<0, 8, A_W3, 0>(y2, qa, blo_n); wg_commit();
    wg_wait<1>(); load_quads<8>(qb, t1);
    wg_fence(); f1_steps<0, 8>(y1, qb, blo_k); wg_commit();
    wg_wait<1>(); load_quads<8>(qa, t1 + 8 * 64);
    wg_fence(); f1_steps<8, 8>(y1, qa, blo_k); wg_commit();
    reg_fence(y2); reg_fence(y3);
    if (tid == 320) TR(0, 18);
    {
      const float k1024 = __uint_as_float(lds32(cb + A_K1024));
#pragma unroll
      for (int i = 0; i < 2; i++)
#pragma unroll
        for (int hf = 0; hf < 2; hf++) {
          const int idx = 16 * (16 * wq + g + 8 * hf) + 8 * i + 2 * t;
          const uint32_t vv = lds32(cb + A_V + idx * 2);
          sts64(cb + A_Y3 + (idx + 4 * (idx >> 6)) * 4, __float_as_uint(fmaf(k1024, bf_lo(vv), y3[4 * i + 2 * hf])),
                __float_as_uint(fmaf(k1024, bf_hi(vv), y3[4 * i + 2 * hf + 1])));
        }
#pragma unroll
      for (int i = 0; i < 3; i++)
#pragma unroll
        for (int hf = 0; hf < 2; hf++) {
          const int idx = 512 * i + 8 * (16 * wq + g + 8 * hf) + 2 * t;
          sts64(cb + A_Y2 + (idx + 4 * (idx >> 6)) * 4, __float_as_uint(y2[4 * i + 2 * hf]), __float_as_uint(y2[4 * i + 2 * hf + 1]));
        }
    }
    wg_wait<1>(); load_quads<8>(qb, t1 + 16 * 64);
    wg_fence(); f1_steps<16, 8>(y1, qb, blo_k); wg_commit();
    wg_wait<1>(); load_quads<8>(qa, t1 + 24 * 64);
    wg_fence(); f1_steps<24, 8>(y1, qa, blo_k); wg_commit();
    wg_wait<1>(); load_quads<5>(qb, t1 + 32 * 64);
    wg_fence(); f1_steps<32, 5>(y1, qb, blo_k); wg_commit();
    bar_sync(1 + wg, 128);
    float ex[12];
#pragma unroll
    for (int i = 1; i < 4; i++)
#pragma unroll
      for (int k = 0; k < 4; k++) {
        const int aa = 8 * i + 2 * t + (k & 1), b = 16 * wq + g + 8 * (k >> 1);
        float e = __uint_as_float(lds32(cb + A_Y2 + ((aa - 8) * 68 + b) * 4));
        if (i >= 2) e += __uint_as_float(lds32(cb + A_Y3 + ((aa - 16) * 68 + b) * 4));
        ex[4 * (i - 1) + k] = e;
      }
    {
      const uint32_t dk = dk16 * 0x10001u;
#pragma unroll
      for (int i = 0; i < 4; i++) {
        const uint4 r = lds128(cb + A_REC + bk * 64 + ((i ^ (bk >> 1)) & 3) * 16);
        ud[i] = hmul2_bf(r.x, dk); ud[4 + i] = hmul2_bf(r.y, dk); xt[i] = r.z; xt[4 + i] = r.w;
      }
    }
    wg_wait<0>();
    reg_fence(y1);
    if (tid == 320) TR(0, 6);
#pragma unroll
    for (int i = 0; i < 12; i++) y1[4 + i] += ex[i];
#pragma unroll
    for (int i = 0; i < 2; i++) {
      const int mi = lane >> 3, aa = 8 * (2 * i + (mi >> 1)) + (lane & 7);
      asm volatile("stmatrix.sync.aligned.m8n8.x4.trans.shared.b16 [%0], {%1,%2,%3,%4};"
                   ::"r"(cb + A_YB + aa * 128 + (((2 * wq + (mi & 1)) ^ (lane & 7)) << 4)),
                     "r"(pack_bf16(y1[8 * i], y1[8 * i + 1])), "r"(pack_bf16(y1[8 * i + 2], y1[8 * i + 3])),
                     "r"(pack_bf16(y1[8 * i + 4], y1[8 * i + 5])), "r"(pack_bf16(y1[8 * i + 6], y1[8 * i + 7])) : "memory");
    }
  }
  bar_sync(1 + wg, 128);
#pragma unroll
  for (int c = 0; c < 2; c++) {
    const int tau = 2 * bk + c, r = ch & 7;
    const uint4 y = lds128(cb + A_YB + (tau >> 3) * 128 + (((tau ^ (tau >> 3)) & 7) << 4));
    g_himg[(size_t)(tau >> 4) * 7168 + (ch >> 3) * 128 + ((tau >> 3) & 1) * 64 + r * 8 + ((tau & 7) ^ r)] =
        make_uint4(hadd2_bf(xt[4 * c], hadd2_bf(y.x, ud[4 * c])), hadd2_bf(xt[4 * c + 1], hadd2_bf(y.y, ud[4 * c + 1])),
                   hadd2_bf(xt[4 * c + 2], hadd2_bf(y.z, ud[4 * c + 2])), hadd2_bf(xt[4 * c + 3], hadd2_bf(y.w, ud[4 * c + 3])));
  }
  if (lane == 0) asm volatile("cp.async.bulk.wait_group 0;" ::: "memory");
  if (tid == 320) TR(0, 7);
}

constexpr int B_SA = 0, B_RING = 114688, B_SLOT = 14848, B_NSLOT = 7;
constexpr int B_CS = B_RING + B_NSLOT * B_SLOT;
constexpr int B_RED = B_CS + 7168;
constexpr int B_BAR = B_RED + 256;
constexpr int B_SMEM = B_BAR + 1024, A_SMEM = 4 * A_CH + 64;

__device__ __forceinline__ uint32_t mapa(uint32_t a, uint32_t r) { uint32_t o; asm("mapa.shared::cluster.u32 %0, %1, %2;" : "=r"(o) : "r"(a), "r"(r)); return o; }
template <class T> __device__ __forceinline__ T* pin(T* p) { asm volatile("" : "+l"(p)); return p; }
__device__ __forceinline__ uint32_t pin(uint32_t v) { asm volatile("" : "+r"(v)); return v; }
template <int Q, int ST>
__device__ __forceinline__ void g1_stage(float (&acc)[116], uint32_t alo, uint32_t blo, uint32_t bar_full, uint32_t bar_h) {
  constexpr int s = Q * 14 + ST, sl = s % B_NSLOT;
  if (Q == 0) mbar_wait(bar_h + 8 * ST, 0);
  mbar_wait(bar_full + 8 * sl, (s / B_NSLOT) & 1);
  wg_fence();
  if (Q == 0) {
    wgmma_ss232<(2 * ST) * 256, 0x40000080u, (sl * B_SLOT) / 16, 32, ST != 0>(acc, alo, blo);
    wgmma_ss232<(2 * ST + 1) * 256, 0x40000080u, (sl * B_SLOT + 256) / 16, 32, 1>(acc, alo, blo);
  } else {
    wgmma_ss224<(2 * ST) * 256, 0x40000080u, (sl * B_SLOT) / 16, 32, ST != 0>(*(float(*)[112])acc, alo, blo);
    wgmma_ss224<(2 * ST + 1) * 256, 0x40000080u, (sl * B_SLOT + 256) / 16, 32, 1>(*(float(*)[112])acc, alo, blo);
  }
}

__global__ void __launch_bounds__(512, 1)
k_front(const __nv_bfloat16* __restrict__ x, const uint32_t* __restrict__ are, const uint32_t* __restrict__ aim,
        const uint32_t* __restrict__ bre, const uint32_t* __restrict__ bim, const uint32_t* __restrict__ cre,
        const uint32_t* __restrict__ cim, const unsigned short* __restrict__ logdt, const unsigned short* __restrict__ dskip,
        const uint4* __restrict__ wgate, const uint4* __restrict__ wup, const uint4* __restrict__ wdown) {
  extern __shared__ __align__(1024) unsigned char sm[];
  const uint32_t bar_rec = s2u(sm) + 4 * A_CH;
  if (threadIdx.x == 320) TR(0, 0);
  asm volatile("griddepcontrol.launch_dependents;");
  if (threadIdx.x == 160) { mbar_init(bar_rec, 20); asm volatile("fence.mbarrier_init.release.cluster;" ::: "memory"); }
  phase_a(sm, bar_rec, bar_rec + 8, x, are, aim, bre, bim, cre, cim, logdt, dskip, wgate, wup, wdown);
}

__global__ void __cluster_dims__(2, 1, 1) __launch_bounds__(384, 1) k_ffn(__nv_bfloat16* __restrict__ out) {
  extern __shared__ __align__(1024) unsigned char sm[];
  const uint32_t sb = s2u(sm);
  const int tid = threadIdx.x, warp = __shfl_sync(~0u, tid >> 5, 0), wg = warp >> 2, lane = tid & 31;
  const uint32_t bar_full = sb + B_BAR, bar_empty = bar_full + 64, bar_h = bar_full + 128, bar_cs = bar_full + 240,
                 bar_hh = bar_full + 304, bar_afree = bar_full + 336, bar_out = bar_full + 352;
  if (tid == 0) {
    TR(1, 0);
    for (int i = 0; i < B_NSLOT; i++) { mbar_init(bar_full + 8 * i, 1); mbar_init(bar_empty + 8 * i, 2); }
    asm volatile("fence.mbarrier_init.release.cluster;" ::: "memory");
  } else if (tid == 32) {
    for (int i = 0; i < 14; i++) mbar_init(bar_h + 8 * i, 1);
    asm volatile("fence.mbarrier_init.release.cluster;" ::: "memory");
  } else if (tid == 64) {
    mbar_init(bar_cs, 1);
    for (int i = 0; i < 4; i++) { mbar_init(bar_hh + 8 * i, 1); mbar_expect(bar_hh + 8 * i, 14336); }
    mbar_init(bar_afree, 4); mbar_init(bar_afree + 8, 2);
    for (int i = 0; i < 6; i++) mbar_init(bar_out + 8 * i, 128);
    asm volatile("fence.mbarrier_init.release.cluster;" ::: "memory");
  } else if (tid >= 128 && tid < 352) {
    sts128(sb + B_RING + ((tid - 128) >> 5) * B_SLOT + 14336 + (tid & 31) * 16, 0x3F803F80u, 0x3F803F80u, 0x3F803F80u, 0x3F803F80u);
  }
  asm volatile("fence.proxy.async.shared::cta;" ::: "memory");
  __syncthreads();
  asm volatile("barrier.cluster.arrive.relaxed.aligned;" ::: "memory");
  const int rank = blockIdx.x & 1, rt = blockIdx.x >> 3, j = blockIdx.x & 7, p = j >> 1, cg = 4 * rank + p;
  const int wq = warp & 3, t128 = tid & 127, g = lane >> 2, t = lane & 3;
  uint32_t ep, tag;
  auto load_ep = [&]() { asm volatile("ld.relaxed.gpu.global.u32 %0, [%1];" : "=r"(ep) : "l"(&g_cnt1) : "memory"); };
  auto a_slot = [&](int i, int own) { return B_SA + (i + (i >= own)) * 14336; };
  auto out_addr = [&](int cc, int w) { return sb + a_slot((cc & 2) + w, cg) + (cc & 1) * 7168; };
  auto in_cta = [&](int q) { return rt * 8 + ((p + 3 - q) & 3) * 2 + rank; };
  auto in_src = [&](int q, int cw) { return g_part + (size_t)(in_cta(q) * 3 + q) * 896 + cw * 112; };
  auto in_bad = [&](uint32_t (&in)[14]) { return ((in[3] ^ tag) | (in[7] ^ tag) | (in[11] ^ tag) | (in[13] ^ tag)) & 0x10000u; };
  auto in_load = [&](uint32_t (&in)[14], const uint4* gs) {
#pragma unroll
    for (int i = 0; i < 3; i++) ld128(gs + i * 32, in + 4 * i);
    asm volatile("{\n.reg .b64 v;\nld.relaxed.gpu.global.b64 v, [%2];\nmov.b64 {%0, %1}, v;\n}"
                 : "=r"(in[12]), "=r"(in[13]) : "l"((const uint2*)(gs + 96) - lane) : "memory");
  };
  auto in_check = [&](uint32_t (&in)[14], int q, int cw) {
    int it = 0;
    while (in_bad(in) && ++it < 400000) in_load(in, pin(in_src(q, cw) + lane));
  };

  if (wg == 2) {
    asm volatile("setmaxnreg.dec.sync.aligned.u32 40;");
    asm volatile("barrier.cluster.wait.aligned;" ::: "memory");
    asm volatile("griddepcontrol.wait;" ::: "memory");
    if (warp == 8) {
      if (lane == 0) TR(1, 1);
      const char* wsrc = (const char*)g_wimg + (size_t)j * 602112;
      const char* hsrc = (const char*)g_himg + (size_t)rt * 114688 + rank * 4096;
#pragma unroll
      for (int s = 0; s < 28; s++) {
        if (s < B_NSLOT) bulk_ld_mc_elect<4096>(sb + B_SA + s * 8192 + rank * 4096, hsrc + s * 8192, bar_h + 8 * s);
        if (s == B_NSLOT) {
#pragma unroll
          for (int i = 7; i < 14; i++) bulk_ld_mc_elect<4096>(sb + B_SA + i * 8192 + rank * 4096, hsrc + i * 8192, bar_h + 8 * i);
          bulk_ld_elect<7168>(sb + B_CS, g_cimg + j * 448, bar_cs);
        }
        if (s >= B_NSLOT) mbar_wait(bar_empty + 8 * (s % B_NSLOT), (s / B_NSLOT + 1) & 1);
        bulk_ld_elect<14336>(sb + B_RING + (s % B_NSLOT) * B_SLOT, wsrc + s * 14336, bar_full + 8 * (s % B_NSLOT));
      }
      const char* dsrc[2] = {wsrc + 401408 + rank * 100352, (const char*)g_wimg + (size_t)(j ^ 1) * 602112 + 401408 + rank * 100352};
#pragma unroll
      for (int i = 0; i < 16; i++) {
        const int ci = i < 3 ? 0 : i < 6 ? 1 : i < 8 ? i - 6 : i < 12 ? 2 : 3;
        const int kp = i < 3 ? i : i < 6 ? i - 3 : i < 8 ? 3 : (i & 3);
        mbar_wait(bar_empty + 8 * (i % B_NSLOT), (i / B_NSLOT + 1) & 1);
        bulk_ld_elect<12544>(sb + B_RING + (i % B_NSLOT) * B_SLOT, dsrc[kp >> 1] + ((p + 1 + ci) & 3) * 25088 + (kp & 1) * 12544, bar_full + 8 * (i % B_NSLOT));
      }
    } else if (warp >= 10) {
      const int t64 = tid - 320;
      load_ep();
      const int r = (lane >> 1) & 7, c = (j & 3) * 2 + (lane & 1);
      const uint32_t src = sb + B_SA + (t64 >> 4) * 2048 + (j >> 2) * 1024 + r * 128 + ((c ^ r) << 4);
      float a[16];
#pragma unroll
      for (int k = 0; k < 16; k++) a[k] = 0.f;
#pragma unroll 1
      for (int i = 0; i < 14; i++) {
        mbar_wait(bar_h + 8 * i, 0);
        uint4 v = lds128(src + i * 8192);
        float e[8] = {bf_lo(v.x), bf_hi(v.x), bf_lo(v.y), bf_hi(v.y), bf_lo(v.z), bf_hi(v.z), bf_lo(v.w), bf_hi(v.w)};
#pragma unroll
        for (int k = 0; k < 8; k++) { a[2 * k] += e[k]; a[2 * k + 1] = fmaf(e[k], e[k], a[2 * k + 1]); }
        __nanosleep(160);
      }
      __syncwarp();
      if (lane == 0) { asm volatile("mbarrier.arrive.shared::cluster.b64 _, [%0];" ::"r"(mapa(bar_afree, rank ^ 1)) : "memory"); }
#pragma unroll
      for (int rd = 0; rd < 4; rd++) {
        const int n = 8 >> rd;
        const bool up = lane & (2 * n);
#pragma unroll
        for (int k = 0; k < 8; k++) {
          if (k < n) {
            float keep = up ? a[k + n] : a[k], give = up ? a[k] : a[k + n];
            a[k] = keep + __shfl_xor_sync(~0u, give, 2 * n);
          }
        }
      }
      float* red = (float*)(sm + B_RED);
      red[(warp & 1) * 32 + (lane & 1) * 16 + (lane >> 1)] = a[0];
      bar_sync(1, 64);
      if (t64 < 16) {
        float mean = (red[2 * t64] + red[32 + 2 * t64]) * (1.f / DM);
        float var = fmaxf(fmaf(-mean, mean, (red[2 * t64 + 1] + red[33 + 2 * t64]) * (1.f / DM)), 0.f);
        float rs = ln_rstd(var);
        asm volatile("st.relaxed.gpu.global.u32 [%0], %1;"
                     ::"l"(g_stat2 + rt * 128 + j * 16 + t64), "r"((__float_as_uint(rs * rs) & ~1u) | ((ep >> 7) & 1u)) : "memory");
      }
      if (t64 == 0) TR(1, 2);
      if (lane == 0) {
        const int w = warp & 1;
        for (int cc = 0; cc < 2; cc++) {
          mbar_wait(bar_out + 8 * (cc * 2 + w), 0);
          asm volatile("cp.async.bulk.global.shared::cta.bulk_group [%0], [%1], 7168;"
                       ::"l"(g_part + (size_t)(blockIdx.x * 3 + cc) * 896 + w * 448), "r"(out_addr(cc, w)) : "memory");
          if (w) TR(1, 27 + cc);
        }
        asm volatile("cp.async.bulk.commit_group;" ::: "memory");
        asm volatile("cp.async.bulk.wait_group 0;" ::: "memory");
      }
    }
  } else {
    asm volatile("setmaxnreg.inc.sync.aligned.u32 232;");
    asm volatile("barrier.cluster.wait.aligned;" ::: "memory");
    uint32_t hh[56];
    const bool relt = t128 == 0;
    auto release = [&](int sl) { if (relt) mbar_arrive(bar_empty + 8 * sl); };
    auto send_hh = [&](int q) {
      const uint32_t da = mapa(sb + a_slot(2 * q + wg, cg ^ 4) + t128 * 16, rank ^ 1), db = mapa(bar_hh + 8 * (2 * q + wg), rank ^ 1);
#pragma unroll
      for (int i = 0; i < 7; i++)
        asm volatile("st.async.weak.shared::cluster.mbarrier::complete_tx::bytes.v4.b32 [%0], {%1, %2, %3, %4}, [%5];"
                     ::"r"(da + i * 2048), "r"(hh[28 * q + 4 * i]), "r"(hh[28 * q + 4 * i + 1]),
                       "r"(hh[28 * q + 4 * i + 2]), "r"(hh[28 * q + 4 * i + 3]), "r"(db) : "memory");
    };
    uint32_t alo = ((sb + B_SA + wg * 1024) & 0x3FFFF) >> 4;
    uint32_t blo = (((sb + B_RING) & 0x3FFFF) >> 4) | (8u << 16);
    const uint32_t clo = ((sb + B_CS) & 0x3FFFF) >> 4;
    uint32_t nm0, nm1;
    if (wg == 1) bar_sync(3, 256);
#define G1S(Q, ST) do { if (ST % 7 == 0) { alo = pin(alo); blo = pin(blo); }   \
      g1_stage<Q, ST>(acc, alo, blo, bar_full, bar_h); wg_commit(); \
      if (ST > 0) { wg_wait<1>(); release((Q * 14 + ST - 1) % B_NSLOT); } } while (0)
#define G1HH(Q) do { \
      _Pragma("unroll") \
      for (int i = 0; i < 28; i++) hh[28 * Q + i] = pack_bf16(acc[2 * i] * acc[56 + 2 * i], acc[2 * i + 1] * acc[57 + 2 * i]); \
    } while (0)
    {
      float acc[116];
      G1S(0, 0);
      if (tid == 0) TR(1, 3);
      G1S(0, 1);
      if (wg == 0) asm volatile("bar.arrive 3, 256;" ::: "memory");
      G1S(0, 2); G1S(0, 3); G1S(0, 4); G1S(0, 5); G1S(0, 6); G1S(0, 7); G1S(0, 8); G1S(0, 9); G1S(0, 10); G1S(0, 11); G1S(0, 12);
      G1S(0, 13);
      if (tid == 0) TR(1, 4);
      mbar_wait(bar_cs, 0);
      wg_wait<0>(); reg_fence(acc); release(13 % B_NSLOT);
      {
        const uint32_t msk = t == 0 ? 0xFFFFFFFFu : t == 1 ? 0xFFFFu : 0u;
        const float a = acc[112] * (-1.f / DM), b = acc[114] * (-1.f / DM);
        nm0 = pack_bf16(a, a) & msk; nm1 = pack_bf16(b, b) & msk;
      }
      wg_fence();
      wgmma_rs224<0, 8, 1>(*(float(*)[112])acc, nm0, nm1, 0u, 0u, clo);
      wg_commit(); wg_wait<0>(); reg_fence(acc);
      G1HH(0);
      if (tid == 0) TR(1, 5);
      G1S(1, 0); G1S(1, 1); G1S(1, 2); G1S(1, 3); G1S(1, 4); G1S(1, 5); G1S(1, 6);
      if (relt) asm volatile("mbarrier.arrive.shared::cluster.b64 _, [%0];" ::"r"(mapa(bar_afree, rank ^ 1)) : "memory");
      G1S(1, 7); G1S(1, 8); G1S(1, 9);
      if (relt) asm volatile("mbarrier.arrive.shared::cluster.b64 _, [%0];" ::"r"(mapa(bar_afree + 8, rank ^ 1)) : "memory");
      mbar_wait(bar_afree, 0);
      send_hh(0);
      G1S(1, 10); G1S(1, 11); G1S(1, 12);
      load_ep();
      g1_stage<1, 13>(acc, alo, blo, bar_full, bar_h);
      wgmma_rs224<224, 8, 1>(*(float(*)[112])acc, nm0, nm1, 0u, 0u, clo);
      wg_commit(); wg_wait<1>(); release(26 % B_NSLOT);
      wg_wait<0>(); reg_fence(acc); release(27 % B_NSLOT);
      G1HH(1);
      if (tid == 0) TR(1, 6);
    }
    float accA[28], accB[28];
    uint32_t ph0[28], ph1[28];
    ep = pin(ep >> 7); tag = pin((ep & 1u) << 16);
    blo += 48u << 16;
#define ISSUE(acc, I, a, FIRST) do { \
      constexpr int s_ = 28 + (I), sl_ = s_ % B_NSLOT; \
      if (sl_ == 0) blo = pin(blo); \
      mbar_wait(bar_full + 8 * sl_, (s_ / B_NSLOT) & 1); \
      wg_fence(); \
      wgmma_rs56<(sl_ * B_SLOT + 0 * 1792) / 16, 8, !(FIRST)>(acc, (a)[0], (a)[1], (a)[2], (a)[3], blo); \
      wgmma_rs56<(sl_ * B_SLOT + 1 * 1792) / 16, 8, 1>(acc, (a)[4], (a)[5], (a)[6], (a)[7], blo); \
      wgmma_rs56<(sl_ * B_SLOT + 2 * 1792) / 16, 8, 1>(acc, (a)[8], (a)[9], (a)[10], (a)[11], blo); \
      wgmma_rs56<(sl_ * B_SLOT + 3 * 1792) / 16, 8, 1>(acc, (a)[12], (a)[13], (a)[14], (a)[15], blo); \
      wgmma_rs56<(sl_ * B_SLOT + 4 * 1792) / 16, 8, 1>(acc, (a)[16], (a)[17], (a)[18], (a)[19], blo); \
      wgmma_rs56<(sl_ * B_SLOT + 5 * 1792) / 16, 8, 1>(acc, (a)[20], (a)[21], (a)[22], (a)[23], blo); \
      wgmma_rs56<(sl_ * B_SLOT + 6 * 1792) / 16, 8, 1>(acc, (a)[24], (a)[25], (a)[26], (a)[27], blo); \
      wg_commit(); } while (0)
    auto rel = [&](int i) { release((28 + i) % B_NSLOT); };
    auto tg = [&](uint32_t v) { return (v & 0xFFFEFFFFu) | tag; };
    auto send = [&](float (&acc)[28], int cc) {
      reg_fence(acc);
      const uint32_t a = out_addr(cc, wg) + wq * 1792;
#pragma unroll
      for (int q = 0; q < 3; q++)
        sts128(a + q * 512 + lane * 16, pack_bf16(acc[8 * q], acc[8 * q + 1]), pack_bf16(acc[8 * q + 2], acc[8 * q + 3]),
               pack_bf16(acc[8 * q + 4], acc[8 * q + 5]), tg(pack_bf16(acc[8 * q + 6], acc[8 * q + 7])));
      sts64(a + 1536 + lane * 8, pack_bf16(acc[24], acc[25]), tg(pack_bf16(acc[26], acc[27])));
      asm volatile("fence.proxy.async.shared::cta;" ::: "memory");
      mbar_arrive(bar_out + 8 * (cc * 2 + wg));
    };
    auto load_hh = [&](uint32_t (&d)[28], int q) {
      mbar_wait(bar_hh + 8 * (2 * q + wg), 0);
      const uint32_t a = sb + a_slot(2 * q + wg, cg) + t128 * 16;
#pragma unroll
      for (int i = 0; i < 7; i++) {
        const uint4 v = lds128(a + i * 2048);
        d[4 * i] = v.x; d[4 * i + 1] = v.y; d[4 * i + 2] = v.z; d[4 * i + 3] = v.w;
      }
    };
    ISSUE(accA, 0, hh, true);
    mbar_wait(bar_afree + 8, 0);
    send_hh(1);
    ISSUE(accA, 1, hh + 28, false);
    load_hh(ph0, 0);
    wg_wait<1>(); rel(0);
    ISSUE(accA, 2, ph0, false);      wg_wait<1>(); rel(1);
    ISSUE(accB, 3, hh, true);        wg_wait<1>(); rel(2);
    ISSUE(accB, 4, hh + 28, false);  wg_wait<1>(); rel(3);
    ISSUE(accB, 5, ph0, false);
    if (tid == 0) TR(1, 11);
    load_hh(ph1, 1);
    wg_wait<1>(); rel(4);
    ISSUE(accA, 6, ph1, false);      wg_wait<1>(); rel(5);
    ISSUE(accB, 7, ph1, false);      wg_wait<1>(); rel(6); send(accA, 0);
    ISSUE(accA, 8, hh, true);        wg_wait<1>(); rel(7); send(accB, 1);
    if (tid == 0) TR(1, 13);
    ISSUE(accA, 9, hh + 28, false);  wg_wait<1>(); rel(8);
    ISSUE(accA, 10, ph0, false);
    ISSUE(accA, 11, ph1, false);
    const int row = rt * 128 + wg * 64 + wq * 16 + g;
    uint32_t r20, r21;
    asm volatile("ld.relaxed.gpu.global.u32 %0, [%1];" : "=r"(r20) : "l"(g_stat2 + row) : "memory");
    asm volatile("ld.relaxed.gpu.global.u32 %0, [%1];" : "=r"(r21) : "l"(g_stat2 + row + 8) : "memory");
    ISSUE(accB, 12, hh, true);
    wg_wait<1>();
    {
      reg_fence(accA);
      uint4* pd = g_part + (size_t)(blockIdx.x * 3 + 2) * 896 + warp * 112 + lane;
#pragma unroll
      for (int q = 0; q < 3; q++)
        st128(pd + q * 32, pack_bf16(accA[8 * q], accA[8 * q + 1]), pack_bf16(accA[8 * q + 2], accA[8 * q + 3]),
              pack_bf16(accA[8 * q + 4], accA[8 * q + 5]), tg(pack_bf16(accA[8 * q + 6], accA[8 * q + 7])));
      asm volatile("{\n.reg .b64 v;\nmov.b64 v, {%1, %2};\nst.relaxed.gpu.global.b64 [%0], v;\n}"
                   ::"l"((uint2*)(pd + 96) - lane), "r"(pack_bf16(accA[24], accA[25])), "r"(tg(pack_bf16(accA[26], accA[27]))) : "memory");
    }
    if (tid == 0) TR(1, 16);
    ISSUE(accB, 13, hh + 28, false);
    ISSUE(accB, 14, ph0, false);
    uint32_t in0[14], in1[14], in2[14];
    in_load(in0, in_src(0, warp) + lane);
    in_load(in1, in_src(1, warp) + lane);
    ISSUE(accB, 15, ph1, false);
    if (tid == 0) TR(1, 7);
    {
      int it = 0;
      while ((((r20 ^ ep) | (r21 ^ ep)) & 1u) && ++it < 400000) {
        asm volatile("ld.relaxed.gpu.global.u32 %0, [%1];" : "=r"(r20) : "l"(g_stat2 + row) : "memory");
        asm volatile("ld.relaxed.gpu.global.u32 %0, [%1];" : "=r"(r21) : "l"(g_stat2 + row + 8) : "memory");
      }
    }
    wg_wait<1>();
    in_load(in2, in_src(2, warp) + lane);
    in_check(in0, 0, warp); in_check(in1, 1, warp);
#pragma unroll
    for (int i = 0; i < 14; i++) { accA[2 * i] = bf_lo(in0[i]) + bf_lo(in1[i]); accA[2 * i + 1] = bf_hi(in0[i]) + bf_hi(in1[i]); }
    if (tid == 0) TR(1, 12);
    wg_wait<0>();
    reg_fence(accB);
    uint32_t hres[16];
#pragma unroll
    for (int i = 0; i < 4; i++) {
      int qq = lane >> 3, r = lane & 7, kg = 7 * cg + 2 * i + (qq >> 1), c = 2 * wq + (qq & 1);
      if (kg > 55) kg = 55;
      asm volatile("ldmatrix.sync.aligned.m8n8.x4.trans.shared.b16 {%0,%1,%2,%3}, [%4];"
                   : "=r"(hres[4 * i]), "=r"(hres[4 * i + 1]), "=r"(hres[4 * i + 2]), "=r"(hres[4 * i + 3])
                   : "r"(sb + B_SA + kg * 2048 + wg * 1024 + r * 128 + ((c ^ r) << 4)) : "memory");
    }
#pragma unroll
    for (int i = 0; i < 28; i++) accB[i] += accA[i];
    if (tid == 0) TR(1, 9);
    in_check(in2, 2, warp);
#pragma unroll
    for (int i = 0; i < 14; i++) { accB[2 * i] += bf_lo(in2[i]); accB[2 * i + 1] += bf_hi(in2[i]); }
    uint32_t* o0 = (uint32_t*)(out + (size_t)row * DM + 56 * cg + 2 * t);
    uint32_t* o1 = o0 + 8 * DM / 2;
#pragma unroll
    for (int i = 0; i < 7; i++) {
      o0[4 * i] = hadd2_bf(hres[2 * i], pack_bf16(accB[4 * i] * __uint_as_float(r20), accB[4 * i + 1] * __uint_as_float(r20)));
      o1[4 * i] = hadd2_bf(hres[2 * i + 1], pack_bf16(accB[4 * i + 2] * __uint_as_float(r21), accB[4 * i + 3] * __uint_as_float(r21)));
    }
    if (tid == 0) TR(1, 10);
    if (tid == 128) TR(1, 15);
  }
}

extern "C" void kernel_launch(void* const* d_in, const int* in_sizes, int n_in, void* d_out, int out_size) {
  const __nv_bfloat16* x = (const __nv_bfloat16*)d_in[0];
  const __nv_bfloat16 *are = (const __nv_bfloat16*)d_in[1], *aim = (const __nv_bfloat16*)d_in[2], *bre = (const __nv_bfloat16*)d_in[3],
                      *bim = (const __nv_bfloat16*)d_in[4], *cre = (const __nv_bfloat16*)d_in[5], *cim = (const __nv_bfloat16*)d_in[6],
                      *logdt = (const __nv_bfloat16*)d_in[7], *dskip = (const __nv_bfloat16*)d_in[8];
  const __nv_bfloat16 *wg = (const __nv_bfloat16*)d_in[10], *wu = (const __nv_bfloat16*)d_in[11], *wd = (const __nv_bfloat16*)d_in[12];

  static bool init = false;
  if (!init) {
    init = true;
    cudaFuncSetAttribute(k_ffn, cudaFuncAttributeMaxDynamicSharedMemorySize, B_SMEM);
    cudaFuncSetAttribute(k_front, cudaFuncAttributeMaxDynamicSharedMemorySize, A_SMEM);
  }
  cudaStream_t st = cudaStreamPerThread;
  k_front<<<128, 512, A_SMEM, st>>>(
      x, (const uint32_t*)are, (const uint32_t*)aim, (const uint32_t*)bre, (const uint32_t*)bim, (const uint32_t*)cre, (const uint32_t*)cim,
      (const unsigned short*)logdt, (const unsigned short*)dskip, (const uint4*)wg, (const uint4*)wu, (const uint4*)wd);
  cudaLaunchConfig_t cfg = {};
  cfg.gridDim = dim3(128); cfg.blockDim = dim3(384); cfg.dynamicSmemBytes = B_SMEM; cfg.stream = st;
  cudaLaunchAttribute at[1];
  at[0].id = cudaLaunchAttributeProgrammaticStreamSerialization; at[0].val.programmaticStreamSerializationAllowed = 1;
  cfg.attrs = at; cfg.numAttrs = 1;
  cudaLaunchKernelEx(&cfg, k_ffn, (__nv_bfloat16*)d_out);
}
```

```cpp
#include <cuda_runtime.h>
#include <cuda_bf16.h>
#include <cuda_fp16.h>
#include <stdint.h>

constexpr int LSEQ = 2048, DM = 448;

__device__ uint4    g_himg[16 * 114688 / 16];
__device__ uint4    g_cimg[8 * 2 * 224];
__device__ uint32_t g_stat2[LSEQ];
__device__ uint4    g_part[128 * 3 * 896];
__device__ uint4    g_wimg[8 * 602112 / 16];
__device__ uint4    g_ux[DM * 128 * 4];
__device__ unsigned g_cnt1;

#define TR(k, i) do {} while (0)
__device__ __forceinline__ uint32_t s2u(const void* p) { return (uint32_t)__cvta_generic_to_shared(p); }
__device__ __forceinline__ void mbar_init(uint32_t b, int c) { asm volatile("mbarrier.init.shared::cta.b64 [%0], %1;" ::"r"(b), "r"(c)); }
__device__ __forceinline__ void mbar_expect(uint32_t b, int bytes) { asm volatile("mbarrier.arrive.expect_tx.shared::cta.b64 _, [%0], %1;" ::"r"(b), "r"(bytes) : "memory"); }
__device__ __forceinline__ void mbar_arrive(uint32_t b) { asm volatile("mbarrier.arrive.shared::cta.b64 _, [%0];" ::"r"(b) : "memory"); }
__device__ __forceinline__ void mbar_wait(uint32_t b, int ph) {
  asm volatile("{\n.reg .pred p;\n.reg .b32 n;\nmov.b32 n, 0;\nLW:\nmbarrier.try_wait.parity.shared::cta.b64 p, [%0], %1;\n@p bra LD;\n"
               "add.u32 n, n, 1;\nsetp.lt.u32 p, n, 4000000;\n@p bra LW;\ntrap;\nLD:\n}" ::"r"(b), "r"(ph) : "memory");
}
__device__ __forceinline__ bool mbar_test(uint32_t b, int ph) {
  uint32_t ok;
  asm volatile("{\n.reg .pred p;\nmbarrier.test_wait.parity.shared::cta.b64 p, [%1], %2;\nselp.u32 %0, 1, 0, p;\n}" : "=r"(ok) : "r"(b), "r"(ph) : "memory");
  return ok;
}
__device__ __forceinline__ void wg_fence() { asm volatile("wgmma.fence.sync.aligned;" ::: "memory"); }
__device__ __forceinline__ void wg_commit() { asm volatile("wgmma.commit_group.sync.aligned;" ::: "memory"); }
template <int N> __device__ __forceinline__ void wg_wait() { asm volatile("wgmma.wait_group.sync.aligned %0;" ::"n"(N) : "memory"); }
template <int N> __device__ __forceinline__ void reg_fence(float (&a)[N]) {
#pragma unroll
  for (int i = 0; i < N; i++) asm volatile("" : "+f"(a[i])::"memory");
}
__device__ __forceinline__ uint32_t pack_bf16(float lo, float hi) {
  uint32_t r; asm("cvt.rn.bf16x2.f32 %0, %1, %2;" : "=r"(r) : "f"(hi), "f"(lo)); return r;
}
__device__ __forceinline__ float bf_lo(uint32_t v) { return __uint_as_float(v << 16); }
__device__ __forceinline__ float bf_hi(uint32_t v) { return __uint_as_float(v & 0xFFFF0000u); }
__device__ __forceinline__ float rbf(float x) { return __bfloat162float(__float2bfloat16_rn(x)); }
__device__ __forceinline__ uint32_t hmul2_bf(uint32_t a, uint32_t b) { uint32_t r; asm("mul.rn.bf16x2 %0, %1, %2;" : "=r"(r) : "r"(a), "r"(b)); return r; }
__device__ __forceinline__ uint32_t hadd2_bf(uint32_t a, uint32_t b) { uint32_t r; asm("add.rn.bf16x2 %0, %1, %2;" : "=r"(r) : "r"(a), "r"(b)); return r; }
__device__ __forceinline__ void bulk_ld(uint32_t dst, const void* src, int bytes, uint32_t bar) {
  asm volatile("cp.async.bulk.shared::cluster.global.mbarrier::complete_tx::bytes [%0], [%1], %2, [%3];"
               ::"r"(dst), "l"(src), "r"(bytes), "r"(bar) : "memory");
}

template <int BYTES>
__device__ __forceinline__ void bulk_ld_elect(uint32_t dst, const void* src, uint32_t bar) {
  asm volatile("{\n.reg .pred p;\nelect.sync _|p, 0xffffffff;\n"
               "@p mbarrier.arrive.expect_tx.shared::cta.b64 _, [%2], %3;\n"
               "@p cp.async.bulk.shared::cluster.global.mbarrier::complete_tx::bytes [%0], [%1], %3, [%2];\n}"
               ::"r"(dst), "l"(src), "r"(bar), "n"(BYTES) : "memory");
}
template <int BYTES>
__device__ __forceinline__ void bulk_ld_mc_elect(uint32_t dst, const void* src, uint32_t bar) {
  asm volatile("{\n.reg .pred p;\nelect.sync _|p, 0xffffffff;\n"
               "@p mbarrier.arrive.expect_tx.shared::cta.b64 _, [%2], %3;\n"
               "@p cp.async.bulk.shared::cluster.global.mbarrier::complete_tx::bytes.multicast::cluster [%0], [%1], %4, [%2], %5;\n}"
               ::"r"(dst), "l"(src), "r"(bar), "n"(2 * BYTES), "n"(BYTES), "h"((uint16_t)3) : "memory");
}
template <int AOFF, uint32_t AHI, int BOFF, uint32_t BHI, int ACC>
__device__ __forceinline__ void wgmma_ss224(float (&d)[112], uint32_t alo, uint32_t blo) {
  asm volatile("{\n.reg .pred p;\n.reg .b64 ad, bd;\nsetp.ne.b32 p, %118, 0;\n"
    "mov.b64 ad, {%112, %115};\nadd.s64 ad, ad, %114;\nmov.b64 bd, {%113, %117};\nadd.s64 bd, bd, %116;\n"
    "wgmma.mma_async.sync.aligned.m64n224k16.f32.bf16.bf16 {%0,%1,%2,%3,%4,%5,%6,%7,%8,%9,%10,%11,%12,%13,%14,%15,%16,%17,%18,%19,%20,%21,%22,%23,%24,%25,%26,%27,%28,%29,%30,%31,%32,%33,%34,%35,%36,%37,%38,%39,%40,%41,%42,%43,%44,%45,%46,%47,%48,%49,%50,%51,%52,%53,%54,%55,%56,%57,%58,%59,%60,%61,%62,%63,%64,%65,%66,%67,%68,%69,%70,%71,%72,%73,%74,%75,%76,%77,%78,%79,%80,%81,%82,%83,%84,%85,%86,%87,%88,%89,%90,%91,%92,%93,%94,%95,%96,%97,%98,%99,%100,%101,%102,%103,%104,%105,%106,%107,%108,%109,%110,%111}, ad, bd, p, 1, 1, 1, 1;\n}\n"
    : "+f"(d[0]),"+f"(d[1]),"+f"(d[2]),"+f"(d[3]),"+f"(d[4]),"+f"(d[5]),"+f"(d[6]),"+f"(d[7]),"+f"(d[8]),"+f"(d[9]),"+f"(d[10]),"+f"(d[11]),"+f"(d[12]),"+f"(d[13]),"+f"(d[14]),"+f"(d[15]),"+f"(d[16]),"+f"(d[17]),"+f"(d[18]),"+f"(d[19]),"+f"(d[20]),"+f"(d[21]),"+f"(d[22]),"+f"(d[23]),"+f"(d[24]),"+f"(d[25]),"+f"(d[26]),"+f"(d[27]),"+f"(d[28]),"+f"(d[29]),"+f"(d[30]),"+f"(d[31]),"+f"(d[32]),"+f"(d[33]),"+f"(d[34]),"+f"(d[35]),"+f"(d[36]),"+f"(d[37]),"+f"(d[38]),"+f"(d[39]),"+f"(d[40]),"+f"(d[41]),"+f"(d[42]),"+f"(d[43]),"+f"(d[44]),"+f"(d[45]),"+f"(d[46]),"+f"(d[47]),"+f"(d[48]),"+f"(d[49]),"+f"(d[50]),"+f"(d[51]),"+f"(d[52]),"+f"(d[53]),"+f"(d[54]),"+f"(d[55]),"+f"(d[56]),"+f"(d[57]),"+f"(d[58]),"+f"(d[59]),"+f"(d[60]),"+f"(d[61]),"+f"(d[62]),"+f"(d[63]),"+f"(d[64]),"+f"(d[65]),"+f"(d[66]),"+f"(d[67]),"+f"(d[68]),"+f"(d[69]),"+f"(d[70]),"+f"(d[71]),"+f"(d[72]),"+f"(d[73]),"+f"(d[74]),"+f"(d[75]),"+f"(d[76]),"+f"(d[77]),"+f"(d[78]),"+f"(d[79]),"+f"(d[80]),"+f"(d[81]),"+f"(d[82]),"+f"(d[83]),"+f"(d[84]),"+f"(d[85]),"+f"(d[86]),"+f"(d[87]),"+f"(d[88]),"+f"(d[89]),"+f"(d[90]),"+f"(d[91]),"+f"(d[92]),"+f"(d[93]),"+f"(d[94]),"+f"(d[95]),"+f"(d[96]),"+f"(d[97]),"+f"(d[98]),"+f"(d[99]),"+f"(d[100]),"+f"(d[101]),"+f"(d[102]),"+f"(d[103]),"+f"(d[104]),"+f"(d[105]),"+f"(d[106]),"+f"(d[107]),"+f"(d[108]),"+f"(d[109]),"+f"(d[110]),"+f"(d[111])
    : "r"(alo), "r"(blo), "n"(AOFF), "n"(AHI), "n"(BOFF), "n"(BHI), "n"(ACC));
}
template <int AOFF, uint32_t AHI, int BOFF, uint32_t BHI, int ACC>
__device__ __forceinline__ void wgmma_ss232(float (&d)[116], uint32_t alo, uint32_t blo) {
  asm volatile("{\n.reg .pred p;\n.reg .b64 ad, bd;\nsetp.ne.b32 p, %122, 0;\n"
    "mov.b64 ad, {%116, %119};\nadd.s64 ad, ad, %118;\nmov.b64 bd, {%117, %121};\nadd.s64 bd, bd, %120;\n"
    "wgmma.mma_async.sync.aligned.m64n232k16.f32.bf16.bf16 {%0,%1,%2,%3,%4,%5,%6,%7,%8,%9,%10,%11,%12,%13,%14,%15,%16,%17,%18,%19,%20,%21,%22,%23,%24,%25,%26,%27,%28,%29,%30,%31,%32,%33,%34,%35,%36,%37,%38,%39,%40,%41,%42,%43,%44,%45,%46,%47,%48,%49,%50,%51,%52,%53,%54,%55,%56,%57,%58,%59,%60,%61,%62,%63,%64,%65,%66,%67,%68,%69,%70,%71,%72,%73,%74,%75,%76,%77,%78,%79,%80,%81,%82,%83,%84,%85,%86,%87,%88,%89,%90,%91,%92,%93,%94,%95,%96,%97,%98,%99,%100,%101,%102,%103,%104,%105,%106,%107,%108,%109,%110,%111,%112,%113,%114,%115}, ad, bd, p, 1, 1, 1, 1;\n}\n"
    : "+f"(d[0]),"+f"(d[1]),"+f"(d[2]),"+f"(d[3]),"+f"(d[4]),"+f"(d[5]),"+f"(d[6]),"+f"(d[7]),"+f"(d[8]),"+f"(d[9]),"+f"(d[10]),"+f"(d[11]),"+f"(d[12]),"+f"(d[13]),"+f"(d[14]),"+f"(d[15]),"+f"(d[16]),"+f"(d[17]),"+f"(d[18]),"+f"(d[19]),"+f"(d[20]),"+f"(d[21]),"+f"(d[22]),"+f"(d[23]),"+f"(d[24]),"+f"(d[25]),"+f"(d[26]),"+f"(d[27]),"+f"(d[28]),"+f"(d[29]),"+f"(d[30]),"+f"(d[31]),"+f"(d[32]),"+f"(d[33]),"+f"(d[34]),"+f"(d[35]),"+f"(d[36]),"+f"(d[37]),"+f"(d[38]),"+f"(d[39]),"+f"(d[40]),"+f"(d[41]),"+f"(d[42]),"+f"(d[43]),"+f"(d[44]),"+f"(d[45]),"+f"(d[46]),"+f"(d[47]),"+f"(d[48]),"+f"(d[49]),"+f"(d[50]),"+f"(d[51]),"+f"(d[52]),"+f"(d[53]),"+f"(d[54]),"+f"(d[55]),"+f"(d[56]),"+f"(d[57]),"+f"(d[58]),"+f"(d[59]),"+f"(d[60]),"+f"(d[61]),"+f"(d[62]),"+f"(d[63]),"+f"(d[64]),"+f"(d[65]),"+f"(d[66]),"+f"(d[67]),"+f"(d[68]),"+f"(d[69]),"+f"(d[70]),"+f"(d[71]),"+f"(d[72]),"+f"(d[73]),"+f"(d[74]),"+f"(d[75]),"+f"(d[76]),"+f"(d[77]),"+f"(d[78]),"+f"(d[79]),"+f"(d[80]),"+f"(d[81]),"+f"(d[82]),"+f"(d[83]),"+f"(d[84]),"+f"(d[85]),"+f"(d[86]),"+f"(d[87]),"+f"(d[88]),"+f"(d[89]),"+f"(d[90]),"+f"(d[91]),"+f"(d[92]),"+f"(d[93]),"+f"(d[94]),"+f"(d[95]),"+f"(d[96]),"+f"(d[97]),"+f"(d[98]),"+f"(d[99]),"+f"(d[100]),"+f"(d[101]),"+f"(d[102]),"+f"(d[103]),"+f"(d[104]),"+f"(d[105]),"+f"(d[106]),"+f"(d[107]),"+f"(d[108]),"+f"(d[109]),"+f"(d[110]),"+f"(d[111]),"+f"(d[112]),"+f"(d[113]),"+f"(d[114]),"+f"(d[115])
    : "r"(alo), "r"(blo), "n"(AOFF), "n"(AHI), "n"(BOFF), "n"(BHI), "n"(ACC));
}
template <int OFF, uint32_t BHI, int ACC>
__device__ __forceinline__ void wgmma_rs224(float (&d)[112], uint32_t a0, uint32_t a1, uint32_t a2, uint32_t a3, uint32_t blo) {
  asm volatile("{\n.reg .pred p;\n.reg .b64 bd;\nsetp.ne.b32 p, %119, 0;\nmov.b64 bd, {%116, %118};\nadd.s64 bd, bd, %117;\n"
    "wgmma.mma_async.sync.aligned.m64n224k16.f32.bf16.bf16 {%0,%1,%2,%3,%4,%5,%6,%7,%8,%9,%10,%11,%12,%13,%14,%15,%16,%17,%18,%19,%20,%21,%22,%23,%24,%25,%26,%27,%28,%29,%30,%31,%32,%33,%34,%35,%36,%37,%38,%39,%40,%41,%42,%43,%44,%45,%46,%47,%48,%49,%50,%51,%52,%53,%54,%55,%56,%57,%58,%59,%60,%61,%62,%63,%64,%65,%66,%67,%68,%69,%70,%71,%72,%73,%74,%75,%76,%77,%78,%79,%80,%81,%82,%83,%84,%85,%86,%87,%88,%89,%90,%91,%92,%93,%94,%95,%96,%97,%98,%99,%100,%101,%102,%103,%104,%105,%106,%107,%108,%109,%110,%111}, {%112,%113,%114,%115}, bd, p, 1, 1, 1;\n}\n"
    : "+f"(d[0]),"+f"(d[1]),"+f"(d[2]),"+f"(d[3]),"+f"(d[4]),"+f"(d[5]),"+f"(d[6]),"+f"(d[7]),"+f"(d[8]),"+f"(d[9]),"+f"(d[10]),"+f"(d[11]),"+f"(d[12]),"+f"(d[13]),"+f"(d[14]),"+f"(d[15]),"+f"(d[16]),"+f"(d[17]),"+f"(d[18]),"+f"(d[19]),"+f"(d[20]),"+f"(d[21]),"+f"(d[22]),"+f"(d[23]),"+f"(d[24]),"+f"(d[25]),"+f"(d[26]),"+f"(d[27]),"+f"(d[28]),"+f"(d[29]),"+f"(d[30]),"+f"(d[31]),"+f"(d[32]),"+f"(d[33]),"+f"(d[34]),"+f"(d[35]),"+f"(d[36]),"+f"(d[37]),"+f"(d[38]),"+f"(d[39]),"+f"(d[40]),"+f"(d[41]),"+f"(d[42]),"+f"(d[43]),"+f"(d[44]),"+f"(d[45]),"+f"(d[46]),"+f"(d[47]),"+f"(d[48]),"+f"(d[49]),"+f"(d[50]),"+f"(d[51]),"+f"(d[52]),"+f"(d[53]),"+f"(d[54]),"+f"(d[55]),"+f"(d[56]),"+f"(d[57]),"+f"(d[58]),"+f"(d[59]),"+f"(d[60]),"+f"(d[61]),"+f"(d[62]),"+f"(d[63]),"+f"(d[64]),"+f"(d[65]),"+f"(d[66]),"+f"(d[67]),"+f"(d[68]),"+f"(d[69]),"+f"(d[70]),"+f"(d[71]),"+f"(d[72]),"+f"(d[73]),"+f"(d[74]),"+f"(d[75]),"+f"(d[76]),"+f"(d[77]),"+f"(d[78]),"+f"(d[79]),"+f"(d[80]),"+f"(d[81]),"+f"(d[82]),"+f"(d[83]),"+f"(d[84]),"+f"(d[85]),"+f"(d[86]),"+f"(d[87]),"+f"(d[88]),"+f"(d[89]),"+f"(d[90]),"+f"(d[91]),"+f"(d[92]),"+f"(d[93]),"+f"(d[94]),"+f"(d[95]),"+f"(d[96]),"+f"(d[97]),"+f"(d[98]),"+f"(d[99]),"+f"(d[100]),"+f"(d[101]),"+f"(d[102]),"+f"(d[103]),"+f"(d[104]),"+f"(d[105]),"+f"(d[106]),"+f"(d[107]),"+f"(d[108]),"+f"(d[109]),"+f"(d[110]),"+f"(d[111])
    : "r"(a0), "r"(a1), "r"(a2), "r"(a3), "r"(blo), "n"(OFF), "n"(BHI), "n"(ACC));
}
template <int OFF, uint32_t BHI, int ACC>
__device__ __forceinline__ void wgmma_rs56(float (&d)[28], uint32_t a0, uint32_t a1, uint32_t a2, uint32_t a3, uint32_t blo) {
  asm volatile("{\n.reg .pred p;\n.reg .b64 bd;\nsetp.ne.b32 p, %35, 0;\nmov.b64 bd, {%32, %34};\nadd.s64 bd, bd, %33;\n"
    "wgmma.mma_async.sync.aligned.m64n56k16.f32.bf16.bf16 {%0,%1,%2,%3,%4,%5,%6,%7,%8,%9,%10,%11,%12,%13,%14,%15,%16,%17,%18,%19,%20,%21,%22,%23,%24,%25,%26,%27}, {%28,%29,%30,%31}, bd, p, 1, 1, 1;\n}\n"
    : "+f"(d[0]),"+f"(d[1]),"+f"(d[2]),"+f"(d[3]),"+f"(d[4]),"+f"(d[5]),"+f"(d[6]),"+f"(d[7]),"+f"(d[8]),"+f"(d[9]),"+f"(d[10]),"+f"(d[11]),"+f"(d[12]),"+f"(d[13]),"+f"(d[14]),"+f"(d[15]),"+f"(d[16]),"+f"(d[17]),"+f"(d[18]),"+f"(d[19]),"+f"(d[20]),"+f"(d[21]),"+f"(d[22]),"+f"(d[23]),"+f"(d[24]),"+f"(d[25]),"+f"(d[26]),"+f"(d[27])
    : "r"(a0), "r"(a1), "r"(a2), "r"(a3), "r"(blo), "n"(OFF), "n"(BHI), "n"(ACC));
}

__device__ __forceinline__ void st128(uint4* p, uint32_t a, uint32_t b, uint32_t c, uint32_t d) {
  asm volatile("{\n.reg .b128 v;\n.reg .b64 lo, hi;\nmov.b64 lo, {%1, %2};\nmov.b64 hi, {%3, %4};\nmov.b128 v, {lo, hi};\n"
               "st.relaxed.gpu.global.b128 [%0], v;\n}" ::"l"(p), "r"(a), "r"(b), "r"(c), "r"(d) : "memory");
}
__device__ __forceinline__ void ld128(const uint4* p, uint32_t* r) {
  asm volatile("{\n.reg .b128 v;\n.reg .b64 lo, hi;\nld.relaxed.gpu.global.b128 v, [%4];\nmov.b128 {lo, hi}, v;\n"
               "mov.b64 {%0, %1}, lo;\nmov.b64 {%2, %3}, hi;\n}" : "=r"(r[0]), "=r"(r[1]), "=r"(r[2]), "=r"(r[3]) : "l"(p) : "memory");
}

template <int OFF, uint32_t BHI, int ACC>
__device__ __forceinline__ void wgmma_rs32(float (&d)[16], uint32_t a0, uint32_t a1, uint32_t a2, uint32_t a3, uint32_t blo) {
  asm volatile("{\n.reg .pred p;\n.reg .b64 bd;\nsetp.ne.b32 p, %23, 0;\nmov.b64 bd, {%20, %22};\nadd.s64 bd, bd, %21;\n"
    "wgmma.mma_async.sync.aligned.m64n32k16.f32.bf16.bf16 {%0,%1,%2,%3,%4,%5,%6,%7,%8,%9,%10,%11,%12,%13,%14,%15}, {%16,%17,%18,%19}, bd, p, 1, 1, 0;\n}\n"
    : "+f"(d[0]),"+f"(d[1]),"+f"(d[2]),"+f"(d[3]),"+f"(d[4]),"+f"(d[5]),"+f"(d[6]),"+f"(d[7]),"+f"(d[8]),"+f"(d[9]),"+f"(d[10]),"+f"(d[11]),"+f"(d[12]),"+f"(d[13]),"+f"(d[14]),"+f"(d[15])
    : "r"(a0), "r"(a1), "r"(a2), "r"(a3), "r"(blo), "n"(OFF), "n"(BHI), "n"(ACC));
}
template <int OFF, uint32_t BHI, int ACC>
__device__ __forceinline__ void wgmma_rs24(float (&d)[12], uint32_t a0, uint32_t a1, uint32_t a2, uint32_t a3, uint32_t blo) {
  asm volatile("{\n.reg .pred p;\n.reg .b64 bd;\nsetp.ne.b32 p, %19, 0;\nmov.b64 bd, {%16, %18};\nadd.s64 bd, bd, %17;\n"
    "wgmma.mma_async.sync.aligned.m64n24k16.f32.bf16.bf16 {%0,%1,%2,%3,%4,%5,%6,%7,%8,%9,%10,%11}, {%12,%13,%14,%15}, bd, p, 1, 1, 1;\n}\n"
    : "+f"(d[0]),"+f"(d[1]),"+f"(d[2]),"+f"(d[3]),"+f"(d[4]),"+f"(d[5]),"+f"(d[6]),"+f"(d[7]),"+f"(d[8]),"+f"(d[9]),"+f"(d[10]),"+f"(d[11])
    : "r"(a0), "r"(a1), "r"(a2), "r"(a3), "r"(blo), "n"(OFF), "n"(BHI), "n"(ACC));
}
template <int OFF, uint32_t BHI, int ACC>
__device__ __forceinline__ void wgmma_rs16(float (&d)[8], uint32_t a0, uint32_t a1, uint32_t a2, uint32_t a3, uint32_t blo) {
  asm volatile("{\n.reg .pred p;\n.reg .b64 bd;\nsetp.ne.b32 p, %15, 0;\nmov.b64 bd, {%12, %14};\nadd.s64 bd, bd, %13;\n"
    "wgmma.mma_async.sync.aligned.m64n16k16.f32.bf16.bf16 {%0,%1,%2,%3,%4,%5,%6,%7}, {%8,%9,%10,%11}, bd, p, 1, 1, 1;\n}\n"
    : "+f"(d[0]),"+f"(d[1]),"+f"(d[2]),"+f"(d[3]),"+f"(d[4]),"+f"(d[5]),"+f"(d[6]),"+f"(d[7])
    : "r"(a0), "r"(a1), "r"(a2), "r"(a3), "r"(blo), "n"(OFF), "n"(BHI), "n"(ACC));
}

constexpr int A_R1 = 0;
constexpr int A_R2A = A_R1 + 2624, A_R2B = A_R2A + 768, A_R3A = A_R2B + 768, A_R3B = A_R3A + 528;
constexpr int A_K1024 = A_R3B + 528;
constexpr int A_W5 = A_K1024 + 16;
constexpr int A_W3 = A_W5 + 4096;
constexpr int A_W9 = A_W3 + 4112;
constexpr int A_W7 = A_W9 + 2080;
constexpr int A_V  = A_W7 + 2080 + 32;
constexpr int A_SCL = A_V + 2048;
constexpr int A_UB = A_SCL + 16;
constexpr int A_STG = A_UB + 5248;
constexpr int A_Y2 = A_STG, A_Y3 = A_Y2 + 6528, A_YB = A_Y3 + 4352;
constexpr int A_REC = A_STG + 4 * 4352;
constexpr int A_CH = A_REC + 8192;
static_assert(A_W5 % 16 == 0 && A_UB % 16 == 0 && A_CH % 16 == 0 && A_YB + 4096 <= A_REC, "layout");

struct cf { float x, y; };
__device__ __forceinline__ cf cmul(cf a, cf b) { cf r; r.x = fmaf(a.x, b.x, -a.y * b.y); r.y = fmaf(a.x, b.y, a.y * b.x); return r; }
__device__ __forceinline__ cf cexp_l(float lr, float li, float l) {
  float mag; asm("ex2.approx.ftz.f32 %0, %1;" : "=f"(mag) : "f"((lr * l) * 1.4426950408889634f));
  const float th = li * l;
  const float k = (fmaf(th, 0.15915494f, 12582912.f)) - 12582912.f;
  float ph = fmaf(th, 0.15915494f, -k);
  ph = fmaf(th, 6.4206383e-9f, ph) * 6.2831853f;
  cf r; r.x = mag * __cosf(ph); r.y = mag * __sinf(ph); return r;
}
__device__ __forceinline__ void sts16(uint32_t a, uint32_t v) { asm volatile("st.shared.u16 [%0], %1;" ::"r"(a), "h"((uint16_t)v) : "memory"); }
__device__ __forceinline__ void sts32(uint32_t a, uint32_t v) { asm volatile("st.shared.u32 [%0], %1;" ::"r"(a), "r"(v) : "memory"); }
__device__ __forceinline__ void sts64(uint32_t a, uint32_t v0, uint32_t v1) { asm volatile("st.shared.v2.u32 [%0], {%1, %2};" ::"r"(a), "r"(v0), "r"(v1) : "memory"); }
__device__ __forceinline__ void sts128(uint32_t a, uint32_t v0, uint32_t v1, uint32_t v2, uint32_t v3) {
  asm volatile("st.shared.v4.u32 [%0], {%1, %2, %3, %4};" ::"r"(a), "r"(v0), "r"(v1), "r"(v2), "r"(v3) : "memory");
}
__device__ __forceinline__ uint32_t lds32(uint32_t a) { uint32_t v; asm volatile("ld.shared.u32 %0, [%1];" : "=r"(v) : "r"(a) : "memory"); return v; }
__device__ __forceinline__ uint4 lds128(uint32_t a) {
  uint4 v; asm volatile("ld.shared.v4.u32 {%0, %1, %2, %3}, [%4];" : "=r"(v.x), "=r"(v.y), "=r"(v.z), "=r"(v.w) : "r"(a) : "memory"); return v;
}
__device__ __forceinline__ void ldsm4(uint32_t* r, uint32_t a) {
  asm volatile("ldmatrix.sync.aligned.m8n8.x4.shared.b16 {%0,%1,%2,%3}, [%4];" : "=r"(r[0]), "=r"(r[1]), "=r"(r[2]), "=r"(r[3]) : "r"(a) : "memory");
}
__device__ __forceinline__ void mma16816(float* d, uint32_t a0, uint32_t a1, uint32_t a2, uint32_t a3, uint32_t b0, uint32_t b1) {
  asm volatile("mma.sync.aligned.m16n8k16.row.col.f32.f16.f16.f32 {%0,%1,%2,%3}, {%4,%5,%6,%7}, {%8,%9}, {%0,%1,%2,%3};"
               : "+f"(d[0]), "+f"(d[1]), "+f"(d[2]), "+f"(d[3]) : "r"(a0), "r"(a1), "r"(a2), "r"(a3), "r"(b0), "r"(b1));
}
__device__ __forceinline__ uint32_t pack_h(float lo, float hi) { uint32_t r; asm("cvt.rn.f16x2.f32 %0, %1, %2;" : "=r"(r) : "f"(hi), "f"(lo)); return r; }
__device__ __forceinline__ uint32_t pack_h(cf v) { return pack_h(v.x, v.y); }
__device__ __forceinline__ uint32_t hcmul(uint32_t x, uint32_t r0, uint32_t r1) {
  const __half2 hx = *(__half2*)&x;
  const __half2 y = __hfma2(__high2half2(hx), *(__half2*)&r1, __hmul2(__low2half2(hx), *(__half2*)&r0));
  return *(const uint32_t*)&y;
}
__device__ __forceinline__ float ln_rstd(float var) {
  float sd, rs;
  asm("sqrt.approx.f32 %0, %1;" : "=f"(sd) : "f"(rbf(rbf(var) + 1e-5f)));
  asm("rcp.approx.f32 %0, %1;" : "=f"(rs) : "f"(rbf(sd)));
  return rs;
}
__device__ __forceinline__ uint32_t hsub2_bf(uint32_t a, uint32_t b) { uint32_t r; asm("sub.rn.bf16x2 %0, %1, %2;" : "=r"(r) : "r"(a), "r"(b)); return r; }
__device__ __forceinline__ void bar_sync(int id, int n) { asm volatile("bar.sync %0, %1;" ::"r"(id), "r"(n) : "memory"); }

template <int S> struct F1B { static constexpr int c = S / 4 + ((S & 3) == 3 ? 0 : 0), cc = (16 * S) / 64, ks = (64 * cc - (16 * S - 48)) / 16, off = (A_UB + 2 * ks * 656 + (9 - cc) * 16) / 16; };

template <int NS>
__device__ __forceinline__ void load_quads(uint32_t* q, uint32_t addr) {
#pragma unroll
  for (int i = 0; i < NS; i++) {
    q[4 * i] = lds32(addr + i * 64); q[4 * i + 1] = lds32(addr + i * 64 + 32);
    q[4 * i + 2] = i ? q[4 * i - 3] : lds32(addr - 32);
    q[4 * i + 3] = q[4 * i];
  }
#pragma unroll
  for (int i = 0; i < 4 * NS; i++) asm volatile("" : "+r"(q[i]));
}
template <int S0, int NS>
__device__ __forceinline__ void f1_steps(float (&acc)[16], const uint32_t* a, uint32_t blo) {
  if constexpr (NS > 0) {
    wgmma_rs32<F1B<S0>::off, 8, S0 != 0>(acc, a[0], a[1], a[2], a[3], blo);
    f1_steps<S0 + 1, NS - 1>(acc, a + 4, blo);
  }
}
template <int S0, int NS, int BASE, int FIRST>
__device__ __forceinline__ void s2_steps(float (&acc)[12], const uint32_t* a, uint32_t blo) {
  if constexpr (NS > 0) {
    wgmma_rs24<BASE / 16 + (112 - 16 * S0), 64, !(FIRST && S0 == 0)>(acc, a[0], a[1], a[2], a[3], blo);
    s2_steps<S0 + 1, NS - 1, BASE, FIRST>(acc, a + 4, blo);
  }
}
template <int S0, int NS, int BASE, int FIRST>
__device__ __forceinline__ void s3_steps(float (&acc)[8], const uint32_t* a, uint32_t blo) {
  if constexpr (NS > 0) {
    wgmma_rs16<BASE / 16 + (48 - 16 * S0), 65, !(FIRST && S0 == 0)>(acc, a[0], a[1], a[2], a[3], blo);
    s3_steps<S0 + 1, NS - 1, BASE, FIRST>(acc, a + 4, blo);
  }
}

__device__ __forceinline__ void phase_a(
        unsigned char* sm, const uint32_t bar_rec, const uint32_t ep_addr,
        const __nv_bfloat16* __restrict__ x, const uint32_t* __restrict__ are, const uint32_t* __restrict__ aim,
        const uint32_t* __restrict__ bre, const uint32_t* __restrict__ bim, const uint32_t* __restrict__ cre,
        const uint32_t* __restrict__ cim, const unsigned short* __restrict__ logdt, const unsigned short* __restrict__ dskip,
        const uint4* __restrict__ wgate, const uint4* __restrict__ wup, const uint4* __restrict__ wdown) {
  const uint32_t sb = s2u(sm);
  const int tid = threadIdx.x, warp = __shfl_sync(~0u, tid >> 5, 0), wg = warp >> 2, lane = tid & 31, wq = warp & 3, t128 = tid & 127;
  const int blk = blockIdx.x;
  const bool conv = blk < 112;

  uint2 xr[4];
  {
    const uint2* p = (const uint2*)(x + (size_t)(blk * 16 + warp) * DM);
    xr[0] = __ldg(p + lane); xr[1] = __ldg(p + 32 + lane); xr[2] = __ldg(p + 64 + lane);
    xr[3] = lane < 16 ? __ldg(p + 96 + lane) : make_uint2(0, 0);
  }
  const int ch = conv ? blk * 4 + wg : 0;
  const uint32_t cb = sb + wg * A_CH;
  uint32_t prm[6];
  {
    const int i = ch * 128 + t128;
    prm[0] = __ldg(are + i); prm[1] = __ldg(aim + i); prm[2] = __ldg(bre + i); prm[3] = __ldg(bim + i); prm[4] = __ldg(cre + i); prm[5] = __ldg(cim + i);
  }
  const uint32_t ldt = __ldg(logdt + ch);
  uint32_t cnt0 = 0;
  if (tid == 0) cnt0 = __ldcg(&g_cnt1);
  const int g = lane >> 2, t = lane & 3;
  const int wu2 = ch >> 1, wjq = wu2 / 14, wst = wu2 % 14;
  const uint32_t wstg = cb + A_W5 + wq * 2944;
  const uint4* ws1 = ((ch & 1) ? wup : wgate) + (size_t)(wst * 32 + g) * 224 + wjq * 14 + wq * 4 + t;
  const uint4* ws2 = wdown + (size_t)(wu2 * 8 + g) * 56 + ((ch & 1) * 4 + wq) * 7 + t;
  auto w_copy = [&](int i) {
    if (i < 4) { if (wq < 3 || t < 2) asm volatile("cp.async.cg.shared.global [%0], [%1], 16;" ::"r"(wstg + t * 512 + i * 128 + g * 16), "l"(ws1 + i * 8 * 224) : "memory"); }
    else if (i == 4 || t < 3) asm volatile("cp.async.cg.shared.global [%0], [%1], 16;" ::"r"(wstg + i * 512 + t * 128 + g * 16), "l"(ws2 + 4 * (i - 4)) : "memory");
  };
#pragma unroll
  for (int i = 0; i < 3; i++) if (i < 2 || t128 < A_W5 / 16 - 256) sts128(cb + (i * 128 + t128) * 16, 0, 0, 0, 0);
  {
    float s = 0.f, q = 0.f;
#pragma unroll
    for (int i = 0; i < 4; i++) {
      const float a = bf_lo(xr[i].x), b = bf_hi(xr[i].x), c = bf_lo(xr[i].y), d = bf_hi(xr[i].y);
      s += (a + b) + (c + d);
      q = fmaf(a, a, q); q = fmaf(b, b, q); q = fmaf(c, c, q); q = fmaf(d, d, q);
    }
#pragma unroll
    for (int o = 16; o; o >>= 1) { s += __shfl_xor_sync(~0u, s, o); q += __shfl_xor_sync(~0u, q, o); }
    const float mean = s * (1.f / DM);
    const float var = fmaxf(fmaf(-mean, mean, q * (1.f / DM)), 0.f);
    const float rs = ln_rstd(var);
    const uint32_t mm = pack_bf16(mean, mean);
    const uint32_t tu = sb + A_REC + (warp >> 3) * A_CH + (warp & 7) * 912 + lane * 8, tx = tu + 2 * A_CH;
#pragma unroll
    for (int i = 0; i < 4; i++) {
      if (i < 3 || lane < 16) {
        const uint32_t d0 = hsub2_bf(xr[i].x, mm), d1 = hsub2_bf(xr[i].y, mm);
        sts64(tu + i * 256, pack_bf16(bf_lo(d0) * rs, bf_hi(d0) * rs), pack_bf16(bf_lo(d1) * rs, bf_hi(d1) * rs));
        sts64(tx + i * 256, xr[i].x, xr[i].y);
      }
    }
  }
  if (tid == 0) sts32(ep_addr, (cnt0 >> 7) + 1u);
  if (tid == 480) {
    asm volatile("cp.async.bulk.prefetch.L2.global [%0], 12544;" ::"l"(wgate + blk * 784) : "memory");
    asm volatile("cp.async.bulk.prefetch.L2.global [%0], 12544;" ::"l"(wup + blk * 784) : "memory");
    asm volatile("cp.async.bulk.prefetch.L2.global [%0], 12544;" ::"l"(wdown + blk * 784) : "memory");
  }
  if (tid == 320) TR(0, 1);
  auto publish_rows = [&]() {
    bar_sync(5, 512);
    uint4* dst = g_ux + ((size_t)(warp * 8 + (lane >> 2)) * 128 + blk) * 4 + ((lane ^ (blk >> 1)) & 3);
#pragma unroll
    for (int i = 0; i < 4; i++) {
      if (i < 3 || warp < 8) {
        uint32_t r[4];
        asm volatile("ldmatrix.sync.aligned.m8n8.x4.trans.shared.b16 {%0,%1,%2,%3}, [%4];" : "=r"(r[0]), "=r"(r[1]), "=r"(r[2]), "=r"(r[3])
                     : "r"(sb + A_REC + (lane >> 3) * A_CH + (lane & 7) * 912 + (warp + 16 * i) * 16) : "memory");
        dst[i * 65536] = make_uint4(r[0], r[1], r[2], r[3]);
      }
    }
    if (warp != 0) asm volatile("bar.arrive 6, 512;" ::: "memory");
  };
  auto release_rows = [&]() {
    if (warp == 0) {
      bar_sync(6, 512);
      if (lane == 0) { asm volatile("red.release.gpu.global.add.u32 [%0], 1;" ::"l"(&g_cnt1) : "memory"); TR(0, 8); }
      __syncwarp();
    }
  };

  if (!conv) {
    publish_rows();
    release_rows();
    const int a = blk - 112, mat = a >> 3, j = a & 7;
    float s[8];
#pragma unroll
    for (int k = 0; k < 8; k++) s[k] = 0.f;
    if (lane < 28) {
      const uint4* src = (mat ? wup : wgate) + j * 28 + lane + (size_t)warp * 224;
#pragma unroll
      for (int hb = 0; hb < 2; hb++) {
        uint4 v[14];
#pragma unroll
        for (int r = 0; r < 14; r++) v[r] = __ldg(src + (size_t)(hb * 14 + r) * 16 * 224);
#pragma unroll
        for (int r = 0; r < 14; r++) {
          s[0] += bf_lo(v[r].x); s[1] += bf_hi(v[r].x); s[2] += bf_lo(v[r].y); s[3] += bf_hi(v[r].y);
          s[4] += bf_lo(v[r].z); s[5] += bf_hi(v[r].z); s[6] += bf_lo(v[r].w); s[7] += bf_hi(v[r].w);
        }
      }
      float4* red = (float4*)(sm + A_STG + warp * 896 + lane * 32);
      red[0] = make_float4(s[0], s[1], s[2], s[3]); red[1] = make_float4(s[4], s[5], s[6], s[7]);
    }
    bar_sync(5, 512);
    if (tid < 224) {
      float t = 0.f;
#pragma unroll
      for (int w = 0; w < 16; w++) t += *(const float*)(sm + A_STG + w * 896 + tid * 4);
      const float hi = rbf(t), mid = rbf(t - hi), lo = rbf(t - hi - mid);
      const int q = tid / 112, n = tid % 112 + 112 * mat;
      __nv_bfloat16* dst = (__nv_bfloat16*)(g_cimg + (j * 2 + q) * 224 + (n >> 3) * 8) + (n & 7);
      dst[0] = __float2bfloat16_rn(hi); dst[8] = __float2bfloat16_rn(mid); dst[16] = __float2bfloat16_rn(lo);
#pragma unroll
      for (int k = 3; k < 8; k++) dst[8 * k] = __float2bfloat16_rn(0.f);
    }
    if (tid == 320) TR(0, 10);
    return;
  }

  const int wr = (wq + wg) & 3;
  const int bk = wr * 32 + lane;
  {
    const uint32_t stg = cb + A_STG + wq * 4352, sw = stg + lane * 8;
    const float dt = rbf(expf(__uint_as_float(ldt << 16)));
    float lr[2], li[2];
    cf bq[2], b0[2], b4[2];
    uint32_t bf[48];
#pragma unroll
    for (int m = 0; m < 2; m++) {
      lr[m] = dt * (m ? bf_hi(prm[0]) : bf_lo(prm[0]));
      li[m] = dt * (m ? bf_hi(prm[1]) : bf_lo(prm[1]));
    }
    {
      cf b[2], z[2];
#pragma unroll
      for (int m = 0; m < 2; m++) {
        cf db, c;
        db.x = dt * (m ? bf_hi(prm[2]) : bf_lo(prm[2])); db.y = -dt * (m ? bf_hi(prm[3]) : bf_lo(prm[3]));
        c.x = m ? bf_hi(prm[4]) : bf_lo(prm[4]); c.y = -(m ? bf_hi(prm[5]) : bf_lo(prm[5]));
        b[m] = cmul(c, db);
        z[m] = cexp_l(lr[m], -li[m], 1.f);
        bq[m] = cexp_l(lr[m], -li[m], 256.f);
      }
      publish_rows();
      {
        const float mx = fmaxf(fmaxf(fabsf(b[0].x), fabsf(b[0].y)), fmaxf(fabsf(b[1].x), fabsf(b[1].y)));
        const uint32_t e = max(__reduce_max_sync(~0u, __float_as_uint(mx)) >> 23, 14u);
        const float sc = __uint_as_float((267u - e) << 23);
        b[0].x *= sc; b[0].y *= sc; b[1].x *= sc; b[1].y *= sc;
        if (lane == 0) sts32(cb + A_SCL + wq * 4, (e - 13u) << 23);
      }
#pragma unroll
      for (int i = 0; i < 8; i++) {
        sts64(sw + i * 272, pack_h(b[0]), pack_h(b[1]));
        if (!(i & 1)) {
          cf e0 = cmul(b[0], bq[0]), e1 = cmul(b[1], bq[1]);
          sts64(sw + (8 + i / 2) * 272, pack_h(e0), pack_h(e1));
          if (i == 0) { b0[0] = e0; b0[1] = e1; }
          if (i == 4) { b4[0] = e0; b4[1] = e1; }
        }
        if (i < 7) { b[0] = cmul(b[0], z[0]); b[1] = cmul(b[1], z[1]); }
        if (i == 5) release_rows();
      }
#pragma unroll
      for (int i = 0; i < 7; i++) {
        b0[0] = cmul(b0[0], bq[0]); b0[1] = cmul(b0[1], bq[1]);
        sts64(sw + (i < 2 ? 12 + 2 * i : i - 2) * 272, pack_h(b0[0]), pack_h(b0[1]));
        if (i < 2) {
          b4[0] = cmul(b4[0], bq[0]); b4[1] = cmul(b4[1], bq[1]);
          sts64(sw + (13 + 2 * i) * 272, pack_h(b4[0]), pack_h(b4[1]));
        }
        if (i == 1) {
          __syncwarp();
#pragma unroll
          for (int n = 0; n < 2; n++)
#pragma unroll
            for (int k2 = 0; k2 < 4; k2++) ldsm4(bf + n * 16 + k2 * 4, stg + (n * 8 + (lane & 7)) * 272 + k2 * 64 + (lane >> 3) * 16);
          __syncwarp();
        }
      }
    }
    uint32_t cv = 0;
    if (tid == 160) asm volatile("ld.relaxed.gpu.global.u32 %0, [%1];" : "=r"(cv) : "l"(&g_cnt1) : "memory");
    {
      const cf p0 = cexp_l(lr[0], li[0], 8.f), p1 = cexp_l(lr[1], li[1], 8.f);
      cf v0 = p0, v1 = p1;
      sts64(sw + 8 * 272, 0x3C00u, 0x3C00u);
#pragma unroll
      for (int i = 1; i < 8; i++) {
        sts64(sw + (8 + i) * 272, pack_h(v0), pack_h(v1));
        v0 = cmul(v0, p0); v1 = cmul(v1, p1);
        if (i < 7) w_copy(i - 1);
      }
      const uint32_t ra = stg + 5 * 272 + (lane >> 2) * 64 + (lane & 1) * 32 + (lane & 2) * 4;
      sts64(ra, pack_h(v0), pack_h(-v0.y, v0.x));
      sts64(ra + 16, pack_h(v1), pack_h(-v1.y, v1.x));
    }
    __syncwarp();
    if (tid == 320) TR(0, 16);
#pragma unroll
    for (int k2 = 0; k2 < 4; k2++) ldsm4(bf + 32 + k2 * 4, stg + (lane & 7) * 272 + k2 * 64 + (lane >> 3) * 16);
    float c[6][4];
#pragma unroll
    for (int i = 0; i < 6; i++) { c[i][0] = 0.f; c[i][1] = 0.f; c[i][2] = 0.f; c[i][3] = 0.f; }
#pragma unroll
    for (int k2 = 0; k2 < 4; k2++) {
      uint32_t a[4];
      ldsm4(a, stg + (8 + (lane & 7)) * 272 + k2 * 64 + (lane >> 3) * 16);
#pragma unroll
      for (int kk = 0; kk < 2; kk++) {
        const int ks = 2 * k2 + kk;
        const uint4 r4 = lds128(stg + 5 * 272 + ks * 64 + t * 16);
        const uint32_t r[4] = {r4.x, r4.z, r4.y, r4.w};
        const uint32_t x0 = a[2 * kk], y0 = a[2 * kk + 1];
        const uint32_t x1 = hcmul(x0, r[0], r[2]), y1 = hcmul(y0, r[1], r[3]);
        const uint32_t x2 = hcmul(x1, r[0], r[2]), y2 = hcmul(y1, r[1], r[3]);
        const uint32_t x3 = hcmul(x2, r[0], r[2]), y3 = hcmul(y2, r[1], r[3]);
#pragma unroll
        for (int n = 0; n < 3; n++) {
          mma16816(c[n * 2], x0, x1, y0, y1, bf[n * 16 + ks * 2], bf[n * 16 + ks * 2 + 1]);
          mma16816(c[n * 2 + 1], x2, x3, y2, y3, bf[n * 16 + ks * 2], bf[n * 16 + ks * 2 + 1]);
        }
      }
      if (k2 == 0 && warp == 5) {
        if (lane == 0) {
          const uint32_t tgt = lds32(ep_addr) * 128u;
          int it = 0;
          while ((int)(cv - tgt) < 0 && ++it < 400000) asm volatile("ld.relaxed.gpu.global.u32 %0, [%1];" : "=r"(cv) : "l"(&g_cnt1) : "memory");
          asm volatile("fence.acquire.gpu;" ::: "memory");
          asm volatile("fence.proxy.async.global;" ::: "memory");
          TR(0, 9);
        }
        __syncwarp();
#pragma unroll
        for (int c2 = 0; c2 < 4; c2++) bulk_ld_elect<8192>(sb + c2 * A_CH + A_REC, g_ux + (size_t)(blk * 4 + c2) * 512, bar_rec);
      }
    }
    asm volatile("cp.async.wait_all;" ::: "memory");
    asm volatile("fence.proxy.async.shared::cta;" ::: "memory");
    __syncwarp();
    if (lane == 0) {
      uint4* img = g_wimg + (size_t)(wjq >> 1) * 37632;
      asm volatile("cp.async.bulk.global.shared::cta.bulk_group [%0], [%1], %2;"
                   ::"l"(img + ((wjq & 1) * 14 + wst) * 896 + ((ch & 1) * 14 + wq * 4) * 32), "r"(wstg), "r"(wq < 3 ? 2048 : 1024) : "memory");
      asm volatile("cp.async.bulk.global.shared::cta.bulk_group [%0], [%1], 896;"
                   ::"l"(img + 25088 + (((ch & 1) * 4 + wq) * 2 + (wjq & 1)) * 784 + wst * 56), "r"(wstg + 2048) : "memory");
      asm volatile("cp.async.bulk.commit_group;" ::: "memory");
    }
#pragma unroll
    for (int i = 0; i < 6; i++)
      sts128(stg + i * 512 + lane * 16, __float_as_uint(c[i][0]), __float_as_uint(c[i][1]), __float_as_uint(c[i][2]), __float_as_uint(c[i][3]));
    if (lane == 0) {
      asm volatile("cp.async.bulk.wait_group.read 0;" ::: "memory");
      mbar_arrive(bar_rec);
    }
  }
  if (tid == 320) TR(0, 2);

  uint32_t xt[8], ud[8];
  {
    mbar_wait(bar_rec, 0);
    if (tid == 320) TR(0, 4);
    uint4 r[4];
#pragma unroll
    for (int i = 0; i < 4; i++) r[i] = lds128(cb + A_REC + bk * 64 + ((i ^ (bk >> 1)) & 3) * 16);
    const uint32_t ua = cb + A_UB + ((2 * bk) & 7) * 656 + ((bk >> 2) + 9) * 16;
    sts128(ua, r[0].x, r[1].x, r[2].x, r[3].x);
    sts128(ua + 656, r[0].y, r[1].y, r[2].y, r[3].y);
    if (wr == 3) {
      if (lane < 31) {
        sts128(cb + A_W5 + lane * 32, 0, 0, 0, 0); sts128(cb + A_W5 + lane * 32 + 16, 0, 0, 0, 0);
        sts128(cb + A_W3 + lane * 32, 0, 0, 0, 0); sts128(cb + A_W3 + lane * 32 + 16, 0, 0, 0, 0);
      } else sts64(cb + A_W3 + 992, 0, 0);
      if (lane < 24) {
#pragma unroll
        for (int i = 0; i < 3; i++) sts128(cb + A_UB + (lane / 3) * 656 + ((lane % 3) * 3 + i) * 16, 0, 0, 0, 0);
      }
    }
    if (bk <= 96) {
      const bool neg = bk == 96;
      const int bp = neg ? -1 : bk;
      uint32_t h[4];
      h[0] = lds32(cb + A_REC + ((bp - 1) & 127) * 64 + ((2 ^ ((bp - 1) >> 1)) & 3) * 16 + 4);
      h[1] = lds32(cb + A_REC + ((bp - 1) & 127) * 64 + ((3 ^ ((bp - 1) >> 1)) & 3) * 16 + 4);
      h[2] = lds32(cb + A_REC + (bp + 1) * 64 + ((0 ^ ((bp + 1) >> 1)) & 3) * 16);
      h[3] = lds32(cb + A_REC + (bp + 1) * 64 + ((1 ^ ((bp + 1) >> 1)) & 3) * 16);
      if (bp <= 0) { h[0] = 0; h[1] = 0; }
      const uint32_t wd[12] = {h[0], h[1], neg ? 0 : r[0].x, neg ? 0 : r[1].x, neg ? 0 : r[2].x, neg ? 0 : r[3].x,
                               neg ? 0 : r[0].y, neg ? 0 : r[1].y, neg ? 0 : r[2].y, neg ? 0 : r[3].y, h[2], h[3]};
      float P[25];
      P[0] = 0.f;
#pragma unroll
      for (int i = 0; i < 12; i++) { P[2 * i + 1] = P[2 * i] + bf_lo(wd[i]); P[2 * i + 2] = P[2 * i + 1] + bf_hi(wd[i]); }
#define WIN(i, hw) (P[(i) + 5 + (hw)] - P[(i) + 4 - (hw)])
#define WPK(i, hw) pack_bf16(WIN(i, hw), WIN((i) + 1, hw))
      const int tp = 2 * bp;
      const uint32_t a3 = cb + A_W3 + (tp + 64) * 16 + 8, a5 = cb + A_W5 + (tp + 64) * 16;
      sts64(a3, WPK(0, 1), WPK(2, 1));
      sts128(a3 + 8, WPK(4, 1), WPK(6, 1), WPK(8, 1), WPK(10, 1));
      sts64(a3 + 24, WPK(12, 1), WPK(14, 1));
      sts128(a5, WPK(0, 2), WPK(2, 2), WPK(4, 2), WPK(6, 2));
      sts128(a5 + 16, WPK(8, 2), WPK(10, 2), WPK(12, 2), WPK(14, 2));
      if (bp < 64) {
        sts128(cb + A_W7 + 1040 + bp * 16, WPK(0, 3), WPK(2, 3), WPK(4, 3), WPK(6, 3));
        sts128(cb + A_W7 + (bp + 1) * 16, WPK(8, 3), WPK(10, 3), WPK(12, 3), WPK(14, 3));
        sts128(cb + A_W9 + (bp + 1) * 16, WPK(0, 4), WPK(2, 4), WPK(4, 4), WPK(6, 4));
        sts128(cb + A_W9 + 1040 + (bp + 1) * 16, WPK(8, 4), WPK(10, 4), WPK(12, 4), WPK(14, 4));
#define VPK(i) pack_bf16(P[(i) + 2] - P[i], P[(i) + 3] - P[(i) + 1])
        sts128(cb + A_V + bp * 32, VPK(0), VPK(2), VPK(4), VPK(6));
        sts128(cb + A_V + bp * 32 + 16, VPK(8), VPK(10), VPK(12), VPK(14));
      }
    }
  }
  asm volatile("fence.proxy.async.shared::cta;" ::: "memory");
  bar_sync(1 + wg, 128);
  if (tid == 320) TR(0, 3);
  {
    const uint4 sc = lds128(cb + A_SCL);
    const float scl[4] = {__uint_as_float(sc.x), __uint_as_float(sc.y), __uint_as_float(sc.z), __uint_as_float(sc.w)};
#pragma unroll
    for (int rep = 0; rep < 2; rep++) {
      const int qd = rep ? 2 + wr : 3 - wr;
      if (rep == 0 || wr >= 2) {
        float s[4] = {0.f, 0.f, 0.f, 0.f};
#pragma unroll
        for (int w = 0; w < 4; w++) {
          uint4 u4 = lds128(cb + A_STG + w * 4352 + qd * 512 + lane * 16);
          s[0] = fmaf(__uint_as_float(u4.x), scl[w], s[0]); s[1] = fmaf(__uint_as_float(u4.y), scl[w], s[1]);
          s[2] = fmaf(__uint_as_float(u4.z), scl[w], s[2]); s[3] = fmaf(__uint_as_float(u4.w), scl[w], s[3]);
        }
#pragma unroll
        for (int hf = 0; hf < 2; hf++) {
          const int j = (qd & 1) * 16 + g + 8 * hf;
          const uint32_t pk = pack_bf16(s[2 * hf + 1], s[2 * hf]);
          const uint32_t v0 = pk >> 16, v1 = pk & 0xFFFFu, v00 = v0 * 0x10001u;
          if (rep == 1) {
            if (t < 2) {
#pragma unroll
              for (int e = 0; e < 2; e++) {
                const int lam = 128 + 32 * (2 * t + e) + j, mu = lam >> 1;
                const uint32_t val = e ? v1 : v0;
                uint32_t a = cb + ((lam & 1) ? A_R3B : A_R3A) + mu * 4;
                if (lam == 128) { a = cb + A_R2A + 128 * 4; sts32(cb + A_K1024, val << 16); }
                sts16(a, val); sts16(a + 6, val);
              }
            } else if (t == 2 && j == 0) { sts16(cb + A_R3A + 128 * 4, v0); }
          } else if (qd < 2) {
            const uint32_t a = cb + A_R1 + (62 + 8 * j + 2 * t) * 4;
            sts16(a, v0); sts32(a + 4, pk); sts16(a + 10, v1);
          } else if (t < 2) {
            const int L = 256 + 8 * j + 4 * t;
            const uint32_t a = cb + A_R1 + (62 + L) * 4;
            if (L > 256) { sts16(a - 4, v0); sts32(a, v00); } else sts16(a, v0);
            sts32(a + 4, v00); sts32(a + 8, pk); sts16(a + 14, v1);
          } else {
            const int mu = 64 + 32 * (t - 2) + j;
            if (mu == 64) {
              const uint32_t a = cb + A_R1 + (62 + 512) * 4;
              sts16(a - 4, v0); sts32(a, v00); sts32(a + 4, v00); sts32(a + 8, v00); sts16(a + 14, v0);
            } else { sts16(cb + A_R2A + mu * 4, v0); sts16(cb + A_R2A + mu * 4 + 6, v0); }
            sts16(cb + A_R2B + mu * 4, v1); sts16(cb + A_R2B + mu * 4 + 6, v1);
          }
        }
      }
    }
  }
  bar_sync(1 + wg, 128);
  if (tid == 320) TR(0, 5);

  {
    const uint32_t cbu = cb;
    const uint32_t blo_k = ((cbu & 0x3FFFF) >> 4) | (41u << 16);
    const uint32_t blo_n = ((cbu & 0x3FFFF) >> 4) | (8u << 16);
    const uint32_t tb = cb + (16 * wq + g - 2 * t) * 4;
    float y1[16], y2[12], y3[8];
    const uint32_t dk16 = __ldg(dskip + ch);
    uint32_t qa[32], qb[32];
    const uint32_t t1 = tb + A_R1 + (62 - 48) * 4;
    load_quads<4>(qa, tb + A_R3A + 17 * 4); load_quads<4>(qa + 16, tb + A_R3B + 16 * 4);
    wg_fence();
    s3_steps<0, 4, A_W9, 1>(y3, qa, blo_n); s3_steps<0, 4, A_W7, 0>(y3, qa + 16, blo_n);
    wg_commit();
    load_quads<8>(qb, tb + A_R2A + 16 * 4);
    wg_fence(); s2_steps<0, 8, A_W5, 1>(y2, qb, blo_n); wg_commit();
    wg_wait<1>(); load_quads<8>(qa, tb + A_R2B + 16 * 4);
    wg_fence(); s2_steps<0, 8, A_W3, 0>(y2, qa, blo_n); wg_commit();
    wg_wait<1>(); load_quads<8>(qb, t1);
    wg_fence(); f1_steps<0, 8>(y1, qb, blo_k); wg_commit();
    wg_wait<1>(); load_quads<8>(qa, t1 + 8 * 64);
    wg_fence(); f1_steps<8, 8>(y1, qa, blo_k); wg_commit();
    reg_fence(y2); reg_fence(y3);
    if (tid == 320) TR(0, 18);
    {
      const float k1024 = __uint_as_float(lds32(cb + A_K1024));
#pragma unroll
      for (int i = 0; i < 2; i++)
#pragma unroll
        for (int hf = 0; hf < 2; hf++) {
          const int idx = 16 * (16 * wq + g + 8 * hf) + 8 * i + 2 * t;
          const uint32_t vv = lds32(cb + A_V + idx * 2);
          sts64(cb + A_Y3 + (idx + 4 * (idx >> 6)) * 4, __float_as_uint(fmaf(k1024, bf_lo(vv), y3[4 * i + 2 * hf])),
                __float_as_uint(fmaf(k1024, bf_hi(vv), y3[4 * i + 2 * hf + 1])));
        }
#pragma unroll
      for (int i = 0; i < 3; i++)
#pragma unroll
        for (int hf = 0; hf < 2; hf++) {
          const int idx = 512 * i + 8 * (16 * wq + g + 8 * hf) + 2 * t;
          sts64(cb + A_Y2 + (idx + 4 * (idx >> 6)) * 4, __float_as_uint(y2[4 * i + 2 * hf]), __float_as_uint(y2[4 * i + 2 * hf + 1]));
        }
    }
    wg_wait<1>(); load_quads<8>(qb, t1 + 16 * 64);
    wg_fence(); f1_steps<16, 8>(y1, qb, blo_k); wg_commit();
    wg_wait<1>(); load_quads<8>(qa, t1 + 24 * 64);
    wg_fence(); f1_steps<24, 8>(y1, qa, blo_k); wg_commit();
    wg_wait<1>(); load_quads<5>(qb, t1 + 32 * 64);
    wg_fence(); f1_steps<32, 5>(y1, qb, blo_k); wg_commit();
    bar_sync(1 + wg, 128);
    float ex[12];
#pragma unroll
    for (int i = 1; i < 4; i++)
#pragma unroll
      for (int k = 0; k < 4; k++) {
        const int aa = 8 * i + 2 * t + (k & 1), b = 16 * wq + g + 8 * (k >> 1);
        float e = __uint_as_float(lds32(cb + A_Y2 + ((aa - 8) * 68 + b) * 4));
        if (i >= 2) e += __uint_as_float(lds32(cb + A_Y3 + ((aa - 16) * 68 + b) * 4));
        ex[4 * (i - 1) + k] = e;
      }
    {
      const uint32_t dk = dk16 * 0x10001u;
#pragma unroll
      for (int i = 0; i < 4; i++) {
        const uint4 r = lds128(cb + A_REC + bk * 64 + ((i ^ (bk >> 1)) & 3) * 16);
        ud[i] = hmul2_bf(r.x, dk); ud[4 + i] = hmul2_bf(r.y, dk); xt[i] = r.z; xt[4 + i] = r.w;
      }
    }
    wg_wait<0>();
    reg_fence(y1);
    if (tid == 320) TR(0, 6);
#pragma unroll
    for (int i = 0; i < 12; i++) y1[4 + i] += ex[i];
#pragma unroll
    for (int i = 0; i < 2; i++) {
      const int mi = lane >> 3, aa = 8 * (2 * i + (mi >> 1)) + (lane & 7);
      asm volatile("stmatrix.sync.aligned.m8n8.x4.trans.shared.b16 [%0], {%1,%2,%3,%4};"
                   ::"r"(cb + A_YB + aa * 128 + (((2 * wq + (mi & 1)) ^ (lane & 7)) << 4)),
                     "r"(pack_bf16(y1[8 * i], y1[8 * i + 1])), "r"(pack_bf16(y1[8 * i + 2], y1[8 * i + 3])),
                     "r"(pack_bf16(y1[8 * i + 4], y1[8 * i + 5])), "r"(pack_bf16(y1[8 * i + 6], y1[8 * i + 7])) : "memory");
    }
  }
  bar_sync(1 + wg, 128);
#pragma unroll
  for (int c = 0; c < 2; c++) {
    const int tau = 2 * bk + c, r = ch & 7;
    const uint4 y = lds128(cb + A_YB + (tau >> 3) * 128 + (((tau ^ (tau >> 3)) & 7) << 4));
    g_himg[(size_t)(tau >> 4) * 7168 + (ch >> 3) * 128 + ((tau >> 3) & 1) * 64 + r * 8 + ((tau & 7) ^ r)] =
        make_uint4(hadd2_bf(xt[4 * c], hadd2_bf(y.x, ud[4 * c])), hadd2_bf(xt[4 * c + 1], hadd2_bf(y.y, ud[4 * c + 1])),
                   hadd2_bf(xt[4 * c + 2], hadd2_bf(y.z, ud[4 * c + 2])), hadd2_bf(xt[4 * c + 3], hadd2_bf(y.w, ud[4 * c + 3])));
  }
  if (lane == 0) asm volatile("cp.async.bulk.wait_group 0;" ::: "memory");
  if (tid == 320) TR(0, 7);
}

constexpr int B_SA = 0, B_RING = 114688, B_SLOT = 14848, B_NSLOT = 7;
constexpr int B_CS = B_RING + B_NSLOT * B_SLOT;
constexpr int B_RED = B_CS + 7168;
constexpr int B_BAR = B_RED + 256;
constexpr int B_SMEM = B_BAR + 1024, A_SMEM = 4 * A_CH + 64;

__device__ __forceinline__ uint32_t mapa(uint32_t a, uint32_t r) { uint32_t o; asm("mapa.shared::cluster.u32 %0, %1, %2;" : "=r"(o) : "r"(a), "r"(r)); return o; }
template <class T> __device__ __forceinline__ T* pin(T* p) { asm volatile("" : "+l"(p)); return p; }
__device__ __forceinline__ uint32_t pin(uint32_t v) { asm volatile("" : "+r"(v)); return v; }
template <int Q, int ST>
__device__ __forceinline__ void g1_stage(float (&acc)[116], uint32_t alo, uint32_t blo, uint32_t bar_full, uint32_t bar_h) {
  constexpr int s = Q * 14 + ST, sl = s % B_NSLOT;
  if (Q == 0) mbar_wait(bar_h + 8 * ST, 0);
  mbar_wait(bar_full + 8 * sl, (s / B_NSLOT) & 1);
  wg_fence();
  if (Q == 0) {
    wgmma_ss232<(2 * ST) * 256, 0x40000080u, (sl * B_SLOT) / 16, 32, ST != 0>(acc, alo, blo);
    wgmma_ss232<(2 * ST + 1) * 256, 0x40000080u, (sl * B_SLOT + 256) / 16, 32, 1>(acc, alo, blo);
  } else {
    wgmma_ss224<(2 * ST) * 256, 0x40000080u, (sl * B_SLOT) / 16, 32, ST != 0>(*(float(*)[112])acc, alo, blo);
    wgmma_ss224<(2 * ST + 1) * 256, 0x40000080u, (sl * B_SLOT + 256) / 16, 32, 1>(*(float(*)[112])acc, alo, blo);
  }
}

__global__ void __launch_bounds__(512, 1)
k_front(const __nv_bfloat16* __restrict__ x, const uint32_t* __restrict__ are, const uint32_t* __restrict__ aim,
        const uint32_t* __restrict__ bre, const uint32_t* __restrict__ bim, const uint32_t* __restrict__ cre,
        const uint32_t* __restrict__ cim, const unsigned short* __restrict__ logdt, const unsigned short* __restrict__ dskip,
        const uint4* __restrict__ wgate, const uint4* __restrict__ wup, const uint4* __restrict__ wdown) {
  extern __shared__ __align__(1024) unsigned char sm[];
  const uint32_t bar_rec = s2u(sm) + 4 * A_CH;
  if (threadIdx.x == 320) TR(0, 0);
  asm volatile("griddepcontrol.launch_dependents;");
  if (threadIdx.x == 160) { mbar_init(bar_rec, 20); asm volatile("fence.mbarrier_init.release.cluster;" ::: "memory"); }
  phase_a(sm, bar_rec, bar_rec + 8, x, are, aim, bre, bim, cre, cim, logdt, dskip, wgate, wup, wdown);
}

__global__ void __cluster_dims__(2, 1, 1) __launch_bounds__(384, 1) k_ffn(__nv_bfloat16* __restrict__ out) {
  extern __shared__ __align__(1024) unsigned char sm[];
  const uint32_t sb = s2u(sm);
  const int tid = threadIdx.x, warp = __shfl_sync(~0u, tid >> 5, 0), wg = warp >> 2, lane = tid & 31;
  const uint32_t bar_full = sb + B_BAR, bar_empty = bar_full + 64, bar_h = bar_full + 128, bar_cs = bar_full + 240,
                 bar_hh = bar_full + 304, bar_afree = bar_full + 336, bar_out = bar_full + 352;
  if (tid == 0) {
    TR(1, 0);
    for (int i = 0; i < B_NSLOT; i++) { mbar_init(bar_full + 8 * i, 1); mbar_init(bar_empty + 8 * i, 2); }
    asm volatile("fence.mbarrier_init.release.cluster;" ::: "memory");
  } else if (tid == 32) {
    for (int i = 0; i < 14; i++) mbar_init(bar_h + 8 * i, 1);
    asm volatile("fence.mbarrier_init.release.cluster;" ::: "memory");
  } else if (tid == 64) {
    mbar_init(bar_cs, 1);
    for (int i = 0; i < 4; i++) { mbar_init(bar_hh + 8 * i, 1); mbar_expect(bar_hh + 8 * i, 14336); }
    mbar_init(bar_afree, 4); mbar_init(bar_afree + 8, 2);
    for (int i = 0; i < 6; i++) mbar_init(bar_out + 8 * i, 128);
    asm volatile("fence.mbarrier_init.release.cluster;" ::: "memory");
  } else if (tid >= 128 && tid < 352) {
    sts128(sb + B_RING + ((tid - 128) >> 5) * B_SLOT + 14336 + (tid & 31) * 16, 0x3F803F80u, 0x3F803F80u, 0x3F803F80u, 0x3F803F80u);
  }
  asm volatile("fence.proxy.async.shared::cta;" ::: "memory");
  __syncthreads();
  asm volatile("barrier.cluster.arrive.relaxed.aligned;" ::: "memory");
  const int rank = blockIdx.x & 1, rt = blockIdx.x >> 3, j = blockIdx.x & 7, p = j >> 1, cg = 4 * rank + p;
  const int wq = warp & 3, t128 = tid & 127, g = lane >> 2, t = lane & 3;
  uint32_t ep, tag;
  auto load_ep = [&]() { asm volatile("ld.relaxed.gpu.global.u32 %0, [%1];" : "=r"(ep) : "l"(&g_cnt1) : "memory"); };
  auto a_slot = [&](int i, int own) { return B_SA + (i + (i >= own)) * 14336; };
  auto out_addr = [&](int cc, int w) { return sb + a_slot((cc & 2) + w, cg) + (cc & 1) * 7168; };
  auto in_cta = [&](int q) { return rt * 8 + ((p + 3 - q) & 3) * 2 + rank; };
  auto in_src = [&](int q, int cw) { return g_part + (size_t)(in_cta(q) * 3 + q) * 896 + cw * 112; };
  auto in_bad = [&](uint32_t (&in)[14]) { return ((in[3] ^ tag) | (in[7] ^ tag) | (in[11] ^ tag) | (in[13] ^ tag)) & 0x10000u; };
  auto in_load = [&](uint32_t (&in)[14], const uint4* gs) {
#pragma unroll
    for (int i = 0; i < 3; i++) ld128(gs + i * 32, in + 4 * i);
    asm volatile("{\n.reg .b64 v;\nld.relaxed.gpu.global.b64 v, [%2];\nmov.b64 {%0, %1}, v;\n}"
                 : "=r"(in[12]), "=r"(in[13]) : "l"((const uint2*)(gs + 96) - lane) : "memory");
  };
  auto in_check = [&](uint32_t (&in)[14], int q, int cw) {
    int it = 0;
    while (in_bad(in) && ++it < 400000) in_load(in, pin(in_src(q, cw) + lane));
  };

  if (wg == 2) {
    asm volatile("setmaxnreg.dec.sync.aligned.u32 40;");
    asm volatile("barrier.cluster.wait.aligned;" ::: "memory");
    asm volatile("griddepcontrol.wait;" ::: "memory");
    if (warp == 8) {
      if (lane == 0) TR(1, 1);
      const char* wsrc = (const char*)g_wimg + (size_t)j * 602112;
      const char* hsrc = (const char*)g_himg + (size_t)rt * 114688 + rank * 4096;
#pragma unroll
      for (int s = 0; s < 28; s++) {
        if (s < B_NSLOT) bulk_ld_mc_elect<4096>(sb + B_SA + s * 8192 + rank * 4096, hsrc + s * 8192, bar_h + 8 * s);
        if (s == B_NSLOT) {
#pragma unroll
          for (int i = 7; i < 14; i++) bulk_ld_mc_elect<4096>(sb + B_SA + i * 8192 + rank * 4096, hsrc + i * 8192, bar_h + 8 * i);
          bulk_ld_elect<7168>(sb + B_CS, g_cimg + j * 448, bar_cs);
        }
        if (s >= B_NSLOT) mbar_wait(bar_empty + 8 * (s % B_NSLOT), (s / B_NSLOT + 1) & 1);
        bulk_ld_elect<14336>(sb + B_RING + (s % B_NSLOT) * B_SLOT, wsrc + s * 14336, bar_full + 8 * (s % B_NSLOT));
      }
      const char* dsrc[2] = {wsrc + 401408 + rank * 100352, (const char*)g_wimg + (size_t)(j ^ 1) * 602112 + 401408 + rank * 100352};
#pragma unroll
      for (int i = 0; i < 16; i++) {
        const int ci = i < 3 ? 0 : i < 6 ? 1 : i < 8 ? i - 6 : i < 12 ? 2 : 3;
        const int kp = i < 3 ? i : i < 6 ? i - 3 : i < 8 ? 3 : (i & 3);
        mbar_wait(bar_empty + 8 * (i % B_NSLOT), (i / B_NSLOT + 1) & 1);
        bulk_ld_elect<12544>(sb + B_RING + (i % B_NSLOT) * B_SLOT, dsrc[kp >> 1] + ((p + 1 + ci) & 3) * 25088 + (kp & 1) * 12544, bar_full + 8 * (i % B_NSLOT));
      }
    } else if (warp >= 10) {
      const int t64 = tid - 320;
      load_ep();
      const int r = (lane >> 1) & 7, c = (j & 3) * 2 + (lane & 1);
      const uint32_t src = sb + B_SA + (t64 >> 4) * 2048 + (j >> 2) * 1024 + r * 128 + ((c ^ r) << 4);
      float a[16];
#pragma unroll
      for (int k = 0; k < 16; k++) a[k] = 0.f;
#pragma unroll 1
      for (int i = 0; i < 14; i++) {
        mbar_wait(bar_h + 8 * i, 0);
        uint4 v = lds128(src + i * 8192);
        float e[8] = {bf_lo(v.x), bf_hi(v.x), bf_lo(v.y), bf_hi(v.y), bf_lo(v.z), bf_hi(v.z), bf_lo(v.w), bf_hi(v.w)};
#pragma unroll
        for (int k = 0; k < 8; k++) { a[2 * k] += e[k]; a[2 * k + 1] = fmaf(e[k], e[k], a[2 * k + 1]); }
        __nanosleep(160);
      }
      __syncwarp();
      if (lane == 0) { asm volatile("mbarrier.arrive.shared::cluster.b64 _, [%0];" ::"r"(mapa(bar_afree, rank ^ 1)) : "memory"); }
#pragma unroll
      for (int rd = 0; rd < 4; rd++) {
        const int n = 8 >> rd;
        const bool up = lane & (2 * n);
#pragma unroll
        for (int k = 0; k < 8; k++) {
          if (k < n) {
            float keep = up ? a[k + n] : a[k], give = up ? a[k] : a[k + n];
            a[k] = keep + __shfl_xor_sync(~0u, give, 2 * n);
          }
        }
      }
      float* red = (float*)(sm + B_RED);
      red[(warp & 1) * 32 + (lane & 1) * 16 + (lane >> 1)] = a[0];
      bar_sync(1, 64);
      if (t64 < 16) {
        float mean = (red[2 * t64] + red[32 + 2 * t64]) * (1.f / DM);
        float var = fmaxf(fmaf(-mean, mean, (red[2 * t64 + 1] + red[33 + 2 * t64]) * (1.f / DM)), 0.f);
        float rs = ln_rstd(var);
        asm volatile("st.relaxed.gpu.global.u32 [%0], %1;"
                     ::"l"(g_stat2 + rt * 128 + j * 16 + t64), "r"((__float_as_uint(rs * rs) & ~1u) | ((ep >> 7) & 1u)) : "memory");
      }
      if (t64 == 0) TR(1, 2);
      if (lane == 0) {
        const int w = warp & 1;
        for (int cc = 0; cc < 2; cc++) {
          mbar_wait(bar_out + 8 * (cc * 2 + w), 0);
          asm volatile("cp.async.bulk.global.shared::cta.bulk_group [%0], [%1], 7168;"
                       ::"l"(g_part + (size_t)(blockIdx.x * 3 + cc) * 896 + w * 448), "r"(out_addr(cc, w)) : "memory");
          if (w) TR(1, 27 + cc);
        }
        asm volatile("cp.async.bulk.commit_group;" ::: "memory");
        asm volatile("cp.async.bulk.wait_group 0;" ::: "memory");
      }
    }
  } else {
    asm volatile("setmaxnreg.inc.sync.aligned.u32 232;");
    asm volatile("barrier.cluster.wait.aligned;" ::: "memory");
    uint32_t hh[56];
    const bool relt = t128 == 0;
    auto release = [&](int sl) { if (relt) mbar_arrive(bar_empty + 8 * sl); };
    auto send_hh = [&](int q) {
      const uint32_t da = mapa(sb + a_slot(2 * q + wg, cg ^ 4) + t128 * 16, rank ^ 1), db = mapa(bar_hh + 8 * (2 * q + wg), rank ^ 1);
#pragma unroll
      for (int i = 0; i < 7; i++)
        asm volatile("st.async.weak.shared::cluster.mbarrier::complete_tx::bytes.v4.b32 [%0], {%1, %2, %3, %4}, [%5];"
                     ::"r"(da + i * 2048), "r"(hh[28 * q + 4 * i]), "r"(hh[28 * q + 4 * i + 1]),
                       "r"(hh[28 * q + 4 * i + 2]), "r"(hh[28 * q + 4 * i + 3]), "r"(db) : "memory");
    };
    uint32_t alo = ((sb + B_SA + wg * 1024) & 0x3FFFF) >> 4;
    uint32_t blo = (((sb + B_RING) & 0x3FFFF) >> 4) | (8u << 16);
    const uint32_t clo = ((sb + B_CS) & 0x3FFFF) >> 4;
    uint32_t nm0, nm1;
    if (wg == 1) bar_sync(3, 256);
#define G1S(Q, ST) do { if (ST % 7 == 0) { alo = pin(alo); blo = pin(blo); }   \
      g1_stage<Q, ST>(acc, alo, blo, bar_full, bar_h); wg_commit(); \
      if (ST > 0) { wg_wait<1>(); release((Q * 14 + ST - 1) % B_NSLOT); } } while (0)
#define G1HH(Q) do { \
      _Pragma("unroll") \
      for (int i = 0; i < 28; i++) hh[28 * Q + i] = pack_bf16(acc[2 * i] * acc[56 + 2 * i], acc[2 * i + 1] * acc[57 + 2 * i]); \
    } while (0)
    {
      float acc[116];
      G1S(0, 0);
      if (tid == 0) TR(1, 3);
      G1S(0, 1);
      if (wg == 0) asm volatile("bar.arrive 3, 256;" ::: "memory");
      G1S(0, 2); G1S(0, 3); G1S(0, 4); G1S(0, 5); G1S(0, 6); G1S(0, 7); G1S(0, 8); G1S(0, 9); G1S(0, 10); G1S(0, 11); G1S(0, 12);
      G1S(0, 13);
      if (tid == 0) TR(1, 4);
      mbar_wait(bar_cs, 0);
      wg_wait<0>(); reg_fence(acc); release(13 % B_NSLOT);
      {
        const uint32_t msk = t == 0 ? 0xFFFFFFFFu : t == 1 ? 0xFFFFu : 0u;
        const float a = acc[112] * (-1.f / DM), b = acc[114] * (-1.f / DM);
        nm0 = pack_bf16(a, a) & msk; nm1 = pack_bf16(b, b) & msk;
      }
      wg_fence();
      wgmma_rs224<0, 8, 1>(*(float(*)[112])acc, nm0, nm1, 0u, 0u, clo);
      wg_commit(); wg_wait<0>(); reg_fence(acc);
      G1HH(0);
      if (tid == 0) TR(1, 5);
      G1S(1, 0); G1S(1, 1); G1S(1, 2); G1S(1, 3); G1S(1, 4); G1S(1, 5); G1S(1, 6);
      if (relt) asm volatile("mbarrier.arrive.shared::cluster.b64 _, [%0];" ::"r"(mapa(bar_afree, rank ^ 1)) : "memory");
      G1S(1, 7); G1S(1, 8); G1S(1, 9);
      if (relt) asm volatile("mbarrier.arrive.shared::cluster.b64 _, [%0];" ::"r"(mapa(bar_afree + 8, rank ^ 1)) : "memory");
      mbar_wait(bar_afree, 0);
      send_hh(0);
      G1S(1, 10); G1S(1, 11); G1S(1, 12);
      load_ep();
      g1_stage<1, 13>(acc, alo, blo, bar_full, bar_h);
      wgmma_rs224<224, 8, 1>(*(float(*)[112])acc, nm0, nm1, 0u, 0u, clo);
      wg_commit(); wg_wait<1>(); release(26 % B_NSLOT);
      wg_wait<0>(); reg_fence(acc); release(27 % B_NSLOT);
      G1HH(1);
      if (tid == 0) TR(1, 6);
    }
    float accA[28], accB[28];
    uint32_t ph0[28], ph1[28];
    ep = pin(ep >> 7); tag = pin((ep & 1u) << 16);
    blo += 48u << 16;
#define ISSUE(acc, I, a, FIRST) do { \
      constexpr int s_ = 28 + (I), sl_ = s_ % B_NSLOT; \
      if (sl_ == 0) blo = pin(blo); \
      mbar_wait(bar_full + 8 * sl_, (s_ / B_NSLOT) & 1); \
      wg_fence(); \
      wgmma_rs56<(sl_ * B_SLOT + 0 * 1792) / 16, 8, !(FIRST)>(acc, (a)[0], (a)[1], (a)[2], (a)[3], blo); \
      wgmma_rs56<(sl_ * B_SLOT + 1 * 1792) / 16, 8, 1>(acc, (a)[4], (a)[5], (a)[6], (a)[7], blo); \
      wgmma_rs56<(sl_ * B_SLOT + 2 * 1792) / 16, 8, 1>(acc, (a)[8], (a)[9], (a)[10], (a)[11], blo); \
      wgmma_rs56<(sl_ * B_SLOT + 3 * 1792) / 16, 8, 1>(acc, (a)[12], (a)[13], (a)[14], (a)[15], blo); \
      wgmma_rs56<(sl_ * B_SLOT + 4 * 1792) / 16, 8, 1>(acc, (a)[16], (a)[17], (a)[18], (a)[19], blo); \
      wgmma_rs56<(sl_ * B_SLOT + 5 * 1792) / 16, 8, 1>(acc, (a)[20], (a)[21], (a)[22], (a)[23], blo); \
      wgmma_rs56<(sl_ * B_SLOT + 6 * 1792) / 16, 8, 1>(acc, (a)[24], (a)[25], (a)[26], (a)[27], blo); \
      wg_commit(); } while (0)
    auto rel = [&](int i) { release((28 + i) % B_NSLOT); };
    auto tg = [&](uint32_t v) { return (v & 0xFFFEFFFFu) | tag; };
    auto send = [&](float (&acc)[28], int cc) {
      reg_fence(acc);
      const uint32_t a = out_addr(cc, wg) + wq * 1792;
#pragma unroll
      for (int q = 0; q < 3; q++)
        sts128(a + q * 512 + lane * 16, pack_bf16(acc[8 * q], acc[8 * q + 1]), pack_bf16(acc[8 * q + 2], acc[8 * q + 3]),
               pack_bf16(acc[8 * q + 4], acc[8 * q + 5]), tg(pack_bf16(acc[8 * q + 6], acc[8 * q + 7])));
      sts64(a + 1536 + lane * 8, pack_bf16(acc[24], acc[25]), tg(pack_bf16(acc[26], acc[27])));
      asm volatile("fence.proxy.async.shared::cta;" ::: "memory");
      mbar_arrive(bar_out + 8 * (cc * 2 + wg));
    };
    auto load_hh = [&](uint32_t (&d)[28], int q) {
      mbar_wait(bar_hh + 8 * (2 * q + wg), 0);
      const uint32_t a = sb + a_slot(2 * q + wg, cg) + t128 * 16;
#pragma unroll
      for (int i = 0; i < 7; i++) {
        const uint4 v = lds128(a + i * 2048);
        d[4 * i] = v.x; d[4 * i + 1] = v.y; d[4 * i + 2] = v.z; d[4 * i + 3] = v.w;
      }
    };
    ISSUE(accA, 0, hh, true);
    mbar_wait(bar_afree + 8, 0);
    send_hh(1);
    ISSUE(accA, 1, hh + 28, false);
    load_hh(ph0, 0);
    wg_wait<1>(); rel(0);
    ISSUE(accA, 2, ph0, false);      wg_wait<1>(); rel(1);
    ISSUE(accB, 3, hh, true);        wg_wait<1>(); rel(2);
    ISSUE(accB, 4, hh + 28, false);  wg_wait<1>(); rel(3);
    ISSUE(accB, 5, ph0, false);
    if (tid == 0) TR(1, 11);
    load_hh(ph1, 1);
    wg_wait<1>(); rel(4);
    ISSUE(accA, 6, ph1, false);      wg_wait<1>(); rel(5);
    ISSUE(accB, 7, ph1, false);      wg_wait<1>(); rel(6); send(accA, 0);
    ISSUE(accA, 8, hh, true);        wg_wait<1>(); rel(7); send(accB, 1);
    if (tid == 0) TR(1, 13);
    ISSUE(accA, 9, hh + 28, false);  wg_wait<1>(); rel(8);
    ISSUE(accA, 10, ph0, false);
    ISSUE(accA, 11, ph1, false);
    const int row = rt * 128 + wg * 64 + wq * 16 + g;
    uint32_t r20, r21;
    asm volatile("ld.relaxed.gpu.global.u32 %0, [%1];" : "=r"(r20) : "l"(g_stat2 + row) : "memory");
    asm volatile("ld.relaxed.gpu.global.u32 %0, [%1];" : "=r"(r21) : "l"(g_stat2 + row + 8) : "memory");
    ISSUE(accB, 12, hh, true);
    wg_wait<1>();
    {
      reg_fence(accA);
      uint4* pd = g_part + (size_t)(blockIdx.x * 3 + 2) * 896 + warp * 112 + lane;
#pragma unroll
      for (int q = 0; q < 3; q++)
        st128(pd + q * 32, pack_bf16(accA[8 * q], accA[8 * q + 1]), pack_bf16(accA[8 * q + 2], accA[8 * q + 3]),
              pack_bf16(accA[8 * q + 4], accA[8 * q + 5]), tg(pack_bf16(accA[8 * q + 6], accA[8 * q + 7])));
      asm volatile("{\n.reg .b64 v;\nmov.b64 v, {%1, %2};\nst.relaxed.gpu.global.b64 [%0], v;\n}"
                   ::"l"((uint2*)(pd + 96) - lane), "r"(pack_bf16(accA[24], accA[25])), "r"(tg(pack_bf16(accA[26], accA[27]))) : "memory");
    }
    if (tid == 0) TR(1, 16);
    ISSUE(accB, 13, hh + 28, false);
    ISSUE(accB, 14, ph0, false);
    uint32_t in0[14], in1[14], in2[14];
    in_load(in0, in_src(0, warp) + lane);
    in_load(in1, in_src(1, warp) + lane);
    ISSUE(accB, 15, ph1, false);
    if (tid == 0) TR(1, 7);
    {
      int it = 0;
      while ((((r20 ^ ep) | (r21 ^ ep)) & 1u) && ++it < 400000) {
        asm volatile("ld.relaxed.gpu.global.u32 %0, [%1];" : "=r"(r20) : "l"(g_stat2 + row) : "memory");
        asm volatile("ld.relaxed.gpu.global.u32 %0, [%1];" : "=r"(r21) : "l"(g_stat2 + row + 8) : "memory");
      }
    }
    wg_wait<1>();
    in_load(in2, in_src(2, warp) + lane);
    in_check(in0, 0, warp); in_check(in1, 1, warp);
#pragma unroll
    for (int i = 0; i < 14; i++) { accA[2 * i] = bf_lo(in0[i]) + bf_lo(in1[i]); accA[2 * i + 1] = bf_hi(in0[i]) + bf_hi(in1[i]); }
    if (tid == 0) TR(1, 12);
    wg_wait<0>();
    reg_fence(accB);
    uint32_t hres[16];
#pragma unroll
    for (int i = 0; i < 4; i++) {
      int qq = lane >> 3, r = lane & 7, kg = 7 * cg + 2 * i + (qq >> 1), c = 2 * wq + (qq & 1);
      if (kg > 55) kg = 55;
      asm volatile("ldmatrix.sync.aligned.m8n8.x4.trans.shared.b16 {%0,%1,%2,%3}, [%4];"
                   : "=r"(hres[4 * i]), "=r"(hres[4 * i + 1]), "=r"(hres[4 * i + 2]), "=r"(hres[4 * i + 3])
                   : "r"(sb + B_SA + kg * 2048 + wg * 1024 + r * 128 + ((c ^ r) << 4)) : "memory");
    }
#pragma unroll
    for (int i = 0; i < 28; i++) accB[i] += accA[i];
    if (tid == 0) TR(1, 9);
    in_check(in2, 2, warp);
#pragma unroll
    for (int i = 0; i < 14; i++) { accB[2 * i] += bf_lo(in2[i]); accB[2 * i + 1] += bf_hi(in2[i]); }
    uint32_t* o0 = (uint32_t*)(out + (size_t)row * DM + 56 * cg + 2 * t);
    uint32_t* o1 = o0 + 8 * DM / 2;
#pragma unroll
    for (int i = 0; i < 7; i++) {
      o0[4 * i] = hadd2_bf(hres[2 * i], pack_bf16(accB[4 * i] * __uint_as_float(r20), accB[4 * i + 1] * __uint_as_float(r20)));
      o1[4 * i] = hadd2_bf(hres[2 * i + 1], pack_bf16(accB[4 * i + 2] * __uint_as_float(r21), accB[4 * i + 3] * __uint_as_float(r21)));
    }
    if (tid == 0) TR(1, 10);
    if (tid == 128) TR(1, 15);
  }
}

extern "C" void kernel_launch(void* const* d_in, const int* in_sizes, int n_in, void* d_out, int out_size) {
  const __nv_bfloat16* x = (const __nv_bfloat16*)d_in[0];
  const __nv_bfloat16 *are = (const __nv_bfloat16*)d_in[1], *aim = (const __nv_bfloat16*)d_in[2], *bre = (const __nv_bfloat16*)d_in[3],
                      *bim = (const __nv_bfloat16*)d_in[4], *cre = (const __nv_bfloat16*)d_in[5], *cim = (const __nv_bfloat16*)d_in[6],
                      *logdt = (const __nv_bfloat16*)d_in[7], *dskip = (const __nv_bfloat16*)d_in[8];
  const __nv_bfloat16 *wg = (const __nv_bfloat16*)d_in[10], *wu = (const __nv_bfloat16*)d_in[11], *wd = (const __nv_bfloat16*)d_in[12];

  static bool init = false;
  if (!init) {
    init = true;
    cudaFuncSetAttribute(k_ffn, cudaFuncAttributeMaxDynamicSharedMemorySize, B_SMEM);
    cudaFuncSetAttribute(k_front, cudaFuncAttributeMaxDynamicSharedMemorySize, A_SMEM);
  }
  cudaStream_t st = cudaStreamPerThread;
  k_front<<<128, 512, A_SMEM, st>>>(
      x, (const uint32_t*)are, (const uint32_t*)aim, (const uint32_t*)bre, (const uint32_t*)bim, (const uint32_t*)cre, (const uint32_t*)cim,
      (const unsigned short*)logdt, (const unsigned short*)dskip, (const uint4*)wg, (const uint4*)wu, (const uint4*)wd);
  cudaLaunchConfig_t cfg = {};
  cfg.gridDim = dim3(128); cfg.blockDim = dim3(384); cfg.dynamicSmemBytes = B_SMEM; cfg.stream = st;
  cudaLaunchAttribute at[1];
  at[0].id = cudaLaunchAttributeProgrammaticStreamSerialization; at[0].val.programmaticStreamSerializationAllowed = 1;
  cfg.attrs = at; cfg.numAttrs = 1;
  cudaLaunchKernelEx(&cfg, k_ffn, (__nv_bfloat16*)d_out);
}
```

```cpp
#include <cuda_runtime.h>
#include <cuda_bf16.h>
#include <cuda_fp16.h>
#include <stdint.h>

constexpr int LSEQ = 2048, DM = 448;

__device__ uint4    g_himg[16 * 114688 / 16];
__device__ uint4    g_cimg[8 * 2 * 224];
__device__ uint32_t g_stat2[LSEQ];
__device__ uint4    g_part[128 * 3 * 896];
__device__ uint4    g_wimg[8 * 602112 / 16];
__device__ uint4    g_ux[DM * 128 * 4];
__device__ unsigned g_cnt1;

#define TR(k, i) do {} while (0)
__device__ __forceinline__ uint32_t s2u(const void* p) { return (uint32_t)__cvta_generic_to_shared(p); }
__device__ __forceinline__ void mbar_init(uint32_t b, int c) { asm volatile("mbarrier.init.shared::cta.b64 [%0], %1;" ::"r"(b), "r"(c)); }
__device__ __forceinline__ void mbar_expect(uint32_t b, int bytes) { asm volatile("mbarrier.arrive.expect_tx.shared::cta.b64 _, [%0], %1;" ::"r"(b), "r"(bytes) : "memory"); }
__device__ __forceinline__ void mbar_arrive(uint32_t b) { asm volatile("mbarrier.arrive.shared::cta.b64 _, [%0];" ::"r"(b) : "memory"); }
__device__ __forceinline__ void mbar_wait(uint32_t b, int ph) {
  asm volatile("{\n.reg .pred p;\n.reg .b32 n;\nmov.b32 n, 0;\nLW:\nmbarrier.try_wait.parity.shared::cta.b64 p, [%0], %1;\n@p bra LD;\n"
               "add.u32 n, n, 1;\nsetp.lt.u32 p, n, 4000000;\n@p bra LW;\ntrap;\nLD:\n}" ::"r"(b), "r"(ph) : "memory");
}
__device__ __forceinline__ bool mbar_test(uint32_t b, int ph) {
  uint32_t ok;
  asm volatile("{\n.reg .pred p;\nmbarrier.test_wait.parity.shared::cta.b64 p, [%1], %2;\nselp.u32 %0, 1, 0, p;\n}" : "=r"(ok) : "r"(b), "r"(ph) : "memory");
  return ok;
}
__device__ __forceinline__ void wg_fence() { asm volatile("wgmma.fence.sync.aligned;" ::: "memory"); }
__device__ __forceinline__ void wg_commit() { asm volatile("wgmma.commit_group.sync.aligned;" ::: "memory"); }
template <int N> __device__ __forceinline__ void wg_wait() { asm volatile("wgmma.wait_group.sync.aligned %0;" ::"n"(N) : "memory"); }
template <int N> __device__ __forceinline__ void reg_fence(float (&a)[N]) {
#pragma unroll
  for (int i = 0; i < N; i++) asm volatile("" : "+f"(a[i])::"memory");
}
__device__ __forceinline__ uint32_t pack_bf16(float lo, float hi) {
  uint32_t r; asm("cvt.rn.bf16x2.f32 %0, %1, %2;" : "=r"(r) : "f"(hi), "f"(lo)); return r;
}
__device__ __forceinline__ float bf_lo(uint32_t v) { return __uint_as_float(v << 16); }
__device__ __forceinline__ float bf_hi(uint32_t v) { return __uint_as_float(v & 0xFFFF0000u); }
__device__ __forceinline__ float rbf(float x) { return __bfloat162float(__float2bfloat16_rn(x)); }
__device__ __forceinline__ uint32_t hmul2_bf(uint32_t a, uint32_t b) { uint32_t r; asm("mul.rn.bf16x2 %0, %1, %2;" : "=r"(r) : "r"(a), "r"(b)); return r; }
__device__ __forceinline__ uint32_t hadd2_bf(uint32_t a, uint32_t b) { uint32_t r; asm("add.rn.bf16x2 %0, %1, %2;" : "=r"(r) : "r"(a), "r"(b)); return r; }
__device__ __forceinline__ void bulk_ld(uint32_t dst, const void* src, int bytes, uint32_t bar) {
  asm volatile("cp.async.bulk.shared::cluster.global.mbarrier::complete_tx::bytes [%0], [%1], %2, [%3];"
               ::"r"(dst), "l"(src), "r"(bytes), "r"(bar) : "memory");
}

template <int BYTES>
__device__ __forceinline__ void bulk_ld_elect(uint32_t dst, const void* src, uint32_t bar) {
  asm volatile("{\n.reg .pred p;\nelect.sync _|p, 0xffffffff;\n"
               "@p mbarrier.arrive.expect_tx.shared::cta.b64 _, [%2], %3;\n"
               "@p cp.async.bulk.shared::cluster.global.mbarrier::complete_tx::bytes [%0], [%1], %3, [%2];\n}"
               ::"r"(dst), "l"(src), "r"(bar), "n"(BYTES) : "memory");
}
template <int BYTES>
__device__ __forceinline__ void bulk_ld_mc_elect(uint32_t dst, const void* src, uint32_t bar) {
  asm volatile("{\n.reg .pred p;\nelect.sync _|p, 0xffffffff;\n"
               "@p mbarrier.arrive.expect_tx.shared::cta.b64 _, [%2], %3;\n"
               "@p cp.async.bulk.shared::cluster.global.mbarrier::complete_tx::bytes.multicast::cluster [%0], [%1], %4, [%2], %5;\n}"
               ::"r"(dst), "l"(src), "r"(bar), "n"(2 * BYTES), "n"(BYTES), "h"((uint16_t)3) : "memory");
}
template <int AOFF, uint32_t AHI, int BOFF, uint32_t BHI, int ACC>
__device__ __forceinline__ void wgmma_ss224(float (&d)[112], uint32_t alo, uint32_t blo) {
  asm volatile("{\n.reg .pred p;\n.reg .b64 ad, bd;\nsetp.ne.b32 p, %118, 0;\n"
    "mov.b64 ad, {%112, %115};\nadd.s64 ad, ad, %114;\nmov.b64 bd, {%113, %117};\nadd.s64 bd, bd, %116;\n"
    "wgmma.mma_async.sync.aligned.m64n224k16.f32.bf16.bf16 {%0,%1,%2,%3,%4,%5,%6,%7,%8,%9,%10,%11,%12,%13,%14,%15,%16,%17,%18,%19,%20,%21,%22,%23,%24,%25,%26,%27,%28,%29,%30,%31,%32,%33,%34,%35,%36,%37,%38,%39,%40,%41,%42,%43,%44,%45,%46,%47,%48,%49,%50,%51,%52,%53,%54,%55,%56,%57,%58,%59,%60,%61,%62,%63,%64,%65,%66,%67,%68,%69,%70,%71,%72,%73,%74,%75,%76,%77,%78,%79,%80,%81,%82,%83,%84,%85,%86,%87,%88,%89,%90,%91,%92,%93,%94,%95,%96,%97,%98,%99,%100,%101,%102,%103,%104,%105,%106,%107,%108,%109,%110,%111}, ad, bd, p, 1, 1, 1, 1;\n}\n"
    : "+f"(d[0]),"+f"(d[1]),"+f"(d[2]),"+f"(d[3]),"+f"(d[4]),"+f"(d[5]),"+f"(d[6]),"+f"(d[7]),"+f"(d[8]),"+f"(d[9]),"+f"(d[10]),"+f"(d[11]),"+f"(d[12]),"+f"(d[13]),"+f"(d[14]),"+f"(d[15]),"+f"(d[16]),"+f"(d[17]),"+f"(d[18]),"+f"(d[19]),"+f"(d[20]),"+f"(d[21]),"+f"(d[22]),"+f"(d[23]),"+f"(d[24]),"+f"(d[25]),"+f"(d[26]),"+f"(d[27]),"+f"(d[28]),"+f"(d[29]),"+f"(d[30]),"+f"(d[31]),"+f"(d[32]),"+f"(d[33]),"+f"(d[34]),"+f"(d[35]),"+f"(d[36]),"+f"(d[37]),"+f"(d[38]),"+f"(d[39]),"+f"(d[40]),"+f"(d[41]),"+f"(d[42]),"+f"(d[43]),"+f"(d[44]),"+f"(d[45]),"+f"(d[46]),"+f"(d[47]),"+f"(d[48]),"+f"(d[49]),"+f"(d[50]),"+f"(d[51]),"+f"(d[52]),"+f"(d[53]),"+f"(d[54]),"+f"(d[55]),"+f"(d[56]),"+f"(d[57]),"+f"(d[58]),"+f"(d[59]),"+f"(d[60]),"+f"(d[61]),"+f"(d[62]),"+f"(d[63]),"+f"(d[64]),"+f"(d[65]),"+f"(d[66]),"+f"(d[67]),"+f"(d[68]),"+f"(d[69]),"+f"(d[70]),"+f"(d[71]),"+f"(d[72]),"+f"(d[73]),"+f"(d[74]),"+f"(d[75]),"+f"(d[76]),"+f"(d[77]),"+f"(d[78]),"+f"(d[79]),"+f"(d[80]),"+f"(d[81]),"+f"(d[82]),"+f"(d[83]),"+f"(d[84]),"+f"(d[85]),"+f"(d[86]),"+f"(d[87]),"+f"(d[88]),"+f"(d[89]),"+f"(d[90]),"+f"(d[91]),"+f"(d[92]),"+f"(d[93]),"+f"(d[94]),"+f"(d[95]),"+f"(d[96]),"+f"(d[97]),"+f"(d[98]),"+f"(d[99]),"+f"(d[100]),"+f"(d[101]),"+f"(d[102]),"+f"(d[103]),"+f"(d[104]),"+f"(d[105]),"+f"(d[106]),"+f"(d[107]),"+f"(d[108]),"+f"(d[109]),"+f"(d[110]),"+f"(d[111])
    : "r"(alo), "r"(blo), "n"(AOFF), "n"(AHI), "n"(BOFF), "n"(BHI), "n"(ACC));
}
template <int AOFF, uint32_t AHI, int BOFF, uint32_t BHI, int ACC>
__device__ __forceinline__ void wgmma_ss232(float (&d)[116], uint32_t alo, uint32_t blo) {
  asm volatile("{\n.reg .pred p;\n.reg .b64 ad, bd;\nsetp.ne.b32 p, %122, 0;\n"
    "mov.b64 ad, {%116, %119};\nadd.s64 ad, ad, %118;\nmov.b64 bd, {%117, %121};\nadd.s64 bd, bd, %120;\n"
    "wgmma.mma_async.sync.aligned.m64n232k16.f32.bf16.bf16 {%0,%1,%2,%3,%4,%5,%6,%7,%8,%9,%10,%11,%12,%13,%14,%15,%16,%17,%18,%19,%20,%21,%22,%23,%24,%25,%26,%27,%28,%29,%30,%31,%32,%33,%34,%35,%36,%37,%38,%39,%40,%41,%42,%43,%44,%45,%46,%47,%48,%49,%50,%51,%52,%53,%54,%55,%56,%57,%58,%59,%60,%61,%62,%63,%64,%65,%66,%67,%68,%69,%70,%71,%72,%73,%74,%75,%76,%77,%78,%79,%80,%81,%82,%83,%84,%85,%86,%87,%88,%89,%90,%91,%92,%93,%94,%95,%96,%97,%98,%99,%100,%101,%102,%103,%104,%105,%106,%107,%108,%109,%110,%111,%112,%113,%114,%115}, ad, bd, p, 1, 1, 1, 1;\n}\n"
    : "+f"(d[0]),"+f"(d[1]),"+f"(d[2]),"+f"(d[3]),"+f"(d[4]),"+f"(d[5]),"+f"(d[6]),"+f"(d[7]),"+f"(d[8]),"+f"(d[9]),"+f"(d[10]),"+f"(d[11]),"+f"(d[12]),"+f"(d[13]),"+f"(d[14]),"+f"(d[15]),"+f"(d[16]),"+f"(d[17]),"+f"(d[18]),"+f"(d[19]),"+f"(d[20]),"+f"(d[21]),"+f"(d[22]),"+f"(d[23]),"+f"(d[24]),"+f"(d[25]),"+f"(d[26]),"+f"(d[27]),"+f"(d[28]),"+f"(d[29]),"+f"(d[30]),"+f"(d[31]),"+f"(d[32]),"+f"(d[33]),"+f"(d[34]),"+f"(d[35]),"+f"(d[36]),"+f"(d[37]),"+f"(d[38]),"+f"(d[39]),"+f"(d[40]),"+f"(d[41]),"+f"(d[42]),"+f"(d[43]),"+f"(d[44]),"+f"(d[45]),"+f"(d[46]),"+f"(d[47]),"+f"(d[48]),"+f"(d[49]),"+f"(d[50]),"+f"(d[51]),"+f"(d[52]),"+f"(d[53]),"+f"(d[54]),"+f"(d[55]),"+f"(d[56]),"+f"(d[57]),"+f"(d[58]),"+f"(d[59]),"+f"(d[60]),"+f"(d[61]),"+f"(d[62]),"+f"(d[63]),"+f"(d[64]),"+f"(d[65]),"+f"(d[66]),"+f"(d[67]),"+f"(d[68]),"+f"(d[69]),"+f"(d[70]),"+f"(d[71]),"+f"(d[72]),"+f"(d[73]),"+f"(d[74]),"+f"(d[75]),"+f"(d[76]),"+f"(d[77]),"+f"(d[78]),"+f"(d[79]),"+f"(d[80]),"+f"(d[81]),"+f"(d[82]),"+f"(d[83]),"+f"(d[84]),"+f"(d[85]),"+f"(d[86]),"+f"(d[87]),"+f"(d[88]),"+f"(d[89]),"+f"(d[90]),"+f"(d[91]),"+f"(d[92]),"+f"(d[93]),"+f"(d[94]),"+f"(d[95]),"+f"(d[96]),"+f"(d[97]),"+f"(d[98]),"+f"(d[99]),"+f"(d[100]),"+f"(d[101]),"+f"(d[102]),"+f"(d[103]),"+f"(d[104]),"+f"(d[105]),"+f"(d[106]),"+f"(d[107]),"+f"(d[108]),"+f"(d[109]),"+f"(d[110]),"+f"(d[111]),"+f"(d[112]),"+f"(d[113]),"+f"(d[114]),"+f"(d[115])
    : "r"(alo), "r"(blo), "n"(AOFF), "n"(AHI), "n"(BOFF), "n"(BHI), "n"(ACC));
}
template <int OFF, uint32_t BHI, int ACC>
__device__ __forceinline__ void wgmma_rs224(float (&d)[112], uint32_t a0, uint32_t a1, uint32_t a2, uint32_t a3, uint32_t blo) {
  asm volatile("{\n.reg .pred p;\n.reg .b64 bd;\nsetp.ne.b32 p, %119, 0;\nmov.b64 bd, {%116, %118};\nadd.s64 bd, bd, %117;\n"
    "wgmma.mma_async.sync.aligned.m64n224k16.f32.bf16.bf16 {%0,%1,%2,%3,%4,%5,%6,%7,%8,%9,%10,%11,%12,%13,%14,%15,%16,%17,%18,%19,%20,%21,%22,%23,%24,%25,%26,%27,%28,%29,%30,%31,%32,%33,%34,%35,%36,%37,%38,%39,%40,%41,%42,%43,%44,%45,%46,%47,%48,%49,%50,%51,%52,%53,%54,%55,%56,%57,%58,%59,%60,%61,%62,%63,%64,%65,%66,%67,%68,%69,%70,%71,%72,%73,%74,%75,%76,%77,%78,%79,%80,%81,%82,%83,%84,%85,%86,%87,%88,%89,%90,%91,%92,%93,%94,%95,%96,%97,%98,%99,%100,%101,%102,%103,%104,%105,%106,%107,%108,%109,%110,%111}, {%112,%113,%114,%115}, bd, p, 1, 1, 1;\n}\n"
    : "+f"(d[0]),"+f"(d[1]),"+f"(d[2]),"+f"(d[3]),"+f"(d[4]),"+f"(d[5]),"+f"(d[6]),"+f"(d[7]),"+f"(d[8]),"+f"(d[9]),"+f"(d[10]),"+f"(d[11]),"+f"(d[12]),"+f"(d[13]),"+f"(d[14]),"+f"(d[15]),"+f"(d[16]),"+f"(d[17]),"+f"(d[18]),"+f"(d[19]),"+f"(d[20]),"+f"(d[21]),"+f"(d[22]),"+f"(d[23]),"+f"(d[24]),"+f"(d[25]),"+f"(d[26]),"+f"(d[27]),"+f"(d[28]),"+f"(d[29]),"+f"(d[30]),"+f"(d[31]),"+f"(d[32]),"+f"(d[33]),"+f"(d[34]),"+f"(d[35]),"+f"(d[36]),"+f"(d[37]),"+f"(d[38]),"+f"(d[39]),"+f"(d[40]),"+f"(d[41]),"+f"(d[42]),"+f"(d[43]),"+f"(d[44]),"+f"(d[45]),"+f"(d[46]),"+f"(d[47]),"+f"(d[48]),"+f"(d[49]),"+f"(d[50]),"+f"(d[51]),"+f"(d[52]),"+f"(d[53]),"+f"(d[54]),"+f"(d[55]),"+f"(d[56]),"+f"(d[57]),"+f"(d[58]),"+f"(d[59]),"+f"(d[60]),"+f"(d[61]),"+f"(d[62]),"+f"(d[63]),"+f"(d[64]),"+f"(d[65]),"+f"(d[66]),"+f"(d[67]),"+f"(d[68]),"+f"(d[69]),"+f"(d[70]),"+f"(d[71]),"+f"(d[72]),"+f"(d[73]),"+f"(d[74]),"+f"(d[75]),"+f"(d[76]),"+f"(d[77]),"+f"(d[78]),"+f"(d[79]),"+f"(d[80]),"+f"(d[81]),"+f"(d[82]),"+f"(d[83]),"+f"(d[84]),"+f"(d[85]),"+f"(d[86]),"+f"(d[87]),"+f"(d[88]),"+f"(d[89]),"+f"(d[90]),"+f"(d[91]),"+f"(d[92]),"+f"(d[93]),"+f"(d[94]),"+f"(d[95]),"+f"(d[96]),"+f"(d[97]),"+f"(d[98]),"+f"(d[99]),"+f"(d[100]),"+f"(d[101]),"+f"(d[102]),"+f"(d[103]),"+f"(d[104]),"+f"(d[105]),"+f"(d[106]),"+f"(d[107]),"+f"(d[108]),"+f"(d[109]),"+f"(d[110]),"+f"(d[111])
    : "r"(a0), "r"(a1), "r"(a2), "r"(a3), "r"(blo), "n"(OFF), "n"(BHI), "n"(ACC));
}
template <int OFF, uint32_t BHI, int ACC>
__device__ __forceinline__ void wgmma_rs56(float (&d)[28], uint32_t a0, uint32_t a1, uint32_t a2, uint32_t a3, uint32_t blo) {
  asm volatile("{\n.reg .pred p;\n.reg .b64 bd;\nsetp.ne.b32 p, %35, 0;\nmov.b64 bd, {%32, %34};\nadd.s64 bd, bd, %33;\n"
    "wgmma.mma_async.sync.aligned.m64n56k16.f32.bf16.bf16 {%0,%1,%2,%3,%4,%5,%6,%7,%8,%9,%10,%11,%12,%13,%14,%15,%16,%17,%18,%19,%20,%21,%22,%23,%24,%25,%26,%27}, {%28,%29,%30,%31}, bd, p, 1, 1, 1;\n}\n"
    : "+f"(d[0]),"+f"(d[1]),"+f"(d[2]),"+f"(d[3]),"+f"(d[4]),"+f"(d[5]),"+f"(d[6]),"+f"(d[7]),"+f"(d[8]),"+f"(d[9]),"+f"(d[10]),"+f"(d[11]),"+f"(d[12]),"+f"(d[13]),"+f"(d[14]),"+f"(d[15]),"+f"(d[16]),"+f"(d[17]),"+f"(d[18]),"+f"(d[19]),"+f"(d[20]),"+f"(d[21]),"+f"(d[22]),"+f"(d[23]),"+f"(d[24]),"+f"(d[25]),"+f"(d[26]),"+f"(d[27])
    : "r"(a0), "r"(a1), "r"(a2), "r"(a3), "r"(blo), "n"(OFF), "n"(BHI), "n"(ACC));
}

__device__ __forceinline__ void st128(uint4* p, uint32_t a, uint32_t b, uint32_t c, uint32_t d) {
  asm volatile("{\n.reg .b128 v;\n.reg .b64 lo, hi;\nmov.b64 lo, {%1, %2};\nmov.b64 hi, {%3, %4};\nmov.b128 v, {lo, hi};\n"
               "st.relaxed.gpu.global.b128 [%0], v;\n}" ::"l"(p), "r"(a), "r"(b), "r"(c), "r"(d) : "memory");
}
__device__ __forceinline__ void ld128(const uint4* p, uint32_t* r) {
  asm volatile("{\n.reg .b128 v;\n.reg .b64 lo, hi;\nld.relaxed.gpu.global.b128 v, [%4];\nmov.b128 {lo, hi}, v;\n"
               "mov.b64 {%0, %1}, lo;\nmov.b64 {%2, %3}, hi;\n}" : "=r"(r[0]), "=r"(r[1]), "=r"(r[2]), "=r"(r[3]) : "l"(p) : "memory");
}

template <int OFF, uint32_t BHI, int ACC>
__device__ __forceinline__ void wgmma_rs32(float (&d)[16], uint32_t a0, uint32_t a1, uint32_t a2, uint32_t a3, uint32_t blo) {
  asm volatile("{\n.reg .pred p;\n.reg .b64 bd;\nsetp.ne.b32 p, %23, 0;\nmov.b64 bd, {%20, %22};\nadd.s64 bd, bd, %21;\n"
    "wgmma.mma_async.sync.aligned.m64n32k16.f32.bf16.bf16 {%0,%1,%2,%3,%4,%5,%6,%7,%8,%9,%10,%11,%12,%13,%14,%15}, {%16,%17,%18,%19}, bd, p, 1, 1, 0;\n}\n"
    : "+f"(d[0]),"+f"(d[1]),"+f"(d[2]),"+f"(d[3]),"+f"(d[4]),"+f"(d[5]),"+f"(d[6]),"+f"(d[7]),"+f"(d[8]),"+f"(d[9]),"+f"(d[10]),"+f"(d[11]),"+f"(d[12]),"+f"(d[13]),"+f"(d[14]),"+f"(d[15])
    : "r"(a0), "r"(a1), "r"(a2), "r"(a3), "r"(blo), "n"(OFF), "n"(BHI), "n"(ACC));
}
template <int OFF, uint32_t BHI, int ACC>
__device__ __forceinline__ void wgmma_rs24(float (&d)[12], uint32_t a0, uint32_t a1, uint32_t a2, uint32_t a3, uint32_t blo) {
  asm volatile("{\n.reg .pred p;\n.reg .b64 bd;\nsetp.ne.b32 p, %19, 0;\nmov.b64 bd, {%16, %18};\nadd.s64 bd, bd, %17;\n"
    "wgmma.mma_async.sync.aligned.m64n24k16.f32.bf16.bf16 {%0,%1,%2,%3,%4,%5,%6,%7,%8,%9,%10,%11}, {%12,%13,%14,%15}, bd, p, 1, 1, 1;\n}\n"
    : "+f"(d[0]),"+f"(d[1]),"+f"(d[2]),"+f"(d[3]),"+f"(d[4]),"+f"(d[5]),"+f"(d[6]),"+f"(d[7]),"+f"(d[8]),"+f"(d[9]),"+f"(d[10]),"+f"(d[11])
    : "r"(a0), "r"(a1), "r"(a2), "r"(a3), "r"(blo), "n"(OFF), "n"(BHI), "n"(ACC));
}
template <int OFF, uint32_t BHI, int ACC>
__device__ __forceinline__ void wgmma_rs16(float (&d)[8], uint32_t a0, uint32_t a1, uint32_t a2, uint32_t a3, uint32_t blo) {
  asm volatile("{\n.reg .pred p;\n.reg .b64 bd;\nsetp.ne.b32 p, %15, 0;\nmov.b64 bd, {%12, %14};\nadd.s64 bd, bd, %13;\n"
    "wgmma.mma_async.sync.aligned.m64n16k16.f32.bf16.bf16 {%0,%1,%2,%3,%4,%5,%6,%7}, {%8,%9,%10,%11}, bd, p, 1, 1, 1;\n}\n"
    : "+f"(d[0]),"+f"(d[1]),"+f"(d[2]),"+f"(d[3]),"+f"(d[4]),"+f"(d[5]),"+f"(d[6]),"+f"(d[7])
    : "r"(a0), "r"(a1), "r"(a2), "r"(a3), "r"(blo), "n"(OFF), "n"(BHI), "n"(ACC));
}

constexpr int A_R1 = 0;
constexpr int A_R2A = A_R1 + 2624, A_R2B = A_R2A + 768, A_R3A = A_R2B + 768, A_R3B = A_R3A + 528;
constexpr int A_K1024 = A_R3B + 528;
constexpr int A_W5 = A_K1024 + 16;
constexpr int A_W3 = A_W5 + 4096;
constexpr int A_W9 = A_W3 + 4112;
constexpr int A_W7 = A_W9 + 2080;
constexpr int A_V  = A_W7 + 2080 + 32;
constexpr int A_SCL = A_V + 2048;
constexpr int A_UB = A_SCL + 16;
constexpr int A_STG = A_UB + 5248;
constexpr int A_Y2 = A_STG, A_Y3 = A_Y2 + 6528, A_YB = A_Y3 + 4352;
constexpr int A_REC = A_STG + 4 * 4352;
constexpr int A_CH = A_REC + 8192;
static_assert(A_W5 % 16 == 0 && A_UB % 16 == 0 && A_CH % 16 == 0 && A_YB + 4096 <= A_REC, "layout");

struct cf { float x, y; };
__device__ __forceinline__ cf cmul(cf a, cf b) { cf r; r.x = fmaf(a.x, b.x, -a.y * b.y); r.y = fmaf(a.x, b.y, a.y * b.x); return r; }
__device__ __forceinline__ cf cexp_l(float lr, float li, float l) {
  float mag; asm("ex2.approx.ftz.f32 %0, %1;" : "=f"(mag) : "f"((lr * l) * 1.4426950408889634f));
  const float th = li * l;
  const float k = (fmaf(th, 0.15915494f, 12582912.f)) - 12582912.f;
  float ph = fmaf(th, 0.15915494f, -k);
  ph = fmaf(th, 6.4206383e-9f, ph) * 6.2831853f;
  cf r; r.x = mag * __cosf(ph); r.y = mag * __sinf(ph); return r;
}
__device__ __forceinline__ void sts16(uint32_t a, uint32_t v) { asm volatile("st.shared.u16 [%0], %1;" ::"r"(a), "h"((uint16_t)v) : "memory"); }
__device__ __forceinline__ void sts32(uint32_t a, uint32_t v) { asm volatile("st.shared.u32 [%0], %1;" ::"r"(a), "r"(v) : "memory"); }
__device__ __forceinline__ void sts64(uint32_t a, uint32_t v0, uint32_t v1) { asm volatile("st.shared.v2.u32 [%0], {%1, %2};" ::"r"(a), "r"(v0), "r"(v1) : "memory"); }
__device__ __forceinline__ void sts128(uint32_t a, uint32_t v0, uint32_t v1, uint32_t v2, uint32_t v3) {
  asm volatile("st.shared.v4.u32 [%0], {%1, %2, %3, %4};" ::"r"(a), "r"(v0), "r"(v1), "r"(v2), "r"(v3) : "memory");
}
__device__ __forceinline__ uint32_t lds32(uint32_t a) { uint32_t v; asm volatile("ld.shared.u32 %0, [%1];" : "=r"(v) : "r"(a) : "memory"); return v; }
__device__ __forceinline__ uint4 lds128(uint32_t a) {
  uint4 v; asm volatile("ld.shared.v4.u32 {%0, %1, %2, %3}, [%4];" : "=r"(v.x), "=r"(v.y), "=r"(v.z), "=r"(v.w) : "r"(a) : "memory"); return v;
}
__device__ __forceinline__ void ldsm4(uint32_t* r, uint32_t a) {
  asm volatile("ldmatrix.sync.aligned.m8n8.x4.shared.b16 {%0,%1,%2,%3}, [%4];" : "=r"(r[0]), "=r"(r[1]), "=r"(r[2]), "=r"(r[3]) : "r"(a) : "memory");
}
__device__ __forceinline__ void mma16816(float* d, uint32_t a0, uint32_t a1, uint32_t a2, uint32_t a3, uint32_t b0, uint32_t b1) {
  asm volatile("mma.sync.aligned.m16n8k16.row.col.f32.f16.f16.f32 {%0,%1,%2,%3}, {%4,%5,%6,%7}, {%8,%9}, {%0,%1,%2,%3};"
               : "+f"(d[0]), "+f"(d[1]), "+f"(d[2]), "+f"(d[3]) : "r"(a0), "r"(a1), "r"(a2), "r"(a3), "r"(b0), "r"(b1));
}
__device__ __forceinline__ uint32_t pack_h(float lo, float hi) { uint32_t r; asm("cvt.rn.f16x2.f32 %0, %1, %2;" : "=r"(r) : "f"(hi), "f"(lo)); return r; }
__device__ __forceinline__ uint32_t pack_h(cf v) { return pack_h(v.x, v.y); }
__device__ __forceinline__ uint32_t hcmul(uint32_t x, uint32_t r0, uint32_t r1) {
  const __half2 hx = *(__half2*)&x;
  const __half2 y = __hfma2(__high2half2(hx), *(__half2*)&r1, __hmul2(__low2half2(hx), *(__half2*)&r0));
  return *(const uint32_t*)&y;
}
__device__ __forceinline__ float ln_rstd(float var) {
  float sd, rs;
  asm("sqrt.approx.f32 %0, %1;" : "=f"(sd) : "f"(rbf(rbf(var) + 1e-5f)));
  asm("rcp.approx.f32 %0, %1;" : "=f"(rs) : "f"(rbf(sd)));
  return rs;
}
__device__ __forceinline__ uint32_t hsub2_bf(uint32_t a, uint32_t b) { uint32_t r; asm("sub.rn.bf16x2 %0, %1, %2;" : "=r"(r) : "r"(a), "r"(b)); return r; }
__device__ __forceinline__ void bar_sync(int id, int n) { asm volatile("bar.sync %0, %1;" ::"r"(id), "r"(n) : "memory"); }

template <int S> struct F1B { static constexpr int c = S / 4 + ((S & 3) == 3 ? 0 : 0), cc = (16 * S) / 64, ks = (64 * cc - (16 * S - 48)) / 16, off = (A_UB + 2 * ks * 656 + (9 - cc) * 16) / 16; };

template <int NS>
__device__ __forceinline__ void load_quads(uint32_t* q, uint32_t addr) {
#pragma unroll
  for (int i = 0; i < NS; i++) {
    q[4 * i] = lds32(addr + i * 64); q[4 * i + 1] = lds32(addr + i * 64 + 32);
    q[4 * i + 2] = i ? q[4 * i - 3] : lds32(addr - 32);
    q[4 * i + 3] = q[4 * i];
  }
#pragma unroll
  for (int i = 0; i < 4 * NS; i++) asm volatile("" : "+r"(q[i]));
}
template <int S0, int NS>
__device__ __forceinline__ void f1_steps(float (&acc)[16], const uint32_t* a, uint32_t blo) {
  if constexpr (NS > 0) {
    wgmma_rs32<F1B<S0>::off, 8, S0 != 0>(acc, a[0], a[1], a[2], a[3], blo);
    f1_steps<S0 + 1, NS - 1>(acc, a + 4, blo);
  }
}
template <int S0, int NS, int BASE, int FIRST>
__device__ __forceinline__ void s2_steps(float (&acc)[12], const uint32_t* a, uint32_t blo) {
  if constexpr (NS > 0) {
    wgmma_rs24<BASE / 16 + (112 - 16 * S0), 64, !(FIRST && S0 == 0)>(acc, a[0], a[1], a[2], a[3], blo);
    s2_steps<S0 + 1, NS - 1, BASE, FIRST>(acc, a + 4, blo);
  }
}
template <int S0, int NS, int BASE, int FIRST>
__device__ __forceinline__ void s3_steps(float (&acc)[8], const uint32_t* a, uint32_t blo) {
  if constexpr (NS > 0) {
    wgmma_rs16<BASE / 16 + (48 - 16 * S0), 65, !(FIRST && S0 == 0)>(acc, a[0], a[1], a[2], a[3], blo);
    s3_steps<S0 + 1, NS - 1, BASE, FIRST>(acc, a + 4, blo);
  }
}

__device__ __forceinline__ void phase_a(
        unsigned char* sm, const uint32_t bar_rec, const uint32_t ep_addr,
        const __nv_bfloat16* __restrict__ x, const uint32_t* __restrict__ are, const uint32_t* __restrict__ aim,
        const uint32_t* __restrict__ bre, const uint32_t* __restrict__ bim, const uint32_t* __restrict__ cre,
        const uint32_t* __restrict__ cim, const unsigned short* __restrict__ logdt, const unsigned short* __restrict__ dskip,
        const uint4* __restrict__ wgate, const uint4* __restrict__ wup, const uint4* __restrict__ wdown) {
  const uint32_t sb = s2u(sm);
  const int tid = threadIdx.x, warp = __shfl_sync(~0u, tid >> 5, 0), wg = warp >> 2, lane = tid & 31, wq = warp & 3, t128 = tid & 127;
  const int blk = blockIdx.x;
  const bool conv = (blk & 7) != 7;
  const int cblk = blk - (blk >> 3);

  uint2 xr[4];
  {
    const uint2* p = (const uint2*)(x + (size_t)(blk * 16 + warp) * DM);
    xr[0] = __ldg(p + lane); xr[1] = __ldg(p + 32 + lane); xr[2] = __ldg(p + 64 + lane);
    xr[3] = lane < 16 ? __ldg(p + 96 + lane) : make_uint2(0, 0);
  }
  const int ch = conv ? cblk * 4 + wg : 0;
  const uint32_t cb = sb + wg * A_CH;
  uint32_t prm[6];
  {
    const int i = ch * 128 + t128;
    prm[0] = __ldg(are + i); prm[1] = __ldg(aim + i); prm[2] = __ldg(bre + i); prm[3] = __ldg(bim + i); prm[4] = __ldg(cre + i); prm[5] = __ldg(cim + i);
  }
  const uint32_t ldt = __ldg(logdt + ch);
  uint32_t cnt0 = 0;
  if (tid == 0) cnt0 = __ldcg(&g_cnt1);
  const int g = lane >> 2, t = lane & 3;
#pragma unroll
  for (int i = 0; i < 4; i++) if (i < 3 || t128 < (A_W5 + 1024) / 16 - 384) sts128(cb + (i * 128 + t128) * 16, 0, 0, 0, 0);
  if (t128 < 64) sts128(cb + A_W3 + t128 * 16, 0, 0, 0, 0);
  if (t128 < 72) sts128(cb + A_UB + (t128 / 9) * 656 + (t128 % 9) * 16, 0, 0, 0, 0);
  {
    float s = 0.f, q = 0.f;
#pragma unroll
    for (int i = 0; i < 4; i++) {
      const float a = bf_lo(xr[i].x), b = bf_hi(xr[i].x), c = bf_lo(xr[i].y), d = bf_hi(xr[i].y);
      s += (a + b) + (c + d);
      q = fmaf(a, a, q); q = fmaf(b, b, q); q = fmaf(c, c, q); q = fmaf(d, d, q);
    }
#pragma unroll
    for (int o = 16; o; o >>= 1) { s += __shfl_xor_sync(~0u, s, o); q += __shfl_xor_sync(~0u, q, o); }
    const float mean = s * (1.f / DM);
    const float var = fmaxf(fmaf(-mean, mean, q * (1.f / DM)), 0.f);
    const float rs = ln_rstd(var);
    const uint32_t mm = pack_bf16(mean, mean);
    const uint32_t tu = sb + A_REC + (warp >> 3) * A_CH + (warp & 7) * 912 + lane * 8, tx = tu + 2 * A_CH;
#pragma unroll
    for (int i = 0; i < 4; i++) {
      if (i < 3 || lane < 16) {
        const uint32_t d0 = hsub2_bf(xr[i].x, mm), d1 = hsub2_bf(xr[i].y, mm);
        sts64(tu + i * 256, pack_bf16(bf_lo(d0) * rs, bf_hi(d0) * rs), pack_bf16(bf_lo(d1) * rs, bf_hi(d1) * rs));
        sts64(tx + i * 256, xr[i].x, xr[i].y);
      }
    }
  }
  if (tid == 0) sts32(ep_addr, (cnt0 >> 7) + 1u);
  if (tid == 320) TR(0, 1);
  auto publish_rows = [&]() {
    bar_sync(5, 512);
    uint4* dst = g_ux + ((size_t)(warp * 8 + (lane >> 2)) * 128 + blk) * 4 + ((lane ^ (blk >> 1)) & 3);
#pragma unroll
    for (int i = 0; i < 4; i++) {
      if (i < 3 || warp < 8) {
        uint32_t r[4];
        asm volatile("ldmatrix.sync.aligned.m8n8.x4.trans.shared.b16 {%0,%1,%2,%3}, [%4];" : "=r"(r[0]), "=r"(r[1]), "=r"(r[2]), "=r"(r[3])
                     : "r"(sb + A_REC + (lane >> 3) * A_CH + (lane & 7) * 912 + (warp + 16 * i) * 16) : "memory");
        dst[i * 65536] = make_uint4(r[0], r[1], r[2], r[3]);
      }
    }
    if (warp != 0) asm volatile("bar.arrive 6, 512;" ::: "memory");
  };
  auto release_rows = [&]() {
    if (warp == 0) {
      bar_sync(6, 512);
      if (lane == 0) { asm volatile("red.release.gpu.global.add.u32 [%0], 1;" ::"l"(&g_cnt1) : "memory"); TR(0, 8); }
      __syncwarp();
    }
  };

  if (!conv) {
    const int a = blk >> 3, mat = a >> 3, j = a & 7;
    uint4 v[14];
    const int cq = warp % 7, rh = warp / 7, ngs = cq * 4 + t;
    const uint4* s1 = (mat ? wup : wgate) + (size_t)(rh * 224 + g) * 224 + j * 28 + ngs;
    uint4* d1 = g_wimg + (size_t)j * 37632 + ((ngs / 14) * 14 + rh * 7) * 896 + (mat * 14 + ngs % 14) * 32 + g;
    if (warp < 14) {
#pragma unroll
      for (int r = 0; r < 14; r++) v[r] = __ldg(s1 + (size_t)r * 8 * 224);
    }
    publish_rows();
    release_rows();
    if (warp < 14) {
      float s[8];
#pragma unroll
      for (int k = 0; k < 8; k++) s[k] = 0.f;
      const int nd = warp * 4 + t;
      const uint4* s2 = wdown + (size_t)(a * 112 + g) * 56 + nd;
      uint4* d2 = g_wimg + (size_t)(a >> 1) * 37632 + 25088 + ((nd / 7) * 2 + (a & 1)) * 784 + (nd % 7) * 8 + g;
#pragma unroll
      for (int hb = 0; hb < 3; hb++) {
#pragma unroll
        for (int r = 0; r < 14; r++) {
          const uint4 w = v[r];
          const int i = hb * 14 + r;
          if (hb < 2) {
            d1[(i >> 2) * 896 + (i & 3) * 8] = w;
            s[0] += bf_lo(w.x); s[1] += bf_hi(w.x); s[2] += bf_lo(w.y); s[3] += bf_hi(w.y);
            s[4] += bf_lo(w.z); s[5] += bf_hi(w.z); s[6] += bf_lo(w.w); s[7] += bf_hi(w.w);
            v[r] = hb == 0 ? __ldg(s1 + (size_t)(14 + r) * 8 * 224) : __ldg(s2 + (size_t)r * 8 * 56);
          } else d2[r * 56] = w;
        }
      }
#pragma unroll
      for (int k = 0; k < 8; k++) { s[k] += __shfl_xor_sync(~0u, s[k], 4); s[k] += __shfl_xor_sync(~0u, s[k], 8); s[k] += __shfl_xor_sync(~0u, s[k], 16); }
      if (g == 0) {
        float4* red = (float4*)(sm + A_STG + rh * 896 + ngs * 32);
        red[0] = make_float4(s[0], s[1], s[2], s[3]); red[1] = make_float4(s[4], s[5], s[6], s[7]);
      }
    }
    bar_sync(5, 512);
    if (tid < 224) {
      const float cs = *(const float*)(sm + A_STG + tid * 4) + *(const float*)(sm + A_STG + 896 + tid * 4);
      const float hi = rbf(cs), mid = rbf(cs - hi), lo = rbf(cs - hi - mid);
      const int q = tid / 112, n = tid % 112 + 112 * mat;
      __nv_bfloat16* dst = (__nv_bfloat16*)(g_cimg + (j * 2 + q) * 224 + (n >> 3) * 8) + (n & 7);
      dst[0] = __float2bfloat16_rn(hi); dst[8] = __float2bfloat16_rn(mid); dst[16] = __float2bfloat16_rn(lo);
#pragma unroll
      for (int k = 3; k < 8; k++) dst[8 * k] = __float2bfloat16_rn(0.f);
    }
    if (tid == 320) TR(0, 10);
    return;
  }

  const int wr = (wq + wg) & 3;
  const int bk = wr * 32 + lane;
  {
    const uint32_t stg = cb + A_STG + wq * 4352, sw = stg + lane * 8;
    const float dt = rbf(expf(__uint_as_float(ldt << 16)));
    float lr[2], li[2];
    cf bq[2], b0[2], b4[2];
    uint32_t bf[48];
#pragma unroll
    for (int m = 0; m < 2; m++) {
      lr[m] = dt * (m ? bf_hi(prm[0]) : bf_lo(prm[0]));
      li[m] = dt * (m ? bf_hi(prm[1]) : bf_lo(prm[1]));
    }
    {
      cf b[2], z[2];
#pragma unroll
      for (int m = 0; m < 2; m++) {
        cf db, c;
        db.x = dt * (m ? bf_hi(prm[2]) : bf_lo(prm[2])); db.y = -dt * (m ? bf_hi(prm[3]) : bf_lo(prm[3]));
        c.x = m ? bf_hi(prm[4]) : bf_lo(prm[4]); c.y = -(m ? bf_hi(prm[5]) : bf_lo(prm[5]));
        b[m] = cmul(c, db);
        z[m] = cexp_l(lr[m], -li[m], 1.f);
        bq[m] = cexp_l(lr[m], -li[m], 256.f);
      }
      publish_rows();
      {
        const float mx = fmaxf(fmaxf(fabsf(b[0].x), fabsf(b[0].y)), fmaxf(fabsf(b[1].x), fabsf(b[1].y)));
        const uint32_t e = max(__reduce_max_sync(~0u, __float_as_uint(mx)) >> 23, 14u);
        const float sc = __uint_as_float((267u - e) << 23);
        b[0].x *= sc; b[0].y *= sc; b[1].x *= sc; b[1].y *= sc;
        if (lane == 0) sts32(cb + A_SCL + wq * 4, (e - 13u) << 23);
      }
#pragma unroll
      for (int i = 0; i < 8; i++) {
        sts64(sw + i * 272, pack_h(b[0]), pack_h(b[1]));
        if (!(i & 1)) {
          cf e0 = cmul(b[0], bq[0]), e1 = cmul(b[1], bq[1]);
          sts64(sw + (8 + i / 2) * 272, pack_h(e0), pack_h(e1));
          if (i == 0) { b0[0] = e0; b0[1] = e1; }
          if (i == 4) { b4[0] = e0; b4[1] = e1; }
        }
        if (i < 7) { b[0] = cmul(b[0], z[0]); b[1] = cmul(b[1], z[1]); }
        if (i == 5) release_rows();
      }
#pragma unroll
      for (int i = 0; i < 7; i++) {
        b0[0] = cmul(b0[0], bq[0]); b0[1] = cmul(b0[1], bq[1]);
        sts64(sw + (i < 2 ? 12 + 2 * i : i - 2) * 272, pack_h(b0[0]), pack_h(b0[1]));
        if (i < 2) {
          b4[0] = cmul(b4[0], bq[0]); b4[1] = cmul(b4[1], bq[1]);
          sts64(sw + (13 + 2 * i) * 272, pack_h(b4[0]), pack_h(b4[1]));
        }
        if (i == 1) {
          __syncwarp();
#pragma unroll
          for (int n = 0; n < 2; n++)
#pragma unroll
            for (int k2 = 0; k2 < 4; k2++) ldsm4(bf + n * 16 + k2 * 4, stg + (n * 8 + (lane & 7)) * 272 + k2 * 64 + (lane >> 3) * 16);
          __syncwarp();
        }
      }
    }
    uint32_t cv = 0;
    if (tid == 160) asm volatile("ld.relaxed.gpu.global.u32 %0, [%1];" : "=r"(cv) : "l"(&g_cnt1) : "memory");
    {
      const cf p0 = cexp_l(lr[0], li[0], 8.f), p1 = cexp_l(lr[1], li[1], 8.f);
      cf v0 = p0, v1 = p1;
      sts64(sw + 8 * 272, 0x3C00u, 0x3C00u);
#pragma unroll
      for (int i = 1; i < 8; i++) {
        sts64(sw + (8 + i) * 272, pack_h(v0), pack_h(v1));
        v0 = cmul(v0, p0); v1 = cmul(v1, p1);
      }
      const uint32_t ra = stg + 5 * 272 + (lane >> 2) * 64 + (lane & 1) * 32 + (lane & 2) * 4;
      sts64(ra, pack_h(v0), pack_h(-v0.y, v0.x));
      sts64(ra + 16, pack_h(v1), pack_h(-v1.y, v1.x));
    }
    __syncwarp();
    if (tid == 320) TR(0, 16);
#pragma unroll
    for (int k2 = 0; k2 < 4; k2++) ldsm4(bf + 32 + k2 * 4, stg + (lane & 7) * 272 + k2 * 64 + (lane >> 3) * 16);
    float c[6][4];
#pragma unroll
    for (int i = 0; i < 6; i++) { c[i][0] = 0.f; c[i][1] = 0.f; c[i][2] = 0.f; c[i][3] = 0.f; }
#pragma unroll
    for (int k2 = 0; k2 < 4; k2++) {
      uint32_t a[4];
      ldsm4(a, stg + (8 + (lane & 7)) * 272 + k2 * 64 + (lane >> 3) * 16);
#pragma unroll
      for (int kk = 0; kk < 2; kk++) {
        const int ks = 2 * k2 + kk;
        const uint4 r4 = lds128(stg + 5 * 272 + ks * 64 + t * 16);
        const uint32_t r[4] = {r4.x, r4.z, r4.y, r4.w};
        const uint32_t x0 = a[2 * kk], y0 = a[2 * kk + 1];
        const uint32_t x1 = hcmul(x0, r[0], r[2]), y1 = hcmul(y0, r[1], r[3]);
        const uint32_t x2 = hcmul(x1, r[0], r[2]), y2 = hcmul(y1, r[1], r[3]);
        const uint32_t x3 = hcmul(x2, r[0], r[2]), y3 = hcmul(y2, r[1], r[3]);
#pragma unroll
        for (int n = 0; n < 3; n++) {
          mma16816(c[n * 2], x0, x1, y0, y1, bf[n * 16 + ks * 2], bf[n * 16 + ks * 2 + 1]);
          mma16816(c[n * 2 + 1], x2, x3, y2, y3, bf[n * 16 + ks * 2], bf[n * 16 + ks * 2 + 1]);
        }
      }
      if (k2 == 0 && warp == 5) {
        if (lane == 0) {
          const uint32_t tgt = lds32(ep_addr) * 128u;
          int it = 0;
          while ((int)(cv - tgt) < 0 && ++it < 400000) asm volatile("ld.relaxed.gpu.global.u32 %0, [%1];" : "=r"(cv) : "l"(&g_cnt1) : "memory");
          asm volatile("fence.acquire.gpu;" ::: "memory");
          asm volatile("fence.proxy.async.global;" ::: "memory");
          TR(0, 9);
        }
        __syncwarp();
#pragma unroll
        for (int c2 = 0; c2 < 4; c2++) bulk_ld_elect<8192>(sb + c2 * A_CH + A_REC, g_ux + (size_t)(cblk * 4 + c2) * 512, bar_rec);
      }
    }
    __syncwarp();
#pragma unroll
    for (int i = 0; i < 6; i++)
      sts128(stg + i * 512 + lane * 16, __float_as_uint(c[i][0]), __float_as_uint(c[i][1]), __float_as_uint(c[i][2]), __float_as_uint(c[i][3]));
  }
  if (tid == 320) TR(0, 2);

  uint32_t xt[8], ud[8];
  {
    mbar_wait(bar_rec, 0);
    if (tid == 320) TR(0, 4);
    uint4 r[4];
#pragma unroll
    for (int i = 0; i < 4; i++) r[i] = lds128(cb + A_REC + bk * 64 + ((i ^ (bk >> 1)) & 3) * 16);
    const uint32_t ua = cb + A_UB + ((2 * bk) & 7) * 656 + ((bk >> 2) + 9) * 16;
    sts128(ua, r[0].x, r[1].x, r[2].x, r[3].x);
    sts128(ua + 656, r[0].y, r[1].y, r[2].y, r[3].y);
    if (bk <= 96) {
      const bool neg = bk == 96;
      const int bp = neg ? -1 : bk;
      uint32_t h[4];
      h[0] = lds32(cb + A_REC + ((bp - 1) & 127) * 64 + ((2 ^ ((bp - 1) >> 1)) & 3) * 16 + 4);
      h[1] = lds32(cb + A_REC + ((bp - 1) & 127) * 64 + ((3 ^ ((bp - 1) >> 1)) & 3) * 16 + 4);
      h[2] = lds32(cb + A_REC + (bp + 1) * 64 + ((0 ^ ((bp + 1) >> 1)) & 3) * 16);
      h[3] = lds32(cb + A_REC + (bp + 1) * 64 + ((1 ^ ((bp + 1) >> 1)) & 3) * 16);
      if (bp <= 0) { h[0] = 0; h[1] = 0; }
      const uint32_t wd[12] = {h[0], h[1], neg ? 0 : r[0].x, neg ? 0 : r[1].x, neg ? 0 : r[2].x, neg ? 0 : r[3].x,
                               neg ? 0 : r[0].y, neg ? 0 : r[1].y, neg ? 0 : r[2].y, neg ? 0 : r[3].y, h[2], h[3]};
      float P[25];
      P[0] = 0.f;
#pragma unroll
      for (int i = 0; i < 12; i++) { P[2 * i + 1] = P[2 * i] + bf_lo(wd[i]); P[2 * i + 2] = P[2 * i + 1] + bf_hi(wd[i]); }
#define WIN(i, hw) (P[(i) + 5 + (hw)] - P[(i) + 4 - (hw)])
#define WPK(i, hw) pack_bf16(WIN(i, hw), WIN((i) + 1, hw))
      const int tp = 2 * bp;
      const uint32_t a3 = cb + A_W3 + (tp + 64) * 16 + 8, a5 = cb + A_W5 + (tp + 64) * 16;
      sts64(a3, WPK(0, 1), WPK(2, 1));
      sts128(a3 + 8, WPK(4, 1), WPK(6, 1), WPK(8, 1), WPK(10, 1));
      sts64(a3 + 24, WPK(12, 1), WPK(14, 1));
      sts128(a5, WPK(0, 2), WPK(2, 2), WPK(4, 2), WPK(6, 2));
      sts128(a5 + 16, WPK(8, 2), WPK(10, 2), WPK(12, 2), WPK(14, 2));
      if (bp < 64) {
        sts128(cb + A_W7 + 1040 + bp * 16, WPK(0, 3), WPK(2, 3), WPK(4, 3), WPK(6, 3));
        sts128(cb + A_W7 + (bp + 1) * 16, WPK(8, 3), WPK(10, 3), WPK(12, 3), WPK(14, 3));
        sts128(cb + A_W9 + (bp + 1) * 16, WPK(0, 4), WPK(2, 4), WPK(4, 4), WPK(6, 4));
        sts128(cb + A_W9 + 1040 + (bp + 1) * 16, WPK(8, 4), WPK(10, 4), WPK(12, 4), WPK(14, 4));
#define VPK(i) pack_bf16(P[(i) + 2] - P[i], P[(i) + 3] - P[(i) + 1])
        sts128(cb + A_V + bp * 32, VPK(0), VPK(2), VPK(4), VPK(6));
        sts128(cb + A_V + bp * 32 + 16, VPK(8), VPK(10), VPK(12), VPK(14));
      }
    }
  }
  asm volatile("fence.proxy.async.shared::cta;" ::: "memory");
  bar_sync(1 + wg, 128);
  if (tid == 320) TR(0, 3);
  {
    const uint4 sc = lds128(cb + A_SCL);
    const float scl[4] = {__uint_as_float(sc.x), __uint_as_float(sc.y), __uint_as_float(sc.z), __uint_as_float(sc.w)};
#pragma unroll
    for (int rep = 0; rep < 2; rep++) {
      const int qd = rep ? 2 + wr : 3 - wr;
      if (rep == 0 || wr >= 2) {
        float s[4] = {0.f, 0.f, 0.f, 0.f};
#pragma unroll
        for (int w = 0; w < 4; w++) {
          uint4 u4 = lds128(cb + A_STG + w * 4352 + qd * 512 + lane * 16);
          s[0] = fmaf(__uint_as_float(u4.x), scl[w], s[0]); s[1] = fmaf(__uint_as_float(u4.y), scl[w], s[1]);
          s[2] = fmaf(__uint_as_float(u4.z), scl[w], s[2]); s[3] = fmaf(__uint_as_float(u4.w), scl[w], s[3]);
        }
#pragma unroll
        for (int hf = 0; hf < 2; hf++) {
          const int j = (qd & 1) * 16 + g + 8 * hf;
          const uint32_t pk = pack_bf16(s[2 * hf + 1], s[2 * hf]);
          const uint32_t v0 = pk >> 16, v1 = pk & 0xFFFFu, v00 = v0 * 0x10001u;
          if (rep == 1) {
            if (t < 2) {
#pragma unroll
              for (int e = 0; e < 2; e++) {
                const int lam = 128 + 32 * (2 * t + e) + j, mu = lam >> 1;
                const uint32_t val = e ? v1 : v0;
                uint32_t a = cb + ((lam & 1) ? A_R3B : A_R3A) + mu * 4;
                if (lam == 128) { a = cb + A_R2A + 128 * 4; sts32(cb + A_K1024, val << 16); }
                sts16(a, val); sts16(a + 6, val);
              }
            } else if (t == 2 && j == 0) { sts16(cb + A_R3A + 128 * 4, v0); }
          } else if (qd < 2) {
            const uint32_t a = cb + A_R1 + (62 + 8 * j + 2 * t) * 4;
            sts16(a, v0); sts32(a + 4, pk); sts16(a + 10, v1);
          } else if (t < 2) {
            const int L = 256 + 8 * j + 4 * t;
            const uint32_t a = cb + A_R1 + (62 + L) * 4;
            if (L > 256) { sts16(a - 4, v0); sts32(a, v00); } else sts16(a, v0);
            sts32(a + 4, v00); sts32(a + 8, pk); sts16(a + 14, v1);
          } else {
            const int mu = 64 + 32 * (t - 2) + j;
            if (mu == 64) {
              const uint32_t a = cb + A_R1 + (62 + 512) * 4;
              sts16(a - 4, v0); sts32(a, v00); sts32(a + 4, v00); sts32(a + 8, v00); sts16(a + 14, v0);
            } else { sts16(cb + A_R2A + mu * 4, v0); sts16(cb + A_R2A + mu * 4 + 6, v0); }
            sts16(cb + A_R2B + mu * 4, v1); sts16(cb + A_R2B + mu * 4 + 6, v1);
          }
        }
      }
    }
  }
  bar_sync(1 + wg, 128);
  if (tid == 320) TR(0, 5);

  {
    const uint32_t cbu = cb;
    const uint32_t blo_k = ((cbu & 0x3FFFF) >> 4) | (41u << 16);
    const uint32_t blo_n = ((cbu & 0x3FFFF) >> 4) | (8u << 16);
    const uint32_t tb = cb + (16 * wq + g - 2 * t) * 4;
    float y1[16], y2[12], y3[8];
    const uint32_t dk16 = __ldg(dskip + ch);
    uint32_t qa[32], qb[32];
    const uint32_t t1 = tb + A_R1 + (62 - 48) * 4;
    load_quads<4>(qa, tb + A_R3A + 17 * 4); load_quads<4>(qa + 16, tb + A_R3B + 16 * 4);
    wg_fence();
    s3_steps<0, 4, A_W9, 1>(y3, qa, blo_n); s3_steps<0, 4, A_W7, 0>(y3, qa + 16, blo_n);
    wg_commit();
    load_quads<8>(qb, tb + A_R2A + 16 * 4);
    wg_fence(); s2_steps<0, 8, A_W5, 1>(y2, qb, blo_n); wg_commit();
    wg_wait<1>(); load_quads<8>(qa, tb + A_R2B + 16 * 4);
    wg_fence(); s2_steps<0, 8, A_W3, 0>(y2, qa, blo_n); wg_commit();
    wg_wait<1>(); load_quads<8>(qb, t1);
    wg_fence(); f1_steps<0, 8>(y1, qb, blo_k); wg_commit();
    wg_wait<1>(); load_quads<8>(qa, t1 + 8 * 64);
    wg_fence(); f1_steps<8, 8>(y1, qa, blo_k); wg_commit();
    reg_fence(y2); reg_fence(y3);
    if (tid == 320) TR(0, 18);
    {
      const float k1024 = __uint_as_float(lds32(cb + A_K1024));
#pragma unroll
      for (int i = 0; i < 2; i++)
#pragma unroll
        for (int hf = 0; hf < 2; hf++) {
          const int idx = 16 * (16 * wq + g + 8 * hf) + 8 * i + 2 * t;
          const uint32_t vv = lds32(cb + A_V + idx * 2);
          sts64(cb + A_Y3 + (idx + 4 * (idx >> 6)) * 4, __float_as_uint(fmaf(k1024, bf_lo(vv), y3[4 * i + 2 * hf])),
                __float_as_uint(fmaf(k1024, bf_hi(vv), y3[4 * i + 2 * hf + 1])));
        }
#pragma unroll
      for (int i = 0; i < 3; i++)
#pragma unroll
        for (int hf = 0; hf < 2; hf++) {
          const int idx = 512 * i + 8 * (16 * wq + g + 8 * hf) + 2 * t;
          sts64(cb + A_Y2 + (idx + 4 * (idx >> 6)) * 4, __float_as_uint(y2[4 * i + 2 * hf]), __float_as_uint(y2[4 * i + 2 * hf + 1]));
        }
    }
    wg_wait<1>(); load_quads<8>(qb, t1 + 16 * 64);
    wg_fence(); f1_steps<16, 8>(y1, qb, blo_k); wg_commit();
    wg_wait<1>(); load_quads<8>(qa, t1 + 24 * 64);
    wg_fence(); f1_steps<24, 8>(y1, qa, blo_k); wg_commit();
    wg_wait<1>(); load_quads<5>(qb, t1 + 32 * 64);
    wg_fence(); f1_steps<32, 5>(y1, qb, blo_k); wg_commit();
    bar_sync(1 + wg, 128);
    float ex[12];
#pragma unroll
    for (int i = 1; i < 4; i++)
#pragma unroll
      for (int k = 0; k < 4; k++) {
        const int aa = 8 * i + 2 * t + (k & 1), b = 16 * wq + g + 8 * (k >> 1);
        float e = __uint_as_float(lds32(cb + A_Y2 + ((aa - 8) * 68 + b) * 4));
        if (i >= 2) e += __uint_as_float(lds32(cb + A_Y3 + ((aa - 16) * 68 + b) * 4));
        ex[4 * (i - 1) + k] = e;
      }
    {
      const uint32_t dk = dk16 * 0x10001u;
#pragma unroll
      for (int i = 0; i < 4; i++) {
        const uint4 r = lds128(cb + A_REC + bk * 64 + ((i ^ (bk >> 1)) & 3) * 16);
        ud[i] = hmul2_bf(r.x, dk); ud[4 + i] = hmul2_bf(r.y, dk); xt[i] = r.z; xt[4 + i] = r.w;
      }
    }
    wg_wait<0>();
    reg_fence(y1);
    if (tid == 320) TR(0, 6);
#pragma unroll
    for (int i = 0; i < 12; i++) y1[4 + i] += ex[i];
#pragma unroll
    for (int i = 0; i < 2; i++) {
      const int mi = lane >> 3, aa = 8 * (2 * i + (mi >> 1)) + (lane & 7);
      asm volatile("stmatrix.sync.aligned.m8n8.x4.trans.shared.b16 [%0], {%1,%2,%3,%4};"
                   ::"r"(cb + A_YB + aa * 128 + (((2 * wq + (mi & 1)) ^ (lane & 7)) << 4)),
                     "r"(pack_bf16(y1[8 * i], y1[8 * i + 1])), "r"(pack_bf16(y1[8 * i + 2], y1[8 * i + 3])),
                     "r"(pack_bf16(y1[8 * i + 4], y1[8 * i + 5])), "r"(pack_bf16(y1[8 * i + 6], y1[8 * i + 7])) : "memory");
    }
  }
  bar_sync(1 + wg, 128);
#pragma unroll
  for (int c = 0; c < 2; c++) {
    const int tau = 2 * bk + c, r = ch & 7;
    const uint4 y = lds128(cb + A_YB + (tau >> 3) * 128 + (((tau ^ (tau >> 3)) & 7) << 4));
    g_himg[(size_t)(tau >> 4) * 7168 + (ch >> 3) * 128 + ((tau >> 3) & 1) * 64 + r * 8 + ((tau & 7) ^ r)] =
        make_uint4(hadd2_bf(xt[4 * c], hadd2_bf(y.x, ud[4 * c])), hadd2_bf(xt[4 * c + 1], hadd2_bf(y.y, ud[4 * c + 1])),
                   hadd2_bf(xt[4 * c + 2], hadd2_bf(y.z, ud[4 * c + 2])), hadd2_bf(xt[4 * c + 3], hadd2_bf(y.w, ud[4 * c + 3])));
  }
  if (tid == 320) TR(0, 7);
}

constexpr int B_SA = 0, B_RING = 114688, B_SLOT = 14848, B_NSLOT = 7;
constexpr int B_CS = B_RING + B_NSLOT * B_SLOT;
constexpr int B_RED = B_CS + 7168;
constexpr int B_BAR = B_RED + 256;
constexpr int B_SMEM = B_BAR + 1024, A_SMEM = 4 * A_CH + 64;

__device__ __forceinline__ uint32_t mapa(uint32_t a, uint32_t r) { uint32_t o; asm("mapa.shared::cluster.u32 %0, %1, %2;" : "=r"(o) : "r"(a), "r"(r)); return o; }
template <class T> __device__ __forceinline__ T* pin(T* p) { asm volatile("" : "+l"(p)); return p; }
__device__ __forceinline__ uint32_t pin(uint32_t v) { asm volatile("" : "+r"(v)); return v; }
template <int Q, int ST>
__device__ __forceinline__ void g1_stage(float (&acc)[116], uint32_t alo, uint32_t blo, uint32_t bar_full, uint32_t bar_h) {
  constexpr int s = Q * 14 + ST, sl = s % B_NSLOT;
  if (Q == 0) mbar_wait(bar_h + 8 * ST, 0);
  mbar_wait(bar_full + 8 * sl, (s / B_NSLOT) & 1);
  wg_fence();
  if (Q == 0) {
    wgmma_ss232<(2 * ST) * 256, 0x40000080u, (sl * B_SLOT) / 16, 32, ST != 0>(acc, alo, blo);
    wgmma_ss232<(2 * ST + 1) * 256, 0x40000080u, (sl * B_SLOT + 256) / 16, 32, 1>(acc, alo, blo);
  } else {
    wgmma_ss224<(2 * ST) * 256, 0x40000080u, (sl * B_SLOT) / 16, 32, ST != 0>(*(float(*)[112])acc, alo, blo);
    wgmma_ss224<(2 * ST + 1) * 256, 0x40000080u, (sl * B_SLOT + 256) / 16, 32, 1>(*(float(*)[112])acc, alo, blo);
  }
}

__global__ void __launch_bounds__(512, 1)
k_front(const __nv_bfloat16* __restrict__ x, const uint32_t* __restrict__ are, const uint32_t* __restrict__ aim,
        const uint32_t* __restrict__ bre, const uint32_t* __restrict__ bim, const uint32_t* __restrict__ cre,
        const uint32_t* __restrict__ cim, const unsigned short* __restrict__ logdt, const unsigned short* __restrict__ dskip,
        const uint4* __restrict__ wgate, const uint4* __restrict__ wup, const uint4* __restrict__ wdown) {
  extern __shared__ __align__(1024) unsigned char sm[];
  const uint32_t bar_rec = s2u(sm) + 4 * A_CH;
  if (threadIdx.x == 320) TR(0, 0);
  asm volatile("griddepcontrol.launch_dependents;");
  if (threadIdx.x == 160) { mbar_init(bar_rec, 4); asm volatile("fence.mbarrier_init.release.cluster;" ::: "memory"); }
  phase_a(sm, bar_rec, bar_rec + 8, x, are, aim, bre, bim, cre, cim, logdt, dskip, wgate, wup, wdown);
}

__global__ void __cluster_dims__(2, 1, 1) __launch_bounds__(384, 1) k_ffn(__nv_bfloat16* __restrict__ out) {
  extern __shared__ __align__(1024) unsigned char sm[];
  const uint32_t sb = s2u(sm);
  const int tid = threadIdx.x, warp = __shfl_sync(~0u, tid >> 5, 0), wg = warp >> 2, lane = tid & 31;
  const uint32_t bar_full = sb + B_BAR, bar_empty = bar_full + 64, bar_h = bar_full + 128, bar_cs = bar_full + 240,
                 bar_hh = bar_full + 304, bar_afree = bar_full + 336, bar_out = bar_full + 352;
  if (tid == 0) {
    TR(1, 0);
    for (int i = 0; i < B_NSLOT; i++) { mbar_init(bar_full + 8 * i, 1); mbar_init(bar_empty + 8 * i, 2); }
    asm volatile("fence.mbarrier_init.release.cluster;" ::: "memory");
  } else if (tid == 32) {
    for (int i = 0; i < 14; i++) mbar_init(bar_h + 8 * i, 1);
    asm volatile("fence.mbarrier_init.release.cluster;" ::: "memory");
  } else if (tid == 64) {
    mbar_init(bar_cs, 1);
    for (int i = 0; i < 4; i++) { mbar_init(bar_hh + 8 * i, 1); mbar_expect(bar_hh + 8 * i, 14336); }
    mbar_init(bar_afree, 4); mbar_init(bar_afree + 8, 2);
    for (int i = 0; i < 6; i++) mbar_init(bar_out + 8 * i, 128);
    asm volatile("fence.mbarrier_init.release.cluster;" ::: "memory");
  } else if (tid >= 128 && tid < 352) {
    sts128(sb + B_RING + ((tid - 128) >> 5) * B_SLOT + 14336 + (tid & 31) * 16, 0x3F803F80u, 0x3F803F80u, 0x3F803F80u, 0x3F803F80u);
  }
  asm volatile("fence.proxy.async.shared::cta;" ::: "memory");
  __syncthreads();
  asm volatile("barrier.cluster.arrive.relaxed.aligned;" ::: "memory");
  const int rank = blockIdx.x & 1, rt = blockIdx.x >> 3, j = blockIdx.x & 7, p = j >> 1, cg = 4 * rank + p;
  const int wq = warp & 3, t128 = tid & 127, g = lane >> 2, t = lane & 3;
  uint32_t ep, tag;
  auto load_ep = [&]() { asm volatile("ld.relaxed.gpu.global.u32 %0, [%1];" : "=r"(ep) : "l"(&g_cnt1) : "memory"); };
  auto a_slot = [&](int i, int own) { return B_SA + (i + (i >= own)) * 14336; };
  auto out_addr = [&](int cc, int w) { return sb + a_slot((cc & 2) + w, cg) + (cc & 1) * 7168; };
  auto in_cta = [&](int q) { return rt * 8 + ((p + 3 - q) & 3) * 2 + rank; };
  auto in_src = [&](int q, int cw) { return g_part + (size_t)(in_cta(q) * 3 + q) * 896 + cw * 112; };
  auto in_bad = [&](uint32_t (&in)[14]) { return ((in[3] ^ tag) | (in[7] ^ tag) | (in[11] ^ tag) | (in[13] ^ tag)) & 0x10000u; };
  auto in_load = [&](uint32_t (&in)[14], const uint4* gs) {
#pragma unroll
    for (int i = 0; i < 3; i++) ld128(gs + i * 32, in + 4 * i);
    asm volatile("{\n.reg .b64 v;\nld.relaxed.gpu.global.b64 v, [%2];\nmov.b64 {%0, %1}, v;\n}"
                 : "=r"(in[12]), "=r"(in[13]) : "l"((const uint2*)(gs + 96) - lane) : "memory");
  };
  auto in_check = [&](uint32_t (&in)[14], int q, int cw) {
    int it = 0;
    while (in_bad(in) && ++it < 400000) in_load(in, pin(in_src(q, cw) + lane));
  };

  if (wg == 2) {
    asm volatile("setmaxnreg.dec.sync.aligned.u32 40;");
    asm volatile("barrier.cluster.wait.aligned;" ::: "memory");
    asm volatile("griddepcontrol.wait;" ::: "memory");
    if (warp == 8) {
      if (lane == 0) TR(1, 1);
      const char* wsrc = (const char*)g_wimg + (size_t)j * 602112;
      const char* hsrc = (const char*)g_himg + (size_t)rt * 114688 + rank * 4096;
#pragma unroll
      for (int s = 0; s < 28; s++) {
        if (s < B_NSLOT) bulk_ld_mc_elect<4096>(sb + B_SA + s * 8192 + rank * 4096, hsrc + s * 8192, bar_h + 8 * s);
        if (s == B_NSLOT) {
#pragma unroll
          for (int i = 7; i < 14; i++) bulk_ld_mc_elect<4096>(sb + B_SA + i * 8192 + rank * 4096, hsrc + i * 8192, bar_h + 8 * i);
          bulk_ld_elect<7168>(sb + B_CS, g_cimg + j * 448, bar_cs);
        }
        if (s >= B_NSLOT) mbar_wait(bar_empty + 8 * (s % B_NSLOT), (s / B_NSLOT + 1) & 1);
        bulk_ld_elect<14336>(sb + B_RING + (s % B_NSLOT) * B_SLOT, wsrc + s * 14336, bar_full + 8 * (s % B_NSLOT));
      }
      const char* dsrc[2] = {wsrc + 401408 + rank * 100352, (const char*)g_wimg + (size_t)(j ^ 1) * 602112 + 401408 + rank * 100352};
#pragma unroll
      for (int i = 0; i < 16; i++) {
        const int ci = i < 3 ? 0 : i < 6 ? 1 : i < 8 ? i - 6 : i < 12 ? 2 : 3;
        const int kp = i < 3 ? i : i < 6 ? i - 3 : i < 8 ? 3 : (i & 3);
        mbar_wait(bar_empty + 8 * (i % B_NSLOT), (i / B_NSLOT + 1) & 1);
        bulk_ld_elect<12544>(sb + B_RING + (i % B_NSLOT) * B_SLOT, dsrc[kp >> 1] + ((p + 1 + ci) & 3) * 25088 + (kp & 1) * 12544, bar_full + 8 * (i % B_NSLOT));
      }
    } else if (warp >= 10) {
      const int t64 = tid - 320;
      load_ep();
      const int r = (lane >> 1) & 7, c = (j & 3) * 2 + (lane & 1);
      const uint32_t src = sb + B_SA + (t64 >> 4) * 2048 + (j >> 2) * 1024 + r * 128 + ((c ^ r) << 4);
      float a[16];
#pragma unroll
      for (int k = 0; k < 16; k++) a[k] = 0.f;
#pragma unroll 1
      for (int i = 0; i < 14; i++) {
        mbar_wait(bar_h + 8 * i, 0);
        uint4 v = lds128(src + i * 8192);
        float e[8] = {bf_lo(v.x), bf_hi(v.x), bf_lo(v.y), bf_hi(v.y), bf_lo(v.z), bf_hi(v.z), bf_lo(v.w), bf_hi(v.w)};
#pragma unroll
        for (int k = 0; k < 8; k++) { a[2 * k] += e[k]; a[2 * k + 1] = fmaf(e[k], e[k], a[2 * k + 1]); }
        __nanosleep(160);
      }
      __syncwarp();
      if (lane == 0) { asm volatile("mbarrier.arrive.shared::cluster.b64 _, [%0];" ::"r"(mapa(bar_afree, rank ^ 1)) : "memory"); }
#pragma unroll
      for (int rd = 0; rd < 4; rd++) {
        const int n = 8 >> rd;
        const bool up = lane & (2 * n);
#pragma unroll
        for (int k = 0; k < 8; k++) {
          if (k < n) {
            float keep = up ? a[k + n] : a[k], give = up ? a[k] : a[k + n];
            a[k] = keep + __shfl_xor_sync(~0u, give, 2 * n);
          }
        }
      }
      float* red = (float*)(sm + B_RED);
      red[(warp & 1) * 32 + (lane & 1) * 16 + (lane >> 1)] = a[0];
      bar_sync(1, 64);
      if (t64 < 16) {
        float mean = (red[2 * t64] + red[32 + 2 * t64]) * (1.f / DM);
        float var = fmaxf(fmaf(-mean, mean, (red[2 * t64 + 1] + red[33 + 2 * t64]) * (1.f / DM)), 0.f);
        float rs = ln_rstd(var);
        asm volatile("st.relaxed.gpu.global.u32 [%0], %1;"
                     ::"l"(g_stat2 + rt * 128 + j * 16 + t64), "r"((__float_as_uint(rs * rs) & ~1u) | ((ep >> 7) & 1u)) : "memory");
      }
      if (t64 == 0) TR(1, 2);
      if (lane == 0) {
        const int w = warp & 1;
        for (int cc = 0; cc < 2; cc++) {
          mbar_wait(bar_out + 8 * (cc * 2 + w), 0);
          asm volatile("cp.async.bulk.global.shared::cta.bulk_group [%0], [%1], 7168;"
                       ::"l"(g_part + (size_t)(blockIdx.x * 3 + cc) * 896 + w * 448), "r"(out_addr(cc, w)) : "memory");
          if (w) TR(1, 27 + cc);
        }
        asm volatile("cp.async.bulk.commit_group;" ::: "memory");
        asm volatile("cp.async.bulk.wait_group 0;" ::: "memory");
      }
    }
  } else {
    asm volatile("setmaxnreg.inc.sync.aligned.u32 232;");
    asm volatile("barrier.cluster.wait.aligned;" ::: "memory");
    uint32_t hh[56];
    const bool relt = t128 == 0;
    auto release = [&](int sl) { if (relt) mbar_arrive(bar_empty + 8 * sl); };
    auto send_hh = [&](int q) {
      const uint32_t da = mapa(sb + a_slot(2 * q + wg, cg ^ 4) + t128 * 16, rank ^ 1), db = mapa(bar_hh + 8 * (2 * q + wg), rank ^ 1);
#pragma unroll
      for (int i = 0; i < 7; i++)
        asm volatile("st.async.weak.shared::cluster.mbarrier::complete_tx::bytes.v4.b32 [%0], {%1, %2, %3, %4}, [%5];"
                     ::"r"(da + i * 2048), "r"(hh[28 * q + 4 * i]), "r"(hh[28 * q + 4 * i + 1]),
                       "r"(hh[28 * q + 4 * i + 2]), "r"(hh[28 * q + 4 * i + 3]), "r"(db) : "memory");
    };
    uint32_t alo = ((sb + B_SA + wg * 1024) & 0x3FFFF) >> 4;
    uint32_t blo = (((sb + B_RING) & 0x3FFFF) >> 4) | (8u << 16);
    const uint32_t clo = ((sb + B_CS) & 0x3FFFF) >> 4;
    uint32_t nm0, nm1;
    if (wg == 1) bar_sync(3, 256);
#define G1S(Q, ST) do { if (ST % 7 == 0) { alo = pin(alo); blo = pin(blo); }   \
      g1_stage<Q, ST>(acc, alo, blo, bar_full, bar_h); wg_commit(); \
      if (ST > 0) { wg_wait<1>(); release((Q * 14 + ST - 1) % B_NSLOT); } } while (0)
#define G1HH(Q) do { \
      _Pragma("unroll") \
      for (int i = 0; i < 28; i++) hh[28 * Q + i] = pack_bf16(acc[2 * i] * acc[56 + 2 * i], acc[2 * i + 1] * acc[57 + 2 * i]); \
    } while (0)
    {
      float acc[116];
      G1S(0, 0);
      if (tid == 0) TR(1, 3);
      G1S(0, 1);
      if (wg == 0) asm volatile("bar.arrive 3, 256;" ::: "memory");
      G1S(0, 2); G1S(0, 3); G1S(0, 4); G1S(0, 5); G1S(0, 6); G1S(0, 7); G1S(0, 8); G1S(0, 9); G1S(0, 10); G1S(0, 11); G1S(0, 12);
      G1S(0, 13);
      if (tid == 0) TR(1, 4);
      mbar_wait(bar_cs, 0);
      wg_wait<0>(); reg_fence(acc); release(13 % B_NSLOT);
      {
        const uint32_t msk = t == 0 ? 0xFFFFFFFFu : t == 1 ? 0xFFFFu : 0u;
        const float a = acc[112] * (-1.f / DM), b = acc[114] * (-1.f / DM);
        nm0 = pack_bf16(a, a) & msk; nm1 = pack_bf16(b, b) & msk;
      }
      wg_fence();
      wgmma_rs224<0, 8, 1>(*(float(*)[112])acc, nm0, nm1, 0u, 0u, clo);
      wg_commit(); wg_wait<0>(); reg_fence(acc);
      G1HH(0);
      if (tid == 0) TR(1, 5);
      G1S(1, 0); G1S(1, 1); G1S(1, 2); G1S(1, 3); G1S(1, 4); G1S(1, 5); G1S(1, 6);
      if (relt) asm volatile("mbarrier.arrive.shared::cluster.b64 _, [%0];" ::"r"(mapa(bar_afree, rank ^ 1)) : "memory");
      G1S(1, 7); G1S(1, 8); G1S(1, 9);
      if (relt) asm volatile("mbarrier.arrive.shared::cluster.b64 _, [%0];" ::"r"(mapa(bar_afree + 8, rank ^ 1)) : "memory");
      mbar_wait(bar_afree, 0);
      send_hh(0);
      G1S(1, 10); G1S(1, 11); G1S(1, 12);
      load_ep();
      g1_stage<1, 13>(acc, alo, blo, bar_full, bar_h);
      wgmma_rs224<224, 8, 1>(*(float(*)[112])acc, nm0, nm1, 0u, 0u, clo);
      wg_commit(); wg_wait<1>(); release(26 % B_NSLOT);
      wg_wait<0>(); reg_fence(acc); release(27 % B_NSLOT);
      G1HH(1);
      if (tid == 0) TR(1, 6);
    }
    float accA[28], accB[28];
    uint32_t ph0[28], ph1[28];
    ep = pin(ep >> 7); tag = pin((ep & 1u) << 16);
    blo += 48u << 16;
#define ISSUE(acc, I, a, FIRST) do { \
      constexpr int s_ = 28 + (I), sl_ = s_ % B_NSLOT; \
      if (sl_ == 0) blo = pin(blo); \
      mbar_wait(bar_full + 8 * sl_, (s_ / B_NSLOT) & 1); \
      wg_fence(); \
      wgmma_rs56<(sl_ * B_SLOT + 0 * 1792) / 16, 8, !(FIRST)>(acc, (a)[0], (a)[1], (a)[2], (a)[3], blo); \
      wgmma_rs56<(sl_ * B_SLOT + 1 * 1792) / 16, 8, 1>(acc, (a)[4], (a)[5], (a)[6], (a)[7], blo); \
      wgmma_rs56<(sl_ * B_SLOT + 2 * 1792) / 16, 8, 1>(acc, (a)[8], (a)[9], (a)[10], (a)[11], blo); \
      wgmma_rs56<(sl_ * B_SLOT + 3 * 1792) / 16, 8, 1>(acc, (a)[12], (a)[13], (a)[14], (a)[15], blo); \
      wgmma_rs56<(sl_ * B_SLOT + 4 * 1792) / 16, 8, 1>(acc, (a)[16], (a)[17], (a)[18], (a)[19], blo); \
      wgmma_rs56<(sl_ * B_SLOT + 5 * 1792) / 16, 8, 1>(acc, (a)[20], (a)[21], (a)[22], (a)[23], blo); \
      wgmma_rs56<(sl_ * B_SLOT + 6 * 1792) / 16, 8, 1>(acc, (a)[24], (a)[25], (a)[26], (a)[27], blo); \
      wg_commit(); } while (0)
    auto rel = [&](int i) { release((28 + i) % B_NSLOT); };
    auto tg = [&](uint32_t v) { return (v & 0xFFFEFFFFu) | tag; };
    auto send = [&](float (&acc)[28], int cc) {
      reg_fence(acc);
      const uint32_t a = out_addr(cc, wg) + wq * 1792;
#pragma unroll
      for (int q = 0; q < 3; q++)
        sts128(a + q * 512 + lane * 16, pack_bf16(acc[8 * q], acc[8 * q + 1]), pack_bf16(acc[8 * q + 2], acc[8 * q + 3]),
               pack_bf16(acc[8 * q + 4], acc[8 * q + 5]), tg(pack_bf16(acc[8 * q + 6], acc[8 * q + 7])));
      sts64(a + 1536 + lane * 8, pack_bf16(acc[24], acc[25]), tg(pack_bf16(acc[26], acc[27])));
      asm volatile("fence.proxy.async.shared::cta;" ::: "memory");
      mbar_arrive(bar_out + 8 * (cc * 2 + wg));
    };
    auto load_hh = [&](uint32_t (&d)[28], int q) {
      mbar_wait(bar_hh + 8 * (2 * q + wg), 0);
      const uint32_t a = sb + a_slot(2 * q + wg, cg) + t128 * 16;
#pragma unroll
      for (int i = 0; i < 7; i++) {
        const uint4 v = lds128(a + i * 2048);
        d[4 * i] = v.x; d[4 * i + 1] = v.y; d[4 * i + 2] = v.z; d[4 * i + 3] = v.w;
      }
    };
    ISSUE(accA, 0, hh, true);
    mbar_wait(bar_afree + 8, 0);
    send_hh(1);
    ISSUE(accA, 1, hh + 28, false);
    load_hh(ph0, 0);
    wg_wait<1>(); rel(0);
    ISSUE(accA, 2, ph0, false);      wg_wait<1>(); rel(1);
    ISSUE(accB, 3, hh, true);        wg_wait<1>(); rel(2);
    ISSUE(accB, 4, hh + 28, false);  wg_wait<1>(); rel(3);
    ISSUE(accB, 5, ph0, false);
    if (tid == 0) TR(1, 11);
    load_hh(ph1, 1);
    wg_wait<1>(); rel(4);
    ISSUE(accA, 6, ph1, false);      wg_wait<1>(); rel(5);
    ISSUE(accB, 7, ph1, false);      wg_wait<1>(); rel(6); send(accA, 0);
    ISSUE(accA, 8, hh, true);        wg_wait<1>(); rel(7); send(accB, 1);
    if (tid == 0) TR(1, 13);
    ISSUE(accA, 9, hh + 28, false);  wg_wait<1>(); rel(8);
    ISSUE(accA, 10, ph0, false);
    ISSUE(accA, 11, ph1, false);
    const int row = rt * 128 + wg * 64 + wq * 16 + g;
    uint32_t r20, r21;
    asm volatile("ld.relaxed.gpu.global.u32 %0, [%1];" : "=r"(r20) : "l"(g_stat2 + row) : "memory");
    asm volatile("ld.relaxed.gpu.global.u32 %0, [%1];" : "=r"(r21) : "l"(g_stat2 + row + 8) : "memory");
    ISSUE(accB, 12, hh, true);
    wg_wait<1>();
    {
      reg_fence(accA);
      uint4* pd = g_part + (size_t)(blockIdx.x * 3 + 2) * 896 + warp * 112 + lane;
#pragma unroll
      for (int q = 0; q < 3; q++)
        st128(pd + q * 32, pack_bf16(accA[8 * q], accA[8 * q + 1]), pack_bf16(accA[8 * q + 2], accA[8 * q + 3]),
              pack_bf16(accA[8 * q + 4], accA[8 * q + 5]), tg(pack_bf16(accA[8 * q + 6], accA[8 * q + 7])));
      asm volatile("{\n.reg .b64 v;\nmov.b64 v, {%1, %2};\nst.relaxed.gpu.global.b64 [%0], v;\n}"
                   ::"l"((uint2*)(pd + 96) - lane), "r"(pack_bf16(accA[24], accA[25])), "r"(tg(pack_bf16(accA[26], accA[27]))) : "memory");
    }
    if (tid == 0) TR(1, 16);
    ISSUE(accB, 13, hh + 28, false);
    ISSUE(accB, 14, ph0, false);
    uint32_t in0[14], in1[14], in2[14];
    in_load(in0, in_src(0, warp) + lane);
    in_load(in1, in_src(1, warp) + lane);
    ISSUE(accB, 15, ph1, false);
    if (tid == 0) TR(1, 7);
    {
      int it = 0;
      while ((((r20 ^ ep) | (r21 ^ ep)) & 1u) && ++it < 400000) {
        asm volatile("ld.relaxed.gpu.global.u32 %0, [%1];" : "=r"(r20) : "l"(g_stat2 + row) : "memory");
        asm volatile("ld.relaxed.gpu.global.u32 %0, [%1];" : "=r"(r21) : "l"(g_stat2 + row + 8) : "memory");
      }
    }
    wg_wait<1>();
    in_load(in2, in_src(2, warp) + lane);
    in_check(in0, 0, warp); in_check(in1, 1, warp);
#pragma unroll
    for (int i = 0; i < 14; i++) { accA[2 * i] = bf_lo(in0[i]) + bf_lo(in1[i]); accA[2 * i + 1] = bf_hi(in0[i]) + bf_hi(in1[i]); }
    if (tid == 0) TR(1, 12);
    wg_wait<0>();
    reg_fence(accB);
    uint32_t hres[16];
#pragma unroll
    for (int i = 0; i < 4; i++) {
      int qq = lane >> 3, r = lane & 7, kg = 7 * cg + 2 * i + (qq >> 1), c = 2 * wq + (qq & 1);
      if (kg > 55) kg = 55;
      asm volatile("ldmatrix.sync.aligned.m8n8.x4.trans.shared.b16 {%0,%1,%2,%3}, [%4];"
                   : "=r"(hres[4 * i]), "=r"(hres[4 * i + 1]), "=r"(hres[4 * i + 2]), "=r"(hres[4 * i + 3])
                   : "r"(sb + B_SA + kg * 2048 + wg * 1024 + r * 128 + ((c ^ r) << 4)) : "memory");
    }
#pragma unroll
    for (int i = 0; i < 28; i++) accB[i] += accA[i];
    if (tid == 0) TR(1, 9);
    in_check(in2, 2, warp);
#pragma unroll
    for (int i = 0; i < 14; i++) { accB[2 * i] += bf_lo(in2[i]); accB[2 * i + 1] += bf_hi(in2[i]); }
    uint32_t* o0 = (uint32_t*)(out + (size_t)row * DM + 56 * cg + 2 * t);
    uint32_t* o1 = o0 + 8 * DM / 2;
#pragma unroll
    for (int i = 0; i < 7; i++) {
      o0[4 * i] = hadd2_bf(hres[2 * i], pack_bf16(accB[4 * i] * __uint_as_float(r20), accB[4 * i + 1] * __uint_as_float(r20)));
      o1[4 * i] = hadd2_bf(hres[2 * i + 1], pack_bf16(accB[4 * i + 2] * __uint_as_float(r21), accB[4 * i + 3] * __uint_as_float(r21)));
    }
    if (tid == 0) TR(1, 10);
    if (tid == 128) TR(1, 15);
  }
}

extern "C" void kernel_launch(void* const* d_in, const int* in_sizes, int n_in, void* d_out, int out_size) {
  const __nv_bfloat16* x = (const __nv_bfloat16*)d_in[0];
  const __nv_bfloat16 *are = (const __nv_bfloat16*)d_in[1], *aim = (const __nv_bfloat16*)d_in[2], *bre = (const __nv_bfloat16*)d_in[3],
                      *bim = (const __nv_bfloat16*)d_in[4], *cre = (const __nv_bfloat16*)d_in[5], *cim = (const __nv_bfloat16*)d_in[6],
                      *logdt = (const __nv_bfloat16*)d_in[7], *dskip = (const __nv_bfloat16*)d_in[8];
  const __nv_bfloat16 *wg = (const __nv_bfloat16*)d_in[10], *wu = (const __nv_bfloat16*)d_in[11], *wd = (const __nv_bfloat16*)d_in[12];

  static bool init = false;
  if (!init) {
    init = true;
    cudaFuncSetAttribute(k_ffn, cudaFuncAttributeMaxDynamicSharedMemorySize, B_SMEM);
    cudaFuncSetAttribute(k_front, cudaFuncAttributeMaxDynamicSharedMemorySize, A_SMEM);
  }
  cudaStream_t st = cudaStreamPerThread;
  k_front<<<128, 512, A_SMEM, st>>>(
      x, (const uint32_t*)are, (const uint32_t*)aim, (const uint32_t*)bre, (const uint32_t*)bim, (const uint32_t*)cre, (const uint32_t*)cim,
      (const unsigned short*)logdt, (const unsigned short*)dskip, (const uint4*)wg, (const uint4*)wu, (const uint4*)wd);
  cudaLaunchConfig_t cfg = {};
  cfg.gridDim = dim3(128); cfg.blockDim = dim3(384); cfg.dynamicSmemBytes = B_SMEM; cfg.stream = st;
  cudaLaunchAttribute at[1];
  at[0].id = cudaLaunchAttributeProgrammaticStreamSerialization; at[0].val.programmaticStreamSerializationAllowed = 1;
  cfg.attrs = at; cfg.numAttrs = 1;
  cudaLaunchKernelEx(&cfg, k_ffn, (__nv_bfloat16*)d_out);
}
```

```cpp
#include <cuda_runtime.h>
#include <cuda_bf16.h>
#include <cuda_fp16.h>
#include <cuda.h>
#include <stdint.h>

constexpr int LSEQ = 2048, DM = 448;

__device__ uint4    g_himg[16 * 114688 / 16];
__device__ uint4    g_cimg[8 * 2 * 224];
__device__ uint32_t g_stat2[LSEQ];
__device__ uint4    g_part[128 * 3 * 896];
__device__ uint4    g_wimg[8 * 602112 / 16];
__device__ uint4    g_ux[DM * 128 * 4];
__device__ unsigned g_cnt1;

#define TR(k, i) do {} while (0)
__device__ __forceinline__ uint32_t s2u(const void* p) { return (uint32_t)__cvta_generic_to_shared(p); }
__device__ __forceinline__ void mbar_init(uint32_t b, int c) { asm volatile("mbarrier.init.shared::cta.b64 [%0], %1;" ::"r"(b), "r"(c)); }
__device__ __forceinline__ void mbar_expect(uint32_t b, int bytes) { asm volatile("mbarrier.arrive.expect_tx.shared::cta.b64 _, [%0], %1;" ::"r"(b), "r"(bytes) : "memory"); }
__device__ __forceinline__ void mbar_arrive(uint32_t b) { asm volatile("mbarrier.arrive.shared::cta.b64 _, [%0];" ::"r"(b) : "memory"); }
__device__ __forceinline__ void mbar_wait(uint32_t b, int ph) {
  asm volatile("{\n.reg .pred p;\n.reg .b32 n;\nmov.b32 n, 0;\nLW:\nmbarrier.try_wait.parity.shared::cta.b64 p, [%0], %1;\n@p bra LD;\n"
               "add.u32 n, n, 1;\nsetp.lt.u32 p, n, 4000000;\n@p bra LW;\ntrap;\nLD:\n}" ::"r"(b), "r"(ph) : "memory");
}
__device__ __forceinline__ bool mbar_test(uint32_t b, int ph) {
  uint32_t ok;
  asm volatile("{\n.reg .pred p;\nmbarrier.test_wait.parity.shared::cta.b64 p, [%1], %2;\nselp.u32 %0, 1, 0, p;\n}" : "=r"(ok) : "r"(b), "r"(ph) : "memory");
  return ok;
}
__device__ __forceinline__ void wg_fence() { asm volatile("wgmma.fence.sync.aligned;" ::: "memory"); }
__device__ __forceinline__ void wg_commit() { asm volatile("wgmma.commit_group.sync.aligned;" ::: "memory"); }
template <int N> __device__ __forceinline__ void wg_wait() { asm volatile("wgmma.wait_group.sync.aligned %0;" ::"n"(N) : "memory"); }
template <int N> __device__ __forceinline__ void reg_fence(float (&a)[N]) {
#pragma unroll
  for (int i = 0; i < N; i++) asm volatile("" : "+f"(a[i])::"memory");
}
__device__ __forceinline__ uint32_t pack_bf16(float lo, float hi) {
  uint32_t r; asm("cvt.rn.bf16x2.f32 %0, %1, %2;" : "=r"(r) : "f"(hi), "f"(lo)); return r;
}
__device__ __forceinline__ float bf_lo(uint32_t v) { return __uint_as_float(v << 16); }
__device__ __forceinline__ float bf_hi(uint32_t v) { return __uint_as_float(v & 0xFFFF0000u); }
__device__ __forceinline__ float rbf(float x) { return __bfloat162float(__float2bfloat16_rn(x)); }
__device__ __forceinline__ uint32_t hmul2_bf(uint32_t a, uint32_t b) { uint32_t r; asm("mul.rn.bf16x2 %0, %1, %2;" : "=r"(r) : "r"(a), "r"(b)); return r; }
__device__ __forceinline__ uint32_t hadd2_bf(uint32_t a, uint32_t b) { uint32_t r; asm("add.rn.bf16x2 %0, %1, %2;" : "=r"(r) : "r"(a), "r"(b)); return r; }
__device__ __forceinline__ void bulk_ld(uint32_t dst, const void* src, int bytes, uint32_t bar) {
  asm volatile("cp.async.bulk.shared::cluster.global.mbarrier::complete_tx::bytes [%0], [%1], %2, [%3];"
               ::"r"(dst), "l"(src), "r"(bytes), "r"(bar) : "memory");
}

template <int BYTES>
__device__ __forceinline__ void bulk_ld_elect(uint32_t dst, const void* src, uint32_t bar) {
  asm volatile("{\n.reg .pred p;\nelect.sync _|p, 0xffffffff;\n"
               "@p mbarrier.arrive.expect_tx.shared::cta.b64 _, [%2], %3;\n"
               "@p cp.async.bulk.shared::cluster.global.mbarrier::complete_tx::bytes [%0], [%1], %3, [%2];\n}"
               ::"r"(dst), "l"(src), "r"(bar), "n"(BYTES) : "memory");
}
template <int BYTES>
__device__ __forceinline__ void bulk_ld_mc_elect(uint32_t dst, const void* src, uint32_t bar) {
  asm volatile("{\n.reg .pred p;\nelect.sync _|p, 0xffffffff;\n"
               "@p mbarrier.arrive.expect_tx.shared::cta.b64 _, [%2], %3;\n"
               "@p cp.async.bulk.shared::cluster.global.mbarrier::complete_tx::bytes.multicast::cluster [%0], [%1], %4, [%2], %5;\n}"
               ::"r"(dst), "l"(src), "r"(bar), "n"(2 * BYTES), "n"(BYTES), "h"((uint16_t)3) : "memory");
}
template <int AOFF, uint32_t AHI, int BOFF, uint32_t BHI, int ACC>
__device__ __forceinline__ void wgmma_ss224(float (&d)[112], uint32_t alo, uint32_t blo) {
  asm volatile("{\n.reg .pred p;\n.reg .b64 ad, bd;\nsetp.ne.b32 p, %118, 0;\n"
    "mov.b64 ad, {%112, %115};\nadd.s64 ad, ad, %114;\nmov.b64 bd, {%113, %117};\nadd.s64 bd, bd, %116;\n"
    "wgmma.mma_async.sync.aligned.m64n224k16.f32.bf16.bf16 {%0,%1,%2,%3,%4,%5,%6,%7,%8,%9,%10,%11,%12,%13,%14,%15,%16,%17,%18,%19,%20,%21,%22,%23,%24,%25,%26,%27,%28,%29,%30,%31,%32,%33,%34,%35,%36,%37,%38,%39,%40,%41,%42,%43,%44,%45,%46,%47,%48,%49,%50,%51,%52,%53,%54,%55,%56,%57,%58,%59,%60,%61,%62,%63,%64,%65,%66,%67,%68,%69,%70,%71,%72,%73,%74,%75,%76,%77,%78,%79,%80,%81,%82,%83,%84,%85,%86,%87,%88,%89,%90,%91,%92,%93,%94,%95,%96,%97,%98,%99,%100,%101,%102,%103,%104,%105,%106,%107,%108,%109,%110,%111}, ad, bd, p, 1, 1, 1, 1;\n}\n"
    : "+f"(d[0]),"+f"(d[1]),"+f"(d[2]),"+f"(d[3]),"+f"(d[4]),"+f"(d[5]),"+f"(d[6]),"+f"(d[7]),"+f"(d[8]),"+f"(d[9]),"+f"(d[10]),"+f"(d[11]),"+f"(d[12]),"+f"(d[13]),"+f"(d[14]),"+f"(d[15]),"+f"(d[16]),"+f"(d[17]),"+f"(d[18]),"+f"(d[19]),"+f"(d[20]),"+f"(d[21]),"+f"(d[22]),"+f"(d[23]),"+f"(d[24]),"+f"(d[25]),"+f"(d[26]),"+f"(d[27]),"+f"(d[28]),"+f"(d[29]),"+f"(d[30]),"+f"(d[31]),"+f"(d[32]),"+f"(d[33]),"+f"(d[34]),"+f"(d[35]),"+f"(d[36]),"+f"(d[37]),"+f"(d[38]),"+f"(d[39]),"+f"(d[40]),"+f"(d[41]),"+f"(d[42]),"+f"(d[43]),"+f"(d[44]),"+f"(d[45]),"+f"(d[46]),"+f"(d[47]),"+f"(d[48]),"+f"(d[49]),"+f"(d[50]),"+f"(d[51]),"+f"(d[52]),"+f"(d[53]),"+f"(d[54]),"+f"(d[55]),"+f"(d[56]),"+f"(d[57]),"+f"(d[58]),"+f"(d[59]),"+f"(d[60]),"+f"(d[61]),"+f"(d[62]),"+f"(d[63]),"+f"(d[64]),"+f"(d[65]),"+f"(d[66]),"+f"(d[67]),"+f"(d[68]),"+f"(d[69]),"+f"(d[70]),"+f"(d[71]),"+f"(d[72]),"+f"(d[73]),"+f"(d[74]),"+f"(d[75]),"+f"(d[76]),"+f"(d[77]),"+f"(d[78]),"+f"(d[79]),"+f"(d[80]),"+f"(d[81]),"+f"(d[82]),"+f"(d[83]),"+f"(d[84]),"+f"(d[85]),"+f"(d[86]),"+f"(d[87]),"+f"(d[88]),"+f"(d[89]),"+f"(d[90]),"+f"(d[91]),"+f"(d[92]),"+f"(d[93]),"+f"(d[94]),"+f"(d[95]),"+f"(d[96]),"+f"(d[97]),"+f"(d[98]),"+f"(d[99]),"+f"(d[100]),"+f"(d[101]),"+f"(d[102]),"+f"(d[103]),"+f"(d[104]),"+f"(d[105]),"+f"(d[106]),"+f"(d[107]),"+f"(d[108]),"+f"(d[109]),"+f"(d[110]),"+f"(d[111])
    : "r"(alo), "r"(blo), "n"(AOFF), "n"(AHI), "n"(BOFF), "n"(BHI), "n"(ACC));
}
template <int AOFF, uint32_t AHI, int BOFF, uint32_t BHI, int ACC>
__device__ __forceinline__ void wgmma_ss232(float (&d)[116], uint32_t alo, uint32_t blo) {
  asm volatile("{\n.reg .pred p;\n.reg .b64 ad, bd;\nsetp.ne.b32 p, %122, 0;\n"
    "mov.b64 ad, {%116, %119};\nadd.s64 ad, ad, %118;\nmov.b64 bd, {%117, %121};\nadd.s64 bd, bd, %120;\n"
    "wgmma.mma_async.sync.aligned.m64n232k16.f32.bf16.bf16 {%0,%1,%2,%3,%4,%5,%6,%7,%8,%9,%10,%11,%12,%13,%14,%15,%16,%17,%18,%19,%20,%21,%22,%23,%24,%25,%26,%27,%28,%29,%30,%31,%32,%33,%34,%35,%36,%37,%38,%39,%40,%41,%42,%43,%44,%45,%46,%47,%48,%49,%50,%51,%52,%53,%54,%55,%56,%57,%58,%59,%60,%61,%62,%63,%64,%65,%66,%67,%68,%69,%70,%71,%72,%73,%74,%75,%76,%77,%78,%79,%80,%81,%82,%83,%84,%85,%86,%87,%88,%89,%90,%91,%92,%93,%94,%95,%96,%97,%98,%99,%100,%101,%102,%103,%104,%105,%106,%107,%108,%109,%110,%111,%112,%113,%114,%115}, ad, bd, p, 1, 1, 1, 1;\n}\n"
    : "+f"(d[0]),"+f"(d[1]),"+f"(d[2]),"+f"(d[3]),"+f"(d[4]),"+f"(d[5]),"+f"(d[6]),"+f"(d[7]),"+f"(d[8]),"+f"(d[9]),"+f"(d[10]),"+f"(d[11]),"+f"(d[12]),"+f"(d[13]),"+f"(d[14]),"+f"(d[15]),"+f"(d[16]),"+f"(d[17]),"+f"(d[18]),"+f"(d[19]),"+f"(d[20]),"+f"(d[21]),"+f"(d[22]),"+f"(d[23]),"+f"(d[24]),"+f"(d[25]),"+f"(d[26]),"+f"(d[27]),"+f"(d[28]),"+f"(d[29]),"+f"(d[30]),"+f"(d[31]),"+f"(d[32]),"+f"(d[33]),"+f"(d[34]),"+f"(d[35]),"+f"(d[36]),"+f"(d[37]),"+f"(d[38]),"+f"(d[39]),"+f"(d[40]),"+f"(d[41]),"+f"(d[42]),"+f"(d[43]),"+f"(d[44]),"+f"(d[45]),"+f"(d[46]),"+f"(d[47]),"+f"(d[48]),"+f"(d[49]),"+f"(d[50]),"+f"(d[51]),"+f"(d[52]),"+f"(d[53]),"+f"(d[54]),"+f"(d[55]),"+f"(d[56]),"+f"(d[57]),"+f"(d[58]),"+f"(d[59]),"+f"(d[60]),"+f"(d[61]),"+f"(d[62]),"+f"(d[63]),"+f"(d[64]),"+f"(d[65]),"+f"(d[66]),"+f"(d[67]),"+f"(d[68]),"+f"(d[69]),"+f"(d[70]),"+f"(d[71]),"+f"(d[72]),"+f"(d[73]),"+f"(d[74]),"+f"(d[75]),"+f"(d[76]),"+f"(d[77]),"+f"(d[78]),"+f"(d[79]),"+f"(d[80]),"+f"(d[81]),"+f"(d[82]),"+f"(d[83]),"+f"(d[84]),"+f"(d[85]),"+f"(d[86]),"+f"(d[87]),"+f"(d[88]),"+f"(d[89]),"+f"(d[90]),"+f"(d[91]),"+f"(d[92]),"+f"(d[93]),"+f"(d[94]),"+f"(d[95]),"+f"(d[96]),"+f"(d[97]),"+f"(d[98]),"+f"(d[99]),"+f"(d[100]),"+f"(d[101]),"+f"(d[102]),"+f"(d[103]),"+f"(d[104]),"+f"(d[105]),"+f"(d[106]),"+f"(d[107]),"+f"(d[108]),"+f"(d[109]),"+f"(d[110]),"+f"(d[111]),"+f"(d[112]),"+f"(d[113]),"+f"(d[114]),"+f"(d[115])
    : "r"(alo), "r"(blo), "n"(AOFF), "n"(AHI), "n"(BOFF), "n"(BHI), "n"(ACC));
}
template <int OFF, uint32_t BHI, int ACC>
__device__ __forceinline__ void wgmma_rs224(float (&d)[112], uint32_t a0, uint32_t a1, uint32_t a2, uint32_t a3, uint32_t blo) {
  asm volatile("{\n.reg .pred p;\n.reg .b64 bd;\nsetp.ne.b32 p, %119, 0;\nmov.b64 bd, {%116, %118};\nadd.s64 bd, bd, %117;\n"
    "wgmma.mma_async.sync.aligned.m64n224k16.f32.bf16.bf16 {%0,%1,%2,%3,%4,%5,%6,%7,%8,%9,%10,%11,%12,%13,%14,%15,%16,%17,%18,%19,%20,%21,%22,%23,%24,%25,%26,%27,%28,%29,%30,%31,%32,%33,%34,%35,%36,%37,%38,%39,%40,%41,%42,%43,%44,%45,%46,%47,%48,%49,%50,%51,%52,%53,%54,%55,%56,%57,%58,%59,%60,%61,%62,%63,%64,%65,%66,%67,%68,%69,%70,%71,%72,%73,%74,%75,%76,%77,%78,%79,%80,%81,%82,%83,%84,%85,%86,%87,%88,%89,%90,%91,%92,%93,%94,%95,%96,%97,%98,%99,%100,%101,%102,%103,%104,%105,%106,%107,%108,%109,%110,%111}, {%112,%113,%114,%115}, bd, p, 1, 1, 1;\n}\n"
    : "+f"(d[0]),"+f"(d[1]),"+f"(d[2]),"+f"(d[3]),"+f"(d[4]),"+f"(d[5]),"+f"(d[6]),"+f"(d[7]),"+f"(d[8]),"+f"(d[9]),"+f"(d[10]),"+f"(d[11]),"+f"(d[12]),"+f"(d[13]),"+f"(d[14]),"+f"(d[15]),"+f"(d[16]),"+f"(d[17]),"+f"(d[18]),"+f"(d[19]),"+f"(d[20]),"+f"(d[21]),"+f"(d[22]),"+f"(d[23]),"+f"(d[24]),"+f"(d[25]),"+f"(d[26]),"+f"(d[27]),"+f"(d[28]),"+f"(d[29]),"+f"(d[30]),"+f"(d[31]),"+f"(d[32]),"+f"(d[33]),"+f"(d[34]),"+f"(d[35]),"+f"(d[36]),"+f"(d[37]),"+f"(d[38]),"+f"(d[39]),"+f"(d[40]),"+f"(d[41]),"+f"(d[42]),"+f"(d[43]),"+f"(d[44]),"+f"(d[45]),"+f"(d[46]),"+f"(d[47]),"+f"(d[48]),"+f"(d[49]),"+f"(d[50]),"+f"(d[51]),"+f"(d[52]),"+f"(d[53]),"+f"(d[54]),"+f"(d[55]),"+f"(d[56]),"+f"(d[57]),"+f"(d[58]),"+f"(d[59]),"+f"(d[60]),"+f"(d[61]),"+f"(d[62]),"+f"(d[63]),"+f"(d[64]),"+f"(d[65]),"+f"(d[66]),"+f"(d[67]),"+f"(d[68]),"+f"(d[69]),"+f"(d[70]),"+f"(d[71]),"+f"(d[72]),"+f"(d[73]),"+f"(d[74]),"+f"(d[75]),"+f"(d[76]),"+f"(d[77]),"+f"(d[78]),"+f"(d[79]),"+f"(d[80]),"+f"(d[81]),"+f"(d[82]),"+f"(d[83]),"+f"(d[84]),"+f"(d[85]),"+f"(d[86]),"+f"(d[87]),"+f"(d[88]),"+f"(d[89]),"+f"(d[90]),"+f"(d[91]),"+f"(d[92]),"+f"(d[93]),"+f"(d[94]),"+f"(d[95]),"+f"(d[96]),"+f"(d[97]),"+f"(d[98]),"+f"(d[99]),"+f"(d[100]),"+f"(d[101]),"+f"(d[102]),"+f"(d[103]),"+f"(d[104]),"+f"(d[105]),"+f"(d[106]),"+f"(d[107]),"+f"(d[108]),"+f"(d[109]),"+f"(d[110]),"+f"(d[111])
    : "r"(a0), "r"(a1), "r"(a2), "r"(a3), "r"(blo), "n"(OFF), "n"(BHI), "n"(ACC));
}
template <int OFF, uint32_t BHI, int ACC>
__device__ __forceinline__ void wgmma_rs56(float (&d)[28], uint32_t a0, uint32_t a1, uint32_t a2, uint32_t a3, uint32_t blo) {
  asm volatile("{\n.reg .pred p;\n.reg .b64 bd;\nsetp.ne.b32 p, %35, 0;\nmov.b64 bd, {%32, %34};\nadd.s64 bd, bd, %33;\n"
    "wgmma.mma_async.sync.aligned.m64n56k16.f32.bf16.bf16 {%0,%1,%2,%3,%4,%5,%6,%7,%8,%9,%10,%11,%12,%13,%14,%15,%16,%17,%18,%19,%20,%21,%22,%23,%24,%25,%26,%27}, {%28,%29,%30,%31}, bd, p, 1, 1, 1;\n}\n"
    : "+f"(d[0]),"+f"(d[1]),"+f"(d[2]),"+f"(d[3]),"+f"(d[4]),"+f"(d[5]),"+f"(d[6]),"+f"(d[7]),"+f"(d[8]),"+f"(d[9]),"+f"(d[10]),"+f"(d[11]),"+f"(d[12]),"+f"(d[13]),"+f"(d[14]),"+f"(d[15]),"+f"(d[16]),"+f"(d[17]),"+f"(d[18]),"+f"(d[19]),"+f"(d[20]),"+f"(d[21]),"+f"(d[22]),"+f"(d[23]),"+f"(d[24]),"+f"(d[25]),"+f"(d[26]),"+f"(d[27])
    : "r"(a0), "r"(a1), "r"(a2), "r"(a3), "r"(blo), "n"(OFF), "n"(BHI), "n"(ACC));
}

__device__ __forceinline__ void st128(uint4* p, uint32_t a, uint32_t b, uint32_t c, uint32_t d) {
  asm volatile("{\n.reg .b128 v;\n.reg .b64 lo, hi;\nmov.b64 lo, {%1, %2};\nmov.b64 hi, {%3, %4};\nmov.b128 v, {lo, hi};\n"
               "st.relaxed.gpu.global.b128 [%0], v;\n}" ::"l"(p), "r"(a), "r"(b), "r"(c), "r"(d) : "memory");
}
__device__ __forceinline__ void ld128(const uint4* p, uint32_t* r) {
  asm volatile("{\n.reg .b128 v;\n.reg .b64 lo, hi;\nld.relaxed.gpu.global.b128 v, [%4];\nmov.b128 {lo, hi}, v;\n"
               "mov.b64 {%0, %1}, lo;\nmov.b64 {%2, %3}, hi;\n}" : "=r"(r[0]), "=r"(r[1]), "=r"(r[2]), "=r"(r[3]) : "l"(p) : "memory");
}

template <int OFF, uint32_t BHI, int ACC>
__device__ __forceinline__ void wgmma_rs32(float (&d)[16], uint32_t a0, uint32_t a1, uint32_t a2, uint32_t a3, uint32_t blo) {
  asm volatile("{\n.reg .pred p;\n.reg .b64 bd;\nsetp.ne.b32 p, %23, 0;\nmov.b64 bd, {%20, %22};\nadd.s64 bd, bd, %21;\n"
    "wgmma.mma_async.sync.aligned.m64n32k16.f32.bf16.bf16 {%0,%1,%2,%3,%4,%5,%6,%7,%8,%9,%10,%11,%12,%13,%14,%15}, {%16,%17,%18,%19}, bd, p, 1, 1, 0;\n}\n"
    : "+f"(d[0]),"+f"(d[1]),"+f"(d[2]),"+f"(d[3]),"+f"(d[4]),"+f"(d[5]),"+f"(d[6]),"+f"(d[7]),"+f"(d[8]),"+f"(d[9]),"+f"(d[10]),"+f"(d[11]),"+f"(d[12]),"+f"(d[13]),"+f"(d[14]),"+f"(d[15])
    : "r"(a0), "r"(a1), "r"(a2), "r"(a3), "r"(blo), "n"(OFF), "n"(BHI), "n"(ACC));
}
template <int OFF, uint32_t BHI, int ACC>
__device__ __forceinline__ void wgmma_rs24(float (&d)[12], uint32_t a0, uint32_t a1, uint32_t a2, uint32_t a3, uint32_t blo) {
  asm volatile("{\n.reg .pred p;\n.reg .b64 bd;\nsetp.ne.b32 p, %19, 0;\nmov.b64 bd, {%16, %18};\nadd.s64 bd, bd, %17;\n"
    "wgmma.mma_async.sync.aligned.m64n24k16.f32.bf16.bf16 {%0,%1,%2,%3,%4,%5,%6,%7,%8,%9,%10,%11}, {%12,%13,%14,%15}, bd, p, 1, 1, 1;\n}\n"
    : "+f"(d[0]),"+f"(d[1]),"+f"(d[2]),"+f"(d[3]),"+f"(d[4]),"+f"(d[5]),"+f"(d[6]),"+f"(d[7]),"+f"(d[8]),"+f"(d[9]),"+f"(d[10]),"+f"(d[11])
    : "r"(a0), "r"(a1), "r"(a2), "r"(a3), "r"(blo), "n"(OFF), "n"(BHI), "n"(ACC));
}
template <int OFF, uint32_t BHI, int ACC>
__device__ __forceinline__ void wgmma_rs16(float (&d)[8], uint32_t a0, uint32_t a1, uint32_t a2, uint32_t a3, uint32_t blo) {
  asm volatile("{\n.reg .pred p;\n.reg .b64 bd;\nsetp.ne.b32 p, %15, 0;\nmov.b64 bd, {%12, %14};\nadd.s64 bd, bd, %13;\n"
    "wgmma.mma_async.sync.aligned.m64n16k16.f32.bf16.bf16 {%0,%1,%2,%3,%4,%5,%6,%7}, {%8,%9,%10,%11}, bd, p, 1, 1, 1;\n}\n"
    : "+f"(d[0]),"+f"(d[1]),"+f"(d[2]),"+f"(d[3]),"+f"(d[4]),"+f"(d[5]),"+f"(d[6]),"+f"(d[7])
    : "r"(a0), "r"(a1), "r"(a2), "r"(a3), "r"(blo), "n"(OFF), "n"(BHI), "n"(ACC));
}

constexpr int A_R1 = 0;
constexpr int A_R2A = A_R1 + 2624, A_R2B = A_R2A + 768, A_R3A = A_R2B + 768, A_R3B = A_R3A + 528;
constexpr int A_K1024 = A_R3B + 528;
constexpr int A_W5 = A_K1024 + 16;
constexpr int A_W3 = A_W5 + 4096;
constexpr int A_W9 = A_W3 + 4112;
constexpr int A_W7 = A_W9 + 2080;
constexpr int A_V  = A_W7 + 2080 + 32;
constexpr int A_SCL = A_V + 2048;
constexpr int A_UB = A_SCL + 16;
constexpr int A_STG = A_UB + 5248;
constexpr int A_Y2 = A_STG, A_Y3 = A_Y2 + 6528, A_YB = A_Y3 + 4352;
constexpr int A_REC = A_STG + 4 * 4352;
constexpr int A_CH = A_REC + 8192;
constexpr int A_BAR = 4 * A_CH, A_WST = (A_BAR + 128 + 127) / 128 * 128;
static_assert(A_W5 % 16 == 0 && A_UB % 16 == 0 && A_CH % 16 == 0 && A_YB + 4096 <= A_REC, "layout");

struct cf { float x, y; };
__device__ __forceinline__ cf cmul(cf a, cf b) { cf r; r.x = fmaf(a.x, b.x, -a.y * b.y); r.y = fmaf(a.x, b.y, a.y * b.x); return r; }
__device__ __forceinline__ cf cexp_l(float lr, float li, float l) {
  float mag; asm("ex2.approx.ftz.f32 %0, %1;" : "=f"(mag) : "f"((lr * l) * 1.4426950408889634f));
  const float th = li * l;
  const float k = (fmaf(th, 0.15915494f, 12582912.f)) - 12582912.f;
  float ph = fmaf(th, 0.15915494f, -k);
  ph = fmaf(th, 6.4206383e-9f, ph) * 6.2831853f;
  cf r; r.x = mag * __cosf(ph); r.y = mag * __sinf(ph); return r;
}
__device__ __forceinline__ void sts16(uint32_t a, uint32_t v) { asm volatile("st.shared.u16 [%0], %1;" ::"r"(a), "h"((uint16_t)v) : "memory"); }
__device__ __forceinline__ void sts32(uint32_t a, uint32_t v) { asm volatile("st.shared.u32 [%0], %1;" ::"r"(a), "r"(v) : "memory"); }
__device__ __forceinline__ void sts64(uint32_t a, uint32_t v0, uint32_t v1) { asm volatile("st.shared.v2.u32 [%0], {%1, %2};" ::"r"(a), "r"(v0), "r"(v1) : "memory"); }
__device__ __forceinline__ void sts128(uint32_t a, uint32_t v0, uint32_t v1, uint32_t v2, uint32_t v3) {
  asm volatile("st.shared.v4.u32 [%0], {%1, %2, %3, %4};" ::"r"(a), "r"(v0), "r"(v1), "r"(v2), "r"(v3) : "memory");
}
__device__ __forceinline__ uint32_t lds32(uint32_t a) { uint32_t v; asm volatile("ld.shared.u32 %0, [%1];" : "=r"(v) : "r"(a) : "memory"); return v; }
__device__ __forceinline__ uint4 lds128(uint32_t a) {
  uint4 v; asm volatile("ld.shared.v4.u32 {%0, %1, %2, %3}, [%4];" : "=r"(v.x), "=r"(v.y), "=r"(v.z), "=r"(v.w) : "r"(a) : "memory"); return v;
}
__device__ __forceinline__ void ldsm4(uint32_t* r, uint32_t a) {
  asm volatile("ldmatrix.sync.aligned.m8n8.x4.shared.b16 {%0,%1,%2,%3}, [%4];" : "=r"(r[0]), "=r"(r[1]), "=r"(r[2]), "=r"(r[3]) : "r"(a) : "memory");
}
__device__ __forceinline__ void mma16816(float* d, uint32_t a0, uint32_t a1, uint32_t a2, uint32_t a3, uint32_t b0, uint32_t b1) {
  asm volatile("mma.sync.aligned.m16n8k16.row.col.f32.f16.f16.f32 {%0,%1,%2,%3}, {%4,%5,%6,%7}, {%8,%9}, {%0,%1,%2,%3};"
               : "+f"(d[0]), "+f"(d[1]), "+f"(d[2]), "+f"(d[3]) : "r"(a0), "r"(a1), "r"(a2), "r"(a3), "r"(b0), "r"(b1));
}
__device__ __forceinline__ uint32_t pack_h(float lo, float hi) { uint32_t r; asm("cvt.rn.f16x2.f32 %0, %1, %2;" : "=r"(r) : "f"(hi), "f"(lo)); return r; }
__device__ __forceinline__ uint32_t pack_h(cf v) { return pack_h(v.x, v.y); }
__device__ __forceinline__ uint32_t hcmul(uint32_t x, uint32_t r0, uint32_t r1) {
  const __half2 hx = *(__half2*)&x;
  const __half2 y = __hfma2(__high2half2(hx), *(__half2*)&r1, __hmul2(__low2half2(hx), *(__half2*)&r0));
  return *(const uint32_t*)&y;
}
__device__ __forceinline__ float ln_rstd(float var) {
  float sd, rs;
  asm("sqrt.approx.f32 %0, %1;" : "=f"(sd) : "f"(rbf(rbf(var) + 1e-5f)));
  asm("rcp.approx.f32 %0, %1;" : "=f"(rs) : "f"(rbf(sd)));
  return rs;
}
__device__ __forceinline__ uint32_t hsub2_bf(uint32_t a, uint32_t b) { uint32_t r; asm("sub.rn.bf16x2 %0, %1, %2;" : "=r"(r) : "r"(a), "r"(b)); return r; }
__device__ __forceinline__ void bar_sync(int id, int n) { asm volatile("bar.sync %0, %1;" ::"r"(id), "r"(n) : "memory"); }

template <int S> struct F1B { static constexpr int c = S / 4 + ((S & 3) == 3 ? 0 : 0), cc = (16 * S) / 64, ks = (64 * cc - (16 * S - 48)) / 16, off = (A_UB + 2 * ks * 656 + (9 - cc) * 16) / 16; };

template <int NS>
__device__ __forceinline__ void load_quads(uint32_t* q, uint32_t addr) {
#pragma unroll
  for (int i = 0; i < NS; i++) {
    q[4 * i] = lds32(addr + i * 64); q[4 * i + 1] = lds32(addr + i * 64 + 32);
    q[4 * i + 2] = i ? q[4 * i - 3] : lds32(addr - 32);
    q[4 * i + 3] = q[4 * i];
  }
#pragma unroll
  for (int i = 0; i < 4 * NS; i++) asm volatile("" : "+r"(q[i]));
}
template <int S0, int NS>
__device__ __forceinline__ void f1_steps(float (&acc)[16], const uint32_t* a, uint32_t blo) {
  if constexpr (NS > 0) {
    wgmma_rs32<F1B<S0>::off, 8, S0 != 0>(acc, a[0], a[1], a[2], a[3], blo);
    f1_steps<S0 + 1, NS - 1>(acc, a + 4, blo);
  }
}
template <int S0, int NS, int BASE, int FIRST>
__device__ __forceinline__ void s2_steps(float (&acc)[12], const uint32_t* a, uint32_t blo) {
  if constexpr (NS > 0) {
    wgmma_rs24<BASE / 16 + (112 - 16 * S0), 64, !(FIRST && S0 == 0)>(acc, a[0], a[1], a[2], a[3], blo);
    s2_steps<S0 + 1, NS - 1, BASE, FIRST>(acc, a + 4, blo);
  }
}
template <int S0, int NS, int BASE, int FIRST>
__device__ __forceinline__ void s3_steps(float (&acc)[8], const uint32_t* a, uint32_t blo) {
  if constexpr (NS > 0) {
    wgmma_rs16<BASE / 16 + (48 - 16 * S0), 65, !(FIRST && S0 == 0)>(acc, a[0], a[1], a[2], a[3], blo);
    s3_steps<S0 + 1, NS - 1, BASE, FIRST>(acc, a + 4, blo);
  }
}

__device__ __forceinline__ void tma3d(uint32_t dst, const CUtensorMap* m, int c1, int c2, uint32_t bar) {
  asm volatile("cp.async.bulk.tensor.3d.shared::cluster.global.mbarrier::complete_tx::bytes [%0], [%1, {0, %3, %4}], [%2];"
               ::"r"(dst), "l"(m), "r"(bar), "r"(c1), "r"(c2) : "memory");
}
__device__ __forceinline__ void bulk_st(void* dst, uint32_t src, int bytes) {
  asm volatile("cp.async.bulk.global.shared::cta.bulk_group [%0], [%1], %2;" ::"l"(dst), "r"(src), "r"(bytes) : "memory");
}

__device__ __forceinline__ void phase_a(
        unsigned char* sm, const uint32_t bar_rec, const uint32_t ep_addr, const CUtensorMap* mg, const CUtensorMap* mu, const CUtensorMap* md,
        const __nv_bfloat16* __restrict__ x, const uint32_t* __restrict__ are, const uint32_t* __restrict__ aim,
        const uint32_t* __restrict__ bre, const uint32_t* __restrict__ bim, const uint32_t* __restrict__ cre,
        const uint32_t* __restrict__ cim, const unsigned short* __restrict__ logdt, const unsigned short* __restrict__ dskip,
        const uint4* __restrict__ wgate, const uint4* __restrict__ wup) {
  const uint32_t sb = s2u(sm), bar_w = bar_rec + 16;
  const int tid = threadIdx.x, warp = __shfl_sync(~0u, tid >> 5, 0), wg = warp >> 2, lane = tid & 31, wq = warp & 3, t128 = tid & 127;
  const int blk = blockIdx.x;
  const bool conv = (blk & 7) != 7;
  const int cblk = blk - (blk >> 3);

  uint2 xr[4];
  {
    const uint2* p = (const uint2*)(x + (size_t)(blk * 16 + warp) * DM);
    xr[0] = __ldg(p + lane); xr[1] = __ldg(p + 32 + lane); xr[2] = __ldg(p + 64 + lane);
    xr[3] = lane < 16 ? __ldg(p + 96 + lane) : make_uint2(0, 0);
  }
  const int ch = conv ? cblk * 4 + wg : 0;
  const uint32_t cb = sb + wg * A_CH;
  uint32_t prm[6];
  {
    const int i = ch * 128 + t128;
    prm[0] = __ldg(are + i); prm[1] = __ldg(aim + i); prm[2] = __ldg(bre + i); prm[3] = __ldg(bim + i); prm[4] = __ldg(cre + i); prm[5] = __ldg(cim + i);
  }
  const uint32_t ldt = __ldg(logdt + ch);
  uint32_t cnt0 = 0;
  if (tid == 0) cnt0 = __ldcg(&g_cnt1);
  const int g = lane >> 2, t = lane & 3;
#pragma unroll
  for (int i = 0; i < 4; i++) if (i < 3 || t128 < (A_W5 + 1024) / 16 - 384) sts128(cb + (i * 128 + t128) * 16, 0, 0, 0, 0);
  if (t128 < 64) sts128(cb + A_W3 + t128 * 16, 0, 0, 0, 0);
  if (t128 < 72) sts128(cb + A_UB + (t128 / 9) * 656 + (t128 % 9) * 16, 0, 0, 0, 0);
  {
    float s = 0.f, q = 0.f;
#pragma unroll
    for (int i = 0; i < 4; i++) {
      const float a = bf_lo(xr[i].x), b = bf_hi(xr[i].x), c = bf_lo(xr[i].y), d = bf_hi(xr[i].y);
      s += (a + b) + (c + d);
      q = fmaf(a, a, q); q = fmaf(b, b, q); q = fmaf(c, c, q); q = fmaf(d, d, q);
    }
#pragma unroll
    for (int o = 16; o; o >>= 1) { s += __shfl_xor_sync(~0u, s, o); q += __shfl_xor_sync(~0u, q, o); }
    const float mean = s * (1.f / DM);
    const float var = fmaxf(fmaf(-mean, mean, q * (1.f / DM)), 0.f);
    const float rs = ln_rstd(var);
    const uint32_t mm = pack_bf16(mean, mean);
    const uint32_t tu = sb + A_REC + (warp >> 3) * A_CH + (warp & 7) * 912 + lane * 8, tx = tu + 2 * A_CH;
#pragma unroll
    for (int i = 0; i < 4; i++) {
      if (i < 3 || lane < 16) {
        const uint32_t d0 = hsub2_bf(xr[i].x, mm), d1 = hsub2_bf(xr[i].y, mm);
        sts64(tu + i * 256, pack_bf16(bf_lo(d0) * rs, bf_hi(d0) * rs), pack_bf16(bf_lo(d1) * rs, bf_hi(d1) * rs));
        sts64(tx + i * 256, xr[i].x, xr[i].y);
      }
    }
  }
  if (tid == 0) sts32(ep_addr, (cnt0 >> 7) + 1u);
  if (tid == 320) TR(0, 1);
  auto publish_rows = [&]() {
    bar_sync(5, 512);
    uint4* dst = g_ux + ((size_t)(warp * 8 + (lane >> 2)) * 128 + blk) * 4 + ((lane ^ (blk >> 1)) & 3);
#pragma unroll
    for (int i = 0; i < 4; i++) {
      if (i < 3 || warp < 8) {
        uint32_t r[4];
        asm volatile("ldmatrix.sync.aligned.m8n8.x4.trans.shared.b16 {%0,%1,%2,%3}, [%4];" : "=r"(r[0]), "=r"(r[1]), "=r"(r[2]), "=r"(r[3])
                     : "r"(sb + A_REC + (lane >> 3) * A_CH + (lane & 7) * 912 + (warp + 16 * i) * 16) : "memory");
        dst[i * 65536] = make_uint4(r[0], r[1], r[2], r[3]);
      }
    }
    if (warp != 0) asm volatile("bar.arrive 6, 512;" ::: "memory");
  };
  auto release_rows = [&]() {
    if (warp == 0) {
      bar_sync(6, 512);
      if (lane == 0) { asm volatile("red.release.gpu.global.add.u32 [%0], 1;" ::"l"(&g_cnt1) : "memory"); TR(0, 8); }
      __syncwarp();
    }
  };

  if (!conv) {
    publish_rows();
    release_rows();
    const int a = blk >> 3, mat = a >> 3, j = a & 7;
    if (warp == 15) bar_sync(7, 64);
    if (warp == 0) asm volatile("bar.arrive 7, 64;" ::: "memory");
    if (tid == 480) {
      asm volatile("fence.proxy.async.shared::cta;" ::: "memory");
      for (int c = 0; c < 8; c++) { mbar_expect(bar_w + 8 * c, 12544); tma3d(sb + 65536 + c * 12544, md, a * 112, c * 7, bar_w + 8 * c); }
    }
    float s[8];
#pragma unroll
    for (int k = 0; k < 8; k++) s[k] = 0.f;
    if (lane < 28) {
      const uint4* src = (mat ? wup : wgate) + j * 28 + lane + (size_t)warp * 224;
#pragma unroll
      for (int hb = 0; hb < 2; hb++) {
        uint4 v[14];
#pragma unroll
        for (int r = 0; r < 14; r++) v[r] = __ldg(src + (size_t)(hb * 14 + r) * 16 * 224);
#pragma unroll
        for (int r = 0; r < 14; r++) {
          s[0] += bf_lo(v[r].x); s[1] += bf_hi(v[r].x); s[2] += bf_lo(v[r].y); s[3] += bf_hi(v[r].y);
          s[4] += bf_lo(v[r].z); s[5] += bf_hi(v[r].z); s[6] += bf_lo(v[r].w); s[7] += bf_hi(v[r].w);
        }
      }
      float4* red = (float4*)(sm + A_STG + warp * 896 + lane * 32);
      red[0] = make_float4(s[0], s[1], s[2], s[3]); red[1] = make_float4(s[4], s[5], s[6], s[7]);
    }
    bar_sync(5, 512);
    if (tid < 224) {
      float cs = 0.f;
#pragma unroll
      for (int w = 0; w < 16; w++) cs += *(const float*)(sm + A_STG + w * 896 + tid * 4);
      const float hi = rbf(cs), mid = rbf(cs - hi), lo = rbf(cs - hi - mid);
      const int q = tid / 112, n = tid % 112 + 112 * mat;
      __nv_bfloat16* dst = (__nv_bfloat16*)(g_cimg + (j * 2 + q) * 224 + (n >> 3) * 8) + (n & 7);
      dst[0] = __float2bfloat16_rn(hi); dst[8] = __float2bfloat16_rn(mid); dst[16] = __float2bfloat16_rn(lo);
#pragma unroll
      for (int k = 3; k < 8; k++) dst[8 * k] = __float2bfloat16_rn(0.f);
    }
    if (tid == 480) {
      for (int c = 0; c < 8; c++) {
        mbar_wait(bar_w + 8 * c, 0);
        bulk_st(g_wimg + (size_t)(a >> 1) * 37632 + 25088 + (c * 2 + (a & 1)) * 784, sb + 65536 + c * 12544, 12544);
      }
      asm volatile("cp.async.bulk.commit_group;" ::: "memory");
      asm volatile("cp.async.bulk.wait_group 0;" ::: "memory");
      TR(0, 10);
    }
    return;
  }

  const int wr = (wq + wg) & 3;
  const int bk = wr * 32 + lane;
  {
    const uint32_t stg = cb + A_STG + wq * 4352, sw = stg + lane * 8;
    const float dt = rbf(expf(__uint_as_float(ldt << 16)));
    float lr[2], li[2];
    cf bq[2], b0[2], b4[2];
    uint32_t bf[48];
#pragma unroll
    for (int m = 0; m < 2; m++) {
      lr[m] = dt * (m ? bf_hi(prm[0]) : bf_lo(prm[0]));
      li[m] = dt * (m ? bf_hi(prm[1]) : bf_lo(prm[1]));
    }
    {
      cf b[2], z[2];
#pragma unroll
      for (int m = 0; m < 2; m++) {
        cf db, c;
        db.x = dt * (m ? bf_hi(prm[2]) : bf_lo(prm[2])); db.y = -dt * (m ? bf_hi(prm[3]) : bf_lo(prm[3]));
        c.x = m ? bf_hi(prm[4]) : bf_lo(prm[4]); c.y = -(m ? bf_hi(prm[5]) : bf_lo(prm[5]));
        b[m] = cmul(c, db);
        z[m] = cexp_l(lr[m], -li[m], 1.f);
        bq[m] = cexp_l(lr[m], -li[m], 256.f);
      }
      publish_rows();
      if (t128 == 96) {
        mbar_expect(bar_w + 8 * wg, 7168);
        tma3d(sb + A_WST + wg * 7168, (ch & 1) ? mu : mg, ((ch >> 1) % 14) * 32, ((ch >> 1) / 14) * 14, bar_w + 8 * wg);
      }
      {
        const float mx = fmaxf(fmaxf(fabsf(b[0].x), fabsf(b[0].y)), fmaxf(fabsf(b[1].x), fabsf(b[1].y)));
        const uint32_t e = max(__reduce_max_sync(~0u, __float_as_uint(mx)) >> 23, 14u);
        const float sc = __uint_as_float((267u - e) << 23);
        b[0].x *= sc; b[0].y *= sc; b[1].x *= sc; b[1].y *= sc;
        if (lane == 0) sts32(cb + A_SCL + wq * 4, (e - 13u) << 23);
      }
#pragma unroll
      for (int i = 0; i < 8; i++) {
        sts64(sw + i * 272, pack_h(b[0]), pack_h(b[1]));
        if (!(i & 1)) {
          cf e0 = cmul(b[0], bq[0]), e1 = cmul(b[1], bq[1]);
          sts64(sw + (8 + i / 2) * 272, pack_h(e0), pack_h(e1));
          if (i == 0) { b0[0] = e0; b0[1] = e1; }
          if (i == 4) { b4[0] = e0; b4[1] = e1; }
        }
        if (i < 7) { b[0] = cmul(b[0], z[0]); b[1] = cmul(b[1], z[1]); }
        if (i == 5) release_rows();
      }
#pragma unroll
      for (int i = 0; i < 7; i++) {
        b0[0] = cmul(b0[0], bq[0]); b0[1] = cmul(b0[1], bq[1]);
        sts64(sw + (i < 2 ? 12 + 2 * i : i - 2) * 272, pack_h(b0[0]), pack_h(b0[1]));
        if (i < 2) {
          b4[0] = cmul(b4[0], bq[0]); b4[1] = cmul(b4[1], bq[1]);
          sts64(sw + (13 + 2 * i) * 272, pack_h(b4[0]), pack_h(b4[1]));
        }
        if (i == 1) {
          __syncwarp();
#pragma unroll
          for (int n = 0; n < 2; n++)
#pragma unroll
            for (int k2 = 0; k2 < 4; k2++) ldsm4(bf + n * 16 + k2 * 4, stg + (n * 8 + (lane & 7)) * 272 + k2 * 64 + (lane >> 3) * 16);
          __syncwarp();
        }
      }
    }
    uint32_t cv = 0;
    if (tid == 160) asm volatile("ld.relaxed.gpu.global.u32 %0, [%1];" : "=r"(cv) : "l"(&g_cnt1) : "memory");
    {
      const cf p0 = cexp_l(lr[0], li[0], 8.f), p1 = cexp_l(lr[1], li[1], 8.f);
      cf v0 = p0, v1 = p1;
      sts64(sw + 8 * 272, 0x3C00u, 0x3C00u);
#pragma unroll
      for (int i = 1; i < 8; i++) {
        sts64(sw + (8 + i) * 272, pack_h(v0), pack_h(v1));
        v0 = cmul(v0, p0); v1 = cmul(v1, p1);
      }
      const uint32_t ra = stg + 5 * 272 + (lane >> 2) * 64 + (lane & 1) * 32 + (lane & 2) * 4;
      sts64(ra, pack_h(v0), pack_h(-v0.y, v0.x));
      sts64(ra + 16, pack_h(v1), pack_h(-v1.y, v1.x));
    }
    __syncwarp();
    if (tid == 320) TR(0, 16);
#pragma unroll
    for (int k2 = 0; k2 < 4; k2++) ldsm4(bf + 32 + k2 * 4, stg + (lane & 7) * 272 + k2 * 64 + (lane >> 3) * 16);
    float c[6][4];
#pragma unroll
    for (int i = 0; i < 6; i++) { c[i][0] = 0.f; c[i][1] = 0.f; c[i][2] = 0.f; c[i][3] = 0.f; }
#pragma unroll
    for (int k2 = 0; k2 < 4; k2++) {
      uint32_t a[4];
      ldsm4(a, stg + (8 + (lane & 7)) * 272 + k2 * 64 + (lane >> 3) * 16);
#pragma unroll
      for (int kk = 0; kk < 2; kk++) {
        const int ks = 2 * k2 + kk;
        const uint4 r4 = lds128(stg + 5 * 272 + ks * 64 + t * 16);
        const uint32_t r[4] = {r4.x, r4.z, r4.y, r4.w};
        const uint32_t x0 = a[2 * kk], y0 = a[2 * kk + 1];
        const uint32_t x1 = hcmul(x0, r[0], r[2]), y1 = hcmul(y0, r[1], r[3]);
        const uint32_t x2 = hcmul(x1, r[0], r[2]), y2 = hcmul(y1, r[1], r[3]);
        const uint32_t x3 = hcmul(x2, r[0], r[2]), y3 = hcmul(y2, r[1], r[3]);
#pragma unroll
        for (int n = 0; n < 3; n++) {
          mma16816(c[n * 2], x0, x1, y0, y1, bf[n * 16 + ks * 2], bf[n * 16 + ks * 2 + 1]);
          mma16816(c[n * 2 + 1], x2, x3, y2, y3, bf[n * 16 + ks * 2], bf[n * 16 + ks * 2 + 1]);
        }
      }
      if (k2 == 0 && warp == 5) {
        if (lane == 0) {
          const uint32_t tgt = lds32(ep_addr) * 128u;
          int it = 0;
          while ((int)(cv - tgt) < 0 && ++it < 400000) asm volatile("ld.relaxed.gpu.global.u32 %0, [%1];" : "=r"(cv) : "l"(&g_cnt1) : "memory");
          asm volatile("fence.acquire.gpu;" ::: "memory");
          asm volatile("fence.proxy.async.global;" ::: "memory");
          TR(0, 9);
        }
        __syncwarp();
#pragma unroll
        for (int c2 = 0; c2 < 4; c2++) bulk_ld_elect<8192>(sb + c2 * A_CH + A_REC, g_ux + (size_t)(cblk * 4 + c2) * 512, bar_rec);
      }
    }
    __syncwarp();
#pragma unroll
    for (int i = 0; i < 6; i++)
      sts128(stg + i * 512 + lane * 16, __float_as_uint(c[i][0]), __float_as_uint(c[i][1]), __float_as_uint(c[i][2]), __float_as_uint(c[i][3]));
  }
  if (tid == 320) TR(0, 2);

  uint32_t xt[8], ud[8];
  {
    mbar_wait(bar_rec, 0);
    if (tid == 320) TR(0, 4);
    uint4 r[4];
#pragma unroll
    for (int i = 0; i < 4; i++) r[i] = lds128(cb + A_REC + bk * 64 + ((i ^ (bk >> 1)) & 3) * 16);
    const uint32_t ua = cb + A_UB + ((2 * bk) & 7) * 656 + ((bk >> 2) + 9) * 16;
    sts128(ua, r[0].x, r[1].x, r[2].x, r[3].x);
    sts128(ua + 656, r[0].y, r[1].y, r[2].y, r[3].y);
    if (bk <= 96) {
      const bool neg = bk == 96;
      const int bp = neg ? -1 : bk;
      uint32_t h[4];
      h[0] = lds32(cb + A_REC + ((bp - 1) & 127) * 64 + ((2 ^ ((bp - 1) >> 1)) & 3) * 16 + 4);
      h[1] = lds32(cb + A_REC + ((bp - 1) & 127) * 64 + ((3 ^ ((bp - 1) >> 1)) & 3) * 16 + 4);
      h[2] = lds32(cb + A_REC + (bp + 1) * 64 + ((0 ^ ((bp + 1) >> 1)) & 3) * 16);
      h[3] = lds32(cb + A_REC + (bp + 1) * 64 + ((1 ^ ((bp + 1) >> 1)) & 3) * 16);
      if (bp <= 0) { h[0] = 0; h[1] = 0; }
      const uint32_t wd[12] = {h[0], h[1], neg ? 0 : r[0].x, neg ? 0 : r[1].x, neg ? 0 : r[2].x, neg ? 0 : r[3].x,
                               neg ? 0 : r[0].y, neg ? 0 : r[1].y, neg ? 0 : r[2].y, neg ? 0 : r[3].y, h[2], h[3]};
      float P[25];
      P[0] = 0.f;
#pragma unroll
      for (int i = 0; i < 12; i++) { P[2 * i + 1] = P[2 * i] + bf_lo(wd[i]); P[2 * i + 2] = P[2 * i + 1] + bf_hi(wd[i]); }
#define WIN(i, hw) (P[(i) + 5 + (hw)] - P[(i) + 4 - (hw)])
#define WPK(i, hw) pack_bf16(WIN(i, hw), WIN((i) + 1, hw))
      const int tp = 2 * bp;
      const uint32_t a3 = cb + A_W3 + (tp + 64) * 16 + 8, a5 = cb + A_W5 + (tp + 64) * 16;
      sts64(a3, WPK(0, 1), WPK(2, 1));
      sts128(a3 + 8, WPK(4, 1), WPK(6, 1), WPK(8, 1), WPK(10, 1));
      sts64(a3 + 24, WPK(12, 1), WPK(14, 1));
      sts128(a5, WPK(0, 2), WPK(2, 2), WPK(4, 2), WPK(6, 2));
      sts128(a5 + 16, WPK(8, 2), WPK(10, 2), WPK(12, 2), WPK(14, 2));
      if (bp < 64) {
        sts128(cb + A_W7 + 1040 + bp * 16, WPK(0, 3), WPK(2, 3), WPK(4, 3), WPK(6, 3));
        sts128(cb + A_W7 + (bp + 1) * 16, WPK(8, 3), WPK(10, 3), WPK(12, 3), WPK(14, 3));
        sts128(cb + A_W9 + (bp + 1) * 16, WPK(0, 4), WPK(2, 4), WPK(4, 4), WPK(6, 4));
        sts128(cb + A_W9 + 1040 + (bp + 1) * 16, WPK(8, 4), WPK(10, 4), WPK(12, 4), WPK(14, 4));
#define VPK(i) pack_bf16(P[(i) + 2] - P[i], P[(i) + 3] - P[(i) + 1])
        sts128(cb + A_V + bp * 32, VPK(0), VPK(2), VPK(4), VPK(6));
        sts128(cb + A_V + bp * 32 + 16, VPK(8), VPK(10), VPK(12), VPK(14));
      }
    }
  }
  asm volatile("fence.proxy.async.shared::cta;" ::: "memory");
  bar_sync(1 + wg, 128);
  if (tid == 320) TR(0, 3);
  {
    const uint4 sc = lds128(cb + A_SCL);
    const float scl[4] = {__uint_as_float(sc.x), __uint_as_float(sc.y), __uint_as_float(sc.z), __uint_as_float(sc.w)};
#pragma unroll
    for (int rep = 0; rep < 2; rep++) {
      const int qd = rep ? 2 + wr : 3 - wr;
      if (rep == 0 || wr >= 2) {
        float s[4] = {0.f, 0.f, 0.f, 0.f};
#pragma unroll
        for (int w = 0; w < 4; w++) {
          uint4 u4 = lds128(cb + A_STG + w * 4352 + qd * 512 + lane * 16);
          s[0] = fmaf(__uint_as_float(u4.x), scl[w], s[0]); s[1] = fmaf(__uint_as_float(u4.y), scl[w], s[1]);
          s[2] = fmaf(__uint_as_float(u4.z), scl[w], s[2]); s[3] = fmaf(__uint_as_float(u4.w), scl[w], s[3]);
        }
#pragma unroll
        for (int hf = 0; hf < 2; hf++) {
          const int j = (qd & 1) * 16 + g + 8 * hf;
          const uint32_t pk = pack_bf16(s[2 * hf + 1], s[2 * hf]);
          const uint32_t v0 = pk >> 16, v1 = pk & 0xFFFFu, v00 = v0 * 0x10001u;
          if (rep == 1) {
            if (t < 2) {
#pragma unroll
              for (int e = 0; e < 2; e++) {
                const int lam = 128 + 32 * (2 * t + e) + j, mu = lam >> 1;
                const uint32_t val = e ? v1 : v0;
                uint32_t a = cb + ((lam & 1) ? A_R3B : A_R3A) + mu * 4;
                if (lam == 128) { a = cb + A_R2A + 128 * 4; sts32(cb + A_K1024, val << 16); }
                sts16(a, val); sts16(a + 6, val);
              }
            } else if (t == 2 && j == 0) { sts16(cb + A_R3A + 128 * 4, v0); }
          } else if (qd < 2) {
            const uint32_t a = cb + A_R1 + (62 + 8 * j + 2 * t) * 4;
            sts16(a, v0); sts32(a + 4, pk); sts16(a + 10, v1);
          } else if (t < 2) {
            const int L = 256 + 8 * j + 4 * t;
            const uint32_t a = cb + A_R1 + (62 + L) * 4;
            if (L > 256) { sts16(a - 4, v0); sts32(a, v00); } else sts16(a, v0);
            sts32(a + 4, v00); sts32(a + 8, pk); sts16(a + 14, v1);
          } else {
            const int mu = 64 + 32 * (t - 2) + j;
            if (mu == 64) {
              const uint32_t a = cb + A_R1 + (62 + 512) * 4;
              sts16(a - 4, v0); sts32(a, v00); sts32(a + 4, v00); sts32(a + 8, v00); sts16(a + 14, v0);
            } else { sts16(cb + A_R2A + mu * 4, v0); sts16(cb + A_R2A + mu * 4 + 6, v0); }
            sts16(cb + A_R2B + mu * 4, v1); sts16(cb + A_R2B + mu * 4 + 6, v1);
          }
        }
      }
    }
  }
  if (t128 == 96) {
    mbar_wait(bar_w + 8 * wg, 0);
    bulk_st(g_wimg + (size_t)((ch >> 1) / 28) * 37632 + ((ch >> 1) % 28) * 896 + (ch & 1) * 448, sb + A_WST + wg * 7168, 7168);
    asm volatile("cp.async.bulk.commit_group;" ::: "memory");
  }
  bar_sync(1 + wg, 128);
  if (tid == 320) TR(0, 5);

  {
    const uint32_t cbu = cb;
    const uint32_t blo_k = ((cbu & 0x3FFFF) >> 4) | (41u << 16);
    const uint32_t blo_n = ((cbu & 0x3FFFF) >> 4) | (8u << 16);
    const uint32_t tb = cb + (16 * wq + g - 2 * t) * 4;
    float y1[16], y2[12], y3[8];
    const uint32_t dk16 = __ldg(dskip + ch);
    uint32_t qa[32], qb[32];
    const uint32_t t1 = tb + A_R1 + (62 - 48) * 4;
    load_quads<4>(qa, tb + A_R3A + 17 * 4); load_quads<4>(qa + 16, tb + A_R3B + 16 * 4);
    wg_fence();
    s3_steps<0, 4, A_W9, 1>(y3, qa, blo_n); s3_steps<0, 4, A_W7, 0>(y3, qa + 16, blo_n);
    wg_commit();
    load_quads<8>(qb, tb + A_R2A + 16 * 4);
    wg_fence(); s2_steps<0, 8, A_W5, 1>(y2, qb, blo_n); wg_commit();
    wg_wait<1>(); load_quads<8>(qa, tb + A_R2B + 16 * 4);
    wg_fence(); s2_steps<0, 8, A_W3, 0>(y2, qa, blo_n); wg_commit();
    wg_wait<1>(); load_quads<8>(qb, t1);
    wg_fence(); f1_steps<0, 8>(y1, qb, blo_k); wg_commit();
    wg_wait<1>(); load_quads<8>(qa, t1 + 8 * 64);
    wg_fence(); f1_steps<8, 8>(y1, qa, blo_k); wg_commit();
    reg_fence(y2); reg_fence(y3);
    if (tid == 320) TR(0, 18);
    {
      const float k1024 = __uint_as_float(lds32(cb + A_K1024));
#pragma unroll
      for (int i = 0; i < 2; i++)
#pragma unroll
        for (int hf = 0; hf < 2; hf++) {
          const int idx = 16 * (16 * wq + g + 8 * hf) + 8 * i + 2 * t;
          const uint32_t vv = lds32(cb + A_V + idx * 2);
          sts64(cb + A_Y3 + (idx + 4 * (idx >> 6)) * 4, __float_as_uint(fmaf(k1024, bf_lo(vv), y3[4 * i + 2 * hf])),
                __float_as_uint(fmaf(k1024, bf_hi(vv), y3[4 * i + 2 * hf + 1])));
        }
#pragma unroll
      for (int i = 0; i < 3; i++)
#pragma unroll
        for (int hf = 0; hf < 2; hf++) {
          const int idx = 512 * i + 8 * (16 * wq + g + 8 * hf) + 2 * t;
          sts64(cb + A_Y2 + (idx + 4 * (idx >> 6)) * 4, __float_as_uint(y2[4 * i + 2 * hf]), __float_as_uint(y2[4 * i + 2 * hf + 1]));
        }
    }
    wg_wait<1>(); load_quads<8>(qb, t1 + 16 * 64);
    wg_fence(); f1_steps<16, 8>(y1, qb, blo_k); wg_commit();
    wg_wait<1>(); load_quads<8>(qa, t1 + 24 * 64);
    wg_fence(); f1_steps<24, 8>(y1, qa, blo_k); wg_commit();
    wg_wait<1>(); load_quads<5>(qb, t1 + 32 * 64);
    wg_fence(); f1_steps<32, 5>(y1, qb, blo_k); wg_commit();
    bar_sync(1 + wg, 128);
    float ex[12];
#pragma unroll
    for (int i = 1; i < 4; i++)
#pragma unroll
      for (int k = 0; k < 4; k++) {
        const int aa = 8 * i + 2 * t + (k & 1), b = 16 * wq + g + 8 * (k >> 1);
        float e = __uint_as_float(lds32(cb + A_Y2 + ((aa - 8) * 68 + b) * 4));
        if (i >= 2) e += __uint_as_float(lds32(cb + A_Y3 + ((aa - 16) * 68 + b) * 4));
        ex[4 * (i - 1) + k] = e;
      }
    {
      const uint32_t dk = dk16 * 0x10001u;
#pragma unroll
      for (int i = 0; i < 4; i++) {
        const uint4 r = lds128(cb + A_REC + bk * 64 + ((i ^ (bk >> 1)) & 3) * 16);
        ud[i] = hmul2_bf(r.x, dk); ud[4 + i] = hmul2_bf(r.y, dk); xt[i] = r.z; xt[4 + i] = r.w;
      }
    }
    wg_wait<0>();
    reg_fence(y1);
    if (tid == 320) TR(0, 6);
#pragma unroll
    for (int i = 0; i < 12; i++) y1[4 + i] += ex[i];
#pragma unroll
    for (int i = 0; i < 2; i++) {
      const int mi = lane >> 3, aa = 8 * (2 * i + (mi >> 1)) + (lane & 7);
      asm volatile("stmatrix.sync.aligned.m8n8.x4.trans.shared.b16 [%0], {%1,%2,%3,%4};"
                   ::"r"(cb + A_YB + aa * 128 + (((2 * wq + (mi & 1)) ^ (lane & 7)) << 4)),
                     "r"(pack_bf16(y1[8 * i], y1[8 * i + 1])), "r"(pack_bf16(y1[8 * i + 2], y1[8 * i + 3])),
                     "r"(pack_bf16(y1[8 * i + 4], y1[8 * i + 5])), "r"(pack_bf16(y1[8 * i + 6], y1[8 * i + 7])) : "memory");
    }
  }
  bar_sync(1 + wg, 128);
#pragma unroll
  for (int c = 0; c < 2; c++) {
    const int tau = 2 * bk + c, r = ch & 7;
    const uint4 y = lds128(cb + A_YB + (tau >> 3) * 128 + (((tau ^ (tau >> 3)) & 7) << 4));
    g_himg[(size_t)(tau >> 4) * 7168 + (ch >> 3) * 128 + ((tau >> 3) & 1) * 64 + r * 8 + ((tau & 7) ^ r)] =
        make_uint4(hadd2_bf(xt[4 * c], hadd2_bf(y.x, ud[4 * c])), hadd2_bf(xt[4 * c + 1], hadd2_bf(y.y, ud[4 * c + 1])),
                   hadd2_bf(xt[4 * c + 2], hadd2_bf(y.z, ud[4 * c + 2])), hadd2_bf(xt[4 * c + 3], hadd2_bf(y.w, ud[4 * c + 3])));
  }
  if (t128 == 96) asm volatile("cp.async.bulk.wait_group 0;" ::: "memory");
  if (tid == 320) TR(0, 7);
}

constexpr int B_SA = 0, B_RING = 114688, B_SLOT = 14848, B_NSLOT = 7;
constexpr int B_CS = B_RING + B_NSLOT * B_SLOT;
constexpr int B_RED = B_CS + 7168;
constexpr int B_BAR = B_RED + 256;
constexpr int B_SMEM = B_BAR + 1024, A_SMEM = A_WST + 28672;

__device__ __forceinline__ uint32_t mapa(uint32_t a, uint32_t r) { uint32_t o; asm("mapa.shared::cluster.u32 %0, %1, %2;" : "=r"(o) : "r"(a), "r"(r)); return o; }
template <class T> __device__ __forceinline__ T* pin(T* p) { asm volatile("" : "+l"(p)); return p; }
__device__ __forceinline__ uint32_t pin(uint32_t v) { asm volatile("" : "+r"(v)); return v; }
template <int Q, int ST>
__device__ __forceinline__ void g1_stage(float (&acc)[116], uint32_t alo, uint32_t blo, uint32_t bar_full, uint32_t bar_h) {
  constexpr int s = Q * 14 + ST, sl = s % B_NSLOT;
  if (Q == 0) mbar_wait(bar_h + 8 * ST, 0);
  mbar_wait(bar_full + 8 * sl, (s / B_NSLOT) & 1);
  wg_fence();
  if (Q == 0) {
    wgmma_ss232<(2 * ST) * 256, 0x40000080u, (sl * B_SLOT) / 16, 32, ST != 0>(acc, alo, blo);
    wgmma_ss232<(2 * ST + 1) * 256, 0x40000080u, (sl * B_SLOT + 256) / 16, 32, 1>(acc, alo, blo);
  } else {
    wgmma_ss224<(2 * ST) * 256, 0x40000080u, (sl * B_SLOT) / 16, 32, ST != 0>(*(float(*)[112])acc, alo, blo);
    wgmma_ss224<(2 * ST + 1) * 256, 0x40000080u, (sl * B_SLOT + 256) / 16, 32, 1>(*(float(*)[112])acc, alo, blo);
  }
}

__global__ void __launch_bounds__(512, 1)
k_front(const __grid_constant__ CUtensorMap mg, const __grid_constant__ CUtensorMap mu, const __grid_constant__ CUtensorMap md,
        const __nv_bfloat16* __restrict__ x, const uint32_t* __restrict__ are, const uint32_t* __restrict__ aim,
        const uint32_t* __restrict__ bre, const uint32_t* __restrict__ bim, const uint32_t* __restrict__ cre,
        const uint32_t* __restrict__ cim, const unsigned short* __restrict__ logdt, const unsigned short* __restrict__ dskip,
        const uint4* __restrict__ wgate, const uint4* __restrict__ wup) {
  extern __shared__ __align__(1024) unsigned char sm[];
  const uint32_t bar_rec = s2u(sm) + A_BAR;
  if (threadIdx.x == 320) TR(0, 0);
  asm volatile("griddepcontrol.launch_dependents;");
  if (threadIdx.x == 160) {
    mbar_init(bar_rec, 4);
    for (int i = 0; i < 8; i++) mbar_init(bar_rec + 16 + 8 * i, 1);
    asm volatile("fence.mbarrier_init.release.cluster;" ::: "memory");
    asm volatile("prefetch.tensormap [%0];" ::"l"(&mg)); asm volatile("prefetch.tensormap [%0];" ::"l"(&mu)); asm volatile("prefetch.tensormap [%0];" ::"l"(&md));
  }
  phase_a(sm, bar_rec, bar_rec + 8, &mg, &mu, &md, x, are, aim, bre, bim, cre, cim, logdt, dskip, wgate, wup);
}

__global__ void __cluster_dims__(2, 1, 1) __launch_bounds__(384, 1) k_ffn(__nv_bfloat16* __restrict__ out) {
  extern __shared__ __align__(1024) unsigned char sm[];
  const uint32_t sb = s2u(sm);
  const int tid = threadIdx.x, warp = __shfl_sync(~0u, tid >> 5, 0), wg = warp >> 2, lane = tid & 31;
  const uint32_t bar_full = sb + B_BAR, bar_empty = bar_full + 64, bar_h = bar_full + 128, bar_cs = bar_full + 240,
                 bar_hh = bar_full + 304, bar_afree = bar_full + 336, bar_out = bar_full + 352;
  if (tid == 0) {
    TR(1, 0);
    for (int i = 0; i < B_NSLOT; i++) { mbar_init(bar_full + 8 * i, 1); mbar_init(bar_empty + 8 * i, 2); }
    asm volatile("fence.mbarrier_init.release.cluster;" ::: "memory");
  } else if (tid == 32) {
    for (int i = 0; i < 14; i++) mbar_init(bar_h + 8 * i, 1);
    asm volatile("fence.mbarrier_init.release.cluster;" ::: "memory");
  } else if (tid == 64) {
    mbar_init(bar_cs, 1);
    for (int i = 0; i < 4; i++) { mbar_init(bar_hh + 8 * i, 1); mbar_expect(bar_hh + 8 * i, 14336); }
    mbar_init(bar_afree, 4); mbar_init(bar_afree + 8, 2);
    for (int i = 0; i < 6; i++) mbar_init(bar_out + 8 * i, 128);
    asm volatile("fence.mbarrier_init.release.cluster;" ::: "memory");
  } else if (tid >= 128 && tid < 352) {
    sts128(sb + B_RING + ((tid - 128) >> 5) * B_SLOT + 14336 + (tid & 31) * 16, 0x3F803F80u, 0x3F803F80u, 0x3F803F80u, 0x3F803F80u);
  }
  asm volatile("fence.proxy.async.shared::cta;" ::: "memory");
  __syncthreads();
  asm volatile("barrier.cluster.arrive.relaxed.aligned;" ::: "memory");
  const int rank = blockIdx.x & 1, rt = blockIdx.x >> 3, j = blockIdx.x & 7, p = j >> 1, cg = 4 * rank + p;
  const int wq = warp & 3, t128 = tid & 127, g = lane >> 2, t = lane & 3;
  uint32_t ep, tag;
  auto load_ep = [&]() { asm volatile("ld.relaxed.gpu.global.u32 %0, [%1];" : "=r"(ep) : "l"(&g_cnt1) : "memory"); };
  auto a_slot = [&](int i, int own) { return B_SA + (i + (i >= own)) * 14336; };
  auto out_addr = [&](int cc, int w) { return sb + a_slot((cc & 2) + w, cg) + (cc & 1) * 7168; };
  auto in_cta = [&](int q) { return rt * 8 + ((p + 3 - q) & 3) * 2 + rank; };
  auto in_src = [&](int q, int cw) { return g_part + (size_t)(in_cta(q) * 3 + q) * 896 + cw * 112; };
  auto in_bad = [&](uint32_t (&in)[14]) { return ((in[3] ^ tag) | (in[7] ^ tag) | (in[11] ^ tag) | (in[13] ^ tag)) & 0x10000u; };
  auto in_load = [&](uint32_t (&in)[14], const uint4* gs) {
#pragma unroll
    for (int i = 0; i < 3; i++) ld128(gs + i * 32, in + 4 * i);
    asm volatile("{\n.reg .b64 v;\nld.relaxed.gpu.global.b64 v, [%2];\nmov.b64 {%0, %1}, v;\n}"
                 : "=r"(in[12]), "=r"(in[13]) : "l"((const uint2*)(gs + 96) - lane) : "memory");
  };
  auto in_check = [&](uint32_t (&in)[14], int q, int cw) {
    int it = 0;
    while (in_bad(in) && ++it < 400000) in_load(in, pin(in_src(q, cw) + lane));
  };

  if (wg == 2) {
    asm volatile("setmaxnreg.dec.sync.aligned.u32 40;");
    asm volatile("barrier.cluster.wait.aligned;" ::: "memory");
    asm volatile("griddepcontrol.wait;" ::: "memory");
    if (warp == 8) {
      if (lane == 0) TR(1, 1);
      const char* wsrc = (const char*)g_wimg + (size_t)j * 602112;
      const char* hsrc = (const char*)g_himg + (size_t)rt * 114688 + rank * 4096;
#pragma unroll
      for (int s = 0; s < 28; s++) {
        if (s < B_NSLOT) bulk_ld_mc_elect<4096>(sb + B_SA + s * 8192 + rank * 4096, hsrc + s * 8192, bar_h + 8 * s);
        if (s == B_NSLOT) {
#pragma unroll
          for (int i = 7; i < 14; i++) bulk_ld_mc_elect<4096>(sb + B_SA + i * 8192 + rank * 4096, hsrc + i * 8192, bar_h + 8 * i);
          bulk_ld_elect<7168>(sb + B_CS, g_cimg + j * 448, bar_cs);
        }
        if (s >= B_NSLOT) mbar_wait(bar_empty + 8 * (s % B_NSLOT), (s / B_NSLOT + 1) & 1);
        bulk_ld_elect<14336>(sb + B_RING + (s % B_NSLOT) * B_SLOT, wsrc + s * 14336, bar_full + 8 * (s % B_NSLOT));
      }
      const char* dsrc[2] = {wsrc + 401408 + rank * 100352, (const char*)g_wimg + (size_t)(j ^ 1) * 602112 + 401408 + rank * 100352};
#pragma unroll
      for (int i = 0; i < 16; i++) {
        const int ci = i < 3 ? 0 : i < 6 ? 1 : i < 8 ? i - 6 : i < 12 ? 2 : 3;
        const int kp = i < 3 ? i : i < 6 ? i - 3 : i < 8 ? 3 : (i & 3);
        mbar_wait(bar_empty + 8 * (i % B_NSLOT), (i / B_NSLOT + 1) & 1);
        bulk_ld_elect<12544>(sb + B_RING + (i % B_NSLOT) * B_SLOT, dsrc[kp >> 1] + ((p + 1 + ci) & 3) * 25088 + (kp & 1) * 12544, bar_full + 8 * (i % B_NSLOT));
      }
    } else if (warp >= 10) {
      const int t64 = tid - 320;
      load_ep();
      const int r = (lane >> 1) & 7, c = (j & 3) * 2 + (lane & 1);
      const uint32_t src = sb + B_SA + (t64 >> 4) * 2048 + (j >> 2) * 1024 + r * 128 + ((c ^ r) << 4);
      float a[16];
#pragma unroll
      for (int k = 0; k < 16; k++) a[k] = 0.f;
#pragma unroll 1
      for (int i = 0; i < 14; i++) {
        mbar_wait(bar_h + 8 * i, 0);
        uint4 v = lds128(src + i * 8192);
        float e[8] = {bf_lo(v.x), bf_hi(v.x), bf_lo(v.y), bf_hi(v.y), bf_lo(v.z), bf_hi(v.z), bf_lo(v.w), bf_hi(v.w)};
#pragma unroll
        for (int k = 0; k < 8; k++) { a[2 * k] += e[k]; a[2 * k + 1] = fmaf(e[k], e[k], a[2 * k + 1]); }
        __nanosleep(160);
      }
      __syncwarp();
      if (lane == 0) { asm volatile("mbarrier.arrive.shared::cluster.b64 _, [%0];" ::"r"(mapa(bar_afree, rank ^ 1)) : "memory"); }
#pragma unroll
      for (int rd = 0; rd < 4; rd++) {
        const int n = 8 >> rd;
        const bool up = lane & (2 * n);
#pragma unroll
        for (int k = 0; k < 8; k++) {
          if (k < n) {
            float keep = up ? a[k + n] : a[k], give = up ? a[k] : a[k + n];
            a[k] = keep + __shfl_xor_sync(~0u, give, 2 * n);
          }
        }
      }
      float* red = (float*)(sm + B_RED);
      red[(warp & 1) * 32 + (lane & 1) * 16 + (lane >> 1)] = a[0];
      bar_sync(1, 64);
      if (t64 < 16) {
        float mean = (red[2 * t64] + red[32 + 2 * t64]) * (1.f / DM);
        float var = fmaxf(fmaf(-mean, mean, (red[2 * t64 + 1] + red[33 + 2 * t64]) * (1.f / DM)), 0.f);
        float rs = ln_rstd(var);
        asm volatile("st.relaxed.gpu.global.u32 [%0], %1;"
                     ::"l"(g_stat2 + rt * 128 + j * 16 + t64), "r"((__float_as_uint(rs * rs) & ~1u) | ((ep >> 7) & 1u)) : "memory");
      }
      if (t64 == 0) TR(1, 2);
      if (lane == 0) {
        const int w = warp & 1;
        for (int cc = 0; cc < 2; cc++) {
          mbar_wait(bar_out + 8 * (cc * 2 + w), 0);
          asm volatile("cp.async.bulk.global.shared::cta.bulk_group [%0], [%1], 7168;"
                       ::"l"(g_part + (size_t)(blockIdx.x * 3 + cc) * 896 + w * 448), "r"(out_addr(cc, w)) : "memory");
          if (w) TR(1, 27 + cc);
        }
        asm volatile("cp.async.bulk.commit_group;" ::: "memory");
        asm volatile("cp.async.bulk.wait_group 0;" ::: "memory");
      }
    }
  } else {
    asm volatile("setmaxnreg.inc.sync.aligned.u32 232;");
    asm volatile("barrier.cluster.wait.aligned;" ::: "memory");
    uint32_t hh[56];
    const bool relt = t128 == 0;
    auto release = [&](int sl) { if (relt) mbar_arrive(bar_empty + 8 * sl); };
    auto send_hh = [&](int q) {
      const uint32_t da = mapa(sb + a_slot(2 * q + wg, cg ^ 4) + t128 * 16, rank ^ 1), db = mapa(bar_hh + 8 * (2 * q + wg), rank ^ 1);
#pragma unroll
      for (int i = 0; i < 7; i++)
        asm volatile("st.async.weak.shared::cluster.mbarrier::complete_tx::bytes.v4.b32 [%0], {%1, %2, %3, %4}, [%5];"
                     ::"r"(da + i * 2048), "r"(hh[28 * q + 4 * i]), "r"(hh[28 * q + 4 * i + 1]),
                       "r"(hh[28 * q + 4 * i + 2]), "r"(hh[28 * q + 4 * i + 3]), "r"(db) : "memory");
    };
    uint32_t alo = ((sb + B_SA + wg * 1024) & 0x3FFFF) >> 4;
    uint32_t blo = (((sb + B_RING) & 0x3FFFF) >> 4) | (8u << 16);
    const uint32_t clo = ((sb + B_CS) & 0x3FFFF) >> 4;
    uint32_t nm0, nm1;
    if (wg == 1) bar_sync(3, 256);
#define G1S(Q, ST) do { if (ST % 7 == 0) { alo = pin(alo); blo = pin(blo); }   \
      g1_stage<Q, ST>(acc, alo, blo, bar_full, bar_h); wg_commit(); \
      if (ST > 0) { wg_wait<1>(); release((Q * 14 + ST - 1) % B_NSLOT); } } while (0)
#define G1HH(Q) do { \
      _Pragma("unroll") \
      for (int i = 0; i < 28; i++) hh[28 * Q + i] = pack_bf16(acc[2 * i] * acc[56 + 2 * i], acc[2 * i + 1] * acc[57 + 2 * i]); \
    } while (0)
    {
      float acc[116];
      G1S(0, 0);
      if (tid == 0) TR(1, 3);
      G1S(0, 1);
      if (wg == 0) asm volatile("bar.arrive 3, 256;" ::: "memory");
      G1S(0, 2); G1S(0, 3); G1S(0, 4); G1S(0, 5); G1S(0, 6); G1S(0, 7); G1S(0, 8); G1S(0, 9); G1S(0, 10); G1S(0, 11); G1S(0, 12);
      G1S(0, 13);
      if (tid == 0) TR(1, 4);
      mbar_wait(bar_cs, 0);
      wg_wait<0>(); reg_fence(acc); release(13 % B_NSLOT);
      {
        const uint32_t msk = t == 0 ? 0xFFFFFFFFu : t == 1 ? 0xFFFFu : 0u;
        const float a = acc[112] * (-1.f / DM), b = acc[114] * (-1.f / DM);
        nm0 = pack_bf16(a, a) & msk; nm1 = pack_bf16(b, b) & msk;
      }
      wg_fence();
      wgmma_rs224<0, 8, 1>(*(float(*)[112])acc, nm0, nm1, 0u, 0u, clo);
      wg_commit(); wg_wait<0>(); reg_fence(acc);
      G1HH(0);
      if (tid == 0) TR(1, 5);
      G1S(1, 0); G1S(1, 1); G1S(1, 2); G1S(1, 3); G1S(1, 4); G1S(1, 5); G1S(1, 6);
      if (relt) asm volatile("mbarrier.arrive.shared::cluster.b64 _, [%0];" ::"r"(mapa(bar_afree, rank ^ 1)) : "memory");
      G1S(1, 7); G1S(1, 8); G1S(1, 9);
      if (relt) asm volatile("mbarrier.arrive.shared::cluster.b64 _, [%0];" ::"r"(mapa(bar_afree + 8, rank ^ 1)) : "memory");
      mbar_wait(bar_afree, 0);
      send_hh(0);
      G1S(1, 10); G1S(1, 11); G1S(1, 12);
      load_ep();
      g1_stage<1, 13>(acc, alo, blo, bar_full, bar_h);
      wgmma_rs224<224, 8, 1>(*(float(*)[112])acc, nm0, nm1, 0u, 0u, clo);
      wg_commit(); wg_wait<1>(); release(26 % B_NSLOT);
      wg_wait<0>(); reg_fence(acc); release(27 % B_NSLOT);
      G1HH(1);
      if (tid == 0) TR(1, 6);
    }
    float accA[28], accB[28];
    uint32_t ph0[28], ph1[28];
    ep = pin(ep >> 7); tag = pin((ep & 1u) << 16);
#define ISSUE(acc, I, a, FIRST) do { \
      constexpr int s_ = 28 + (I), sl_ = s_ % B_NSLOT; \
      if (sl_ == 0) blo = pin(blo); \
      mbar_wait(bar_full + 8 * sl_, (s_ / B_NSLOT) & 1); \
      wg_fence(); \
      wgmma_rs56<(sl_ * B_SLOT + 0 * 256) / 16, 112, !(FIRST)>(acc, (a)[0], (a)[1], (a)[2], (a)[3], blo); \
      wgmma_rs56<(sl_ * B_SLOT + 1 * 256) / 16, 112, 1>(acc, (a)[4], (a)[5], (a)[6], (a)[7], blo); \
      wgmma_rs56<(sl_ * B_SLOT + 2 * 256) / 16, 112, 1>(acc, (a)[8], (a)[9], (a)[10], (a)[11], blo); \
      wgmma_rs56<(sl_ * B_SLOT + 3 * 256) / 16, 112, 1>(acc, (a)[12], (a)[13], (a)[14], (a)[15], blo); \
      wgmma_rs56<(sl_ * B_SLOT + 4 * 256) / 16, 112, 1>(acc, (a)[16], (a)[17], (a)[18], (a)[19], blo); \
      wgmma_rs56<(sl_ * B_SLOT + 5 * 256) / 16, 112, 1>(acc, (a)[20], (a)[21], (a)[22], (a)[23], blo); \
      wgmma_rs56<(sl_ * B_SLOT + 6 * 256) / 16, 112, 1>(acc, (a)[24], (a)[25], (a)[26], (a)[27], blo); \
      wg_commit(); } while (0)
    auto rel = [&](int i) { release((28 + i) % B_NSLOT); };
    auto tg = [&](uint32_t v) { return (v & 0xFFFEFFFFu) | tag; };
    auto send = [&](float (&acc)[28], int cc) {
      reg_fence(acc);
      const uint32_t a = out_addr(cc, wg) + wq * 1792;
#pragma unroll
      for (int q = 0; q < 3; q++)
        sts128(a + q * 512 + lane * 16, pack_bf16(acc[8 * q], acc[8 * q + 1]), pack_bf16(acc[8 * q + 2], acc[8 * q + 3]),
               pack_bf16(acc[8 * q + 4], acc[8 * q + 5]), tg(pack_bf16(acc[8 * q + 6], acc[8 * q + 7])));
      sts64(a + 1536 + lane * 8, pack_bf16(acc[24], acc[25]), tg(pack_bf16(acc[26], acc[27])));
      asm volatile("fence.proxy.async.shared::cta;" ::: "memory");
      mbar_arrive(bar_out + 8 * (cc * 2 + wg));
    };
    auto load_hh = [&](uint32_t (&d)[28], int q) {
      mbar_wait(bar_hh + 8 * (2 * q + wg), 0);
      const uint32_t a = sb + a_slot(2 * q + wg, cg) + t128 * 16;
#pragma unroll
      for (int i = 0; i < 7; i++) {
        const uint4 v = lds128(a + i * 2048);
        d[4 * i] = v.x; d[4 * i + 1] = v.y; d[4 * i + 2] = v.z; d[4 * i + 3] = v.w;
      }
    };
    ISSUE(accA, 0, hh, true);
    mbar_wait(bar_afree + 8, 0);
    send_hh(1);
    ISSUE(accA, 1, hh + 28, false);
    load_hh(ph0, 0);
    wg_wait<1>(); rel(0);
    ISSUE(accA, 2, ph0, false);      wg_wait<1>(); rel(1);
    ISSUE(accB, 3, hh, true);        wg_wait<1>(); rel(2);
    ISSUE(accB, 4, hh + 28, false);  wg_wait<1>(); rel(3);
    ISSUE(accB, 5, ph0, false);
    if (tid == 0) TR(1, 11);
    load_hh(ph1, 1);
    wg_wait<1>(); rel(4);
    ISSUE(accA, 6, ph1, false);      wg_wait<1>(); rel(5);
    ISSUE(accB, 7, ph1, false);      wg_wait<1>(); rel(6); send(accA, 0);
    ISSUE(accA, 8, hh, true);        wg_wait<1>(); rel(7); send(accB, 1);
    if (tid == 0) TR(1, 13);
    ISSUE(accA, 9, hh + 28, false);  wg_wait<1>(); rel(8);
    ISSUE(accA, 10, ph0, false);
    ISSUE(accA, 11, ph1, false);
    const int row = rt * 128 + wg * 64 + wq * 16 + g;
    uint32_t r20, r21;
    asm volatile("ld.relaxed.gpu.global.u32 %0, [%1];" : "=r"(r20) : "l"(g_stat2 + row) : "memory");
    asm volatile("ld.relaxed.gpu.global.u32 %0, [%1];" : "=r"(r21) : "l"(g_stat2 + row + 8) : "memory");
    ISSUE(accB, 12, hh, true);
    wg_wait<1>();
    {
      reg_fence(accA);
      uint4* pd = g_part + (size_t)(blockIdx.x * 3 + 2) * 896 + warp * 112 + lane;
#pragma unroll
      for (int q = 0; q < 3; q++)
        st128(pd + q * 32, pack_bf16(accA[8 * q], accA[8 * q + 1]), pack_bf16(accA[8 * q + 2], accA[8 * q + 3]),
              pack_bf16(accA[8 * q + 4], accA[8 * q + 5]), tg(pack_bf16(accA[8 * q + 6], accA[8 * q + 7])));
      asm volatile("{\n.reg .b64 v;\nmov.b64 v, {%1, %2};\nst.relaxed.gpu.global.b64 [%0], v;\n}"
                   ::"l"((uint2*)(pd + 96) - lane), "r"(pack_bf16(accA[24], accA[25])), "r"(tg(pack_bf16(accA[26], accA[27]))) : "memory");
    }
    if (tid == 0) TR(1, 16);
    ISSUE(accB, 13, hh + 28, false);
    ISSUE(accB, 14, ph0, false);
    uint32_t in0[14], in1[14], in2[14];
    in_load(in0, in_src(0, warp) + lane);
    in_load(in1, in_src(1, warp) + lane);
    ISSUE(accB, 15, ph1, false);
    if (tid == 0) TR(1, 7);
    {
      int it = 0;
      while ((((r20 ^ ep) | (r21 ^ ep)) & 1u) && ++it < 400000) {
        asm volatile("ld.relaxed.gpu.global.u32 %0, [%1];" : "=r"(r20) : "l"(g_stat2 + row) : "memory");
        asm volatile("ld.relaxed.gpu.global.u32 %0, [%1];" : "=r"(r21) : "l"(g_stat2 + row + 8) : "memory");
      }
    }
    wg_wait<1>();
    in_load(in2, in_src(2, warp) + lane);
    in_check(in0, 0, warp); in_check(in1, 1, warp);
#pragma unroll
    for (int i = 0; i < 14; i++) { accA[2 * i] = bf_lo(in0[i]) + bf_lo(in1[i]); accA[2 * i + 1] = bf_hi(in0[i]) + bf_hi(in1[i]); }
    if (tid == 0) TR(1, 12);
    wg_wait<0>();
    reg_fence(accB);
    uint32_t hres[16];
#pragma unroll
    for (int i = 0; i < 4; i++) {
      int qq = lane >> 3, r = lane & 7, kg = 7 * cg + 2 * i + (qq >> 1), c = 2 * wq + (qq & 1);
      if (kg > 55) kg = 55;
      asm volatile("ldmatrix.sync.aligned.m8n8.x4.trans.shared.b16 {%0,%1,%2,%3}, [%4];"
                   : "=r"(hres[4 * i]), "=r"(hres[4 * i + 1]), "=r"(hres[4 * i + 2]), "=r"(hres[4 * i + 3])
                   : "r"(sb + B_SA + kg * 2048 + wg * 1024 + r * 128 + ((c ^ r) << 4)) : "memory");
    }
#pragma unroll
    for (int i = 0; i < 28; i++) accB[i] += accA[i];
    if (tid == 0) TR(1, 9);
    in_check(in2, 2, warp);
#pragma unroll
    for (int i = 0; i < 14; i++) { accB[2 * i] += bf_lo(in2[i]); accB[2 * i + 1] += bf_hi(in2[i]); }
    uint32_t* o0 = (uint32_t*)(out + (size_t)row * DM + 56 * cg + 2 * t);
    uint32_t* o1 = o0 + 8 * DM / 2;
#pragma unroll
    for (int i = 0; i < 7; i++) {
      o0[4 * i] = hadd2_bf(hres[2 * i], pack_bf16(accB[4 * i] * __uint_as_float(r20), accB[4 * i + 1] * __uint_as_float(r20)));
      o1[4 * i] = hadd2_bf(hres[2 * i + 1], pack_bf16(accB[4 * i + 2] * __uint_as_float(r21), accB[4 * i + 3] * __uint_as_float(r21)));
    }
    if (tid == 0) TR(1, 10);
    if (tid == 128) TR(1, 15);
  }
}

typedef CUresult (*EncFn)(CUtensorMap*, CUtensorMapDataType, cuuint32_t, void*, const cuuint64_t*, const cuuint64_t*,
                          const cuuint32_t*, const cuuint32_t*, CUtensorMapInterleave, CUtensorMapSwizzle,
                          CUtensorMapL2promotion, CUtensorMapFloatOOBfill);

extern "C" void kernel_launch(void* const* d_in, const int* in_sizes, int n_in, void* d_out, int out_size) {
  const __nv_bfloat16* x = (const __nv_bfloat16*)d_in[0];
  const __nv_bfloat16 *are = (const __nv_bfloat16*)d_in[1], *aim = (const __nv_bfloat16*)d_in[2], *bre = (const __nv_bfloat16*)d_in[3],
                      *bim = (const __nv_bfloat16*)d_in[4], *cre = (const __nv_bfloat16*)d_in[5], *cim = (const __nv_bfloat16*)d_in[6],
                      *logdt = (const __nv_bfloat16*)d_in[7], *dskip = (const __nv_bfloat16*)d_in[8];
  const __nv_bfloat16 *wg = (const __nv_bfloat16*)d_in[10], *wu = (const __nv_bfloat16*)d_in[11], *wd = (const __nv_bfloat16*)d_in[12];

  static EncFn enc = nullptr;
  if (!enc) {
    void* fn = nullptr; cudaDriverEntryPointQueryResult qr;
    cudaGetDriverEntryPoint("cuTensorMapEncodeTiled", &fn, cudaEnableDefault, &qr);
    enc = (EncFn)fn;
    cudaFuncSetAttribute(k_ffn, cudaFuncAttributeMaxDynamicSharedMemorySize, B_SMEM);
    cudaFuncSetAttribute(k_front, cudaFuncAttributeMaxDynamicSharedMemorySize, A_SMEM);
  }
  CUtensorMap mg, mu, md;
  {
    cuuint32_t es[3] = {1, 1, 1};
    cuuint64_t d1[3] = {8, 448, 224}, s1[2] = {3584, 16}; cuuint32_t b1[3] = {8, 32, 14};
    cuuint64_t d2[3] = {8, 1792, 56}, s2[2] = {896, 16}; cuuint32_t b2[3] = {8, 112, 7};
    enc(&mg, CU_TENSOR_MAP_DATA_TYPE_BFLOAT16, 3, (void*)wg, d1, s1, b1, es, CU_TENSOR_MAP_INTERLEAVE_NONE, CU_TENSOR_MAP_SWIZZLE_NONE, CU_TENSOR_MAP_L2_PROMOTION_L2_256B, CU_TENSOR_MAP_FLOAT_OOB_FILL_NONE);
    enc(&mu, CU_TENSOR_MAP_DATA_TYPE_BFLOAT16, 3, (void*)wu, d1, s1, b1, es, CU_TENSOR_MAP_INTERLEAVE_NONE, CU_TENSOR_MAP_SWIZZLE_NONE, CU_TENSOR_MAP_L2_PROMOTION_L2_256B, CU_TENSOR_MAP_FLOAT_OOB_FILL_NONE);
    enc(&md, CU_TENSOR_MAP_DATA_TYPE_BFLOAT16, 3, (void*)wd, d2, s2, b2, es, CU_TENSOR_MAP_INTERLEAVE_NONE, CU_TENSOR_MAP_SWIZZLE_NONE, CU_TENSOR_MAP_L2_PROMOTION_L2_256B, CU_TENSOR_MAP_FLOAT_OOB_FILL_NONE);
  }
  cudaStream_t st = cudaStreamPerThread;
  k_front<<<128, 512, A_SMEM, st>>>(
      mg, mu, md, x, (const uint32_t*)are, (const uint32_t*)aim, (const uint32_t*)bre, (const uint32_t*)bim, (const uint32_t*)cre, (const uint32_t*)cim,
      (const unsigned short*)logdt, (const unsigned short*)dskip, (const uint4*)wg, (const uint4*)wu);
  cudaLaunchConfig_t cfg = {};
  cfg.gridDim = dim3(128); cfg.blockDim = dim3(384); cfg.dynamicSmemBytes = B_SMEM; cfg.stream = st;
  cudaLaunchAttribute at[1];
  at[0].id = cudaLaunchAttributeProgrammaticStreamSerialization; at[0].val.programmaticStreamSerializationAllowed = 1;
  cfg.attrs = at; cfg.numAttrs = 1;
  cudaLaunchKernelEx(&cfg, k_ffn, (__nv_bfloat16*)d_out);
}
```

```cpp
#include <cuda_runtime.h>
#include <cuda_bf16.h>
#include <cuda_fp16.h>
#include <cuda.h>
#include <stdint.h>

constexpr int LSEQ = 2048, DM = 448;

__device__ uint4    g_himg[16 * 114688 / 16];
__device__ uint4    g_cimg[8 * 2 * 224];
__device__ uint32_t g_stat2[LSEQ];
__device__ uint4    g_part[128 * 3 * 896];
__device__ uint4    g_wimg[8 * 602112 / 16];
__device__ uint4    g_ux[DM * 128 * 4];
__device__ unsigned g_cnt1;

#define TR(k, i) do {} while (0)
__device__ __forceinline__ uint32_t s2u(const void* p) { return (uint32_t)__cvta_generic_to_shared(p); }
__device__ __forceinline__ void mbar_init(uint32_t b, int c) { asm volatile("mbarrier.init.shared::cta.b64 [%0], %1;" ::"r"(b), "r"(c)); }
__device__ __forceinline__ void mbar_expect(uint32_t b, int bytes) { asm volatile("mbarrier.arrive.expect_tx.shared::cta.b64 _, [%0], %1;" ::"r"(b), "r"(bytes) : "memory"); }
__device__ __forceinline__ void mbar_arrive(uint32_t b) { asm volatile("mbarrier.arrive.shared::cta.b64 _, [%0];" ::"r"(b) : "memory"); }
__device__ __forceinline__ void mbar_wait(uint32_t b, int ph) {
  asm volatile("{\n.reg .pred p;\n.reg .b32 n;\nmov.b32 n, 0;\nLW:\nmbarrier.try_wait.parity.shared::cta.b64 p, [%0], %1;\n@p bra LD;\n"
               "add.u32 n, n, 1;\nsetp.lt.u32 p, n, 4000000;\n@p bra LW;\ntrap;\nLD:\n}" ::"r"(b), "r"(ph) : "memory");
}
__device__ __forceinline__ bool mbar_test(uint32_t b, int ph) {
  uint32_t ok;
  asm volatile("{\n.reg .pred p;\nmbarrier.test_wait.parity.shared::cta.b64 p, [%1], %2;\nselp.u32 %0, 1, 0, p;\n}" : "=r"(ok) : "r"(b), "r"(ph) : "memory");
  return ok;
}
__device__ __forceinline__ void wg_fence() { asm volatile("wgmma.fence.sync.aligned;" ::: "memory"); }
__device__ __forceinline__ void wg_commit() { asm volatile("wgmma.commit_group.sync.aligned;" ::: "memory"); }
template <int N> __device__ __forceinline__ void wg_wait() { asm volatile("wgmma.wait_group.sync.aligned %0;" ::"n"(N) : "memory"); }
template <int N> __device__ __forceinline__ void reg_fence(float (&a)[N]) {
#pragma unroll
  for (int i = 0; i < N; i++) asm volatile("" : "+f"(a[i])::"memory");
}
__device__ __forceinline__ uint32_t pack_bf16(float lo, float hi) {
  uint32_t r; asm("cvt.rn.bf16x2.f32 %0, %1, %2;" : "=r"(r) : "f"(hi), "f"(lo)); return r;
}
__device__ __forceinline__ float bf_lo(uint32_t v) { return __uint_as_float(v << 16); }
__device__ __forceinline__ float bf_hi(uint32_t v) { return __uint_as_float(v & 0xFFFF0000u); }
__device__ __forceinline__ float rbf(float x) { return __bfloat162float(__float2bfloat16_rn(x)); }
__device__ __forceinline__ uint32_t hmul2_bf(uint32_t a, uint32_t b) { uint32_t r; asm("mul.rn.bf16x2 %0, %1, %2;" : "=r"(r) : "r"(a), "r"(b)); return r; }
__device__ __forceinline__ uint32_t hadd2_bf(uint32_t a, uint32_t b) { uint32_t r; asm("add.rn.bf16x2 %0, %1, %2;" : "=r"(r) : "r"(a), "r"(b)); return r; }
__device__ __forceinline__ void bulk_ld(uint32_t dst, const void* src, int bytes, uint32_t bar) {
  asm volatile("cp.async.bulk.shared::cluster.global.mbarrier::complete_tx::bytes [%0], [%1], %2, [%3];"
               ::"r"(dst), "l"(src), "r"(bytes), "r"(bar) : "memory");
}

template <int BYTES>
__device__ __forceinline__ void bulk_ld_elect(uint32_t dst, const void* src, uint32_t bar) {
  asm volatile("{\n.reg .pred p;\nelect.sync _|p, 0xffffffff;\n"
               "@p mbarrier.arrive.expect_tx.shared::cta.b64 _, [%2], %3;\n"
               "@p cp.async.bulk.shared::cluster.global.mbarrier::complete_tx::bytes [%0], [%1], %3, [%2];\n}"
               ::"r"(dst), "l"(src), "r"(bar), "n"(BYTES) : "memory");
}
template <int BYTES>
__device__ __forceinline__ void bulk_ld_mc_elect(uint32_t dst, const void* src, uint32_t bar) {
  asm volatile("{\n.reg .pred p;\nelect.sync _|p, 0xffffffff;\n"
               "@p mbarrier.arrive.expect_tx.shared::cta.b64 _, [%2], %3;\n"
               "@p cp.async.bulk.shared::cluster.global.mbarrier::complete_tx::bytes.multicast::cluster [%0], [%1], %4, [%2], %5;\n}"
               ::"r"(dst), "l"(src), "r"(bar), "n"(2 * BYTES), "n"(BYTES), "h"((uint16_t)3) : "memory");
}
template <int AOFF, uint32_t AHI, int BOFF, uint32_t BHI, int ACC>
__device__ __forceinline__ void wgmma_ss224(float (&d)[112], uint32_t alo, uint32_t blo) {
  asm volatile("{\n.reg .pred p;\n.reg .b64 ad, bd;\nsetp.ne.b32 p, %118, 0;\n"
    "mov.b64 ad, {%112, %115};\nadd.s64 ad, ad, %114;\nmov.b64 bd, {%113, %117};\nadd.s64 bd, bd, %116;\n"
    "wgmma.mma_async.sync.aligned.m64n224k16.f32.bf16.bf16 {%0,%1,%2,%3,%4,%5,%6,%7,%8,%9,%10,%11,%12,%13,%14,%15,%16,%17,%18,%19,%20,%21,%22,%23,%24,%25,%26,%27,%28,%29,%30,%31,%32,%33,%34,%35,%36,%37,%38,%39,%40,%41,%42,%43,%44,%45,%46,%47,%48,%49,%50,%51,%52,%53,%54,%55,%56,%57,%58,%59,%60,%61,%62,%63,%64,%65,%66,%67,%68,%69,%70,%71,%72,%73,%74,%75,%76,%77,%78,%79,%80,%81,%82,%83,%84,%85,%86,%87,%88,%89,%90,%91,%92,%93,%94,%95,%96,%97,%98,%99,%100,%101,%102,%103,%104,%105,%106,%107,%108,%109,%110,%111}, ad, bd, p, 1, 1, 1, 1;\n}\n"
    : "+f"(d[0]),"+f"(d[1]),"+f"(d[2]),"+f"(d[3]),"+f"(d[4]),"+f"(d[5]),"+f"(d[6]),"+f"(d[7]),"+f"(d[8]),"+f"(d[9]),"+f"(d[10]),"+f"(d[11]),"+f"(d[12]),"+f"(d[13]),"+f"(d[14]),"+f"(d[15]),"+f"(d[16]),"+f"(d[17]),"+f"(d[18]),"+f"(d[19]),"+f"(d[20]),"+f"(d[21]),"+f"(d[22]),"+f"(d[23]),"+f"(d[24]),"+f"(d[25]),"+f"(d[26]),"+f"(d[27]),"+f"(d[28]),"+f"(d[29]),"+f"(d[30]),"+f"(d[31]),"+f"(d[32]),"+f"(d[33]),"+f"(d[34]),"+f"(d[35]),"+f"(d[36]),"+f"(d[37]),"+f"(d[38]),"+f"(d[39]),"+f"(d[40]),"+f"(d[41]),"+f"(d[42]),"+f"(d[43]),"+f"(d[44]),"+f"(d[45]),"+f"(d[46]),"+f"(d[47]),"+f"(d[48]),"+f"(d[49]),"+f"(d[50]),"+f"(d[51]),"+f"(d[52]),"+f"(d[53]),"+f"(d[54]),"+f"(d[55]),"+f"(d[56]),"+f"(d[57]),"+f"(d[58]),"+f"(d[59]),"+f"(d[60]),"+f"(d[61]),"+f"(d[62]),"+f"(d[63]),"+f"(d[64]),"+f"(d[65]),"+f"(d[66]),"+f"(d[67]),"+f"(d[68]),"+f"(d[69]),"+f"(d[70]),"+f"(d[71]),"+f"(d[72]),"+f"(d[73]),"+f"(d[74]),"+f"(d[75]),"+f"(d[76]),"+f"(d[77]),"+f"(d[78]),"+f"(d[79]),"+f"(d[80]),"+f"(d[81]),"+f"(d[82]),"+f"(d[83]),"+f"(d[84]),"+f"(d[85]),"+f"(d[86]),"+f"(d[87]),"+f"(d[88]),"+f"(d[89]),"+f"(d[90]),"+f"(d[91]),"+f"(d[92]),"+f"(d[93]),"+f"(d[94]),"+f"(d[95]),"+f"(d[96]),"+f"(d[97]),"+f"(d[98]),"+f"(d[99]),"+f"(d[100]),"+f"(d[101]),"+f"(d[102]),"+f"(d[103]),"+f"(d[104]),"+f"(d[105]),"+f"(d[106]),"+f"(d[107]),"+f"(d[108]),"+f"(d[109]),"+f"(d[110]),"+f"(d[111])
    : "r"(alo), "r"(blo), "n"(AOFF), "n"(AHI), "n"(BOFF), "n"(BHI), "n"(ACC));
}
template <int AOFF, uint32_t AHI, int BOFF, uint32_t BHI, int ACC>
__device__ __forceinline__ void wgmma_ss232(float (&d)[116], uint32_t alo, uint32_t blo) {
  asm volatile("{\n.reg .pred p;\n.reg .b64 ad, bd;\nsetp.ne.b32 p, %122, 0;\n"
    "mov.b64 ad, {%116, %119};\nadd.s64 ad, ad, %118;\nmov.b64 bd, {%117, %121};\nadd.s64 bd, bd, %120;\n"
    "wgmma.mma_async.sync.aligned.m64n232k16.f32.bf16.bf16 {%0,%1,%2,%3,%4,%5,%6,%7,%8,%9,%10,%11,%12,%13,%14,%15,%16,%17,%18,%19,%20,%21,%22,%23,%24,%25,%26,%27,%28,%29,%30,%31,%32,%33,%34,%35,%36,%37,%38,%39,%40,%41,%42,%43,%44,%45,%46,%47,%48,%49,%50,%51,%52,%53,%54,%55,%56,%57,%58,%59,%60,%61,%62,%63,%64,%65,%66,%67,%68,%69,%70,%71,%72,%73,%74,%75,%76,%77,%78,%79,%80,%81,%82,%83,%84,%85,%86,%87,%88,%89,%90,%91,%92,%93,%94,%95,%96,%97,%98,%99,%100,%101,%102,%103,%104,%105,%106,%107,%108,%109,%110,%111,%112,%113,%114,%115}, ad, bd, p, 1, 1, 1, 1;\n}\n"
    : "+f"(d[0]),"+f"(d[1]),"+f"(d[2]),"+f"(d[3]),"+f"(d[4]),"+f"(d[5]),"+f"(d[6]),"+f"(d[7]),"+f"(d[8]),"+f"(d[9]),"+f"(d[10]),"+f"(d[11]),"+f"(d[12]),"+f"(d[13]),"+f"(d[14]),"+f"(d[15]),"+f"(d[16]),"+f"(d[17]),"+f"(d[18]),"+f"(d[19]),"+f"(d[20]),"+f"(d[21]),"+f"(d[22]),"+f"(d[23]),"+f"(d[24]),"+f"(d[25]),"+f"(d[26]),"+f"(d[27]),"+f"(d[28]),"+f"(d[29]),"+f"(d[30]),"+f"(d[31]),"+f"(d[32]),"+f"(d[33]),"+f"(d[34]),"+f"(d[35]),"+f"(d[36]),"+f"(d[37]),"+f"(d[38]),"+f"(d[39]),"+f"(d[40]),"+f"(d[41]),"+f"(d[42]),"+f"(d[43]),"+f"(d[44]),"+f"(d[45]),"+f"(d[46]),"+f"(d[47]),"+f"(d[48]),"+f"(d[49]),"+f"(d[50]),"+f"(d[51]),"+f"(d[52]),"+f"(d[53]),"+f"(d[54]),"+f"(d[55]),"+f"(d[56]),"+f"(d[57]),"+f"(d[58]),"+f"(d[59]),"+f"(d[60]),"+f"(d[61]),"+f"(d[62]),"+f"(d[63]),"+f"(d[64]),"+f"(d[65]),"+f"(d[66]),"+f"(d[67]),"+f"(d[68]),"+f"(d[69]),"+f"(d[70]),"+f"(d[71]),"+f"(d[72]),"+f"(d[73]),"+f"(d[74]),"+f"(d[75]),"+f"(d[76]),"+f"(d[77]),"+f"(d[78]),"+f"(d[79]),"+f"(d[80]),"+f"(d[81]),"+f"(d[82]),"+f"(d[83]),"+f"(d[84]),"+f"(d[85]),"+f"(d[86]),"+f"(d[87]),"+f"(d[88]),"+f"(d[89]),"+f"(d[90]),"+f"(d[91]),"+f"(d[92]),"+f"(d[93]),"+f"(d[94]),"+f"(d[95]),"+f"(d[96]),"+f"(d[97]),"+f"(d[98]),"+f"(d[99]),"+f"(d[100]),"+f"(d[101]),"+f"(d[102]),"+f"(d[103]),"+f"(d[104]),"+f"(d[105]),"+f"(d[106]),"+f"(d[107]),"+f"(d[108]),"+f"(d[109]),"+f"(d[110]),"+f"(d[111]),"+f"(d[112]),"+f"(d[113]),"+f"(d[114]),"+f"(d[115])
    : "r"(alo), "r"(blo), "n"(AOFF), "n"(AHI), "n"(BOFF), "n"(BHI), "n"(ACC));
}
template <int OFF, uint32_t BHI, int ACC>
__device__ __forceinline__ void wgmma_rs224(float (&d)[112], uint32_t a0, uint32_t a1, uint32_t a2, uint32_t a3, uint32_t blo) {
  asm volatile("{\n.reg .pred p;\n.reg .b64 bd;\nsetp.ne.b32 p, %119, 0;\nmov.b64 bd, {%116, %118};\nadd.s64 bd, bd, %117;\n"
    "wgmma.mma_async.sync.aligned.m64n224k16.f32.bf16.bf16 {%0,%1,%2,%3,%4,%5,%6,%7,%8,%9,%10,%11,%12,%13,%14,%15,%16,%17,%18,%19,%20,%21,%22,%23,%24,%25,%26,%27,%28,%29,%30,%31,%32,%33,%34,%35,%36,%37,%38,%39,%40,%41,%42,%43,%44,%45,%46,%47,%48,%49,%50,%51,%52,%53,%54,%55,%56,%57,%58,%59,%60,%61,%62,%63,%64,%65,%66,%67,%68,%69,%70,%71,%72,%73,%74,%75,%76,%77,%78,%79,%80,%81,%82,%83,%84,%85,%86,%87,%88,%89,%90,%91,%92,%93,%94,%95,%96,%97,%98,%99,%100,%101,%102,%103,%104,%105,%106,%107,%108,%109,%110,%111}, {%112,%113,%114,%115}, bd, p, 1, 1, 1;\n}\n"
    : "+f"(d[0]),"+f"(d[1]),"+f"(d[2]),"+f"(d[3]),"+f"(d[4]),"+f"(d[5]),"+f"(d[6]),"+f"(d[7]),"+f"(d[8]),"+f"(d[9]),"+f"(d[10]),"+f"(d[11]),"+f"(d[12]),"+f"(d[13]),"+f"(d[14]),"+f"(d[15]),"+f"(d[16]),"+f"(d[17]),"+f"(d[18]),"+f"(d[19]),"+f"(d[20]),"+f"(d[21]),"+f"(d[22]),"+f"(d[23]),"+f"(d[24]),"+f"(d[25]),"+f"(d[26]),"+f"(d[27]),"+f"(d[28]),"+f"(d[29]),"+f"(d[30]),"+f"(d[31]),"+f"(d[32]),"+f"(d[33]),"+f"(d[34]),"+f"(d[35]),"+f"(d[36]),"+f"(d[37]),"+f"(d[38]),"+f"(d[39]),"+f"(d[40]),"+f"(d[41]),"+f"(d[42]),"+f"(d[43]),"+f"(d[44]),"+f"(d[45]),"+f"(d[46]),"+f"(d[47]),"+f"(d[48]),"+f"(d[49]),"+f"(d[50]),"+f"(d[51]),"+f"(d[52]),"+f"(d[53]),"+f"(d[54]),"+f"(d[55]),"+f"(d[56]),"+f"(d[57]),"+f"(d[58]),"+f"(d[59]),"+f"(d[60]),"+f"(d[61]),"+f"(d[62]),"+f"(d[63]),"+f"(d[64]),"+f"(d[65]),"+f"(d[66]),"+f"(d[67]),"+f"(d[68]),"+f"(d[69]),"+f"(d[70]),"+f"(d[71]),"+f"(d[72]),"+f"(d[73]),"+f"(d[74]),"+f"(d[75]),"+f"(d[76]),"+f"(d[77]),"+f"(d[78]),"+f"(d[79]),"+f"(d[80]),"+f"(d[81]),"+f"(d[82]),"+f"(d[83]),"+f"(d[84]),"+f"(d[85]),"+f"(d[86]),"+f"(d[87]),"+f"(d[88]),"+f"(d[89]),"+f"(d[90]),"+f"(d[91]),"+f"(d[92]),"+f"(d[93]),"+f"(d[94]),"+f"(d[95]),"+f"(d[96]),"+f"(d[97]),"+f"(d[98]),"+f"(d[99]),"+f"(d[100]),"+f"(d[101]),"+f"(d[102]),"+f"(d[103]),"+f"(d[104]),"+f"(d[105]),"+f"(d[106]),"+f"(d[107]),"+f"(d[108]),"+f"(d[109]),"+f"(d[110]),"+f"(d[111])
    : "r"(a0), "r"(a1), "r"(a2), "r"(a3), "r"(blo), "n"(OFF), "n"(BHI), "n"(ACC));
}
template <int OFF, uint32_t BHI, int ACC>
__device__ __forceinline__ void wgmma_rs56(float (&d)[28], uint32_t a0, uint32_t a1, uint32_t a2, uint32_t a3, uint32_t blo) {
  asm volatile("{\n.reg .pred p;\n.reg .b64 bd;\nsetp.ne.b32 p, %35, 0;\nmov.b64 bd, {%32, %34};\nadd.s64 bd, bd, %33;\n"
    "wgmma.mma_async.sync.aligned.m64n56k16.f32.bf16.bf16 {%0,%1,%2,%3,%4,%5,%6,%7,%8,%9,%10,%11,%12,%13,%14,%15,%16,%17,%18,%19,%20,%21,%22,%23,%24,%25,%26,%27}, {%28,%29,%30,%31}, bd, p, 1, 1, 1;\n}\n"
    : "+f"(d[0]),"+f"(d[1]),"+f"(d[2]),"+f"(d[3]),"+f"(d[4]),"+f"(d[5]),"+f"(d[6]),"+f"(d[7]),"+f"(d[8]),"+f"(d[9]),"+f"(d[10]),"+f"(d[11]),"+f"(d[12]),"+f"(d[13]),"+f"(d[14]),"+f"(d[15]),"+f"(d[16]),"+f"(d[17]),"+f"(d[18]),"+f"(d[19]),"+f"(d[20]),"+f"(d[21]),"+f"(d[22]),"+f"(d[23]),"+f"(d[24]),"+f"(d[25]),"+f"(d[26]),"+f"(d[27])
    : "r"(a0), "r"(a1), "r"(a2), "r"(a3), "r"(blo), "n"(OFF), "n"(BHI), "n"(ACC));
}

__device__ __forceinline__ void st128(uint4* p, uint32_t a, uint32_t b, uint32_t c, uint32_t d) {
  asm volatile("{\n.reg .b128 v;\n.reg .b64 lo, hi;\nmov.b64 lo, {%1, %2};\nmov.b64 hi, {%3, %4};\nmov.b128 v, {lo, hi};\n"
               "st.relaxed.gpu.global.b128 [%0], v;\n}" ::"l"(p), "r"(a), "r"(b), "r"(c), "r"(d) : "memory");
}
__device__ __forceinline__ void ld128(const uint4* p, uint32_t* r) {
  asm volatile("{\n.reg .b128 v;\n.reg .b64 lo, hi;\nld.relaxed.gpu.global.b128 v, [%4];\nmov.b128 {lo, hi}, v;\n"
               "mov.b64 {%0, %1}, lo;\nmov.b64 {%2, %3}, hi;\n}" : "=r"(r[0]), "=r"(r[1]), "=r"(r[2]), "=r"(r[3]) : "l"(p) : "memory");
}

template <int OFF, uint32_t BHI, int ACC>
__device__ __forceinline__ void wgmma_rs32(float (&d)[16], uint32_t a0, uint32_t a1, uint32_t a2, uint32_t a3, uint32_t blo) {
  asm volatile("{\n.reg .pred p;\n.reg .b64 bd;\nsetp.ne.b32 p, %23, 0;\nmov.b64 bd, {%20, %22};\nadd.s64 bd, bd, %21;\n"
    "wgmma.mma_async.sync.aligned.m64n32k16.f32.bf16.bf16 {%0,%1,%2,%3,%4,%5,%6,%7,%8,%9,%10,%11,%12,%13,%14,%15}, {%16,%17,%18,%19}, bd, p, 1, 1, 0;\n}\n"
    : "+f"(d[0]),"+f"(d[1]),"+f"(d[2]),"+f"(d[3]),"+f"(d[4]),"+f"(d[5]),"+f"(d[6]),"+f"(d[7]),"+f"(d[8]),"+f"(d[9]),"+f"(d[10]),"+f"(d[11]),"+f"(d[12]),"+f"(d[13]),"+f"(d[14]),"+f"(d[15])
    : "r"(a0), "r"(a1), "r"(a2), "r"(a3), "r"(blo), "n"(OFF), "n"(BHI), "n"(ACC));
}
template <int OFF, uint32_t BHI, int ACC>
__device__ __forceinline__ void wgmma_rs24(float (&d)[12], uint32_t a0, uint32_t a1, uint32_t a2, uint32_t a3, uint32_t blo) {
  asm volatile("{\n.reg .pred p;\n.reg .b64 bd;\nsetp.ne.b32 p, %19, 0;\nmov.b64 bd, {%16, %18};\nadd.s64 bd, bd, %17;\n"
    "wgmma.mma_async.sync.aligned.m64n24k16.f32.bf16.bf16 {%0,%1,%2,%3,%4,%5,%6,%7,%8,%9,%10,%11}, {%12,%13,%14,%15}, bd, p, 1, 1, 1;\n}\n"
    : "+f"(d[0]),"+f"(d[1]),"+f"(d[2]),"+f"(d[3]),"+f"(d[4]),"+f"(d[5]),"+f"(d[6]),"+f"(d[7]),"+f"(d[8]),"+f"(d[9]),"+f"(d[10]),"+f"(d[11])
    : "r"(a0), "r"(a1), "r"(a2), "r"(a3), "r"(blo), "n"(OFF), "n"(BHI), "n"(ACC));
}
template <int OFF, uint32_t BHI, int ACC>
__device__ __forceinline__ void wgmma_rs16(float (&d)[8], uint32_t a0, uint32_t a1, uint32_t a2, uint32_t a3, uint32_t blo) {
  asm volatile("{\n.reg .pred p;\n.reg .b64 bd;\nsetp.ne.b32 p, %15, 0;\nmov.b64 bd, {%12, %14};\nadd.s64 bd, bd, %13;\n"
    "wgmma.mma_async.sync.aligned.m64n16k16.f32.bf16.bf16 {%0,%1,%2,%3,%4,%5,%6,%7}, {%8,%9,%10,%11}, bd, p, 1, 1, 1;\n}\n"
    : "+f"(d[0]),"+f"(d[1]),"+f"(d[2]),"+f"(d[3]),"+f"(d[4]),"+f"(d[5]),"+f"(d[6]),"+f"(d[7])
    : "r"(a0), "r"(a1), "r"(a2), "r"(a3), "r"(blo), "n"(OFF), "n"(BHI), "n"(ACC));
}

constexpr int A_R1 = 0;
constexpr int A_R2A = A_R1 + 2624, A_R2B = A_R2A + 768, A_R3A = A_R2B + 768, A_R3B = A_R3A + 528;
constexpr int A_K1024 = A_R3B + 528;
constexpr int A_W5 = A_K1024 + 16;
constexpr int A_W3 = A_W5 + 4096;
constexpr int A_W9 = A_W3 + 4112;
constexpr int A_W7 = A_W9 + 2080;
constexpr int A_V  = A_W7 + 2080 + 32;
constexpr int A_SCL = A_V + 2048;
constexpr int A_UB = A_SCL + 16;
constexpr int A_STG = A_UB + 5248;
constexpr int A_Y2 = A_STG, A_Y3 = A_Y2 + 6528, A_YB = A_Y3 + 4352;
constexpr int A_REC = A_STG + 4 * 4352;
constexpr int A_CH = A_REC + 8192;
constexpr int A_BAR = 4 * A_CH, A_WST = (A_BAR + 128 + 127) / 128 * 128;
static_assert(A_W5 % 16 == 0 && A_UB % 16 == 0 && A_CH % 16 == 0 && A_YB + 4096 <= A_REC, "layout");

struct cf { float x, y; };
__device__ __forceinline__ cf cmul(cf a, cf b) { cf r; r.x = fmaf(a.x, b.x, -a.y * b.y); r.y = fmaf(a.x, b.y, a.y * b.x); return r; }
__device__ __forceinline__ cf cexp_l(float lr, float li, float l) {
  float mag; asm("ex2.approx.ftz.f32 %0, %1;" : "=f"(mag) : "f"((lr * l) * 1.4426950408889634f));
  const float th = li * l;
  const float k = (fmaf(th, 0.15915494f, 12582912.f)) - 12582912.f;
  float ph = fmaf(th, 0.15915494f, -k);
  ph = fmaf(th, 6.4206383e-9f, ph) * 6.2831853f;
  cf r; r.x = mag * __cosf(ph); r.y = mag * __sinf(ph); return r;
}
__device__ __forceinline__ void sts16(uint32_t a, uint32_t v) { asm volatile("st.shared.u16 [%0], %1;" ::"r"(a), "h"((uint16_t)v) : "memory"); }
__device__ __forceinline__ void sts32(uint32_t a, uint32_t v) { asm volatile("st.shared.u32 [%0], %1;" ::"r"(a), "r"(v) : "memory"); }
__device__ __forceinline__ void sts64(uint32_t a, uint32_t v0, uint32_t v1) { asm volatile("st.shared.v2.u32 [%0], {%1, %2};" ::"r"(a), "r"(v0), "r"(v1) : "memory"); }
__device__ __forceinline__ void sts128(uint32_t a, uint32_t v0, uint32_t v1, uint32_t v2, uint32_t v3) {
  asm volatile("st.shared.v4.u32 [%0], {%1, %2, %3, %4};" ::"r"(a), "r"(v0), "r"(v1), "r"(v2), "r"(v3) : "memory");
}
__device__ __forceinline__ uint32_t lds32(uint32_t a) { uint32_t v; asm volatile("ld.shared.u32 %0, [%1];" : "=r"(v) : "r"(a) : "memory"); return v; }
__device__ __forceinline__ uint4 lds128(uint32_t a) {
  uint4 v; asm volatile("ld.shared.v4.u32 {%0, %1, %2, %3}, [%4];" : "=r"(v.x), "=r"(v.y), "=r"(v.z), "=r"(v.w) : "r"(a) : "memory"); return v;
}
__device__ __forceinline__ void ldsm4(uint32_t* r, uint32_t a) {
  asm volatile("ldmatrix.sync.aligned.m8n8.x4.shared.b16 {%0,%1,%2,%3}, [%4];" : "=r"(r[0]), "=r"(r[1]), "=r"(r[2]), "=r"(r[3]) : "r"(a) : "memory");
}
__device__ __forceinline__ void mma16816(float* d, uint32_t a0, uint32_t a1, uint32_t a2, uint32_t a3, uint32_t b0, uint32_t b1) {
  asm volatile("mma.sync.aligned.m16n8k16.row.col.f32.f16.f16.f32 {%0,%1,%2,%3}, {%4,%5,%6,%7}, {%8,%9}, {%0,%1,%2,%3};"
               : "+f"(d[0]), "+f"(d[1]), "+f"(d[2]), "+f"(d[3]) : "r"(a0), "r"(a1), "r"(a2), "r"(a3), "r"(b0), "r"(b1));
}
__device__ __forceinline__ uint32_t pack_h(float lo, float hi) { uint32_t r; asm("cvt.rn.f16x2.f32 %0, %1, %2;" : "=r"(r) : "f"(hi), "f"(lo)); return r; }
__device__ __forceinline__ uint32_t pack_h(cf v) { return pack_h(v.x, v.y); }
__device__ __forceinline__ uint32_t hcmul(uint32_t x, uint32_t r0, uint32_t r1) {
  const __half2 hx = *(__half2*)&x;
  const __half2 y = __hfma2(__high2half2(hx), *(__half2*)&r1, __hmul2(__low2half2(hx), *(__half2*)&r0));
  return *(const uint32_t*)&y;
}
__device__ __forceinline__ float ln_rstd(float var) {
  float sd, rs;
  asm("sqrt.approx.f32 %0, %1;" : "=f"(sd) : "f"(rbf(rbf(var) + 1e-5f)));
  asm("rcp.approx.f32 %0, %1;" : "=f"(rs) : "f"(rbf(sd)));
  return rs;
}
__device__ __forceinline__ uint32_t hsub2_bf(uint32_t a, uint32_t b) { uint32_t r; asm("sub.rn.bf16x2 %0, %1, %2;" : "=r"(r) : "r"(a), "r"(b)); return r; }
__device__ __forceinline__ void bar_sync(int id, int n) { asm volatile("bar.sync %0, %1;" ::"r"(id), "r"(n) : "memory"); }

template <int S> struct F1B { static constexpr int c = S / 4 + ((S & 3) == 3 ? 0 : 0), cc = (16 * S) / 64, ks = (64 * cc - (16 * S - 48)) / 16, off = (A_UB + 2 * ks * 656 + (9 - cc) * 16) / 16; };

template <int NS>
__device__ __forceinline__ void load_quads(uint32_t* q, uint32_t addr) {
#pragma unroll
  for (int i = 0; i < NS; i++) {
    q[4 * i] = lds32(addr + i * 64); q[4 * i + 1] = lds32(addr + i * 64 + 32);
    q[4 * i + 2] = i ? q[4 * i - 3] : lds32(addr - 32);
    q[4 * i + 3] = q[4 * i];
  }
#pragma unroll
  for (int i = 0; i < 4 * NS; i++) asm volatile("" : "+r"(q[i]));
}
template <int S0, int NS>
__device__ __forceinline__ void f1_steps(float (&acc)[16], const uint32_t* a, uint32_t blo) {
  if constexpr (NS > 0) {
    wgmma_rs32<F1B<S0>::off, 8, S0 != 0>(acc, a[0], a[1], a[2], a[3], blo);
    f1_steps<S0 + 1, NS - 1>(acc, a + 4, blo);
  }
}
template <int S0, int NS, int BASE, int FIRST>
__device__ __forceinline__ void s2_steps(float (&acc)[12], const uint32_t* a, uint32_t blo) {
  if constexpr (NS > 0) {
    wgmma_rs24<BASE / 16 + (112 - 16 * S0), 64, !(FIRST && S0 == 0)>(acc, a[0], a[1], a[2], a[3], blo);
    s2_steps<S0 + 1, NS - 1, BASE, FIRST>(acc, a + 4, blo);
  }
}
template <int S0, int NS, int BASE, int FIRST>
__device__ __forceinline__ void s3_steps(float (&acc)[8], const uint32_t* a, uint32_t blo) {
  if constexpr (NS > 0) {
    wgmma_rs16<BASE / 16 + (48 - 16 * S0), 65, !(FIRST && S0 == 0)>(acc, a[0], a[1], a[2], a[3], blo);
    s3_steps<S0 + 1, NS - 1, BASE, FIRST>(acc, a + 4, blo);
  }
}

__device__ __forceinline__ void tma3d(uint32_t dst, const CUtensorMap* m, int c1, int c2, uint32_t bar) {
  asm volatile("cp.async.bulk.tensor.3d.shared::cluster.global.mbarrier::complete_tx::bytes [%0], [%1, {0, %3, %4}], [%2];"
               ::"r"(dst), "l"(m), "r"(bar), "r"(c1), "r"(c2) : "memory");
}
__device__ __forceinline__ void bulk_st(void* dst, uint32_t src, int bytes) {
  asm volatile("cp.async.bulk.global.shared::cta.bulk_group [%0], [%1], %2;" ::"l"(dst), "r"(src), "r"(bytes) : "memory");
}

__device__ __forceinline__ void phase_a(
        unsigned char* sm, const uint32_t bar_rec, const uint32_t ep_addr, const CUtensorMap* mg, const CUtensorMap* mu, const CUtensorMap* md,
        const __nv_bfloat16* __restrict__ x, const uint32_t* __restrict__ are, const uint32_t* __restrict__ aim,
        const uint32_t* __restrict__ bre, const uint32_t* __restrict__ bim, const uint32_t* __restrict__ cre,
        const uint32_t* __restrict__ cim, const unsigned short* __restrict__ logdt, const unsigned short* __restrict__ dskip,
        const uint4* __restrict__ wgate, const uint4* __restrict__ wup) {
  const uint32_t sb = s2u(sm), bar_w = bar_rec + 16;
  const int tid = threadIdx.x, warp = __shfl_sync(~0u, tid >> 5, 0), wg = warp >> 2, lane = tid & 31, wq = warp & 3, t128 = tid & 127;
  const int blk = blockIdx.x;
  const bool conv = (blk & 7) != 7;
  const int cblk = blk - (blk >> 3);

  uint2 xr[4];
  {
    const uint2* p = (const uint2*)(x + (size_t)(blk * 16 + warp) * DM);
    xr[0] = __ldg(p + lane); xr[1] = __ldg(p + 32 + lane); xr[2] = __ldg(p + 64 + lane);
    xr[3] = lane < 16 ? __ldg(p + 96 + lane) : make_uint2(0, 0);
  }
  const int ch = conv ? cblk * 4 + wg : 0;
  const uint32_t cb = sb + wg * A_CH;
  uint32_t prm[6];
  {
    const int i = ch * 128 + t128;
    prm[0] = __ldg(are + i); prm[1] = __ldg(aim + i); prm[2] = __ldg(bre + i); prm[3] = __ldg(bim + i); prm[4] = __ldg(cre + i); prm[5] = __ldg(cim + i);
  }
  const uint32_t ldt = __ldg(logdt + ch);
  uint32_t cnt0 = 0;
  if (tid == 0) cnt0 = __ldcg(&g_cnt1);
  const int g = lane >> 2, t = lane & 3;
#pragma unroll
  for (int i = 0; i < 4; i++) if (i < 3 || t128 < (A_W5 + 1024) / 16 - 384) sts128(cb + (i * 128 + t128) * 16, 0, 0, 0, 0);
  if (t128 < 64) sts128(cb + A_W3 + t128 * 16, 0, 0, 0, 0);
  if (t128 < 72) sts128(cb + A_UB + (t128 / 9) * 656 + (t128 % 9) * 16, 0, 0, 0, 0);
  {
    float s = 0.f, q = 0.f;
#pragma unroll
    for (int i = 0; i < 4; i++) {
      const float a = bf_lo(xr[i].x), b = bf_hi(xr[i].x), c = bf_lo(xr[i].y), d = bf_hi(xr[i].y);
      s += (a + b) + (c + d);
      q = fmaf(a, a, q); q = fmaf(b, b, q); q = fmaf(c, c, q); q = fmaf(d, d, q);
    }
#pragma unroll
    for (int o = 16; o; o >>= 1) { s += __shfl_xor_sync(~0u, s, o); q += __shfl_xor_sync(~0u, q, o); }
    const float mean = s * (1.f / DM);
    const float var = fmaxf(fmaf(-mean, mean, q * (1.f / DM)), 0.f);
    const float rs = ln_rstd(var);
    const uint32_t mm = pack_bf16(mean, mean);
    const uint32_t tu = sb + A_REC + (warp >> 3) * A_CH + (warp & 7) * 912 + lane * 8, tx = tu + 2 * A_CH;
#pragma unroll
    for (int i = 0; i < 4; i++) {
      if (i < 3 || lane < 16) {
        const uint32_t d0 = hsub2_bf(xr[i].x, mm), d1 = hsub2_bf(xr[i].y, mm);
        sts64(tu + i * 256, pack_bf16(bf_lo(d0) * rs, bf_hi(d0) * rs), pack_bf16(bf_lo(d1) * rs, bf_hi(d1) * rs));
        sts64(tx + i * 256, xr[i].x, xr[i].y);
      }
    }
  }
  if (tid == 0) sts32(ep_addr, (cnt0 >> 7) + 1u);
  if (tid == 320) TR(0, 1);
  auto publish_rows = [&]() {
    bar_sync(5, 512);
    uint4* dst = g_ux + ((size_t)(warp * 8 + (lane >> 2)) * 128 + blk) * 4 + ((lane ^ (blk >> 1)) & 3);
#pragma unroll
    for (int i = 0; i < 4; i++) {
      if (i < 3 || warp < 8) {
        uint32_t r[4];
        asm volatile("ldmatrix.sync.aligned.m8n8.x4.trans.shared.b16 {%0,%1,%2,%3}, [%4];" : "=r"(r[0]), "=r"(r[1]), "=r"(r[2]), "=r"(r[3])
                     : "r"(sb + A_REC + (lane >> 3) * A_CH + (lane & 7) * 912 + (warp + 16 * i) * 16) : "memory");
        dst[i * 65536] = make_uint4(r[0], r[1], r[2], r[3]);
      }
    }
    if (warp != 0) asm volatile("bar.arrive 6, 512;" ::: "memory");
  };
  auto release_rows = [&]() {
    if (warp == 0) {
      bar_sync(6, 512);
      if (lane == 0) { asm volatile("red.release.gpu.global.add.u32 [%0], 1;" ::"l"(&g_cnt1) : "memory"); TR(0, 8); }
      __syncwarp();
    }
  };

  if (!conv) {
    publish_rows();
    release_rows();
    const int a = blk >> 3, mat = a >> 3, j = a & 7;
    if (warp == 15) bar_sync(7, 64);
    if (warp == 0) asm volatile("bar.arrive 7, 64;" ::: "memory");
    if (warp == 15) {
      if (lane == 0) {
        asm volatile("fence.proxy.async.shared::cta;" ::: "memory");
        for (int c = 0; c < 8; c++) { mbar_expect(bar_w + 8 * c, 12544); tma3d(sb + 65536 + c * 12544, md, a * 112, c * 7, bar_w + 8 * c); }
        for (int c = 0; c < 8; c++) {
          mbar_wait(bar_w + 8 * c, 0);
          bulk_st(g_wimg + (size_t)(a >> 1) * 37632 + 25088 + (c * 2 + (a & 1)) * 784, sb + 65536 + c * 12544, 12544);
        }
        asm volatile("cp.async.bulk.commit_group;" ::: "memory");
        asm volatile("cp.async.bulk.wait_group 0;" ::: "memory");
        TR(0, 10);
      }
      return;
    }
    float s[8];
#pragma unroll
    for (int k = 0; k < 8; k++) s[k] = 0.f;
    if (lane < 28 && warp < 14) {
      const uint4* src = (mat ? wup : wgate) + j * 28 + lane + (size_t)warp * 224;
#pragma unroll
      for (int hb = 0; hb < 2; hb++) {
        uint4 v[16];
#pragma unroll
        for (int r = 0; r < 16; r++) v[r] = __ldg(src + (size_t)(hb * 16 + r) * 14 * 224);
#pragma unroll
        for (int r = 0; r < 16; r++) {
          s[0] += bf_lo(v[r].x); s[1] += bf_hi(v[r].x); s[2] += bf_lo(v[r].y); s[3] += bf_hi(v[r].y);
          s[4] += bf_lo(v[r].z); s[5] += bf_hi(v[r].z); s[6] += bf_lo(v[r].w); s[7] += bf_hi(v[r].w);
        }
      }
      float4* red = (float4*)(sm + A_STG + warp * 896 + lane * 32);
      red[0] = make_float4(s[0], s[1], s[2], s[3]); red[1] = make_float4(s[4], s[5], s[6], s[7]);
    }
    bar_sync(5, 480);
    if (tid < 224) {
      float cs = 0.f;
#pragma unroll
      for (int w = 0; w < 14; w++) cs += *(const float*)(sm + A_STG + w * 896 + tid * 4);
      const float hi = rbf(cs), mid = rbf(cs - hi), lo = rbf(cs - hi - mid);
      const int q = tid / 112, n = tid % 112 + 112 * mat;
      __nv_bfloat16* dst = (__nv_bfloat16*)(g_cimg + (j * 2 + q) * 224 + (n >> 3) * 8) + (n & 7);
      dst[0] = __float2bfloat16_rn(hi); dst[8] = __float2bfloat16_rn(mid); dst[16] = __float2bfloat16_rn(lo);
#pragma unroll
      for (int k = 3; k < 8; k++) dst[8 * k] = __float2bfloat16_rn(0.f);
    }
    if (tid == 0) TR(0, 11);
    return;
  }

  const int wr = (wq + wg) & 3;
  const int bk = wr * 32 + lane;
  {
    const uint32_t stg = cb + A_STG + wq * 4352, sw = stg + lane * 8;
    const float dt = rbf(expf(__uint_as_float(ldt << 16)));
    float lr[2], li[2];
    cf bq[2], b0[2], b4[2];
    uint32_t bf[48];
#pragma unroll
    for (int m = 0; m < 2; m++) {
      lr[m] = dt * (m ? bf_hi(prm[0]) : bf_lo(prm[0]));
      li[m] = dt * (m ? bf_hi(prm[1]) : bf_lo(prm[1]));
    }
    {
      cf b[2], z[2];
#pragma unroll
      for (int m = 0; m < 2; m++) {
        cf db, c;
        db.x = dt * (m ? bf_hi(prm[2]) : bf_lo(prm[2])); db.y = -dt * (m ? bf_hi(prm[3]) : bf_lo(prm[3]));
        c.x = m ? bf_hi(prm[4]) : bf_lo(prm[4]); c.y = -(m ? bf_hi(prm[5]) : bf_lo(prm[5]));
        b[m] = cmul(c, db);
        z[m] = cexp_l(lr[m], -li[m], 1.f);
        bq[m] = cexp_l(lr[m], -li[m], 256.f);
      }
      publish_rows();
      {
        const float mx = fmaxf(fmaxf(fabsf(b[0].x), fabsf(b[0].y)), fmaxf(fabsf(b[1].x), fabsf(b[1].y)));
        const uint32_t e = max(__reduce_max_sync(~0u, __float_as_uint(mx)) >> 23, 14u);
        const float sc = __uint_as_float((267u - e) << 23);
        b[0].x *= sc; b[0].y *= sc; b[1].x *= sc; b[1].y *= sc;
        if (lane == 0) sts32(cb + A_SCL + wq * 4, (e - 13u) << 23);
      }
#pragma unroll
      for (int i = 0; i < 8; i++) {
        sts64(sw + i * 272, pack_h(b[0]), pack_h(b[1]));
        if (!(i & 1)) {
          cf e0 = cmul(b[0], bq[0]), e1 = cmul(b[1], bq[1]);
          sts64(sw + (8 + i / 2) * 272, pack_h(e0), pack_h(e1));
          if (i == 0) { b0[0] = e0; b0[1] = e1; }
          if (i == 4) { b4[0] = e0; b4[1] = e1; }
        }
        if (i < 7) { b[0] = cmul(b[0], z[0]); b[1] = cmul(b[1], z[1]); }
        if (i == 0) release_rows();
      }
#pragma unroll
      for (int i = 0; i < 7; i++) {
        b0[0] = cmul(b0[0], bq[0]); b0[1] = cmul(b0[1], bq[1]);
        sts64(sw + (i < 2 ? 12 + 2 * i : i - 2) * 272, pack_h(b0[0]), pack_h(b0[1]));
        if (i < 2) {
          b4[0] = cmul(b4[0], bq[0]); b4[1] = cmul(b4[1], bq[1]);
          sts64(sw + (13 + 2 * i) * 272, pack_h(b4[0]), pack_h(b4[1]));
        }
        if (i == 1) {
          __syncwarp();
#pragma unroll
          for (int n = 0; n < 2; n++)
#pragma unroll
            for (int k2 = 0; k2 < 4; k2++) ldsm4(bf + n * 16 + k2 * 4, stg + (n * 8 + (lane & 7)) * 272 + k2 * 64 + (lane >> 3) * 16);
          __syncwarp();
        }
      }
    }
    uint32_t cv = 0;
    if (tid == 160) asm volatile("ld.relaxed.gpu.global.u32 %0, [%1];" : "=r"(cv) : "l"(&g_cnt1) : "memory");
    {
      const cf p0 = cexp_l(lr[0], li[0], 8.f), p1 = cexp_l(lr[1], li[1], 8.f);
      cf v0 = p0, v1 = p1;
      sts64(sw + 8 * 272, 0x3C00u, 0x3C00u);
#pragma unroll
      for (int i = 1; i < 8; i++) {
        sts64(sw + (8 + i) * 272, pack_h(v0), pack_h(v1));
        v0 = cmul(v0, p0); v1 = cmul(v1, p1);
      }
      const uint32_t ra = stg + 5 * 272 + (lane >> 2) * 64 + (lane & 1) * 32 + (lane & 2) * 4;
      sts64(ra, pack_h(v0), pack_h(-v0.y, v0.x));
      sts64(ra + 16, pack_h(v1), pack_h(-v1.y, v1.x));
    }
    __syncwarp();
    if (tid == 320) TR(0, 16);
#pragma unroll
    for (int k2 = 0; k2 < 4; k2++) ldsm4(bf + 32 + k2 * 4, stg + (lane & 7) * 272 + k2 * 64 + (lane >> 3) * 16);
      if (warp == 5) {
        if (lane == 0) {
          const uint32_t tgt = lds32(ep_addr) * 128u;
          int it = 0;
          while ((int)(cv - tgt) < 0 && ++it < 400000) asm volatile("ld.relaxed.gpu.global.u32 %0, [%1];" : "=r"(cv) : "l"(&g_cnt1) : "memory");
          asm volatile("fence.acquire.gpu;" ::: "memory");
          asm volatile("fence.proxy.async.global;" ::: "memory");
          TR(0, 9);
        }
        __syncwarp();
#pragma unroll
        for (int c2 = 0; c2 < 4; c2++) bulk_ld_elect<8192>(sb + c2 * A_CH + A_REC, g_ux + (size_t)(cblk * 4 + c2) * 512, bar_rec);
      }
    float c[6][4];
#pragma unroll
    for (int i = 0; i < 6; i++) { c[i][0] = 0.f; c[i][1] = 0.f; c[i][2] = 0.f; c[i][3] = 0.f; }
#pragma unroll
    for (int k2 = 0; k2 < 4; k2++) {
      uint32_t a[4];
      ldsm4(a, stg + (8 + (lane & 7)) * 272 + k2 * 64 + (lane >> 3) * 16);
#pragma unroll
      for (int kk = 0; kk < 2; kk++) {
        const int ks = 2 * k2 + kk;
        const uint4 r4 = lds128(stg + 5 * 272 + ks * 64 + t * 16);
        const uint32_t r[4] = {r4.x, r4.z, r4.y, r4.w};
        const uint32_t x0 = a[2 * kk], y0 = a[2 * kk + 1];
        const uint32_t x1 = hcmul(x0, r[0], r[2]), y1 = hcmul(y0, r[1], r[3]);
        const uint32_t x2 = hcmul(x1, r[0], r[2]), y2 = hcmul(y1, r[1], r[3]);
        const uint32_t x3 = hcmul(x2, r[0], r[2]), y3 = hcmul(y2, r[1], r[3]);
#pragma unroll
        for (int n = 0; n < 3; n++) {
          mma16816(c[n * 2], x0, x1, y0, y1, bf[n * 16 + ks * 2], bf[n * 16 + ks * 2 + 1]);
          mma16816(c[n * 2 + 1], x2, x3, y2, y3, bf[n * 16 + ks * 2], bf[n * 16 + ks * 2 + 1]);
        }
      }
      if (k2 == 2 && t128 == 96) {
        mbar_expect(bar_w + 8 * wg, 7168);
        tma3d(sb + A_WST + wg * 7168, (ch & 1) ? mu : mg, ((ch >> 1) % 14) * 32, ((ch >> 1) / 14) * 14, bar_w + 8 * wg);
      }
    }
    __syncwarp();
#pragma unroll
    for (int i = 0; i < 6; i++)
      sts128(stg + i * 512 + lane * 16, __float_as_uint(c[i][0]), __float_as_uint(c[i][1]), __float_as_uint(c[i][2]), __float_as_uint(c[i][3]));
  }
  if (tid == 320) TR(0, 2);

  uint32_t xt[8], ud[8];
  {
    mbar_wait(bar_rec, 0);
    if (tid == 320) TR(0, 4);
    uint4 r[4];
#pragma unroll
    for (int i = 0; i < 4; i++) r[i] = lds128(cb + A_REC + bk * 64 + ((i ^ (bk >> 1)) & 3) * 16);
    const uint32_t ua = cb + A_UB + ((2 * bk) & 7) * 656 + ((bk >> 2) + 9) * 16;
    sts128(ua, r[0].x, r[1].x, r[2].x, r[3].x);
    sts128(ua + 656, r[0].y, r[1].y, r[2].y, r[3].y);
    if (bk <= 96) {
      const bool neg = bk == 96;
      const int bp = neg ? -1 : bk;
      uint32_t h[4];
      h[0] = lds32(cb + A_REC + ((bp - 1) & 127) * 64 + ((2 ^ ((bp - 1) >> 1)) & 3) * 16 + 4);
      h[1] = lds32(cb + A_REC + ((bp - 1) & 127) * 64 + ((3 ^ ((bp - 1) >> 1)) & 3) * 16 + 4);
      h[2] = lds32(cb + A_REC + (bp + 1) * 64 + ((0 ^ ((bp + 1) >> 1)) & 3) * 16);
      h[3] = lds32(cb + A_REC + (bp + 1) * 64 + ((1 ^ ((bp + 1) >> 1)) & 3) * 16);
      if (bp <= 0) { h[0] = 0; h[1] = 0; }
      const uint32_t wd[12] = {h[0], h[1], neg ? 0 : r[0].x, neg ? 0 : r[1].x, neg ? 0 : r[2].x, neg ? 0 : r[3].x,
                               neg ? 0 : r[0].y, neg ? 0 : r[1].y, neg ? 0 : r[2].y, neg ? 0 : r[3].y, h[2], h[3]};
      float P[25];
      P[0] = 0.f;
#pragma unroll
      for (int i = 0; i < 12; i++) { P[2 * i + 1] = P[2 * i] + bf_lo(wd[i]); P[2 * i + 2] = P[2 * i + 1] + bf_hi(wd[i]); }
#define WIN(i, hw) (P[(i) + 5 + (hw)] - P[(i) + 4 - (hw)])
#define WPK(i, hw) pack_bf16(WIN(i, hw), WIN((i) + 1, hw))
      const int tp = 2 * bp;
      const uint32_t a3 = cb + A_W3 + (tp + 64) * 16 + 8, a5 = cb + A_W5 + (tp + 64) * 16;
      sts64(a3, WPK(0, 1), WPK(2, 1));
      sts128(a3 + 8, WPK(4, 1), WPK(6, 1), WPK(8, 1), WPK(10, 1));
      sts64(a3 + 24, WPK(12, 1), WPK(14, 1));
      sts128(a5, WPK(0, 2), WPK(2, 2), WPK(4, 2), WPK(6, 2));
      sts128(a5 + 16, WPK(8, 2), WPK(10, 2), WPK(12, 2), WPK(14, 2));
      if (bp < 64) {
        sts128(cb + A_W7 + 1040 + bp * 16, WPK(0, 3), WPK(2, 3), WPK(4, 3), WPK(6, 3));
        sts128(cb + A_W7 + (bp + 1) * 16, WPK(8, 3), WPK(10, 3), WPK(12, 3), WPK(14, 3));
        sts128(cb + A_W9 + (bp + 1) * 16, WPK(0, 4), WPK(2, 4), WPK(4, 4), WPK(6, 4));
        sts128(cb + A_W9 + 1040 + (bp + 1) * 16, WPK(8, 4), WPK(10, 4), WPK(12, 4), WPK(14, 4));
#define VPK(i) pack_bf16(P[(i) + 2] - P[i], P[(i) + 3] - P[(i) + 1])
        sts128(cb + A_V + bp * 32, VPK(0), VPK(2), VPK(4), VPK(6));
        sts128(cb + A_V + bp * 32 + 16, VPK(8), VPK(10), VPK(12), VPK(14));
      }
    }
  }
  asm volatile("fence.proxy.async.shared::cta;" ::: "memory");
  bar_sync(1 + wg, 128);
  if (tid == 320) TR(0, 3);
  {
    const uint4 sc = lds128(cb + A_SCL);
    const float scl[4] = {__uint_as_float(sc.x), __uint_as_float(sc.y), __uint_as_float(sc.z), __uint_as_float(sc.w)};
#pragma unroll
    for (int rep = 0; rep < 2; rep++) {
      const int qd = rep ? 2 + wr : 3 - wr;
      if (rep == 0 || wr >= 2) {
        float s[4] = {0.f, 0.f, 0.f, 0.f};
#pragma unroll
        for (int w = 0; w < 4; w++) {
          uint4 u4 = lds128(cb + A_STG + w * 4352 + qd * 512 + lane * 16);
          s[0] = fmaf(__uint_as_float(u4.x), scl[w], s[0]); s[1] = fmaf(__uint_as_float(u4.y), scl[w], s[1]);
          s[2] = fmaf(__uint_as_float(u4.z), scl[w], s[2]); s[3] = fmaf(__uint_as_float(u4.w), scl[w], s[3]);
        }
#pragma unroll
        for (int hf = 0; hf < 2; hf++) {
          const int j = (qd & 1) * 16 + g + 8 * hf;
          const uint32_t pk = pack_bf16(s[2 * hf + 1], s[2 * hf]);
          const uint32_t v0 = pk >> 16, v1 = pk & 0xFFFFu, v00 = v0 * 0x10001u;
          if (rep == 1) {
            if (t < 2) {
#pragma unroll
              for (int e = 0; e < 2; e++) {
                const int lam = 128 + 32 * (2 * t + e) + j, mu = lam >> 1;
                const uint32_t val = e ? v1 : v0;
                uint32_t a = cb + ((lam & 1) ? A_R3B : A_R3A) + mu * 4;
                if (lam == 128) { a = cb + A_R2A + 128 * 4; sts32(cb + A_K1024, val << 16); }
                sts16(a, val); sts16(a + 6, val);
              }
            } else if (t == 2 && j == 0) { sts16(cb + A_R3A + 128 * 4, v0); }
          } else if (qd < 2) {
            const uint32_t a = cb + A_R1 + (62 + 8 * j + 2 * t) * 4;
            sts16(a, v0); sts32(a + 4, pk); sts16(a + 10, v1);
          } else if (t < 2) {
            const int L = 256 + 8 * j + 4 * t;
            const uint32_t a = cb + A_R1 + (62 + L) * 4;
            if (L > 256) { sts16(a - 4, v0); sts32(a, v00); } else sts16(a, v0);
            sts32(a + 4, v00); sts32(a + 8, pk); sts16(a + 14, v1);
          } else {
            const int mu = 64 + 32 * (t - 2) + j;
            if (mu == 64) {
              const uint32_t a = cb + A_R1 + (62 + 512) * 4;
              sts16(a - 4, v0); sts32(a, v00); sts32(a + 4, v00); sts32(a + 8, v00); sts16(a + 14, v0);
            } else { sts16(cb + A_R2A + mu * 4, v0); sts16(cb + A_R2A + mu * 4 + 6, v0); }
            sts16(cb + A_R2B + mu * 4, v1); sts16(cb + A_R2B + mu * 4 + 6, v1);
          }
        }
      }
    }
  }
  bar_sync(1 + wg, 128);
  if (tid == 320) TR(0, 5);

  {
    const uint32_t cbu = cb;
    const uint32_t blo_k = ((cbu & 0x3FFFF) >> 4) | (41u << 16);
    const uint32_t blo_n = ((cbu & 0x3FFFF) >> 4) | (8u << 16);
    const uint32_t tb = cb + (16 * wq + g - 2 * t) * 4;
    float y1[16], y2[12], y3[8];
    const uint32_t dk16 = __ldg(dskip + ch);
    uint32_t qa[32], qb[32];
    const uint32_t t1 = tb + A_R1 + (62 - 48) * 4;
    load_quads<4>(qa, tb + A_R3A + 17 * 4); load_quads<4>(qa + 16, tb + A_R3B + 16 * 4);
    wg_fence();
    s3_steps<0, 4, A_W9, 1>(y3, qa, blo_n); s3_steps<0, 4, A_W7, 0>(y3, qa + 16, blo_n);
    wg_commit();
    load_quads<8>(qb, tb + A_R2A + 16 * 4);
    wg_fence(); s2_steps<0, 8, A_W5, 1>(y2, qb, blo_n); wg_commit();
    wg_wait<1>(); load_quads<8>(qa, tb + A_R2B + 16 * 4);
    wg_fence(); s2_steps<0, 8, A_W3, 0>(y2, qa, blo_n); wg_commit();
    wg_wait<1>(); load_quads<8>(qb, t1);
    wg_fence(); f1_steps<0, 8>(y1, qb, blo_k); wg_commit();
    wg_wait<1>(); load_quads<8>(qa, t1 + 8 * 64);
    wg_fence(); f1_steps<8, 8>(y1, qa, blo_k); wg_commit();
    reg_fence(y2); reg_fence(y3);
  if (t128 == 96) {
    mbar_wait(bar_w + 8 * wg, 0);
    bulk_st(g_wimg + (size_t)((ch >> 1) / 28) * 37632 + ((ch >> 1) % 28) * 896 + (ch & 1) * 448, sb + A_WST + wg * 7168, 7168);
    asm volatile("cp.async.bulk.commit_group;" ::: "memory");
  }

    if (tid == 320) TR(0, 18);
    {
      const float k1024 = __uint_as_float(lds32(cb + A_K1024));
#pragma unroll
      for (int i = 0; i < 2; i++)
#pragma unroll
        for (int hf = 0; hf < 2; hf++) {
          const int idx = 16 * (16 * wq + g + 8 * hf) + 8 * i + 2 * t;
          const uint32_t vv = lds32(cb + A_V + idx * 2);
          sts64(cb + A_Y3 + (idx + 4 * (idx >> 6)) * 4, __float_as_uint(fmaf(k1024, bf_lo(vv), y3[4 * i + 2 * hf])),
                __float_as_uint(fmaf(k1024, bf_hi(vv), y3[4 * i + 2 * hf + 1])));
        }
#pragma unroll
      for (int i = 0; i < 3; i++)
#pragma unroll
        for (int hf = 0; hf < 2; hf++) {
          const int idx = 512 * i + 8 * (16 * wq + g + 8 * hf) + 2 * t;
          sts64(cb + A_Y2 + (idx + 4 * (idx >> 6)) * 4, __float_as_uint(y2[4 * i + 2 * hf]), __float_as_uint(y2[4 * i + 2 * hf + 1]));
        }
    }
    wg_wait<1>(); load_quads<8>(qb, t1 + 16 * 64);
    wg_fence(); f1_steps<16, 8>(y1, qb, blo_k); wg_commit();
    wg_wait<1>(); load_quads<8>(qa, t1 + 24 * 64);
    wg_fence(); f1_steps<24, 8>(y1, qa, blo_k); wg_commit();
    wg_wait<1>(); load_quads<5>(qb, t1 + 32 * 64);
    wg_fence(); f1_steps<32, 5>(y1, qb, blo_k); wg_commit();
    bar_sync(1 + wg, 128);
    float ex[12];
#pragma unroll
    for (int i = 1; i < 4; i++)
#pragma unroll
      for (int k = 0; k < 4; k++) {
        const int aa = 8 * i + 2 * t + (k & 1), b = 16 * wq + g + 8 * (k >> 1);
        float e = __uint_as_float(lds32(cb + A_Y2 + ((aa - 8) * 68 + b) * 4));
        if (i >= 2) e += __uint_as_float(lds32(cb + A_Y3 + ((aa - 16) * 68 + b) * 4));
        ex[4 * (i - 1) + k] = e;
      }
    {
      const uint32_t dk = dk16 * 0x10001u;
#pragma unroll
      for (int i = 0; i < 4; i++) {
        const uint4 r = lds128(cb + A_REC + bk * 64 + ((i ^ (bk >> 1)) & 3) * 16);
        ud[i] = hmul2_bf(r.x, dk); ud[4 + i] = hmul2_bf(r.y, dk); xt[i] = r.z; xt[4 + i] = r.w;
      }
    }
    wg_wait<0>();
    reg_fence(y1);
    if (tid == 320) TR(0, 6);
#pragma unroll
    for (int i = 0; i < 12; i++) y1[4 + i] += ex[i];
#pragma unroll
    for (int i = 0; i < 2; i++) {
      const int mi = lane >> 3, aa = 8 * (2 * i + (mi >> 1)) + (lane & 7);
      asm volatile("stmatrix.sync.aligned.m8n8.x4.trans.shared.b16 [%0], {%1,%2,%3,%4};"
                   ::"r"(cb + A_YB + aa * 128 + (((2 * wq + (mi & 1)) ^ (lane & 7)) << 4)),
                     "r"(pack_bf16(y1[8 * i], y1[8 * i + 1])), "r"(pack_bf16(y1[8 * i + 2], y1[8 * i + 3])),
                     "r"(pack_bf16(y1[8 * i + 4], y1[8 * i + 5])), "r"(pack_bf16(y1[8 * i + 6], y1[8 * i + 7])) : "memory");
    }
  }
  bar_sync(1 + wg, 128);
#pragma unroll
  for (int c = 0; c < 2; c++) {
    const int tau = 2 * bk + c, r = ch & 7;
    const uint4 y = lds128(cb + A_YB + (tau >> 3) * 128 + (((tau ^ (tau >> 3)) & 7) << 4));
    g_himg[(size_t)(tau >> 4) * 7168 + (ch >> 3) * 128 + ((tau >> 3) & 1) * 64 + r * 8 + ((tau & 7) ^ r)] =
        make_uint4(hadd2_bf(xt[4 * c], hadd2_bf(y.x, ud[4 * c])), hadd2_bf(xt[4 * c + 1], hadd2_bf(y.y, ud[4 * c + 1])),
                   hadd2_bf(xt[4 * c + 2], hadd2_bf(y.z, ud[4 * c + 2])), hadd2_bf(xt[4 * c + 3], hadd2_bf(y.w, ud[4 * c + 3])));
  }
  if (t128 == 96) asm volatile("cp.async.bulk.wait_group 0;" ::: "memory");
  if (tid == 320) TR(0, 7);
}

constexpr int B_SA = 0, B_RING = 114688, B_SLOT = 14848, B_NSLOT = 7;
constexpr int B_CS = B_RING + B_NSLOT * B_SLOT;
constexpr int B_RED = B_CS + 7168;
constexpr int B_BAR = B_RED + 256;
constexpr int B_SMEM = B_BAR + 1024, A_SMEM = A_WST + 28672;

__device__ __forceinline__ uint32_t mapa(uint32_t a, uint32_t r) { uint32_t o; asm("mapa.shared::cluster.u32 %0, %1, %2;" : "=r"(o) : "r"(a), "r"(r)); return o; }
template <class T> __device__ __forceinline__ T* pin(T* p) { asm volatile("" : "+l"(p)); return p; }
__device__ __forceinline__ uint32_t pin(uint32_t v) { asm volatile("" : "+r"(v)); return v; }
template <int Q, int ST>
__device__ __forceinline__ void g1_stage(float (&acc)[116], uint32_t alo, uint32_t blo, uint32_t bar_full, uint32_t bar_h) {
  constexpr int s = Q * 14 + ST, sl = s % B_NSLOT;
  if (Q == 0) mbar_wait(bar_h + 8 * ST, 0);
  mbar_wait(bar_full + 8 * sl, (s / B_NSLOT) & 1);
  wg_fence();
  if (Q == 0) {
    wgmma_ss232<(2 * ST) * 256, 0x40000080u, (sl * B_SLOT) / 16, 32, ST != 0>(acc, alo, blo);
    wgmma_ss232<(2 * ST + 1) * 256, 0x40000080u, (sl * B_SLOT + 256) / 16, 32, 1>(acc, alo, blo);
  } else {
    wgmma_ss224<(2 * ST) * 256, 0x40000080u, (sl * B_SLOT) / 16, 32, ST != 0>(*(float(*)[112])acc, alo, blo);
    wgmma_ss224<(2 * ST + 1) * 256, 0x40000080u, (sl * B_SLOT + 256) / 16, 32, 1>(*(float(*)[112])acc, alo, blo);
  }
}

__global__ void __launch_bounds__(512, 1)
k_front(const __grid_constant__ CUtensorMap mg, const __grid_constant__ CUtensorMap mu, const __grid_constant__ CUtensorMap md,
        const __nv_bfloat16* __restrict__ x, const uint32_t* __restrict__ are, const uint32_t* __restrict__ aim,
        const uint32_t* __restrict__ bre, const uint32_t* __restrict__ bim, const uint32_t* __restrict__ cre,
        const uint32_t* __restrict__ cim, const unsigned short* __restrict__ logdt, const unsigned short* __restrict__ dskip,
        const uint4* __restrict__ wgate, const uint4* __restrict__ wup) {
  extern __shared__ __align__(1024) unsigned char sm[];
  const uint32_t bar_rec = s2u(sm) + A_BAR;
  if (threadIdx.x == 320) TR(0, 0);
  asm volatile("griddepcontrol.launch_dependents;");
  if (threadIdx.x == 160) {
    mbar_init(bar_rec, 4);
    for (int i = 0; i < 8; i++) mbar_init(bar_rec + 16 + 8 * i, 1);
    asm volatile("fence.mbarrier_init.release.cluster;" ::: "memory");
    asm volatile("prefetch.tensormap [%0];" ::"l"(&mg)); asm volatile("prefetch.tensormap [%0];" ::"l"(&mu)); asm volatile("prefetch.tensormap [%0];" ::"l"(&md));
  }
  phase_a(sm, bar_rec, bar_rec + 8, &mg, &mu, &md, x, are, aim, bre, bim, cre, cim, logdt, dskip, wgate, wup);
}

__global__ void __cluster_dims__(2, 1, 1) __launch_bounds__(384, 1) k_ffn(__nv_bfloat16* __restrict__ out) {
  extern __shared__ __align__(1024) unsigned char sm[];
  const uint32_t sb = s2u(sm);
  const int tid = threadIdx.x, warp = __shfl_sync(~0u, tid >> 5, 0), wg = warp >> 2, lane = tid & 31;
  const uint32_t bar_full = sb + B_BAR, bar_empty = bar_full + 64, bar_h = bar_full + 128, bar_cs = bar_full + 240,
                 bar_hh = bar_full + 304, bar_afree = bar_full + 336, bar_out = bar_full + 352;
  if (tid == 0) {
    TR(1, 0);
    for (int i = 0; i < B_NSLOT; i++) { mbar_init(bar_full + 8 * i, 1); mbar_init(bar_empty + 8 * i, 2); }
    asm volatile("fence.mbarrier_init.release.cluster;" ::: "memory");
  } else if (tid == 32) {
    for (int i = 0; i < 14; i++) mbar_init(bar_h + 8 * i, 1);
    asm volatile("fence.mbarrier_init.release.cluster;" ::: "memory");
  } else if (tid == 64) {
    mbar_init(bar_cs, 1);
    for (int i = 0; i < 4; i++) { mbar_init(bar_hh + 8 * i, 1); mbar_expect(bar_hh + 8 * i, 14336); }
    mbar_init(bar_afree, 4); mbar_init(bar_afree + 8, 2);
    for (int i = 0; i < 6; i++) mbar_init(bar_out + 8 * i, 128);
    asm volatile("fence.mbarrier_init.release.cluster;" ::: "memory");
  } else if (tid >= 128 && tid < 352) {
    sts128(sb + B_RING + ((tid - 128) >> 5) * B_SLOT + 14336 + (tid & 31) * 16, 0x3F803F80u, 0x3F803F80u, 0x3F803F80u, 0x3F803F80u);
  }
  asm volatile("fence.proxy.async.shared::cta;" ::: "memory");
  __syncthreads();
  asm volatile("barrier.cluster.arrive.relaxed.aligned;" ::: "memory");
  const int rank = blockIdx.x & 1, rt = blockIdx.x >> 3, j = blockIdx.x & 7, p = j >> 1, cg = 4 * rank + p;
  const int wq = warp & 3, t128 = tid & 127, g = lane >> 2, t = lane & 3;
  uint32_t ep, tag;
  auto load_ep = [&]() { asm volatile("ld.relaxed.gpu.global.u32 %0, [%1];" : "=r"(ep) : "l"(&g_cnt1) : "memory"); };
  auto a_slot = [&](int i, int own) { return B_SA + (i + (i >= own)) * 14336; };
  auto out_addr = [&](int cc, int w) { return sb + a_slot((cc & 2) + w, cg) + (cc & 1) * 7168; };
  auto in_cta = [&](int q) { return rt * 8 + ((p + 3 - q) & 3) * 2 + rank; };
  auto in_src = [&](int q, int cw) { return g_part + (size_t)(in_cta(q) * 3 + q) * 896 + cw * 112; };
  auto in_bad = [&](uint32_t (&in)[14]) { return ((in[3] ^ tag) | (in[7] ^ tag) | (in[11] ^ tag) | (in[13] ^ tag)) & 0x10000u; };
  auto in_load = [&](uint32_t (&in)[14], const uint4* gs) {
#pragma unroll
    for (int i = 0; i < 3; i++) ld128(gs + i * 32, in + 4 * i);
    asm volatile("{\n.reg .b64 v;\nld.relaxed.gpu.global.b64 v, [%2];\nmov.b64 {%0, %1}, v;\n}"
                 : "=r"(in[12]), "=r"(in[13]) : "l"((const uint2*)(gs + 96) - lane) : "memory");
  };
  auto in_check = [&](uint32_t (&in)[14], int q, int cw) {
    int it = 0;
    while (in_bad(in) && ++it < 400000) in_load(in, pin(in_src(q, cw) + lane));
  };

  if (wg == 2) {
    asm volatile("setmaxnreg.dec.sync.aligned.u32 40;");
    asm volatile("barrier.cluster.wait.aligned;" ::: "memory");
    asm volatile("griddepcontrol.wait;" ::: "memory");
    if (warp == 8) {
      if (lane == 0) TR(1, 1);
      const char* wsrc = (const char*)g_wimg + (size_t)j * 602112;
      const char* hsrc = (const char*)g_himg + (size_t)rt * 114688 + rank * 4096;
#pragma unroll
      for (int s = 0; s < 28; s++) {
        if (s < B_NSLOT) bulk_ld_mc_elect<4096>(sb + B_SA + s * 8192 + rank * 4096, hsrc + s * 8192, bar_h + 8 * s);
        if (s == B_NSLOT) {
#pragma unroll
          for (int i = 7; i < 14; i++) bulk_ld_mc_elect<4096>(sb + B_SA + i * 8192 + rank * 4096, hsrc + i * 8192, bar_h + 8 * i);
          bulk_ld_elect<7168>(sb + B_CS, g_cimg + j * 448, bar_cs);
        }
        if (s >= B_NSLOT) mbar_wait(bar_empty + 8 * (s % B_NSLOT), (s / B_NSLOT + 1) & 1);
        bulk_ld_elect<14336>(sb + B_RING + (s % B_NSLOT) * B_SLOT, wsrc + s * 14336, bar_full + 8 * (s % B_NSLOT));
      }
      const char* dsrc[2] = {wsrc + 401408 + rank * 100352, (const char*)g_wimg + (size_t)(j ^ 1) * 602112 + 401408 + rank * 100352};
#pragma unroll
      for (int i = 0; i < 16; i++) {
        const int ci = i < 3 ? 0 : i < 6 ? 1 : i < 8 ? i - 6 : i < 12 ? 2 : 3;
        const int kp = i < 3 ? i : i < 6 ? i - 3 : i < 8 ? 3 : (i & 3);
        mbar_wait(bar_empty + 8 * (i % B_NSLOT), (i / B_NSLOT + 1) & 1);
        bulk_ld_elect<12544>(sb + B_RING + (i % B_NSLOT) * B_SLOT, dsrc[kp >> 1] + ((p + 1 + ci) & 3) * 25088 + (kp & 1) * 12544, bar_full + 8 * (i % B_NSLOT));
      }
    } else if (warp >= 10) {
      const int t64 = tid - 320;
      load_ep();
      const int r = (lane >> 1) & 7, c = (j & 3) * 2 + (lane & 1);
      const uint32_t src = sb + B_SA + (t64 >> 4) * 2048 + (j >> 2) * 1024 + r * 128 + ((c ^ r) << 4);
      float a[16];
#pragma unroll
      for (int k = 0; k < 16; k++) a[k] = 0.f;
#pragma unroll 1
      for (int i = 0; i < 14; i++) {
        mbar_wait(bar_h + 8 * i, 0);
        uint4 v = lds128(src + i * 8192);
        float e[8] = {bf_lo(v.x), bf_hi(v.x), bf_lo(v.y), bf_hi(v.y), bf_lo(v.z), bf_hi(v.z), bf_lo(v.w), bf_hi(v.w)};
#pragma unroll
        for (int k = 0; k < 8; k++) { a[2 * k] += e[k]; a[2 * k + 1] = fmaf(e[k], e[k], a[2 * k + 1]); }
        __nanosleep(160);
      }
      __syncwarp();
      if (lane == 0) { asm volatile("mbarrier.arrive.shared::cluster.b64 _, [%0];" ::"r"(mapa(bar_afree, rank ^ 1)) : "memory"); }
#pragma unroll
      for (int rd = 0; rd < 4; rd++) {
        const int n = 8 >> rd;
        const bool up = lane & (2 * n);
#pragma unroll
        for (int k = 0; k < 8; k++) {
          if (k < n) {
            float keep = up ? a[k + n] : a[k], give = up ? a[k] : a[k + n];
            a[k] = keep + __shfl_xor_sync(~0u, give, 2 * n);
          }
        }
      }
      float* red = (float*)(sm + B_RED);
      red[(warp & 1) * 32 + (lane & 1) * 16 + (lane >> 1)] = a[0];
      bar_sync(1, 64);
      if (t64 < 16) {
        float mean = (red[2 * t64] + red[32 + 2 * t64]) * (1.f / DM);
        float var = fmaxf(fmaf(-mean, mean, (red[2 * t64 + 1] + red[33 + 2 * t64]) * (1.f / DM)), 0.f);
        float rs = ln_rstd(var);
        asm volatile("st.relaxed.gpu.global.u32 [%0], %1;"
                     ::"l"(g_stat2 + rt * 128 + j * 16 + t64), "r"((__float_as_uint(rs * rs) & ~1u) | ((ep >> 7) & 1u)) : "memory");
      }
      if (t64 == 0) TR(1, 2);
      if (lane == 0) {
        const int w = warp & 1;
        for (int cc = 0; cc < 2; cc++) {
          mbar_wait(bar_out + 8 * (cc * 2 + w), 0);
          asm volatile("cp.async.bulk.global.shared::cta.bulk_group [%0], [%1], 7168;"
                       ::"l"(g_part + (size_t)(blockIdx.x * 3 + cc) * 896 + w * 448), "r"(out_addr(cc, w)) : "memory");
          if (w) TR(1, 27 + cc);
        }
        asm volatile("cp.async.bulk.commit_group;" ::: "memory");
        asm volatile("cp.async.bulk.wait_group 0;" ::: "memory");
      }
    }
  } else {
    asm volatile("setmaxnreg.inc.sync.aligned.u32 232;");
    asm volatile("barrier.cluster.wait.aligned;" ::: "memory");
    uint32_t hh[56];
    const bool relt = t128 == 0;
    auto release = [&](int sl) { if (relt) mbar_arrive(bar_empty + 8 * sl); };
    auto send_hh = [&](int q) {
      const uint32_t da = mapa(sb + a_slot(2 * q + wg, cg ^ 4) + t128 * 16, rank ^ 1), db = mapa(bar_hh + 8 * (2 * q + wg), rank ^ 1);
#pragma unroll
      for (int i = 0; i < 7; i++)
        asm volatile("st.async.weak.shared::cluster.mbarrier::complete_tx::bytes.v4.b32 [%0], {%1, %2, %3, %4}, [%5];"
                     ::"r"(da + i * 2048), "r"(hh[28 * q + 4 * i]), "r"(hh[28 * q + 4 * i + 1]),
                       "r"(hh[28 * q + 4 * i + 2]), "r"(hh[28 * q + 4 * i + 3]), "r"(db) : "memory");
    };
    uint32_t alo = ((sb + B_SA + wg * 1024) & 0x3FFFF) >> 4;
    uint32_t blo = (((sb + B_RING) & 0x3FFFF) >> 4) | (8u << 16);
    const uint32_t clo = ((sb + B_CS) & 0x3FFFF) >> 4;
    uint32_t nm0, nm1;
    if (wg == 1) bar_sync(3, 256);
#define G1S(Q, ST) do { if (ST % 7 == 0) { alo = pin(alo); blo = pin(blo); }   \
      g1_stage<Q, ST>(acc, alo, blo, bar_full, bar_h); wg_commit(); \
      if (ST > 0) { wg_wait<1>(); release((Q * 14 + ST - 1) % B_NSLOT); } } while (0)
#define G1HH(Q) do { \
      _Pragma("unroll") \
      for (int i = 0; i < 28; i++) hh[28 * Q + i] = pack_bf16(acc[2 * i] * acc[56 + 2 * i], acc[2 * i + 1] * acc[57 + 2 * i]); \
    } while (0)
    {
      float acc[116];
      G1S(0, 0);
      if (tid == 0) TR(1, 3);
      G1S(0, 1);
      if (wg == 0) asm volatile("bar.arrive 3, 256;" ::: "memory");
      G1S(0, 2); G1S(0, 3); G1S(0, 4); G1S(0, 5); G1S(0, 6); G1S(0, 7); G1S(0, 8); G1S(0, 9); G1S(0, 10); G1S(0, 11); G1S(0, 12);
      G1S(0, 13);
      if (tid == 0) TR(1, 4);
      mbar_wait(bar_cs, 0);
      wg_wait<0>(); reg_fence(acc); release(13 % B_NSLOT);
      {
        const uint32_t msk = t == 0 ? 0xFFFFFFFFu : t == 1 ? 0xFFFFu : 0u;
        const float a = acc[112] * (-1.f / DM), b = acc[114] * (-1.f / DM);
        nm0 = pack_bf16(a, a) & msk; nm1 = pack_bf16(b, b) & msk;
      }
      wg_fence();
      wgmma_rs224<0, 8, 1>(*(float(*)[112])acc, nm0, nm1, 0u, 0u, clo);
      wg_commit(); wg_wait<0>(); reg_fence(acc);
      G1HH(0);
      if (tid == 0) TR(1, 5);
      G1S(1, 0); G1S(1, 1); G1S(1, 2); G1S(1, 3); G1S(1, 4); G1S(1, 5); G1S(1, 6);
      if (relt) asm volatile("mbarrier.arrive.shared::cluster.b64 _, [%0];" ::"r"(mapa(bar_afree, rank ^ 1)) : "memory");
      G1S(1, 7); G1S(1, 8); G1S(1, 9);
      if (relt) asm volatile("mbarrier.arrive.shared::cluster.b64 _, [%0];" ::"r"(mapa(bar_afree + 8, rank ^ 1)) : "memory");
      mbar_wait(bar_afree, 0);
      send_hh(0);
      G1S(1, 10); G1S(1, 11); G1S(1, 12);
      load_ep();
      g1_stage<1, 13>(acc, alo, blo, bar_full, bar_h);
      wgmma_rs224<224, 8, 1>(*(float(*)[112])acc, nm0, nm1, 0u, 0u, clo);
      wg_commit(); wg_wait<1>(); release(26 % B_NSLOT);
      wg_wait<0>(); reg_fence(acc); release(27 % B_NSLOT);
      G1HH(1);
      if (tid == 0) TR(1, 6);
    }
    float accA[28], accB[28];
    uint32_t ph0[28], ph1[28];
    ep = pin(ep >> 7); tag = pin((ep & 1u) << 16);
#define ISSUE(acc, I, a, FIRST) do { \
      constexpr int s_ = 28 + (I), sl_ = s_ % B_NSLOT; \
      if (sl_ == 0) blo = pin(blo); \
      mbar_wait(bar_full + 8 * sl_, (s_ / B_NSLOT) & 1); \
      wg_fence(); \
      wgmma_rs56<(sl_ * B_SLOT + 0 * 256) / 16, 112, !(FIRST)>(acc, (a)[0], (a)[1], (a)[2], (a)[3], blo); \
      wgmma_rs56<(sl_ * B_SLOT + 1 * 256) / 16, 112, 1>(acc, (a)[4], (a)[5], (a)[6], (a)[7], blo); \
      wgmma_rs56<(sl_ * B_SLOT + 2 * 256) / 16, 112, 1>(acc, (a)[8], (a)[9], (a)[10], (a)[11], blo); \
      wgmma_rs56<(sl_ * B_SLOT + 3 * 256) / 16, 112, 1>(acc, (a)[12], (a)[13], (a)[14], (a)[15], blo); \
      wgmma_rs56<(sl_ * B_SLOT + 4 * 256) / 16, 112, 1>(acc, (a)[16], (a)[17], (a)[18], (a)[19], blo); \
      wgmma_rs56<(sl_ * B_SLOT + 5 * 256) / 16, 112, 1>(acc, (a)[20], (a)[21], (a)[22], (a)[23], blo); \
      wgmma_rs56<(sl_ * B_SLOT + 6 * 256) / 16, 112, 1>(acc, (a)[24], (a)[25], (a)[26], (a)[27], blo); \
      wg_commit(); } while (0)
    auto rel = [&](int i) { release((28 + i) % B_NSLOT); };
    auto tg = [&](uint32_t v) { return (v & 0xFFFEFFFFu) | tag; };
    auto send = [&](float (&acc)[28], int cc) {
      reg_fence(acc);
      const uint32_t a = out_addr(cc, wg) + wq * 1792;
#pragma unroll
      for (int q = 0; q < 3; q++)
        sts128(a + q * 512 + lane * 16, pack_bf16(acc[8 * q], acc[8 * q + 1]), pack_bf16(acc[8 * q + 2], acc[8 * q + 3]),
               pack_bf16(acc[8 * q + 4], acc[8 * q + 5]), tg(pack_bf16(acc[8 * q + 6], acc[8 * q + 7])));
      sts64(a + 1536 + lane * 8, pack_bf16(acc[24], acc[25]), tg(pack_bf16(acc[26], acc[27])));
      asm volatile("fence.proxy.async.shared::cta;" ::: "memory");
      mbar_arrive(bar_out + 8 * (cc * 2 + wg));
    };
    auto load_hh = [&](uint32_t (&d)[28], int q) {
      mbar_wait(bar_hh + 8 * (2 * q + wg), 0);
      const uint32_t a = sb + a_slot(2 * q + wg, cg) + t128 * 16;
#pragma unroll
      for (int i = 0; i < 7; i++) {
        const uint4 v = lds128(a + i * 2048);
        d[4 * i] = v.x; d[4 * i + 1] = v.y; d[4 * i + 2] = v.z; d[4 * i + 3] = v.w;
      }
    };
    ISSUE(accA, 0, hh, true);
    mbar_wait(bar_afree + 8, 0);
    send_hh(1);
    ISSUE(accA, 1, hh + 28, false);
    load_hh(ph0, 0);
    wg_wait<1>(); rel(0);
    ISSUE(accA, 2, ph0, false);      wg_wait<1>(); rel(1);
    ISSUE(accB, 3, hh, true);        wg_wait<1>(); rel(2);
    ISSUE(accB, 4, hh + 28, false);  wg_wait<1>(); rel(3);
    ISSUE(accB, 5, ph0, false);
    if (tid == 0) TR(1, 11);
    load_hh(ph1, 1);
    wg_wait<1>(); rel(4);
    ISSUE(accA, 6, ph1, false);      wg_wait<1>(); rel(5);
    ISSUE(accB, 7, ph1, false);      wg_wait<1>(); rel(6); send(accA, 0);
    ISSUE(accA, 8, hh, true);        wg_wait<1>(); rel(7); send(accB, 1);
    if (tid == 0) TR(1, 13);
    ISSUE(accA, 9, hh + 28, false);  wg_wait<1>(); rel(8);
    ISSUE(accA, 10, ph0, false);
    ISSUE(accA, 11, ph1, false);
    const int row = rt * 128 + wg * 64 + wq * 16 + g;
    uint32_t r20, r21;
    asm volatile("ld.relaxed.gpu.global.u32 %0, [%1];" : "=r"(r20) : "l"(g_stat2 + row) : "memory");
    asm volatile("ld.relaxed.gpu.global.u32 %0, [%1];" : "=r"(r21) : "l"(g_stat2 + row + 8) : "memory");
    ISSUE(accB, 12, hh, true);
    wg_wait<1>();
    {
      reg_fence(accA);
      uint4* pd = g_part + (size_t)(blockIdx.x * 3 + 2) * 896 + warp * 112 + lane;
#pragma unroll
      for (int q = 0; q < 3; q++)
        st128(pd + q * 32, pack_bf16(accA[8 * q], accA[8 * q + 1]), pack_bf16(accA[8 * q + 2], accA[8 * q + 3]),
              pack_bf16(accA[8 * q + 4], accA[8 * q + 5]), tg(pack_bf16(accA[8 * q + 6], accA[8 * q + 7])));
      asm volatile("{\n.reg .b64 v;\nmov.b64 v, {%1, %2};\nst.relaxed.gpu.global.b64 [%0], v;\n}"
                   ::"l"((uint2*)(pd + 96) - lane), "r"(pack_bf16(accA[24], accA[25])), "r"(tg(pack_bf16(accA[26], accA[27]))) : "memory");
    }
    if (tid == 0) TR(1, 16);
    ISSUE(accB, 13, hh + 28, false);
    ISSUE(accB, 14, ph0, false);
    uint32_t in0[14], in1[14], in2[14];
    in_load(in0, in_src(0, warp) + lane);
    in_load(in1, in_src(1, warp) + lane);
    ISSUE(accB, 15, ph1, false);
    if (tid == 0) TR(1, 7);
    {
      int it = 0;
      while ((((r20 ^ ep) | (r21 ^ ep)) & 1u) && ++it < 400000) {
        asm volatile("ld.relaxed.gpu.global.u32 %0, [%1];" : "=r"(r20) : "l"(g_stat2 + row) : "memory");
        asm volatile("ld.relaxed.gpu.global.u32 %0, [%1];" : "=r"(r21) : "l"(g_stat2 + row + 8) : "memory");
      }
    }
    wg_wait<1>();
    in_load(in2, in_src(2, warp) + lane);
    in_check(in0, 0, warp); in_check(in1, 1, warp);
#pragma unroll
    for (int i = 0; i < 14; i++) { accA[2 * i] = bf_lo(in0[i]) + bf_lo(in1[i]); accA[2 * i + 1] = bf_hi(in0[i]) + bf_hi(in1[i]); }
    if (tid == 0) TR(1, 12);
    wg_wait<0>();
    reg_fence(accB);
    uint32_t hres[16];
#pragma unroll
    for (int i = 0; i < 4; i++) {
      int qq = lane >> 3, r = lane & 7, kg = 7 * cg + 2 * i + (qq >> 1), c = 2 * wq + (qq & 1);
      if (kg > 55) kg = 55;
      asm volatile("ldmatrix.sync.aligned.m8n8.x4.trans.shared.b16 {%0,%1,%2,%3}, [%4];"
                   : "=r"(hres[4 * i]), "=r"(hres[4 * i + 1]), "=r"(hres[4 * i + 2]), "=r"(hres[4 * i + 3])
                   : "r"(sb + B_SA + kg * 2048 + wg * 1024 + r * 128 + ((c ^ r) << 4)) : "memory");
    }
#pragma unroll
    for (int i = 0; i < 28; i++) accB[i] += accA[i];
    if (tid == 0) TR(1, 9);
    in_check(in2, 2, warp);
#pragma unroll
    for (int i = 0; i < 14; i++) { accB[2 * i] += bf_lo(in2[i]); accB[2 * i + 1] += bf_hi(in2[i]); }
    uint32_t* o0 = (uint32_t*)(out + (size_t)row * DM + 56 * cg + 2 * t);
    uint32_t* o1 = o0 + 8 * DM / 2;
#pragma unroll
    for (int i = 0; i < 7; i++) {
      o0[4 * i] = hadd2_bf(hres[2 * i], pack_bf16(accB[4 * i] * __uint_as_float(r20), accB[4 * i + 1] * __uint_as_float(r20)));
      o1[4 * i] = hadd2_bf(hres[2 * i + 1], pack_bf16(accB[4 * i + 2] * __uint_as_float(r21), accB[4 * i + 3] * __uint_as_float(r21)));
    }
    if (tid == 0) TR(1, 10);
    if (tid == 128) TR(1, 15);
  }
}

typedef CUresult (*EncFn)(CUtensorMap*, CUtensorMapDataType, cuuint32_t, void*, const cuuint64_t*, const cuuint64_t*,
                          const cuuint32_t*, const cuuint32_t*, CUtensorMapInterleave, CUtensorMapSwizzle,
                          CUtensorMapL2promotion, CUtensorMapFloatOOBfill);

extern "C" void kernel_launch(void* const* d_in, const int* in_sizes, int n_in, void* d_out, int out_size) {
  const __nv_bfloat16* x = (const __nv_bfloat16*)d_in[0];
  const __nv_bfloat16 *are = (const __nv_bfloat16*)d_in[1], *aim = (const __nv_bfloat16*)d_in[2], *bre = (const __nv_bfloat16*)d_in[3],
                      *bim = (const __nv_bfloat16*)d_in[4], *cre = (const __nv_bfloat16*)d_in[5], *cim = (const __nv_bfloat16*)d_in[6],
                      *logdt = (const __nv_bfloat16*)d_in[7], *dskip = (const __nv_bfloat16*)d_in[8];
  const __nv_bfloat16 *wg = (const __nv_bfloat16*)d_in[10], *wu = (const __nv_bfloat16*)d_in[11], *wd = (const __nv_bfloat16*)d_in[12];

  static EncFn enc = nullptr;
  if (!enc) {
    void* fn = nullptr; cudaDriverEntryPointQueryResult qr;
    cudaGetDriverEntryPoint("cuTensorMapEncodeTiled", &fn, cudaEnableDefault, &qr);
    enc = (EncFn)fn;
    cudaFuncSetAttribute(k_ffn, cudaFuncAttributeMaxDynamicSharedMemorySize, B_SMEM);
    cudaFuncSetAttribute(k_front, cudaFuncAttributeMaxDynamicSharedMemorySize, A_SMEM);
  }
  CUtensorMap mg, mu, md;
  {
    cuuint32_t es[3] = {1, 1, 1};
    cuuint64_t d1[3] = {8, 448, 224}, s1[2] = {3584, 16}; cuuint32_t b1[3] = {8, 32, 14};
    cuuint64_t d2[3] = {8, 1792, 56}, s2[2] = {896, 16}; cuuint32_t b2[3] = {8, 112, 7};
    enc(&mg, CU_TENSOR_MAP_DATA_TYPE_BFLOAT16, 3, (void*)wg, d1, s1, b1, es, CU_TENSOR_MAP_INTERLEAVE_NONE, CU_TENSOR_MAP_SWIZZLE_NONE, CU_TENSOR_MAP_L2_PROMOTION_L2_256B, CU_TENSOR_MAP_FLOAT_OOB_FILL_NONE);
    enc(&mu, CU_TENSOR_MAP_DATA_TYPE_BFLOAT16, 3, (void*)wu, d1, s1, b1, es, CU_TENSOR_MAP_INTERLEAVE_NONE, CU_TENSOR_MAP_SWIZZLE_NONE, CU_TENSOR_MAP_L2_PROMOTION_L2_256B, CU_TENSOR_MAP_FLOAT_OOB_FILL_NONE);
    enc(&md, CU_TENSOR_MAP_DATA_TYPE_BFLOAT16, 3, (void*)wd, d2, s2, b2, es, CU_TENSOR_MAP_INTERLEAVE_NONE, CU_TENSOR_MAP_SWIZZLE_NONE, CU_TENSOR_MAP_L2_PROMOTION_L2_256B, CU_TENSOR_MAP_FLOAT_OOB_FILL_NONE);
  }
  cudaStream_t st = cudaStreamPerThread;
  k_front<<<128, 512, A_SMEM, st>>>(
      mg, mu, md, x, (const uint32_t*)are, (const uint32_t*)aim, (const uint32_t*)bre, (const uint32_t*)bim, (const uint32_t*)cre, (const uint32_t*)cim,
      (const unsigned short*)logdt, (const unsigned short*)dskip, (const uint4*)wg, (const uint4*)wu);
  cudaLaunchConfig_t cfg = {};
  cfg.gridDim = dim3(128); cfg.blockDim = dim3(384); cfg.dynamicSmemBytes = B_SMEM; cfg.stream = st;
  cudaLaunchAttribute at[1];
  at[0].id = cudaLaunchAttributeProgrammaticStreamSerialization; at[0].val.programmaticStreamSerializationAllowed = 1;
  cfg.attrs = at; cfg.numAttrs = 1;
  cudaLaunchKernelEx(&cfg, k_ffn, (__nv_bfloat16*)d_out);
}
```

```cpp
#include <cuda_runtime.h>
#include <cuda_bf16.h>
#include <cuda_fp16.h>
#include <cuda.h>
#include <stdint.h>

constexpr int LSEQ = 2048, DM = 448;

__device__ uint4    g_himg[16 * 114688 / 16];
__device__ uint4    g_cimg[8 * 2 * 224];
__device__ uint32_t g_stat2[LSEQ];
__device__ uint4    g_part[128 * 3 * 896];
__device__ uint4    g_wimg[8 * 602112 / 16];
__device__ uint4    g_ux[DM * 128 * 4];
__device__ unsigned g_cnt1;

#define TR(k, i) do {} while (0)
__device__ __forceinline__ uint32_t s2u(const void* p) { return (uint32_t)__cvta_generic_to_shared(p); }
__device__ __forceinline__ void mbar_init(uint32_t b, int c) { asm volatile("mbarrier.init.shared::cta.b64 [%0], %1;" ::"r"(b), "r"(c)); }
__device__ __forceinline__ void mbar_expect(uint32_t b, int bytes) { asm volatile("mbarrier.arrive.expect_tx.shared::cta.b64 _, [%0], %1;" ::"r"(b), "r"(bytes) : "memory"); }
__device__ __forceinline__ void mbar_arrive(uint32_t b) { asm volatile("mbarrier.arrive.shared::cta.b64 _, [%0];" ::"r"(b) : "memory"); }
__device__ __forceinline__ void mbar_wait(uint32_t b, int ph) {
  asm volatile("{\n.reg .pred p;\n.reg .b32 n;\nmov.b32 n, 0;\nLW:\nmbarrier.try_wait.parity.shared::cta.b64 p, [%0], %1;\n@p bra LD;\n"
               "add.u32 n, n, 1;\nsetp.lt.u32 p, n, 4000000;\n@p bra LW;\ntrap;\nLD:\n}" ::"r"(b), "r"(ph) : "memory");
}
__device__ __forceinline__ bool mbar_test(uint32_t b, int ph) {
  uint32_t ok;
  asm volatile("{\n.reg .pred p;\nmbarrier.test_wait.parity.shared::cta.b64 p, [%1], %2;\nselp.u32 %0, 1, 0, p;\n}" : "=r"(ok) : "r"(b), "r"(ph) : "memory");
  return ok;
}
__device__ __forceinline__ void wg_fence() { asm volatile("wgmma.fence.sync.aligned;" ::: "memory"); }
__device__ __forceinline__ void wg_commit() { asm volatile("wgmma.commit_group.sync.aligned;" ::: "memory"); }
template <int N> __device__ __forceinline__ void wg_wait() { asm volatile("wgmma.wait_group.sync.aligned %0;" ::"n"(N) : "memory"); }
template <int N> __device__ __forceinline__ void reg_fence(float (&a)[N]) {
#pragma unroll
  for (int i = 0; i < N; i++) asm volatile("" : "+f"(a[i])::"memory");
}
__device__ __forceinline__ uint32_t pack_bf16(float lo, float hi) {
  uint32_t r; asm("cvt.rn.bf16x2.f32 %0, %1, %2;" : "=r"(r) : "f"(hi), "f"(lo)); return r;
}
__device__ __forceinline__ float bf_lo(uint32_t v) { return __uint_as_float(v << 16); }
__device__ __forceinline__ float bf_hi(uint32_t v) { return __uint_as_float(v & 0xFFFF0000u); }
__device__ __forceinline__ float rbf(float x) { return __bfloat162float(__float2bfloat16_rn(x)); }
__device__ __forceinline__ uint32_t hmul2_bf(uint32_t a, uint32_t b) { uint32_t r; asm("mul.rn.bf16x2 %0, %1, %2;" : "=r"(r) : "r"(a), "r"(b)); return r; }
__device__ __forceinline__ uint32_t hadd2_bf(uint32_t a, uint32_t b) { uint32_t r; asm("add.rn.bf16x2 %0, %1, %2;" : "=r"(r) : "r"(a), "r"(b)); return r; }
__device__ __forceinline__ void bulk_ld(uint32_t dst, const void* src, int bytes, uint32_t bar) {
  asm volatile("cp.async.bulk.shared::cluster.global.mbarrier::complete_tx::bytes [%0], [%1], %2, [%3];"
               ::"r"(dst), "l"(src), "r"(bytes), "r"(bar) : "memory");
}

template <int BYTES>
__device__ __forceinline__ void bulk_ld_elect(uint32_t dst, const void* src, uint32_t bar) {
  asm volatile("{\n.reg .pred p;\nelect.sync _|p, 0xffffffff;\n"
               "@p mbarrier.arrive.expect_tx.shared::cta.b64 _, [%2], %3;\n"
               "@p cp.async.bulk.shared::cluster.global.mbarrier::complete_tx::bytes [%0], [%1], %3, [%2];\n}"
               ::"r"(dst), "l"(src), "r"(bar), "n"(BYTES) : "memory");
}
template <int BYTES>
__device__ __forceinline__ void bulk_ld_mc_elect(uint32_t dst, const void* src, uint32_t bar) {
  asm volatile("{\n.reg .pred p;\nelect.sync _|p, 0xffffffff;\n"
               "@p mbarrier.arrive.expect_tx.shared::cta.b64 _, [%2], %3;\n"
               "@p cp.async.bulk.shared::cluster.global.mbarrier::complete_tx::bytes.multicast::cluster [%0], [%1], %4, [%2], %5;\n}"
               ::"r"(dst), "l"(src), "r"(bar), "n"(2 * BYTES), "n"(BYTES), "h"((uint16_t)3) : "memory");
}
template <int AOFF, uint32_t AHI, int BOFF, uint32_t BHI, int ACC>
__device__ __forceinline__ void wgmma_ss224(float (&d)[112], uint32_t alo, uint32_t blo) {
  asm volatile("{\n.reg .pred p;\n.reg .b64 ad, bd;\nsetp.ne.b32 p, %118, 0;\n"
    "mov.b64 ad, {%112, %115};\nadd.s64 ad, ad, %114;\nmov.b64 bd, {%113, %117};\nadd.s64 bd, bd, %116;\n"
    "wgmma.mma_async.sync.aligned.m64n224k16.f32.bf16.bf16 {%0,%1,%2,%3,%4,%5,%6,%7,%8,%9,%10,%11,%12,%13,%14,%15,%16,%17,%18,%19,%20,%21,%22,%23,%24,%25,%26,%27,%28,%29,%30,%31,%32,%33,%34,%35,%36,%37,%38,%39,%40,%41,%42,%43,%44,%45,%46,%47,%48,%49,%50,%51,%52,%53,%54,%55,%56,%57,%58,%59,%60,%61,%62,%63,%64,%65,%66,%67,%68,%69,%70,%71,%72,%73,%74,%75,%76,%77,%78,%79,%80,%81,%82,%83,%84,%85,%86,%87,%88,%89,%90,%91,%92,%93,%94,%95,%96,%97,%98,%99,%100,%101,%102,%103,%104,%105,%106,%107,%108,%109,%110,%111}, ad, bd, p, 1, 1, 1, 1;\n}\n"
    : "+f"(d[0]),"+f"(d[1]),"+f"(d[2]),"+f"(d[3]),"+f"(d[4]),"+f"(d[5]),"+f"(d[6]),"+f"(d[7]),"+f"(d[8]),"+f"(d[9]),"+f"(d[10]),"+f"(d[11]),"+f"(d[12]),"+f"(d[13]),"+f"(d[14]),"+f"(d[15]),"+f"(d[16]),"+f"(d[17]),"+f"(d[18]),"+f"(d[19]),"+f"(d[20]),"+f"(d[21]),"+f"(d[22]),"+f"(d[23]),"+f"(d[24]),"+f"(d[25]),"+f"(d[26]),"+f"(d[27]),"+f"(d[28]),"+f"(d[29]),"+f"(d[30]),"+f"(d[31]),"+f"(d[32]),"+f"(d[33]),"+f"(d[34]),"+f"(d[35]),"+f"(d[36]),"+f"(d[37]),"+f"(d[38]),"+f"(d[39]),"+f"(d[40]),"+f"(d[41]),"+f"(d[42]),"+f"(d[43]),"+f"(d[44]),"+f"(d[45]),"+f"(d[46]),"+f"(d[47]),"+f"(d[48]),"+f"(d[49]),"+f"(d[50]),"+f"(d[51]),"+f"(d[52]),"+f"(d[53]),"+f"(d[54]),"+f"(d[55]),"+f"(d[56]),"+f"(d[57]),"+f"(d[58]),"+f"(d[59]),"+f"(d[60]),"+f"(d[61]),"+f"(d[62]),"+f"(d[63]),"+f"(d[64]),"+f"(d[65]),"+f"(d[66]),"+f"(d[67]),"+f"(d[68]),"+f"(d[69]),"+f"(d[70]),"+f"(d[71]),"+f"(d[72]),"+f"(d[73]),"+f"(d[74]),"+f"(d[75]),"+f"(d[76]),"+f"(d[77]),"+f"(d[78]),"+f"(d[79]),"+f"(d[80]),"+f"(d[81]),"+f"(d[82]),"+f"(d[83]),"+f"(d[84]),"+f"(d[85]),"+f"(d[86]),"+f"(d[87]),"+f"(d[88]),"+f"(d[89]),"+f"(d[90]),"+f"(d[91]),"+f"(d[92]),"+f"(d[93]),"+f"(d[94]),"+f"(d[95]),"+f"(d[96]),"+f"(d[97]),"+f"(d[98]),"+f"(d[99]),"+f"(d[100]),"+f"(d[101]),"+f"(d[102]),"+f"(d[103]),"+f"(d[104]),"+f"(d[105]),"+f"(d[106]),"+f"(d[107]),"+f"(d[108]),"+f"(d[109]),"+f"(d[110]),"+f"(d[111])
    : "r"(alo), "r"(blo), "n"(AOFF), "n"(AHI), "n"(BOFF), "n"(BHI), "n"(ACC));
}
template <int AOFF, uint32_t AHI, int BOFF, uint32_t BHI, int ACC>
__device__ __forceinline__ void wgmma_ss232(float (&d)[116], uint32_t alo, uint32_t blo) {
  asm volatile("{\n.reg .pred p;\n.reg .b64 ad, bd;\nsetp.ne.b32 p, %122, 0;\n"
    "mov.b64 ad, {%116, %119};\nadd.s64 ad, ad, %118;\nmov.b64 bd, {%117, %121};\nadd.s64 bd, bd, %120;\n"
    "wgmma.mma_async.sync.aligned.m64n232k16.f32.bf16.bf16 {%0,%1,%2,%3,%4,%5,%6,%7,%8,%9,%10,%11,%12,%13,%14,%15,%16,%17,%18,%19,%20,%21,%22,%23,%24,%25,%26,%27,%28,%29,%30,%31,%32,%33,%34,%35,%36,%37,%38,%39,%40,%41,%42,%43,%44,%45,%46,%47,%48,%49,%50,%51,%52,%53,%54,%55,%56,%57,%58,%59,%60,%61,%62,%63,%64,%65,%66,%67,%68,%69,%70,%71,%72,%73,%74,%75,%76,%77,%78,%79,%80,%81,%82,%83,%84,%85,%86,%87,%88,%89,%90,%91,%92,%93,%94,%95,%96,%97,%98,%99,%100,%101,%102,%103,%104,%105,%106,%107,%108,%109,%110,%111,%112,%113,%114,%115}, ad, bd, p, 1, 1, 1, 1;\n}\n"
    : "+f"(d[0]),"+f"(d[1]),"+f"(d[2]),"+f"(d[3]),"+f"(d[4]),"+f"(d[5]),"+f"(d[6]),"+f"(d[7]),"+f"(d[8]),"+f"(d[9]),"+f"(d[10]),"+f"(d[11]),"+f"(d[12]),"+f"(d[13]),"+f"(d[14]),"+f"(d[15]),"+f"(d[16]),"+f"(d[17]),"+f"(d[18]),"+f"(d[19]),"+f"(d[20]),"+f"(d[21]),"+f"(d[22]),"+f"(d[23]),"+f"(d[24]),"+f"(d[25]),"+f"(d[26]),"+f"(d[27]),"+f"(d[28]),"+f"(d[29]),"+f"(d[30]),"+f"(d[31]),"+f"(d[32]),"+f"(d[33]),"+f"(d[34]),"+f"(d[35]),"+f"(d[36]),"+f"(d[37]),"+f"(d[38]),"+f"(d[39]),"+f"(d[40]),"+f"(d[41]),"+f"(d[42]),"+f"(d[43]),"+f"(d[44]),"+f"(d[45]),"+f"(d[46]),"+f"(d[47]),"+f"(d[48]),"+f"(d[49]),"+f"(d[50]),"+f"(d[51]),"+f"(d[52]),"+f"(d[53]),"+f"(d[54]),"+f"(d[55]),"+f"(d[56]),"+f"(d[57]),"+f"(d[58]),"+f"(d[59]),"+f"(d[60]),"+f"(d[61]),"+f"(d[62]),"+f"(d[63]),"+f"(d[64]),"+f"(d[65]),"+f"(d[66]),"+f"(d[67]),"+f"(d[68]),"+f"(d[69]),"+f"(d[70]),"+f"(d[71]),"+f"(d[72]),"+f"(d[73]),"+f"(d[74]),"+f"(d[75]),"+f"(d[76]),"+f"(d[77]),"+f"(d[78]),"+f"(d[79]),"+f"(d[80]),"+f"(d[81]),"+f"(d[82]),"+f"(d[83]),"+f"(d[84]),"+f"(d[85]),"+f"(d[86]),"+f"(d[87]),"+f"(d[88]),"+f"(d[89]),"+f"(d[90]),"+f"(d[91]),"+f"(d[92]),"+f"(d[93]),"+f"(d[94]),"+f"(d[95]),"+f"(d[96]),"+f"(d[97]),"+f"(d[98]),"+f"(d[99]),"+f"(d[100]),"+f"(d[101]),"+f"(d[102]),"+f"(d[103]),"+f"(d[104]),"+f"(d[105]),"+f"(d[106]),"+f"(d[107]),"+f"(d[108]),"+f"(d[109]),"+f"(d[110]),"+f"(d[111]),"+f"(d[112]),"+f"(d[113]),"+f"(d[114]),"+f"(d[115])
    : "r"(alo), "r"(blo), "n"(AOFF), "n"(AHI), "n"(BOFF), "n"(BHI), "n"(ACC));
}
template <int OFF, uint32_t BHI, int ACC>
__device__ __forceinline__ void wgmma_rs224(float (&d)[112], uint32_t a0, uint32_t a1, uint32_t a2, uint32_t a3, uint32_t blo) {
  asm volatile("{\n.reg .pred p;\n.reg .b64 bd;\nsetp.ne.b32 p, %119, 0;\nmov.b64 bd, {%116, %118};\nadd.s64 bd, bd, %117;\n"
    "wgmma.mma_async.sync.aligned.m64n224k16.f32.bf16.bf16 {%0,%1,%2,%3,%4,%5,%6,%7,%8,%9,%10,%11,%12,%13,%14,%15,%16,%17,%18,%19,%20,%21,%22,%23,%24,%25,%26,%27,%28,%29,%30,%31,%32,%33,%34,%35,%36,%37,%38,%39,%40,%41,%42,%43,%44,%45,%46,%47,%48,%49,%50,%51,%52,%53,%54,%55,%56,%57,%58,%59,%60,%61,%62,%63,%64,%65,%66,%67,%68,%69,%70,%71,%72,%73,%74,%75,%76,%77,%78,%79,%80,%81,%82,%83,%84,%85,%86,%87,%88,%89,%90,%91,%92,%93,%94,%95,%96,%97,%98,%99,%100,%101,%102,%103,%104,%105,%106,%107,%108,%109,%110,%111}, {%112,%113,%114,%115}, bd, p, 1, 1, 1;\n}\n"
    : "+f"(d[0]),"+f"(d[1]),"+f"(d[2]),"+f"(d[3]),"+f"(d[4]),"+f"(d[5]),"+f"(d[6]),"+f"(d[7]),"+f"(d[8]),"+f"(d[9]),"+f"(d[10]),"+f"(d[11]),"+f"(d[12]),"+f"(d[13]),"+f"(d[14]),"+f"(d[15]),"+f"(d[16]),"+f"(d[17]),"+f"(d[18]),"+f"(d[19]),"+f"(d[20]),"+f"(d[21]),"+f"(d[22]),"+f"(d[23]),"+f"(d[24]),"+f"(d[25]),"+f"(d[26]),"+f"(d[27]),"+f"(d[28]),"+f"(d[29]),"+f"(d[30]),"+f"(d[31]),"+f"(d[32]),"+f"(d[33]),"+f"(d[34]),"+f"(d[35]),"+f"(d[36]),"+f"(d[37]),"+f"(d[38]),"+f"(d[39]),"+f"(d[40]),"+f"(d[41]),"+f"(d[42]),"+f"(d[43]),"+f"(d[44]),"+f"(d[45]),"+f"(d[46]),"+f"(d[47]),"+f"(d[48]),"+f"(d[49]),"+f"(d[50]),"+f"(d[51]),"+f"(d[52]),"+f"(d[53]),"+f"(d[54]),"+f"(d[55]),"+f"(d[56]),"+f"(d[57]),"+f"(d[58]),"+f"(d[59]),"+f"(d[60]),"+f"(d[61]),"+f"(d[62]),"+f"(d[63]),"+f"(d[64]),"+f"(d[65]),"+f"(d[66]),"+f"(d[67]),"+f"(d[68]),"+f"(d[69]),"+f"(d[70]),"+f"(d[71]),"+f"(d[72]),"+f"(d[73]),"+f"(d[74]),"+f"(d[75]),"+f"(d[76]),"+f"(d[77]),"+f"(d[78]),"+f"(d[79]),"+f"(d[80]),"+f"(d[81]),"+f"(d[82]),"+f"(d[83]),"+f"(d[84]),"+f"(d[85]),"+f"(d[86]),"+f"(d[87]),"+f"(d[88]),"+f"(d[89]),"+f"(d[90]),"+f"(d[91]),"+f"(d[92]),"+f"(d[93]),"+f"(d[94]),"+f"(d[95]),"+f"(d[96]),"+f"(d[97]),"+f"(d[98]),"+f"(d[99]),"+f"(d[100]),"+f"(d[101]),"+f"(d[102]),"+f"(d[103]),"+f"(d[104]),"+f"(d[105]),"+f"(d[106]),"+f"(d[107]),"+f"(d[108]),"+f"(d[109]),"+f"(d[110]),"+f"(d[111])
    : "r"(a0), "r"(a1), "r"(a2), "r"(a3), "r"(blo), "n"(OFF), "n"(BHI), "n"(ACC));
}
template <int OFF, uint32_t BHI, int ACC>
__device__ __forceinline__ void wgmma_rs56(float (&d)[28], uint32_t a0, uint32_t a1, uint32_t a2, uint32_t a3, uint32_t blo) {
  asm volatile("{\n.reg .pred p;\n.reg .b64 bd;\nsetp.ne.b32 p, %35, 0;\nmov.b64 bd, {%32, %34};\nadd.s64 bd, bd, %33;\n"
    "wgmma.mma_async.sync.aligned.m64n56k16.f32.bf16.bf16 {%0,%1,%2,%3,%4,%5,%6,%7,%8,%9,%10,%11,%12,%13,%14,%15,%16,%17,%18,%19,%20,%21,%22,%23,%24,%25,%26,%27}, {%28,%29,%30,%31}, bd, p, 1, 1, 1;\n}\n"
    : "+f"(d[0]),"+f"(d[1]),"+f"(d[2]),"+f"(d[3]),"+f"(d[4]),"+f"(d[5]),"+f"(d[6]),"+f"(d[7]),"+f"(d[8]),"+f"(d[9]),"+f"(d[10]),"+f"(d[11]),"+f"(d[12]),"+f"(d[13]),"+f"(d[14]),"+f"(d[15]),"+f"(d[16]),"+f"(d[17]),"+f"(d[18]),"+f"(d[19]),"+f"(d[20]),"+f"(d[21]),"+f"(d[22]),"+f"(d[23]),"+f"(d[24]),"+f"(d[25]),"+f"(d[26]),"+f"(d[27])
    : "r"(a0), "r"(a1), "r"(a2), "r"(a3), "r"(blo), "n"(OFF), "n"(BHI), "n"(ACC));
}

__device__ __forceinline__ void st128(uint4* p, uint32_t a, uint32_t b, uint32_t c, uint32_t d) {
  asm volatile("{\n.reg .b128 v;\n.reg .b64 lo, hi;\nmov.b64 lo, {%1, %2};\nmov.b64 hi, {%3, %4};\nmov.b128 v, {lo, hi};\n"
               "st.relaxed.gpu.global.b128 [%0], v;\n}" ::"l"(p), "r"(a), "r"(b), "r"(c), "r"(d) : "memory");
}
__device__ __forceinline__ void ld128(const uint4* p, uint32_t* r) {
  asm volatile("{\n.reg .b128 v;\n.reg .b64 lo, hi;\nld.relaxed.gpu.global.b128 v, [%4];\nmov.b128 {lo, hi}, v;\n"
               "mov.b64 {%0, %1}, lo;\nmov.b64 {%2, %3}, hi;\n}" : "=r"(r[0]), "=r"(r[1]), "=r"(r[2]), "=r"(r[3]) : "l"(p) : "memory");
}

template <int OFF, uint32_t BHI, int ACC>
__device__ __forceinline__ void wgmma_rs32(float (&d)[16], uint32_t a0, uint32_t a1, uint32_t a2, uint32_t a3, uint32_t blo) {
  asm volatile("{\n.reg .pred p;\n.reg .b64 bd;\nsetp.ne.b32 p, %23, 0;\nmov.b64 bd, {%20, %22};\nadd.s64 bd, bd, %21;\n"
    "wgmma.mma_async.sync.aligned.m64n32k16.f32.bf16.bf16 {%0,%1,%2,%3,%4,%5,%6,%7,%8,%9,%10,%11,%12,%13,%14,%15}, {%16,%17,%18,%19}, bd, p, 1, 1, 0;\n}\n"
    : "+f"(d[0]),"+f"(d[1]),"+f"(d[2]),"+f"(d[3]),"+f"(d[4]),"+f"(d[5]),"+f"(d[6]),"+f"(d[7]),"+f"(d[8]),"+f"(d[9]),"+f"(d[10]),"+f"(d[11]),"+f"(d[12]),"+f"(d[13]),"+f"(d[14]),"+f"(d[15])
    : "r"(a0), "r"(a1), "r"(a2), "r"(a3), "r"(blo), "n"(OFF), "n"(BHI), "n"(ACC));
}
template <int OFF, uint32_t BHI, int ACC>
__device__ __forceinline__ void wgmma_rs24(float (&d)[12], uint32_t a0, uint32_t a1, uint32_t a2, uint32_t a3, uint32_t blo) {
  asm volatile("{\n.reg .pred p;\n.reg .b64 bd;\nsetp.ne.b32 p, %19, 0;\nmov.b64 bd, {%16, %18};\nadd.s64 bd, bd, %17;\n"
    "wgmma.mma_async.sync.aligned.m64n24k16.f32.bf16.bf16 {%0,%1,%2,%3,%4,%5,%6,%7,%8,%9,%10,%11}, {%12,%13,%14,%15}, bd, p, 1, 1, 1;\n}\n"
    : "+f"(d[0]),"+f"(d[1]),"+f"(d[2]),"+f"(d[3]),"+f"(d[4]),"+f"(d[5]),"+f"(d[6]),"+f"(d[7]),"+f"(d[8]),"+f"(d[9]),"+f"(d[10]),"+f"(d[11])
    : "r"(a0), "r"(a1), "r"(a2), "r"(a3), "r"(blo), "n"(OFF), "n"(BHI), "n"(ACC));
}
template <int OFF, uint32_t BHI, int ACC>
__device__ __forceinline__ void wgmma_rs16(float (&d)[8], uint32_t a0, uint32_t a1, uint32_t a2, uint32_t a3, uint32_t blo) {
  asm volatile("{\n.reg .pred p;\n.reg .b64 bd;\nsetp.ne.b32 p, %15, 0;\nmov.b64 bd, {%12, %14};\nadd.s64 bd, bd, %13;\n"
    "wgmma.mma_async.sync.aligned.m64n16k16.f32.bf16.bf16 {%0,%1,%2,%3,%4,%5,%6,%7}, {%8,%9,%10,%11}, bd, p, 1, 1, 1;\n}\n"
    : "+f"(d[0]),"+f"(d[1]),"+f"(d[2]),"+f"(d[3]),"+f"(d[4]),"+f"(d[5]),"+f"(d[6]),"+f"(d[7])
    : "r"(a0), "r"(a1), "r"(a2), "r"(a3), "r"(blo), "n"(OFF), "n"(BHI), "n"(ACC));
}

constexpr int A_R1 = 0;
constexpr int A_R2A = A_R1 + 2624, A_R2B = A_R2A + 768, A_R3A = A_R2B + 768, A_R3B = A_R3A + 528;
constexpr int A_K1024 = A_R3B + 528;
constexpr int A_W5 = A_K1024 + 16;
constexpr int A_W3 = A_W5 + 4096;
constexpr int A_W9 = A_W3 + 4112;
constexpr int A_W7 = A_W9 + 2080;
constexpr int A_V  = A_W7 + 2080 + 32;
constexpr int A_SCL = A_V + 2048;
constexpr int A_UB = A_SCL + 16;
constexpr int A_STG = A_UB + 5248;
constexpr int A_Y2 = A_STG, A_Y3 = A_Y2 + 6528, A_YB = A_Y3 + 4352;
constexpr int A_REC = A_STG + 4 * 4352;
constexpr int A_CH = A_REC + 8192;
constexpr int A_BAR = 4 * A_CH, A_WST = (A_BAR + 128 + 127) / 128 * 128;
static_assert(A_W5 % 16 == 0 && A_UB % 16 == 0 && A_CH % 16 == 0 && A_YB + 4096 <= A_REC, "layout");

struct cf { float x, y; };
__device__ __forceinline__ cf cmul(cf a, cf b) { cf r; r.x = fmaf(a.x, b.x, -a.y * b.y); r.y = fmaf(a.x, b.y, a.y * b.x); return r; }
__device__ __forceinline__ cf cexp_l(float lr, float li, float l) {
  float mag; asm("ex2.approx.ftz.f32 %0, %1;" : "=f"(mag) : "f"((lr * l) * 1.4426950408889634f));
  const float th = li * l;
  const float k = (fmaf(th, 0.15915494f, 12582912.f)) - 12582912.f;
  float ph = fmaf(th, 0.15915494f, -k);
  ph = fmaf(th, 6.4206383e-9f, ph) * 6.2831853f;
  cf r; r.x = mag * __cosf(ph); r.y = mag * __sinf(ph); return r;
}
__device__ __forceinline__ void sts16(uint32_t a, uint32_t v) { asm volatile("st.shared.u16 [%0], %1;" ::"r"(a), "h"((uint16_t)v) : "memory"); }
__device__ __forceinline__ void sts32(uint32_t a, uint32_t v) { asm volatile("st.shared.u32 [%0], %1;" ::"r"(a), "r"(v) : "memory"); }
__device__ __forceinline__ void sts64(uint32_t a, uint32_t v0, uint32_t v1) { asm volatile("st.shared.v2.u32 [%0], {%1, %2};" ::"r"(a), "r"(v0), "r"(v1) : "memory"); }
__device__ __forceinline__ void sts128(uint32_t a, uint32_t v0, uint32_t v1, uint32_t v2, uint32_t v3) {
  asm volatile("st.shared.v4.u32 [%0], {%1, %2, %3, %4};" ::"r"(a), "r"(v0), "r"(v1), "r"(v2), "r"(v3) : "memory");
}
__device__ __forceinline__ uint32_t lds32(uint32_t a) { uint32_t v; asm volatile("ld.shared.u32 %0, [%1];" : "=r"(v) : "r"(a) : "memory"); return v; }
__device__ __forceinline__ uint4 lds128(uint32_t a) {
  uint4 v; asm volatile("ld.shared.v4.u32 {%0, %1, %2, %3}, [%4];" : "=r"(v.x), "=r"(v.y), "=r"(v.z), "=r"(v.w) : "r"(a) : "memory"); return v;
}
__device__ __forceinline__ void ldsm4(uint32_t* r, uint32_t a) {
  asm volatile("ldmatrix.sync.aligned.m8n8.x4.shared.b16 {%0,%1,%2,%3}, [%4];" : "=r"(r[0]), "=r"(r[1]), "=r"(r[2]), "=r"(r[3]) : "r"(a) : "memory");
}
__device__ __forceinline__ void mma16816(float* d, uint32_t a0, uint32_t a1, uint32_t a2, uint32_t a3, uint32_t b0, uint32_t b1) {
  asm volatile("mma.sync.aligned.m16n8k16.row.col.f32.f16.f16.f32 {%0,%1,%2,%3}, {%4,%5,%6,%7}, {%8,%9}, {%0,%1,%2,%3};"
               : "+f"(d[0]), "+f"(d[1]), "+f"(d[2]), "+f"(d[3]) : "r"(a0), "r"(a1), "r"(a2), "r"(a3), "r"(b0), "r"(b1));
}
__device__ __forceinline__ uint32_t pack_h(float lo, float hi) { uint32_t r; asm("cvt.rn.f16x2.f32 %0, %1, %2;" : "=r"(r) : "f"(hi), "f"(lo)); return r; }
__device__ __forceinline__ uint32_t pack_h(cf v) { return pack_h(v.x, v.y); }
__device__ __forceinline__ uint32_t hcmul(uint32_t x, uint32_t r0, uint32_t r1) {
  const __half2 hx = *(__half2*)&x;
  const __half2 y = __hfma2(__high2half2(hx), *(__half2*)&r1, __hmul2(__low2half2(hx), *(__half2*)&r0));
  return *(const uint32_t*)&y;
}
__device__ __forceinline__ float ln_rstd(float var) {
  float sd, rs;
  asm("sqrt.approx.f32 %0, %1;" : "=f"(sd) : "f"(rbf(rbf(var) + 1e-5f)));
  asm("rcp.approx.f32 %0, %1;" : "=f"(rs) : "f"(rbf(sd)));
  return rs;
}
__device__ __forceinline__ uint32_t hsub2_bf(uint32_t a, uint32_t b) { uint32_t r; asm("sub.rn.bf16x2 %0, %1, %2;" : "=r"(r) : "r"(a), "r"(b)); return r; }
__device__ __forceinline__ void bar_sync(int id, int n) { asm volatile("bar.sync %0, %1;" ::"r"(id), "r"(n) : "memory"); }

template <int S> struct F1B { static constexpr int c = S / 4 + ((S & 3) == 3 ? 0 : 0), cc = (16 * S) / 64, ks = (64 * cc - (16 * S - 48)) / 16, off = (A_UB + 2 * ks * 656 + (9 - cc) * 16) / 16; };

template <int NS>
__device__ __forceinline__ void load_quads(uint32_t* q, uint32_t addr) {
#pragma unroll
  for (int i = 0; i < NS; i++) {
    q[4 * i] = lds32(addr + i * 64); q[4 * i + 1] = lds32(addr + i * 64 + 32);
    q[4 * i + 2] = i ? q[4 * i - 3] : lds32(addr - 32);
    q[4 * i + 3] = q[4 * i];
  }
#pragma unroll
  for (int i = 0; i < 4 * NS; i++) asm volatile("" : "+r"(q[i]));
}
template <int S0, int NS>
__device__ __forceinline__ void f1_steps(float (&acc)[16], const uint32_t* a, uint32_t blo) {
  if constexpr (NS > 0) {
    wgmma_rs32<F1B<S0>::off, 8, S0 != 0>(acc, a[0], a[1], a[2], a[3], blo);
    f1_steps<S0 + 1, NS - 1>(acc, a + 4, blo);
  }
}
template <int S0, int NS, int BASE, int FIRST>
__device__ __forceinline__ void s2_steps(float (&acc)[12], const uint32_t* a, uint32_t blo) {
  if constexpr (NS > 0) {
    wgmma_rs24<BASE / 16 + (112 - 16 * S0), 64, !(FIRST && S0 == 0)>(acc, a[0], a[1], a[2], a[3], blo);
    s2_steps<S0 + 1, NS - 1, BASE, FIRST>(acc, a + 4, blo);
  }
}
template <int S0, int NS, int BASE, int FIRST>
__device__ __forceinline__ void s3_steps(float (&acc)[8], const uint32_t* a, uint32_t blo) {
  if constexpr (NS > 0) {
    wgmma_rs16<BASE / 16 + (48 - 16 * S0), 65, !(FIRST && S0 == 0)>(acc, a[0], a[1], a[2], a[3], blo);
    s3_steps<S0 + 1, NS - 1, BASE, FIRST>(acc, a + 4, blo);
  }
}

__device__ __forceinline__ void tma3d(uint32_t dst, const CUtensorMap* m, int c1, int c2, uint32_t bar) {
  asm volatile("cp.async.bulk.tensor.3d.shared::cluster.global.mbarrier::complete_tx::bytes [%0], [%1, {0, %3, %4}], [%2];"
               ::"r"(dst), "l"(m), "r"(bar), "r"(c1), "r"(c2) : "memory");
}
__device__ __forceinline__ void bulk_st(void* dst, uint32_t src, int bytes) {
  asm volatile("cp.async.bulk.global.shared::cta.bulk_group [%0], [%1], %2;" ::"l"(dst), "r"(src), "r"(bytes) : "memory");
}

__device__ __forceinline__ void phase_a(
        unsigned char* sm, const uint32_t bar_rec, const uint32_t ep_addr, const CUtensorMap* mg, const CUtensorMap* mu, const CUtensorMap* md,
        const __nv_bfloat16* __restrict__ x, const uint32_t* __restrict__ are, const uint32_t* __restrict__ aim,
        const uint32_t* __restrict__ bre, const uint32_t* __restrict__ bim, const uint32_t* __restrict__ cre,
        const uint32_t* __restrict__ cim, const unsigned short* __restrict__ logdt, const unsigned short* __restrict__ dskip,
        const uint4* __restrict__ wgate, const uint4* __restrict__ wup) {
  const uint32_t sb = s2u(sm), bar_w = bar_rec + 16;
  const int tid = threadIdx.x, warp = __shfl_sync(~0u, tid >> 5, 0), wg = warp >> 2, lane = tid & 31, wq = warp & 3, t128 = tid & 127;
  const int blk = blockIdx.x;
  const bool conv = (blk & 7) != 7;
  const int cblk = blk - (blk >> 3);

  uint2 xr[4];
  {
    const uint2* p = (const uint2*)(x + (size_t)(blk * 16 + warp) * DM);
    xr[0] = __ldg(p + lane); xr[1] = __ldg(p + 32 + lane); xr[2] = __ldg(p + 64 + lane);
    xr[3] = lane < 16 ? __ldg(p + 96 + lane) : make_uint2(0, 0);
  }
  const int ch = conv ? cblk * 4 + wg : 0;
  const uint32_t cb = sb + wg * A_CH;
  uint32_t prm[6];
  {
    const int i = ch * 128 + t128;
    prm[0] = __ldg(are + i); prm[1] = __ldg(aim + i); prm[2] = __ldg(bre + i); prm[3] = __ldg(bim + i); prm[4] = __ldg(cre + i); prm[5] = __ldg(cim + i);
  }
  const uint32_t ldt = __ldg(logdt + ch);
  uint32_t cnt0 = 0;
  if (tid == 0) cnt0 = __ldcg(&g_cnt1);
  const int g = lane >> 2, t = lane & 3;
  if (conv) {
#pragma unroll
    for (int i = 0; i < 4; i++) if (i < 3 || t128 < (A_W5 + 1024) / 16 - 384) sts128(cb + (i * 128 + t128) * 16, 0, 0, 0, 0);
    if (t128 < 64) sts128(cb + A_W3 + t128 * 16, 0, 0, 0, 0);
    if (t128 < 72) sts128(cb + A_UB + (t128 / 9) * 656 + (t128 % 9) * 16, 0, 0, 0, 0);
  } else if (tid == 160) {
    for (int c = 0; c < 8; c++) { mbar_expect(bar_w + 8 * c, 12544); tma3d(sb + (c >> 1) * 50560 + (c & 1) * 12544, md, (blk >> 3) * 112, c * 7, bar_w + 8 * c); }
  }
  {
    float s = 0.f, q = 0.f;
#pragma unroll
    for (int i = 0; i < 4; i++) {
      const float a = bf_lo(xr[i].x), b = bf_hi(xr[i].x), c = bf_lo(xr[i].y), d = bf_hi(xr[i].y);
      s += (a + b) + (c + d);
      q = fmaf(a, a, q); q = fmaf(b, b, q); q = fmaf(c, c, q); q = fmaf(d, d, q);
    }
#pragma unroll
    for (int o = 16; o; o >>= 1) { s += __shfl_xor_sync(~0u, s, o); q += __shfl_xor_sync(~0u, q, o); }
    const float mean = s * (1.f / DM);
    const float var = fmaxf(fmaf(-mean, mean, q * (1.f / DM)), 0.f);
    const float rs = ln_rstd(var);
    const uint32_t mm = pack_bf16(mean, mean);
    const uint32_t tu = sb + A_REC + (warp >> 3) * A_CH + (warp & 7) * 912 + lane * 8, tx = tu + 2 * A_CH;
#pragma unroll
    for (int i = 0; i < 4; i++) {
      if (i < 3 || lane < 16) {
        const uint32_t d0 = hsub2_bf(xr[i].x, mm), d1 = hsub2_bf(xr[i].y, mm);
        sts64(tu + i * 256, pack_bf16(bf_lo(d0) * rs, bf_hi(d0) * rs), pack_bf16(bf_lo(d1) * rs, bf_hi(d1) * rs));
        sts64(tx + i * 256, xr[i].x, xr[i].y);
      }
    }
  }
  if (tid == 0) sts32(ep_addr, (cnt0 >> 7) + 1u);
  if (tid == 320) TR(0, 1);
  auto publish_rows = [&]() {
    bar_sync(5, 512);
    uint4* dst = g_ux + ((size_t)(warp * 8 + (lane >> 2)) * 128 + blk) * 4 + ((lane ^ (blk >> 1)) & 3);
#pragma unroll
    for (int i = 0; i < 4; i++) {
      if (i < 3 || warp < 8) {
        uint32_t r[4];
        asm volatile("ldmatrix.sync.aligned.m8n8.x4.trans.shared.b16 {%0,%1,%2,%3}, [%4];" : "=r"(r[0]), "=r"(r[1]), "=r"(r[2]), "=r"(r[3])
                     : "r"(sb + A_REC + (lane >> 3) * A_CH + (lane & 7) * 912 + (warp + 16 * i) * 16) : "memory");
        dst[i * 65536] = make_uint4(r[0], r[1], r[2], r[3]);
      }
    }
    if (warp != 0) asm volatile("bar.arrive 6, 512;" ::: "memory");
  };
  auto release_rows = [&]() {
    if (warp == 0) {
      bar_sync(6, 512);
      if (lane == 0) { asm volatile("red.release.gpu.global.add.u32 [%0], 1;" ::"l"(&g_cnt1) : "memory"); TR(0, 8); }
      __syncwarp();
    }
  };

  publish_rows();
  release_rows();
  if (!conv) {
    const int a = blk >> 3, mat = a >> 3, j = a & 7;
    if (warp == 15) {
      if (lane == 0) {
        for (int c = 0; c < 8; c++) {
          mbar_wait(bar_w + 8 * c, 0);
          bulk_st(g_wimg + (size_t)(a >> 1) * 37632 + 25088 + (c * 2 + (a & 1)) * 784, sb + (c >> 1) * 50560 + (c & 1) * 12544, 12544);
        }
        asm volatile("cp.async.bulk.commit_group;" ::: "memory");
        asm volatile("cp.async.bulk.wait_group 0;" ::: "memory");
        TR(0, 10);
      }
      return;
    }
    bar_sync(7, 480);
    float s[8];
#pragma unroll
    for (int k = 0; k < 8; k++) s[k] = 0.f;
    if (lane < 28 && warp < 14) {
      const uint4* src = (mat ? wup : wgate) + j * 28 + lane + (size_t)warp * 224;
#pragma unroll
      for (int hb = 0; hb < 2; hb++) {
        uint4 v[16];
#pragma unroll
        for (int r = 0; r < 16; r++) v[r] = __ldg(src + (size_t)(hb * 16 + r) * 14 * 224);
#pragma unroll
        for (int r = 0; r < 16; r++) {
          s[0] += bf_lo(v[r].x); s[1] += bf_hi(v[r].x); s[2] += bf_lo(v[r].y); s[3] += bf_hi(v[r].y);
          s[4] += bf_lo(v[r].z); s[5] += bf_hi(v[r].z); s[6] += bf_lo(v[r].w); s[7] += bf_hi(v[r].w);
        }
      }
      float4* red = (float4*)(sm + 25088 + warp * 896 + lane * 32);
      red[0] = make_float4(s[0], s[1], s[2], s[3]); red[1] = make_float4(s[4], s[5], s[6], s[7]);
    }
    bar_sync(5, 480);
    if (tid < 224) {
      float cs = 0.f;
#pragma unroll
      for (int w = 0; w < 14; w++) cs += *(const float*)(sm + 25088 + w * 896 + tid * 4);
      const float hi = rbf(cs), mid = rbf(cs - hi), lo = rbf(cs - hi - mid);
      const int q = tid / 112, n = tid % 112 + 112 * mat;
      __nv_bfloat16* dst = (__nv_bfloat16*)(g_cimg + (j * 2 + q) * 224 + (n >> 3) * 8) + (n & 7);
      dst[0] = __float2bfloat16_rn(hi); dst[8] = __float2bfloat16_rn(mid); dst[16] = __float2bfloat16_rn(lo);
#pragma unroll
      for (int k = 3; k < 8; k++) dst[8 * k] = __float2bfloat16_rn(0.f);
    }
    if (tid == 0) TR(0, 11);
    return;
  }

  const int wr = (wq + wg) & 3;
  const int bk = wr * 32 + lane;
  {
    const uint32_t stg = cb + A_STG + wq * 4352, sw = stg + lane * 8;
    const float dt = rbf(expf(__uint_as_float(ldt << 16)));
    float lr[2], li[2];
    cf bq[2], b0[2], b4[2];
    uint32_t bf[48], cv = 0;
#pragma unroll
    for (int m = 0; m < 2; m++) {
      lr[m] = dt * (m ? bf_hi(prm[0]) : bf_lo(prm[0]));
      li[m] = dt * (m ? bf_hi(prm[1]) : bf_lo(prm[1]));
    }
    {
      cf b[2], z[2];
#pragma unroll
      for (int m = 0; m < 2; m++) {
        cf db, c;
        db.x = dt * (m ? bf_hi(prm[2]) : bf_lo(prm[2])); db.y = -dt * (m ? bf_hi(prm[3]) : bf_lo(prm[3]));
        c.x = m ? bf_hi(prm[4]) : bf_lo(prm[4]); c.y = -(m ? bf_hi(prm[5]) : bf_lo(prm[5]));
        b[m] = cmul(c, db);
        z[m] = cexp_l(lr[m], -li[m], 1.f);
        bq[m] = cexp_l(lr[m], -li[m], 256.f);
      }
      {
        const float mx = fmaxf(fmaxf(fabsf(b[0].x), fabsf(b[0].y)), fmaxf(fabsf(b[1].x), fabsf(b[1].y)));
        const uint32_t e = max(__reduce_max_sync(~0u, __float_as_uint(mx)) >> 23, 14u);
        const float sc = __uint_as_float((267u - e) << 23);
        b[0].x *= sc; b[0].y *= sc; b[1].x *= sc; b[1].y *= sc;
        if (lane == 0) sts32(cb + A_SCL + wq * 4, (e - 13u) << 23);
      }
#pragma unroll
      for (int i = 0; i < 8; i++) {
        sts64(sw + i * 272, pack_h(b[0]), pack_h(b[1]));
        if (!(i & 1)) {
          cf e0 = cmul(b[0], bq[0]), e1 = cmul(b[1], bq[1]);
          sts64(sw + (8 + i / 2) * 272, pack_h(e0), pack_h(e1));
          if (i == 0) { b0[0] = e0; b0[1] = e1; }
          if (i == 4) { b4[0] = e0; b4[1] = e1; }
        }
        if (i < 7) { b[0] = cmul(b[0], z[0]); b[1] = cmul(b[1], z[1]); }
      }
#pragma unroll
      for (int i = 0; i < 7; i++) {
        b0[0] = cmul(b0[0], bq[0]); b0[1] = cmul(b0[1], bq[1]);
        sts64(sw + (i < 2 ? 12 + 2 * i : i - 2) * 272, pack_h(b0[0]), pack_h(b0[1]));
        if (i < 2) {
          b4[0] = cmul(b4[0], bq[0]); b4[1] = cmul(b4[1], bq[1]);
          sts64(sw + (13 + 2 * i) * 272, pack_h(b4[0]), pack_h(b4[1]));
        }
        if (i == 1) {
          __syncwarp();
#pragma unroll
          for (int n = 0; n < 2; n++)
#pragma unroll
            for (int k2 = 0; k2 < 4; k2++) ldsm4(bf + n * 16 + k2 * 4, stg + (n * 8 + (lane & 7)) * 272 + k2 * 64 + (lane >> 3) * 16);
          __syncwarp();
          if (tid == 160) asm volatile("ld.relaxed.gpu.global.u32 %0, [%1];" : "=r"(cv) : "l"(&g_cnt1) : "memory");
        }
      }
    }
      if (warp == 5) {
        if (lane == 0) {
          const uint32_t tgt = lds32(ep_addr) * 128u;
          int it = 0;
          while ((int)(cv - tgt) < 0 && ++it < 400000) asm volatile("ld.relaxed.gpu.global.u32 %0, [%1];" : "=r"(cv) : "l"(&g_cnt1) : "memory");
          asm volatile("fence.acquire.gpu;" ::: "memory");
          asm volatile("fence.proxy.async.global;" ::: "memory");
          TR(0, 9);
        }
        __syncwarp();
#pragma unroll
        for (int c2 = 0; c2 < 4; c2++) bulk_ld_elect<8192>(sb + c2 * A_CH + A_REC, g_ux + (size_t)(cblk * 4 + c2) * 512, bar_rec);
      }
    {
      const cf p0 = cexp_l(lr[0], li[0], 8.f), p1 = cexp_l(lr[1], li[1], 8.f);
      cf v0 = p0, v1 = p1;
      sts64(sw + 8 * 272, 0x3C00u, 0x3C00u);
#pragma unroll
      for (int i = 1; i < 8; i++) {
        sts64(sw + (8 + i) * 272, pack_h(v0), pack_h(v1));
        v0 = cmul(v0, p0); v1 = cmul(v1, p1);
      }
      const uint32_t ra = stg + 5 * 272 + (lane >> 2) * 64 + (lane & 1) * 32 + (lane & 2) * 4;
      sts64(ra, pack_h(v0), pack_h(-v0.y, v0.x));
      sts64(ra + 16, pack_h(v1), pack_h(-v1.y, v1.x));
    }
    __syncwarp();
    if (tid == 320) TR(0, 16);
#pragma unroll
    for (int k2 = 0; k2 < 4; k2++) ldsm4(bf + 32 + k2 * 4, stg + (lane & 7) * 272 + k2 * 64 + (lane >> 3) * 16);
    float c[6][4];
#pragma unroll
    for (int i = 0; i < 6; i++) { c[i][0] = 0.f; c[i][1] = 0.f; c[i][2] = 0.f; c[i][3] = 0.f; }
#pragma unroll
    for (int k2 = 0; k2 < 4; k2++) {
      uint32_t a[4];
      ldsm4(a, stg + (8 + (lane & 7)) * 272 + k2 * 64 + (lane >> 3) * 16);
#pragma unroll
      for (int kk = 0; kk < 2; kk++) {
        const int ks = 2 * k2 + kk;
        const uint4 r4 = lds128(stg + 5 * 272 + ks * 64 + t * 16);
        const uint32_t r[4] = {r4.x, r4.z, r4.y, r4.w};
        const uint32_t x0 = a[2 * kk], y0 = a[2 * kk + 1];
        const uint32_t x1 = hcmul(x0, r[0], r[2]), y1 = hcmul(y0, r[1], r[3]);
        const uint32_t x2 = hcmul(x1, r[0], r[2]), y2 = hcmul(y1, r[1], r[3]);
        const uint32_t x3 = hcmul(x2, r[0], r[2]), y3 = hcmul(y2, r[1], r[3]);
#pragma unroll
        for (int n = 0; n < 3; n++) {
          mma16816(c[n * 2], x0, x1, y0, y1, bf[n * 16 + ks * 2], bf[n * 16 + ks * 2 + 1]);
          mma16816(c[n * 2 + 1], x2, x3, y2, y3, bf[n * 16 + ks * 2], bf[n * 16 + ks * 2 + 1]);
        }
      }
    }
    __syncwarp();
#pragma unroll
    for (int i = 0; i < 6; i++)
      sts128(stg + i * 512 + lane * 16, __float_as_uint(c[i][0]), __float_as_uint(c[i][1]), __float_as_uint(c[i][2]), __float_as_uint(c[i][3]));
  }
  if (tid == 320) TR(0, 2);

  uint32_t xt[8], ud[8];
  {
    mbar_wait(bar_rec, 0);
    if (tid == 320) TR(0, 4);
      if (bk == 127) {
        mbar_expect(bar_w + 8 * wg, 7168);
        tma3d(sb + A_WST + wg * 7168, (ch & 1) ? mu : mg, ((ch >> 1) % 14) * 32, ((ch >> 1) / 14) * 14, bar_w + 8 * wg);
      }
    uint4 r[4];
#pragma unroll
    for (int i = 0; i < 4; i++) r[i] = lds128(cb + A_REC + bk * 64 + ((i ^ (bk >> 1)) & 3) * 16);
    const uint32_t ua = cb + A_UB + ((2 * bk) & 7) * 656 + ((bk >> 2) + 9) * 16;
    sts128(ua, r[0].x, r[1].x, r[2].x, r[3].x);
    sts128(ua + 656, r[0].y, r[1].y, r[2].y, r[3].y);
    if (bk <= 96) {
      const bool neg = bk == 96;
      const int bp = neg ? -1 : bk;
      uint32_t h[4];
      h[0] = lds32(cb + A_REC + ((bp - 1) & 127) * 64 + ((2 ^ ((bp - 1) >> 1)) & 3) * 16 + 4);
      h[1] = lds32(cb + A_REC + ((bp - 1) & 127) * 64 + ((3 ^ ((bp - 1) >> 1)) & 3) * 16 + 4);
      h[2] = lds32(cb + A_REC + (bp + 1) * 64 + ((0 ^ ((bp + 1) >> 1)) & 3) * 16);
      h[3] = lds32(cb + A_REC + (bp + 1) * 64 + ((1 ^ ((bp + 1) >> 1)) & 3) * 16);
      if (bp <= 0) { h[0] = 0; h[1] = 0; }
      const uint32_t wd[12] = {h[0], h[1], neg ? 0 : r[0].x, neg ? 0 : r[1].x, neg ? 0 : r[2].x, neg ? 0 : r[3].x,
                               neg ? 0 : r[0].y, neg ? 0 : r[1].y, neg ? 0 : r[2].y, neg ? 0 : r[3].y, h[2], h[3]};
      float P[25];
      P[0] = 0.f;
#pragma unroll
      for (int i = 0; i < 12; i++) { P[2 * i + 1] = P[2 * i] + bf_lo(wd[i]); P[2 * i + 2] = P[2 * i + 1] + bf_hi(wd[i]); }
#define WIN(i, hw) (P[(i) + 5 + (hw)] - P[(i) + 4 - (hw)])
#define WPK(i, hw) pack_bf16(WIN(i, hw), WIN((i) + 1, hw))
      const int tp = 2 * bp;
      const uint32_t a3 = cb + A_W3 + (tp + 64) * 16 + 8, a5 = cb + A_W5 + (tp + 64) * 16;
      sts64(a3, WPK(0, 1), WPK(2, 1));
      sts128(a3 + 8, WPK(4, 1), WPK(6, 1), WPK(8, 1), WPK(10, 1));
      sts64(a3 + 24, WPK(12, 1), WPK(14, 1));
      sts128(a5, WPK(0, 2), WPK(2, 2), WPK(4, 2), WPK(6, 2));
      sts128(a5 + 16, WPK(8, 2), WPK(10, 2), WPK(12, 2), WPK(14, 2));
      if (bp < 64) {
        sts128(cb + A_W7 + 1040 + bp * 16, WPK(0, 3), WPK(2, 3), WPK(4, 3), WPK(6, 3));
        sts128(cb + A_W7 + (bp + 1) * 16, WPK(8, 3), WPK(10, 3), WPK(12, 3), WPK(14, 3));
        sts128(cb + A_W9 + (bp + 1) * 16, WPK(0, 4), WPK(2, 4), WPK(4, 4), WPK(6, 4));
        sts128(cb + A_W9 + 1040 + (bp + 1) * 16, WPK(8, 4), WPK(10, 4), WPK(12, 4), WPK(14, 4));
#define VPK(i) pack_bf16(P[(i) + 2] - P[i], P[(i) + 3] - P[(i) + 1])
        sts128(cb + A_V + bp * 32, VPK(0), VPK(2), VPK(4), VPK(6));
        sts128(cb + A_V + bp * 32 + 16, VPK(8), VPK(10), VPK(12), VPK(14));
      }
    }
  }
  asm volatile("fence.proxy.async.shared::cta;" ::: "memory");
  bar_sync(1 + wg, 128);
  if (tid == 320) TR(0, 3);
  {
    const uint4 sc = lds128(cb + A_SCL);
    const float scl[4] = {__uint_as_float(sc.x), __uint_as_float(sc.y), __uint_as_float(sc.z), __uint_as_float(sc.w)};
#pragma unroll
    for (int rep = 0; rep < 2; rep++) {
      const int qd = rep ? 2 + wr : 3 - wr;
      if (rep == 0 || wr >= 2) {
        float s[4] = {0.f, 0.f, 0.f, 0.f};
#pragma unroll
        for (int w = 0; w < 4; w++) {
          uint4 u4 = lds128(cb + A_STG + w * 4352 + qd * 512 + lane * 16);
          s[0] = fmaf(__uint_as_float(u4.x), scl[w], s[0]); s[1] = fmaf(__uint_as_float(u4.y), scl[w], s[1]);
          s[2] = fmaf(__uint_as_float(u4.z), scl[w], s[2]); s[3] = fmaf(__uint_as_float(u4.w), scl[w], s[3]);
        }
#pragma unroll
        for (int hf = 0; hf < 2; hf++) {
          const int j = (qd & 1) * 16 + g + 8 * hf;
          const uint32_t pk = pack_bf16(s[2 * hf + 1], s[2 * hf]);
          const uint32_t v0 = pk >> 16, v1 = pk & 0xFFFFu, v00 = v0 * 0x10001u;
          if (rep == 1) {
            if (t < 2) {
#pragma unroll
              for (int e = 0; e < 2; e++) {
                const int lam = 128 + 32 * (2 * t + e) + j, mu = lam >> 1;
                const uint32_t val = e ? v1 : v0;
                uint32_t a = cb + ((lam & 1) ? A_R3B : A_R3A) + mu * 4;
                if (lam == 128) { a = cb + A_R2A + 128 * 4; sts32(cb + A_K1024, val << 16); }
                sts16(a, val); sts16(a + 6, val);
              }
            } else if (t == 2 && j == 0) { sts16(cb + A_R3A + 128 * 4, v0); }
          } else if (qd < 2) {
            const uint32_t a = cb + A_R1 + (62 + 8 * j + 2 * t) * 4;
            sts16(a, v0); sts32(a + 4, pk); sts16(a + 10, v1);
          } else if (t < 2) {
            const int L = 256 + 8 * j + 4 * t;
            const uint32_t a = cb + A_R1 + (62 + L) * 4;
            if (L > 256) { sts16(a - 4, v0); sts32(a, v00); } else sts16(a, v0);
            sts32(a + 4, v00); sts32(a + 8, pk); sts16(a + 14, v1);
          } else {
            const int mu = 64 + 32 * (t - 2) + j;
            if (mu == 64) {
              const uint32_t a = cb + A_R1 + (62 + 512) * 4;
              sts16(a - 4, v0); sts32(a, v00); sts32(a + 4, v00); sts32(a + 8, v00); sts16(a + 14, v0);
            } else { sts16(cb + A_R2A + mu * 4, v0); sts16(cb + A_R2A + mu * 4 + 6, v0); }
            sts16(cb + A_R2B + mu * 4, v1); sts16(cb + A_R2B + mu * 4 + 6, v1);
          }
        }
      }
    }
  }
  bar_sync(1 + wg, 128);
  if (tid == 320) TR(0, 5);

  {
    const uint32_t cbu = cb;
    const uint32_t blo_k = ((cbu & 0x3FFFF) >> 4) | (41u << 16);
    const uint32_t blo_n = ((cbu & 0x3FFFF) >> 4) | (8u << 16);
    const uint32_t tb = cb + (16 * wq + g - 2 * t) * 4;
    float y1[16], y2[12], y3[8];
    const uint32_t dk16 = __ldg(dskip + ch);
    uint32_t qa[32], qb[32];
    const uint32_t t1 = tb + A_R1 + (62 - 48) * 4;
    load_quads<4>(qa, tb + A_R3A + 17 * 4); load_quads<4>(qa + 16, tb + A_R3B + 16 * 4);
    wg_fence();
    s3_steps<0, 4, A_W9, 1>(y3, qa, blo_n); s3_steps<0, 4, A_W7, 0>(y3, qa + 16, blo_n);
    wg_commit();
    load_quads<8>(qb, tb + A_R2A + 16 * 4);
    wg_fence(); s2_steps<0, 8, A_W5, 1>(y2, qb, blo_n); wg_commit();
    wg_wait<1>(); load_quads<8>(qa, tb + A_R2B + 16 * 4);
    wg_fence(); s2_steps<0, 8, A_W3, 0>(y2, qa, blo_n); wg_commit();
    wg_wait<1>(); load_quads<8>(qb, t1);
    wg_fence(); f1_steps<0, 8>(y1, qb, blo_k); wg_commit();
    wg_wait<1>(); load_quads<8>(qa, t1 + 8 * 64);
    wg_fence(); f1_steps<8, 8>(y1, qa, blo_k); wg_commit();
    reg_fence(y2); reg_fence(y3);
    if (tid == 320) TR(0, 18);
    {
      const float k1024 = __uint_as_float(lds32(cb + A_K1024));
#pragma unroll
      for (int i = 0; i < 2; i++)
#pragma unroll
        for (int hf = 0; hf < 2; hf++) {
          const int idx = 16 * (16 * wq + g + 8 * hf) + 8 * i + 2 * t;
          const uint32_t vv = lds32(cb + A_V + idx * 2);
          sts64(cb + A_Y3 + (idx + 4 * (idx >> 6)) * 4, __float_as_uint(fmaf(k1024, bf_lo(vv), y3[4 * i + 2 * hf])),
                __float_as_uint(fmaf(k1024, bf_hi(vv), y3[4 * i + 2 * hf + 1])));
        }
#pragma unroll
      for (int i = 0; i < 3; i++)
#pragma unroll
        for (int hf = 0; hf < 2; hf++) {
          const int idx = 512 * i + 8 * (16 * wq + g + 8 * hf) + 2 * t;
          sts64(cb + A_Y2 + (idx + 4 * (idx >> 6)) * 4, __float_as_uint(y2[4 * i + 2 * hf]), __float_as_uint(y2[4 * i + 2 * hf + 1]));
        }
    }
    wg_wait<1>(); load_quads<8>(qb, t1 + 16 * 64);
    wg_fence(); f1_steps<16, 8>(y1, qb, blo_k); wg_commit();
    wg_wait<1>(); load_quads<8>(qa, t1 + 24 * 64);
    wg_fence(); f1_steps<24, 8>(y1, qa, blo_k); wg_commit();
  if (bk == 127) {
    mbar_wait(bar_w + 8 * wg, 0);
    bulk_st(g_wimg + (size_t)((ch >> 1) / 28) * 37632 + ((ch >> 1) % 28) * 896 + (ch & 1) * 448, sb + A_WST + wg * 7168, 7168);
    asm volatile("cp.async.bulk.commit_group;" ::: "memory");
  }

    wg_wait<1>(); load_quads<5>(qb, t1 + 32 * 64);
    wg_fence(); f1_steps<32, 5>(y1, qb, blo_k); wg_commit();
    bar_sync(1 + wg, 128);
    float ex[12];
#pragma unroll
    for (int i = 1; i < 4; i++)
#pragma unroll
      for (int k = 0; k < 4; k++) {
        const int aa = 8 * i + 2 * t + (k & 1), b = 16 * wq + g + 8 * (k >> 1);
        float e = __uint_as_float(lds32(cb + A_Y2 + ((aa - 8) * 68 + b) * 4));
        if (i >= 2) e += __uint_as_float(lds32(cb + A_Y3 + ((aa - 16) * 68 + b) * 4));
        ex[4 * (i - 1) + k] = e;
      }
    {
      const uint32_t dk = dk16 * 0x10001u;
#pragma unroll
      for (int i = 0; i < 4; i++) {
        const uint4 r = lds128(cb + A_REC + bk * 64 + ((i ^ (bk >> 1)) & 3) * 16);
        ud[i] = hmul2_bf(r.x, dk); ud[4 + i] = hmul2_bf(r.y, dk); xt[i] = r.z; xt[4 + i] = r.w;
      }
    }
    wg_wait<0>();
    reg_fence(y1);
    if (tid == 320) TR(0, 6);
#pragma unroll
    for (int i = 0; i < 12; i++) y1[4 + i] += ex[i];
#pragma unroll
    for (int i = 0; i < 2; i++) {
      const int mi = lane >> 3, aa = 8 * (2 * i + (mi >> 1)) + (lane & 7);
      asm volatile("stmatrix.sync.aligned.m8n8.x4.trans.shared.b16 [%0], {%1,%2,%3,%4};"
                   ::"r"(cb + A_YB + aa * 128 + (((2 * wq + (mi & 1)) ^ (lane & 7)) << 4)),
                     "r"(pack_bf16(y1[8 * i], y1[8 * i + 1])), "r"(pack_bf16(y1[8 * i + 2], y1[8 * i + 3])),
                     "r"(pack_bf16(y1[8 * i + 4], y1[8 * i + 5])), "r"(pack_bf16(y1[8 * i + 6], y1[8 * i + 7])) : "memory");
    }
  }
  bar_sync(1 + wg, 128);
#pragma unroll
  for (int c = 0; c < 2; c++) {
    const int tau = 2 * bk + c, r = ch & 7;
    const uint4 y = lds128(cb + A_YB + (tau >> 3) * 128 + (((tau ^ (tau >> 3)) & 7) << 4));
    g_himg[(size_t)(tau >> 4) * 7168 + (ch >> 3) * 128 + ((tau >> 3) & 1) * 64 + r * 8 + ((tau & 7) ^ r)] =
        make_uint4(hadd2_bf(xt[4 * c], hadd2_bf(y.x, ud[4 * c])), hadd2_bf(xt[4 * c + 1], hadd2_bf(y.y, ud[4 * c + 1])),
                   hadd2_bf(xt[4 * c + 2], hadd2_bf(y.z, ud[4 * c + 2])), hadd2_bf(xt[4 * c + 3], hadd2_bf(y.w, ud[4 * c + 3])));
  }
  if (bk == 127) asm volatile("cp.async.bulk.wait_group 0;" ::: "memory");
  if (tid == 320) TR(0, 7);
}

constexpr int B_SA = 0, B_RING = 114688, B_SLOT = 14848, B_NSLOT = 7;
constexpr int B_CS = B_RING + B_NSLOT * B_SLOT;
constexpr int B_RED = B_CS + 7168;
constexpr int B_BAR = B_RED + 256;
constexpr int B_SMEM = B_BAR + 1024, A_SMEM = A_WST + 28672;

__device__ __forceinline__ uint32_t mapa(uint32_t a, uint32_t r) { uint32_t o; asm("mapa.shared::cluster.u32 %0, %1, %2;" : "=r"(o) : "r"(a), "r"(r)); return o; }
template <class T> __device__ __forceinline__ T* pin(T* p) { asm volatile("" : "+l"(p)); return p; }
__device__ __forceinline__ uint32_t pin(uint32_t v) { asm volatile("" : "+r"(v)); return v; }
template <int Q, int ST>
__device__ __forceinline__ void g1_stage(float (&acc)[116], uint32_t alo, uint32_t blo, uint32_t bar_full, uint32_t bar_h) {
  constexpr int s = Q * 14 + ST, sl = s % B_NSLOT;
  if (Q == 0) mbar_wait(bar_h + 8 * ST, 0);
  mbar_wait(bar_full + 8 * sl, (s / B_NSLOT) & 1);
  wg_fence();
  if (Q == 0) {
    wgmma_ss232<(2 * ST) * 256, 0x40000080u, (sl * B_SLOT) / 16, 32, ST != 0>(acc, alo, blo);
    wgmma_ss232<(2 * ST + 1) * 256, 0x40000080u, (sl * B_SLOT + 256) / 16, 32, 1>(acc, alo, blo);
  } else {
    wgmma_ss224<(2 * ST) * 256, 0x40000080u, (sl * B_SLOT) / 16, 32, ST != 0>(*(float(*)[112])acc, alo, blo);
    wgmma_ss224<(2 * ST + 1) * 256, 0x40000080u, (sl * B_SLOT + 256) / 16, 32, 1>(*(float(*)[112])acc, alo, blo);
  }
}

__global__ void __launch_bounds__(512, 1)
k_front(const __grid_constant__ CUtensorMap mg, const __grid_constant__ CUtensorMap mu, const __grid_constant__ CUtensorMap md,
        const __nv_bfloat16* __restrict__ x, const uint32_t* __restrict__ are, const uint32_t* __restrict__ aim,
        const uint32_t* __restrict__ bre, const uint32_t* __restrict__ bim, const uint32_t* __restrict__ cre,
        const uint32_t* __restrict__ cim, const unsigned short* __restrict__ logdt, const unsigned short* __restrict__ dskip,
        const uint4* __restrict__ wgate, const uint4* __restrict__ wup) {
  extern __shared__ __align__(1024) unsigned char sm[];
  const uint32_t bar_rec = s2u(sm) + A_BAR;
  if (threadIdx.x == 320) TR(0, 0);
  asm volatile("griddepcontrol.launch_dependents;");
  if (threadIdx.x == 160) {
    mbar_init(bar_rec, 4);
    for (int i = 0; i < 8; i++) mbar_init(bar_rec + 16 + 8 * i, 1);
    asm volatile("fence.mbarrier_init.release.cluster;" ::: "memory");
    asm volatile("prefetch.tensormap [%0];" ::"l"(&mg)); asm volatile("prefetch.tensormap [%0];" ::"l"(&mu)); asm volatile("prefetch.tensormap [%0];" ::"l"(&md));
  }
  phase_a(sm, bar_rec, bar_rec + 8, &mg, &mu, &md, x, are, aim, bre, bim, cre, cim, logdt, dskip, wgate, wup);
}

__global__ void __cluster_dims__(2, 1, 1) __launch_bounds__(384, 1) k_ffn(__nv_bfloat16* __restrict__ out) {
  extern __shared__ __align__(1024) unsigned char sm[];
  const uint32_t sb = s2u(sm);
  const int tid = threadIdx.x, warp = __shfl_sync(~0u, tid >> 5, 0), wg = warp >> 2, lane = tid & 31;
  const uint32_t bar_full = sb + B_BAR, bar_empty = bar_full + 64, bar_h = bar_full + 128, bar_cs = bar_full + 240,
                 bar_hh = bar_full + 304, bar_afree = bar_full + 336, bar_out = bar_full + 352;
  if (tid == 0) {
    TR(1, 0);
    for (int i = 0; i < B_NSLOT; i++) { mbar_init(bar_full + 8 * i, 1); mbar_init(bar_empty + 8 * i, 2); }
    asm volatile("fence.mbarrier_init.release.cluster;" ::: "memory");
  } else if (tid == 32) {
    for (int i = 0; i < 14; i++) mbar_init(bar_h + 8 * i, 1);
    asm volatile("fence.mbarrier_init.release.cluster;" ::: "memory");
  } else if (tid == 64) {
    mbar_init(bar_cs, 1);
    for (int i = 0; i < 4; i++) { mbar_init(bar_hh + 8 * i, 1); mbar_expect(bar_hh + 8 * i, 14336); }
    mbar_init(bar_afree, 4); mbar_init(bar_afree + 8, 2);
    for (int i = 0; i < 6; i++) mbar_init(bar_out + 8 * i, 128);
    asm volatile("fence.mbarrier_init.release.cluster;" ::: "memory");
  } else if (tid >= 128 && tid < 352) {
    sts128(sb + B_RING + ((tid - 128) >> 5) * B_SLOT + 14336 + (tid & 31) * 16, 0x3F803F80u, 0x3F803F80u, 0x3F803F80u, 0x3F803F80u);
  }
  asm volatile("fence.proxy.async.shared::cta;" ::: "memory");
  __syncthreads();
  asm volatile("barrier.cluster.arrive.relaxed.aligned;" ::: "memory");
  const int rank = blockIdx.x & 1, rt = blockIdx.x >> 3, j = blockIdx.x & 7, p = j >> 1, cg = 4 * rank + p;
  const int wq = warp & 3, t128 = tid & 127, g = lane >> 2, t = lane & 3;
  uint32_t ep, tag;
  auto load_ep = [&]() { asm volatile("ld.relaxed.gpu.global.u32 %0, [%1];" : "=r"(ep) : "l"(&g_cnt1) : "memory"); };
  auto a_slot = [&](int i, int own) { return B_SA + (i + (i >= own)) * 14336; };
  auto out_addr = [&](int cc, int w) { return sb + a_slot((cc & 2) + w, cg) + (cc & 1) * 7168; };
  auto in_cta = [&](int q) { return rt * 8 + ((p + 3 - q) & 3) * 2 + rank; };
  auto in_src = [&](int q, int cw) { return g_part + (size_t)(in_cta(q) * 3 + q) * 896 + cw * 112; };
  auto in_bad = [&](uint32_t (&in)[14]) { return ((in[3] ^ tag) | (in[7] ^ tag) | (in[11] ^ tag) | (in[13] ^ tag)) & 0x10000u; };
  auto in_load = [&](uint32_t (&in)[14], const uint4* gs) {
#pragma unroll
    for (int i = 0; i < 3; i++) ld128(gs + i * 32, in + 4 * i);
    asm volatile("{\n.reg .b64 v;\nld.relaxed.gpu.global.b64 v, [%2];\nmov.b64 {%0, %1}, v;\n}"
                 : "=r"(in[12]), "=r"(in[13]) : "l"((const uint2*)(gs + 96) - lane) : "memory");
  };
  auto in_check = [&](uint32_t (&in)[14], int q, int cw) {
    int it = 0;
    while (in_bad(in) && ++it < 400000) in_load(in, pin(in_src(q, cw) + lane));
  };

  if (wg == 2) {
    asm volatile("setmaxnreg.dec.sync.aligned.u32 40;");
    asm volatile("barrier.cluster.wait.aligned;" ::: "memory");
    asm volatile("griddepcontrol.wait;" ::: "memory");
    if (warp == 8) {
      if (lane == 0) TR(1, 1);
      const char* wsrc = (const char*)g_wimg + (size_t)j * 602112;
      const char* hsrc = (const char*)g_himg + (size_t)rt * 114688 + rank * 4096;
#pragma unroll
      for (int s = 0; s < 28; s++) {
        if (s < B_NSLOT) bulk_ld_mc_elect<4096>(sb + B_SA + s * 8192 + rank * 4096, hsrc + s * 8192, bar_h + 8 * s);
        if (s == B_NSLOT) {
#pragma unroll
          for (int i = 7; i < 14; i++) bulk_ld_mc_elect<4096>(sb + B_SA + i * 8192 + rank * 4096, hsrc + i * 8192, bar_h + 8 * i);
          bulk_ld_elect<7168>(sb + B_CS, g_cimg + j * 448, bar_cs);
        }
        if (s >= B_NSLOT) mbar_wait(bar_empty + 8 * (s % B_NSLOT), (s / B_NSLOT + 1) & 1);
        bulk_ld_elect<14336>(sb + B_RING + (s % B_NSLOT) * B_SLOT, wsrc + s * 14336, bar_full + 8 * (s % B_NSLOT));
      }
      const char* dsrc[2] = {wsrc + 401408 + rank * 100352, (const char*)g_wimg + (size_t)(j ^ 1) * 602112 + 401408 + rank * 100352};
#pragma unroll
      for (int i = 0; i < 16; i++) {
        const int ci = i < 3 ? 0 : i < 6 ? 1 : i < 8 ? i - 6 : i < 12 ? 2 : 3;
        const int kp = i < 3 ? i : i < 6 ? i - 3 : i < 8 ? 3 : (i & 3);
        mbar_wait(bar_empty + 8 * (i % B_NSLOT), (i / B_NSLOT + 1) & 1);
        bulk_ld_elect<12544>(sb + B_RING + (i % B_NSLOT) * B_SLOT, dsrc[kp >> 1] + ((p + 1 + ci) & 3) * 25088 + (kp & 1) * 12544, bar_full + 8 * (i % B_NSLOT));
      }
    } else if (warp >= 10) {
      const int t64 = tid - 320;
      load_ep();
      const int r = (lane >> 1) & 7, c = (j & 3) * 2 + (lane & 1);
      const uint32_t src = sb + B_SA + (t64 >> 4) * 2048 + (j >> 2) * 1024 + r * 128 + ((c ^ r) << 4);
      float a[16];
#pragma unroll
      for (int k = 0; k < 16; k++) a[k] = 0.f;
#pragma unroll 1
      for (int i = 0; i < 14; i++) {
        mbar_wait(bar_h + 8 * i, 0);
        uint4 v = lds128(src + i * 8192);
        float e[8] = {bf_lo(v.x), bf_hi(v.x), bf_lo(v.y), bf_hi(v.y), bf_lo(v.z), bf_hi(v.z), bf_lo(v.w), bf_hi(v.w)};
#pragma unroll
        for (int k = 0; k < 8; k++) { a[2 * k] += e[k]; a[2 * k + 1] = fmaf(e[k], e[k], a[2 * k + 1]); }
        __nanosleep(160);
      }
      __syncwarp();
      if (lane == 0) { asm volatile("mbarrier.arrive.shared::cluster.b64 _, [%0];" ::"r"(mapa(bar_afree, rank ^ 1)) : "memory"); }
#pragma unroll
      for (int rd = 0; rd < 4; rd++) {
        const int n = 8 >> rd;
        const bool up = lane & (2 * n);
#pragma unroll
        for (int k = 0; k < 8; k++) {
          if (k < n) {
            float keep = up ? a[k + n] : a[k], give = up ? a[k] : a[k + n];
            a[k] = keep + __shfl_xor_sync(~0u, give, 2 * n);
          }
        }
      }
      float* red = (float*)(sm + B_RED);
      red[(warp & 1) * 32 + (lane & 1) * 16 + (lane >> 1)] = a[0];
      bar_sync(1, 64);
      if (t64 < 16) {
        float mean = (red[2 * t64] + red[32 + 2 * t64]) * (1.f / DM);
        float var = fmaxf(fmaf(-mean, mean, (red[2 * t64 + 1] + red[33 + 2 * t64]) * (1.f / DM)), 0.f);
        float rs = ln_rstd(var);
        asm volatile("st.relaxed.gpu.global.u32 [%0], %1;"
                     ::"l"(g_stat2 + rt * 128 + j * 16 + t64), "r"((__float_as_uint(rs * rs) & ~1u) | ((ep >> 7) & 1u)) : "memory");
      }
      if (t64 == 0) TR(1, 2);
      if (lane == 0) {
        const int w = warp & 1;
        for (int cc = 0; cc < 2; cc++) {
          mbar_wait(bar_out + 8 * (cc * 2 + w), 0);
          asm volatile("cp.async.bulk.global.shared::cta.bulk_group [%0], [%1], 7168;"
                       ::"l"(g_part + (size_t)(blockIdx.x * 3 + cc) * 896 + w * 448), "r"(out_addr(cc, w)) : "memory");
          if (w) TR(1, 27 + cc);
        }
        asm volatile("cp.async.bulk.commit_group;" ::: "memory");
        asm volatile("cp.async.bulk.wait_group 0;" ::: "memory");
      }
    }
  } else {
    asm volatile("setmaxnreg.inc.sync.aligned.u32 232;");
    asm volatile("barrier.cluster.wait.aligned;" ::: "memory");
    uint32_t hh[56];
    const bool relt = t128 == 0;
    auto release = [&](int sl) { if (relt) mbar_arrive(bar_empty + 8 * sl); };
    auto send_hh = [&](int q) {
      const uint32_t da = mapa(sb + a_slot(2 * q + wg, cg ^ 4) + t128 * 16, rank ^ 1), db = mapa(bar_hh + 8 * (2 * q + wg), rank ^ 1);
#pragma unroll
      for (int i = 0; i < 7; i++)
        asm volatile("st.async.weak.shared::cluster.mbarrier::complete_tx::bytes.v4.b32 [%0], {%1, %2, %3, %4}, [%5];"
                     ::"r"(da + i * 2048), "r"(hh[28 * q + 4 * i]), "r"(hh[28 * q + 4 * i + 1]),
                       "r"(hh[28 * q + 4 * i + 2]), "r"(hh[28 * q + 4 * i + 3]), "r"(db) : "memory");
    };
    uint32_t alo = ((sb + B_SA + wg * 1024) & 0x3FFFF) >> 4;
    uint32_t blo = (((sb + B_RING) & 0x3FFFF) >> 4) | (8u << 16);
    const uint32_t clo = ((sb + B_CS) & 0x3FFFF) >> 4;
    uint32_t nm0, nm1;
    if (wg == 1) bar_sync(3, 256);
#define G1S(Q, ST) do { if (ST % 7 == 0) { alo = pin(alo); blo = pin(blo); }   \
      g1_stage<Q, ST>(acc, alo, blo, bar_full, bar_h); wg_commit(); \
      if (ST > 0) { wg_wait<1>(); release((Q * 14 + ST - 1) % B_NSLOT); } } while (0)
#define G1HH(Q) do { \
      _Pragma("unroll") \
      for (int i = 0; i < 28; i++) hh[28 * Q + i] = pack_bf16(acc[2 * i] * acc[56 + 2 * i], acc[2 * i + 1] * acc[57 + 2 * i]); \
    } while (0)
    {
      float acc[116];
      G1S(0, 0);
      if (tid == 0) TR(1, 3);
      G1S(0, 1);
      if (wg == 0) asm volatile("bar.arrive 3, 256;" ::: "memory");
      G1S(0, 2); G1S(0, 3); G1S(0, 4); G1S(0, 5); G1S(0, 6); G1S(0, 7); G1S(0, 8); G1S(0, 9); G1S(0, 10); G1S(0, 11); G1S(0, 12);
      G1S(0, 13);
      if (tid == 0) TR(1, 4);
      mbar_wait(bar_cs, 0);
      wg_wait<0>(); reg_fence(acc); release(13 % B_NSLOT);
      {
        const uint32_t msk = t == 0 ? 0xFFFFFFFFu : t == 1 ? 0xFFFFu : 0u;
        const float a = acc[112] * (-1.f / DM), b = acc[114] * (-1.f / DM);
        nm0 = pack_bf16(a, a) & msk; nm1 = pack_bf16(b, b) & msk;
      }
      wg_fence();
      wgmma_rs224<0, 8, 1>(*(float(*)[112])acc, nm0, nm1, 0u, 0u, clo);
      wg_commit(); wg_wait<0>(); reg_fence(acc);
      G1HH(0);
      if (tid == 0) TR(1, 5);
      G1S(1, 0); G1S(1, 1); G1S(1, 2); G1S(1, 3); G1S(1, 4); G1S(1, 5); G1S(1, 6);
      if (relt) asm volatile("mbarrier.arrive.shared::cluster.b64 _, [%0];" ::"r"(mapa(bar_afree, rank ^ 1)) : "memory");
      G1S(1, 7); G1S(1, 8); G1S(1, 9);
      if (relt) asm volatile("mbarrier.arrive.shared::cluster.b64 _, [%0];" ::"r"(mapa(bar_afree + 8, rank ^ 1)) : "memory");
      mbar_wait(bar_afree, 0);
      send_hh(0);
      G1S(1, 10); G1S(1, 11); G1S(1, 12);
      load_ep();
      g1_stage<1, 13>(acc, alo, blo, bar_full, bar_h);
      wgmma_rs224<224, 8, 1>(*(float(*)[112])acc, nm0, nm1, 0u, 0u, clo);
      wg_commit(); wg_wait<1>(); release(26 % B_NSLOT);
      wg_wait<0>(); reg_fence(acc); release(27 % B_NSLOT);
      G1HH(1);
      if (tid == 0) TR(1, 6);
    }
    float accA[28], accB[28];
    uint32_t ph0[28], ph1[28];
    ep = pin(ep >> 7); tag = pin((ep & 1u) << 16);
#define ISSUE(acc, I, a, FIRST) do { \
      constexpr int s_ = 28 + (I), sl_ = s_ % B_NSLOT; \
      if (sl_ == 0) blo = pin(blo); \
      mbar_wait(bar_full + 8 * sl_, (s_ / B_NSLOT) & 1); \
      wg_fence(); \
      wgmma_rs56<(sl_ * B_SLOT + 0 * 256) / 16, 112, !(FIRST)>(acc, (a)[0], (a)[1], (a)[2], (a)[3], blo); \
      wgmma_rs56<(sl_ * B_SLOT + 1 * 256) / 16, 112, 1>(acc, (a)[4], (a)[5], (a)[6], (a)[7], blo); \
      wgmma_rs56<(sl_ * B_SLOT + 2 * 256) / 16, 112, 1>(acc, (a)[8], (a)[9], (a)[10], (a)[11], blo); \
      wgmma_rs56<(sl_ * B_SLOT + 3 * 256) / 16, 112, 1>(acc, (a)[12], (a)[13], (a)[14], (a)[15], blo); \
      wgmma_rs56<(sl_ * B_SLOT + 4 * 256) / 16, 112, 1>(acc, (a)[16], (a)[17], (a)[18], (a)[19], blo); \
      wgmma_rs56<(sl_ * B_SLOT + 5 * 256) / 16, 112, 1>(acc, (a)[20], (a)[21], (a)[22], (a)[23], blo); \
      wgmma_rs56<(sl_ * B_SLOT + 6 * 256) / 16, 112, 1>(acc, (a)[24], (a)[25], (a)[26], (a)[27], blo); \
      wg_commit(); } while (0)
    auto rel = [&](int i) { release((28 + i) % B_NSLOT); };
    auto tg = [&](uint32_t v) { return (v & 0xFFFEFFFFu) | tag; };
    auto send = [&](float (&acc)[28], int cc) {
      reg_fence(acc);
      const uint32_t a = out_addr(cc, wg) + wq * 1792;
#pragma unroll
      for (int q = 0; q < 3; q++)
        sts128(a + q * 512 + lane * 16, pack_bf16(acc[8 * q], acc[8 * q + 1]), pack_bf16(acc[8 * q + 2], acc[8 * q + 3]),
               pack_bf16(acc[8 * q + 4], acc[8 * q + 5]), tg(pack_bf16(acc[8 * q + 6], acc[8 * q + 7])));
      sts64(a + 1536 + lane * 8, pack_bf16(acc[24], acc[25]), tg(pack_bf16(acc[26], acc[27])));
      asm volatile("fence.proxy.async.shared::cta;" ::: "memory");
      mbar_arrive(bar_out + 8 * (cc * 2 + wg));
    };
    auto load_hh = [&](uint32_t (&d)[28], int q) {
      mbar_wait(bar_hh + 8 * (2 * q + wg), 0);
      const uint32_t a = sb + a_slot(2 * q + wg, cg) + t128 * 16;
#pragma unroll
      for (int i = 0; i < 7; i++) {
        const uint4 v = lds128(a + i * 2048);
        d[4 * i] = v.x; d[4 * i + 1] = v.y; d[4 * i + 2] = v.z; d[4 * i + 3] = v.w;
      }
    };
    ISSUE(accA, 0, hh, true);
    mbar_wait(bar_afree + 8, 0);
    send_hh(1);
    ISSUE(accA, 1, hh + 28, false);
    load_hh(ph0, 0);
    wg_wait<1>(); rel(0);
    ISSUE(accA, 2, ph0, false);      wg_wait<1>(); rel(1);
    ISSUE(accB, 3, hh, true);        wg_wait<1>(); rel(2);
    ISSUE(accB, 4, hh + 28, false);  wg_wait<1>(); rel(3);
    ISSUE(accB, 5, ph0, false);
    if (tid == 0) TR(1, 11);
    load_hh(ph1, 1);
    wg_wait<1>(); rel(4);
    ISSUE(accA, 6, ph1, false);      wg_wait<1>(); rel(5);
    ISSUE(accB, 7, ph1, false);      wg_wait<1>(); rel(6); send(accA, 0);
    ISSUE(accA, 8, hh, true);        wg_wait<1>(); rel(7); send(accB, 1);
    if (tid == 0) TR(1, 13);
    ISSUE(accA, 9, hh + 28, false);  wg_wait<1>(); rel(8);
    ISSUE(accA, 10, ph0, false);
    ISSUE(accA, 11, ph1, false);
    const int row = rt * 128 + wg * 64 + wq * 16 + g;
    uint32_t r20, r21;
    asm volatile("ld.relaxed.gpu.global.u32 %0, [%1];" : "=r"(r20) : "l"(g_stat2 + row) : "memory");
    asm volatile("ld.relaxed.gpu.global.u32 %0, [%1];" : "=r"(r21) : "l"(g_stat2 + row + 8) : "memory");
    ISSUE(accB, 12, hh, true);
    wg_wait<1>();
    {
      reg_fence(accA);
      uint4* pd = g_part + (size_t)(blockIdx.x * 3 + 2) * 896 + warp * 112 + lane;
#pragma unroll
      for (int q = 0; q < 3; q++)
        st128(pd + q * 32, pack_bf16(accA[8 * q], accA[8 * q + 1]), pack_bf16(accA[8 * q + 2], accA[8 * q + 3]),
              pack_bf16(accA[8 * q + 4], accA[8 * q + 5]), tg(pack_bf16(accA[8 * q + 6], accA[8 * q + 7])));
      asm volatile("{\n.reg .b64 v;\nmov.b64 v, {%1, %2};\nst.relaxed.gpu.global.b64 [%0], v;\n}"
                   ::"l"((uint2*)(pd + 96) - lane), "r"(pack_bf16(accA[24], accA[25])), "r"(tg(pack_bf16(accA[26], accA[27]))) : "memory");
    }
    if (tid == 0) TR(1, 16);
    ISSUE(accB, 13, hh + 28, false);
    ISSUE(accB, 14, ph0, false);
    uint32_t in0[14], in1[14], in2[14];
    in_load(in0, in_src(0, warp) + lane);
    in_load(in1, in_src(1, warp) + lane);
    ISSUE(accB, 15, ph1, false);
    if (tid == 0) TR(1, 7);
    {
      int it = 0;
      while ((((r20 ^ ep) | (r21 ^ ep)) & 1u) && ++it < 400000) {
        asm volatile("ld.relaxed.gpu.global.u32 %0, [%1];" : "=r"(r20) : "l"(g_stat2 + row) : "memory");
        asm volatile("ld.relaxed.gpu.global.u32 %0, [%1];" : "=r"(r21) : "l"(g_stat2 + row + 8) : "memory");
      }
    }
    wg_wait<1>();
    in_load(in2, in_src(2, warp) + lane);
    in_check(in0, 0, warp); in_check(in1, 1, warp);
#pragma unroll
    for (int i = 0; i < 14; i++) { accA[2 * i] = bf_lo(in0[i]) + bf_lo(in1[i]); accA[2 * i + 1] = bf_hi(in0[i]) + bf_hi(in1[i]); }
    if (tid == 0) TR(1, 12);
    wg_wait<0>();
    reg_fence(accB);
    uint32_t hres[16];
#pragma unroll
    for (int i = 0; i < 4; i++) {
      int qq = lane >> 3, r = lane & 7, kg = 7 * cg + 2 * i + (qq >> 1), c = 2 * wq + (qq & 1);
      if (kg > 55) kg = 55;
      asm volatile("ldmatrix.sync.aligned.m8n8.x4.trans.shared.b16 {%0,%1,%2,%3}, [%4];"
                   : "=r"(hres[4 * i]), "=r"(hres[4 * i + 1]), "=r"(hres[4 * i + 2]), "=r"(hres[4 * i + 3])
                   : "r"(sb + B_SA + kg * 2048 + wg * 1024 + r * 128 + ((c ^ r) << 4)) : "memory");
    }
#pragma unroll
    for (int i = 0; i < 28; i++) accB[i] += accA[i];
    if (tid == 0) TR(1, 9);
    in_check(in2, 2, warp);
#pragma unroll
    for (int i = 0; i < 14; i++) { accB[2 * i] += bf_lo(in2[i]); accB[2 * i + 1] += bf_hi(in2[i]); }
    uint32_t* o0 = (uint32_t*)(out + (size_t)row * DM + 56 * cg + 2 * t);
    uint32_t* o1 = o0 + 8 * DM / 2;
#pragma unroll
    for (int i = 0; i < 7; i++) {
      o0[4 * i] = hadd2_bf(hres[2 * i], pack_bf16(accB[4 * i] * __uint_as_float(r20), accB[4 * i + 1] * __uint_as_float(r20)));
      o1[4 * i] = hadd2_bf(hres[2 * i + 1], pack_bf16(accB[4 * i + 2] * __uint_as_float(r21), accB[4 * i + 3] * __uint_as_float(r21)));
    }
    if (tid == 0) TR(1, 10);
    if (tid == 128) TR(1, 15);
  }
}

typedef CUresult (*EncFn)(CUtensorMap*, CUtensorMapDataType, cuuint32_t, void*, const cuuint64_t*, const cuuint64_t*,
                          const cuuint32_t*, const cuuint32_t*, CUtensorMapInterleave, CUtensorMapSwizzle,
                          CUtensorMapL2promotion, CUtensorMapFloatOOBfill);

extern "C" void kernel_launch(void* const* d_in, const int* in_sizes, int n_in, void* d_out, int out_size) {
  const __nv_bfloat16* x = (const __nv_bfloat16*)d_in[0];
  const __nv_bfloat16 *are = (const __nv_bfloat16*)d_in[1], *aim = (const __nv_bfloat16*)d_in[2], *bre = (const __nv_bfloat16*)d_in[3],
                      *bim = (const __nv_bfloat16*)d_in[4], *cre = (const __nv_bfloat16*)d_in[5], *cim = (const __nv_bfloat16*)d_in[6],
                      *logdt = (const __nv_bfloat16*)d_in[7], *dskip = (const __nv_bfloat16*)d_in[8];
  const __nv_bfloat16 *wg = (const __nv_bfloat16*)d_in[10], *wu = (const __nv_bfloat16*)d_in[11], *wd = (const __nv_bfloat16*)d_in[12];

  static EncFn enc = nullptr;
  if (!enc) {
    void* fn = nullptr; cudaDriverEntryPointQueryResult qr;
    cudaGetDriverEntryPoint("cuTensorMapEncodeTiled", &fn, cudaEnableDefault, &qr);
    enc = (EncFn)fn;
    cudaFuncSetAttribute(k_ffn, cudaFuncAttributeMaxDynamicSharedMemorySize, B_SMEM);
    cudaFuncSetAttribute(k_front, cudaFuncAttributeMaxDynamicSharedMemorySize, A_SMEM);
  }
  CUtensorMap mg, mu, md;
  {
    cuuint32_t es[3] = {1, 1, 1};
    cuuint64_t d1[3] = {8, 448, 224}, s1[2] = {3584, 16}; cuuint32_t b1[3] = {8, 32, 14};
    cuuint64_t d2[3] = {8, 1792, 56}, s2[2] = {896, 16}; cuuint32_t b2[3] = {8, 112, 7};
    enc(&mg, CU_TENSOR_MAP_DATA_TYPE_BFLOAT16, 3, (void*)wg, d1, s1, b1, es, CU_TENSOR_MAP_INTERLEAVE_NONE, CU_TENSOR_MAP_SWIZZLE_NONE, CU_TENSOR_MAP_L2_PROMOTION_L2_256B, CU_TENSOR_MAP_FLOAT_OOB_FILL_NONE);
    enc(&mu, CU_TENSOR_MAP_DATA_TYPE_BFLOAT16, 3, (void*)wu, d1, s1, b1, es, CU_TENSOR_MAP_INTERLEAVE_NONE, CU_TENSOR_MAP_SWIZZLE_NONE, CU_TENSOR_MAP_L2_PROMOTION_L2_256B, CU_TENSOR_MAP_FLOAT_OOB_FILL_NONE);
    enc(&md, CU_TENSOR_MAP_DATA_TYPE_BFLOAT16, 3, (void*)wd, d2, s2, b2, es, CU_TENSOR_MAP_INTERLEAVE_NONE, CU_TENSOR_MAP_SWIZZLE_NONE, CU_TENSOR_MAP_L2_PROMOTION_L2_256B, CU_TENSOR_MAP_FLOAT_OOB_FILL_NONE);
  }
  cudaStream_t st = cudaStreamPerThread;
  k_front<<<128, 512, A_SMEM, st>>>(
      mg, mu, md, x, (const uint32_t*)are, (const uint32_t*)aim, (const uint32_t*)bre, (const uint32_t*)bim, (const uint32_t*)cre, (const uint32_t*)cim,
      (const unsigned short*)logdt, (const unsigned short*)dskip, (const uint4*)wg, (const uint4*)wu);
  cudaLaunchConfig_t cfg = {};
  cfg.gridDim = dim3(128); cfg.blockDim = dim3(384); cfg.dynamicSmemBytes = B_SMEM; cfg.stream = st;
  cudaLaunchAttribute at[1];
  at[0].id = cudaLaunchAttributeProgrammaticStreamSerialization; at[0].val.programmaticStreamSerializationAllowed = 1;
  cfg.attrs = at; cfg.numAttrs = 1;
  cudaLaunchKernelEx(&cfg, k_ffn, (__nv_bfloat16*)d_out);
}
```

```cpp
#include <cuda_runtime.h>
#include <cuda_bf16.h>
#include <cuda_fp16.h>
#include <cuda.h>
#include <stdint.h>

constexpr int LSEQ = 2048, DM = 448;

__device__ uint4    g_himg[16 * 114688 / 16];
__device__ uint4    g_cimg[8 * 2 * 224];
__device__ uint32_t g_stat2[LSEQ];
__device__ uint4    g_part[128 * 3 * 896];
__device__ uint4    g_wimg[8 * 602112 / 16];
__device__ uint4    g_ux[DM * 128 * 4];
__device__ unsigned g_cnt1;

#define TR(k, i) do {} while (0)
__device__ __forceinline__ uint32_t s2u(const void* p) { return (uint32_t)__cvta_generic_to_shared(p); }
__device__ __forceinline__ void mbar_init(uint32_t b, int c) { asm volatile("mbarrier.init.shared::cta.b64 [%0], %1;" ::"r"(b), "r"(c)); }
__device__ __forceinline__ void mbar_expect(uint32_t b, int bytes) { asm volatile("mbarrier.arrive.expect_tx.shared::cta.b64 _, [%0], %1;" ::"r"(b), "r"(bytes) : "memory"); }
__device__ __forceinline__ void mbar_arrive(uint32_t b) { asm volatile("mbarrier.arrive.shared::cta.b64 _, [%0];" ::"r"(b) : "memory"); }
__device__ __forceinline__ void mbar_wait(uint32_t b, int ph) {
  asm volatile("{\n.reg .pred p;\n.reg .b32 n;\nmov.b32 n, 0;\nLW:\nmbarrier.try_wait.parity.shared::cta.b64 p, [%0], %1;\n@p bra LD;\n"
               "add.u32 n, n, 1;\nsetp.lt.u32 p, n, 4000000;\n@p bra LW;\ntrap;\nLD:\n}" ::"r"(b), "r"(ph) : "memory");
}
__device__ __forceinline__ bool mbar_test(uint32_t b, int ph) {
  uint32_t ok;
  asm volatile("{\n.reg .pred p;\nmbarrier.test_wait.parity.shared::cta.b64 p, [%1], %2;\nselp.u32 %0, 1, 0, p;\n}" : "=r"(ok) : "r"(b), "r"(ph) : "memory");
  return ok;
}
__device__ __forceinline__ void wg_fence() { asm volatile("wgmma.fence.sync.aligned;" ::: "memory"); }
__device__ __forceinline__ void wg_commit() { asm volatile("wgmma.commit_group.sync.aligned;" ::: "memory"); }
template <int N> __device__ __forceinline__ void wg_wait() { asm volatile("wgmma.wait_group.sync.aligned %0;" ::"n"(N) : "memory"); }
template <int N> __device__ __forceinline__ void reg_fence(float (&a)[N]) {
#pragma unroll
  for (int i = 0; i < N; i++) asm volatile("" : "+f"(a[i])::"memory");
}
__device__ __forceinline__ uint32_t pack_bf16(float lo, float hi) {
  uint32_t r; asm("cvt.rn.bf16x2.f32 %0, %1, %2;" : "=r"(r) : "f"(hi), "f"(lo)); return r;
}
__device__ __forceinline__ float bf_lo(uint32_t v) { return __uint_as_float(v << 16); }
__device__ __forceinline__ float bf_hi(uint32_t v) { return __uint_as_float(v & 0xFFFF0000u); }
__device__ __forceinline__ float rbf(float x) { return __bfloat162float(__float2bfloat16_rn(x)); }
__device__ __forceinline__ uint32_t hmul2_bf(uint32_t a, uint32_t b) { uint32_t r; asm("mul.rn.bf16x2 %0, %1, %2;" : "=r"(r) : "r"(a), "r"(b)); return r; }
__device__ __forceinline__ uint32_t hadd2_bf(uint32_t a, uint32_t b) { uint32_t r; asm("add.rn.bf16x2 %0, %1, %2;" : "=r"(r) : "r"(a), "r"(b)); return r; }
__device__ __forceinline__ void bulk_ld(uint32_t dst, const void* src, int bytes, uint32_t bar) {
  asm volatile("cp.async.bulk.shared::cluster.global.mbarrier::complete_tx::bytes [%0], [%1], %2, [%3];"
               ::"r"(dst), "l"(src), "r"(bytes), "r"(bar) : "memory");
}

template <int BYTES>
__device__ __forceinline__ void bulk_ld_elect(uint32_t dst, const void* src, uint32_t bar) {
  asm volatile("{\n.reg .pred p;\nelect.sync _|p, 0xffffffff;\n"
               "@p mbarrier.arrive.expect_tx.shared::cta.b64 _, [%2], %3;\n"
               "@p cp.async.bulk.shared::cluster.global.mbarrier::complete_tx::bytes [%0], [%1], %3, [%2];\n}"
               ::"r"(dst), "l"(src), "r"(bar), "n"(BYTES) : "memory");
}
template <int BYTES>
__device__ __forceinline__ void bulk_ld_mc_elect(uint32_t dst, const void* src, uint32_t bar) {
  asm volatile("{\n.reg .pred p;\nelect.sync _|p, 0xffffffff;\n"
               "@p mbarrier.arrive.expect_tx.shared::cta.b64 _, [%2], %3;\n"
               "@p cp.async.bulk.shared::cluster.global.mbarrier::complete_tx::bytes.multicast::cluster [%0], [%1], %4, [%2], %5;\n}"
               ::"r"(dst), "l"(src), "r"(bar), "n"(2 * BYTES), "n"(BYTES), "h"((uint16_t)3) : "memory");
}
template <int AOFF, uint32_t AHI, int BOFF, uint32_t BHI, int ACC>
__device__ __forceinline__ void wgmma_ss224(float (&d)[112], uint32_t alo, uint32_t blo) {
  asm volatile("{\n.reg .pred p;\n.reg .b64 ad, bd;\nsetp.ne.b32 p, %118, 0;\n"
    "mov.b64 ad, {%112, %115};\nadd.s64 ad, ad, %114;\nmov.b64 bd, {%113, %117};\nadd.s64 bd, bd, %116;\n"
    "wgmma.mma_async.sync.aligned.m64n224k16.f32.bf16.bf16 {%0,%1,%2,%3,%4,%5,%6,%7,%8,%9,%10,%11,%12,%13,%14,%15,%16,%17,%18,%19,%20,%21,%22,%23,%24,%25,%26,%27,%28,%29,%30,%31,%32,%33,%34,%35,%36,%37,%38,%39,%40,%41,%42,%43,%44,%45,%46,%47,%48,%49,%50,%51,%52,%53,%54,%55,%56,%57,%58,%59,%60,%61,%62,%63,%64,%65,%66,%67,%68,%69,%70,%71,%72,%73,%74,%75,%76,%77,%78,%79,%80,%81,%82,%83,%84,%85,%86,%87,%88,%89,%90,%91,%92,%93,%94,%95,%96,%97,%98,%99,%100,%101,%102,%103,%104,%105,%106,%107,%108,%109,%110,%111}, ad, bd, p, 1, 1, 1, 1;\n}\n"
    : "+f"(d[0]),"+f"(d[1]),"+f"(d[2]),"+f"(d[3]),"+f"(d[4]),"+f"(d[5]),"+f"(d[6]),"+f"(d[7]),"+f"(d[8]),"+f"(d[9]),"+f"(d[10]),"+f"(d[11]),"+f"(d[12]),"+f"(d[13]),"+f"(d[14]),"+f"(d[15]),"+f"(d[16]),"+f"(d[17]),"+f"(d[18]),"+f"(d[19]),"+f"(d[20]),"+f"(d[21]),"+f"(d[22]),"+f"(d[23]),"+f"(d[24]),"+f"(d[25]),"+f"(d[26]),"+f"(d[27]),"+f"(d[28]),"+f"(d[29]),"+f"(d[30]),"+f"(d[31]),"+f"(d[32]),"+f"(d[33]),"+f"(d[34]),"+f"(d[35]),"+f"(d[36]),"+f"(d[37]),"+f"(d[38]),"+f"(d[39]),"+f"(d[40]),"+f"(d[41]),"+f"(d[42]),"+f"(d[43]),"+f"(d[44]),"+f"(d[45]),"+f"(d[46]),"+f"(d[47]),"+f"(d[48]),"+f"(d[49]),"+f"(d[50]),"+f"(d[51]),"+f"(d[52]),"+f"(d[53]),"+f"(d[54]),"+f"(d[55]),"+f"(d[56]),"+f"(d[57]),"+f"(d[58]),"+f"(d[59]),"+f"(d[60]),"+f"(d[61]),"+f"(d[62]),"+f"(d[63]),"+f"(d[64]),"+f"(d[65]),"+f"(d[66]),"+f"(d[67]),"+f"(d[68]),"+f"(d[69]),"+f"(d[70]),"+f"(d[71]),"+f"(d[72]),"+f"(d[73]),"+f"(d[74]),"+f"(d[75]),"+f"(d[76]),"+f"(d[77]),"+f"(d[78]),"+f"(d[79]),"+f"(d[80]),"+f"(d[81]),"+f"(d[82]),"+f"(d[83]),"+f"(d[84]),"+f"(d[85]),"+f"(d[86]),"+f"(d[87]),"+f"(d[88]),"+f"(d[89]),"+f"(d[90]),"+f"(d[91]),"+f"(d[92]),"+f"(d[93]),"+f"(d[94]),"+f"(d[95]),"+f"(d[96]),"+f"(d[97]),"+f"(d[98]),"+f"(d[99]),"+f"(d[100]),"+f"(d[101]),"+f"(d[102]),"+f"(d[103]),"+f"(d[104]),"+f"(d[105]),"+f"(d[106]),"+f"(d[107]),"+f"(d[108]),"+f"(d[109]),"+f"(d[110]),"+f"(d[111])
    : "r"(alo), "r"(blo), "n"(AOFF), "n"(AHI), "n"(BOFF), "n"(BHI), "n"(ACC));
}
template <int AOFF, uint32_t AHI, int BOFF, uint32_t BHI, int ACC>
__device__ __forceinline__ void wgmma_ss232(float (&d)[116], uint32_t alo, uint32_t blo) {
  asm volatile("{\n.reg .pred p;\n.reg .b64 ad, bd;\nsetp.ne.b32 p, %122, 0;\n"
    "mov.b64 ad, {%116, %119};\nadd.s64 ad, ad, %118;\nmov.b64 bd, {%117, %121};\nadd.s64 bd, bd, %120;\n"
    "wgmma.mma_async.sync.aligned.m64n232k16.f32.bf16.bf16 {%0,%1,%2,%3,%4,%5,%6,%7,%8,%9,%10,%11,%12,%13,%14,%15,%16,%17,%18,%19,%20,%21,%22,%23,%24,%25,%26,%27,%28,%29,%30,%31,%32,%33,%34,%35,%36,%37,%38,%39,%40,%41,%42,%43,%44,%45,%46,%47,%48,%49,%50,%51,%52,%53,%54,%55,%56,%57,%58,%59,%60,%61,%62,%63,%64,%65,%66,%67,%68,%69,%70,%71,%72,%73,%74,%75,%76,%77,%78,%79,%80,%81,%82,%83,%84,%85,%86,%87,%88,%89,%90,%91,%92,%93,%94,%95,%96,%97,%98,%99,%100,%101,%102,%103,%104,%105,%106,%107,%108,%109,%110,%111,%112,%113,%114,%115}, ad, bd, p, 1, 1, 1, 1;\n}\n"
    : "+f"(d[0]),"+f"(d[1]),"+f"(d[2]),"+f"(d[3]),"+f"(d[4]),"+f"(d[5]),"+f"(d[6]),"+f"(d[7]),"+f"(d[8]),"+f"(d[9]),"+f"(d[10]),"+f"(d[11]),"+f"(d[12]),"+f"(d[13]),"+f"(d[14]),"+f"(d[15]),"+f"(d[16]),"+f"(d[17]),"+f"(d[18]),"+f"(d[19]),"+f"(d[20]),"+f"(d[21]),"+f"(d[22]),"+f"(d[23]),"+f"(d[24]),"+f"(d[25]),"+f"(d[26]),"+f"(d[27]),"+f"(d[28]),"+f"(d[29]),"+f"(d[30]),"+f"(d[31]),"+f"(d[32]),"+f"(d[33]),"+f"(d[34]),"+f"(d[35]),"+f"(d[36]),"+f"(d[37]),"+f"(d[38]),"+f"(d[39]),"+f"(d[40]),"+f"(d[41]),"+f"(d[42]),"+f"(d[43]),"+f"(d[44]),"+f"(d[45]),"+f"(d[46]),"+f"(d[47]),"+f"(d[48]),"+f"(d[49]),"+f"(d[50]),"+f"(d[51]),"+f"(d[52]),"+f"(d[53]),"+f"(d[54]),"+f"(d[55]),"+f"(d[56]),"+f"(d[57]),"+f"(d[58]),"+f"(d[59]),"+f"(d[60]),"+f"(d[61]),"+f"(d[62]),"+f"(d[63]),"+f"(d[64]),"+f"(d[65]),"+f"(d[66]),"+f"(d[67]),"+f"(d[68]),"+f"(d[69]),"+f"(d[70]),"+f"(d[71]),"+f"(d[72]),"+f"(d[73]),"+f"(d[74]),"+f"(d[75]),"+f"(d[76]),"+f"(d[77]),"+f"(d[78]),"+f"(d[79]),"+f"(d[80]),"+f"(d[81]),"+f"(d[82]),"+f"(d[83]),"+f"(d[84]),"+f"(d[85]),"+f"(d[86]),"+f"(d[87]),"+f"(d[88]),"+f"(d[89]),"+f"(d[90]),"+f"(d[91]),"+f"(d[92]),"+f"(d[93]),"+f"(d[94]),"+f"(d[95]),"+f"(d[96]),"+f"(d[97]),"+f"(d[98]),"+f"(d[99]),"+f"(d[100]),"+f"(d[101]),"+f"(d[102]),"+f"(d[103]),"+f"(d[104]),"+f"(d[105]),"+f"(d[106]),"+f"(d[107]),"+f"(d[108]),"+f"(d[109]),"+f"(d[110]),"+f"(d[111]),"+f"(d[112]),"+f"(d[113]),"+f"(d[114]),"+f"(d[115])
    : "r"(alo), "r"(blo), "n"(AOFF), "n"(AHI), "n"(BOFF), "n"(BHI), "n"(ACC));
}
template <int OFF, uint32_t BHI, int ACC>
__device__ __forceinline__ void wgmma_rs224(float (&d)[112], uint32_t a0, uint32_t a1, uint32_t a2, uint32_t a3, uint32_t blo) {
  asm volatile("{\n.reg .pred p;\n.reg .b64 bd;\nsetp.ne.b32 p, %119, 0;\nmov.b64 bd, {%116, %118};\nadd.s64 bd, bd, %117;\n"
    "wgmma.mma_async.sync.aligned.m64n224k16.f32.bf16.bf16 {%0,%1,%2,%3,%4,%5,%6,%7,%8,%9,%10,%11,%12,%13,%14,%15,%16,%17,%18,%19,%20,%21,%22,%23,%24,%25,%26,%27,%28,%29,%30,%31,%32,%33,%34,%35,%36,%37,%38,%39,%40,%41,%42,%43,%44,%45,%46,%47,%48,%49,%50,%51,%52,%53,%54,%55,%56,%57,%58,%59,%60,%61,%62,%63,%64,%65,%66,%67,%68,%69,%70,%71,%72,%73,%74,%75,%76,%77,%78,%79,%80,%81,%82,%83,%84,%85,%86,%87,%88,%89,%90,%91,%92,%93,%94,%95,%96,%97,%98,%99,%100,%101,%102,%103,%104,%105,%106,%107,%108,%109,%110,%111}, {%112,%113,%114,%115}, bd, p, 1, 1, 1;\n}\n"
    : "+f"(d[0]),"+f"(d[1]),"+f"(d[2]),"+f"(d[3]),"+f"(d[4]),"+f"(d[5]),"+f"(d[6]),"+f"(d[7]),"+f"(d[8]),"+f"(d[9]),"+f"(d[10]),"+f"(d[11]),"+f"(d[12]),"+f"(d[13]),"+f"(d[14]),"+f"(d[15]),"+f"(d[16]),"+f"(d[17]),"+f"(d[18]),"+f"(d[19]),"+f"(d[20]),"+f"(d[21]),"+f"(d[22]),"+f"(d[23]),"+f"(d[24]),"+f"(d[25]),"+f"(d[26]),"+f"(d[27]),"+f"(d[28]),"+f"(d[29]),"+f"(d[30]),"+f"(d[31]),"+f"(d[32]),"+f"(d[33]),"+f"(d[34]),"+f"(d[35]),"+f"(d[36]),"+f"(d[37]),"+f"(d[38]),"+f"(d[39]),"+f"(d[40]),"+f"(d[41]),"+f"(d[42]),"+f"(d[43]),"+f"(d[44]),"+f"(d[45]),"+f"(d[46]),"+f"(d[47]),"+f"(d[48]),"+f"(d[49]),"+f"(d[50]),"+f"(d[51]),"+f"(d[52]),"+f"(d[53]),"+f"(d[54]),"+f"(d[55]),"+f"(d[56]),"+f"(d[57]),"+f"(d[58]),"+f"(d[59]),"+f"(d[60]),"+f"(d[61]),"+f"(d[62]),"+f"(d[63]),"+f"(d[64]),"+f"(d[65]),"+f"(d[66]),"+f"(d[67]),"+f"(d[68]),"+f"(d[69]),"+f"(d[70]),"+f"(d[71]),"+f"(d[72]),"+f"(d[73]),"+f"(d[74]),"+f"(d[75]),"+f"(d[76]),"+f"(d[77]),"+f"(d[78]),"+f"(d[79]),"+f"(d[80]),"+f"(d[81]),"+f"(d[82]),"+f"(d[83]),"+f"(d[84]),"+f"(d[85]),"+f"(d[86]),"+f"(d[87]),"+f"(d[88]),"+f"(d[89]),"+f"(d[90]),"+f"(d[91]),"+f"(d[92]),"+f"(d[93]),"+f"(d[94]),"+f"(d[95]),"+f"(d[96]),"+f"(d[97]),"+f"(d[98]),"+f"(d[99]),"+f"(d[100]),"+f"(d[101]),"+f"(d[102]),"+f"(d[103]),"+f"(d[104]),"+f"(d[105]),"+f"(d[106]),"+f"(d[107]),"+f"(d[108]),"+f"(d[109]),"+f"(d[110]),"+f"(d[111])
    : "r"(a0), "r"(a1), "r"(a2), "r"(a3), "r"(blo), "n"(OFF), "n"(BHI), "n"(ACC));
}
template <int OFF, uint32_t BHI, int ACC>
__device__ __forceinline__ void wgmma_rs56(float (&d)[28], uint32_t a0, uint32_t a1, uint32_t a2, uint32_t a3, uint32_t blo) {
  asm volatile("{\n.reg .pred p;\n.reg .b64 bd;\nsetp.ne.b32 p, %35, 0;\nmov.b64 bd, {%32, %34};\nadd.s64 bd, bd, %33;\n"
    "wgmma.mma_async.sync.aligned.m64n56k16.f32.bf16.bf16 {%0,%1,%2,%3,%4,%5,%6,%7,%8,%9,%10,%11,%12,%13,%14,%15,%16,%17,%18,%19,%20,%21,%22,%23,%24,%25,%26,%27}, {%28,%29,%30,%31}, bd, p, 1, 1, 1;\n}\n"
    : "+f"(d[0]),"+f"(d[1]),"+f"(d[2]),"+f"(d[3]),"+f"(d[4]),"+f"(d[5]),"+f"(d[6]),"+f"(d[7]),"+f"(d[8]),"+f"(d[9]),"+f"(d[10]),"+f"(d[11]),"+f"(d[12]),"+f"(d[13]),"+f"(d[14]),"+f"(d[15]),"+f"(d[16]),"+f"(d[17]),"+f"(d[18]),"+f"(d[19]),"+f"(d[20]),"+f"(d[21]),"+f"(d[22]),"+f"(d[23]),"+f"(d[24]),"+f"(d[25]),"+f"(d[26]),"+f"(d[27])
    : "r"(a0), "r"(a1), "r"(a2), "r"(a3), "r"(blo), "n"(OFF), "n"(BHI), "n"(ACC));
}

__device__ __forceinline__ void st128(uint4* p, uint32_t a, uint32_t b, uint32_t c, uint32_t d) {
  asm volatile("{\n.reg .b128 v;\n.reg .b64 lo, hi;\nmov.b64 lo, {%1, %2};\nmov.b64 hi, {%3, %4};\nmov.b128 v, {lo, hi};\n"
               "st.relaxed.gpu.global.b128 [%0], v;\n}" ::"l"(p), "r"(a), "r"(b), "r"(c), "r"(d) : "memory");
}
__device__ __forceinline__ void ld128(const uint4* p, uint32_t* r) {
  asm volatile("{\n.reg .b128 v;\n.reg .b64 lo, hi;\nld.relaxed.gpu.global.b128 v, [%4];\nmov.b128 {lo, hi}, v;\n"
               "mov.b64 {%0, %1}, lo;\nmov.b64 {%2, %3}, hi;\n}" : "=r"(r[0]), "=r"(r[1]), "=r"(r[2]), "=r"(r[3]) : "l"(p) : "memory");
}

template <int OFF, uint32_t BHI, int ACC>
__device__ __forceinline__ void wgmma_rs32(float (&d)[16], uint32_t a0, uint32_t a1, uint32_t a2, uint32_t a3, uint32_t blo) {
  asm volatile("{\n.reg .pred p;\n.reg .b64 bd;\nsetp.ne.b32 p, %23, 0;\nmov.b64 bd, {%20, %22};\nadd.s64 bd, bd, %21;\n"
    "wgmma.mma_async.sync.aligned.m64n32k16.f32.bf16.bf16 {%0,%1,%2,%3,%4,%5,%6,%7,%8,%9,%10,%11,%12,%13,%14,%15}, {%16,%17,%18,%19}, bd, p, 1, 1, 0;\n}\n"
    : "+f"(d[0]),"+f"(d[1]),"+f"(d[2]),"+f"(d[3]),"+f"(d[4]),"+f"(d[5]),"+f"(d[6]),"+f"(d[7]),"+f"(d[8]),"+f"(d[9]),"+f"(d[10]),"+f"(d[11]),"+f"(d[12]),"+f"(d[13]),"+f"(d[14]),"+f"(d[15])
    : "r"(a0), "r"(a1), "r"(a2), "r"(a3), "r"(blo), "n"(OFF), "n"(BHI), "n"(ACC));
}
template <int OFF, uint32_t BHI, int ACC>
__device__ __forceinline__ void wgmma_rs24(float (&d)[12], uint32_t a0, uint32_t a1, uint32_t a2, uint32_t a3, uint32_t blo) {
  asm volatile("{\n.reg .pred p;\n.reg .b64 bd;\nsetp.ne.b32 p, %19, 0;\nmov.b64 bd, {%16, %18};\nadd.s64 bd, bd, %17;\n"
    "wgmma.mma_async.sync.aligned.m64n24k16.f32.bf16.bf16 {%0,%1,%2,%3,%4,%5,%6,%7,%8,%9,%10,%11}, {%12,%13,%14,%15}, bd, p, 1, 1, 1;\n}\n"
    : "+f"(d[0]),"+f"(d[1]),"+f"(d[2]),"+f"(d[3]),"+f"(d[4]),"+f"(d[5]),"+f"(d[6]),"+f"(d[7]),"+f"(d[8]),"+f"(d[9]),"+f"(d[10]),"+f"(d[11])
    : "r"(a0), "r"(a1), "r"(a2), "r"(a3), "r"(blo), "n"(OFF), "n"(BHI), "n"(ACC));
}
template <int OFF, uint32_t BHI, int ACC>
__device__ __forceinline__ void wgmma_rs16(float (&d)[8], uint32_t a0, uint32_t a1, uint32_t a2, uint32_t a3, uint32_t blo) {
  asm volatile("{\n.reg .pred p;\n.reg .b64 bd;\nsetp.ne.b32 p, %15, 0;\nmov.b64 bd, {%12, %14};\nadd.s64 bd, bd, %13;\n"
    "wgmma.mma_async.sync.aligned.m64n16k16.f32.bf16.bf16 {%0,%1,%2,%3,%4,%5,%6,%7}, {%8,%9,%10,%11}, bd, p, 1, 1, 1;\n}\n"
    : "+f"(d[0]),"+f"(d[1]),"+f"(d[2]),"+f"(d[3]),"+f"(d[4]),"+f"(d[5]),"+f"(d[6]),"+f"(d[7])
    : "r"(a0), "r"(a1), "r"(a2), "r"(a3), "r"(blo), "n"(OFF), "n"(BHI), "n"(ACC));
}

constexpr int A_R1 = 0;
constexpr int A_R2A = A_R1 + 2624, A_R2B = A_R2A + 768, A_R3A = A_R2B + 768, A_R3B = A_R3A + 528;
constexpr int A_K1024 = A_R3B + 528;
constexpr int A_W5 = A_K1024 + 16;
constexpr int A_W3 = A_W5 + 4096;
constexpr int A_W9 = A_W3 + 4112;
constexpr int A_W7 = A_W9 + 2080;
constexpr int A_V  = A_W7 + 2080 + 32;
constexpr int A_SCL = A_V + 2048;
constexpr int A_UB = A_SCL + 16;
constexpr int A_STG = A_UB + 5248;
constexpr int A_Y2 = A_STG, A_Y3 = A_Y2 + 6528, A_YB = A_Y3 + 4352;
constexpr int A_REC = A_STG + 4 * 4352;
constexpr int A_CH = A_REC + 8192;
constexpr int A_BAR = 4 * A_CH, A_WST = (A_BAR + 128 + 127) / 128 * 128;
static_assert(A_W5 % 16 == 0 && A_UB % 16 == 0 && A_CH % 16 == 0 && A_YB + 4096 <= A_REC, "layout");

struct cf { float x, y; };
__device__ __forceinline__ cf cmul(cf a, cf b) { cf r; r.x = fmaf(a.x, b.x, -a.y * b.y); r.y = fmaf(a.x, b.y, a.y * b.x); return r; }
__device__ __forceinline__ cf cexp_l(float lr, float li, float l) {
  float mag; asm("ex2.approx.ftz.f32 %0, %1;" : "=f"(mag) : "f"((lr * l) * 1.4426950408889634f));
  const float th = li * l;
  const float k = (fmaf(th, 0.15915494f, 12582912.f)) - 12582912.f;
  float ph = fmaf(th, 0.15915494f, -k);
  ph = fmaf(th, 6.4206383e-9f, ph) * 6.2831853f;
  cf r; r.x = mag * __cosf(ph); r.y = mag * __sinf(ph); return r;
}
__device__ __forceinline__ void sts16(uint32_t a, uint32_t v) { asm volatile("st.shared.u16 [%0], %1;" ::"r"(a), "h"((uint16_t)v) : "memory"); }
__device__ __forceinline__ void sts32(uint32_t a, uint32_t v) { asm volatile("st.shared.u32 [%0], %1;" ::"r"(a), "r"(v) : "memory"); }
__device__ __forceinline__ void sts64(uint32_t a, uint32_t v0, uint32_t v1) { asm volatile("st.shared.v2.u32 [%0], {%1, %2};" ::"r"(a), "r"(v0), "r"(v1) : "memory"); }
__device__ __forceinline__ void sts128(uint32_t a, uint32_t v0, uint32_t v1, uint32_t v2, uint32_t v3) {
  asm volatile("st.shared.v4.u32 [%0], {%1, %2, %3, %4};" ::"r"(a), "r"(v0), "r"(v1), "r"(v2), "r"(v3) : "memory");
}
__device__ __forceinline__ uint32_t lds32(uint32_t a) { uint32_t v; asm volatile("ld.shared.u32 %0, [%1];" : "=r"(v) : "r"(a) : "memory"); return v; }
__device__ __forceinline__ uint4 lds128(uint32_t a) {
  uint4 v; asm volatile("ld.shared.v4.u32 {%0, %1, %2, %3}, [%4];" : "=r"(v.x), "=r"(v.y), "=r"(v.z), "=r"(v.w) : "r"(a) : "memory"); return v;
}
__device__ __forceinline__ void ldsm4(uint32_t* r, uint32_t a) {
  asm volatile("ldmatrix.sync.aligned.m8n8.x4.shared.b16 {%0,%1,%2,%3}, [%4];" : "=r"(r[0]), "=r"(r[1]), "=r"(r[2]), "=r"(r[3]) : "r"(a) : "memory");
}
__device__ __forceinline__ void mma16816(float* d, uint32_t a0, uint32_t a1, uint32_t a2, uint32_t a3, uint32_t b0, uint32_t b1) {
  asm volatile("mma.sync.aligned.m16n8k16.row.col.f32.f16.f16.f32 {%0,%1,%2,%3}, {%4,%5,%6,%7}, {%8,%9}, {%0,%1,%2,%3};"
               : "+f"(d[0]), "+f"(d[1]), "+f"(d[2]), "+f"(d[3]) : "r"(a0), "r"(a1), "r"(a2), "r"(a3), "r"(b0), "r"(b1));
}
__device__ __forceinline__ uint32_t pack_h(float lo, float hi) { uint32_t r; asm("cvt.rn.f16x2.f32 %0, %1, %2;" : "=r"(r) : "f"(hi), "f"(lo)); return r; }
__device__ __forceinline__ uint32_t pack_h(cf v) { return pack_h(v.x, v.y); }
__device__ __forceinline__ uint32_t hcmul(uint32_t x, uint32_t r0, uint32_t r1) {
  const __half2 hx = *(__half2*)&x;
  const __half2 y = __hfma2(__high2half2(hx), *(__half2*)&r1, __hmul2(__low2half2(hx), *(__half2*)&r0));
  return *(const uint32_t*)&y;
}
__device__ __forceinline__ float ln_rstd(float var) {
  float sd, rs;
  asm("sqrt.approx.f32 %0, %1;" : "=f"(sd) : "f"(rbf(rbf(var) + 1e-5f)));
  asm("rcp.approx.f32 %0, %1;" : "=f"(rs) : "f"(rbf(sd)));
  return rs;
}
__device__ __forceinline__ uint32_t hsub2_bf(uint32_t a, uint32_t b) { uint32_t r; asm("sub.rn.bf16x2 %0, %1, %2;" : "=r"(r) : "r"(a), "r"(b)); return r; }
__device__ __forceinline__ void bar_sync(int id, int n) { asm volatile("bar.sync %0, %1;" ::"r"(id), "r"(n) : "memory"); }

template <int S> struct F1B { static constexpr int c = S / 4 + ((S & 3) == 3 ? 0 : 0), cc = (16 * S) / 64, ks = (64 * cc - (16 * S - 48)) / 16, off = (A_UB + 2 * ks * 656 + (9 - cc) * 16) / 16; };

template <int NS>
__device__ __forceinline__ void load_quads(uint32_t* q, uint32_t addr) {
#pragma unroll
  for (int i = 0; i < NS; i++) {
    q[4 * i] = lds32(addr + i * 64); q[4 * i + 1] = lds32(addr + i * 64 + 32);
    q[4 * i + 2] = i ? q[4 * i - 3] : lds32(addr - 32);
    q[4 * i + 3] = q[4 * i];
  }
#pragma unroll
  for (int i = 0; i < 4 * NS; i++) asm volatile("" : "+r"(q[i]));
}
template <int S0, int NS>
__device__ __forceinline__ void f1_steps(float (&acc)[16], const uint32_t* a, uint32_t blo) {
  if constexpr (NS > 0) {
    wgmma_rs32<F1B<S0>::off, 8, S0 != 0>(acc, a[0], a[1], a[2], a[3], blo);
    f1_steps<S0 + 1, NS - 1>(acc, a + 4, blo);
  }
}
template <int S0, int NS, int BASE, int FIRST>
__device__ __forceinline__ void s2_steps(float (&acc)[12], const uint32_t* a, uint32_t blo) {
  if constexpr (NS > 0) {
    wgmma_rs24<BASE / 16 + (112 - 16 * S0), 64, !(FIRST && S0 == 0)>(acc, a[0], a[1], a[2], a[3], blo);
    s2_steps<S0 + 1, NS - 1, BASE, FIRST>(acc, a + 4, blo);
  }
}
template <int S0, int NS, int BASE, int FIRST>
__device__ __forceinline__ void s3_steps(float (&acc)[8], const uint32_t* a, uint32_t blo) {
  if constexpr (NS > 0) {
    wgmma_rs16<BASE / 16 + (48 - 16 * S0), 65, !(FIRST && S0 == 0)>(acc, a[0], a[1], a[2], a[3], blo);
    s3_steps<S0 + 1, NS - 1, BASE, FIRST>(acc, a + 4, blo);
  }
}

__device__ __forceinline__ void tma3d(uint32_t dst, const CUtensorMap* m, int c1, int c2, uint32_t bar) {
  asm volatile("cp.async.bulk.tensor.3d.shared::cluster.global.mbarrier::complete_tx::bytes [%0], [%1, {0, %3, %4}], [%2];"
               ::"r"(dst), "l"(m), "r"(bar), "r"(c1), "r"(c2) : "memory");
}
__device__ __forceinline__ void bulk_st(void* dst, uint32_t src, int bytes) {
  asm volatile("cp.async.bulk.global.shared::cta.bulk_group [%0], [%1], %2;" ::"l"(dst), "r"(src), "r"(bytes) : "memory");
}

__device__ __forceinline__ void phase_a(
        unsigned char* sm, const uint32_t bar_rec, const uint32_t ep_addr, const CUtensorMap* mg, const CUtensorMap* mu, const CUtensorMap* md,
        const __nv_bfloat16* __restrict__ x, const uint32_t* __restrict__ are, const uint32_t* __restrict__ aim,
        const uint32_t* __restrict__ bre, const uint32_t* __restrict__ bim, const uint32_t* __restrict__ cre,
        const uint32_t* __restrict__ cim, const unsigned short* __restrict__ logdt, const unsigned short* __restrict__ dskip,
        const uint4* __restrict__ wgate, const uint4* __restrict__ wup, const uint4* __restrict__ wdown) {
  const uint32_t sb = s2u(sm), bar_w = bar_rec + 16;
  const int tid = threadIdx.x, warp = __shfl_sync(~0u, tid >> 5, 0), wg = warp >> 2, lane = tid & 31, wq = warp & 3, t128 = tid & 127;
  const int blk = blockIdx.x;
  const bool conv = (blk & 7) != 7;
  const int cblk = blk - (blk >> 3);

  uint2 xr[4];
  {
    const uint2* p = (const uint2*)(x + (size_t)(blk * 16 + warp) * DM);
    xr[0] = __ldg(p + lane); xr[1] = __ldg(p + 32 + lane); xr[2] = __ldg(p + 64 + lane);
    xr[3] = lane < 16 ? __ldg(p + 96 + lane) : make_uint2(0, 0);
  }
  const int ch = conv ? cblk * 4 + wg : 0;
  const uint32_t cb = sb + wg * A_CH;
  uint32_t prm[6];
  {
    const int i = ch * 128 + t128;
    prm[0] = __ldg(are + i); prm[1] = __ldg(aim + i); prm[2] = __ldg(bre + i); prm[3] = __ldg(bim + i); prm[4] = __ldg(cre + i); prm[5] = __ldg(cim + i);
  }
  const uint32_t ldt = __ldg(logdt + ch);
  uint32_t cnt0 = 0;
  if (tid == 0) cnt0 = __ldcg(&g_cnt1);
  const int g = lane >> 2, t = lane & 3;
  if (conv) {
#pragma unroll
    for (int i = 0; i < 4; i++) if (i < 3 || t128 < (A_W5 + 1024) / 16 - 384) sts128(cb + (i * 128 + t128) * 16, 0, 0, 0, 0);
    if (t128 < 64) sts128(cb + A_W3 + t128 * 16, 0, 0, 0, 0);
    if (t128 < 72) sts128(cb + A_UB + (t128 / 9) * 656 + (t128 % 9) * 16, 0, 0, 0, 0);
  }
  {
    float s = 0.f, q = 0.f;
#pragma unroll
    for (int i = 0; i < 4; i++) {
      const float a = bf_lo(xr[i].x), b = bf_hi(xr[i].x), c = bf_lo(xr[i].y), d = bf_hi(xr[i].y);
      s += (a + b) + (c + d);
      q = fmaf(a, a, q); q = fmaf(b, b, q); q = fmaf(c, c, q); q = fmaf(d, d, q);
    }
#pragma unroll
    for (int o = 16; o; o >>= 1) { s += __shfl_xor_sync(~0u, s, o); q += __shfl_xor_sync(~0u, q, o); }
    const float mean = s * (1.f / DM);
    const float var = fmaxf(fmaf(-mean, mean, q * (1.f / DM)), 0.f);
    const float rs = ln_rstd(var);
    const uint32_t mm = pack_bf16(mean, mean);
    const uint32_t tu = sb + A_REC + (warp >> 3) * A_CH + (warp & 7) * 912 + lane * 8, tx = tu + 2 * A_CH;
#pragma unroll
    for (int i = 0; i < 4; i++) {
      if (i < 3 || lane < 16) {
        const uint32_t d0 = hsub2_bf(xr[i].x, mm), d1 = hsub2_bf(xr[i].y, mm);
        sts64(tu + i * 256, pack_bf16(bf_lo(d0) * rs, bf_hi(d0) * rs), pack_bf16(bf_lo(d1) * rs, bf_hi(d1) * rs));
        sts64(tx + i * 256, xr[i].x, xr[i].y);
      }
    }
  }
  if (tid == 0) sts32(ep_addr, (cnt0 >> 7) + 1u);
  if (tid == 480) {
    asm volatile("cp.async.bulk.prefetch.L2.global [%0], 12544;" ::"l"(wgate + blk * 784) : "memory");
    asm volatile("cp.async.bulk.prefetch.L2.global [%0], 12544;" ::"l"(wup + blk * 784) : "memory");
    asm volatile("cp.async.bulk.prefetch.L2.global [%0], 12544;" ::"l"(wdown + blk * 784) : "memory");
  }
  if (tid == 320) TR(0, 1);
  auto publish_rows = [&]() {
    bar_sync(5, 512);
    uint4* dst = g_ux + ((size_t)(warp * 8 + (lane >> 2)) * 128 + blk) * 4 + ((lane ^ (blk >> 1)) & 3);
#pragma unroll
    for (int i = 0; i < 4; i++) {
      if (i < 3 || warp < 8) {
        uint32_t r[4];
        asm volatile("ldmatrix.sync.aligned.m8n8.x4.trans.shared.b16 {%0,%1,%2,%3}, [%4];" : "=r"(r[0]), "=r"(r[1]), "=r"(r[2]), "=r"(r[3])
                     : "r"(sb + A_REC + (lane >> 3) * A_CH + (lane & 7) * 912 + (warp + 16 * i) * 16) : "memory");
        dst[i * 65536] = make_uint4(r[0], r[1], r[2], r[3]);
      }
    }
    if (warp != 0) asm volatile("bar.arrive 6, 512;" ::: "memory");
  };
  auto release_rows = [&]() {
    if (warp == 0) {
      bar_sync(6, 512);
      if (lane == 0) { asm volatile("red.release.gpu.global.add.u32 [%0], 1;" ::"l"(&g_cnt1) : "memory"); TR(0, 8); }
      __syncwarp();
    }
  };

  publish_rows();
  release_rows();
  if (!conv) {
    const int a = blk >> 3, mat = a >> 3, j = a & 7;
    bar_sync(7, 512);
    if (warp == 15) {
      if (lane == 0) {
        for (int c = 0; c < 8; c++) { mbar_expect(bar_w + 8 * c, 12544); tma3d(sb + (c >> 1) * 50560 + (c & 1) * 12544, md, a * 112, c * 7, bar_w + 8 * c); }
        for (int c = 0; c < 8; c++) {
          mbar_wait(bar_w + 8 * c, 0);
          bulk_st(g_wimg + (size_t)(a >> 1) * 37632 + 25088 + (c * 2 + (a & 1)) * 784, sb + (c >> 1) * 50560 + (c & 1) * 12544, 12544);
        }
        asm volatile("cp.async.bulk.commit_group;" ::: "memory");
        asm volatile("cp.async.bulk.wait_group 0;" ::: "memory");
        TR(0, 10);
      }
      return;
    }
    float s[8];
#pragma unroll
    for (int k = 0; k < 8; k++) s[k] = 0.f;
    if (lane < 28 && warp < 14) {
      const uint4* src = (mat ? wup : wgate) + j * 28 + lane + (size_t)warp * 224;
#pragma unroll
      for (int hb = 0; hb < 2; hb++) {
        uint4 v[16];
#pragma unroll
        for (int r = 0; r < 16; r++) v[r] = __ldg(src + (size_t)(hb * 16 + r) * 14 * 224);
#pragma unroll
        for (int r = 0; r < 16; r++) {
          s[0] += bf_lo(v[r].x); s[1] += bf_hi(v[r].x); s[2] += bf_lo(v[r].y); s[3] += bf_hi(v[r].y);
          s[4] += bf_lo(v[r].z); s[5] += bf_hi(v[r].z); s[6] += bf_lo(v[r].w); s[7] += bf_hi(v[r].w);
        }
      }
      float4* red = (float4*)(sm + 25088 + warp * 896 + lane * 32);
      red[0] = make_float4(s[0], s[1], s[2], s[3]); red[1] = make_float4(s[4], s[5], s[6], s[7]);
    }
    bar_sync(5, 480);
    if (tid < 224) {
      float cs = 0.f;
#pragma unroll
      for (int w = 0; w < 14; w++) cs += *(const float*)(sm + 25088 + w * 896 + tid * 4);
      const float hi = rbf(cs), mid = rbf(cs - hi), lo = rbf(cs - hi - mid);
      const int q = tid / 112, n = tid % 112 + 112 * mat;
      __nv_bfloat16* dst = (__nv_bfloat16*)(g_cimg + (j * 2 + q) * 224 + (n >> 3) * 8) + (n & 7);
      dst[0] = __float2bfloat16_rn(hi); dst[8] = __float2bfloat16_rn(mid); dst[16] = __float2bfloat16_rn(lo);
#pragma unroll
      for (int k = 3; k < 8; k++) dst[8 * k] = __float2bfloat16_rn(0.f);
    }
    if (tid == 0) TR(0, 11);
    return;
  }

  const int wr = (wq + wg) & 3;
  const int bk = wr * 32 + lane;
  {
    const uint32_t stg = cb + A_STG + wq * 4352, sw = stg + lane * 8;
    const float dt = rbf(expf(__uint_as_float(ldt << 16)));
    float lr[2], li[2];
    cf bq[2], b0[2], b4[2];
    uint32_t bf[48], cv = 0;
#pragma unroll
    for (int m = 0; m < 2; m++) {
      lr[m] = dt * (m ? bf_hi(prm[0]) : bf_lo(prm[0]));
      li[m] = dt * (m ? bf_hi(prm[1]) : bf_lo(prm[1]));
    }
    {
      cf b[2], z[2];
#pragma unroll
      for (int m = 0; m < 2; m++) {
        cf db, c;
        db.x = dt * (m ? bf_hi(prm[2]) : bf_lo(prm[2])); db.y = -dt * (m ? bf_hi(prm[3]) : bf_lo(prm[3]));
        c.x = m ? bf_hi(prm[4]) : bf_lo(prm[4]); c.y = -(m ? bf_hi(prm[5]) : bf_lo(prm[5]));
        b[m] = cmul(c, db);
        z[m] = cexp_l(lr[m], -li[m], 1.f);
        bq[m] = cexp_l(lr[m], -li[m], 256.f);
      }
      {
        const float mx = fmaxf(fmaxf(fabsf(b[0].x), fabsf(b[0].y)), fmaxf(fabsf(b[1].x), fabsf(b[1].y)));
        const uint32_t e = max(__reduce_max_sync(~0u, __float_as_uint(mx)) >> 23, 14u);
        const float sc = __uint_as_float((267u - e) << 23);
        b[0].x *= sc; b[0].y *= sc; b[1].x *= sc; b[1].y *= sc;
        if (lane == 0) sts32(cb + A_SCL + wq * 4, (e - 13u) << 23);
      }
#pragma unroll
      for (int i = 0; i < 8; i++) {
        sts64(sw + i * 272, pack_h(b[0]), pack_h(b[1]));
        if (!(i & 1)) {
          cf e0 = cmul(b[0], bq[0]), e1 = cmul(b[1], bq[1]);
          sts64(sw + (8 + i / 2) * 272, pack_h(e0), pack_h(e1));
          if (i == 0) { b0[0] = e0; b0[1] = e1; }
          if (i == 4) { b4[0] = e0; b4[1] = e1; }
        }
        if (i < 7) { b[0] = cmul(b[0], z[0]); b[1] = cmul(b[1], z[1]); }
      }
#pragma unroll
      for (int i = 0; i < 7; i++) {
        b0[0] = cmul(b0[0], bq[0]); b0[1] = cmul(b0[1], bq[1]);
        sts64(sw + (i < 2 ? 12 + 2 * i : i - 2) * 272, pack_h(b0[0]), pack_h(b0[1]));
        if (i < 2) {
          b4[0] = cmul(b4[0], bq[0]); b4[1] = cmul(b4[1], bq[1]);
          sts64(sw + (13 + 2 * i) * 272, pack_h(b4[0]), pack_h(b4[1]));
        }
        if (i == 1) {
          __syncwarp();
#pragma unroll
          for (int n = 0; n < 2; n++)
#pragma unroll
            for (int k2 = 0; k2 < 4; k2++) ldsm4(bf + n * 16 + k2 * 4, stg + (n * 8 + (lane & 7)) * 272 + k2 * 64 + (lane >> 3) * 16);
          __syncwarp();
          if (tid == 160) asm volatile("ld.relaxed.gpu.global.u32 %0, [%1];" : "=r"(cv) : "l"(&g_cnt1) : "memory");
        }
      }
    }
      if (warp == 5) {
        if (lane == 0) {
          const uint32_t tgt = lds32(ep_addr) * 128u;
          int it = 0;
          while ((int)(cv - tgt) < 0 && ++it < 400000) asm volatile("ld.relaxed.gpu.global.u32 %0, [%1];" : "=r"(cv) : "l"(&g_cnt1) : "memory");
          asm volatile("fence.acquire.gpu;" ::: "memory");
          asm volatile("fence.proxy.async.global;" ::: "memory");
          TR(0, 9);
        }
        __syncwarp();
#pragma unroll
        for (int c2 = 0; c2 < 4; c2++) bulk_ld_elect<8192>(sb + c2 * A_CH + A_REC, g_ux + (size_t)(cblk * 4 + c2) * 512, bar_rec);
      }
    {
      const cf p0 = cexp_l(lr[0], li[0], 8.f), p1 = cexp_l(lr[1], li[1], 8.f);
      cf v0 = p0, v1 = p1;
      sts64(sw + 8 * 272, 0x3C00u, 0x3C00u);
#pragma unroll
      for (int i = 1; i < 8; i++) {
        sts64(sw + (8 + i) * 272, pack_h(v0), pack_h(v1));
        v0 = cmul(v0, p0); v1 = cmul(v1, p1);
      }
      const uint32_t ra = stg + 5 * 272 + (lane >> 2) * 64 + (lane & 1) * 32 + (lane & 2) * 4;
      sts64(ra, pack_h(v0), pack_h(-v0.y, v0.x));
      sts64(ra + 16, pack_h(v1), pack_h(-v1.y, v1.x));
    }
    __syncwarp();
    if (tid == 320) TR(0, 16);
#pragma unroll
    for (int k2 = 0; k2 < 4; k2++) ldsm4(bf + 32 + k2 * 4, stg + (lane & 7) * 272 + k2 * 64 + (lane >> 3) * 16);
    float c[6][4];
#pragma unroll
    for (int i = 0; i < 6; i++) { c[i][0] = 0.f; c[i][1] = 0.f; c[i][2] = 0.f; c[i][3] = 0.f; }
#pragma unroll
    for (int k2 = 0; k2 < 4; k2++) {
      uint32_t a[4];
      ldsm4(a, stg + (8 + (lane & 7)) * 272 + k2 * 64 + (lane >> 3) * 16);
#pragma unroll
      for (int kk = 0; kk < 2; kk++) {
        const int ks = 2 * k2 + kk;
        const uint4 r4 = lds128(stg + 5 * 272 + ks * 64 + t * 16);
        const uint32_t r[4] = {r4.x, r4.z, r4.y, r4.w};
        const uint32_t x0 = a[2 * kk], y0 = a[2 * kk + 1];
        const uint32_t x1 = hcmul(x0, r[0], r[2]), y1 = hcmul(y0, r[1], r[3]);
        const uint32_t x2 = hcmul(x1, r[0], r[2]), y2 = hcmul(y1, r[1], r[3]);
        const uint32_t x3 = hcmul(x2, r[0], r[2]), y3 = hcmul(y2, r[1], r[3]);
#pragma unroll
        for (int n = 0; n < 3; n++) {
          mma16816(c[n * 2], x0, x1, y0, y1, bf[n * 16 + ks * 2], bf[n * 16 + ks * 2 + 1]);
          mma16816(c[n * 2 + 1], x2, x3, y2, y3, bf[n * 16 + ks * 2], bf[n * 16 + ks * 2 + 1]);
        }
      }
    }
    __syncwarp();
#pragma unroll
    for (int i = 0; i < 6; i++)
      sts128(stg + i * 512 + lane * 16, __float_as_uint(c[i][0]), __float_as_uint(c[i][1]), __float_as_uint(c[i][2]), __float_as_uint(c[i][3]));
  }
  if (tid == 320) TR(0, 2);

  bar_sync(1 + wg, 128);
  {
    const uint4 sc = lds128(cb + A_SCL);
    const float scl[4] = {__uint_as_float(sc.x), __uint_as_float(sc.y), __uint_as_float(sc.z), __uint_as_float(sc.w)};
#pragma unroll
    for (int rep = 0; rep < 2; rep++) {
      const int qd = rep ? 2 + wr : 3 - wr;
      if (rep == 0 || wr >= 2) {
        float s[4] = {0.f, 0.f, 0.f, 0.f};
#pragma unroll
        for (int w = 0; w < 4; w++) {
          uint4 u4 = lds128(cb + A_STG + w * 4352 + qd * 512 + lane * 16);
          s[0] = fmaf(__uint_as_float(u4.x), scl[w], s[0]); s[1] = fmaf(__uint_as_float(u4.y), scl[w], s[1]);
          s[2] = fmaf(__uint_as_float(u4.z), scl[w], s[2]); s[3] = fmaf(__uint_as_float(u4.w), scl[w], s[3]);
        }
#pragma unroll
        for (int hf = 0; hf < 2; hf++) {
          const int j = (qd & 1) * 16 + g + 8 * hf;
          const uint32_t pk = pack_bf16(s[2 * hf + 1], s[2 * hf]);
          const uint32_t v0 = pk >> 16, v1 = pk & 0xFFFFu, v00 = v0 * 0x10001u;
          if (rep == 1) {
            if (t < 2) {
#pragma unroll
              for (int e = 0; e < 2; e++) {
                const int lam = 128 + 32 * (2 * t + e) + j, mu = lam >> 1;
                const uint32_t val = e ? v1 : v0;
                uint32_t a = cb + ((lam & 1) ? A_R3B : A_R3A) + mu * 4;
                if (lam == 128) { a = cb + A_R2A + 128 * 4; sts32(cb + A_K1024, val << 16); }
                sts16(a, val); sts16(a + 6, val);
              }
            } else if (t == 2 && j == 0) { sts16(cb + A_R3A + 128 * 4, v0); }
          } else if (qd < 2) {
            const uint32_t a = cb + A_R1 + (62 + 8 * j + 2 * t) * 4;
            sts16(a, v0); sts32(a + 4, pk); sts16(a + 10, v1);
          } else if (t < 2) {
            const int L = 256 + 8 * j + 4 * t;
            const uint32_t a = cb + A_R1 + (62 + L) * 4;
            if (L > 256) { sts16(a - 4, v0); sts32(a, v00); } else sts16(a, v0);
            sts32(a + 4, v00); sts32(a + 8, pk); sts16(a + 14, v1);
          } else {
            const int mu = 64 + 32 * (t - 2) + j;
            if (mu == 64) {
              const uint32_t a = cb + A_R1 + (62 + 512) * 4;
              sts16(a - 4, v0); sts32(a, v00); sts32(a + 4, v00); sts32(a + 8, v00); sts16(a + 14, v0);
            } else { sts16(cb + A_R2A + mu * 4, v0); sts16(cb + A_R2A + mu * 4 + 6, v0); }
            sts16(cb + A_R2B + mu * 4, v1); sts16(cb + A_R2B + mu * 4 + 6, v1);
          }
        }
      }
    }
  }
  if (tid == 320) TR(0, 3);
  uint32_t xt[8], ud[8];
  {
    mbar_wait(bar_rec, 0);
    if (tid == 320) TR(0, 4);
      if (bk == 127) {
        mbar_expect(bar_w + 8 * wg, 7168);
        tma3d(sb + A_WST + wg * 7168, (ch & 1) ? mu : mg, ((ch >> 1) % 14) * 32, ((ch >> 1) / 14) * 14, bar_w + 8 * wg);
      }
    uint4 r[4];
#pragma unroll
    for (int i = 0; i < 4; i++) r[i] = lds128(cb + A_REC + bk * 64 + ((i ^ (bk >> 1)) & 3) * 16);
    const uint32_t ua = cb + A_UB + ((2 * bk) & 7) * 656 + ((bk >> 2) + 9) * 16;
    sts128(ua, r[0].x, r[1].x, r[2].x, r[3].x);
    sts128(ua + 656, r[0].y, r[1].y, r[2].y, r[3].y);
    if (bk <= 96) {
      const bool neg = bk == 96;
      const int bp = neg ? -1 : bk;
      uint32_t h[4];
      h[0] = lds32(cb + A_REC + ((bp - 1) & 127) * 64 + ((2 ^ ((bp - 1) >> 1)) & 3) * 16 + 4);
      h[1] = lds32(cb + A_REC + ((bp - 1) & 127) * 64 + ((3 ^ ((bp - 1) >> 1)) & 3) * 16 + 4);
      h[2] = lds32(cb + A_REC + (bp + 1) * 64 + ((0 ^ ((bp + 1) >> 1)) & 3) * 16);
      h[3] = lds32(cb + A_REC + (bp + 1) * 64 + ((1 ^ ((bp + 1) >> 1)) & 3) * 16);
      if (bp <= 0) { h[0] = 0; h[1] = 0; }
      const uint32_t wd[12] = {h[0], h[1], neg ? 0 : r[0].x, neg ? 0 : r[1].x, neg ? 0 : r[2].x, neg ? 0 : r[3].x,
                               neg ? 0 : r[0].y, neg ? 0 : r[1].y, neg ? 0 : r[2].y, neg ? 0 : r[3].y, h[2], h[3]};
      float P[25];
      P[0] = 0.f;
#pragma unroll
      for (int i = 0; i < 12; i++) { P[2 * i + 1] = P[2 * i] + bf_lo(wd[i]); P[2 * i + 2] = P[2 * i + 1] + bf_hi(wd[i]); }
#define WIN(i, hw) (P[(i) + 5 + (hw)] - P[(i) + 4 - (hw)])
#define WPK(i, hw) pack_bf16(WIN(i, hw), WIN((i) + 1, hw))
      const int tp = 2 * bp;
      const uint32_t a3 = cb + A_W3 + (tp + 64) * 16 + 8, a5 = cb + A_W5 + (tp + 64) * 16;
      sts64(a3, WPK(0, 1), WPK(2, 1));
      sts128(a3 + 8, WPK(4, 1), WPK(6, 1), WPK(8, 1), WPK(10, 1));
      sts64(a3 + 24, WPK(12, 1), WPK(14, 1));
      sts128(a5, WPK(0, 2), WPK(2, 2), WPK(4, 2), WPK(6, 2));
      sts128(a5 + 16, WPK(8, 2), WPK(10, 2), WPK(12, 2), WPK(14, 2));
      if (bp < 64) {
        sts128(cb + A_W7 + 1040 + bp * 16, WPK(0, 3), WPK(2, 3), WPK(4, 3), WPK(6, 3));
        sts128(cb + A_W7 + (bp + 1) * 16, WPK(8, 3), WPK(10, 3), WPK(12, 3), WPK(14, 3));
        sts128(cb + A_W9 + (bp + 1) * 16, WPK(0, 4), WPK(2, 4), WPK(4, 4), WPK(6, 4));
        sts128(cb + A_W9 + 1040 + (bp + 1) * 16, WPK(8, 4), WPK(10, 4), WPK(12, 4), WPK(14, 4));
#define VPK(i) pack_bf16(P[(i) + 2] - P[i], P[(i) + 3] - P[(i) + 1])
        sts128(cb + A_V + bp * 32, VPK(0), VPK(2), VPK(4), VPK(6));
        sts128(cb + A_V + bp * 32 + 16, VPK(8), VPK(10), VPK(12), VPK(14));
      }
    }
  }
  asm volatile("fence.proxy.async.shared::cta;" ::: "memory");
  bar_sync(1 + wg, 128);
  if (tid == 320) TR(0, 5);

  {
    const uint32_t cbu = cb;
    const uint32_t blo_k = ((cbu & 0x3FFFF) >> 4) | (41u << 16);
    const uint32_t blo_n = ((cbu & 0x3FFFF) >> 4) | (8u << 16);
    const uint32_t tb = cb + (16 * wq + g - 2 * t) * 4;
    float y1[16], y2[12], y3[8];
    const uint32_t dk16 = __ldg(dskip + ch);
    uint32_t qa[32], qb[32];
    const uint32_t t1 = tb + A_R1 + (62 - 48) * 4;
    load_quads<4>(qa, tb + A_R3A + 17 * 4); load_quads<4>(qa + 16, tb + A_R3B + 16 * 4);
    wg_fence();
    s3_steps<0, 4, A_W9, 1>(y3, qa, blo_n); s3_steps<0, 4, A_W7, 0>(y3, qa + 16, blo_n);
    wg_commit();
    load_quads<8>(qb, tb + A_R2A + 16 * 4);
    wg_fence(); s2_steps<0, 8, A_W5, 1>(y2, qb, blo_n); wg_commit();
    wg_wait<1>(); load_quads<8>(qa, tb + A_R2B + 16 * 4);
    wg_fence(); s2_steps<0, 8, A_W3, 0>(y2, qa, blo_n); wg_commit();
    wg_wait<1>(); load_quads<8>(qb, t1);
    wg_fence(); f1_steps<0, 8>(y1, qb, blo_k); wg_commit();
    wg_wait<1>(); load_quads<8>(qa, t1 + 8 * 64);
    wg_fence(); f1_steps<8, 8>(y1, qa, blo_k); wg_commit();
    reg_fence(y2); reg_fence(y3);
    if (tid == 320) TR(0, 18);
    {
      const float k1024 = __uint_as_float(lds32(cb + A_K1024));
#pragma unroll
      for (int i = 0; i < 2; i++)
#pragma unroll
        for (int hf = 0; hf < 2; hf++) {
          const int idx = 16 * (16 * wq + g + 8 * hf) + 8 * i + 2 * t;
          const uint32_t vv = lds32(cb + A_V + idx * 2);
          sts64(cb + A_Y3 + (idx + 4 * (idx >> 6)) * 4, __float_as_uint(fmaf(k1024, bf_lo(vv), y3[4 * i + 2 * hf])),
                __float_as_uint(fmaf(k1024, bf_hi(vv), y3[4 * i + 2 * hf + 1])));
        }
#pragma unroll
      for (int i = 0; i < 3; i++)
#pragma unroll
        for (int hf = 0; hf < 2; hf++) {
          const int idx = 512 * i + 8 * (16 * wq + g + 8 * hf) + 2 * t;
          sts64(cb + A_Y2 + (idx + 4 * (idx >> 6)) * 4, __float_as_uint(y2[4 * i + 2 * hf]), __float_as_uint(y2[4 * i + 2 * hf + 1]));
        }
    }
    wg_wait<1>(); load_quads<8>(qb, t1 + 16 * 64);
    wg_fence(); f1_steps<16, 8>(y1, qb, blo_k); wg_commit();
    wg_wait<1>(); load_quads<8>(qa, t1 + 24 * 64);
    wg_fence(); f1_steps<24, 8>(y1, qa, blo_k); wg_commit();
  if (bk == 127) {
    mbar_wait(bar_w + 8 * wg, 0);
    bulk_st(g_wimg + (size_t)((ch >> 1) / 28) * 37632 + ((ch >> 1) % 28) * 896 + (ch & 1) * 448, sb + A_WST + wg * 7168, 7168);
    asm volatile("cp.async.bulk.commit_group;" ::: "memory");
  }

    wg_wait<1>(); load_quads<5>(qb, t1 + 32 * 64);
    wg_fence(); f1_steps<32, 5>(y1, qb, blo_k); wg_commit();
    bar_sync(1 + wg, 128);
    float ex[12];
#pragma unroll
    for (int i = 1; i < 4; i++)
#pragma unroll
      for (int k = 0; k < 4; k++) {
        const int aa = 8 * i + 2 * t + (k & 1), b = 16 * wq + g + 8 * (k >> 1);
        float e = __uint_as_float(lds32(cb + A_Y2 + ((aa - 8) * 68 + b) * 4));
        if (i >= 2) e += __uint_as_float(lds32(cb + A_Y3 + ((aa - 16) * 68 + b) * 4));
        ex[4 * (i - 1) + k] = e;
      }
    {
      const uint32_t dk = dk16 * 0x10001u;
#pragma unroll
      for (int i = 0; i < 4; i++) {
        const uint4 r = lds128(cb + A_REC + bk * 64 + ((i ^ (bk >> 1)) & 3) * 16);
        ud[i] = hmul2_bf(r.x, dk); ud[4 + i] = hmul2_bf(r.y, dk); xt[i] = r.z; xt[4 + i] = r.w;
      }
    }
    wg_wait<0>();
    reg_fence(y1);
    if (tid == 320) TR(0, 6);
#pragma unroll
    for (int i = 0; i < 12; i++) y1[4 + i] += ex[i];
#pragma unroll
    for (int i = 0; i < 2; i++) {
      const int mi = lane >> 3, aa = 8 * (2 * i + (mi >> 1)) + (lane & 7);
      asm volatile("stmatrix.sync.aligned.m8n8.x4.trans.shared.b16 [%0], {%1,%2,%3,%4};"
                   ::"r"(cb + A_YB + aa * 128 + (((2 * wq + (mi & 1)) ^ (lane & 7)) << 4)),
                     "r"(pack_bf16(y1[8 * i], y1[8 * i + 1])), "r"(pack_bf16(y1[8 * i + 2], y1[8 * i + 3])),
                     "r"(pack_bf16(y1[8 * i + 4], y1[8 * i + 5])), "r"(pack_bf16(y1[8 * i + 6], y1[8 * i + 7])) : "memory");
    }
  }
  bar_sync(1 + wg, 128);
#pragma unroll
  for (int c = 0; c < 2; c++) {
    const int tau = 2 * bk + c, r = ch & 7;
    const uint4 y = lds128(cb + A_YB + (tau >> 3) * 128 + (((tau ^ (tau >> 3)) & 7) << 4));
    g_himg[(size_t)(tau >> 4) * 7168 + (ch >> 3) * 128 + ((tau >> 3) & 1) * 64 + r * 8 + ((tau & 7) ^ r)] =
        make_uint4(hadd2_bf(xt[4 * c], hadd2_bf(y.x, ud[4 * c])), hadd2_bf(xt[4 * c + 1], hadd2_bf(y.y, ud[4 * c + 1])),
                   hadd2_bf(xt[4 * c + 2], hadd2_bf(y.z, ud[4 * c + 2])), hadd2_bf(xt[4 * c + 3], hadd2_bf(y.w, ud[4 * c + 3])));
  }
  if (bk == 127) asm volatile("cp.async.bulk.wait_group 0;" ::: "memory");
  if (tid == 320) TR(0, 7);
}

constexpr int B_SA = 0, B_RING = 114688, B_SLOT = 14848, B_NSLOT = 7;
constexpr int B_CS = B_RING + B_NSLOT * B_SLOT;
constexpr int B_RED = B_CS + 7168;
constexpr int B_BAR = B_RED + 256;
constexpr int B_SMEM = B_BAR + 1024, A_SMEM = A_WST + 28672;

__device__ __forceinline__ uint32_t mapa(uint32_t a, uint32_t r) { uint32_t o; asm("mapa.shared::cluster.u32 %0, %1, %2;" : "=r"(o) : "r"(a), "r"(r)); return o; }
template <class T> __device__ __forceinline__ T* pin(T* p) { asm volatile("" : "+l"(p)); return p; }
__device__ __forceinline__ uint32_t pin(uint32_t v) { asm volatile("" : "+r"(v)); return v; }
template <int Q, int ST>
__device__ __forceinline__ void g1_stage(float (&acc)[116], uint32_t alo, uint32_t blo, uint32_t bar_full, uint32_t bar_h) {
  constexpr int s = Q * 14 + ST, sl = s % B_NSLOT;
  if (Q == 0) mbar_wait(bar_h + 8 * ST, 0);
  mbar_wait(bar_full + 8 * sl, (s / B_NSLOT) & 1);
  wg_fence();
  if (Q == 0) {
    wgmma_ss232<(2 * ST) * 256, 0x40000080u, (sl * B_SLOT) / 16, 32, ST != 0>(acc, alo, blo);
    wgmma_ss232<(2 * ST + 1) * 256, 0x40000080u, (sl * B_SLOT + 256) / 16, 32, 1>(acc, alo, blo);
  } else {
    wgmma_ss224<(2 * ST) * 256, 0x40000080u, (sl * B_SLOT) / 16, 32, ST != 0>(*(float(*)[112])acc, alo, blo);
    wgmma_ss224<(2 * ST + 1) * 256, 0x40000080u, (sl * B_SLOT + 256) / 16, 32, 1>(*(float(*)[112])acc, alo, blo);
  }
}

__global__ void __launch_bounds__(512, 1)
k_front(const __grid_constant__ CUtensorMap mg, const __grid_constant__ CUtensorMap mu, const __grid_constant__ CUtensorMap md,
        const __nv_bfloat16* __restrict__ x, const uint32_t* __restrict__ are, const uint32_t* __restrict__ aim,
        const uint32_t* __restrict__ bre, const uint32_t* __restrict__ bim, const uint32_t* __restrict__ cre,
        const uint32_t* __restrict__ cim, const unsigned short* __restrict__ logdt, const unsigned short* __restrict__ dskip,
        const uint4* __restrict__ wgate, const uint4* __restrict__ wup, const uint4* __restrict__ wdown) {
  extern __shared__ __align__(1024) unsigned char sm[];
  const uint32_t bar_rec = s2u(sm) + A_BAR;
  if (threadIdx.x == 320) TR(0, 0);
  asm volatile("griddepcontrol.launch_dependents;");
  if (threadIdx.x == 160) {
    mbar_init(bar_rec, 4);
    for (int i = 0; i < 8; i++) mbar_init(bar_rec + 16 + 8 * i, 1);
    asm volatile("fence.mbarrier_init.release.cluster;" ::: "memory");
    asm volatile("prefetch.tensormap [%0];" ::"l"(&mg)); asm volatile("prefetch.tensormap [%0];" ::"l"(&mu)); asm volatile("prefetch.tensormap [%0];" ::"l"(&md));
  }
  phase_a(sm, bar_rec, bar_rec + 8, &mg, &mu, &md, x, are, aim, bre, bim, cre, cim, logdt, dskip, wgate, wup, wdown);
}

__global__ void __cluster_dims__(2, 1, 1) __launch_bounds__(384, 1) k_ffn(__nv_bfloat16* __restrict__ out) {
  extern __shared__ __align__(1024) unsigned char sm[];
  const uint32_t sb = s2u(sm);
  const int tid = threadIdx.x, warp = __shfl_sync(~0u, tid >> 5, 0), wg = warp >> 2, lane = tid & 31;
  const uint32_t bar_full = sb + B_BAR, bar_empty = bar_full + 64, bar_h = bar_full + 128, bar_cs = bar_full + 240,
                 bar_hh = bar_full + 304, bar_afree = bar_full + 336, bar_out = bar_full + 352;
  if (tid == 0) {
    TR(1, 0);
    for (int i = 0; i < B_NSLOT; i++) { mbar_init(bar_full + 8 * i, 1); mbar_init(bar_empty + 8 * i, 2); }
    asm volatile("fence.mbarrier_init.release.cluster;" ::: "memory");
  } else if (tid == 32) {
    for (int i = 0; i < 14; i++) mbar_init(bar_h + 8 * i, 1);
    asm volatile("fence.mbarrier_init.release.cluster;" ::: "memory");
  } else if (tid == 64) {
    mbar_init(bar_cs, 1);
    for (int i = 0; i < 4; i++) { mbar_init(bar_hh + 8 * i, 1); mbar_expect(bar_hh + 8 * i, 14336); }
    mbar_init(bar_afree, 4); mbar_init(bar_afree + 8, 2);
    for (int i = 0; i < 6; i++) mbar_init(bar_out + 8 * i, 128);
    asm volatile("fence.mbarrier_init.release.cluster;" ::: "memory");
  } else if (tid >= 128 && tid < 352) {
    sts128(sb + B_RING + ((tid - 128) >> 5) * B_SLOT + 14336 + (tid & 31) * 16, 0x3F803F80u, 0x3F803F80u, 0x3F803F80u, 0x3F803F80u);
  }
  asm volatile("fence.proxy.async.shared::cta;" ::: "memory");
  __syncthreads();
  asm volatile("barrier.cluster.arrive.relaxed.aligned;" ::: "memory");
  const int rank = blockIdx.x & 1, rt = blockIdx.x >> 3, j = blockIdx.x & 7, p = j >> 1, cg = 4 * rank + p;
  const int wq = warp & 3, t128 = tid & 127, g = lane >> 2, t = lane & 3;
  uint32_t ep, tag;
  auto load_ep = [&]() { asm volatile("ld.relaxed.gpu.global.u32 %0, [%1];" : "=r"(ep) : "l"(&g_cnt1) : "memory"); };
  auto a_slot = [&](int i, int own) { return B_SA + (i + (i >= own)) * 14336; };
  auto out_addr = [&](int cc, int w) { return sb + a_slot((cc & 2) + w, cg) + (cc & 1) * 7168; };
  auto in_cta = [&](int q) { return rt * 8 + ((p + 3 - q) & 3) * 2 + rank; };
  auto in_src = [&](int q, int cw) { return g_part + (size_t)(in_cta(q) * 3 + q) * 896 + cw * 112; };
  auto in_bad = [&](uint32_t (&in)[14]) { return ((in[3] ^ tag) | (in[7] ^ tag) | (in[11] ^ tag) | (in[13] ^ tag)) & 0x10000u; };
  auto in_load = [&](uint32_t (&in)[14], const uint4* gs) {
#pragma unroll
    for (int i = 0; i < 3; i++) ld128(gs + i * 32, in + 4 * i);
    asm volatile("{\n.reg .b64 v;\nld.relaxed.gpu.global.b64 v, [%2];\nmov.b64 {%0, %1}, v;\n}"
                 : "=r"(in[12]), "=r"(in[13]) : "l"((const uint2*)(gs + 96) - lane) : "memory");
  };
  auto in_check = [&](uint32_t (&in)[14], int q, int cw) {
    int it = 0;
    while (in_bad(in) && ++it < 400000) in_load(in, pin(in_src(q, cw) + lane));
  };

  if (wg == 2) {
    asm volatile("setmaxnreg.dec.sync.aligned.u32 40;");
    asm volatile("barrier.cluster.wait.aligned;" ::: "memory");
    asm volatile("griddepcontrol.wait;" ::: "memory");
    if (warp == 8) {
      if (lane == 0) TR(1, 1);
      const char* wsrc = (const char*)g_wimg + (size_t)j * 602112;
      const char* hsrc = (const char*)g_himg + (size_t)rt * 114688 + rank * 4096;
#pragma unroll
      for (int s = 0; s < 28; s++) {
        if (s < B_NSLOT) bulk_ld_mc_elect<4096>(sb + B_SA + s * 8192 + rank * 4096, hsrc + s * 8192, bar_h + 8 * s);
        if (s == B_NSLOT) {
#pragma unroll
          for (int i = 7; i < 14; i++) bulk_ld_mc_elect<4096>(sb + B_SA + i * 8192 + rank * 4096, hsrc + i * 8192, bar_h + 8 * i);
          bulk_ld_elect<7168>(sb + B_CS, g_cimg + j * 448, bar_cs);
        }
        if (s >= B_NSLOT) mbar_wait(bar_empty + 8 * (s % B_NSLOT), (s / B_NSLOT + 1) & 1);
        bulk_ld_elect<14336>(sb + B_RING + (s % B_NSLOT) * B_SLOT, wsrc + s * 14336, bar_full + 8 * (s % B_NSLOT));
      }
      const char* dsrc[2] = {wsrc + 401408 + rank * 100352, (const char*)g_wimg + (size_t)(j ^ 1) * 602112 + 401408 + rank * 100352};
#pragma unroll
      for (int i = 0; i < 16; i++) {
        const int ci = i < 3 ? 0 : i < 6 ? 1 : i < 8 ? i - 6 : i < 12 ? 2 : 3;
        const int kp = i < 3 ? i : i < 6 ? i - 3 : i < 8 ? 3 : (i & 3);
        mbar_wait(bar_empty + 8 * (i % B_NSLOT), (i / B_NSLOT + 1) & 1);
        bulk_ld_elect<12544>(sb + B_RING + (i % B_NSLOT) * B_SLOT, dsrc[kp >> 1] + ((p + 1 + ci) & 3) * 25088 + (kp & 1) * 12544, bar_full + 8 * (i % B_NSLOT));
      }
    } else if (warp >= 10) {
      const int t64 = tid - 320;
      load_ep();
      const int r = (lane >> 1) & 7, c = (j & 3) * 2 + (lane & 1);
      const uint32_t src = sb + B_SA + (t64 >> 4) * 2048 + (j >> 2) * 1024 + r * 128 + ((c ^ r) << 4);
      float a[16];
#pragma unroll
      for (int k = 0; k < 16; k++) a[k] = 0.f;
#pragma unroll 1
      for (int i = 0; i < 14; i++) {
        mbar_wait(bar_h + 8 * i, 0);
        uint4 v = lds128(src + i * 8192);
        float e[8] = {bf_lo(v.x), bf_hi(v.x), bf_lo(v.y), bf_hi(v.y), bf_lo(v.z), bf_hi(v.z), bf_lo(v.w), bf_hi(v.w)};
#pragma unroll
        for (int k = 0; k < 8; k++) { a[2 * k] += e[k]; a[2 * k + 1] = fmaf(e[k], e[k], a[2 * k + 1]); }
        __nanosleep(160);
      }
      __syncwarp();
      if (lane == 0) { asm volatile("mbarrier.arrive.shared::cluster.b64 _, [%0];" ::"r"(mapa(bar_afree, rank ^ 1)) : "memory"); }
#pragma unroll
      for (int rd = 0; rd < 4; rd++) {
        const int n = 8 >> rd;
        const bool up = lane & (2 * n);
#pragma unroll
        for (int k = 0; k < 8; k++) {
          if (k < n) {
            float keep = up ? a[k + n] : a[k], give = up ? a[k] : a[k + n];
            a[k] = keep + __shfl_xor_sync(~0u, give, 2 * n);
          }
        }
      }
      float* red = (float*)(sm + B_RED);
      red[(warp & 1) * 32 + (lane & 1) * 16 + (lane >> 1)] = a[0];
      bar_sync(1, 64);
      if (t64 < 16) {
        float mean = (red[2 * t64] + red[32 + 2 * t64]) * (1.f / DM);
        float var = fmaxf(fmaf(-mean, mean, (red[2 * t64 + 1] + red[33 + 2 * t64]) * (1.f / DM)), 0.f);
        float rs = ln_rstd(var);
        asm volatile("st.relaxed.gpu.global.u32 [%0], %1;"
                     ::"l"(g_stat2 + rt * 128 + j * 16 + t64), "r"((__float_as_uint(rs * rs) & ~1u) | ((ep >> 7) & 1u)) : "memory");
      }
      if (t64 == 0) TR(1, 2);
      if (lane == 0) {
        const int w = warp & 1;
        for (int cc = 0; cc < 2; cc++) {
          mbar_wait(bar_out + 8 * (cc * 2 + w), 0);
          asm volatile("cp.async.bulk.global.shared::cta.bulk_group [%0], [%1], 7168;"
                       ::"l"(g_part + (size_t)(blockIdx.x * 3 + cc) * 896 + w * 448), "r"(out_addr(cc, w)) : "memory");
          if (w) TR(1, 27 + cc);
        }
        asm volatile("cp.async.bulk.commit_group;" ::: "memory");
        asm volatile("cp.async.bulk.wait_group 0;" ::: "memory");
      }
    }
  } else {
    asm volatile("setmaxnreg.inc.sync.aligned.u32 232;");
    asm volatile("barrier.cluster.wait.aligned;" ::: "memory");
    uint32_t hh[56];
    const bool relt = t128 == 0;
    auto release = [&](int sl) { if (relt) mbar_arrive(bar_empty + 8 * sl); };
    auto send_hh = [&](int q) {
      const uint32_t da = mapa(sb + a_slot(2 * q + wg, cg ^ 4) + t128 * 16, rank ^ 1), db = mapa(bar_hh + 8 * (2 * q + wg), rank ^ 1);
#pragma unroll
      for (int i = 0; i < 7; i++)
        asm volatile("st.async.weak.shared::cluster.mbarrier::complete_tx::bytes.v4.b32 [%0], {%1, %2, %3, %4}, [%5];"
                     ::"r"(da + i * 2048), "r"(hh[28 * q + 4 * i]), "r"(hh[28 * q + 4 * i + 1]),
                       "r"(hh[28 * q + 4 * i + 2]), "r"(hh[28 * q + 4 * i + 3]), "r"(db) : "memory");
    };
    uint32_t alo = ((sb + B_SA + wg * 1024) & 0x3FFFF) >> 4;
    uint32_t blo = (((sb + B_RING) & 0x3FFFF) >> 4) | (8u << 16);
    const uint32_t clo = ((sb + B_CS) & 0x3FFFF) >> 4;
    uint32_t nm0, nm1;
    if (wg == 1) bar_sync(3, 256);
#define G1S(Q, ST) do { if (ST % 7 == 0) { alo = pin(alo); blo = pin(blo); }   \
      g1_stage<Q, ST>(acc, alo, blo, bar_full, bar_h); wg_commit(); \
      if (ST > 0) { wg_wait<1>(); release((Q * 14 + ST - 1) % B_NSLOT); } } while (0)
#define G1HH(Q) do { \
      _Pragma("unroll") \
      for (int i = 0; i < 28; i++) hh[28 * Q + i] = pack_bf16(acc[2 * i] * acc[56 + 2 * i], acc[2 * i + 1] * acc[57 + 2 * i]); \
    } while (0)
    {
      float acc[116];
      G1S(0, 0);
      if (tid == 0) TR(1, 3);
      G1S(0, 1);
      if (wg == 0) asm volatile("bar.arrive 3, 256;" ::: "memory");
      G1S(0, 2); G1S(0, 3); G1S(0, 4); G1S(0, 5); G1S(0, 6); G1S(0, 7); G1S(0, 8); G1S(0, 9); G1S(0, 10); G1S(0, 11); G1S(0, 12);
      G1S(0, 13);
      if (tid == 0) TR(1, 4);
      mbar_wait(bar_cs, 0);
      wg_wait<0>(); reg_fence(acc); release(13 % B_NSLOT);
      {
        const uint32_t msk = t == 0 ? 0xFFFFFFFFu : t == 1 ? 0xFFFFu : 0u;
        const float a = acc[112] * (-1.f / DM), b = acc[114] * (-1.f / DM);
        nm0 = pack_bf16(a, a) & msk; nm1 = pack_bf16(b, b) & msk;
      }
      wg_fence();
      wgmma_rs224<0, 8, 1>(*(float(*)[112])acc, nm0, nm1, 0u, 0u, clo);
      wg_commit(); wg_wait<0>(); reg_fence(acc);
      G1HH(0);
      if (tid == 0) TR(1, 5);
      G1S(1, 0); G1S(1, 1); G1S(1, 2); G1S(1, 3); G1S(1, 4); G1S(1, 5); G1S(1, 6);
      if (relt) asm volatile("mbarrier.arrive.shared::cluster.b64 _, [%0];" ::"r"(mapa(bar_afree, rank ^ 1)) : "memory");
      G1S(1, 7); G1S(1, 8); G1S(1, 9);
      if (relt) asm volatile("mbarrier.arrive.shared::cluster.b64 _, [%0];" ::"r"(mapa(bar_afree + 8, rank ^ 1)) : "memory");
      mbar_wait(bar_afree, 0);
      send_hh(0);
      G1S(1, 10); G1S(1, 11); G1S(1, 12);
      load_ep();
      g1_stage<1, 13>(acc, alo, blo, bar_full, bar_h);
      wgmma_rs224<224, 8, 1>(*(float(*)[112])acc, nm0, nm1, 0u, 0u, clo);
      wg_commit(); wg_wait<1>(); release(26 % B_NSLOT);
      wg_wait<0>(); reg_fence(acc); release(27 % B_NSLOT);
      G1HH(1);
      if (tid == 0) TR(1, 6);
    }
    float accA[28], accB[28];
    uint32_t ph0[28], ph1[28];
    ep = pin(ep >> 7); tag = pin((ep & 1u) << 16);
#define ISSUE(acc, I, a, FIRST) do { \
      constexpr int s_ = 28 + (I), sl_ = s_ % B_NSLOT; \
      if (sl_ == 0) blo = pin(blo); \
      mbar_wait(bar_full + 8 * sl_, (s_ / B_NSLOT) & 1); \
      wg_fence(); \
      wgmma_rs56<(sl_ * B_SLOT + 0 * 256) / 16, 112, !(FIRST)>(acc, (a)[0], (a)[1], (a)[2], (a)[3], blo); \
      wgmma_rs56<(sl_ * B_SLOT + 1 * 256) / 16, 112, 1>(acc, (a)[4], (a)[5], (a)[6], (a)[7], blo); \
      wgmma_rs56<(sl_ * B_SLOT + 2 * 256) / 16, 112, 1>(acc, (a)[8], (a)[9], (a)[10], (a)[11], blo); \
      wgmma_rs56<(sl_ * B_SLOT + 3 * 256) / 16, 112, 1>(acc, (a)[12], (a)[13], (a)[14], (a)[15], blo); \
      wgmma_rs56<(sl_ * B_SLOT + 4 * 256) / 16, 112, 1>(acc, (a)[16], (a)[17], (a)[18], (a)[19], blo); \
      wgmma_rs56<(sl_ * B_SLOT + 5 * 256) / 16, 112, 1>(acc, (a)[20], (a)[21], (a)[22], (a)[23], blo); \
      wgmma_rs56<(sl_ * B_SLOT + 6 * 256) / 16, 112, 1>(acc, (a)[24], (a)[25], (a)[26], (a)[27], blo); \
      wg_commit(); } while (0)
    auto rel = [&](int i) { release((28 + i) % B_NSLOT); };
    auto tg = [&](uint32_t v) { return (v & 0xFFFEFFFFu) | tag; };
    auto send = [&](float (&acc)[28], int cc) {
      reg_fence(acc);
      const uint32_t a = out_addr(cc, wg) + wq * 1792;
#pragma unroll
      for (int q = 0; q < 3; q++)
        sts128(a + q * 512 + lane * 16, pack_bf16(acc[8 * q], acc[8 * q + 1]), pack_bf16(acc[8 * q + 2], acc[8 * q + 3]),
               pack_bf16(acc[8 * q + 4], acc[8 * q + 5]), tg(pack_bf16(acc[8 * q + 6], acc[8 * q + 7])));
      sts64(a + 1536 + lane * 8, pack_bf16(acc[24], acc[25]), tg(pack_bf16(acc[26], acc[27])));
      asm volatile("fence.proxy.async.shared::cta;" ::: "memory");
      mbar_arrive(bar_out + 8 * (cc * 2 + wg));
    };
    auto load_hh = [&](uint32_t (&d)[28], int q) {
      mbar_wait(bar_hh + 8 * (2 * q + wg), 0);
      const uint32_t a = sb + a_slot(2 * q + wg, cg) + t128 * 16;
#pragma unroll
      for (int i = 0; i < 7; i++) {
        const uint4 v = lds128(a + i * 2048);
        d[4 * i] = v.x; d[4 * i + 1] = v.y; d[4 * i + 2] = v.z; d[4 * i + 3] = v.w;
      }
    };
    ISSUE(accA, 0, hh, true);
    mbar_wait(bar_afree + 8, 0);
    send_hh(1);
    ISSUE(accA, 1, hh + 28, false);
    load_hh(ph0, 0);
    wg_wait<1>(); rel(0);
    ISSUE(accA, 2, ph0, false);      wg_wait<1>(); rel(1);
    ISSUE(accB, 3, hh, true);        wg_wait<1>(); rel(2);
    ISSUE(accB, 4, hh + 28, false);  wg_wait<1>(); rel(3);
    ISSUE(accB, 5, ph0, false);
    if (tid == 0) TR(1, 11);
    load_hh(ph1, 1);
    wg_wait<1>(); rel(4);
    ISSUE(accA, 6, ph1, false);      wg_wait<1>(); rel(5);
    ISSUE(accB, 7, ph1, false);      wg_wait<1>(); rel(6); send(accA, 0);
    ISSUE(accA, 8, hh, true);        wg_wait<1>(); rel(7); send(accB, 1);
    if (tid == 0) TR(1, 13);
    ISSUE(accA, 9, hh + 28, false);  wg_wait<1>(); rel(8);
    ISSUE(accA, 10, ph0, false);
    ISSUE(accA, 11, ph1, false);
    const int row = rt * 128 + wg * 64 + wq * 16 + g;
    uint32_t r20, r21;
    asm volatile("ld.relaxed.gpu.global.u32 %0, [%1];" : "=r"(r20) : "l"(g_stat2 + row) : "memory");
    asm volatile("ld.relaxed.gpu.global.u32 %0, [%1];" : "=r"(r21) : "l"(g_stat2 + row + 8) : "memory");
    ISSUE(accB, 12, hh, true);
    wg_wait<1>();
    {
      reg_fence(accA);
      uint4* pd = g_part + (size_t)(blockIdx.x * 3 + 2) * 896 + warp * 112 + lane;
#pragma unroll
      for (int q = 0; q < 3; q++)
        st128(pd + q * 32, pack_bf16(accA[8 * q], accA[8 * q + 1]), pack_bf16(accA[8 * q + 2], accA[8 * q + 3]),
              pack_bf16(accA[8 * q + 4], accA[8 * q + 5]), tg(pack_bf16(accA[8 * q + 6], accA[8 * q + 7])));
      asm volatile("{\n.reg .b64 v;\nmov.b64 v, {%1, %2};\nst.relaxed.gpu.global.b64 [%0], v;\n}"
                   ::"l"((uint2*)(pd + 96) - lane), "r"(pack_bf16(accA[24], accA[25])), "r"(tg(pack_bf16(accA[26], accA[27]))) : "memory");
    }
    if (tid == 0) TR(1, 16);
    ISSUE(accB, 13, hh + 28, false);
    ISSUE(accB, 14, ph0, false);
    uint32_t in0[14], in1[14], in2[14];
    in_load(in0, in_src(0, warp) + lane);
    in_load(in1, in_src(1, warp) + lane);
    ISSUE(accB, 15, ph1, false);
    if (tid == 0) TR(1, 7);
    {
      int it = 0;
      while ((((r20 ^ ep) | (r21 ^ ep)) & 1u) && ++it < 400000) {
        asm volatile("ld.relaxed.gpu.global.u32 %0, [%1];" : "=r"(r20) : "l"(g_stat2 + row) : "memory");
        asm volatile("ld.relaxed.gpu.global.u32 %0, [%1];" : "=r"(r21) : "l"(g_stat2 + row + 8) : "memory");
      }
    }
    in_check(in0, 0, warp); in_check(in1, 1, warp);
#pragma unroll
    for (int i = 0; i < 14; i++) { accA[2 * i] = bf_lo(in0[i]) + bf_lo(in1[i]); accA[2 * i + 1] = bf_hi(in0[i]) + bf_hi(in1[i]); }
    if (tid == 0) TR(1, 12);
    wg_wait<0>();
    reg_fence(accB);
    in_load(in2, in_src(2, warp) + lane);
    uint32_t hres[16];
#pragma unroll
    for (int i = 0; i < 4; i++) {
      int qq = lane >> 3, r = lane & 7, kg = 7 * cg + 2 * i + (qq >> 1), c = 2 * wq + (qq & 1);
      if (kg > 55) kg = 55;
      asm volatile("ldmatrix.sync.aligned.m8n8.x4.trans.shared.b16 {%0,%1,%2,%3}, [%4];"
                   : "=r"(hres[4 * i]), "=r"(hres[4 * i + 1]), "=r"(hres[4 * i + 2]), "=r"(hres[4 * i + 3])
                   : "r"(sb + B_SA + kg * 2048 + wg * 1024 + r * 128 + ((c ^ r) << 4)) : "memory");
    }
#pragma unroll
    for (int i = 0; i < 28; i++) accB[i] += accA[i];
    if (tid == 0) TR(1, 9);
    in_check(in2, 2, warp);
#pragma unroll
    for (int i = 0; i < 14; i++) { accB[2 * i] += bf_lo(in2[i]); accB[2 * i + 1] += bf_hi(in2[i]); }
    {
      uint32_t o[16];
#pragma unroll
      for (int i = 0; i < 7; i++) {
        o[2 * i] = hadd2_bf(hres[2 * i], pack_bf16(accB[4 * i] * __uint_as_float(r20), accB[4 * i + 1] * __uint_as_float(r20)));
        o[2 * i + 1] = hadd2_bf(hres[2 * i + 1], pack_bf16(accB[4 * i + 2] * __uint_as_float(r21), accB[4 * i + 3] * __uint_as_float(r21)));
      }
      o[14] = 0; o[15] = 0;
      const uint32_t ob = sb + a_slot(4 + wg, cg) + wq * 2304;
#pragma unroll
      for (int i = 0; i < 4; i++)
        asm volatile("stmatrix.sync.aligned.m8n8.x4.shared.b16 [%0], {%1,%2,%3,%4};"
                     ::"r"(ob + (lane & 15) * 144 + (2 * i + (lane >> 4)) * 16), "r"(o[4 * i]), "r"(o[4 * i + 1]), "r"(o[4 * i + 2]), "r"(o[4 * i + 3]) : "memory");
      __syncwarp();
      uint4* op = (uint4*)(out + (size_t)(rt * 128 + wg * 64 + wq * 16) * DM + 56 * cg);
#pragma unroll
      for (int i = 0; i < 4; i++) {
        if ((lane & 7) < 7) {
          const int r = 4 * i + (lane >> 3);
          op[r * 56 + (lane & 7)] = lds128(ob + r * 144 + (lane & 7) * 16);
        }
      }
    }
    if (tid == 0) TR(1, 10);
    if (tid == 128) TR(1, 15);
  }
}

typedef CUresult (*EncFn)(CUtensorMap*, CUtensorMapDataType, cuuint32_t, void*, const cuuint64_t*, const cuuint64_t*,
                          const cuuint32_t*, const cuuint32_t*, CUtensorMapInterleave, CUtensorMapSwizzle,
                          CUtensorMapL2promotion, CUtensorMapFloatOOBfill);

extern "C" void kernel_launch(void* const* d_in, const int* in_sizes, int n_in, void* d_out, int out_size) {
  const __nv_bfloat16* x = (const __nv_bfloat16*)d_in[0];
  const __nv_bfloat16 *are = (const __nv_bfloat16*)d_in[1], *aim = (const __nv_bfloat16*)d_in[2], *bre = (const __nv_bfloat16*)d_in[3],
                      *bim = (const __nv_bfloat16*)d_in[4], *cre = (const __nv_bfloat16*)d_in[5], *cim = (const __nv_bfloat16*)d_in[6],
                      *logdt = (const __nv_bfloat16*)d_in[7], *dskip = (const __nv_bfloat16*)d_in[8];
  const __nv_bfloat16 *wg = (const __nv_bfloat16*)d_in[10], *wu = (const __nv_bfloat16*)d_in[11], *wd = (const __nv_bfloat16*)d_in[12];

  static EncFn enc = nullptr;
  if (!enc) {
    void* fn = nullptr; cudaDriverEntryPointQueryResult qr;
    cudaGetDriverEntryPoint("cuTensorMapEncodeTiled", &fn, cudaEnableDefault, &qr);
    enc = (EncFn)fn;
    cudaFuncSetAttribute(k_ffn, cudaFuncAttributeMaxDynamicSharedMemorySize, B_SMEM);
    cudaFuncSetAttribute(k_front, cudaFuncAttributeMaxDynamicSharedMemorySize, A_SMEM);
  }
  CUtensorMap mg, mu, md;
  {
    cuuint32_t es[3] = {1, 1, 1};
    cuuint64_t d1[3] = {8, 448, 224}, s1[2] = {3584, 16}; cuuint32_t b1[3] = {8, 32, 14};
    cuuint64_t d2[3] = {8, 1792, 56}, s2[2] = {896, 16}; cuuint32_t b2[3] = {8, 112, 7};
    enc(&mg, CU_TENSOR_MAP_DATA_TYPE_BFLOAT16, 3, (void*)wg, d1, s1, b1, es, CU_TENSOR_MAP_INTERLEAVE_NONE, CU_TENSOR_MAP_SWIZZLE_NONE, CU_TENSOR_MAP_L2_PROMOTION_L2_256B, CU_TENSOR_MAP_FLOAT_OOB_FILL_NONE);
    enc(&mu, CU_TENSOR_MAP_DATA_TYPE_BFLOAT16, 3, (void*)wu, d1, s1, b1, es, CU_TENSOR_MAP_INTERLEAVE_NONE, CU_TENSOR_MAP_SWIZZLE_NONE, CU_TENSOR_MAP_L2_PROMOTION_L2_256B, CU_TENSOR_MAP_FLOAT_OOB_FILL_NONE);
    enc(&md, CU_TENSOR_MAP_DATA_TYPE_BFLOAT16, 3, (void*)wd, d2, s2, b2, es, CU_TENSOR_MAP_INTERLEAVE_NONE, CU_TENSOR_MAP_SWIZZLE_NONE, CU_TENSOR_MAP_L2_PROMOTION_L2_256B, CU_TENSOR_MAP_FLOAT_OOB_FILL_NONE);
  }
  cudaStream_t st = cudaStreamPerThread;
  k_front<<<128, 512, A_SMEM, st>>>(
      mg, mu, md, x, (const uint32_t*)are, (const uint32_t*)aim, (const uint32_t*)bre, (const uint32_t*)bim, (const uint32_t*)cre, (const uint32_t*)cim,
      (const unsigned short*)logdt, (const unsigned short*)dskip, (const uint4*)wg, (const uint4*)wu, (const uint4*)wd);
  cudaLaunchConfig_t cfg = {};
  cfg.gridDim = dim3(128); cfg.blockDim = dim3(384); cfg.dynamicSmemBytes = B_SMEM; cfg.stream = st;
  cudaLaunchAttribute at[1];
  at[0].id = cudaLaunchAttributeProgrammaticStreamSerialization; at[0].val.programmaticStreamSerializationAllowed = 1;
  cfg.attrs = at; cfg.numAttrs = 1;
  cudaLaunchKernelEx(&cfg, k_ffn, (__nv_bfloat16*)d_out);
}
```

```cpp
#include <cuda_runtime.h>
#include <cuda_bf16.h>
#include <cuda_fp16.h>
#include <cuda.h>
#include <stdint.h>

constexpr int LSEQ = 2048, DM = 448;

__device__ __align__(1024) uint4    g_himg[16 * 114688 / 16];
__device__ __align__(1024) uint4    g_cimg[8 * 2 * 224];
__device__ __align__(1024) uint32_t g_stat2[LSEQ];
__device__ __align__(1024) uint4    g_part[128 * 3 * 896];
__device__ __align__(1024) uint4    g_wimg[8 * 602112 / 16];
__device__ __align__(1024) uint4    g_ux[DM * 128 * 4];
__device__ __align__(1024) unsigned g_cnt1;

#define TR(k, i) do {} while (0)
__device__ __forceinline__ uint32_t s2u(const void* p) { return (uint32_t)__cvta_generic_to_shared(p); }
__device__ __forceinline__ void mbar_init(uint32_t b, int c) { asm volatile("mbarrier.init.shared::cta.b64 [%0], %1;" ::"r"(b), "r"(c)); }
__device__ __forceinline__ void mbar_expect(uint32_t b, int bytes) { asm volatile("mbarrier.arrive.expect_tx.shared::cta.b64 _, [%0], %1;" ::"r"(b), "r"(bytes) : "memory"); }
__device__ __forceinline__ void mbar_arrive(uint32_t b) { asm volatile("mbarrier.arrive.shared::cta.b64 _, [%0];" ::"r"(b) : "memory"); }
__device__ __forceinline__ void mbar_wait(uint32_t b, int ph) {
  asm volatile("{\n.reg .pred p;\n.reg .b32 n;\nmov.b32 n, 0;\nLW:\nmbarrier.try_wait.parity.shared::cta.b64 p, [%0], %1;\n@p bra LD;\n"
               "add.u32 n, n, 1;\nsetp.lt.u32 p, n, 4000000;\n@p bra LW;\ntrap;\nLD:\n}" ::"r"(b), "r"(ph) : "memory");
}
__device__ __forceinline__ void wg_fence() { asm volatile("wgmma.fence.sync.aligned;" ::: "memory"); }
__device__ __forceinline__ void wg_commit() { asm volatile("wgmma.commit_group.sync.aligned;" ::: "memory"); }
template <int N> __device__ __forceinline__ void wg_wait() { asm volatile("wgmma.wait_group.sync.aligned %0;" ::"n"(N) : "memory"); }
template <int N> __device__ __forceinline__ void reg_fence(float (&a)[N]) {
#pragma unroll
  for (int i = 0; i < N; i++) asm volatile("" : "+f"(a[i])::"memory");
}
template <class T> __device__ __forceinline__ T* pin(T* p) { asm volatile("" : "+l"(p)); return p; }
__device__ __forceinline__ uint32_t pin(uint32_t v) { asm volatile("" : "+r"(v)); return v; }
__device__ __forceinline__ uint32_t pack_bf16(float lo, float hi) {
  uint32_t r; asm("cvt.rn.bf16x2.f32 %0, %1, %2;" : "=r"(r) : "f"(hi), "f"(lo)); return r;
}
__device__ __forceinline__ float bf_lo(uint32_t v) { return __uint_as_float(v << 16); }
__device__ __forceinline__ float bf_hi(uint32_t v) { return __uint_as_float(v & 0xFFFF0000u); }
__device__ __forceinline__ float rbf(float x) { return __bfloat162float(__float2bfloat16_rn(x)); }
__device__ __forceinline__ uint32_t hmul2_bf(uint32_t a, uint32_t b) { uint32_t r; asm("mul.rn.bf16x2 %0, %1, %2;" : "=r"(r) : "r"(a), "r"(b)); return r; }
__device__ __forceinline__ uint32_t hadd2_bf(uint32_t a, uint32_t b) { uint32_t r; asm("add.rn.bf16x2 %0, %1, %2;" : "=r"(r) : "r"(a), "r"(b)); return r; }
template <int BYTES>
__device__ __forceinline__ void bulk_ld_elect(uint32_t dst, const void* src, uint32_t bar) {
  asm volatile("{\n.reg .pred p;\nelect.sync _|p, 0xffffffff;\n"
               "@p mbarrier.arrive.expect_tx.shared::cta.b64 _, [%2], %3;\n"
               "@p cp.async.bulk.shared::cluster.global.mbarrier::complete_tx::bytes [%0], [%1], %3, [%2];\n}"
               ::"r"(dst), "l"(src), "r"(bar), "n"(BYTES) : "memory");
}
template <int BYTES>
__device__ __forceinline__ void bulk_ld_mc_elect(uint32_t dst, const void* src, uint32_t bar) {
  asm volatile("{\n.reg .pred p;\nelect.sync _|p, 0xffffffff;\n"
               "@p mbarrier.arrive.expect_tx.shared::cta.b64 _, [%2], %3;\n"
               "@p cp.async.bulk.shared::cluster.global.mbarrier::complete_tx::bytes.multicast::cluster [%0], [%1], %4, [%2], %5;\n}"
               ::"r"(dst), "l"(src), "r"(bar), "n"(2 * BYTES), "n"(BYTES), "h"((uint16_t)3) : "memory");
}
template <int AOFF, uint32_t AHI, int BOFF, uint32_t BHI, int ACC>
__device__ __forceinline__ void wgmma_ss224(float (&d)[112], uint32_t alo, uint32_t blo) {
  asm volatile("{\n.reg .pred p;\n.reg .b64 ad, bd;\nsetp.ne.b32 p, %118, 0;\n"
    "mov.b64 ad, {%112, %115};\nadd.s64 ad, ad, %114;\nmov.b64 bd, {%113, %117};\nadd.s64 bd, bd, %116;\n"
    "wgmma.mma_async.sync.aligned.m64n224k16.f32.bf16.bf16 {%0,%1,%2,%3,%4,%5,%6,%7,%8,%9,%10,%11,%12,%13,%14,%15,%16,%17,%18,%19,%20,%21,%22,%23,%24,%25,%26,%27,%28,%29,%30,%31,%32,%33,%34,%35,%36,%37,%38,%39,%40,%41,%42,%43,%44,%45,%46,%47,%48,%49,%50,%51,%52,%53,%54,%55,%56,%57,%58,%59,%60,%61,%62,%63,%64,%65,%66,%67,%68,%69,%70,%71,%72,%73,%74,%75,%76,%77,%78,%79,%80,%81,%82,%83,%84,%85,%86,%87,%88,%89,%90,%91,%92,%93,%94,%95,%96,%97,%98,%99,%100,%101,%102,%103,%104,%105,%106,%107,%108,%109,%110,%111}, ad, bd, p, 1, 1, 1, 1;\n}\n"
    : "+f"(d[0]),"+f"(d[1]),"+f"(d[2]),"+f"(d[3]),"+f"(d[4]),"+f"(d[5]),"+f"(d[6]),"+f"(d[7]),"+f"(d[8]),"+f"(d[9]),"+f"(d[10]),"+f"(d[11]),"+f"(d[12]),"+f"(d[13]),"+f"(d[14]),"+f"(d[15]),"+f"(d[16]),"+f"(d[17]),"+f"(d[18]),"+f"(d[19]),"+f"(d[20]),"+f"(d[21]),"+f"(d[22]),"+f"(d[23]),"+f"(d[24]),"+f"(d[25]),"+f"(d[26]),"+f"(d[27]),"+f"(d[28]),"+f"(d[29]),"+f"(d[30]),"+f"(d[31]),"+f"(d[32]),"+f"(d[33]),"+f"(d[34]),"+f"(d[35]),"+f"(d[36]),"+f"(d[37]),"+f"(d[38]),"+f"(d[39]),"+f"(d[40]),"+f"(d[41]),"+f"(d[42]),"+f"(d[43]),"+f"(d[44]),"+f"(d[45]),"+f"(d[46]),"+f"(d[47]),"+f"(d[48]),"+f"(d[49]),"+f"(d[50]),"+f"(d[51]),"+f"(d[52]),"+f"(d[53]),"+f"(d[54]),"+f"(d[55]),"+f"(d[56]),"+f"(d[57]),"+f"(d[58]),"+f"(d[59]),"+f"(d[60]),"+f"(d[61]),"+f"(d[62]),"+f"(d[63]),"+f"(d[64]),"+f"(d[65]),"+f"(d[66]),"+f"(d[67]),"+f"(d[68]),"+f"(d[69]),"+f"(d[70]),"+f"(d[71]),"+f"(d[72]),"+f"(d[73]),"+f"(d[74]),"+f"(d[75]),"+f"(d[76]),"+f"(d[77]),"+f"(d[78]),"+f"(d[79]),"+f"(d[80]),"+f"(d[81]),"+f"(d[82]),"+f"(d[83]),"+f"(d[84]),"+f"(d[85]),"+f"(d[86]),"+f"(d[87]),"+f"(d[88]),"+f"(d[89]),"+f"(d[90]),"+f"(d[91]),"+f"(d[92]),"+f"(d[93]),"+f"(d[94]),"+f"(d[95]),"+f"(d[96]),"+f"(d[97]),"+f"(d[98]),"+f"(d[99]),"+f"(d[100]),"+f"(d[101]),"+f"(d[102]),"+f"(d[103]),"+f"(d[104]),"+f"(d[105]),"+f"(d[106]),"+f"(d[107]),"+f"(d[108]),"+f"(d[109]),"+f"(d[110]),"+f"(d[111])
    : "r"(alo), "r"(blo), "n"(AOFF), "n"(AHI), "n"(BOFF), "n"(BHI), "n"(ACC));
}
template <int AOFF, uint32_t AHI, int BOFF, uint32_t BHI, int ACC>
__device__ __forceinline__ void wgmma_ss232(float (&d)[116], uint32_t alo, uint32_t blo) {
  asm volatile("{\n.reg .pred p;\n.reg .b64 ad, bd;\nsetp.ne.b32 p, %122, 0;\n"
    "mov.b64 ad, {%116, %119};\nadd.s64 ad, ad, %118;\nmov.b64 bd, {%117, %121};\nadd.s64 bd, bd, %120;\n"
    "wgmma.mma_async.sync.aligned.m64n232k16.f32.bf16.bf16 {%0,%1,%2,%3,%4,%5,%6,%7,%8,%9,%10,%11,%12,%13,%14,%15,%16,%17,%18,%19,%20,%21,%22,%23,%24,%25,%26,%27,%28,%29,%30,%31,%32,%33,%34,%35,%36,%37,%38,%39,%40,%41,%42,%43,%44,%45,%46,%47,%48,%49,%50,%51,%52,%53,%54,%55,%56,%57,%58,%59,%60,%61,%62,%63,%64,%65,%66,%67,%68,%69,%70,%71,%72,%73,%74,%75,%76,%77,%78,%79,%80,%81,%82,%83,%84,%85,%86,%87,%88,%89,%90,%91,%92,%93,%94,%95,%96,%97,%98,%99,%100,%101,%102,%103,%104,%105,%106,%107,%108,%109,%110,%111,%112,%113,%114,%115}, ad, bd, p, 1, 1, 1, 1;\n}\n"
    : "+f"(d[0]),"+f"(d[1]),"+f"(d[2]),"+f"(d[3]),"+f"(d[4]),"+f"(d[5]),"+f"(d[6]),"+f"(d[7]),"+f"(d[8]),"+f"(d[9]),"+f"(d[10]),"+f"(d[11]),"+f"(d[12]),"+f"(d[13]),"+f"(d[14]),"+f"(d[15]),"+f"(d[16]),"+f"(d[17]),"+f"(d[18]),"+f"(d[19]),"+f"(d[20]),"+f"(d[21]),"+f"(d[22]),"+f"(d[23]),"+f"(d[24]),"+f"(d[25]),"+f"(d[26]),"+f"(d[27]),"+f"(d[28]),"+f"(d[29]),"+f"(d[30]),"+f"(d[31]),"+f"(d[32]),"+f"(d[33]),"+f"(d[34]),"+f"(d[35]),"+f"(d[36]),"+f"(d[37]),"+f"(d[38]),"+f"(d[39]),"+f"(d[40]),"+f"(d[41]),"+f"(d[42]),"+f"(d[43]),"+f"(d[44]),"+f"(d[45]),"+f"(d[46]),"+f"(d[47]),"+f"(d[48]),"+f"(d[49]),"+f"(d[50]),"+f"(d[51]),"+f"(d[52]),"+f"(d[53]),"+f"(d[54]),"+f"(d[55]),"+f"(d[56]),"+f"(d[57]),"+f"(d[58]),"+f"(d[59]),"+f"(d[60]),"+f"(d[61]),"+f"(d[62]),"+f"(d[63]),"+f"(d[64]),"+f"(d[65]),"+f"(d[66]),"+f"(d[67]),"+f"(d[68]),"+f"(d[69]),"+f"(d[70]),"+f"(d[71]),"+f"(d[72]),"+f"(d[73]),"+f"(d[74]),"+f"(d[75]),"+f"(d[76]),"+f"(d[77]),"+f"(d[78]),"+f"(d[79]),"+f"(d[80]),"+f"(d[81]),"+f"(d[82]),"+f"(d[83]),"+f"(d[84]),"+f"(d[85]),"+f"(d[86]),"+f"(d[87]),"+f"(d[88]),"+f"(d[89]),"+f"(d[90]),"+f"(d[91]),"+f"(d[92]),"+f"(d[93]),"+f"(d[94]),"+f"(d[95]),"+f"(d[96]),"+f"(d[97]),"+f"(d[98]),"+f"(d[99]),"+f"(d[100]),"+f"(d[101]),"+f"(d[102]),"+f"(d[103]),"+f"(d[104]),"+f"(d[105]),"+f"(d[106]),"+f"(d[107]),"+f"(d[108]),"+f"(d[109]),"+f"(d[110]),"+f"(d[111]),"+f"(d[112]),"+f"(d[113]),"+f"(d[114]),"+f"(d[115])
    : "r"(alo), "r"(blo), "n"(AOFF), "n"(AHI), "n"(BOFF), "n"(BHI), "n"(ACC));
}
template <int OFF, uint32_t BHI, int ACC>
__device__ __forceinline__ void wgmma_rs224(float (&d)[112], uint32_t a0, uint32_t a1, uint32_t a2, uint32_t a3, uint32_t blo) {
  asm volatile("{\n.reg .pred p;\n.reg .b64 bd;\nsetp.ne.b32 p, %119, 0;\nmov.b64 bd, {%116, %118};\nadd.s64 bd, bd, %117;\n"
    "wgmma.mma_async.sync.aligned.m64n224k16.f32.bf16.bf16 {%0,%1,%2,%3,%4,%5,%6,%7,%8,%9,%10,%11,%12,%13,%14,%15,%16,%17,%18,%19,%20,%21,%22,%23,%24,%25,%26,%27,%28,%29,%30,%31,%32,%33,%34,%35,%36,%37,%38,%39,%40,%41,%42,%43,%44,%45,%46,%47,%48,%49,%50,%51,%52,%53,%54,%55,%56,%57,%58,%59,%60,%61,%62,%63,%64,%65,%66,%67,%68,%69,%70,%71,%72,%73,%74,%75,%76,%77,%78,%79,%80,%81,%82,%83,%84,%85,%86,%87,%88,%89,%90,%91,%92,%93,%94,%95,%96,%97,%98,%99,%100,%101,%102,%103,%104,%105,%106,%107,%108,%109,%110,%111}, {%112,%113,%114,%115}, bd, p, 1, 1, 1;\n}\n"
    : "+f"(d[0]),"+f"(d[1]),"+f"(d[2]),"+f"(d[3]),"+f"(d[4]),"+f"(d[5]),"+f"(d[6]),"+f"(d[7]),"+f"(d[8]),"+f"(d[9]),"+f"(d[10]),"+f"(d[11]),"+f"(d[12]),"+f"(d[13]),"+f"(d[14]),"+f"(d[15]),"+f"(d[16]),"+f"(d[17]),"+f"(d[18]),"+f"(d[19]),"+f"(d[20]),"+f"(d[21]),"+f"(d[22]),"+f"(d[23]),"+f"(d[24]),"+f"(d[25]),"+f"(d[26]),"+f"(d[27]),"+f"(d[28]),"+f"(d[29]),"+f"(d[30]),"+f"(d[31]),"+f"(d[32]),"+f"(d[33]),"+f"(d[34]),"+f"(d[35]),"+f"(d[36]),"+f"(d[37]),"+f"(d[38]),"+f"(d[39]),"+f"(d[40]),"+f"(d[41]),"+f"(d[42]),"+f"(d[43]),"+f"(d[44]),"+f"(d[45]),"+f"(d[46]),"+f"(d[47]),"+f"(d[48]),"+f"(d[49]),"+f"(d[50]),"+f"(d[51]),"+f"(d[52]),"+f"(d[53]),"+f"(d[54]),"+f"(d[55]),"+f"(d[56]),"+f"(d[57]),"+f"(d[58]),"+f"(d[59]),"+f"(d[60]),"+f"(d[61]),"+f"(d[62]),"+f"(d[63]),"+f"(d[64]),"+f"(d[65]),"+f"(d[66]),"+f"(d[67]),"+f"(d[68]),"+f"(d[69]),"+f"(d[70]),"+f"(d[71]),"+f"(d[72]),"+f"(d[73]),"+f"(d[74]),"+f"(d[75]),"+f"(d[76]),"+f"(d[77]),"+f"(d[78]),"+f"(d[79]),"+f"(d[80]),"+f"(d[81]),"+f"(d[82]),"+f"(d[83]),"+f"(d[84]),"+f"(d[85]),"+f"(d[86]),"+f"(d[87]),"+f"(d[88]),"+f"(d[89]),"+f"(d[90]),"+f"(d[91]),"+f"(d[92]),"+f"(d[93]),"+f"(d[94]),"+f"(d[95]),"+f"(d[96]),"+f"(d[97]),"+f"(d[98]),"+f"(d[99]),"+f"(d[100]),"+f"(d[101]),"+f"(d[102]),"+f"(d[103]),"+f"(d[104]),"+f"(d[105]),"+f"(d[106]),"+f"(d[107]),"+f"(d[108]),"+f"(d[109]),"+f"(d[110]),"+f"(d[111])
    : "r"(a0), "r"(a1), "r"(a2), "r"(a3), "r"(blo), "n"(OFF), "n"(BHI), "n"(ACC));
}
template <int OFF, uint32_t BHI, int ACC>
__device__ __forceinline__ void wgmma_rs56(float (&d)[28], uint32_t a0, uint32_t a1, uint32_t a2, uint32_t a3, uint32_t blo) {
  asm volatile("{\n.reg .pred p;\n.reg .b64 bd;\nsetp.ne.b32 p, %35, 0;\nmov.b64 bd, {%32, %34};\nadd.s64 bd, bd, %33;\n"
    "wgmma.mma_async.sync.aligned.m64n56k16.f32.bf16.bf16 {%0,%1,%2,%3,%4,%5,%6,%7,%8,%9,%10,%11,%12,%13,%14,%15,%16,%17,%18,%19,%20,%21,%22,%23,%24,%25,%26,%27}, {%28,%29,%30,%31}, bd, p, 1, 1, 1;\n}\n"
    : "+f"(d[0]),"+f"(d[1]),"+f"(d[2]),"+f"(d[3]),"+f"(d[4]),"+f"(d[5]),"+f"(d[6]),"+f"(d[7]),"+f"(d[8]),"+f"(d[9]),"+f"(d[10]),"+f"(d[11]),"+f"(d[12]),"+f"(d[13]),"+f"(d[14]),"+f"(d[15]),"+f"(d[16]),"+f"(d[17]),"+f"(d[18]),"+f"(d[19]),"+f"(d[20]),"+f"(d[21]),"+f"(d[22]),"+f"(d[23]),"+f"(d[24]),"+f"(d[25]),"+f"(d[26]),"+f"(d[27])
    : "r"(a0), "r"(a1), "r"(a2), "r"(a3), "r"(blo), "n"(OFF), "n"(BHI), "n"(ACC));
}

__device__ __forceinline__ void st128(uint4* p, uint32_t a, uint32_t b, uint32_t c, uint32_t d) {
  asm volatile("{\n.reg .b128 v;\n.reg .b64 lo, hi;\nmov.b64 lo, {%1, %2};\nmov.b64 hi, {%3, %4};\nmov.b128 v, {lo, hi};\n"
               "st.relaxed.gpu.global.b128 [%0], v;\n}" ::"l"(p), "r"(a), "r"(b), "r"(c), "r"(d) : "memory");
}
__device__ __forceinline__ void ld128(const uint4* p, uint32_t* r) {
  asm volatile("{\n.reg .b128 v;\n.reg .b64 lo, hi;\nld.relaxed.gpu.global.b128 v, [%4];\nmov.b128 {lo, hi}, v;\n"
               "mov.b64 {%0, %1}, lo;\nmov.b64 {%2, %3}, hi;\n}" : "=r"(r[0]), "=r"(r[1]), "=r"(r[2]), "=r"(r[3]) : "l"(p) : "memory");
}

template <int OFF, uint32_t BHI, int ACC>
__device__ __forceinline__ void wgmma_rs32(float (&d)[16], uint32_t a0, uint32_t a1, uint32_t a2, uint32_t a3, uint32_t blo) {
  asm volatile("{\n.reg .pred p;\n.reg .b64 bd;\nsetp.ne.b32 p, %23, 0;\nmov.b64 bd, {%20, %22};\nadd.s64 bd, bd, %21;\n"
    "wgmma.mma_async.sync.aligned.m64n32k16.f32.bf16.bf16 {%0,%1,%2,%3,%4,%5,%6,%7,%8,%9,%10,%11,%12,%13,%14,%15}, {%16,%17,%18,%19}, bd, p, 1, 1, 0;\n}\n"
    : "+f"(d[0]),"+f"(d[1]),"+f"(d[2]),"+f"(d[3]),"+f"(d[4]),"+f"(d[5]),"+f"(d[6]),"+f"(d[7]),"+f"(d[8]),"+f"(d[9]),"+f"(d[10]),"+f"(d[11]),"+f"(d[12]),"+f"(d[13]),"+f"(d[14]),"+f"(d[15])
    : "r"(a0), "r"(a1), "r"(a2), "r"(a3), "r"(blo), "n"(OFF), "n"(BHI), "n"(ACC));
}
template <int OFF, uint32_t BHI, int ACC>
__device__ __forceinline__ void wgmma_rs24(float (&d)[12], uint32_t a0, uint32_t a1, uint32_t a2, uint32_t a3, uint32_t blo) {
  asm volatile("{\n.reg .pred p;\n.reg .b64 bd;\nsetp.ne.b32 p, %19, 0;\nmov.b64 bd, {%16, %18};\nadd.s64 bd, bd, %17;\n"
    "wgmma.mma_async.sync.aligned.m64n24k16.f32.bf16.bf16 {%0,%1,%2,%3,%4,%5,%6,%7,%8,%9,%10,%11}, {%12,%13,%14,%15}, bd, p, 1, 1, 1;\n}\n"
    : "+f"(d[0]),"+f"(d[1]),"+f"(d[2]),"+f"(d[3]),"+f"(d[4]),"+f"(d[5]),"+f"(d[6]),"+f"(d[7]),"+f"(d[8]),"+f"(d[9]),"+f"(d[10]),"+f"(d[11])
    : "r"(a0), "r"(a1), "r"(a2), "r"(a3), "r"(blo), "n"(OFF), "n"(BHI), "n"(ACC));
}
template <int OFF, uint32_t BHI, int ACC>
__device__ __forceinline__ void wgmma_rs16(float (&d)[8], uint32_t a0, uint32_t a1, uint32_t a2, uint32_t a3, uint32_t blo) {
  asm volatile("{\n.reg .pred p;\n.reg .b64 bd;\nsetp.ne.b32 p, %15, 0;\nmov.b64 bd, {%12, %14};\nadd.s64 bd, bd, %13;\n"
    "wgmma.mma_async.sync.aligned.m64n16k16.f32.bf16.bf16 {%0,%1,%2,%3,%4,%5,%6,%7}, {%8,%9,%10,%11}, bd, p, 1, 1, 1;\n}\n"
    : "+f"(d[0]),"+f"(d[1]),"+f"(d[2]),"+f"(d[3]),"+f"(d[4]),"+f"(d[5]),"+f"(d[6]),"+f"(d[7])
    : "r"(a0), "r"(a1), "r"(a2), "r"(a3), "r"(blo), "n"(OFF), "n"(BHI), "n"(ACC));
}

constexpr int A_R1 = 0;
constexpr int A_R2A = A_R1 + 2624, A_R2B = A_R2A + 768, A_R3A = A_R2B + 768, A_R3B = A_R3A + 528;
constexpr int A_K1024 = A_R3B + 528;
constexpr int A_W5 = A_K1024 + 16;
constexpr int A_W3 = A_W5 + 4096;
constexpr int A_W9 = A_W3 + 4112;
constexpr int A_W7 = A_W9 + 2080;
constexpr int A_V  = A_W7 + 2080;
constexpr int A_SCL = A_V + 2048;
constexpr int A_UB = A_SCL + 16;
constexpr int A_STG = A_UB + 5248;
constexpr int A_Y2 = A_STG, A_Y3 = A_Y2 + 6528, A_YB = A_Y3 + 4352;
constexpr int A_REC = (A_STG + 4 * 4352 + 255) / 256 * 256;
constexpr int A_CH = A_REC + 8192;
constexpr int A_BAR = 4 * A_CH, A_WST = (A_BAR + 128 + 511) / 512 * 512;
static_assert(A_W5 % 16 == 0 && A_UB % 16 == 0 && A_CH % 16 == 0 && A_YB + 4096 <= A_REC, "layout");

struct cf { float x, y; };
__device__ __forceinline__ cf cmul(cf a, cf b) { cf r; r.x = fmaf(a.x, b.x, -a.y * b.y); r.y = fmaf(a.x, b.y, a.y * b.x); return r; }
__device__ __forceinline__ cf cexp_l(float lr, float li, float l) {
  float mag; asm("ex2.approx.ftz.f32 %0, %1;" : "=f"(mag) : "f"((lr * l) * 1.4426950408889634f));
  const float th = li * l;
  const float k = (fmaf(th, 0.15915494f, 12582912.f)) - 12582912.f;
  float ph = fmaf(th, 0.15915494f, -k);
  ph = fmaf(th, 6.4206383e-9f, ph) * 6.2831853f;
  cf r; r.x = mag * __cosf(ph); r.y = mag * __sinf(ph); return r;
}
__device__ __forceinline__ void sts16(uint32_t a, uint32_t v) { asm volatile("st.shared.u16 [%0], %1;" ::"r"(a), "h"((uint16_t)v) : "memory"); }
__device__ __forceinline__ void sts32(uint32_t a, uint32_t v) { asm volatile("st.shared.u32 [%0], %1;" ::"r"(a), "r"(v) : "memory"); }
__device__ __forceinline__ void sts64(uint32_t a, uint32_t v0, uint32_t v1) { asm volatile("st.shared.v2.u32 [%0], {%1, %2};" ::"r"(a), "r"(v0), "r"(v1) : "memory"); }
__device__ __forceinline__ void sts128(uint32_t a, uint32_t v0, uint32_t v1, uint32_t v2, uint32_t v3) {
  asm volatile("st.shared.v4.u32 [%0], {%1, %2, %3, %4};" ::"r"(a), "r"(v0), "r"(v1), "r"(v2), "r"(v3) : "memory");
}
__device__ __forceinline__ uint32_t lds32(uint32_t a) { uint32_t v; asm volatile("ld.shared.u32 %0, [%1];" : "=r"(v) : "r"(a) : "memory"); return v; }
__device__ __forceinline__ uint4 lds128(uint32_t a) {
  uint4 v; asm volatile("ld.shared.v4.u32 {%0, %1, %2, %3}, [%4];" : "=r"(v.x), "=r"(v.y), "=r"(v.z), "=r"(v.w) : "r"(a) : "memory"); return v;
}
__device__ __forceinline__ void ldsm4(uint32_t* r, uint32_t a) {
  asm volatile("ldmatrix.sync.aligned.m8n8.x4.shared.b16 {%0,%1,%2,%3}, [%4];" : "=r"(r[0]), "=r"(r[1]), "=r"(r[2]), "=r"(r[3]) : "r"(a) : "memory");
}
__device__ __forceinline__ void mma16816(float* d, uint32_t a0, uint32_t a1, uint32_t a2, uint32_t a3, uint32_t b0, uint32_t b1) {
  asm volatile("mma.sync.aligned.m16n8k16.row.col.f32.f16.f16.f32 {%0,%1,%2,%3}, {%4,%5,%6,%7}, {%8,%9}, {%0,%1,%2,%3};"
               : "+f"(d[0]), "+f"(d[1]), "+f"(d[2]), "+f"(d[3]) : "r"(a0), "r"(a1), "r"(a2), "r"(a3), "r"(b0), "r"(b1));
}
__device__ __forceinline__ uint32_t pack_h(float lo, float hi) { uint32_t r; asm("cvt.rn.f16x2.f32 %0, %1, %2;" : "=r"(r) : "f"(hi), "f"(lo)); return r; }
__device__ __forceinline__ uint32_t pack_h(cf v) { return pack_h(v.x, v.y); }
__device__ __forceinline__ uint32_t hcmul(uint32_t x, uint32_t r0, uint32_t r1) {
  const __half2 hx = *(__half2*)&x;
  const __half2 y = __hfma2(__high2half2(hx), *(__half2*)&r1, __hmul2(__low2half2(hx), *(__half2*)&r0));
  return *(const uint32_t*)&y;
}
__device__ __forceinline__ float ln_rstd(float var) {
  float sd, rs;
  asm("sqrt.approx.ftz.f32 %0, %1;" : "=f"(sd) : "f"(rbf(rbf(var) + 1e-5f)));
  asm("rcp.approx.ftz.f32 %0, %1;" : "=f"(rs) : "f"(rbf(sd)));
  return rs;
}
__device__ __forceinline__ uint32_t hsub2_bf(uint32_t a, uint32_t b) { uint32_t r; asm("sub.rn.bf16x2 %0, %1, %2;" : "=r"(r) : "r"(a), "r"(b)); return r; }
__device__ __forceinline__ void bar_sync(int id, int n) { asm volatile("bar.sync %0, %1;" ::"r"(id), "r"(n) : "memory"); }

template <int S> struct F1B { static constexpr int cc = (16 * S) / 64, ks = (64 * cc - (16 * S - 48)) / 16, off = (A_UB + 2 * ks * 656 + (9 - cc) * 16) / 16; };

template <int NS>
__device__ __forceinline__ void load_quads(uint32_t* q, uint32_t addr) {
#pragma unroll
  for (int i = 0; i < NS; i++) {
    q[4 * i] = lds32(addr + i * 64); q[4 * i + 1] = lds32(addr + i * 64 + 32);
    q[4 * i + 2] = i ? q[4 * i - 3] : lds32(addr - 32);
    q[4 * i + 3] = q[4 * i];
  }
#pragma unroll
  for (int i = 0; i < 4 * NS; i++) asm volatile("" : "+r"(q[i]));
}
template <int S0, int NS>
__device__ __forceinline__ void f1_steps(float (&acc)[16], const uint32_t* a, uint32_t blo) {
  if constexpr (NS > 0) {
    wgmma_rs32<F1B<S0>::off, 8, S0 != 0>(acc, a[0], a[1], a[2], a[3], blo);
    f1_steps<S0 + 1, NS - 1>(acc, a + 4, blo);
  }
}
template <int S0, int NS, int BASE, int FIRST>
__device__ __forceinline__ void s2_steps(float (&acc)[12], const uint32_t* a, uint32_t blo) {
  if constexpr (NS > 0) {
    wgmma_rs24<BASE / 16 + (112 - 16 * S0), 64, !(FIRST && S0 == 0)>(acc, a[0], a[1], a[2], a[3], blo);
    s2_steps<S0 + 1, NS - 1, BASE, FIRST>(acc, a + 4, blo);
  }
}
template <int S0, int NS, int BASE, int FIRST>
__device__ __forceinline__ void s3_steps(float (&acc)[8], const uint32_t* a, uint32_t blo) {
  if constexpr (NS > 0) {
    wgmma_rs16<BASE / 16 + (48 - 16 * S0), 65, !(FIRST && S0 == 0)>(acc, a[0], a[1], a[2], a[3], blo);
    s3_steps<S0 + 1, NS - 1, BASE, FIRST>(acc, a + 4, blo);
  }
}

__device__ __forceinline__ void tma3d(uint32_t dst, const CUtensorMap* m, int c1, int c2, uint32_t bar) {
  asm volatile("cp.async.bulk.tensor.3d.shared::cluster.global.mbarrier::complete_tx::bytes [%0], [%1, {0, %3, %4}], [%2];"
               ::"r"(dst), "l"(m), "r"(bar), "r"(c1), "r"(c2) : "memory");
}
__device__ __forceinline__ void bulk_st(void* dst, uint32_t src, int bytes) {
  asm volatile("cp.async.bulk.global.shared::cta.bulk_group [%0], [%1], %2;" ::"l"(dst), "r"(src), "r"(bytes) : "memory");
}

__device__ __forceinline__ void phase_a(
        unsigned char* sm, const uint32_t bar_rec, const CUtensorMap* mg, const CUtensorMap* mu, const CUtensorMap* md, const CUtensorMap* mx, const CUtensorMap* ml,
        const __nv_bfloat16* __restrict__ x, const uint32_t* __restrict__ are, const uint32_t* __restrict__ aim,
        const uint32_t* __restrict__ bre, const uint32_t* __restrict__ bim, const uint32_t* __restrict__ cre,
        const uint32_t* __restrict__ cim, const unsigned short* __restrict__ logdt, const unsigned short* __restrict__ dskip,
        const uint4* __restrict__ wgate, const uint4* __restrict__ wup) {
  const uint32_t sb = s2u(sm), bar_w = bar_rec + 16;
  const int tid = threadIdx.x, warp = __shfl_sync(~0u, tid >> 5, 0), wg = warp >> 2, lane = tid & 31, wq = warp & 3, t128 = tid & 127;
  const int blk = blockIdx.x;
  const bool conv = (blk & 7) != 7;
  const int cblk = blk - (blk >> 3);

  uint2 xr[4];
  {
    const uint2* p = (const uint2*)(x + (size_t)(blk * 16 + warp) * DM) + lane;
#pragma unroll
    for (int i = 0; i < 3; i++) asm volatile("ld.global.nc.v2.u32 {%0, %1}, [%2];" : "=r"(xr[i].x), "=r"(xr[i].y) : "l"(p + 32 * i));
    xr[3] = make_uint2(0, 0);
    if (lane < 16) asm volatile("ld.global.nc.v2.u32 {%0, %1}, [%2];" : "=r"(xr[3].x), "=r"(xr[3].y) : "l"(p + 96));
  }
  const int ch = conv ? cblk * 4 + wg : 0;
  const uint32_t cb = sb + wg * A_CH;
  uint32_t prm[6], ldt;
  {
    const int i = ch * 128 + t128;
    const uint32_t* const ps[6] = {are, aim, bre, bim, cre, cim};
#pragma unroll
    for (int k = 0; k < 6; k++) asm volatile("ld.global.nc.u32 %0, [%1];" : "=r"(prm[k]) : "l"(ps[k] + i));
    asm volatile("ld.global.nc.u16 %0, [%1];" : "=r"(ldt) : "l"(logdt + ch));
  }
  uint32_t cnt0 = 0;
  if (tid == 160) asm volatile("ld.relaxed.gpu.global.u32 %0, [%1];" : "=r"(cnt0) : "l"(&g_cnt1));
  if (tid == 192) {
    mbar_init(bar_rec, 1); mbar_init(bar_rec + 8, 1);
    for (int i = 0; i < 6; i++) mbar_init(bar_rec + 16 + 8 * i, 1);
    asm volatile("fence.mbarrier_init.release.cluster;" ::: "memory");
    asm volatile("prefetch.tensormap [%0];" ::"l"(mx)); asm volatile("prefetch.tensormap [%0];" ::"l"(ml)); asm volatile("prefetch.tensormap [%0];" ::"l"(mg)); asm volatile("prefetch.tensormap [%0];" ::"l"(mu)); asm volatile("prefetch.tensormap [%0];" ::"l"(md));
  }
  const int g = lane >> 2, t = lane & 3;
  if (conv) {
#pragma unroll
    for (int i = 0; i < 4; i++) if (i < 3 || t128 < (A_W5 + 1024) / 16 - 384) sts128(cb + (i * 128 + t128) * 16, 0, 0, 0, 0);
    if (t128 < 64) sts128(cb + A_W3 + t128 * 16, 0, 0, 0, 0);
    if (t128 < 72) sts128(cb + A_UB + (t128 / 9) * 656 + (t128 % 9) * 16, 0, 0, 0, 0);
  }
  {
    float s = 0.f, q = 0.f;
#pragma unroll
    for (int i = 0; i < 4; i++) {
      const float a = bf_lo(xr[i].x), b = bf_hi(xr[i].x), c = bf_lo(xr[i].y), d = bf_hi(xr[i].y);
      s += (a + b) + (c + d);
      q = fmaf(a, a, q); q = fmaf(b, b, q); q = fmaf(c, c, q); q = fmaf(d, d, q);
    }
#pragma unroll
    for (int o = 16; o; o >>= 1) { s += __shfl_xor_sync(~0u, s, o); q += __shfl_xor_sync(~0u, q, o); }
    const float mean = s * (1.f / DM);
    const float var = fmaxf(fmaf(-mean, mean, q * (1.f / DM)), 0.f);
    const float rs = ln_rstd(var);
    const uint32_t mm = pack_bf16(mean, mean);
    const uint32_t tu = sb + A_REC + (warp >> 3) * A_CH + (warp & 7) * 912 + lane * 8, tx = tu + 2 * A_CH;
#pragma unroll
    for (int i = 0; i < 4; i++) {
      if (i < 3 || lane < 16) {
        const uint32_t d0 = hsub2_bf(xr[i].x, mm), d1 = hsub2_bf(xr[i].y, mm);
        sts64(tu + i * 256, pack_bf16(bf_lo(d0) * rs, bf_hi(d0) * rs), pack_bf16(bf_lo(d1) * rs, bf_hi(d1) * rs));
        sts64(tx + i * 256, xr[i].x, xr[i].y);
      }
    }
  }
  cnt0 = pin(cnt0);
  if (tid == 320) TR(0, 1);
  auto publish_rows = [&]() {
    bar_sync(5, 512);
    uint32_t r[4][4];
#pragma unroll
    for (int i = 0; i < 4; i++)
      if (i < 3 || warp < 8)
        asm volatile("ldmatrix.sync.aligned.m8n8.x4.trans.shared.b16 {%0,%1,%2,%3}, [%4];" : "=r"(r[i][0]), "=r"(r[i][1]), "=r"(r[i][2]), "=r"(r[i][3])
                     : "r"(sb + A_REC + (lane >> 3) * A_CH + (lane & 7) * 912 + (warp + 16 * i) * 16) : "memory");
#pragma unroll
    for (int i = 0; i < 4; i++)
      if (i < 3 || warp < 8)
        asm volatile("stmatrix.sync.aligned.m8n8.x4.shared.b16 [%0], {%1,%2,%3,%4};"
                     ::"r"(sb + A_WST + (warp + 16 * i) * 512 + (lane & 7) * 64 + (((lane >> 3) ^ (lane >> 1)) & 3) * 16),
                       "r"(r[i][0]), "r"(r[i][1]), "r"(r[i][2]), "r"(r[i][3]) : "memory");
    asm volatile("fence.proxy.async.shared::cta;" ::: "memory");
    if (warp != 0) asm volatile("bar.arrive 6, 512;" ::: "memory");
    else {
      bar_sync(6, 512);
      if (lane == 0) {
#pragma unroll
        for (int i = 0; i < 2; i++)
          asm volatile("cp.async.bulk.tensor.3d.global.shared::cta.bulk_group [%0, {0, %2, %3}], [%1];"
                       ::"l"(mx), "r"(sb + A_WST + i * 14336), "r"(blk), "r"(i * 224) : "memory");
        asm volatile("cp.async.bulk.commit_group;" ::: "memory");
      }
      __syncwarp();
    }
  };
  auto release_rows = [&]() {
    if (tid == 0) {
      asm volatile("cp.async.bulk.wait_group 0;" ::: "memory");
      asm volatile("fence.proxy.async.global;" ::: "memory");
      asm volatile("red.release.gpu.global.add.u32 [%0], 1;" ::"l"(&g_cnt1) : "memory");
      TR(0, 8);
    }
    __syncwarp();
  };
  auto wd_load = [&]() { mbar_expect(bar_w + 8, 12544); tma3d(sb + A_WST, md, (blk >> 3) * 112, (blk & 7) * 7, bar_w + 8); };
  auto wd_store = [&]() {
    mbar_wait(bar_w + 8, 0);
    bulk_st(g_wimg + (size_t)(blk >> 4) * 37632 + 25088 + ((blk & 7) * 2 + ((blk >> 3) & 1)) * 784, sb + A_WST, 12544);
  };
  if (!conv) {
    const int a = blk >> 3, mat = a >> 3, j = a & 7;
    publish_rows();
    release_rows();
    bar_sync(7, 512);
    if (warp >= 14) {
      if (tid == 480) {
        wd_load(); wd_store();
        asm volatile("cp.async.bulk.commit_group;" ::: "memory");
        asm volatile("cp.async.bulk.wait_group 0;" ::: "memory");
        TR(0, 10);
      }
      return;
    }
    float s[8];
#pragma unroll
    for (int k = 0; k < 8; k++) s[k] = 0.f;
    if (lane < 28) {
      const uint4* src = (mat ? wup : wgate) + j * 28 + lane + (size_t)warp * 224;
#pragma unroll
      for (int hb = 0; hb < 2; hb++) {
        uint4 v[16];
#pragma unroll
        for (int r = 0; r < 16; r++) v[r] = __ldg(src + (size_t)(hb * 16 + r) * 14 * 224);
#pragma unroll
        for (int r = 0; r < 16; r++) {
          s[0] += bf_lo(v[r].x); s[1] += bf_hi(v[r].x); s[2] += bf_lo(v[r].y); s[3] += bf_hi(v[r].y);
          s[4] += bf_lo(v[r].z); s[5] += bf_hi(v[r].z); s[6] += bf_lo(v[r].w); s[7] += bf_hi(v[r].w);
        }
      }
      float4* red = (float4*)(sm + 25088 + warp * 896 + lane * 32);
      red[0] = make_float4(s[0], s[1], s[2], s[3]); red[1] = make_float4(s[4], s[5], s[6], s[7]);
    }
    bar_sync(5, 448);
    if (tid < 224) {
      float cs = 0.f;
#pragma unroll
      for (int w = 0; w < 14; w++) cs += *(const float*)(sm + 25088 + w * 896 + tid * 4);
      const float hi = rbf(cs), mid = rbf(cs - hi), lo = rbf(cs - hi - mid);
      const int q = tid / 112, n = tid % 112 + 112 * mat;
      __nv_bfloat16* dst = (__nv_bfloat16*)(g_cimg + (j * 2 + q) * 224 + (n >> 3) * 8) + (n & 7);
      dst[0] = __float2bfloat16_rn(hi); dst[8] = __float2bfloat16_rn(mid); dst[16] = __float2bfloat16_rn(lo);
#pragma unroll
      for (int k = 3; k < 8; k++) dst[8 * k] = __float2bfloat16_rn(0.f);
    }
    if (tid == 0) TR(0, 11);
    return;
  }

  publish_rows();
  const int wr = (wq + wg) & 3;
  const int bk = wr * 32 + lane;
  {
    const uint32_t stg = cb + A_STG + wq * 4352, sw = stg + lane * 8;
    const float dt = rbf(expf(__uint_as_float(ldt << 16)));
    float lr[2], li[2];
    cf bq[2], b0[2], b4[2];
    uint32_t bf[48], cv = 0;
#pragma unroll
    for (int m = 0; m < 2; m++) {
      lr[m] = dt * (m ? bf_hi(prm[0]) : bf_lo(prm[0]));
      li[m] = dt * (m ? bf_hi(prm[1]) : bf_lo(prm[1]));
    }
    {
      cf b[2], z[2];
#pragma unroll
      for (int m = 0; m < 2; m++) {
        cf db, c;
        db.x = dt * (m ? bf_hi(prm[2]) : bf_lo(prm[2])); db.y = -dt * (m ? bf_hi(prm[3]) : bf_lo(prm[3]));
        c.x = m ? bf_hi(prm[4]) : bf_lo(prm[4]); c.y = -(m ? bf_hi(prm[5]) : bf_lo(prm[5]));
        b[m] = cmul(c, db);
        z[m] = cexp_l(lr[m], -li[m], 1.f);
        bq[m] = cexp_l(lr[m], -li[m], 256.f);
      }
      {
        const float mx = fmaxf(fmaxf(fabsf(b[0].x), fabsf(b[0].y)), fmaxf(fabsf(b[1].x), fabsf(b[1].y)));
        const uint32_t e = max(__reduce_max_sync(~0u, __float_as_uint(mx)) >> 23, 14u);
        const float sc = __uint_as_float((267u - e) << 23);
        b[0].x *= sc; b[0].y *= sc; b[1].x *= sc; b[1].y *= sc;
        if (lane == 0) sts32(cb + A_SCL + wq * 4, (e - 13u) << 23);
      }
#pragma unroll
      for (int i = 0; i < 8; i++) {
        sts64(sw + i * 272, pack_h(b[0]), pack_h(b[1]));
        if (!(i & 1)) {
          cf e0 = cmul(b[0], bq[0]), e1 = cmul(b[1], bq[1]);
          sts64(sw + (8 + i / 2) * 272, pack_h(e0), pack_h(e1));
          if (i == 0) { b0[0] = e0; b0[1] = e1; }
          if (i == 4) { b4[0] = e0; b4[1] = e1; }
        }
        if (i < 7) { b[0] = cmul(b[0], z[0]); b[1] = cmul(b[1], z[1]); }
        if (i == 1) release_rows();
      }
#pragma unroll
      for (int i = 0; i < 7; i++) {
        b0[0] = cmul(b0[0], bq[0]); b0[1] = cmul(b0[1], bq[1]);
        sts64(sw + (i < 2 ? 12 + 2 * i : i - 2) * 272, pack_h(b0[0]), pack_h(b0[1]));
        if (i < 2) {
          b4[0] = cmul(b4[0], bq[0]); b4[1] = cmul(b4[1], bq[1]);
          sts64(sw + (13 + 2 * i) * 272, pack_h(b4[0]), pack_h(b4[1]));
        }
        if (i == 1) {
          __syncwarp();
#pragma unroll
          for (int n = 0; n < 2; n++)
#pragma unroll
            for (int k2 = 0; k2 < 4; k2++) ldsm4(bf + n * 16 + k2 * 4, stg + (n * 8 + (lane & 7)) * 272 + k2 * 64 + (lane >> 3) * 16);
          __syncwarp();
          if (tid == 160) asm volatile("ld.relaxed.gpu.global.u32 %0, [%1];" : "=r"(cv) : "l"(&g_cnt1) : "memory");
        }
      }
    }
      if (warp == 5) {
        if (lane == 0) {
          const uint32_t tgt = (cnt0 & ~127u) + 128u;
          int it = 0;
          while ((int)(cv - tgt) < 0 && ++it < 400000) asm volatile("ld.relaxed.gpu.global.u32 %0, [%1];" : "=r"(cv) : "l"(&g_cnt1) : "memory");
          asm volatile("fence.acquire.gpu;" ::: "memory");
          asm volatile("fence.proxy.async.global;" ::: "memory");
          TR(0, 9);
          mbar_expect(bar_rec + 8, 16384);
#pragma unroll
          for (int i = 0; i < 4; i++) mbar_expect(bar_rec + 32 + 8 * i, 4096);
#pragma unroll
          for (int i = 0; i < 8; i++)
            asm volatile("cp.async.bulk.tensor.3d.shared::cluster.global.mbarrier::complete_tx::bytes [%0], [%1, {%3, 0, %4}], [%2];"
                         ::"r"(sb + (3 - (i & 3)) * A_CH + A_REC + (i >> 2) * 4096), "l"(ml), "r"(i < 4 ? bar_rec + 56 - 8 * i : bar_rec + 8), "r"((i >> 2) * 16), "r"(cblk * 4 + 3 - (i & 3)) : "memory");
        }
        __syncwarp();
      }
    {
      const cf p0 = cexp_l(lr[0], li[0], 8.f), p1 = cexp_l(lr[1], li[1], 8.f);
      cf v0 = p0, v1 = p1;
      sts64(sw + 8 * 272, 0x3C00u, 0x3C00u);
#pragma unroll
      for (int i = 1; i < 8; i++) {
        sts64(sw + (8 + i) * 272, pack_h(v0), pack_h(v1));
        v0 = cmul(v0, p0); v1 = cmul(v1, p1);
      }
      const uint32_t ra = stg + 5 * 272 + (lane >> 2) * 64 + (lane & 1) * 32 + (lane & 2) * 4;
      sts64(ra, pack_h(v0), pack_h(-v0.y, v0.x));
      sts64(ra + 16, pack_h(v1), pack_h(-v1.y, v1.x));
    }
    __syncwarp();
    if (tid == 320) TR(0, 16);
#pragma unroll
    for (int k2 = 0; k2 < 4; k2++) ldsm4(bf + 32 + k2 * 4, stg + (lane & 7) * 272 + k2 * 64 + (lane >> 3) * 16);
    float c[6][4];
#pragma unroll
    for (int i = 0; i < 6; i++) { c[i][0] = 0.f; c[i][1] = 0.f; c[i][2] = 0.f; c[i][3] = 0.f; }
#pragma unroll
    for (int k2 = 0; k2 < 4; k2++) {
      uint32_t a[4];
      ldsm4(a, stg + (8 + (lane & 7)) * 272 + k2 * 64 + (lane >> 3) * 16);
#pragma unroll
      for (int kk = 0; kk < 2; kk++) {
        const int ks = 2 * k2 + kk;
        const uint4 r4 = lds128(stg + 5 * 272 + ks * 64 + t * 16);
        const uint32_t r[4] = {r4.x, r4.z, r4.y, r4.w};
        const uint32_t x0 = a[2 * kk], y0 = a[2 * kk + 1];
        const uint32_t x1 = hcmul(x0, r[0], r[2]), y1 = hcmul(y0, r[1], r[3]);
        const uint32_t x2 = hcmul(x1, r[0], r[2]), y2 = hcmul(y1, r[1], r[3]);
        const uint32_t x3 = hcmul(x2, r[0], r[2]), y3 = hcmul(y2, r[1], r[3]);
#pragma unroll
        for (int n = 0; n < 3; n++) {
          mma16816(c[n * 2], x0, x1, y0, y1, bf[n * 16 + ks * 2], bf[n * 16 + ks * 2 + 1]);
          mma16816(c[n * 2 + 1], x2, x3, y2, y3, bf[n * 16 + ks * 2], bf[n * 16 + ks * 2 + 1]);
        }
      }
    }
    __syncwarp();
#pragma unroll
    for (int i = 0; i < 6; i++)
      sts128(stg + i * 512 + lane * 16, __float_as_uint(c[i][0]), __float_as_uint(c[i][1]), __float_as_uint(c[i][2]), __float_as_uint(c[i][3]));
  }
  if (tid == 320) TR(0, 2);

  bar_sync(1 + wg, 128);
  if (wr >= 2) {
    const uint4 sc = lds128(cb + A_SCL);
    const float scl[4] = {__uint_as_float(sc.x), __uint_as_float(sc.y), __uint_as_float(sc.z), __uint_as_float(sc.w)};
#pragma unroll
    for (int qd = 0; qd < 6; qd++) {
      if ((qd < 2) == (wr == 2)) {
        float s[4] = {0.f, 0.f, 0.f, 0.f};
#pragma unroll
        for (int w = 0; w < 4; w++) {
          uint4 u4 = lds128(cb + A_STG + w * 4352 + qd * 512 + lane * 16);
          s[0] = fmaf(__uint_as_float(u4.x), scl[w], s[0]); s[1] = fmaf(__uint_as_float(u4.y), scl[w], s[1]);
          s[2] = fmaf(__uint_as_float(u4.z), scl[w], s[2]); s[3] = fmaf(__uint_as_float(u4.w), scl[w], s[3]);
        }
#pragma unroll
        for (int hf = 0; hf < 2; hf++) {
          const int j0 = (qd & 1) * 16 + 8 * hf, j = j0 + g;
          const uint32_t pk = pack_bf16(s[2 * hf + 1], s[2 * hf]);
          const uint32_t v0 = pk >> 16, v00 = __byte_perm(pk, 0, 0x3232);
          const bool first = j0 == 0 && g == 0;
          if (qd >= 4) {
            uint32_t a = cb + ((g & 1) ? A_R3B : A_R3A) + (64 + 32 * t + (j >> 1)) * 4;
            if (t < 2) { sts16(a + 64, pk); sts16(a + 70, pk); }
            if (first && t == 0) { a = cb + A_R2A + 128 * 4; sts32(cb + A_K1024, pk & 0xFFFF0000u); }
            if (t < 2 || (first && t == 2)) { sts16(a, v0); sts16(a + 6, v0); }
          } else if (qd < 2) {
            const uint32_t a = cb + A_R1 + (62 + 8 * j + 2 * t) * 4;
            sts16(a, v0); sts32(a + 4, pk); sts16(a + 10, pk);
          } else {
            const bool l512 = first && t == 2;
            if (t < 2 || l512) {
              const uint32_t a = cb + A_R1 + (l512 ? 62 + 512 : 62 + 256 + 8 * j + 4 * t) * 4;
              if (first && t == 0) sts16(a, v0); else { sts16(a - 4, v0); sts32(a, v00); }
              sts32(a + 4, v00); sts32(a + 8, l512 ? v00 : pk); sts16(a + 14, l512 ? v0 : pk);
            }
            if (t >= 2) {
              const uint32_t a = cb + A_R2A + (32 * t + j) * 4;
              if (!l512) { sts16(a, v0); sts16(a + 6, v0); }
              sts16(a + (A_R2B - A_R2A), pk); sts16(a + (A_R2B - A_R2A) + 6, pk);
            }
          }
        }
      }
    }
  }
  if (tid == 320) TR(0, 3);
  {
    mbar_wait(bar_rec + 32 + 8 * wg, 0);
    if (tid == 320) TR(0, 4);
    if (tid == 127) {
      asm volatile("griddepcontrol.launch_dependents;" ::: "memory");
      mbar_expect(bar_w, 28672);
#pragma unroll
      for (int i = 0; i < 4; i++) tma3d(sb + A_WST + i * 7168, (i & 1) ? mu : mg, ((cblk % 7) * 2 + (i >> 1)) * 32, (cblk / 7) * 7, bar_w);
    }
    auto rc = [&](int c) { return cb + A_REC + ((c ^ ((c >> 3) & 1)) << 4); };
    const uint4 r0 = lds128(rc(2 * bk)), r1 = lds128(rc(2 * bk + 1));
    const uint32_t ua = cb + A_UB + ((2 * bk) & 7) * 656 + ((bk >> 2) + 9) * 16;
    sts128(ua, r0.x, r0.y, r0.z, r0.w);
    sts128(ua + 656, r1.x, r1.y, r1.z, r1.w);
    if (wr < 3) {
      uint32_t h[4];
      asm volatile("ld.shared.v2.u32 {%0, %1}, [%2];" : "=r"(h[0]), "=r"(h[1]) : "r"(rc((2 * bk - 1) & 255) + 8) : "memory");
      asm volatile("ld.shared.v2.u32 {%0, %1}, [%2];" : "=r"(h[2]), "=r"(h[3]) : "r"(rc(2 * bk + 2)) : "memory");
      if (bk == 0) { h[0] = 0; h[1] = 0; }
      const uint32_t wd[12] = {h[0], h[1], r0.x, r0.y, r0.z, r0.w, r1.x, r1.y, r1.z, r1.w, h[2], h[3]};
      float P[25];
      P[0] = 0.f;
#pragma unroll
      for (int i = 0; i < 12; i++) { P[2 * i + 1] = P[2 * i] + bf_lo(wd[i]); P[2 * i + 2] = P[2 * i + 1] + bf_hi(wd[i]); }
#define WIN(i, hw) (P[(i) + 5 + (hw)] - P[(i) + 4 - (hw)])
#define WPK(i, hw) pack_bf16(WIN(i, hw), WIN((i) + 1, hw))
      const uint32_t a3 = cb + A_W3 + (2 * bk + 64) * 16 + 8, a5 = cb + A_W5 + (2 * bk + 64) * 16;
      sts64(a3, WPK(0, 1), WPK(2, 1));
      sts128(a3 + 8, WPK(4, 1), WPK(6, 1), WPK(8, 1), WPK(10, 1));
      sts64(a3 + 24, WPK(12, 1), WPK(14, 1));
      sts128(a5, WPK(0, 2), WPK(2, 2), WPK(4, 2), WPK(6, 2));
      sts128(a5 + 16, WPK(8, 2), WPK(10, 2), WPK(12, 2), WPK(14, 2));
      if (wr < 2) {
        sts128(cb + A_W7 + 1040 + bk * 16, WPK(0, 3), WPK(2, 3), WPK(4, 3), WPK(6, 3));
        sts128(cb + A_W7 + (bk + 1) * 16, WPK(8, 3), WPK(10, 3), WPK(12, 3), WPK(14, 3));
        sts128(cb + A_W9 + (bk + 1) * 16, WPK(0, 4), WPK(2, 4), WPK(4, 4), WPK(6, 4));
        sts128(cb + A_W9 + 1040 + (bk + 1) * 16, WPK(8, 4), WPK(10, 4), WPK(12, 4), WPK(14, 4));
#define VPK(i) pack_bf16(P[(i) + 2] - P[i], P[(i) + 3] - P[(i) + 1])
        sts128(cb + A_V + bk * 32, VPK(0), VPK(2), VPK(4), VPK(6));
        sts128(cb + A_V + bk * 32 + 16, VPK(8), VPK(10), VPK(12), VPK(14));
        if (bk == 0) {
          const uint32_t s01 = pack_bf16(0.f, P[5]), s12 = pack_bf16(P[5], P[6]), s23 = pack_bf16(P[6], P[7]), s34 = pack_bf16(P[7], P[8]);
          sts64(a3 - 8, 0, s01);
          sts32(a5 - 4, s12);
          sts128(cb + A_W7, 0, 0, s01, s23);
          sts128(cb + A_W9, 0, 0, 0, 0);
          sts128(cb + A_W9 + 1040, 0, 0, s12, s34);
        }
      }
    }
  }
  asm volatile("fence.proxy.async.shared::cta;" ::: "memory");
  bar_sync(1 + wg, 128);
  if (tid == 320) TR(0, 5);

  uint32_t xt[8], ud[8];
  {
    const uint32_t blo_k = ((cb & 0x3FFFF) >> 4) | (41u << 16);
    const uint32_t blo_n = ((cb & 0x3FFFF) >> 4) | (8u << 16);
    const uint32_t tb = cb + (16 * wq + g - 2 * t) * 4;
    float y1[16], y2[12], y3[8];
    const uint32_t dk16 = __ldg(dskip + ch);
    uint32_t qa[32], qb[32];
    const uint32_t t1 = tb + A_R1 + (62 - 48) * 4;
    load_quads<4>(qa, tb + A_R3A + 17 * 4); load_quads<4>(qa + 16, tb + A_R3B + 16 * 4);
    wg_fence();
    s3_steps<0, 4, A_W9, 1>(y3, qa, blo_n); s3_steps<0, 4, A_W7, 0>(y3, qa + 16, blo_n);
    wg_commit();
    load_quads<8>(qb, tb + A_R2A + 16 * 4);
    wg_fence(); s2_steps<0, 8, A_W5, 1>(y2, qb, blo_n); wg_commit();
    if (tid == 127) {
      mbar_wait(bar_w, 0);
      bulk_st(g_wimg + (size_t)(cblk / 14) * 37632 + (cblk % 14) * 1792, sb + A_WST, 28672);
      asm volatile("cp.async.bulk.commit_group;" ::: "memory");
    }
    __syncwarp();
    wg_wait<1>(); load_quads<8>(qa, tb + A_R2B + 16 * 4);
    wg_fence(); s2_steps<0, 8, A_W3, 0>(y2, qa, blo_n); wg_commit();
    wg_wait<1>(); load_quads<8>(qb, t1);
    wg_fence(); f1_steps<0, 8>(y1, qb, blo_k); wg_commit();
    if (tid == 127) { asm volatile("cp.async.bulk.wait_group.read 0;" ::: "memory"); wd_load(); }
    __syncwarp();
    wg_wait<1>(); load_quads<8>(qa, t1 + 8 * 64);
    wg_fence(); f1_steps<8, 8>(y1, qa, blo_k); wg_commit();
    reg_fence(y2); reg_fence(y3);
    if (tid == 320) TR(0, 18);
    {
      const float k1024 = __uint_as_float(lds32(cb + A_K1024));
      const uint32_t va = cb + A_V + wq * 512 + g * 32 + t * 4;
      const uint32_t y3a = cb + A_Y3 + wq * 1088 + g * 64 + (g >> 2) * 16 + t * 8, y2a = cb + A_Y2 + wq * 544 + g * 32 + t * 8;
#pragma unroll
      for (int i = 0; i < 2; i++)
#pragma unroll
        for (int hf = 0; hf < 2; hf++) {
          const uint32_t vv = lds32(va + hf * 256 + i * 16);
          sts64(y3a + hf * 544 + i * 32, __float_as_uint(fmaf(k1024, bf_lo(vv), y3[4 * i + 2 * hf])),
                __float_as_uint(fmaf(k1024, bf_hi(vv), y3[4 * i + 2 * hf + 1])));
        }
#pragma unroll
      for (int i = 0; i < 3; i++)
#pragma unroll
        for (int hf = 0; hf < 2; hf++)
          sts64(y2a + i * 2176 + hf * 272, __float_as_uint(y2[4 * i + 2 * hf]), __float_as_uint(y2[4 * i + 2 * hf + 1]));
    }
    wg_wait<1>(); load_quads<8>(qb, t1 + 16 * 64);
    wg_fence(); f1_steps<16, 8>(y1, qb, blo_k); wg_commit();
    if (tid == 127) { wd_store(); asm volatile("cp.async.bulk.commit_group;" ::: "memory"); }
    __syncwarp();
    wg_wait<1>(); load_quads<8>(qa, t1 + 24 * 64);
    wg_fence(); f1_steps<24, 8>(y1, qa, blo_k); wg_commit();
    wg_wait<1>(); load_quads<5>(qb, t1 + 32 * 64);
    wg_fence(); f1_steps<32, 5>(y1, qb, blo_k); wg_commit();
    bar_sync(1 + wg, 128);
    float ex[12];
#pragma unroll
    for (int i = 1; i < 4; i++)
#pragma unroll
      for (int k = 0; k < 4; k++) {
        const int aa = 8 * i + 2 * t + (k & 1), b = 16 * wq + g + 8 * (k >> 1);
        float e = __uint_as_float(lds32(cb + A_Y2 + ((aa - 8) * 68 + b) * 4));
        if (i >= 2) e += __uint_as_float(lds32(cb + A_Y3 + ((aa - 16) * 68 + b) * 4));
        ex[4 * (i - 1) + k] = e;
      }
    {
      const uint32_t dk = dk16 * 0x10001u;
      mbar_wait(bar_rec + 8, 0);
#pragma unroll
      for (int c = 0; c < 2; c++) {
        const uint32_t a = cb + A_REC + wq * 1024 + c * 512 + ((lane ^ ((lane >> 3) & 1)) << 4);
        const uint4 uu = lds128(a), xx = lds128(a + 4096);
        ud[4 * c] = hmul2_bf(uu.x, dk); ud[4 * c + 1] = hmul2_bf(uu.y, dk); ud[4 * c + 2] = hmul2_bf(uu.z, dk); ud[4 * c + 3] = hmul2_bf(uu.w, dk);
        xt[4 * c] = xx.x; xt[4 * c + 1] = xx.y; xt[4 * c + 2] = xx.z; xt[4 * c + 3] = xx.w;
      }
    }
    wg_wait<0>();
    reg_fence(y1);
    if (tid == 320) TR(0, 6);
#pragma unroll
    for (int i = 0; i < 12; i++) y1[4 + i] += ex[i];
#pragma unroll
    for (int i = 0; i < 2; i++) {
      const int mi = lane >> 3, aa = 8 * (2 * i + (mi >> 1)) + (lane & 7);
      asm volatile("stmatrix.sync.aligned.m8n8.x4.trans.shared.b16 [%0], {%1,%2,%3,%4};"
                   ::"r"(cb + A_YB + aa * 128 + (((2 * wq + (mi & 1)) ^ (lane & 7)) << 4)),
                     "r"(pack_bf16(y1[8 * i], y1[8 * i + 1])), "r"(pack_bf16(y1[8 * i + 2], y1[8 * i + 3])),
                     "r"(pack_bf16(y1[8 * i + 4], y1[8 * i + 5])), "r"(pack_bf16(y1[8 * i + 6], y1[8 * i + 7])) : "memory");
    }
  }
  bar_sync(1 + wg, 128);
#pragma unroll
  for (int c = 0; c < 2; c++) {
    const int tau = wq * 64 + c * 32 + lane, r = ch & 7;
    const uint4 y = lds128(cb + A_YB + (tau >> 3) * 128 + (((tau ^ (tau >> 3)) & 7) << 4));
    g_himg[(size_t)(tau >> 4) * 7168 + (ch >> 3) * 128 + ((tau >> 3) & 1) * 64 + r * 8 + ((tau & 7) ^ r)] =
        make_uint4(hadd2_bf(xt[4 * c], hadd2_bf(y.x, ud[4 * c])), hadd2_bf(xt[4 * c + 1], hadd2_bf(y.y, ud[4 * c + 1])),
                   hadd2_bf(xt[4 * c + 2], hadd2_bf(y.z, ud[4 * c + 2])), hadd2_bf(xt[4 * c + 3], hadd2_bf(y.w, ud[4 * c + 3])));
  }
  if (tid == 127) asm volatile("cp.async.bulk.wait_group 0;" ::: "memory");
  if (tid == 320) TR(0, 7);
}

constexpr int NUNI = 2;
constexpr int B_SA = 0, B_CS = 114688, B_RING = B_CS + 7168, B_SLOT = 15360, B_NSLOT = 7;
constexpr int B_RED = B_RING + B_NSLOT * B_SLOT;
constexpr int B_BAR = B_RED + 256;
constexpr int B_SMEM = B_BAR + 512, A_SMEM = A_WST + 28672;

__device__ __forceinline__ uint32_t mapa(uint32_t a, uint32_t r) { uint32_t o; asm("mapa.shared::cluster.u32 %0, %1, %2;" : "=r"(o) : "r"(a), "r"(r)); return o; }
template <int Q, int ST>
__device__ __forceinline__ void g1_stage(float (&acc)[116], uint32_t alo, uint32_t blo, uint32_t bar_full, uint32_t bar_h) {
  constexpr int s = Q * 14 + ST, sl = s % B_NSLOT;
  if (Q == 0) mbar_wait(bar_h + 8 * ST, 0);
  mbar_wait(bar_full + 8 * sl, (s / B_NSLOT) & 1);
  wg_fence();
  if (Q == 0) {
    wgmma_ss232<(2 * ST) * 256, 0x40000080u, (sl * B_SLOT) / 16, 0xC0000010u, ST != 0>(acc, alo, blo);
    wgmma_ss232<(2 * ST + 1) * 256, 0x40000080u, (sl * B_SLOT + 512) / 16, 0xC0000010u, 1>(acc, alo, blo);
  } else {
    wgmma_ss224<(2 * ST) * 256, 0x40000080u, (sl * B_SLOT) / 16, 0xC0000010u, ST != 0>(*(float(*)[112])acc, alo, blo);
    wgmma_ss224<(2 * ST + 1) * 256, 0x40000080u, (sl * B_SLOT + 512) / 16, 0xC0000010u, 1>(*(float(*)[112])acc, alo, blo);
  }
}

__global__ void __launch_bounds__(512, 1)
k_front(const __nv_bfloat16* __restrict__ x, const uint32_t* __restrict__ are, const uint32_t* __restrict__ aim,
        const uint32_t* __restrict__ bre, const uint32_t* __restrict__ bim, const uint32_t* __restrict__ cre,
        const uint32_t* __restrict__ cim, const unsigned short* __restrict__ logdt, const unsigned short* __restrict__ dskip,
        const uint4* __restrict__ wgate, const uint4* __restrict__ wup,
        const __grid_constant__ CUtensorMap mg, const __grid_constant__ CUtensorMap mu, const __grid_constant__ CUtensorMap md,
        const __grid_constant__ CUtensorMap mx, const __grid_constant__ CUtensorMap ml) {
  extern __shared__ __align__(1024) unsigned char sm[];
  const uint32_t bar_rec = s2u(sm) + A_BAR;
  if (threadIdx.x == 320) TR(0, 0);
  if ((blockIdx.x & 7) == 7) asm volatile("griddepcontrol.launch_dependents;");
  phase_a(sm, bar_rec, &mg, &mu, &md, &mx, &ml, x, are, aim, bre, bim, cre, cim, logdt, dskip, wgate, wup);
}

__global__ void __cluster_dims__(2, 1, 1) __launch_bounds__(384, 1) k_ffn(__nv_bfloat16* __restrict__ out) {
  extern __shared__ __align__(1024) unsigned char sm[];
  const uint32_t sb = s2u(sm);
  const int tid = threadIdx.x, warp = __shfl_sync(~0u, tid >> 5, 0), wg = warp >> 2, lane = tid & 31;
  const uint32_t bar_full = sb + B_BAR, bar_empty = bar_full + 64, bar_h = bar_full + 128, bar_cs = bar_full + 240,
                 bar_hh = bar_full + 304, bar_afree = bar_full + 336, bar_out = bar_full + 352;
  if (warp == 8) {
    if (lane == 0) {
#pragma unroll
      for (int i = 0; i < 31; i++) if (i != 7 && i != 15) mbar_init(bar_full + 8 * i, (i >> 3) == 1 ? 2 : 1);
      asm volatile("fence.mbarrier_init.release.cluster;" ::: "memory");
    }
    __syncwarp();
    asm volatile("bar.arrive 0, 384;" ::: "memory");
  } else {
    if (tid == 224) {
      TR(1, 0);
      for (int i = 0; i < 4; i++) { mbar_init(bar_hh + 8 * i, 1); mbar_expect(bar_hh + 8 * i, 14336); }
      mbar_init(bar_afree, 4); mbar_init(bar_afree + 8, 2);
      for (int i = 0; i < 6; i++) mbar_init(bar_out + 8 * i, 128);
      asm volatile("fence.mbarrier_init.release.cluster;" ::: "memory");
    } else if (tid < 224) {
      const uint32_t oa = sb + B_RING + (tid >> 5) * B_SLOT + 14336 + (tid & 31) * 32;
      sts128(oa, 0x3F803F80u, 0x3F803F80u, 0x3F803F80u, 0x3F803F80u);
      sts128(oa + 16, 0x3F803F80u, 0x3F803F80u, 0x3F803F80u, 0x3F803F80u);
      asm volatile("fence.proxy.async.shared::cta;" ::: "memory");
    }
    __syncwarp();
  }
  asm volatile("barrier.cluster.arrive.relaxed.aligned;" ::: "memory");
  const int rank = blockIdx.x & 1, rt = blockIdx.x >> 3, j = blockIdx.x & 7, p = j >> 1, cg = 4 * rank + p;
  const int wq = warp & 3, t128 = tid & 127, g = lane >> 2, t = lane & 3;
  uint32_t ep, tag;
  auto load_ep = [&]() { asm volatile("ld.relaxed.gpu.global.u32 %0, [%1];" : "=r"(ep) : "l"(&g_cnt1) : "memory"); };
  auto a_slot = [&](int i, int own) { return B_SA + (i + (i >= own)) * 14336; };
  auto out_addr = [&](int cc, int w) { return sb + a_slot((cc & 2) + w, cg) + (cc & 1) * 7168; };
  auto in_cta = [&](int q) { return rt * 8 + ((p + 3 - q) & 3) * 2 + rank; };
  auto in_src = [&](int q, int cw) { return g_part + (size_t)(in_cta(q) * 3 + q) * 896 + cw * 112; };
  auto in_bad = [&](uint32_t (&in)[14]) { return ((in[3] ^ tag) | (in[7] ^ tag) | (in[11] ^ tag) | (in[13] ^ tag)) & 0x10000u; };
  auto in_load = [&](uint32_t (&in)[14], const uint4* gs) {
#pragma unroll
    for (int i = 0; i < 3; i++) ld128(gs + i * 32, in + 4 * i);
    asm volatile("{\n.reg .b64 v;\nld.relaxed.gpu.global.b64 v, [%2];\nmov.b64 {%0, %1}, v;\n}"
                 : "=r"(in[12]), "=r"(in[13]) : "l"((const uint2*)(gs + 96) - lane) : "memory");
  };
  auto in_check = [&](uint32_t (&in)[14], int q, int cw) {
    int it = 0;
    while (in_bad(in) && ++it < 400000) in_load(in, pin(in_src(q, cw) + lane));
  };

  if (wg == 2) {
    asm volatile("setmaxnreg.dec.sync.aligned.u32 40;");
    if (warp != 8) { bar_sync(0, 384); asm volatile("barrier.cluster.wait.aligned;" ::: "memory"); }
    asm volatile("griddepcontrol.wait;" ::: "memory");
    if (warp == 8) {
      if (lane == 0) TR(1, 1);
      const char* wsrc = (const char*)g_wimg + (size_t)j * 602112;
      const char* hsrc = (const char*)g_himg + (size_t)rt * 114688 + rank * 4096;
#pragma unroll
      for (int s = 0; s < 28; s++) {
        if (s < NUNI) bulk_ld_elect<8192>(sb + B_SA + s * 8192, hsrc - rank * 4096 + s * 8192, bar_h + 8 * s);
        if (s == NUNI) asm volatile("barrier.cluster.wait.aligned;" ::: "memory");
        if (s >= NUNI && s < B_NSLOT) bulk_ld_mc_elect<4096>(sb + B_SA + s * 8192 + rank * 4096, hsrc + s * 8192, bar_h + 8 * s);
        if (s == B_NSLOT) {
#pragma unroll
          for (int i = 7; i < 14; i++) bulk_ld_mc_elect<4096>(sb + B_SA + i * 8192 + rank * 4096, hsrc + i * 8192, bar_h + 8 * i);
          bulk_ld_elect<7168>(sb + B_CS, g_cimg + j * 448, bar_cs);
        }
        if (s >= B_NSLOT) mbar_wait(bar_empty + 8 * (s % B_NSLOT), (s / B_NSLOT + 1) & 1);
        bulk_ld_elect<14336>(sb + B_RING + (s % B_NSLOT) * B_SLOT, wsrc + s * 14336, bar_full + 8 * (s % B_NSLOT));
      }
      const char* dsrc[2] = {wsrc + 401408 + rank * 100352, (const char*)g_wimg + (size_t)(j ^ 1) * 602112 + 401408 + rank * 100352};
#pragma unroll
      for (int i = 0; i < 16; i++) {
        const int ci = i < 3 ? 0 : i < 6 ? 1 : i < 8 ? i - 6 : i < 12 ? 2 : 3;
        const int kp = i < 3 ? i : i < 6 ? i - 3 : i < 8 ? 3 : (i & 3);
        mbar_wait(bar_empty + 8 * (i % B_NSLOT), (i / B_NSLOT + 1) & 1);
        bulk_ld_elect<12544>(sb + B_RING + (i % B_NSLOT) * B_SLOT, dsrc[kp >> 1] + ((p + 1 + ci) & 3) * 25088 + (kp & 1) * 12544, bar_full + 8 * (i % B_NSLOT));
      }
    } else if (warp >= 10) {
      const int t64 = tid - 320;
      load_ep();
      const int r = (lane >> 1) & 7, c = (j & 3) * 2 + (lane & 1);
      const uint32_t src = sb + B_SA + (t64 >> 4) * 2048 + (j >> 2) * 1024 + r * 128 + ((c ^ r) << 4);
      float a[16];
#pragma unroll
      for (int k = 0; k < 16; k++) a[k] = 0.f;
#pragma unroll 1
      for (int i = 0; i < 14; i++) {
        mbar_wait(bar_h + 8 * i, 0);
        uint4 v = lds128(src + i * 8192);
        float e[8] = {bf_lo(v.x), bf_hi(v.x), bf_lo(v.y), bf_hi(v.y), bf_lo(v.z), bf_hi(v.z), bf_lo(v.w), bf_hi(v.w)};
#pragma unroll
        for (int k = 0; k < 8; k++) { a[2 * k] += e[k]; a[2 * k + 1] = fmaf(e[k], e[k], a[2 * k + 1]); }

      }
      __syncwarp();
      if (lane == 0) { asm volatile("mbarrier.arrive.shared::cluster.b64 _, [%0];" ::"r"(mapa(bar_afree, rank ^ 1)) : "memory"); }
#pragma unroll
      for (int rd = 0; rd < 4; rd++) {
        const int n = 8 >> rd;
        const bool up = lane & (2 * n);
#pragma unroll
        for (int k = 0; k < 8; k++) {
          if (k < n) {
            float keep = up ? a[k + n] : a[k], give = up ? a[k] : a[k + n];
            a[k] = keep + __shfl_xor_sync(~0u, give, 2 * n);
          }
        }
      }
      float* red = (float*)(sm + B_RED);
      red[(warp & 1) * 32 + (lane & 1) * 16 + (lane >> 1)] = a[0];
      bar_sync(1, 64);
      if (t64 < 16) {
        float mean = (red[2 * t64] + red[32 + 2 * t64]) * (1.f / DM);
        float var = fmaxf(fmaf(-mean, mean, (red[2 * t64 + 1] + red[33 + 2 * t64]) * (1.f / DM)), 0.f);
        float rs = ln_rstd(var);
        asm volatile("st.relaxed.gpu.global.u32 [%0], %1;"
                     ::"l"(g_stat2 + rt * 128 + j * 16 + t64), "r"((__float_as_uint(rs * rs) & ~1u) | ((ep >> 7) & 1u)) : "memory");
      }
      if (t64 == 0) TR(1, 2);
      if (lane == 0) {
        const int w = warp & 1;
        for (int cc = 0; cc < 2; cc++) {
          mbar_wait(bar_out + 8 * (cc * 2 + w), 0);
          asm volatile("cp.async.bulk.global.shared::cta.bulk_group [%0], [%1], 7168;"
                       ::"l"(g_part + (size_t)(blockIdx.x * 3 + cc) * 896 + w * 448), "r"(out_addr(cc, w)) : "memory");
          if (w) TR(1, 27 + cc);
        }
        asm volatile("cp.async.bulk.commit_group;" ::: "memory");
        asm volatile("cp.async.bulk.wait_group 0;" ::: "memory");
      }
    }
  } else {
    asm volatile("setmaxnreg.inc.sync.aligned.u32 232;");
    bar_sync(0, 384);
    asm volatile("barrier.cluster.wait.aligned;" ::: "memory");
    uint32_t hh[56];
    const bool relt = t128 == 0;
    auto release = [&](int sl) { if (relt) mbar_arrive(bar_empty + 8 * sl); };
    auto send_hh = [&](int q) {
      const uint32_t da = mapa(sb + a_slot(2 * q + wg, cg ^ 4) + t128 * 16, rank ^ 1), db = mapa(bar_hh + 8 * (2 * q + wg), rank ^ 1);
#pragma unroll
      for (int i = 0; i < 7; i++)
        asm volatile("st.async.weak.shared::cluster.mbarrier::complete_tx::bytes.v4.b32 [%0], {%1, %2, %3, %4}, [%5];"
                     ::"r"(da + i * 2048), "r"(hh[28 * q + 4 * i]), "r"(hh[28 * q + 4 * i + 1]),
                       "r"(hh[28 * q + 4 * i + 2]), "r"(hh[28 * q + 4 * i + 3]), "r"(db) : "memory");
    };
    uint32_t alo = ((sb + B_SA + wg * 1024) & 0x3FFFF) >> 4;
    uint32_t blo = (((sb + B_RING) & 0x3FFFF) >> 4) | (64u << 16);
    const uint32_t clo = ((sb + B_CS) & 0x3FFFF) >> 4;
    uint32_t nm0, nm1;
    if (wg == 1) bar_sync(3, 256);
#define G1S(Q, ST) do { if (ST % 7 == 0) { alo = pin(alo); blo = pin(blo); }   \
      g1_stage<Q, ST>(acc, alo, blo, bar_full, bar_h); wg_commit(); \
      if (ST > 0) { wg_wait<1>(); release((Q * 14 + ST - 1) % B_NSLOT); } } while (0)
#define G1HH(Q) do { \
      _Pragma("unroll") \
      for (int i = 0; i < 28; i++) hh[28 * Q + i] = pack_bf16(acc[2 * i] * acc[56 + 2 * i], acc[2 * i + 1] * acc[57 + 2 * i]); \
    } while (0)
    {
      float acc[116];
      G1S(0, 0);
      if (tid == 0) TR(1, 3);
      G1S(0, 1);
      if (wg == 0) asm volatile("bar.arrive 3, 256;" ::: "memory");
      G1S(0, 2); G1S(0, 3); G1S(0, 4); G1S(0, 5); G1S(0, 6); G1S(0, 7); G1S(0, 8); G1S(0, 9); G1S(0, 10); G1S(0, 11); G1S(0, 12);
      G1S(0, 13);
      if (tid == 0) TR(1, 4);
      mbar_wait(bar_cs, 0);
      wg_wait<0>(); reg_fence(acc); release(13 % B_NSLOT);
      {
        const uint32_t msk = t == 0 ? 0xFFFFFFFFu : t == 1 ? 0xFFFFu : 0u;
        const float a = acc[112] * (-1.f / DM), b = acc[114] * (-1.f / DM);
        nm0 = pack_bf16(a, a) & msk; nm1 = pack_bf16(b, b) & msk;
      }
      wg_fence();
      wgmma_rs224<0, 8, 1>(*(float(*)[112])acc, nm0, nm1, 0u, 0u, clo);
      wg_commit(); wg_wait<0>(); reg_fence(acc);
      G1HH(0);
      if (tid == 0) TR(1, 5);
      G1S(1, 0); G1S(1, 1); G1S(1, 2); G1S(1, 3); G1S(1, 4); G1S(1, 5); G1S(1, 6);
      if (relt) asm volatile("mbarrier.arrive.shared::cluster.b64 _, [%0];" ::"r"(mapa(bar_afree, rank ^ 1)) : "memory");
      G1S(1, 7); G1S(1, 8); G1S(1, 9);
      if (relt) asm volatile("mbarrier.arrive.shared::cluster.b64 _, [%0];" ::"r"(mapa(bar_afree + 8, rank ^ 1)) : "memory");
      mbar_wait(bar_afree, 0);
      send_hh(0);
      G1S(1, 10); G1S(1, 11); G1S(1, 12);
      load_ep();
      g1_stage<1, 13>(acc, alo, blo, bar_full, bar_h);
      wgmma_rs224<224, 8, 1>(*(float(*)[112])acc, nm0, nm1, 0u, 0u, clo);
      wg_commit(); wg_wait<1>(); release(26 % B_NSLOT);
      wg_wait<0>(); reg_fence(acc); release(27 % B_NSLOT);
      G1HH(1);
      if (tid == 0) TR(1, 6);
    }
    float accA[28], accB[28];
    uint32_t ph0[28], ph1[28];
    ep = pin(ep >> 7); tag = pin((ep & 1u) << 16);
    blo -= 56u << 16;
#define ISSUE(acc, I, a, FIRST) do { \
      constexpr int s_ = 28 + (I), sl_ = s_ % B_NSLOT; \
      if (sl_ == 0) blo = pin(blo); \
      mbar_wait(bar_full + 8 * sl_, (s_ / B_NSLOT) & 1); \
      wg_fence(); \
      wgmma_rs56<(sl_ * B_SLOT + 0 * 256) / 16, 112, !(FIRST)>(acc, (a)[0], (a)[1], (a)[2], (a)[3], blo); \
      wgmma_rs56<(sl_ * B_SLOT + 1 * 256) / 16, 112, 1>(acc, (a)[4], (a)[5], (a)[6], (a)[7], blo); \
      wgmma_rs56<(sl_ * B_SLOT + 2 * 256) / 16, 112, 1>(acc, (a)[8], (a)[9], (a)[10], (a)[11], blo); \
      wgmma_rs56<(sl_ * B_SLOT + 3 * 256) / 16, 112, 1>(acc, (a)[12], (a)[13], (a)[14], (a)[15], blo); \
      wgmma_rs56<(sl_ * B_SLOT + 4 * 256) / 16, 112, 1>(acc, (a)[16], (a)[17], (a)[18], (a)[19], blo); \
      wgmma_rs56<(sl_ * B_SLOT + 5 * 256) / 16, 112, 1>(acc, (a)[20], (a)[21], (a)[22], (a)[23], blo); \
      wgmma_rs56<(sl_ * B_SLOT + 6 * 256) / 16, 112, 1>(acc, (a)[24], (a)[25], (a)[26], (a)[27], blo); \
      wg_commit(); } while (0)
    auto rel = [&](int i) { release((28 + i) % B_NSLOT); };
    auto tg = [&](uint32_t v) { return (v & 0xFFFEFFFFu) | tag; };
    auto send = [&](float (&acc)[28], int cc) {
      reg_fence(acc);
      const uint32_t a = out_addr(cc, wg) + wq * 1792;
#pragma unroll
      for (int q = 0; q < 3; q++)
        sts128(a + q * 512 + lane * 16, pack_bf16(acc[8 * q], acc[8 * q + 1]), pack_bf16(acc[8 * q + 2], acc[8 * q + 3]),
               pack_bf16(acc[8 * q + 4], acc[8 * q + 5]), tg(pack_bf16(acc[8 * q + 6], acc[8 * q + 7])));
      sts64(a + 1536 + lane * 8, pack_bf16(acc[24], acc[25]), tg(pack_bf16(acc[26], acc[27])));
      asm volatile("fence.proxy.async.shared::cta;" ::: "memory");
      mbar_arrive(bar_out + 8 * (cc * 2 + wg));
    };
    auto load_hh = [&](uint32_t (&d)[28], int q) {
      mbar_wait(bar_hh + 8 * (2 * q + wg), 0);
      const uint32_t a = sb + a_slot(2 * q + wg, cg) + t128 * 16;
#pragma unroll
      for (int i = 0; i < 7; i++) {
        const uint4 v = lds128(a + i * 2048);
        d[4 * i] = v.x; d[4 * i + 1] = v.y; d[4 * i + 2] = v.z; d[4 * i + 3] = v.w;
      }
    };
    ISSUE(accA, 0, hh, true);
    mbar_wait(bar_afree + 8, 0);
    send_hh(1);
    ISSUE(accA, 1, hh + 28, false);
    load_hh(ph0, 0);
    wg_wait<1>(); rel(0);
    ISSUE(accA, 2, ph0, false);      wg_wait<1>(); rel(1);
    ISSUE(accB, 3, hh, true);        wg_wait<1>(); rel(2);
    ISSUE(accB, 4, hh + 28, false);  wg_wait<1>(); rel(3);
    ISSUE(accB, 5, ph0, false);
    if (tid == 0) TR(1, 11);
    load_hh(ph1, 1);
    wg_wait<1>(); rel(4);
    ISSUE(accA, 6, ph1, false);      wg_wait<1>(); rel(5);
    ISSUE(accB, 7, ph1, false);      wg_wait<1>(); rel(6); send(accA, 0);
    ISSUE(accA, 8, hh, true);        wg_wait<1>(); rel(7); send(accB, 1);
    if (tid == 0) TR(1, 13);
    ISSUE(accA, 9, hh + 28, false);  wg_wait<1>(); rel(8);
    ISSUE(accA, 10, ph0, false);
    ISSUE(accA, 11, ph1, false);
    const int row = rt * 128 + wg * 64 + wq * 16 + g;
    uint32_t r20, r21;
    asm volatile("ld.relaxed.gpu.global.u32 %0, [%1];" : "=r"(r20) : "l"(g_stat2 + row) : "memory");
    asm volatile("ld.relaxed.gpu.global.u32 %0, [%1];" : "=r"(r21) : "l"(g_stat2 + row + 8) : "memory");
    ISSUE(accB, 12, hh, true);
    wg_wait<1>();
    {
      reg_fence(accA);
      uint4* pd = g_part + (size_t)(blockIdx.x * 3 + 2) * 896 + warp * 112 + lane;
#pragma unroll
      for (int q = 0; q < 3; q++)
        st128(pd + q * 32, pack_bf16(accA[8 * q], accA[8 * q + 1]), pack_bf16(accA[8 * q + 2], accA[8 * q + 3]),
              pack_bf16(accA[8 * q + 4], accA[8 * q + 5]), tg(pack_bf16(accA[8 * q + 6], accA[8 * q + 7])));
      asm volatile("{\n.reg .b64 v;\nmov.b64 v, {%1, %2};\nst.relaxed.gpu.global.b64 [%0], v;\n}"
                   ::"l"((uint2*)(pd + 96) - lane), "r"(pack_bf16(accA[24], accA[25])), "r"(tg(pack_bf16(accA[26], accA[27]))) : "memory");
    }
    if (tid == 0) TR(1, 16);
    ISSUE(accB, 13, hh + 28, false);
    uint32_t in0[14], in1[14], in2[14];
    in_load(in0, in_src(0, warp) + lane);
    in_load(in1, in_src(1, warp) + lane);
    ISSUE(accB, 14, ph0, false);
    ISSUE(accB, 15, ph1, false);
    if (tid == 0) TR(1, 7);
    {
      int it = 0;
      while ((((r20 ^ ep) | (r21 ^ ep)) & 1u) && ++it < 400000) {
        asm volatile("ld.relaxed.gpu.global.u32 %0, [%1];" : "=r"(r20) : "l"(g_stat2 + row) : "memory");
        asm volatile("ld.relaxed.gpu.global.u32 %0, [%1];" : "=r"(r21) : "l"(g_stat2 + row + 8) : "memory");
      }
    }
    in_check(in0, 0, warp); in_check(in1, 1, warp);
#pragma unroll
    for (int i = 0; i < 14; i++) { accA[2 * i] = bf_lo(in0[i]) + bf_lo(in1[i]); accA[2 * i + 1] = bf_hi(in0[i]) + bf_hi(in1[i]); }
    if (tid == 0) TR(1, 12);
    in_load(in2, in_src(2, warp) + lane);
    wg_wait<0>();
    reg_fence(accB);
    uint32_t hres[16];
#pragma unroll
    for (int i = 0; i < 4; i++) {
      int qq = lane >> 3, r = lane & 7, kg = 7 * cg + 2 * i + (qq >> 1), c = 2 * wq + (qq & 1);
      if (kg > 55) kg = 55;
      asm volatile("ldmatrix.sync.aligned.m8n8.x4.trans.shared.b16 {%0,%1,%2,%3}, [%4];"
                   : "=r"(hres[4 * i]), "=r"(hres[4 * i + 1]), "=r"(hres[4 * i + 2]), "=r"(hres[4 * i + 3])
                   : "r"(sb + B_SA + kg * 2048 + wg * 1024 + r * 128 + ((c ^ r) << 4)) : "memory");
    }
#pragma unroll
    for (int i = 0; i < 28; i++) accB[i] += accA[i];
    if (tid == 0) TR(1, 9);
    in_check(in2, 2, warp);
#pragma unroll
    for (int i = 0; i < 14; i++) { accB[2 * i] += bf_lo(in2[i]); accB[2 * i + 1] += bf_hi(in2[i]); }
    {
      uint32_t o[16];
#pragma unroll
      for (int i = 0; i < 7; i++) {
        o[2 * i] = hadd2_bf(hres[2 * i], pack_bf16(accB[4 * i] * __uint_as_float(r20), accB[4 * i + 1] * __uint_as_float(r20)));
        o[2 * i + 1] = hadd2_bf(hres[2 * i + 1], pack_bf16(accB[4 * i + 2] * __uint_as_float(r21), accB[4 * i + 3] * __uint_as_float(r21)));
      }
      o[14] = 0; o[15] = 0;
      const uint32_t ob = sb + a_slot(4 + wg, cg) + wq * 2304;
#pragma unroll
      for (int i = 0; i < 4; i++)
        asm volatile("stmatrix.sync.aligned.m8n8.x4.shared.b16 [%0], {%1,%2,%3,%4};"
                     ::"r"(ob + (lane & 15) * 144 + (2 * i + (lane >> 4)) * 16), "r"(o[4 * i]), "r"(o[4 * i + 1]), "r"(o[4 * i + 2]), "r"(o[4 * i + 3]) : "memory");
      __syncwarp();
      uint4* op = (uint4*)(out + (size_t)(rt * 128 + wg * 64 + wq * 16) * DM + 56 * cg);
#pragma unroll
      for (int i = 0; i < 4; i++) {
        if ((lane & 7) < 7) {
          const int r = 4 * i + (lane >> 3);
          op[r * 56 + (lane & 7)] = lds128(ob + r * 144 + (lane & 7) * 16);
        }
      }
    }
    if (tid == 0) TR(1, 10);
    if (tid == 128) TR(1, 15);
  }
}

typedef CUresult (*EncFn)(CUtensorMap*, CUtensorMapDataType, cuuint32_t, void*, const cuuint64_t*, const cuuint64_t*,
                          const cuuint32_t*, const cuuint32_t*, CUtensorMapInterleave, CUtensorMapSwizzle,
                          CUtensorMapL2promotion, CUtensorMapFloatOOBfill);

extern "C" void kernel_launch(void* const* d_in, const int* in_sizes, int n_in, void* d_out, int out_size) {
  const __nv_bfloat16* x = (const __nv_bfloat16*)d_in[0];
  const __nv_bfloat16 *are = (const __nv_bfloat16*)d_in[1], *aim = (const __nv_bfloat16*)d_in[2], *bre = (const __nv_bfloat16*)d_in[3],
                      *bim = (const __nv_bfloat16*)d_in[4], *cre = (const __nv_bfloat16*)d_in[5], *cim = (const __nv_bfloat16*)d_in[6],
                      *logdt = (const __nv_bfloat16*)d_in[7], *dskip = (const __nv_bfloat16*)d_in[8];
  const __nv_bfloat16 *wg = (const __nv_bfloat16*)d_in[10], *wu = (const __nv_bfloat16*)d_in[11], *wd = (const __nv_bfloat16*)d_in[12];

  static EncFn enc = nullptr;
  if (!enc) {
    void* fn = nullptr; cudaDriverEntryPointQueryResult qr;
    cudaGetDriverEntryPoint("cuTensorMapEncodeTiled", &fn, cudaEnableDefault, &qr);
    enc = (EncFn)fn;
    cudaFuncSetAttribute(k_ffn, cudaFuncAttributeMaxDynamicSharedMemorySize, B_SMEM);
    cudaFuncSetAttribute(k_front, cudaFuncAttributeMaxDynamicSharedMemorySize, A_SMEM);
  }
  CUtensorMap mg, mu, md, mx, ml;
  {
    cuuint32_t es[3] = {1, 1, 1};
    cuuint64_t d1[3] = {16, 448, 112}, s1[2] = {3584, 32}; cuuint32_t b1[3] = {16, 32, 7};
    cuuint64_t d2[3] = {8, 1792, 56}, s2[2] = {896, 16}; cuuint32_t b2[3] = {8, 112, 7};
    enc(&mg, CU_TENSOR_MAP_DATA_TYPE_BFLOAT16, 3, (void*)wg, d1, s1, b1, es, CU_TENSOR_MAP_INTERLEAVE_NONE, CU_TENSOR_MAP_SWIZZLE_32B, CU_TENSOR_MAP_L2_PROMOTION_L2_256B, CU_TENSOR_MAP_FLOAT_OOB_FILL_NONE);
    enc(&mu, CU_TENSOR_MAP_DATA_TYPE_BFLOAT16, 3, (void*)wu, d1, s1, b1, es, CU_TENSOR_MAP_INTERLEAVE_NONE, CU_TENSOR_MAP_SWIZZLE_32B, CU_TENSOR_MAP_L2_PROMOTION_L2_256B, CU_TENSOR_MAP_FLOAT_OOB_FILL_NONE);
    void* ux = nullptr; cudaGetSymbolAddress(&ux, g_ux);
    cuuint64_t d3[3] = {32, 128, 448}, s3[2] = {64, 8192}; cuuint32_t b3[3] = {32, 1, 224};
    enc(&mx, CU_TENSOR_MAP_DATA_TYPE_BFLOAT16, 3, ux, d3, s3, b3, es, CU_TENSOR_MAP_INTERLEAVE_NONE, CU_TENSOR_MAP_SWIZZLE_64B, CU_TENSOR_MAP_L2_PROMOTION_NONE, CU_TENSOR_MAP_FLOAT_OOB_FILL_NONE);
    cuuint32_t b4[3] = {16, 128, 1};
    enc(&ml, CU_TENSOR_MAP_DATA_TYPE_BFLOAT16, 3, ux, d3, s3, b4, es, CU_TENSOR_MAP_INTERLEAVE_NONE, CU_TENSOR_MAP_SWIZZLE_32B, CU_TENSOR_MAP_L2_PROMOTION_NONE, CU_TENSOR_MAP_FLOAT_OOB_FILL_NONE);
    enc(&md, CU_TENSOR_MAP_DATA_TYPE_BFLOAT16, 3, (void*)wd, d2, s2, b2, es, CU_TENSOR_MAP_INTERLEAVE_NONE, CU_TENSOR_MAP_SWIZZLE_NONE, CU_TENSOR_MAP_L2_PROMOTION_L2_256B, CU_TENSOR_MAP_FLOAT_OOB_FILL_NONE);
  }
  cudaStream_t st = cudaStreamPerThread;
  k_front<<<128, 512, A_SMEM, st>>>(
      x, (const uint32_t*)are, (const uint32_t*)aim, (const uint32_t*)bre, (const uint32_t*)bim, (const uint32_t*)cre, (const uint32_t*)cim,
      (const unsigned short*)logdt, (const unsigned short*)dskip, (const uint4*)wg, (const uint4*)wu, mg, mu, md, mx, ml);
  cudaLaunchConfig_t cfg = {};
  cfg.gridDim = dim3(128); cfg.blockDim = dim3(384); cfg.dynamicSmemBytes = B_SMEM; cfg.stream = st;
  cudaLaunchAttribute at[1];
  at[0].id = cudaLaunchAttributeProgrammaticStreamSerialization; at[0].val.programmaticStreamSerializationAllowed = 1;
  cfg.attrs = at; cfg.numAttrs = 1;
  cudaLaunchKernelEx(&cfg, k_ffn, (__nv_bfloat16*)d_out);
}
```
